```python
import torch

def _softmax(x, axis=-1):
    return torch.softmax(x, dim=axis)
def _gelu(x):
    return torch.nn.functional.gelu(x, approximate="tanh")
def _silu(x):
    return torch.nn.functional.silu(x)
def _sigmoid(x):
    return torch.sigmoid(x)
def _layernorm(x, axis=-1, eps=1e-5):
    m = x.mean(dim=axis, keepdim=True)
    v = x.var(dim=axis, keepdim=True, unbiased=False)
    return (x - m) / torch.sqrt(v + eps)
def _scatter_add(tgt, idx, src, axis=0):
    return tgt.clone().index_add_(axis, idx, src)
def _segment_sum(src, seg, n):
    out = torch.zeros((n,) + src.shape[1:], dtype=src.dtype)
    return out.index_add_(0, seg, src)
def _pad(x, pw):
    flat = tuple(v for pair in reversed(pw) for v in pair)
    return torch.nn.functional.pad(x, flat)

kernel_name = 'standalone__fft_conv__vision'

def setup_inputs():

    _w = (lambda a: (lambda t: t.to(torch.bfloat16) if t.is_floating_point() else t)(torch.as_tensor(a)))
    H = W = 224
    C = 96
    K = 7
    return {
        "x": _w((lambda *s: torch.randn(*s, dtype=torch.bfloat16) * 0.05)(1, H, W, C)),
        "w": _w((lambda *s: torch.randn(*s, dtype=torch.bfloat16) * 0.05)(K, K, C, C)),
    }

def reference(x, w):
    B, H, W, C = x.shape
    K = w.shape[0]
    wp = _pad(w, ((0, H - K), (0, W - K), (0, 0), (0, 0)))
    Xf = (lambda x, axes=(-2,-1): torch.fft.rfft2(x.float(), dim=axes))(x, axes=(1, 2))
    Wf = (lambda x, axes=(-2,-1): torch.fft.rfft2(x.float(), dim=axes))(wp, axes=(0, 1))
    Yf = torch.einsum('bhwi,hwio->bhwo', Xf, Wf)
    y = (lambda x, s, axes=(-2,-1): torch.fft.irfft2(x, s=s, dim=axes).to(torch.bfloat16))(Yf, (H, W), axes=(1, 2))
    return y
```

```cpp
#include <cuda_runtime.h>
#include <cuda_bf16.h>
#include <cuda.h>
#include <stdint.h>

__device__ __align__(128) const uint32_t TAB_P1[4160] = {
0x3f75,0,0x3f72,0,0x8000,0,0xbe19,0,0x3f750000,0,0x3f720000,0,0x80000000,0,0xbe190000,0,
0,0x3f75,0,0x3f72,0,0x8000,0,0xbe19,0,0x3f750000,0,0x3f720000,0,0x80000000,0,0xbe190000,
0x3f69,0,0x3f5a,0,0xbe97,0,0xbede,0,0x3f690000,0,0x3f5a0000,0,0xbe970000,0,0xbede0000,0,
0,0x3f69,0,0x3f5a,0,0xbe97,0,0xbede,0,0x3f690000,0,0x3f5a0000,0,0xbe970000,0,0xbede0000,
0x3f75,0,0x3f5a,0,0x8000,0,0xbede,0,0x3f750000,0,0x3f5a0000,0,0x80000000,0,0xbede0000,0,
0,0x3f75,0,0x3f5a,0,0x8000,0,0xbede,0,0x3f750000,0,0x3f5a0000,0,0x80000000,0,0xbede0000,
0x3f10,0,0x3e19,0,0xbf46,0,0xbf72,0,0x3f100000,0,0x3e190000,0,0xbf460000,0,0xbf720000,0,
0,0x3f10,0,0x3e19,0,0xbf46,0,0xbf72,0,0x3f100000,0,0x3e190000,0,0xbf460000,0,0xbf720000,
0x3f75,0,0x3f2d,0,0x8000,0,0xbf2d,0,0x3f750000,0,0x3f2d0000,0,0x80000000,0,0xbf2d0000,0,
0,0x3f75,0,0x3f2d,0,0x8000,0,0xbf2d,0,0x3f750000,0,0x3f2d0000,0,0x80000000,0,0xbf2d0000,
0,0,0xbf2d,0,0xbf75,0,0xbf2d,0,0,0,0xbf2d0000,0,0xbf750000,0,0xbf2d0000,0,
0,0,0,0xbf2d,0,0xbf75,0,0xbf2d,0,0,0,0xbf2d0000,0,0xbf750000,0,0xbf2d0000,
0x3f75,0,0x3ede,0,0x8000,0,0xbf5a,0,0x3f750000,0,0x3ede0000,0,0x80000000,0,0xbf5a0000,0,
0,0x3f75,0,0x3ede,0,0x8000,0,0xbf5a,0,0x3f750000,0,0x3ede0000,0,0x80000000,0,0xbf5a0000,
0xbf10,0,0xbf72,0,0xbf46,0,0x3e19,0,0xbf100000,0,0xbf720000,0,0xbf460000,0,0x3e190000,0,
0,0xbf10,0,0xbf72,0,0xbf46,0,0x3e19,0,0xbf100000,0,0xbf720000,0,0xbf460000,0,0x3e190000,
0x3f75,0,0x3e19,0,0x8000,0,0xbf72,0,0x3f750000,0,0x3e190000,0,0x80000000,0,0xbf720000,0,
0,0x3f75,0,0x3e19,0,0x8000,0,0xbf72,0,0x3f750000,0,0x3e190000,0,0x80000000,0,0xbf720000,
0xbf69,0,0xbede,0,0xbe97,0,0x3f5a,0,0xbf690000,0,0xbede0000,0,0xbe970000,0,0x3f5a0000,0,
0,0xbf69,0,0xbede,0,0xbe97,0,0x3f5a,0,0xbf690000,0,0xbede0000,0,0xbe970000,0,0x3f5a0000,
0x3f75,0,0xbe19,0,0x8000,0,0xbf72,0,0x3f750000,0,0xbe190000,0,0x80000000,0,0xbf720000,0,
0,0x3f75,0,0xbe19,0,0x8000,0,0xbf72,0,0x3f750000,0,0xbe190000,0,0x80000000,0,0xbf720000,
0xbf69,0,0x3ede,0,0x3e97,0,0x3f5a,0,0xbf690000,0,0x3ede0000,0,0x3e970000,0,0x3f5a0000,0,
0,0xbf69,0,0x3ede,0,0x3e97,0,0x3f5a,0,0xbf690000,0,0x3ede0000,0,0x3e970000,0,0x3f5a0000,
0x3f75,0,0xbede,0,0x8000,0,0xbf5a,0,0x3f750000,0,0xbede0000,0,0x80000000,0,0xbf5a0000,0,
0,0x3f75,0,0xbede,0,0x8000,0,0xbf5a,0,0x3f750000,0,0xbede0000,0,0x80000000,0,0xbf5a0000,
0xbf10,0,0x3f72,0,0x3f46,0,0x3e19,0,0xbf100000,0,0x3f720000,0,0x3f460000,0,0x3e190000,0,
0,0xbf10,0,0x3f72,0,0x3f46,0,0x3e19,0,0xbf100000,0,0x3f720000,0,0x3f460000,0,0x3e190000,
0x3f75,0,0xbf2d,0,0x8000,0,0xbf2d,0,0x3f750000,0,0xbf2d0000,0,0x80000000,0,0xbf2d0000,0,
0,0x3f75,0,0xbf2d,0,0x8000,0,0xbf2d,0,0x3f750000,0,0xbf2d0000,0,0x80000000,0,0xbf2d0000,
0,0,0x3f2d,0,0x3f75,0,0xbf2d,0,0,0,0x3f2d0000,0,0x3f750000,0,0xbf2d0000,0,
0,0,0,0x3f2d,0,0x3f75,0,0xbf2d,0,0,0,0x3f2d0000,0,0x3f750000,0,0xbf2d0000,
0x3f75,0,0xbf5a,0,0x8000,0,0xbede,0,0x3f750000,0,0xbf5a0000,0,0x80000000,0,0xbede0000,0,
0,0x3f75,0,0xbf5a,0,0x8000,0,0xbede,0,0x3f750000,0,0xbf5a0000,0,0x80000000,0,0xbede0000,
0x3f10,0,0xbe19,0,0x3f46,0,0xbf72,0,0x3f100000,0,0xbe190000,0,0x3f460000,0,0xbf720000,0,
0,0x3f10,0,0xbe19,0,0x3f46,0,0xbf72,0,0x3f100000,0,0xbe190000,0,0x3f460000,0,0xbf720000,
0x3f75,0,0xbf72,0,0x8000,0,0xbe19,0,0x3f750000,0,0xbf720000,0,0x80000000,0,0xbe190000,0,
0,0x3f75,0,0xbf72,0,0x8000,0,0xbe19,0,0x3f750000,0,0xbf720000,0,0x80000000,0,0xbe190000,
0x3f69,0,0xbf5a,0,0x3e97,0,0xbede,0,0x3f690000,0,0xbf5a0000,0,0x3e970000,0,0xbede0000,0,
0,0x3f69,0,0xbf5a,0,0x3e97,0,0xbede,0,0x3f690000,0,0xbf5a0000,0,0x3e970000,0,0xbede0000,
0x3f46,0,0x3f2d,0,0xbf10,0,0xbf2d,0,0x3f460000,0,0x3f2d0000,0,0xbf100000,0,0xbf2d0000,0,
0,0x3f46,0,0x3f2d,0,0xbf10,0,0xbf2d,0,0x3f460000,0,0x3f2d0000,0,0xbf100000,0,0xbf2d0000,
0x3f10,0,0x3ede,0,0xbf46,0,0xbf5a,0,0x3f100000,0,0x3ede0000,0,0xbf460000,0,0xbf5a0000,0,
0,0x3f10,0,0x3ede,0,0xbf46,0,0xbf5a,0,0x3f100000,0,0x3ede0000,0,0xbf460000,0,0xbf5a0000,
0xbe97,0,0xbf2d,0,0xbf69,0,0xbf2d,0,0xbe970000,0,0xbf2d0000,0,0xbf690000,0,0xbf2d0000,0,
0,0xbe97,0,0xbf2d,0,0xbf69,0,0xbf2d,0,0xbe970000,0,0xbf2d0000,0,0xbf690000,0,0xbf2d0000,
0xbf69,0,0xbf72,0,0xbe97,0,0x3e19,0,0xbf690000,0,0xbf720000,0,0xbe970000,0,0x3e190000,0,
0,0xbf69,0,0xbf72,0,0xbe97,0,0x3e19,0,0xbf690000,0,0xbf720000,0,0xbe970000,0,0x3e190000,
0xbf75,0,0xbf2d,0,0x8000,0,0x3f2d,0,0xbf750000,0,0xbf2d0000,0,0x80000000,0,0x3f2d0000,0,
0,0xbf75,0,0xbf2d,0,0x8000,0,0x3f2d,0,0xbf750000,0,0xbf2d0000,0,0x80000000,0,0x3f2d0000,
0,0,0x3f2d,0,0x3f75,0,0x3f2d,0,0,0,0x3f2d0000,0,0x3f750000,0,0x3f2d0000,0,
0,0,0,0x3f2d,0,0x3f75,0,0x3f2d,0,0,0,0x3f2d0000,0,0x3f750000,0,0x3f2d0000,
0xbe97,0,0x3f2d,0,0x3f69,0,0x3f2d,0,0xbe970000,0,0x3f2d0000,0,0x3f690000,0,0x3f2d0000,0,
0,0xbe97,0,0x3f2d,0,0x3f69,0,0x3f2d,0,0xbe970000,0,0x3f2d0000,0,0x3f690000,0,0x3f2d0000,
0x3f69,0,0x3e19,0,0xbe97,0,0xbf72,0,0x3f690000,0,0x3e190000,0,0xbe970000,0,0xbf720000,0,
0,0x3f69,0,0x3e19,0,0xbe97,0,0xbf72,0,0x3f690000,0,0x3e190000,0,0xbe970000,0,0xbf720000,
0x3f46,0,0x3f2d,0,0x3f10,0,0xbf2d,0,0x3f460000,0,0x3f2d0000,0,0x3f100000,0,0xbf2d0000,0,
0,0x3f46,0,0x3f2d,0,0x3f10,0,0xbf2d,0,0x3f460000,0,0x3f2d0000,0,0x3f100000,0,0xbf2d0000,
0xbf10,0,0xbf5a,0,0xbf46,0,0x3ede,0,0xbf100000,0,0xbf5a0000,0,0xbf460000,0,0x3ede0000,0,
0,0xbf10,0,0xbf5a,0,0xbf46,0,0x3ede,0,0xbf100000,0,0xbf5a0000,0,0xbf460000,0,0x3ede0000,
0x3f46,0,0xbf2d,0,0xbf10,0,0xbf2d,0,0x3f460000,0,0xbf2d0000,0,0xbf100000,0,0xbf2d0000,0,
0,0x3f46,0,0xbf2d,0,0xbf10,0,0xbf2d,0,0x3f460000,0,0xbf2d0000,0,0xbf100000,0,0xbf2d0000,
0xbf10,0,0x3f5a,0,0x3f46,0,0x3ede,0,0xbf100000,0,0x3f5a0000,0,0x3f460000,0,0x3ede0000,0,
0,0xbf10,0,0x3f5a,0,0x3f46,0,0x3ede,0,0xbf100000,0,0x3f5a0000,0,0x3f460000,0,0x3ede0000,
0xbe97,0,0xbf2d,0,0xbf69,0,0x3f2d,0,0xbe970000,0,0xbf2d0000,0,0xbf690000,0,0x3f2d0000,0,
0,0xbe97,0,0xbf2d,0,0xbf69,0,0x3f2d,0,0xbe970000,0,0xbf2d0000,0,0xbf690000,0,0x3f2d0000,
0x3f69,0,0xbe19,0,0x3e97,0,0xbf72,0,0x3f690000,0,0xbe190000,0,0x3e970000,0,0xbf720000,0,
0,0x3f69,0,0xbe19,0,0x3e97,0,0xbf72,0,0x3f690000,0,0xbe190000,0,0x3e970000,0,0xbf720000,
0xbf75,0,0x3f2d,0,0x8000,0,0x3f2d,0,0xbf750000,0,0x3f2d0000,0,0x80000000,0,0x3f2d0000,0,
0,0xbf75,0,0x3f2d,0,0x8000,0,0x3f2d,0,0xbf750000,0,0x3f2d0000,0,0x80000000,0,0x3f2d0000,
0,0,0xbf2d,0,0xbf75,0,0x3f2d,0,0,0,0xbf2d0000,0,0xbf750000,0,0x3f2d0000,0,
0,0,0,0xbf2d,0,0xbf75,0,0x3f2d,0,0,0,0xbf2d0000,0,0xbf750000,0,0x3f2d0000,
0xbe97,0,0x3f2d,0,0x3f69,0,0xbf2d,0,0xbe970000,0,0x3f2d0000,0,0x3f690000,0,0xbf2d0000,0,
0,0xbe97,0,0x3f2d,0,0x3f69,0,0xbf2d,0,0xbe970000,0,0x3f2d0000,0,0x3f690000,0,0xbf2d0000,
0xbf69,0,0x3f72,0,0x3e97,0,0x3e19,0,0xbf690000,0,0x3f720000,0,0x3e970000,0,0x3e190000,0,
0,0xbf69,0,0x3f72,0,0x3e97,0,0x3e19,0,0xbf690000,0,0x3f720000,0,0x3e970000,0,0x3e190000,
0x3f46,0,0xbf2d,0,0x3f10,0,0xbf2d,0,0x3f460000,0,0xbf2d0000,0,0x3f100000,0,0xbf2d0000,0,
0,0x3f46,0,0xbf2d,0,0x3f10,0,0xbf2d,0,0x3f460000,0,0xbf2d0000,0,0x3f100000,0,0xbf2d0000,
0x3f10,0,0xbede,0,0x3f46,0,0xbf5a,0,0x3f100000,0,0xbede0000,0,0x3f460000,0,0xbf5a0000,0,
0,0x3f10,0,0xbede,0,0x3f46,0,0xbf5a,0,0x3f100000,0,0xbede0000,0,0x3f460000,0,0xbf5a0000,
0x3e97,0,0x3e19,0,0xbf69,0,0xbf72,0,0x3e970000,0,0x3e190000,0,0xbf690000,0,0xbf720000,0,
0,0x3e97,0,0x3e19,0,0xbf69,0,0xbf72,0,0x3e970000,0,0x3e190000,0,0xbf690000,0,0xbf720000,
0,0,0xbe19,0,0xbf75,0,0xbf72,0,0,0,0xbe190000,0,0xbf750000,0,0xbf720000,0,
0,0,0,0xbe19,0,0xbf75,0,0xbf72,0,0,0,0xbe190000,0,0xbf750000,0,0xbf720000,
0xbf46,0,0xbede,0,0x3f10,0,0x3f5a,0,0xbf460000,0,0xbede0000,0,0x3f100000,0,0x3f5a0000,0,
0,0xbf46,0,0xbede,0,0x3f10,0,0x3f5a,0,0xbf460000,0,0xbede0000,0,0x3f100000,0,0x3f5a0000,
0,0,0x3ede,0,0x3f75,0,0x3f5a,0,0,0,0x3ede0000,0,0x3f750000,0,0x3f5a0000,0,
0,0,0,0x3ede,0,0x3f75,0,0x3f5a,0,0,0,0x3ede0000,0,0x3f750000,0,0x3f5a0000,
0x3f75,0,0x3f2d,0,0x8000,0,0xbf2d,0,0x3f750000,0,0x3f2d0000,0,0x80000000,0,0xbf2d0000,0,
0,0x3f75,0,0x3f2d,0,0x8000,0,0xbf2d,0,0x3f750000,0,0x3f2d0000,0,0x80000000,0,0xbf2d0000,
0,0,0xbf2d,0,0xbf75,0,0xbf2d,0,0,0,0xbf2d0000,0,0xbf750000,0,0xbf2d0000,0,
0,0,0,0xbf2d,0,0xbf75,0,0xbf2d,0,0,0,0xbf2d0000,0,0xbf750000,0,0xbf2d0000,
0xbf46,0,0xbf5a,0,0xbf10,0,0x3ede,0,0xbf460000,0,0xbf5a0000,0,0xbf100000,0,0x3ede0000,0,
0,0xbf46,0,0xbf5a,0,0xbf10,0,0x3ede,0,0xbf460000,0,0xbf5a0000,0,0xbf100000,0,0x3ede0000,
0,0,0x3f5a,0,0x3f75,0,0x3ede,0,0,0,0x3f5a0000,0,0x3f750000,0,0x3ede0000,0,
0,0,0,0x3f5a,0,0x3f75,0,0x3ede,0,0,0,0x3f5a0000,0,0x3f750000,0,0x3ede0000,
0x3e97,0,0x3f72,0,0x3f69,0,0xbe19,0,0x3e970000,0,0x3f720000,0,0x3f690000,0,0xbe190000,0,
0,0x3e97,0,0x3f72,0,0x3f69,0,0xbe19,0,0x3e970000,0,0x3f720000,0,0x3f690000,0,0xbe190000,
0,0,0xbf72,0,0xbf75,0,0xbe19,0,0,0,0xbf720000,0,0xbf750000,0,0xbe190000,0,
0,0,0,0xbf72,0,0xbf75,0,0xbe19,0,0,0,0xbf720000,0,0xbf750000,0,0xbe190000,
0x3e97,0,0xbf72,0,0xbf69,0,0xbe19,0,0x3e970000,0,0xbf720000,0,0xbf690000,0,0xbe190000,0,
0,0x3e97,0,0xbf72,0,0xbf69,0,0xbe19,0,0x3e970000,0,0xbf720000,0,0xbf690000,0,0xbe190000,
0,0,0x3f72,0,0x3f75,0,0xbe19,0,0,0,0x3f720000,0,0x3f750000,0,0xbe190000,0,
0,0,0,0x3f72,0,0x3f75,0,0xbe19,0,0,0,0x3f720000,0,0x3f750000,0,0xbe190000,
0xbf46,0,0x3f5a,0,0x3f10,0,0x3ede,0,0xbf460000,0,0x3f5a0000,0,0x3f100000,0,0x3ede0000,0,
0,0xbf46,0,0x3f5a,0,0x3f10,0,0x3ede,0,0xbf460000,0,0x3f5a0000,0,0x3f100000,0,0x3ede0000,
0,0,0xbf5a,0,0xbf75,0,0x3ede,0,0,0,0xbf5a0000,0,0xbf750000,0,0x3ede0000,0,
0,0,0,0xbf5a,0,0xbf75,0,0x3ede,0,0,0,0xbf5a0000,0,0xbf750000,0,0x3ede0000,
0x3f75,0,0xbf2d,0,0x8000,0,0xbf2d,0,0x3f750000,0,0xbf2d0000,0,0x80000000,0,0xbf2d0000,0,
0,0x3f75,0,0xbf2d,0,0x8000,0,0xbf2d,0,0x3f750000,0,0xbf2d0000,0,0x80000000,0,0xbf2d0000,
0,0,0x3f2d,0,0x3f75,0,0xbf2d,0,0,0,0x3f2d0000,0,0x3f750000,0,0xbf2d0000,0,
0,0,0,0x3f2d,0,0x3f75,0,0xbf2d,0,0,0,0x3f2d0000,0,0x3f750000,0,0xbf2d0000,
0xbf46,0,0x3ede,0,0xbf10,0,0x3f5a,0,0xbf460000,0,0x3ede0000,0,0xbf100000,0,0x3f5a0000,0,
0,0xbf46,0,0x3ede,0,0xbf10,0,0x3f5a,0,0xbf460000,0,0x3ede0000,0,0xbf100000,0,0x3f5a0000,
0,0,0xbede,0,0xbf75,0,0x3f5a,0,0,0,0xbede0000,0,0xbf750000,0,0x3f5a0000,0,
0,0,0,0xbede,0,0xbf75,0,0x3f5a,0,0,0,0xbede0000,0,0xbf750000,0,0x3f5a0000,
0x3e97,0,0xbe19,0,0x3f69,0,0xbf72,0,0x3e970000,0,0xbe190000,0,0x3f690000,0,0xbf720000,0,
0,0x3e97,0,0xbe19,0,0x3f69,0,0xbf72,0,0x3e970000,0,0xbe190000,0,0x3f690000,0,0xbf720000,
0,0,0x3e19,0,0x3f75,0,0xbf72,0,0,0,0x3e190000,0,0x3f750000,0,0xbf720000,0,
0,0,0,0x3e19,0,0x3f75,0,0xbf72,0,0,0,0x3e190000,0,0x3f750000,0,0xbf720000,
0xbe97,0,0xbede,0,0xbf69,0,0xbf5a,0,0xbe970000,0,0xbede0000,0,0xbf690000,0,0xbf5a0000,0,
0,0xbe97,0,0xbede,0,0xbf69,0,0xbf5a,0,0xbe970000,0,0xbede0000,0,0xbf690000,0,0xbf5a0000,
0xbf10,0,0xbf2d,0,0xbf46,0,0xbf2d,0,0xbf100000,0,0xbf2d0000,0,0xbf460000,0,0xbf2d0000,0,
0,0xbf10,0,0xbf2d,0,0xbf46,0,0xbf2d,0,0xbf100000,0,0xbf2d0000,0,0xbf460000,0,0xbf2d0000,
0x3f46,0,0x3f72,0,0x3f10,0,0x3e19,0,0x3f460000,0,0x3f720000,0,0x3f100000,0,0x3e190000,0,
0,0x3f46,0,0x3f72,0,0x3f10,0,0x3e19,0,0x3f460000,0,0x3f720000,0,0x3f100000,0,0x3e190000,
0x3f69,0,0x3f2d,0,0xbe97,0,0xbf2d,0,0x3f690000,0,0x3f2d0000,0,0xbe970000,0,0xbf2d0000,0,
0,0x3f69,0,0x3f2d,0,0xbe97,0,0xbf2d,0,0x3f690000,0,0x3f2d0000,0,0xbe970000,0,0xbf2d0000,
0xbf75,0,0xbf2d,0,0x8000,0,0x3f2d,0,0xbf750000,0,0xbf2d0000,0,0x80000000,0,0x3f2d0000,0,
0,0xbf75,0,0xbf2d,0,0x8000,0,0x3f2d,0,0xbf750000,0,0xbf2d0000,0,0x80000000,0,0x3f2d0000,
0,0,0x3f2d,0,0x3f75,0,0x3f2d,0,0,0,0x3f2d0000,0,0x3f750000,0,0x3f2d0000,0,
0,0,0,0x3f2d,0,0x3f75,0,0x3f2d,0,0,0,0x3f2d0000,0,0x3f750000,0,0x3f2d0000,
0x3f46,0,0xbe19,0,0xbf10,0,0xbf72,0,0x3f460000,0,0xbe190000,0,0xbf100000,0,0xbf720000,0,
0,0x3f46,0,0xbe19,0,0xbf10,0,0xbf72,0,0x3f460000,0,0xbe190000,0,0xbf100000,0,0xbf720000,
0xbf69,0,0xbf2d,0,0xbe97,0,0x3f2d,0,0xbf690000,0,0xbf2d0000,0,0xbe970000,0,0x3f2d0000,0,
0,0xbf69,0,0xbf2d,0,0xbe97,0,0x3f2d,0,0xbf690000,0,0xbf2d0000,0,0xbe970000,0,0x3f2d0000,
0xbe97,0,0x3f5a,0,0x3f69,0,0x3ede,0,0xbe970000,0,0x3f5a0000,0,0x3f690000,0,0x3ede0000,0,
0,0xbe97,0,0x3f5a,0,0x3f69,0,0x3ede,0,0xbe970000,0,0x3f5a0000,0,0x3f690000,0,0x3ede0000,
0x3f10,0,0xbf2d,0,0xbf46,0,0xbf2d,0,0x3f100000,0,0xbf2d0000,0,0xbf460000,0,0xbf2d0000,0,
0,0x3f10,0,0xbf2d,0,0xbf46,0,0xbf2d,0,0x3f100000,0,0xbf2d0000,0,0xbf460000,0,0xbf2d0000,
0xbe97,0,0xbf5a,0,0xbf69,0,0x3ede,0,0xbe970000,0,0xbf5a0000,0,0xbf690000,0,0x3ede0000,0,
0,0xbe97,0,0xbf5a,0,0xbf69,0,0x3ede,0,0xbe970000,0,0xbf5a0000,0,0xbf690000,0,0x3ede0000,
0x3f10,0,0x3f2d,0,0x3f46,0,0xbf2d,0,0x3f100000,0,0x3f2d0000,0,0x3f460000,0,0xbf2d0000,0,
0,0x3f10,0,0x3f2d,0,0x3f46,0,0xbf2d,0,0x3f100000,0,0x3f2d0000,0,0x3f460000,0,0xbf2d0000,
0x3f46,0,0x3e19,0,0x3f10,0,0xbf72,0,0x3f460000,0,0x3e190000,0,0x3f100000,0,0xbf720000,0,
0,0x3f46,0,0x3e19,0,0x3f10,0,0xbf72,0,0x3f460000,0,0x3e190000,0,0x3f100000,0,0xbf720000,
0xbf69,0,0x3f2d,0,0x3e97,0,0x3f2d,0,0xbf690000,0,0x3f2d0000,0,0x3e970000,0,0x3f2d0000,0,
0,0xbf69,0,0x3f2d,0,0x3e97,0,0x3f2d,0,0xbf690000,0,0x3f2d0000,0,0x3e970000,0,0x3f2d0000,
0xbf75,0,0x3f2d,0,0x8000,0,0x3f2d,0,0xbf750000,0,0x3f2d0000,0,0x80000000,0,0x3f2d0000,0,
0,0xbf75,0,0x3f2d,0,0x8000,0,0x3f2d,0,0xbf750000,0,0x3f2d0000,0,0x80000000,0,0x3f2d0000,
0,0,0xbf2d,0,0xbf75,0,0x3f2d,0,0,0,0xbf2d0000,0,0xbf750000,0,0x3f2d0000,0,
0,0,0,0xbf2d,0,0xbf75,0,0x3f2d,0,0,0,0xbf2d0000,0,0xbf750000,0,0x3f2d0000,
0x3f46,0,0xbf72,0,0xbf10,0,0x3e19,0,0x3f460000,0,0xbf720000,0,0xbf100000,0,0x3e190000,0,
0,0x3f46,0,0xbf72,0,0xbf10,0,0x3e19,0,0x3f460000,0,0xbf720000,0,0xbf100000,0,0x3e190000,
0x3f69,0,0xbf2d,0,0x3e97,0,0xbf2d,0,0x3f690000,0,0xbf2d0000,0,0x3e970000,0,0xbf2d0000,0,
0,0x3f69,0,0xbf2d,0,0x3e97,0,0xbf2d,0,0x3f690000,0,0xbf2d0000,0,0x3e970000,0,0xbf2d0000,
0xbe97,0,0x3ede,0,0x3f69,0,0xbf5a,0,0xbe970000,0,0x3ede0000,0,0x3f690000,0,0xbf5a0000,0,
0,0xbe97,0,0x3ede,0,0x3f69,0,0xbf5a,0,0xbe970000,0,0x3ede0000,0,0x3f690000,0,0xbf5a0000,
0xbf10,0,0x3f2d,0,0x3f46,0,0xbf2d,0,0xbf100000,0,0x3f2d0000,0,0x3f460000,0,0xbf2d0000,0,
0,0xbf10,0,0x3f2d,0,0x3f46,0,0xbf2d,0,0xbf100000,0,0x3f2d0000,0,0x3f460000,0,0xbf2d0000,
0xbf46,0,0xbf5a,0,0xbf10,0,0xbede,0,0xbf460000,0,0xbf5a0000,0,0xbf100000,0,0xbede0000,0,
0,0xbf46,0,0xbf5a,0,0xbf10,0,0xbede,0,0xbf460000,0,0xbf5a0000,0,0xbf100000,0,0xbede0000,
0xbf69,0,0xbf72,0,0xbe97,0,0xbe19,0,0xbf690000,0,0xbf720000,0,0xbe970000,0,0xbe190000,0,
0,0xbf69,0,0xbf72,0,0xbe97,0,0xbe19,0,0xbf690000,0,0xbf720000,0,0xbe970000,0,0xbe190000,
0x3e97,0,0xbe19,0,0xbf69,0,0xbf72,0,0x3e970000,0,0xbe190000,0,0xbf690000,0,0xbf720000,0,
0,0x3e97,0,0xbe19,0,0xbf69,0,0xbf72,0,0x3e970000,0,0xbe190000,0,0xbf690000,0,0xbf720000,
0xbf10,0,0xbf5a,0,0xbf46,0,0xbede,0,0xbf100000,0,0xbf5a0000,0,0xbf460000,0,0xbede0000,0,
0,0xbf10,0,0xbf5a,0,0xbf46,0,0xbede,0,0xbf100000,0,0xbf5a0000,0,0xbf460000,0,0xbede0000,
0x3f75,0,0x3f2d,0,0x8000,0,0xbf2d,0,0x3f750000,0,0x3f2d0000,0,0x80000000,0,0xbf2d0000,0,
0,0x3f75,0,0x3f2d,0,0x8000,0,0xbf2d,0,0x3f750000,0,0x3f2d0000,0,0x80000000,0,0xbf2d0000,
0,0,0xbf2d,0,0xbf75,0,0xbf2d,0,0,0,0xbf2d0000,0,0xbf750000,0,0xbf2d0000,0,
0,0,0,0xbf2d,0,0xbf75,0,0xbf2d,0,0,0,0xbf2d0000,0,0xbf750000,0,0xbf2d0000,
0x3e97,0,0x3f72,0,0x3f69,0,0x3e19,0,0x3e970000,0,0x3f720000,0,0x3f690000,0,0x3e190000,0,
0,0x3e97,0,0x3f72,0,0x3f69,0,0x3e19,0,0x3e970000,0,0x3f720000,0,0x3f690000,0,0x3e190000,
0x3f10,0,0xbede,0,0xbf46,0,0xbf5a,0,0x3f100000,0,0xbede0000,0,0xbf460000,0,0xbf5a0000,0,
0,0x3f10,0,0xbede,0,0xbf46,0,0xbf5a,0,0x3f100000,0,0xbede0000,0,0xbf460000,0,0xbf5a0000,
0xbf46,0,0x3ede,0,0x3f10,0,0x3f5a,0,0xbf460000,0,0x3ede0000,0,0x3f100000,0,0x3f5a0000,0,
0,0xbf46,0,0x3ede,0,0x3f10,0,0x3f5a,0,0xbf460000,0,0x3ede0000,0,0x3f100000,0,0x3f5a0000,
0x3f69,0,0xbe19,0,0xbe97,0,0xbf72,0,0x3f690000,0,0xbe190000,0,0xbe970000,0,0xbf720000,0,
0,0x3f69,0,0xbe19,0,0xbe97,0,0xbf72,0,0x3f690000,0,0xbe190000,0,0xbe970000,0,0xbf720000,
0xbf46,0,0xbede,0,0xbf10,0,0x3f5a,0,0xbf460000,0,0xbede0000,0,0xbf100000,0,0x3f5a0000,0,
0,0xbf46,0,0xbede,0,0xbf10,0,0x3f5a,0,0xbf460000,0,0xbede0000,0,0xbf100000,0,0x3f5a0000,
0x3f69,0,0x3e19,0,0x3e97,0,0xbf72,0,0x3f690000,0,0x3e190000,0,0x3e970000,0,0xbf720000,0,
0,0x3f69,0,0x3e19,0,0x3e97,0,0xbf72,0,0x3f690000,0,0x3e190000,0,0x3e970000,0,0xbf720000,
0x3e97,0,0xbf72,0,0xbf69,0,0x3e19,0,0x3e970000,0,0xbf720000,0,0xbf690000,0,0x3e190000,0,
0,0x3e97,0,0xbf72,0,0xbf69,0,0x3e19,0,0x3e970000,0,0xbf720000,0,0xbf690000,0,0x3e190000,
0x3f10,0,0x3ede,0,0x3f46,0,0xbf5a,0,0x3f100000,0,0x3ede0000,0,0x3f460000,0,0xbf5a0000,0,
0,0x3f10,0,0x3ede,0,0x3f46,0,0xbf5a,0,0x3f100000,0,0x3ede0000,0,0x3f460000,0,0xbf5a0000,
0x3f75,0,0xbf2d,0,0x8000,0,0xbf2d,0,0x3f750000,0,0xbf2d0000,0,0x80000000,0,0xbf2d0000,0,
0,0x3f75,0,0xbf2d,0,0x8000,0,0xbf2d,0,0x3f750000,0,0xbf2d0000,0,0x80000000,0,0xbf2d0000,
0,0,0x3f2d,0,0x3f75,0,0xbf2d,0,0,0,0x3f2d0000,0,0x3f750000,0,0xbf2d0000,0,
0,0,0,0x3f2d,0,0x3f75,0,0xbf2d,0,0,0,0x3f2d0000,0,0x3f750000,0,0xbf2d0000,
0x3e97,0,0x3e19,0,0x3f69,0,0xbf72,0,0x3e970000,0,0x3e190000,0,0x3f690000,0,0xbf720000,0,
0,0x3e97,0,0x3e19,0,0x3f69,0,0xbf72,0,0x3e970000,0,0x3e190000,0,0x3f690000,0,0xbf720000,
0xbf10,0,0x3f5a,0,0x3f46,0,0xbede,0,0xbf100000,0,0x3f5a0000,0,0x3f460000,0,0xbede0000,0,
0,0xbf10,0,0x3f5a,0,0x3f46,0,0xbede,0,0xbf100000,0,0x3f5a0000,0,0x3f460000,0,0xbede0000,
0xbf46,0,0x3f5a,0,0x3f10,0,0xbede,0,0xbf460000,0,0x3f5a0000,0,0x3f100000,0,0xbede0000,0,
0,0xbf46,0,0x3f5a,0,0x3f10,0,0xbede,0,0xbf460000,0,0x3f5a0000,0,0x3f100000,0,0xbede0000,
0xbf69,0,0x3f72,0,0x3e97,0,0xbe19,0,0xbf690000,0,0x3f720000,0,0x3e970000,0,0xbe190000,0,
0,0xbf69,0,0x3f72,0,0x3e97,0,0xbe19,0,0xbf690000,0,0x3f720000,0,0x3e970000,0,0xbe190000,
0x3f37,0x3f37,0x3f37,0x3f37,0x3f378000,0x3f378000,0x3f378000,0x3f378000,0x3f37,0x3e623f2e,0x3ed73f14,0x3f143ed7,0x3f378000,0x3f2ebe62,0x3f14bed7,0x3ed7bf14,
0x3f37,0x3ed73f14,0x3f2e3e62,0x3f2ebe62,0x3f378000,0x3f14bed7,0x3e62bf2e,0xbe62bf2e,0x3f37,0x3f143ed7,0x3f2ebe62,0x3e62bf2e,0x3f378000,0x3ed7bf14,0xbe62bf2e,0xbf2ebe62,
0x3f37,0x3f37,0x3f37,0x3f37,0x3f378000,0x3f378000,0x3f378000,0x3f378000,0x3f2e3e62,0x3f370000,0x3f2ebe62,0x3f14bed7,0x3e62bf2e,0xbf37,0xbe62bf2e,0xbed7bf14,
0x3ed7bf14,0xbf37,0xbed7bf14,0xbf2ebe62,0xbf14bed7,0xbf378000,0xbf143ed7,0xbe623f2e,0xbed7bf14,0xbf370000,0xbed73f14,0x3e623f2e,0xbf143ed7,0x3f37,0x3f143ed7,0x3f2ebe62,
0x3f37,0x3f2e3e62,0x3ed7bf14,0xbed7bf14,0x3f378000,0x3e62bf2e,0xbf14bed7,0xbf143ed7,0x3f37,0x3f370000,0xbf37,0xbf370000,0x3f378000,0xbf37,0xbf378000,0x3f37,
0x3f37,0x3f2ebe62,0xbed7bf14,0xbed73f14,0x3f378000,0xbe62bf2e,0xbf143ed7,0x3f143ed7,0x3f37,0x3f14bed7,0xbf2ebe62,0x3e623f2e,0x3f378000,0xbed7bf14,0xbe623f2e,0x3f2ebe62,
0xbf2e3e62,0x3f37,0x3f2e3e62,0x3ed7bf14,0x3e623f2e,0x3f378000,0x3e62bf2e,0xbf14bed7,0x3f37,0x3f370000,0xbf37,0xbf370000,0x3f378000,0xbf37,0xbf378000,0x3f37,
0x3f2e3e62,0xbf37,0xbf2e3e62,0x3ed73f14,0x3e62bf2e,0xbf378000,0x3e623f2e,0x3f14bed7,0x3ed7bf14,0xbf370000,0x3ed73f14,0x3e62bf2e,0xbf14bed7,0x3f37,0x3f14bed7,0xbf2ebe62,
0x3f37,0x3ed7bf14,0xbf2e3e62,0x3f2e3e62,0x3f378000,0xbf14bed7,0x3e623f2e,0x3e62bf2e,0x3f37,0x3e62bf2e,0xbed73f14,0x3f14bed7,0x3f378000,0xbf2ebe62,0x3f143ed7,0xbed7bf14,
0x3f37,0xbf37,0x3f37,0xbf37,0x3f378000,0xbf378000,0x3f378000,0xbf378000,0x3f37,0xbe62bf2e,0x3ed73f14,0xbf14bed7,0x3f378000,0xbf2e3e62,0x3f14bed7,0xbed73f14,
0xbed7bf14,0x3f37,0x3ed7bf14,0xbf2e3e62,0xbf143ed7,0x3f378000,0xbf14bed7,0x3e623f2e,0xbf2e3e62,0x3f370000,0xbf2ebe62,0x3f143ed7,0x3e623f2e,0xbf37,0xbe623f2e,0x3ed7bf14,
0x3f37,0xbf37,0x3f37,0xbf37,0x3f378000,0xbf378000,0x3f378000,0xbf378000,0x3f2e3e62,0xbf370000,0x3f2ebe62,0xbf143ed7,0x3e62bf2e,0x3f37,0xbe62bf2e,0x3ed73f14,
0x3f37,0xbed7bf14,0x3f2e3e62,0xbf2e3e62,0x3f378000,0xbf143ed7,0x3e62bf2e,0x3e623f2e,0x3f37,0xbf14bed7,0x3f2ebe62,0xbe623f2e,0x3f378000,0xbed73f14,0xbe62bf2e,0x3f2e3e62,
0x3f37,0xbf2ebe62,0x3ed7bf14,0x3ed73f14,0x3f378000,0xbe623f2e,0xbf14bed7,0x3f14bed7,0x3f37,0xbf370000,0xbf37,0x3f370000,0x3f378000,0x3f37,0xbf378000,0xbf37,
0x3ed7bf14,0x3f37,0xbed7bf14,0x3f2e3e62,0xbf14bed7,0x3f378000,0xbf143ed7,0x3e62bf2e,0xbed7bf14,0x3f370000,0xbed73f14,0xbe62bf2e,0xbf143ed7,0xbf37,0x3f143ed7,0xbf2e3e62,
0xbf2e3e62,0xbf37,0x3f2e3e62,0xbed73f14,0x3e623f2e,0xbf378000,0x3e62bf2e,0x3f143ed7,0x3f37,0xbf370000,0xbf37,0x3f370000,0x3f378000,0x3f37,0xbf378000,0xbf37,
0x3f37,0xbf2e3e62,0xbed7bf14,0x3ed7bf14,0x3f378000,0x3e623f2e,0xbf143ed7,0xbf14bed7,0x3f37,0xbf143ed7,0xbf2ebe62,0xbe62bf2e,0x3f378000,0x3ed73f14,0xbe623f2e,0xbf2e3e62,
0x3f37,0xbed73f14,0xbf2e3e62,0xbf2ebe62,0x3f378000,0x3f143ed7,0x3e623f2e,0xbe623f2e,0x3f37,0xbe623f2e,0xbed73f14,0xbf143ed7,0x3f378000,0x3f2e3e62,0x3f143ed7,0x3ed73f14,
0x3f2e3e62,0x3f37,0xbf2e3e62,0xbed7bf14,0x3e62bf2e,0x3f378000,0x3e623f2e,0xbf143ed7,0x3ed7bf14,0x3f370000,0x3ed73f14,0xbe623f2e,0xbf14bed7,0xbf37,0x3f14bed7,0x3f2e3e62,
0xbed7bf14,0xbf37,0x3ed7bf14,0x3f2ebe62,0xbf143ed7,0xbf378000,0xbf14bed7,0xbe62bf2e,0xbf2e3e62,0xbf370000,0xbf2ebe62,0xbf14bed7,0x3e623f2e,0x3f37,0xbe623f2e,0xbed73f14,
0x3f37,0x3f37,0x3f37,0x3f37,0x3f378000,0x3f378000,0x3f378000,0x3f378000,0x3ed7bf14,0x3e62bf2e,0xbf37,0xbe62bf2e,0xbf14bed7,0xbf2ebe62,0xbf378000,0xbf2e3e62,
0xbf2e3e62,0xbed73f14,0x3f37,0x3ed73f14,0x3e623f2e,0x3f143ed7,0x3f378000,0x3f14bed7,0x3f2e3e62,0x3f14bed7,0xbf37,0xbf14bed7,0x3e62bf2e,0xbed7bf14,0xbf378000,0xbed73f14,
0x3f37,0x3f37,0x3f37,0x3f37,0x3f378000,0x3f378000,0x3f378000,0x3f378000,0xbed7bf14,0xbf14bed7,0xbf2ebe62,0xbf370000,0xbf143ed7,0xbed73f14,0xbe623f2e,0x3f37,
0x3f2e3e62,0x3f2ebe62,0x3ed7bf14,0xbf37,0x3e62bf2e,0xbe62bf2e,0xbf14bed7,0xbf378000,0xbf2e3e62,0xbe623f2e,0x3ed73f14,0x3f370000,0x3e623f2e,0x3f2e3e62,0x3f14bed7,0xbf37,
0xbed7bf14,0xbf2e3e62,0x3f37,0x3f2e3e62,0xbf143ed7,0x3e623f2e,0x3f378000,0x3e62bf2e,0x3f37,0x3f370000,0xbf37,0xbf370000,0x3f378000,0xbf37,0xbf378000,0x3f37,
0x3ed7bf14,0xbf2ebe62,0x3f37,0x3f2ebe62,0xbf14bed7,0xbe623f2e,0x3f378000,0xbe62bf2e,0xbf2e3e62,0x3f143ed7,0xbf37,0xbf143ed7,0x3e623f2e,0x3ed7bf14,0xbf378000,0x3ed73f14,
0x3ed7bf14,0xbed7bf14,0xbf2e3e62,0x3f37,0xbf14bed7,0xbf143ed7,0x3e623f2e,0x3f378000,0x3f37,0x3f370000,0xbf37,0xbf370000,0x3f378000,0xbf37,0xbf378000,0x3f37,
0xbed7bf14,0xbed73f14,0x3f2e3e62,0xbf37,0xbf143ed7,0x3f143ed7,0x3e62bf2e,0xbf378000,0x3f2e3e62,0xbe62bf2e,0xbed73f14,0x3f370000,0x3e62bf2e,0xbf2e3e62,0x3f143ed7,0xbf37,
0x3f2e3e62,0xbed7bf14,0x3f37,0x3ed7bf14,0x3e62bf2e,0xbf143ed7,0x3f378000,0xbf14bed7,0xbed7bf14,0x3e623f2e,0xbf37,0xbe623f2e,0xbf143ed7,0x3f2ebe62,0xbf378000,0x3f2e3e62,
0x3f37,0xbf37,0x3f37,0xbf37,0x3f378000,0xbf378000,0x3f378000,0xbf378000,0x3ed7bf14,0xbe623f2e,0xbf37,0x3e623f2e,0xbf14bed7,0x3f2e3e62,0xbf378000,0x3f2ebe62,
0xbf2e3e62,0x3f2e3e62,0xbed7bf14,0x3f37,0x3e623f2e,0x3e62bf2e,0xbf143ed7,0x3f378000,0x3ed7bf14,0xbf143ed7,0x3f2ebe62,0xbf370000,0xbf14bed7,0x3ed73f14,0xbe62bf2e,0x3f37,
0x3f37,0xbf37,0x3f37,0xbf37,0x3f378000,0xbf378000,0x3f378000,0xbf378000,0xbed7bf14,0x3f143ed7,0xbf2ebe62,0x3f370000,0xbf143ed7,0x3ed7bf14,0xbe623f2e,0xbf37,
0xbf2e3e62,0x3ed7bf14,0x3f37,0xbed7bf14,0x3e623f2e,0xbf14bed7,0x3f378000,0xbf143ed7,0x3f2e3e62,0xbf143ed7,0xbf37,0x3f143ed7,0x3e62bf2e,0x3ed73f14,0xbf378000,0x3ed7bf14,
0xbed7bf14,0x3f2ebe62,0x3f37,0xbf2ebe62,0xbf143ed7,0xbe62bf2e,0x3f378000,0xbe623f2e,0x3f37,0xbf370000,0xbf37,0x3f370000,0x3f378000,0x3f37,0xbf378000,0xbf37,
0x3f2e3e62,0xbf2e3e62,0x3ed7bf14,0x3f37,0x3e62bf2e,0x3e623f2e,0xbf14bed7,0x3f378000,0xbf2e3e62,0x3e62bf2e,0x3ed73f14,0xbf370000,0x3e623f2e,0xbf2ebe62,0x3f14bed7,0x3f37,
0x3ed7bf14,0x3ed73f14,0xbf2e3e62,0xbf37,0xbf14bed7,0x3f14bed7,0x3e623f2e,0xbf378000,0x3f37,0xbf370000,0xbf37,0x3f370000,0x3f378000,0x3f37,0xbf378000,0xbf37,
0x3ed7bf14,0x3f2e3e62,0x3f37,0xbf2e3e62,0xbf14bed7,0x3e62bf2e,0x3f378000,0x3e623f2e,0xbf2e3e62,0xbf14bed7,0xbf37,0x3f14bed7,0x3e623f2e,0xbed73f14,0xbf378000,0xbed7bf14,
0x3f2e3e62,0x3ed73f14,0x3f37,0xbed73f14,0x3e62bf2e,0x3f14bed7,0x3f378000,0x3f143ed7,0xbed7bf14,0xbe62bf2e,0xbf37,0x3e62bf2e,0xbf143ed7,0xbf2e3e62,0xbf378000,0xbf2ebe62,
0xbed7bf14,0x3ed7bf14,0x3f2e3e62,0x3f37,0xbf143ed7,0xbf14bed7,0x3e62bf2e,0x3f378000,0x3f2e3e62,0x3e623f2e,0xbed73f14,0xbf370000,0x3e62bf2e,0x3f2ebe62,0x3f143ed7,0x3f37,
0xbf2e3e62,0xbf2ebe62,0xbed7bf14,0xbf37,0x3e623f2e,0xbe623f2e,0xbf143ed7,0xbf378000,0x3ed7bf14,0x3f14bed7,0x3f2ebe62,0x3f370000,0xbf14bed7,0xbed7bf14,0xbe62bf2e,0xbf37,
0x3f37,0x3f37,0x3f37,0x3f37,0x3f378000,0x3f378000,0x3f378000,0x3f378000,0xbf2e3e62,0xbf143ed7,0xbed73f14,0xbe623f2e,0x3e623f2e,0x3ed73f14,0x3f143ed7,0x3f2e3e62,
0xbed7bf14,0xbf2ebe62,0xbf2e3e62,0xbed73f14,0xbf143ed7,0xbe623f2e,0x3e623f2e,0x3f143ed7,0x3ed7bf14,0xbe62bf2e,0xbf2ebe62,0xbf143ed7,0xbf14bed7,0xbf2e3e62,0xbe623f2e,0x3ed73f14,
0,0,0,0,0,0,0,0,0,0,0,0,0,0,0,0,
0,0,0,0,0,0,0,0,0,0,0,0,0,0,0,0,
0x3f2e3e62,0x3ed7bf14,0xbed7bf14,0xbf2e3e62,0x3e62bf2e,0xbf14bed7,0xbf143ed7,0x3e623f2e,0x3f37,0x3f370000,0xbf37,0xbf370000,0x3f378000,0xbf37,0xbf378000,0x3f37,
0xbf2e3e62,0x3ed73f14,0x3ed7bf14,0xbf2ebe62,0x3e623f2e,0x3f14bed7,0xbf14bed7,0xbe623f2e,0xbed7bf14,0xbe623f2e,0x3f2ebe62,0xbf14bed7,0xbf143ed7,0x3f2e3e62,0xbe62bf2e,0xbed73f14,
0,0,0,0,0,0,0,0,0,0,0,0,0,0,0,0,
0,0,0,0,0,0,0,0,0,0,0,0,0,0,0,0,
0x3ed7bf14,0xbf2e3e62,0x3f2e3e62,0xbed7bf14,0xbf14bed7,0x3e623f2e,0x3e62bf2e,0xbf143ed7,0x3f2e3e62,0xbf14bed7,0x3ed73f14,0xbe62bf2e,0x3e62bf2e,0xbed73f14,0x3f14bed7,0xbf2e3e62,
0x3f37,0xbf37,0x3f37,0xbf37,0x3f378000,0xbf378000,0x3f378000,0xbf378000,0xbf2e3e62,0x3f14bed7,0xbed73f14,0x3e62bf2e,0x3e623f2e,0xbed7bf14,0x3f143ed7,0xbf2ebe62,
0,0,0,0,0,0,0,0,0,0,0,0,0,0,0,0,
0,0,0,0,0,0,0,0,0,0,0,0,0,0,0,0,
0xbed7bf14,0x3f2e3e62,0xbf2e3e62,0x3ed7bf14,0xbf143ed7,0x3e62bf2e,0x3e623f2e,0xbf14bed7,0x3ed7bf14,0x3e623f2e,0xbf2ebe62,0x3f14bed7,0xbf14bed7,0x3f2ebe62,0xbe623f2e,0xbed7bf14,
0x3f2e3e62,0xbed73f14,0xbed7bf14,0x3f2ebe62,0x3e62bf2e,0x3f143ed7,0xbf143ed7,0xbe62bf2e,0x3f37,0xbf370000,0xbf37,0x3f370000,0x3f378000,0x3f37,0xbf378000,0xbf37,
0,0,0,0,0,0,0,0,0,0,0,0,0,0,0,0,
0,0,0,0,0,0,0,0,0,0,0,0,0,0,0,0,
0xbf2e3e62,0xbed7bf14,0x3ed7bf14,0x3f2e3e62,0x3e623f2e,0xbf143ed7,0xbf14bed7,0x3e62bf2e,0xbed7bf14,0x3e62bf2e,0x3f2ebe62,0x3f143ed7,0xbf143ed7,0xbf2ebe62,0xbe62bf2e,0x3ed7bf14,
0x3ed7bf14,0x3f2ebe62,0x3f2e3e62,0x3ed73f14,0xbf14bed7,0xbe62bf2e,0x3e62bf2e,0x3f14bed7,0x3f2e3e62,0x3f143ed7,0x3ed73f14,0x3e623f2e,0x3e62bf2e,0x3ed7bf14,0x3f14bed7,0x3f2ebe62,
0,0,0,0,0,0,0,0,0,0,0,0,0,0,0,0,
0,0,0,0,0,0,0,0,0,0,0,0,0,0,0,0,
};
__device__ __align__(128) const uint32_t TAB_P3[3008] = {
0,0,0,0,0,0,0,0,0,0,0,0,0,0,0,0,
0x80003f37,0xbf2ebe62,0x3ed7bf14,0x3ed73f14,0x3f370000,0xbe623f2e,0xbf14bed7,0x3f14bed7,0x80003f37,0xbf14bed7,0x3f2ebe62,0xbe623f2e,0x3f370000,0xbed73f14,0xbe62bf2e,0x3f2e3e62,
0,0,0,0,0,0,0,0,0,0,0,0,0,0,0,0,
0xbf2e3e62,0x8000bf37,0x3f2e3e62,0xbed73f14,0x3e623f2e,0xbf370000,0x3e62bf2e,0x3f143ed7,0xbed7bf14,0x3f370000,0xbed73f14,0xbe62bf2e,0xbf143ed7,0xbf37,0x3f143ed7,0xbf2e3e62,
0x80003f37,0xbed7bf14,0x3f2e3e62,0xbf2e3e62,0x3f370000,0xbf143ed7,0x3e62bf2e,0x3e623f2e,0x80003f37,0xbe62bf2e,0x3ed73f14,0xbf14bed7,0x3f370000,0xbf2e3e62,0x3f14bed7,0xbed73f14,
0x80003f37,0x8000bf37,0x80003f37,0x8000bf37,0x3f370000,0xbf370000,0x3f370000,0xbf370000,0x80003f37,0x3e62bf2e,0xbed73f14,0x3f14bed7,0x3f370000,0xbf2ebe62,0x3f143ed7,0xbed7bf14,
0x3ed7bf14,0x80003f37,0xbed7bf14,0x3f2e3e62,0xbf14bed7,0x3f370000,0xbf143ed7,0x3e62bf2e,0x3f2e3e62,0xbf370000,0x3f2ebe62,0xbf143ed7,0x3e62bf2e,0x3f37,0xbe62bf2e,0x3ed73f14,
0x80003f37,0x8000bf37,0x80003f37,0x8000bf37,0x3f370000,0xbf370000,0x3f370000,0xbf370000,0xbf2e3e62,0x3f370000,0xbf2ebe62,0x3f143ed7,0x3e623f2e,0xbf37,0xbe623f2e,0x3ed7bf14,
0x80003f37,0x3ed7bf14,0xbf2e3e62,0x3f2e3e62,0x3f370000,0xbf14bed7,0x3e623f2e,0x3e62bf2e,0x80003f37,0x3f14bed7,0xbf2ebe62,0x3e623f2e,0x3f370000,0xbed7bf14,0xbe623f2e,0x3f2ebe62,
0x80003f37,0x3f2ebe62,0xbed7bf14,0xbed73f14,0x3f370000,0xbe62bf2e,0xbf143ed7,0x3f143ed7,0x80003f37,0x3f370000,0x8000bf37,0xbf370000,0x3f370000,0xbf37,0xbf370000,0x3f37,
0xbed7bf14,0x80003f37,0x3ed7bf14,0xbf2e3e62,0xbf143ed7,0x3f370000,0xbf14bed7,0x3e623f2e,0x3ed7bf14,0xbf370000,0x3ed73f14,0x3e62bf2e,0xbf14bed7,0x3f37,0x3f14bed7,0xbf2ebe62,
0x3f2e3e62,0x8000bf37,0xbf2e3e62,0x3ed73f14,0x3e62bf2e,0xbf370000,0x3e623f2e,0x3f14bed7,0x80003f37,0x3f370000,0x8000bf37,0xbf370000,0x3f370000,0xbf37,0xbf370000,0x3f37,
0x80003f37,0x3f2e3e62,0x3ed7bf14,0xbed7bf14,0x3f370000,0x3e62bf2e,0xbf14bed7,0xbf143ed7,0x80003f37,0x3f143ed7,0x3f2ebe62,0x3e62bf2e,0x3f370000,0x3ed7bf14,0xbe62bf2e,0xbf2ebe62,
0x80003f37,0x3ed73f14,0x3f2e3e62,0x3f2ebe62,0x3f370000,0x3f14bed7,0x3e62bf2e,0xbe62bf2e,0x80003f37,0x3e623f2e,0x3ed73f14,0x3f143ed7,0x3f370000,0x3f2ebe62,0x3f14bed7,0x3ed7bf14,
0xbf2e3e62,0x80003f37,0x3f2e3e62,0x3ed7bf14,0x3e623f2e,0x3f370000,0x3e62bf2e,0xbf14bed7,0xbed7bf14,0xbf370000,0xbed73f14,0x3e623f2e,0xbf143ed7,0x3f37,0x3f143ed7,0x3f2ebe62,
0x3ed7bf14,0x8000bf37,0xbed7bf14,0xbf2ebe62,0xbf14bed7,0xbf370000,0xbf143ed7,0xbe623f2e,0x3f2e3e62,0x3f370000,0x3f2ebe62,0x3f14bed7,0x3e62bf2e,0xbf37,0xbe62bf2e,0xbed7bf14,
0,0,0,0,0,0,0,0,0,0,0,0,0,0,0,0,
0xbed7bf14,0x3f2ebe62,0x80003f37,0xbf2ebe62,0xbf143ed7,0xbe62bf2e,0x3f370000,0xbe623f2e,0x3f2e3e62,0xbf143ed7,0x8000bf37,0x3f143ed7,0x3e62bf2e,0x3ed73f14,0xbf370000,0x3ed7bf14,
0,0,0,0,0,0,0,0,0,0,0,0,0,0,0,0,
0x3ed7bf14,0x3ed73f14,0xbf2e3e62,0x8000bf37,0xbf14bed7,0x3f14bed7,0x3e623f2e,0xbf370000,0xbf2e3e62,0x3e62bf2e,0x3ed73f14,0xbf370000,0x3e623f2e,0xbf2ebe62,0x3f14bed7,0x3f37,
0xbf2e3e62,0x3ed7bf14,0x80003f37,0xbed7bf14,0x3e623f2e,0xbf14bed7,0x3f370000,0xbf143ed7,0x3ed7bf14,0xbe623f2e,0x8000bf37,0x3e623f2e,0xbf14bed7,0x3f2e3e62,0xbf370000,0x3f2ebe62,
0x80003f37,0x8000bf37,0x80003f37,0x8000bf37,0x3f370000,0xbf370000,0x3f370000,0xbf370000,0xbed7bf14,0x3e623f2e,0x8000bf37,0xbe623f2e,0xbf143ed7,0x3f2ebe62,0xbf370000,0x3f2e3e62,
0x3f2e3e62,0xbf2e3e62,0x3ed7bf14,0x80003f37,0x3e62bf2e,0x3e623f2e,0xbf14bed7,0x3f370000,0xbed7bf14,0x3f143ed7,0xbf2ebe62,0x3f370000,0xbf143ed7,0x3ed7bf14,0xbe623f2e,0xbf37,
0x80003f37,0x8000bf37,0x80003f37,0x8000bf37,0x3f370000,0xbf370000,0x3f370000,0xbf370000,0x3ed7bf14,0xbf143ed7,0x3f2ebe62,0xbf370000,0xbf14bed7,0x3ed73f14,0xbe62bf2e,0x3f37,
0x3f2e3e62,0xbed7bf14,0x80003f37,0x3ed7bf14,0x3e62bf2e,0xbf143ed7,0x3f370000,0xbf14bed7,0xbf2e3e62,0x3f143ed7,0x8000bf37,0xbf143ed7,0x3e623f2e,0x3ed7bf14,0xbf370000,0x3ed73f14,
0x3ed7bf14,0xbf2ebe62,0x80003f37,0x3f2ebe62,0xbf14bed7,0xbe623f2e,0x3f370000,0xbe62bf2e,0x80003f37,0x3f370000,0x8000bf37,0xbf370000,0x3f370000,0xbf37,0xbf370000,0x3f37,
0xbf2e3e62,0x3f2e3e62,0xbed7bf14,0x80003f37,0x3e623f2e,0x3e62bf2e,0xbf143ed7,0x3f370000,0x3f2e3e62,0xbe62bf2e,0xbed73f14,0x3f370000,0x3e62bf2e,0xbf2e3e62,0x3f143ed7,0xbf37,
0xbed7bf14,0xbed73f14,0x3f2e3e62,0x8000bf37,0xbf143ed7,0x3f143ed7,0x3e62bf2e,0xbf370000,0x80003f37,0x3f370000,0x8000bf37,0xbf370000,0x3f370000,0xbf37,0xbf370000,0x3f37,
0xbed7bf14,0xbf2e3e62,0x80003f37,0x3f2e3e62,0xbf143ed7,0x3e623f2e,0x3f370000,0x3e62bf2e,0x3f2e3e62,0x3f14bed7,0x8000bf37,0xbf14bed7,0x3e62bf2e,0xbed7bf14,0xbf370000,0xbed73f14,
0xbf2e3e62,0xbed73f14,0x80003f37,0x3ed73f14,0x3e623f2e,0x3f143ed7,0x3f370000,0x3f14bed7,0x3ed7bf14,0x3e62bf2e,0x8000bf37,0xbe62bf2e,0xbf14bed7,0xbf2ebe62,0xbf370000,0xbf2e3e62,
0x3ed7bf14,0xbed7bf14,0xbf2e3e62,0x80003f37,0xbf14bed7,0xbf143ed7,0x3e623f2e,0x3f370000,0xbf2e3e62,0xbe623f2e,0x3ed73f14,0x3f370000,0x3e623f2e,0x3f2e3e62,0x3f14bed7,0xbf37,
0x3f2e3e62,0x3f2ebe62,0x3ed7bf14,0x8000bf37,0x3e62bf2e,0xbe62bf2e,0xbf14bed7,0xbf370000,0xbed7bf14,0xbf14bed7,0xbf2ebe62,0xbf370000,0xbf143ed7,0xbed73f14,0xbe623f2e,0x3f37,
0,0,0,0,0,0,0,0,0,0,0,0,0,0,0,0,
0,0,0,0,0,0,0,0,0,0,0,0,0,0,0,0,
0,0,0,0,0,0,0,0,0,0,0,0,0,0,0,0,
0x3f2e3e62,0xbed73f14,0xbed7bf14,0x3f2ebe62,0x3e62bf2e,0x3f143ed7,0xbf143ed7,0xbe62bf2e,0x3ed7bf14,0x3e623f2e,0xbf2ebe62,0x3f14bed7,0xbf14bed7,0x3f2ebe62,0xbe623f2e,0xbed7bf14,
0,0,0,0,0,0,0,0,0,0,0,0,0,0,0,0,
0,0,0,0,0,0,0,0,0,0,0,0,0,0,0,0,
0xbed7bf14,0x3f2e3e62,0xbf2e3e62,0x3ed7bf14,0xbf143ed7,0x3e62bf2e,0x3e623f2e,0xbf14bed7,0xbf2e3e62,0x3f14bed7,0xbed73f14,0x3e62bf2e,0x3e623f2e,0xbed7bf14,0x3f143ed7,0xbf2ebe62,
0x80003f37,0x8000bf37,0x80003f37,0x8000bf37,0x3f370000,0xbf370000,0x3f370000,0xbf370000,0x3f2e3e62,0xbf14bed7,0x3ed73f14,0xbe62bf2e,0x3e62bf2e,0xbed73f14,0x3f14bed7,0xbf2e3e62,
0,0,0,0,0,0,0,0,0,0,0,0,0,0,0,0,
0,0,0,0,0,0,0,0,0,0,0,0,0,0,0,0,
0x3ed7bf14,0xbf2e3e62,0x3f2e3e62,0xbed7bf14,0xbf14bed7,0x3e623f2e,0x3e62bf2e,0xbf143ed7,0xbed7bf14,0xbe623f2e,0x3f2ebe62,0xbf14bed7,0xbf143ed7,0x3f2e3e62,0xbe62bf2e,0xbed73f14,
0xbf2e3e62,0x3ed73f14,0x3ed7bf14,0xbf2ebe62,0x3e623f2e,0x3f14bed7,0xbf14bed7,0xbe623f2e,0x80003f37,0x3f370000,0x8000bf37,0xbf370000,0x3f370000,0xbf37,0xbf370000,0x3f37,
0,0,0,0,0,0,0,0,0,0,0,0,0,0,0,0,
0,0,0,0,0,0,0,0,0,0,0,0,0,0,0,0,
0x3f2e3e62,0x3ed7bf14,0xbed7bf14,0xbf2e3e62,0x3e62bf2e,0xbf14bed7,0xbf143ed7,0x3e623f2e,0x3ed7bf14,0xbe62bf2e,0xbf2ebe62,0xbf143ed7,0xbf14bed7,0xbf2e3e62,0xbe623f2e,0x3ed73f14,
0xbed7bf14,0xbf2ebe62,0xbf2e3e62,0xbed73f14,0xbf143ed7,0xbe623f2e,0x3e623f2e,0x3f143ed7,0xbf2e3e62,0xbf143ed7,0xbed73f14,0xbe623f2e,0x3e623f2e,0x3ed73f14,0x3f143ed7,0x3f2e3e62,
0xbf463f10,0,0,0,0,0xbf463f10,0,0,0,0,0xbf463f10,0,0,0,0,0xbf463f10,
0xbf5a3ede,0,0,0,0,0xbf5a3ede,0,0,0,0,0xbf5a3ede,0,0,0,0,0xbf5a3ede,
0xbe97bf69,0,0,0,0,0xbe97bf69,0,0,0,0,0xbe97bf69,0,0,0,0,0xbe97bf69,
0x3e19bf72,0,0,0,0,0x3e19bf72,0,0,0,0,0x3e19bf72,0,0,0,0,0x3e19bf72,
0xbf693e97,0,0,0,0,0xbf693e97,0,0,0,0,0xbf693e97,0,0,0,0,0xbf693e97,
0xbf723e19,0,0,0,0,0xbf723e19,0,0,0,0,0xbf723e19,0,0,0,0,0xbf723e19,
0x3f10bf46,0,0,0,0,0x3f10bf46,0,0,0,0,0x3f10bf46,0,0,0,0,0x3f10bf46,
0x3f5abede,0,0,0,0,0x3f5abede,0,0,0,0,0x3f5abede,0,0,0,0,0x3f5abede,
0xbf750000,0,0,0,0,0xbf750000,0,0,0,0,0xbf750000,0,0,0,0,0xbf750000,
0xbf72be19,0,0,0,0,0xbf72be19,0,0,0,0,0xbf72be19,0,0,0,0,0xbf72be19,
0x3f750000,0,0,0,0,0x3f750000,0,0,0,0,0x3f750000,0,0,0,0,0x3f750000,
0x3f5a3ede,0,0,0,0,0x3f5a3ede,0,0,0,0,0x3f5a3ede,0,0,0,0,0x3f5a3ede,
0xbf69be97,0,0,0,0,0xbf69be97,0,0,0,0,0xbf69be97,0,0,0,0,0xbf69be97,
0xbf5abede,0,0,0,0,0xbf5abede,0,0,0,0,0xbf5abede,0,0,0,0,0xbf5abede,
0x3f103f46,0,0,0,0,0x3f103f46,0,0,0,0,0x3f103f46,0,0,0,0,0x3f103f46,
0x3e193f72,0,0,0,0,0x3e193f72,0,0,0,0,0x3e193f72,0,0,0,0,0x3e193f72,
0xbf46bf10,0,0,0,0,0xbf46bf10,0,0,0,0,0xbf46bf10,0,0,0,0,0xbf46bf10,
0xbf2dbf2d,0,0,0,0,0xbf2dbf2d,0,0,0,0,0xbf2dbf2d,0,0,0,0,0xbf2dbf2d,
0xbe973f69,0,0,0,0,0xbe973f69,0,0,0,0,0xbe973f69,0,0,0,0,0xbe973f69,
0xbf2d3f2d,0,0,0,0,0xbf2d3f2d,0,0,0,0,0xbf2d3f2d,0,0,0,0,0xbf2d3f2d,
0xbf10bf46,0,0,0,0,0xbf10bf46,0,0,0,0,0xbf10bf46,0,0,0,0,0xbf10bf46,
0xbedebf5a,0,0,0,0,0xbedebf5a,0,0,0,0,0xbedebf5a,0,0,0,0,0xbedebf5a,
0xbf693e97,0,0,0,0,0xbf693e97,0,0,0,0,0xbf693e97,0,0,0,0,0xbf693e97,
0xbf72be19,0,0,0,0,0xbf72be19,0,0,0,0,0xbf72be19,0,0,0,0,0xbf72be19,
0xbe97bf69,0,0,0,0,0xbe97bf69,0,0,0,0,0xbe97bf69,0,0,0,0,0xbe97bf69,
0xbe19bf72,0,0,0,0,0xbe19bf72,0,0,0,0,0xbe19bf72,0,0,0,0,0xbe19bf72,
0xbf46bf10,0,0,0,0,0xbf46bf10,0,0,0,0,0xbf46bf10,0,0,0,0,0xbf46bf10,
0xbedebf5a,0,0,0,0,0xbedebf5a,0,0,0,0,0xbedebf5a,0,0,0,0,0xbedebf5a,
0x3f750000,0,0,0,0,0x3f750000,0,0,0,0,0x3f750000,0,0,0,0,0x3f750000,
0x3f2d3f2d,0,0,0,0,0x3f2d3f2d,0,0,0,0,0x3f2d3f2d,0,0,0,0,0x3f2d3f2d,
0xbe973f69,0,0,0,0,0xbe973f69,0,0,0,0,0xbe973f69,0,0,0,0,0xbe973f69,
0xbf723e19,0,0,0,0,0xbf723e19,0,0,0,0,0xbf723e19,0,0,0,0,0xbf723e19,
0x80003f75,0,0,0,0,0x80003f75,0,0,0,0,0x80003f75,0,0,0,0,0x80003f75,
0xbf2d3f2d,0,0,0,0,0xbf2d3f2d,0,0,0,0,0xbf2d3f2d,0,0,0,0,0xbf2d3f2d,
0xbf10bf46,0,0,0,0,0xbf10bf46,0,0,0,0,0xbf10bf46,0,0,0,0,0xbf10bf46,
0x3edebf5a,0,0,0,0,0x3edebf5a,0,0,0,0,0x3edebf5a,0,0,0,0,0x3edebf5a,
0xbf750000,0,0,0,0,0xbf750000,0,0,0,0,0xbf750000,0,0,0,0,0xbf750000,
0xbf2dbf2d,0,0,0,0,0xbf2dbf2d,0,0,0,0,0xbf2dbf2d,0,0,0,0,0xbf2dbf2d,
0x3f750000,0,0,0,0,0x3f750000,0,0,0,0,0x3f750000,0,0,0,0,0x3f750000,
0x3ede3f5a,0,0,0,0,0x3ede3f5a,0,0,0,0,0x3ede3f5a,0,0,0,0,0x3ede3f5a,
0x8000bf75,0,0,0,0,0x8000bf75,0,0,0,0,0x8000bf75,0,0,0,0,0x8000bf75,
0x3f2dbf2d,0,0,0,0,0x3f2dbf2d,0,0,0,0,0x3f2dbf2d,0,0,0,0,0x3f2dbf2d,
0xbf103f46,0,0,0,0,0xbf103f46,0,0,0,0,0xbf103f46,0,0,0,0,0xbf103f46,
0xbf72be19,0,0,0,0,0xbf72be19,0,0,0,0,0xbf72be19,0,0,0,0,0xbf72be19,
0x3f750000,0,0,0,0,0x3f750000,0,0,0,0,0x3f750000,0,0,0,0,0x3f750000,
0x3f2d3f2d,0,0,0,0,0x3f2d3f2d,0,0,0,0,0x3f2d3f2d,0,0,0,0,0x3f2d3f2d,
0xbe97bf69,0,0,0,0,0xbe97bf69,0,0,0,0,0xbe97bf69,0,0,0,0,0xbe97bf69,
0x3f2dbf2d,0,0,0,0,0x3f2dbf2d,0,0,0,0,0x3f2dbf2d,0,0,0,0,0x3f2dbf2d,
0x80003f75,0,0,0,0,0x80003f75,0,0,0,0,0x80003f75,0,0,0,0,0x80003f75,
0xbf2d3f2d,0,0,0,0,0xbf2d3f2d,0,0,0,0,0xbf2d3f2d,0,0,0,0,0xbf2d3f2d,
0x3f693e97,0,0,0,0,0x3f693e97,0,0,0,0,0x3f693e97,0,0,0,0,0x3f693e97,
0x3e193f72,0,0,0,0,0x3e193f72,0,0,0,0,0x3e193f72,0,0,0,0,0x3e193f72,
0xbf750000,0,0,0,0,0xbf750000,0,0,0,0,0xbf750000,0,0,0,0,0xbf750000,
0xbf2dbf2d,0,0,0,0,0xbf2dbf2d,0,0,0,0,0xbf2dbf2d,0,0,0,0,0xbf2dbf2d,
0xbf463f10,0,0,0,0,0xbf463f10,0,0,0,0,0xbf463f10,0,0,0,0,0xbf463f10,
0xbf5abede,0,0,0,0,0xbf5abede,0,0,0,0,0xbf5abede,0,0,0,0,0xbf5abede,
0xbf46bf10,0,0,0,0,0xbf46bf10,0,0,0,0,0xbf46bf10,0,0,0,0,0xbf46bf10,
0x3edebf5a,0,0,0,0,0x3edebf5a,0,0,0,0,0x3edebf5a,0,0,0,0,0x3edebf5a,
0x3f46bf10,0,0,0,0,0x3f46bf10,0,0,0,0,0x3f46bf10,0,0,0,0,0x3f46bf10,
0x3ede3f5a,0,0,0,0,0x3ede3f5a,0,0,0,0,0x3ede3f5a,0,0,0,0,0x3ede3f5a,
0x3f693e97,0,0,0,0,0x3f693e97,0,0,0,0,0x3f693e97,0,0,0,0,0x3f693e97,
0xbe193f72,0,0,0,0,0xbe193f72,0,0,0,0,0xbe193f72,0,0,0,0,0xbe193f72,
0xbf693e97,0,0,0,0,0xbf693e97,0,0,0,0,0xbf693e97,0,0,0,0,0xbf693e97,
0xbe19bf72,0,0,0,0,0xbe19bf72,0,0,0,0,0xbe19bf72,0,0,0,0,0xbe19bf72,
0xbf750000,0,0,0,0,0xbf750000,0,0,0,0,0xbf750000,0,0,0,0,0xbf750000,
0xbe19bf72,0,0,0,0,0xbe19bf72,0,0,0,0,0xbe19bf72,0,0,0,0,0xbe19bf72,
0x3f750000,0,0,0,0,0x3f750000,0,0,0,0,0x3f750000,0,0,0,0,0x3f750000,
0xbe193f72,0,0,0,0,0xbe193f72,0,0,0,0,0xbe193f72,0,0,0,0,0xbe193f72,
0x3f69be97,0,0,0,0,0x3f69be97,0,0,0,0,0x3f69be97,0,0,0,0,0x3f69be97,
0x3ede3f5a,0,0,0,0,0x3ede3f5a,0,0,0,0,0x3ede3f5a,0,0,0,0,0x3ede3f5a,
0xbf69be97,0,0,0,0,0xbf69be97,0,0,0,0,0xbf69be97,0,0,0,0,0xbf69be97,
0x3edebf5a,0,0,0,0,0x3edebf5a,0,0,0,0,0x3edebf5a,0,0,0,0,0x3edebf5a,
0xbf463f10,0,0,0,0,0xbf463f10,0,0,0,0,0xbf463f10,0,0,0,0,0xbf463f10,
0xbf2dbf2d,0,0,0,0,0xbf2dbf2d,0,0,0,0,0xbf2dbf2d,0,0,0,0,0xbf2dbf2d,
0x3f463f10,0,0,0,0,0x3f463f10,0,0,0,0,0x3f463f10,0,0,0,0,0x3f463f10,
0xbf2d3f2d,0,0,0,0,0xbf2d3f2d,0,0,0,0,0xbf2d3f2d,0,0,0,0,0xbf2d3f2d,
0x3f10bf46,0,0,0,0,0x3f10bf46,0,0,0,0,0x3f10bf46,0,0,0,0,0x3f10bf46,
0x3f5a3ede,0,0,0,0,0x3f5a3ede,0,0,0,0,0x3f5a3ede,0,0,0,0,0x3f5a3ede,
0xbf10bf46,0,0,0,0,0xbf10bf46,0,0,0,0,0xbf10bf46,0,0,0,0,0xbf10bf46,
0x3f5abede,0,0,0,0,0x3f5abede,0,0,0,0,0x3f5abede,0,0,0,0,0x3f5abede,
0xbe973f69,0,0,0,0,0xbe973f69,0,0,0,0,0xbe973f69,0,0,0,0,0xbe973f69,
0xbf72be19,0,0,0,0,0xbf72be19,0,0,0,0,0xbf72be19,0,0,0,0,0xbf72be19,
0x3e973f69,0,0,0,0,0x3e973f69,0,0,0,0,0x3e973f69,0,0,0,0,0x3e973f69,
0xbf723e19,0,0,0,0,0xbf723e19,0,0,0,0,0xbf723e19,0,0,0,0,0xbf723e19,
0x3e973f69,0,0,0,0,0x3e973f69,0,0,0,0,0x3e973f69,0,0,0,0,0x3e973f69,
0xbf72be19,0,0,0,0,0xbf72be19,0,0,0,0,0xbf72be19,0,0,0,0,0xbf72be19,
0xbf750000,0,0,0,0,0xbf750000,0,0,0,0,0xbf750000,0,0,0,0,0xbf750000,
0x3f2dbf2d,0,0,0,0,0x3f2dbf2d,0,0,0,0,0x3f2dbf2d,0,0,0,0,0x3f2dbf2d,
0x3f10bf46,0,0,0,0,0x3f10bf46,0,0,0,0,0x3f10bf46,0,0,0,0,0x3f10bf46,
0x3ede3f5a,0,0,0,0,0x3ede3f5a,0,0,0,0,0x3ede3f5a,0,0,0,0,0x3ede3f5a,
0x80003f75,0,0,0,0,0x80003f75,0,0,0,0,0x80003f75,0,0,0,0,0x80003f75,
0xbf2dbf2d,0,0,0,0,0xbf2dbf2d,0,0,0,0,0xbf2dbf2d,0,0,0,0,0xbf2dbf2d,
0xbf750000,0,0,0,0,0xbf750000,0,0,0,0,0xbf750000,0,0,0,0,0xbf750000,
0x3edebf5a,0,0,0,0,0x3edebf5a,0,0,0,0,0x3edebf5a,0,0,0,0,0x3edebf5a,
0x3f750000,0,0,0,0,0x3f750000,0,0,0,0,0x3f750000,0,0,0,0,0x3f750000,
0xbf2d3f2d,0,0,0,0,0xbf2d3f2d,0,0,0,0,0xbf2d3f2d,0,0,0,0,0xbf2d3f2d,
0x3f103f46,0,0,0,0,0x3f103f46,0,0,0,0,0x3f103f46,0,0,0,0,0x3f103f46,
0xbf723e19,0,0,0,0,0xbf723e19,0,0,0,0,0xbf723e19,0,0,0,0,0xbf723e19,
0x8000bf75,0,0,0,0,0x8000bf75,0,0,0,0,0x8000bf75,0,0,0,0,0x8000bf75,
0x3f2d3f2d,0,0,0,0,0x3f2d3f2d,0,0,0,0,0x3f2d3f2d,0,0,0,0,0x3f2d3f2d,
0x3e97bf69,0,0,0,0,0x3e97bf69,0,0,0,0,0x3e97bf69,0,0,0,0,0x3e97bf69,
0x3f2d3f2d,0,0,0,0,0x3f2d3f2d,0,0,0,0,0x3f2d3f2d,0,0,0,0,0x3f2d3f2d,
0xbf750000,0,0,0,0,0xbf750000,0,0,0,0,0xbf750000,0,0,0,0,0xbf750000,
0x3f2dbf2d,0,0,0,0,0x3f2dbf2d,0,0,0,0,0x3f2dbf2d,0,0,0,0,0x3f2dbf2d,
0xbf693e97,0,0,0,0,0xbf693e97,0,0,0,0,0xbf693e97,0,0,0,0,0xbf693e97,
0x3e19bf72,0,0,0,0,0x3e19bf72,0,0,0,0,0x3e19bf72,0,0,0,0,0x3e19bf72,
0x80003f75,0,0,0,0,0x80003f75,0,0,0,0,0x80003f75,0,0,0,0,0x80003f75,
0xbf2dbf2d,0,0,0,0,0xbf2dbf2d,0,0,0,0,0xbf2dbf2d,0,0,0,0,0xbf2dbf2d,
0x3f463f10,0,0,0,0,0x3f463f10,0,0,0,0,0x3f463f10,0,0,0,0,0x3f463f10,
0xbf5a3ede,0,0,0,0,0xbf5a3ede,0,0,0,0,0xbf5a3ede,0,0,0,0,0xbf5a3ede,
0x3f750000,0,0,0,0,0x3f750000,0,0,0,0,0x3f750000,0,0,0,0,0x3f750000,
0xbf2d3f2d,0,0,0,0,0xbf2d3f2d,0,0,0,0,0xbf2d3f2d,0,0,0,0,0xbf2d3f2d,
0x3e97bf69,0,0,0,0,0x3e97bf69,0,0,0,0,0x3e97bf69,0,0,0,0,0x3e97bf69,
0x3e193f72,0,0,0,0,0x3e193f72,0,0,0,0,0x3e193f72,0,0,0,0,0x3e193f72,
0x3f463f10,0,0,0,0,0x3f463f10,0,0,0,0,0x3f463f10,0,0,0,0,0x3f463f10,
0xbf5abede,0,0,0,0,0xbf5abede,0,0,0,0,0xbf5abede,0,0,0,0,0xbf5abede,
0xbf10bf46,0,0,0,0,0xbf10bf46,0,0,0,0,0xbf10bf46,0,0,0,0,0xbf10bf46,
0x3f5a3ede,0,0,0,0,0x3f5a3ede,0,0,0,0,0x3f5a3ede,0,0,0,0,0x3f5a3ede,
0x3f693e97,0,0,0,0,0x3f693e97,0,0,0,0,0x3f693e97,0,0,0,0,0x3f693e97,
0xbf72be19,0,0,0,0,0xbf72be19,0,0,0,0,0xbf72be19,0,0,0,0,0xbf72be19,
0xbf750000,0,0,0,0,0xbf750000,0,0,0,0,0xbf750000,0,0,0,0,0xbf750000,
0x3f5abede,0,0,0,0,0x3f5abede,0,0,0,0,0x3f5abede,0,0,0,0,0x3f5abede,
0x3f750000,0,0,0,0,0x3f750000,0,0,0,0,0x3f750000,0,0,0,0,0x3f750000,
0xbf723e19,0,0,0,0,0xbf723e19,0,0,0,0,0xbf723e19,0,0,0,0,0xbf723e19,
0xbf103f46,0,0,0,0,0xbf103f46,0,0,0,0,0xbf103f46,0,0,0,0,0xbf103f46,
0x3e19bf72,0,0,0,0,0x3e19bf72,0,0,0,0,0x3e19bf72,0,0,0,0,0x3e19bf72,
0x3f69be97,0,0,0,0,0x3f69be97,0,0,0,0,0x3f69be97,0,0,0,0,0x3f69be97,
0xbf5a3ede,0,0,0,0,0xbf5a3ede,0,0,0,0,0xbf5a3ede,0,0,0,0,0xbf5a3ede,
0x3e973f69,0,0,0,0,0x3e973f69,0,0,0,0,0x3e973f69,0,0,0,0,0x3e973f69,
0xbf2dbf2d,0,0,0,0,0xbf2dbf2d,0,0,0,0,0xbf2dbf2d,0,0,0,0,0xbf2dbf2d,
0x3f46bf10,0,0,0,0,0x3f46bf10,0,0,0,0,0x3f46bf10,0,0,0,0,0x3f46bf10,
0xbf2d3f2d,0,0,0,0,0xbf2d3f2d,0,0,0,0,0xbf2d3f2d,0,0,0,0,0xbf2d3f2d,
0x3f693e97,0,0,0,0,0x3f693e97,0,0,0,0,0x3f693e97,0,0,0,0,0x3f693e97,
0xbf723e19,0,0,0,0,0xbf723e19,0,0,0,0,0xbf723e19,0,0,0,0,0xbf723e19,
0x3f10bf46,0,0,0,0,0x3f10bf46,0,0,0,0,0x3f10bf46,0,0,0,0,0x3f10bf46,
0xbede3f5a,0,0,0,0,0xbede3f5a,0,0,0,0,0xbede3f5a,0,0,0,0,0xbede3f5a,
0x3f46bf10,0,0,0,0,0x3f46bf10,0,0,0,0,0x3f46bf10,0,0,0,0,0x3f46bf10,
0xbede3f5a,0,0,0,0,0xbede3f5a,0,0,0,0,0xbede3f5a,0,0,0,0,0xbede3f5a,
0x3e97bf69,0,0,0,0,0x3e97bf69,0,0,0,0,0x3e97bf69,0,0,0,0,0x3e97bf69,
0xbe193f72,0,0,0,0,0xbe193f72,0,0,0,0,0xbe193f72,0,0,0,0,0xbe193f72,
};
__device__ __align__(128) const uint32_t TAB_W[14336] = {
0x3f753f75,0,0x3f723f72,0xbe19be19,0x3f753f75,0,0x3f723f72,0xbe19be19,0x3f753f75,0,0x3f723f72,0xbe19be19,0x3f723f75,0xbe190000,0x3f693f69,0xbe97be97,
0x3f693f75,0xbe970000,0x3f2d3f5a,0xbf2dbede,0x3f103f46,0xbf46bf10,0x3e193ede,0xbf72bf5a,0x3e97,0xbf75bf69,0xbedebe19,0xbf5abf72,0x3f72be97,0xbe19bf69,0x3f463f69,0xbf10be97,
0x3f463f75,0xbf100000,0x3e193f2d,0xbf72bf2d,0xbe973e97,0xbf69bf69,0xbf5abede,0xbedebf5a,0xbf75bf46,0xbf10,0xbf2dbf72,0x3f2d3e19,0x3f72bf46,0xbe193f10,0x3f103f69,0xbf46be97,
0x3f103f75,0xbf460000,0xbede3ede,0xbf5abf5a,0xbf69be97,0xbe97bf69,0xbf2dbf72,0x3f2dbe19,0xbf46,0x3f753f10,0x3f5a3e19,0x3ede3f72,0x3f723f46,0xbe193f10,0x3e973f69,0xbf69be97,
0x3e973f75,0xbf690000,0xbf5a3e19,0xbedebf72,0xbf46bf46,0x3f10bf10,0x3edebf2d,0x3f5a3f2d,0x3f753e97,0x3f69,0x3e193f72,0xbf72be19,0x3f723e97,0xbe19bf69,0x3f69,0xbf75be97,
0x3f75,0xbf750000,0xbf72be19,0x3e19bf72,0xbf75,0x3f750000,0x3f723e19,0xbe193f72,0x3f75,0xbf750000,0xbf72be19,0x3e19bf72,0x3f72bf75,0xbe190000,0xbe973f69,0xbf69be97,
0xbe973f75,0xbf690000,0xbf2dbede,0x3f2dbf5a,0x3f46bf46,0x3f103f10,0x3e193f5a,0xbf723ede,0xbf753e97,0xbf69,0x3edebf72,0x3f5a3e19,0x3f723e97,0xbe193f69,0xbf103f69,0xbf46be97,
0xbf103f75,0xbf460000,0xbe19bf2d,0x3f72bf2d,0x3f69be97,0xbe973f69,0xbf5a3f5a,0xbedebede,0xbf46,0x3f75bf10,0x3f2d3e19,0xbf2d3f72,0x3f723f46,0xbe19bf10,0xbf463f69,0xbf10be97,
0xbf463f75,0xbf100000,0x3edebf5a,0x3f5abede,0x3e973e97,0xbf693f69,0xbf2d3e19,0x3f2dbf72,0x3f75bf46,0x3f10,0xbf5a3f72,0xbedebe19,0x3f72bf46,0xbe19bf10,0xbf693f69,0xbe97be97,
0xbf693f75,0xbe970000,0x3f5abf72,0x3edebe19,0xbf103f46,0xbf463f10,0x3edebf2d,0x3f5abf2d,0x3e97,0xbf753f69,0xbe19be19,0x3f72bf72,0x3f72be97,0xbe193f69,0xbf753f69,0xbe97,
0xbf753f75,0,0x3f72bf72,0xbe193e19,0xbf753f75,0,0x3f72bf72,0xbe193e19,0xbf753f75,0,0x3f72bf72,0xbe193e19,0x3f723f75,0xbe190000,0xbf693f69,0x3e97be97,
0xbf693f75,0x3e970000,0x3f2dbf5a,0xbf2d3ede,0xbf103f46,0x3f46bf10,0x3e19bede,0xbf723f5a,0x3e97,0x3f75bf69,0xbede3e19,0xbf5a3f72,0x3f72be97,0xbe19bf69,0xbf463f69,0x3f10be97,
0xbf463f75,0x3f100000,0x3e19bf2d,0xbf723f2d,0x3e973e97,0x3f69bf69,0xbf5a3ede,0xbede3f5a,0x3f75bf46,0xbf10,0xbf2d3f72,0x3f2dbe19,0x3f72bf46,0xbe193f10,0xbf103f69,0x3f46be97,
0xbf103f75,0x3f460000,0xbedebede,0xbf5a3f5a,0x3f69be97,0x3e97bf69,0xbf2d3f72,0x3f2d3e19,0xbf46,0xbf753f10,0x3f5abe19,0x3edebf72,0x3f723f46,0xbe193f10,0xbe973f69,0x3f69be97,
0xbe973f75,0x3f690000,0xbf5abe19,0xbede3f72,0x3f46bf46,0xbf10bf10,0x3ede3f2d,0x3f5abf2d,0xbf753e97,0x3f69,0x3e19bf72,0xbf723e19,0x3f723e97,0xbe19bf69,0x3f69,0x3f75be97,
0x3f75,0x3f750000,0xbf723e19,0x3e193f72,0xbf75,0xbf750000,0x3f72be19,0xbe19bf72,0x3f75,0x3f750000,0xbf723e19,0x3e193f72,0x3f72bf75,0xbe190000,0x3e973f69,0x3f69be97,
0x3e973f75,0x3f690000,0xbf2d3ede,0x3f2d3f5a,0xbf46bf46,0xbf103f10,0x3e19bf5a,0xbf72bede,0x3f753e97,0xbf69,0x3ede3f72,0x3f5abe19,0x3f723e97,0xbe193f69,0x3f103f69,0x3f46be97,
0x3f103f75,0x3f460000,0xbe193f2d,0x3f723f2d,0xbf69be97,0x3e973f69,0xbf5abf5a,0xbede3ede,0xbf46,0xbf75bf10,0x3f2dbe19,0xbf2dbf72,0x3f723f46,0xbe19bf10,0x3f463f69,0x3f10be97,
0x3f463f75,0x3f100000,0x3ede3f5a,0x3f5a3ede,0xbe973e97,0x3f693f69,0xbf2dbe19,0x3f2d3f72,0xbf75bf46,0x3f10,0xbf5abf72,0xbede3e19,0x3f72bf46,0xbe19bf10,0x3f693f69,0x3e97be97,
0x3f693f75,0x3e970000,0x3f5a3f72,0x3ede3e19,0x3f103f46,0x3f463f10,0x3ede3f2d,0x3f5a3f2d,0x3e97,0x3f753f69,0xbe193e19,0x3f723f72,0x3f72be97,0xbe193f69,0x3f753f69,0xbe97,
0x3f753f75,0,0x3f5a3f5a,0xbedebede,0x3f753f75,0,0x3f5a3f5a,0xbedebede,0x3f753f75,0,0x3f5a3f5a,0xbedebede,0x3f5a3f75,0xbede0000,0x3f103f10,0xbf46bf46,
0x3f693f75,0xbe970000,0x3ede3f2d,0xbf5abf2d,0x3f103f46,0xbf46bf10,0xbe193e19,0xbf72bf72,0x3e97,0xbf75bf69,0xbf2dbede,0xbf2dbf5a,0x3f5abe97,0xbedebf69,0x3e973f10,0xbf69bf46,
0x3f463f75,0xbf100000,0xbe193ede,0xbf72bf5a,0xbe973e97,0xbf69bf69,0xbf72bf2d,0xbe19bf2d,0xbf75bf46,0xbf10,0xbedebf5a,0x3f5a3ede,0x3f5abf46,0xbede3f10,0x3f10,0xbf75bf46,
0x3f103f75,0xbf460000,0xbf2d3e19,0xbf2dbf72,0xbf69be97,0xbe97bf69,0xbedebf72,0x3f5a3e19,0xbf46,0x3f753f10,0x3f723ede,0x3e193f5a,0x3f5a3f46,0xbede3f10,0xbe973f10,0xbf69bf46,
0x3e973f75,0xbf690000,0xbf72be19,0xbe19bf72,0xbf46bf46,0x3f10bf10,0x3f2dbede,0x3f2d3f5a,0x3f753e97,0x3f69,0xbe193f5a,0xbf72bede,0x3f5a3e97,0xbedebf69,0xbf103f10,0xbf46bf46,
0x3f75,0xbf750000,0xbf5abede,0x3edebf5a,0xbf75,0x3f750000,0x3f5a3ede,0xbede3f5a,0x3f75,0xbf750000,0xbf5abede,0x3edebf5a,0x3f5abf75,0xbede0000,0xbf463f10,0xbf10bf46,
0xbe973f75,0xbf690000,0xbedebf2d,0x3f5abf2d,0x3f46bf46,0x3f103f10,0xbe193f72,0xbf723e19,0xbf753e97,0xbf69,0x3f2dbf5a,0x3f2d3ede,0x3f5a3e97,0xbede3f69,0xbf693f10,0xbe97bf46,
0xbf103f75,0xbf460000,0x3e19bf5a,0x3f72bede,0x3f69be97,0xbe973f69,0xbf723f2d,0xbe19bf2d,0xbf46,0x3f75bf10,0x3ede3ede,0xbf5a3f5a,0x3f5a3f46,0xbedebf10,0xbf753f10,0xbf46,
0xbf463f75,0xbf100000,0x3f2dbf72,0x3f2dbe19,0x3e973e97,0xbf693f69,0xbedebe19,0x3f5abf72,0x3f75bf46,0x3f10,0xbf723f5a,0xbe19bede,0x3f5abf46,0xbedebf10,0xbf693f10,0x3e97bf46,
0xbf693f75,0xbe970000,0x3f72bf72,0x3e193e19,0xbf103f46,0xbf463f10,0x3f2dbf5a,0x3f2dbede,0x3e97,0xbf753f69,0x3e19bede,0x3f72bf5a,0x3f5abe97,0xbede3f69,0xbf463f10,0x3f10bf46,
0xbf753f75,0,0x3f5abf5a,0xbede3ede,0xbf753f75,0,0x3f5abf5a,0xbede3ede,0xbf753f75,0,0x3f5abf5a,0xbede3ede,0x3f5a3f75,0xbede0000,0xbf103f10,0x3f46bf46,
0xbf693f75,0x3e970000,0x3edebf2d,0xbf5a3f2d,0xbf103f46,0x3f46bf10,0xbe19be19,0xbf723f72,0x3e97,0x3f75bf69,0xbf2d3ede,0xbf2d3f5a,0x3f5abe97,0xbedebf69,0xbe973f10,0x3f69bf46,
0x3f693f69,0xbe97be97,0x3f5a3f5a,0xbedebede,0x3f693f69,0xbe97be97,0x3f5a3f5a,0xbedebede,0x3f5a3f69,0xbedebe97,0x3f463f46,0xbf10bf10,0x3f5a3f5a,0xbedebede,0x3f463f46,0xbf10bf10,
0x3e973f10,0xbf69bf46,0xbe193e19,0xbf72bf72,0xbe970000,0xbf69bf75,0xbf2dbede,0xbf2dbf5a,0x3f5abf10,0xbedebf46,0x3f103f46,0xbf46bf10,0x3ede3f2d,0xbf5abf2d,0x3e97,0xbf75bf69,
0xbf100000,0xbf46bf75,0xbf72bf2d,0xbe19bf2d,0xbf69bf69,0x3e97be97,0xbedebf5a,0x3f5a3ede,0x3f5abf10,0xbede3f46,0x3e973f46,0xbf69bf10,0xbe193ede,0xbf72bf5a,0xbf46be97,0xbf10bf69,
0xbf75bf10,0xbf46,0xbedebf72,0x3f5a3e19,0x3e97bf10,0x3f693f46,0x3f723ede,0x3e193f5a,0x3f5a3f69,0xbede3e97,0x3f46,0xbf75bf10,0xbf2d3e19,0xbf2dbf72,0xbf69bf46,0x3e97bf10,
0xbf10bf69,0x3f46be97,0x3f2dbede,0x3f2d3f5a,0x3f693f10,0xbe973f46,0xbe193f5a,0xbf72bede,0x3f5a0000,0xbedebf75,0xbe973f46,0xbf69bf10,0xbf72be19,0xbe19bf72,0xbe97bf75,0x3f690000,
0x3e97bf69,0x3f693e97,0x3f5a3ede,0xbede3f5a,0xbe973f69,0xbf69be97,0xbf5abede,0x3edebf5a,0x3f5abf69,0xbede3e97,0xbf103f46,0xbf46bf10,0xbf5abede,0x3edebf5a,0x3f10bf46,0x3f463f10,
0x3f69bf10,0x3e973f46,0xbe193f72,0xbf723e19,0xbf690000,0x3e97bf75,0x3f2dbf5a,0x3f2d3ede,0x3f5a3f10,0xbede3f46,0xbf463f46,0xbf10bf10,0xbedebf2d,0x3f5abf2d,0x3f75be97,0x3f69,
0x3f460000,0xbf103f75,0xbf723f2d,0xbe19bf2d,0x3e97bf69,0x3f69be97,0x3ede3ede,0xbf5a3f5a,0x3f5a3f10,0xbedebf46,0xbf693f46,0xbe97bf10,0x3e19bf5a,0x3f72bede,0x3f103e97,0xbf463f69,
0x3f10,0xbf753f46,0xbedebe19,0x3f5abf72,0x3f69bf10,0xbe973f46,0xbf723f5a,0xbe19bede,0x3f5abf69,0xbedebe97,0xbf753f46,0xbf10,0x3f2dbf72,0x3f2dbe19,0xbe973f46,0xbf693f10,
0xbf463f69,0xbf103e97,0x3f2dbf5a,0x3f2dbede,0xbe973f10,0xbf693f46,0x3e19bede,0x3f72bf5a,0x3f5a0000,0xbede3f75,0xbf693f46,0x3e97bf10,0x3f72bf72,0x3e193e19,0xbf693f75,0xbe970000,
0xbf693f69,0x3e97be97,0x3f5abf5a,0xbede3ede,0xbf693f69,0x3e97be97,0x3f5abf5a,0xbede3ede,0x3f5a3f69,0xbedebe97,0xbf463f46,0x3f10bf10,0x3f5abf5a,0xbede3ede,0xbf463f46,0x3f10bf10,
0xbe973f10,0x3f69bf46,0xbe19be19,0xbf723f72,0x3e970000,0x3f69bf75,0xbf2d3ede,0xbf2d3f5a,0x3f5abf10,0xbedebf46,0xbf103f46,0x3f46bf10,0x3edebf2d,0xbf5a3f2d,0x3e97,0x3f75bf69,
0x3f100000,0x3f46bf75,0xbf723f2d,0xbe193f2d,0x3f69bf69,0xbe97be97,0xbede3f5a,0x3f5abede,0x3f5abf10,0xbede3f46,0xbe973f46,0x3f69bf10,0xbe19bede,0xbf723f5a,0x3f46be97,0x3f10bf69,
0x3f75bf10,0xbf46,0xbede3f72,0x3f5abe19,0xbe97bf10,0xbf693f46,0x3f72bede,0x3e19bf5a,0x3f5a3f69,0xbede3e97,0x3f46,0x3f75bf10,0xbf2dbe19,0xbf2d3f72,0x3f69bf46,0xbe97bf10,
0x3f10bf69,0xbf46be97,0x3f2d3ede,0x3f2dbf5a,0xbf693f10,0x3e973f46,0xbe19bf5a,0xbf723ede,0x3f5a0000,0xbedebf75,0x3e973f46,0x3f69bf10,0xbf723e19,0xbe193f72,0x3e97bf75,0xbf690000,
0xbe97bf69,0xbf693e97,0x3f5abede,0xbedebf5a,0x3e973f69,0x3f69be97,0xbf5a3ede,0x3ede3f5a,0x3f5abf69,0xbede3e97,0x3f103f46,0x3f46bf10,0xbf5a3ede,0x3ede3f5a,0xbf10bf46,0xbf463f10,
0xbf69bf10,0xbe973f46,0xbe19bf72,0xbf72be19,0x3f690000,0xbe97bf75,0x3f2d3f5a,0x3f2dbede,0x3f5a3f10,0xbede3f46,0x3f463f46,0x3f10bf10,0xbede3f2d,0x3f5a3f2d,0xbf75be97,0x3f69,
0xbf460000,0x3f103f75,0xbf72bf2d,0xbe193f2d,0xbe97bf69,0xbf69be97,0x3edebede,0xbf5abf5a,0x3f5a3f10,0xbedebf46,0x3f693f46,0x3e97bf10,0x3e193f5a,0x3f723ede,0xbf103e97,0x3f463f69,
0x3f10,0x3f753f46,0xbede3e19,0x3f5a3f72,0xbf69bf10,0x3e973f46,0xbf72bf5a,0xbe193ede,0x3f5abf69,0xbedebe97,0x3f753f46,0xbf10,0x3f2d3f72,0x3f2d3e19,0x3e973f46,0x3f693f10,
0x3f463f69,0x3f103e97,0x3f2d3f5a,0x3f2d3ede,0x3e973f10,0x3f693f46,0x3e193ede,0x3f723f5a,0x3f5a0000,0xbede3f75,0x3f693f46,0xbe97bf10,0x3f723f72,0x3e19be19,0x3f693f75,0x3e970000,
0x3f103f10,0xbf46bf46,0x3e193e19,0xbf72bf72,0x3f103f10,0xbf46bf46,0x3e193e19,0xbf72bf72,0x3e193f10,0xbf72bf46,0xbe97be97,0xbf69bf69,0x3e193e19,0xbf72bf72,0xbe97be97,0xbf69bf69,
0xbe970000,0xbf69bf75,0xbf5abf2d,0xbedebf2d,0xbf46bf10,0xbf10bf46,0xbf72bf72,0x3e19be19,0x3e19bf69,0xbf72be97,0xbf10be97,0xbf46bf69,0xbedebe19,0xbf5abf72,0xbf69bf46,0xbe97bf10,
0xbf69bf10,0xbe97bf46,0xbf2dbf72,0x3f2d3e19,0xbf10bf69,0x3f463e97,0x3edebe19,0x3f5a3f72,0x3e190000,0xbf723f75,0xbf46be97,0xbf10bf69,0xbf5abede,0xbedebf5a,0xbf46bf75,0x3f100000,
0xbf46bf69,0x3f10be97,0x3edebede,0x3f5a3f5a,0x3f460000,0x3f103f75,0x3f2d3f72,0xbf2d3e19,0x3e193f69,0xbf72be97,0xbf69be97,0xbe97bf69,0xbf72bf2d,0x3e19bf2d,0xbf46,0x3f753f10,
0xbf69,0x3f753e97,0x3f723ede,0xbe193f5a,0x3f103f69,0xbf463e97,0xbf5a3e19,0xbedebf72,0x3e19bf10,0xbf72bf46,0xbf75be97,0xbf69,0xbf2dbf5a,0x3f2dbede,0x3f46be97,0x3f103f69,
0x3f46bf10,0x3f103f46,0x3e193f72,0xbf723e19,0xbf463f10,0xbf10bf46,0xbe19bf72,0x3f72be19,0x3e19bf10,0xbf723f46,0xbf69be97,0x3e97bf69,0xbe19bf72,0x3f72be19,0x3f693e97,0xbe973f69,
0x3f690000,0xbe973f75,0xbf5a3f2d,0xbedebf2d,0xbf10bf10,0x3f46bf46,0x3f72be19,0xbe193f72,0x3e193f69,0xbf723e97,0xbf46be97,0x3f10bf69,0x3edebf72,0x3f5a3e19,0x3e973f46,0xbf693f10,
0x3e973f10,0xbf693f46,0xbf2dbe19,0x3f2dbf72,0x3f46bf69,0x3f103e97,0xbede3f72,0xbf5a3e19,0x3e190000,0xbf72bf75,0xbf10be97,0x3f46bf69,0x3f5abf5a,0x3ede3ede,0xbf103f75,0xbf460000,
0xbf103f69,0xbf463e97,0x3edebf5a,0x3f5abede,0x3f100000,0xbf463f75,0xbf2d3e19,0x3f2dbf72,0x3e19bf69,0xbf723e97,0xbe97be97,0x3f69bf69,0x3f72bf2d,0xbe193f2d,0xbf753f46,0xbf10,
0xbf753f69,0xbe97,0x3f72bf5a,0xbe193ede,0xbf463f69,0xbf103e97,0x3f5abf72,0x3edebe19,0x3e193f10,0xbf723f46,0xbe97,0x3f75bf69,0x3f2dbede,0xbf2d3f5a,0xbf103e97,0x3f46bf69,
0xbf103f10,0x3f46bf46,0x3e19be19,0xbf723f72,0xbf103f10,0x3f46bf46,0x3e19be19,0xbf723f72,0x3e193f10,0xbf72bf46,0x3e97be97,0x3f69bf69,0x3e19be19,0xbf723f72,0x3e97be97,0x3f69bf69,
0x3e970000,0x3f69bf75,0xbf5a3f2d,0xbede3f2d,0x3f46bf10,0x3f10bf46,0xbf723f72,0x3e193e19,0x3e19bf69,0xbf72be97,0x3f10be97,0x3f46bf69,0xbede3e19,0xbf5a3f72,0x3f69bf46,0x3e97bf10,
0x3f463f46,0xbf10bf10,0x3f2d3f2d,0xbf2dbf2d,0x3f2d3f46,0xbf2dbf10,0x3f103f10,0xbf46bf46,0x3f2d3f2d,0xbf2dbf2d,0x3f103f10,0xbf46bf46,0x3f2d3f2d,0xbf2dbf2d,0x3f103f10,0xbf46bf46,
0xbf10be97,0xbf46bf69,0xbf5abf2d,0xbedebf2d,0x3f2dbf46,0xbf2dbf10,0x3e973f10,0xbf69bf46,0x3e193ede,0xbf72bf5a,0xbe970000,0xbf69bf75,0xbedebe19,0xbf5abf72,0xbf46bf10,0xbf10bf46,
0xbf46bf75,0x3f100000,0xbe19bf2d,0x3f723f2d,0x3f2dbe97,0xbf2d3f69,0x3f10,0xbf75bf46,0xbede3e19,0xbf5abf72,0xbf69bf10,0xbe97bf46,0xbf72bf5a,0x3e19bede,0xbf10bf69,0x3f463e97,
0x3f10be97,0x3f463f69,0x3f723f2d,0xbe193f2d,0x3f2d3f75,0xbf2d0000,0xbe973f10,0xbf69bf46,0xbf5abe19,0xbedebf72,0xbf46bf69,0x3f10be97,0xbe19bf5a,0x3f723ede,0x3f460000,0x3f103f75,
0x3f463f46,0xbf103f10,0xbede3f2d,0xbf5abf2d,0x3f2dbe97,0xbf2dbf69,0xbf103f10,0xbf46bf46,0xbf72bede,0x3e19bf5a,0xbf69,0x3f753e97,0x3f5abe19,0x3ede3f72,0x3f103f69,0xbf463e97,
0xbf103f46,0xbf46bf10,0xbf2dbf2d,0x3f2dbf2d,0x3f2dbf46,0xbf2d3f10,0xbf463f10,0xbf10bf46,0xbf2dbf2d,0x3f2dbf2d,0x3f46bf10,0x3f103f46,0x3f2d3f2d,0xbf2d3f2d,0xbf463f10,0xbf10bf46,
0xbf46be97,0x3f10bf69,0x3f5abf2d,0x3ede3f2d,0x3f2d3f46,0xbf2d3f10,0xbf693f10,0xbe97bf46,0xbe19bf5a,0x3f72bede,0x3f690000,0xbe973f75,0xbede3f72,0xbf5abe19,0xbf10bf10,0x3f46bf46,
0x3f10bf75,0x3f460000,0x3e193f2d,0xbf723f2d,0x3f2d3e97,0xbf2dbf69,0xbf753f10,0xbf46,0x3edebf72,0x3f5abe19,0x3e973f10,0xbf693f46,0xbf723ede,0x3e19bf5a,0x3f46bf69,0x3f103e97,
0x3f46be97,0xbf103f69,0xbf723f2d,0x3e19bf2d,0x3f2dbf75,0xbf2d0000,0xbf693f10,0x3e97bf46,0x3f5abf72,0x3ede3e19,0xbf103f69,0xbf463e97,0xbe19bede,0x3f72bf5a,0x3f100000,0xbf463f75,
0xbf103f46,0xbf463f10,0x3edebf2d,0x3f5abf2d,0x3f2d3e97,0xbf2d3f69,0xbf463f10,0x3f10bf46,0x3f72bf5a,0xbe193ede,0xbf753f69,0xbe97,0x3f5abf72,0x3edebe19,0xbf463f69,0xbf103e97,
0xbf463f46,0x3f10bf10,0x3f2dbf2d,0xbf2d3f2d,0x3f2d3f46,0xbf2dbf10,0xbf103f10,0x3f46bf46,0x3f2dbf2d,0xbf2d3f2d,0xbf103f10,0x3f46bf46,0x3f2dbf2d,0xbf2d3f2d,0xbf103f10,0x3f46bf46,
0x3f10be97,0x3f46bf69,0xbf5a3f2d,0xbede3f2d,0x3f2dbf46,0xbf2dbf10,0xbe973f10,0x3f69bf46,0x3e19bede,0xbf723f5a,0x3e970000,0x3f69bf75,0xbede3e19,0xbf5a3f72,0x3f46bf10,0x3f10bf46,
0x3f46bf75,0xbf100000,0xbe193f2d,0x3f72bf2d,0x3f2dbe97,0xbf2d3f69,0x3f10,0x3f75bf46,0xbedebe19,0xbf5a3f72,0x3f69bf10,0x3e97bf46,0xbf723f5a,0x3e193ede,0x3f10bf69,0xbf463e97,
0xbf10be97,0xbf463f69,0x3f72bf2d,0xbe19bf2d,0x3f2d3f75,0xbf2d0000,0x3e973f10,0x3f69bf46,0xbf5a3e19,0xbede3f72,0x3f46bf69,0xbf10be97,0xbe193f5a,0x3f72bede,0xbf460000,0xbf103f75,
0xbf463f46,0x3f103f10,0xbedebf2d,0xbf5a3f2d,0x3f2dbe97,0xbf2dbf69,0x3f103f10,0x3f46bf46,0xbf723ede,0x3e193f5a,0xbf69,0xbf753e97,0x3f5a3e19,0x3edebf72,0xbf103f69,0x3f463e97,
0x3f103f46,0x3f46bf10,0xbf2d3f2d,0x3f2d3f2d,0x3f2dbf46,0xbf2d3f10,0x3f463f10,0x3f10bf46,0xbf2d3f2d,0x3f2d3f2d,0xbf46bf10,0xbf103f46,0x3f2dbf2d,0xbf2dbf2d,0x3f463f10,0x3f10bf46,
0x3f46be97,0xbf10bf69,0x3f5a3f2d,0x3edebf2d,0x3f2d3f46,0xbf2d3f10,0x3f693f10,0x3e97bf46,0xbe193f5a,0x3f723ede,0xbf690000,0x3e973f75,0xbedebf72,0xbf5a3e19,0x3f10bf10,0xbf46bf46,
0xbf10bf75,0xbf460000,0x3e19bf2d,0xbf72bf2d,0x3f2d3e97,0xbf2dbf69,0x3f753f10,0xbf46,0x3ede3f72,0x3f5a3e19,0xbe973f10,0x3f693f46,0xbf72bede,0x3e193f5a,0xbf46bf69,0xbf103e97,
0xbf46be97,0x3f103f69,0xbf72bf2d,0x3e193f2d,0x3f2dbf75,0xbf2d0000,0x3f693f10,0xbe97bf46,0x3f5a3f72,0x3edebe19,0x3f103f69,0x3f463e97,0xbe193ede,0x3f723f5a,0xbf100000,0x3f463f75,
0x3f103f46,0x3f463f10,0x3ede3f2d,0x3f5a3f2d,0x3f2d3e97,0xbf2d3f69,0x3f463f10,0xbf10bf46,0x3f723f5a,0xbe19bede,0x3f753f69,0xbe97,0x3f5a3f72,0x3ede3e19,0x3f463f69,0x3f103e97,
0xbe97be97,0xbf69bf69,0xbf2dbf2d,0xbf2dbf2d,0xbf2dbe97,0xbf2dbf69,0xbf69bf69,0xbe97be97,0xbf2dbf2d,0xbf2dbf2d,0xbf69bf69,0xbe97be97,0xbf2dbf2d,0xbf2dbf2d,0xbf69bf69,0xbe97be97,
0xbf69bf75,0x3e970000,0xbedebf2d,0x3f5a3f2d,0xbf2dbf46,0xbf2d3f10,0xbf75bf69,0xbe97,0xbf72bf5a,0xbe19bede,0xbf46bf69,0x3f103e97,0xbf5abf72,0x3ede3e19,0xbe97bf10,0x3f693f46,
0x3e97be97,0x3f693f69,0x3f723f2d,0x3e193f2d,0xbf2d3f46,0xbf2d3f10,0xbf69bf69,0x3e97be97,0xbf5abf72,0x3edebe19,0xbf10,0x3f753f46,0x3e19bede,0x3f723f5a,0x3f693f10,0x3e973f46,
0x3f693f46,0xbe973f10,0xbe193f2d,0xbf72bf2d,0xbf2d3e97,0xbf2dbf69,0xbf46bf69,0x3f10be97,0xbedebf72,0x3f5a3e19,0x3f460000,0x3f103f75,0x3f723ede,0x3e193f5a,0x3e973f69,0xbf69be97,
0xbe973f46,0xbf69bf10,0xbf5abf2d,0x3edebf2d,0xbf2dbf75,0xbf2d0000,0xbf10bf69,0x3f46be97,0x3e19bf5a,0x3f723ede,0x3f693f10,0xbe973f46,0x3ede3f72,0xbf5a3e19,0xbf690000,0xbe97bf75,
0xbf69be97,0x3e97bf69,0x3f2dbf2d,0x3f2d3f2d,0xbf2d3e97,0xbf2d3f69,0xbe97bf69,0x3f69be97,0x3f2dbf2d,0x3f2d3f2d,0x3e973f69,0xbf693e97,0xbf2d3f2d,0xbf2dbf2d,0xbe97bf69,0x3f69be97,
0x3e97bf75,0x3f690000,0x3ede3f2d,0xbf5a3f2d,0xbf2d3f46,0xbf2dbf10,0xbf69,0x3f75be97,0x3f72bede,0x3e193f5a,0xbf103f69,0xbf46be97,0xbf5abe19,0x3edebf72,0x3f69bf10,0x3e973f46,
0x3f69be97,0xbe973f69,0xbf723f2d,0xbe19bf2d,0xbf2dbf46,0xbf2dbf10,0x3e97bf69,0x3f69be97,0x3f5abe19,0xbede3f72,0xbf753f10,0xbf46,0x3e19bf5a,0x3f72bede,0x3e973f10,0xbf693f46,
0xbe973f46,0xbf693f10,0x3e19bf2d,0x3f72bf2d,0xbf2dbe97,0xbf2d3f69,0x3f10bf69,0x3f46be97,0x3ede3e19,0xbf5a3f72,0xbf100000,0x3f46bf75,0x3f72bf5a,0x3e193ede,0xbf693f69,0xbe97be97,
0xbf693f46,0x3e97bf10,0x3f5abf2d,0xbede3f2d,0xbf2d3f75,0xbf2d0000,0x3f46bf69,0x3f10be97,0xbe193ede,0xbf723f5a,0x3e97bf10,0x3f69bf46,0x3edebe19,0xbf5a3f72,0xbe970000,0x3f69bf75,
0x3e97be97,0x3f69bf69,0xbf2d3f2d,0xbf2d3f2d,0xbf2dbe97,0xbf2dbf69,0x3f69bf69,0x3e97be97,0xbf2d3f2d,0xbf2d3f2d,0x3f69bf69,0x3e97be97,0xbf2d3f2d,0xbf2d3f2d,0x3f69bf69,0x3e97be97,
0x3f69bf75,0xbe970000,0xbede3f2d,0x3f5abf2d,0xbf2dbf46,0xbf2d3f10,0x3f75bf69,0xbe97,0xbf723f5a,0xbe193ede,0x3f46bf69,0xbf103e97,0xbf5a3f72,0x3edebe19,0x3e97bf10,0xbf693f46,
0,0,0x3f10,0xbf46,0,0,0,0,0,0,0,0,0,0,0,0,
0,0,0xbf69,0xbe97,0,0,0,0,0,0,0,0,0,0,0,0,
0,0,0,0x3f75,0,0,0,0,0,0,0,0,0,0,0,0,
0,0,0x3f69,0xbe97,0,0,0,0,0,0,0,0,0,0,0,0,
0,0,0xbf10,0xbf46,0,0,0,0,0,0,0,0,0,0,0,0,
0,0,0xbf10,0x3f46,0,0,0,0,0,0,0,0,0,0,0,0,
0,0,0x3f69,0x3e97,0,0,0,0,0,0,0,0,0,0,0,0,
0,0,0,0xbf75,0,0,0,0,0,0,0,0,0,0,0,0,
0,0,0xbf69,0x3e97,0,0,0,0,0,0,0,0,0,0,0,0,
0,0,0x3f10,0x3f46,0,0,0,0,0,0,0,0,0,0,0,0,
0,0,0x3f10,0xbf46,0,0,0,0,0,0,0,0,0,0,0,0,
0,0,0xbf69,0xbe97,0,0,0,0,0,0,0,0,0,0,0,0,
0,0,0,0x3f75,0,0,0,0,0,0,0,0,0,0,0,0,
0,0,0x3f69,0xbe97,0,0,0,0,0,0,0,0,0,0,0,0,
0,0,0xbf10,0xbf46,0,0,0,0,0,0,0,0,0,0,0,0,
0,0,0xbf10,0x3f46,0,0,0,0,0,0,0,0,0,0,0,0,
0,0,0x3f69,0x3e97,0,0,0,0,0,0,0,0,0,0,0,0,
0,0,0,0xbf75,0,0,0,0,0,0,0,0,0,0,0,0,
0,0,0xbf69,0x3e97,0,0,0,0,0,0,0,0,0,0,0,0,
0,0,0x3f10,0x3f46,0,0,0,0,0,0,0,0,0,0,0,0,
0,0,0xbf69,0xbe97,0,0,0,0,0,0,0,0,0,0,0,0,
0,0,0,0x3f75,0,0,0,0,0,0,0,0,0,0,0,0,
0,0,0x3f69,0xbe97,0,0,0,0,0,0,0,0,0,0,0,0,
0,0,0xbf10,0xbf46,0,0,0,0,0,0,0,0,0,0,0,0,
0,0,0xbf10,0x3f46,0,0,0,0,0,0,0,0,0,0,0,0,
0,0,0x3f69,0x3e97,0,0,0,0,0,0,0,0,0,0,0,0,
0,0,0,0xbf75,0,0,0,0,0,0,0,0,0,0,0,0,
0,0,0xbf69,0x3e97,0,0,0,0,0,0,0,0,0,0,0,0,
0,0,0x3f10,0x3f46,0,0,0,0,0,0,0,0,0,0,0,0,
0,0,0x3f10,0xbf46,0,0,0,0,0,0,0,0,0,0,0,0,
0,0,0xbf69,0xbe97,0,0,0,0,0,0,0,0,0,0,0,0,
0,0,0,0x3f75,0,0,0,0,0,0,0,0,0,0,0,0,
0xbf463f75,0x3f100000,0xbe19bede,0xbf723f5a,0x3e973e97,0x3f69bf69,0xbf723f2d,0xbe193f2d,0x3f75bf46,0xbf10,0xbede3f5a,0x3f5abede,0x3f5abf46,0xbede3f10,0x3f10,0x3f75bf46,
0xbf103f75,0x3f460000,0xbf2dbe19,0xbf2d3f72,0x3f69be97,0x3e97bf69,0xbede3f72,0x3f5abe19,0xbf46,0xbf753f10,0x3f72bede,0x3e19bf5a,0x3f5a3f46,0xbede3f10,0x3e973f10,0x3f69bf46,
0xbe973f75,0x3f690000,0xbf723e19,0xbe193f72,0x3f46bf46,0xbf10bf10,0x3f2d3ede,0x3f2dbf5a,0xbf753e97,0x3f69,0xbe19bf5a,0xbf723ede,0x3f5a3e97,0xbedebf69,0x3f103f10,0x3f46bf46,
0x3f75,0x3f750000,0xbf5a3ede,0x3ede3f5a,0xbf75,0xbf750000,0x3f5abede,0xbedebf5a,0x3f75,0x3f750000,0xbf5a3ede,0x3ede3f5a,0x3f5abf75,0xbede0000,0x3f463f10,0x3f10bf46,
0x3e973f75,0x3f690000,0xbede3f2d,0x3f5a3f2d,0xbf46bf46,0xbf103f10,0xbe19bf72,0xbf72be19,0x3f753e97,0xbf69,0x3f2d3f5a,0x3f2dbede,0x3f5a3e97,0xbede3f69,0x3f693f10,0x3e97bf46,
0x3f103f75,0x3f460000,0x3e193f5a,0x3f723ede,0xbf69be97,0x3e973f69,0xbf72bf2d,0xbe193f2d,0xbf46,0xbf75bf10,0x3edebede,0xbf5abf5a,0x3f5a3f46,0xbedebf10,0x3f753f10,0xbf46,
0x3f463f75,0x3f100000,0x3f2d3f72,0x3f2d3e19,0xbe973e97,0x3f693f69,0xbede3e19,0x3f5a3f72,0xbf75bf46,0x3f10,0xbf72bf5a,0xbe193ede,0x3f5abf46,0xbedebf10,0x3f693f10,0xbe97bf46,
0x3f693f75,0x3e970000,0x3f723f72,0x3e19be19,0x3f103f46,0x3f463f10,0x3f2d3f5a,0x3f2d3ede,0x3e97,0x3f753f69,0x3e193ede,0x3f723f5a,0x3f5abe97,0xbede3f69,0x3f463f10,0xbf10bf46,
0x3f753f75,0,0x3f2d3f2d,0xbf2dbf2d,0x3f753f75,0,0x3f2d3f2d,0xbf2dbf2d,0x3f753f75,0,0x3f2d3f2d,0xbf2dbf2d,0x3f2d3f75,0xbf2d0000,0,0xbf75bf75,
0x3f693f75,0xbe970000,0x3e193ede,0xbf72bf5a,0x3f103f46,0xbf46bf10,0xbedebe19,0xbf5abf72,0x3e97,0xbf75bf69,0xbf5abf2d,0xbedebf2d,0x3f2dbe97,0xbf2dbf69,0xbe970000,0xbf69bf75,
0x3f463f75,0xbf100000,0xbede3e19,0xbf5abf72,0xbe973e97,0xbf69bf69,0xbf72bf5a,0x3e19bede,0xbf75bf46,0xbf10,0xbe19bf2d,0x3f723f2d,0x3f2dbf46,0xbf2d3f10,0xbf100000,0xbf46bf75,
0x3f103f75,0xbf460000,0xbf5abe19,0xbedebf72,0xbf69be97,0xbe97bf69,0xbe19bf5a,0x3f723ede,0xbf46,0x3f753f10,0x3f723f2d,0xbe193f2d,0x3f2d3f46,0xbf2d3f10,0xbf460000,0xbf10bf75,
0x3e973f75,0xbf690000,0xbf72bede,0x3e19bf5a,0xbf46bf46,0x3f10bf10,0x3f5abe19,0x3ede3f72,0x3f753e97,0x3f69,0xbede3f2d,0xbf5abf2d,0x3f2d3e97,0xbf2dbf69,0xbf690000,0xbe97bf75,
0x3f75,0xbf750000,0xbf2dbf2d,0x3f2dbf2d,0xbf75,0x3f750000,0x3f2d3f2d,0xbf2d3f2d,0x3f75,0xbf750000,0xbf2dbf2d,0x3f2dbf2d,0x3f2dbf75,0xbf2d0000,0xbf750000,0xbf75,
0xbe973f75,0xbf690000,0xbe19bf5a,0x3f72bede,0x3f46bf46,0x3f103f10,0xbede3f72,0xbf5abe19,0xbf753e97,0xbf69,0x3f5abf2d,0x3ede3f2d,0x3f2d3e97,0xbf2d3f69,0xbf690000,0x3e97bf75,
0xbf103f75,0xbf460000,0x3edebf72,0x3f5abe19,0x3f69be97,0xbe973f69,0xbf723ede,0x3e19bf5a,0xbf46,0x3f75bf10,0x3e193f2d,0xbf723f2d,0x3f2d3f46,0xbf2dbf10,0xbf460000,0x3f10bf75,
0xbf463f75,0xbf100000,0x3f5abf72,0x3ede3e19,0x3e973e97,0xbf693f69,0xbe19bede,0x3f72bf5a,0x3f75bf46,0x3f10,0xbf723f2d,0x3e19bf2d,0x3f2dbf46,0xbf2dbf10,0xbf100000,0x3f46bf75,
0xbf693f75,0xbe970000,0x3f72bf5a,0xbe193ede,0xbf103f46,0xbf463f10,0x3f5abf72,0x3edebe19,0x3e97,0xbf753f69,0x3edebf2d,0x3f5abf2d,0x3f2dbe97,0xbf2d3f69,0xbe970000,0x3f69bf75,
0xbf753f75,0,0x3f2dbf2d,0xbf2d3f2d,0xbf753f75,0,0x3f2dbf2d,0xbf2d3f2d,0xbf753f75,0,0x3f2dbf2d,0xbf2d3f2d,0x3f2d3f75,0xbf2d0000,0,0x3f75bf75,
0xbf693f75,0x3e970000,0x3e19bede,0xbf723f5a,0xbf103f46,0x3f46bf10,0xbede3e19,0xbf5a3f72,0x3e97,0x3f75bf69,0xbf5a3f2d,0xbede3f2d,0x3f2dbe97,0xbf2dbf69,0x3e970000,0x3f69bf75,
0xbf463f75,0x3f100000,0xbedebe19,0xbf5a3f72,0x3e973e97,0x3f69bf69,0xbf723f5a,0x3e193ede,0x3f75bf46,0xbf10,0xbe193f2d,0x3f72bf2d,0x3f2dbf46,0xbf2d3f10,0x3f100000,0x3f46bf75,
0xbf103f75,0x3f460000,0xbf5a3e19,0xbede3f72,0x3f69be97,0x3e97bf69,0xbe193f5a,0x3f72bede,0xbf46,0xbf753f10,0x3f72bf2d,0xbe19bf2d,0x3f2d3f46,0xbf2d3f10,0x3f460000,0x3f10bf75,
0xbe973f75,0x3f690000,0xbf723ede,0x3e193f5a,0x3f46bf46,0xbf10bf10,0x3f5a3e19,0x3edebf72,0xbf753e97,0x3f69,0xbedebf2d,0xbf5a3f2d,0x3f2d3e97,0xbf2dbf69,0x3f690000,0x3e97bf75,
0x3f75,0x3f750000,0xbf2d3f2d,0x3f2d3f2d,0xbf75,0xbf750000,0x3f2dbf2d,0xbf2dbf2d,0x3f75,0x3f750000,0xbf2d3f2d,0x3f2d3f2d,0x3f2dbf75,0xbf2d0000,0x3f750000,0xbf75,
0x3e973f75,0x3f690000,0xbe193f5a,0x3f723ede,0xbf46bf46,0xbf103f10,0xbedebf72,0xbf5a3e19,0x3f753e97,0xbf69,0x3f5a3f2d,0x3edebf2d,0x3f2d3e97,0xbf2d3f69,0x3f690000,0xbe97bf75,
0x3f103f75,0x3f460000,0x3ede3f72,0x3f5a3e19,0xbf69be97,0x3e973f69,0xbf72bede,0x3e193f5a,0xbf46,0xbf75bf10,0x3e19bf2d,0xbf72bf2d,0x3f2d3f46,0xbf2dbf10,0x3f460000,0xbf10bf75,
0x3f463f75,0x3f100000,0x3f5a3f72,0x3edebe19,0xbe973e97,0x3f693f69,0xbe193ede,0x3f723f5a,0xbf75bf46,0x3f10,0xbf72bf2d,0x3e193f2d,0x3f2dbf46,0xbf2dbf10,0x3f100000,0xbf46bf75,
0x3f693f75,0x3e970000,0x3f723f5a,0xbe19bede,0x3f103f46,0x3f463f10,0x3f5a3f72,0x3ede3e19,0x3e97,0x3f753f69,0x3ede3f2d,0x3f5a3f2d,0x3f2dbe97,0xbf2d3f69,0x3e970000,0xbf69bf75,
0x3f753f75,0,0x3ede3ede,0xbf5abf5a,0x3f753f75,0,0x3ede3ede,0xbf5abf5a,0x3f753f75,0,0x3ede3ede,0xbf5abf5a,0x3ede3f75,0xbf5a0000,0xbf10bf10,0xbf46bf46,
0x3f693f75,0xbe970000,0xbe193e19,0xbf72bf72,0x3f103f46,0xbf46bf10,0xbf2dbede,0xbf2dbf5a,0x3e97,0xbf75bf69,0xbf72bf5a,0xbe19bede,0x3edebe97,0xbf5abf69,0xbf46bf10,0xbf10bf46,
0x3f463f75,0xbf100000,0xbf2dbe19,0xbf2dbf72,0xbe973e97,0xbf69bf69,0xbf5abf72,0x3edebe19,0xbf75bf46,0xbf10,0x3e19bede,0x3f723f5a,0x3edebf46,0xbf5a3f10,0xbf69bf10,0xbe97bf46,
0x3f103f75,0xbf460000,0xbf72bede,0xbe19bf5a,0xbf69be97,0xbe97bf69,0x3e19bf2d,0x3f723f2d,0xbf46,0x3f753f10,0x3f5a3f5a,0xbede3ede,0x3ede3f46,0xbf5a3f10,0xbf75bf10,0xbf46,
0x3f69bf10,0x3e97bf46,0xbf2d3f72,0x3f2dbe19,0x3f10bf69,0xbf463e97,0x3ede3e19,0x3f5abf72,0x3e190000,0xbf723f75,0x3f46be97,0x3f10bf69,0xbf5a3ede,0xbede3f5a,0x3f46bf75,0xbf100000,
0x3f46bf69,0xbf10be97,0x3ede3ede,0x3f5abf5a,0xbf460000,0xbf103f75,0x3f2dbf72,0xbf2dbe19,0x3e193f69,0xbf72be97,0x3f69be97,0x3e97bf69,0xbf723f2d,0x3e193f2d,0xbf46,0xbf753f10,
0xbf69,0xbf753e97,0x3f72bede,0xbe19bf5a,0xbf103f69,0x3f463e97,0xbf5abe19,0xbede3f72,0x3e19bf10,0xbf72bf46,0x3f75be97,0xbf69,0xbf2d3f5a,0x3f2d3ede,0xbf46be97,0xbf103f69,
0xbf46bf10,0xbf103f46,0x3e19bf72,0xbf72be19,0x3f463f10,0x3f10bf46,0xbe193f72,0x3f723e19,0x3e19bf10,0xbf723f46,0x3f69be97,0xbe97bf69,0xbe193f72,0x3f723e19,0xbf693e97,0x3e973f69,
0xbf690000,0x3e973f75,0xbf5abf2d,0xbede3f2d,0x3f10bf10,0xbf46bf46,0x3f723e19,0xbe19bf72,0x3e193f69,0xbf723e97,0x3f46be97,0xbf10bf69,0x3ede3f72,0x3f5abe19,0xbe973f46,0x3f693f10,
0xbe973f10,0x3f693f46,0xbf2d3e19,0x3f2d3f72,0xbf46bf69,0xbf103e97,0xbedebf72,0xbf5abe19,0x3e190000,0xbf72bf75,0x3f10be97,0xbf46bf69,0x3f5a3f5a,0x3edebede,0x3f103f75,0x3f460000,
0x3f103f69,0x3f463e97,0x3ede3f5a,0x3f5a3ede,0xbf100000,0x3f463f75,0xbf2dbe19,0x3f2d3f72,0x3e19bf69,0xbf723e97,0x3e97be97,0xbf69bf69,0x3f723f2d,0xbe19bf2d,0x3f753f46,0xbf10,
0x3f753f69,0xbe97,0x3f723f5a,0xbe19bede,0x3f463f69,0x3f103e97,0x3f5a3f72,0x3ede3e19,0x3e193f10,0xbf723f46,0xbe97,0xbf75bf69,0x3f2d3ede,0xbf2dbf5a,0x3f103e97,0xbf46bf69,
0,0xbf75bf75,0xbf2dbf2d,0xbf2dbf2d,0,0xbf75bf75,0xbf2dbf2d,0xbf2dbf2d,0xbf2d0000,0xbf2dbf75,0xbf75bf75,0,0xbf2dbf2d,0xbf2dbf2d,0xbf75bf75,0,
0xbf46bf10,0xbf10bf46,0xbf5abf72,0x3ede3e19,0xbf75bf69,0xbe97,0xbedebf2d,0x3f5a3f2d,0xbf2dbf69,0xbf2d3e97,0xbf69bf75,0x3e970000,0xbf72bf5a,0xbe19bede,0xbf10bf46,0x3f463f10,
0xbf69bf69,0x3e97be97,0x3e19bede,0x3f723f5a,0xbf10,0x3f753f46,0x3f723f2d,0x3e193f2d,0xbf2d3f10,0xbf2d3f46,0xbf46bf75,0x3f100000,0xbf5abf72,0x3edebe19,0x3e97be97,0x3f693f69,
0xbe97bf69,0x3f693e97,0x3f723ede,0x3e193f5a,0x3f753f10,0x3f46,0xbe193f2d,0xbf72bf2d,0xbf2d3f10,0xbf2dbf46,0xbf10bf75,0x3f460000,0xbedebf72,0x3f5a3e19,0x3f693e97,0x3e973f69,
0x3f10bf10,0x3f463f46,0x3ede3f72,0xbf5a3e19,0x3f69,0xbf75be97,0xbf5abf2d,0x3edebf2d,0xbf2dbf69,0xbf2dbe97,0xbe97bf75,0x3f690000,0x3e19bf5a,0x3f723ede,0x3f463f46,0xbf103f10,
0x3f750000,0x3f75,0xbf2d3f2d,0xbf2dbf2d,0xbf750000,0xbf75,0x3f2dbf2d,0x3f2d3f2d,0xbf2d0000,0xbf2d3f75,0xbf75,0x3f750000,0x3f2dbf2d,0x3f2d3f2d,0x3f75,0xbf750000,
0x3f103f10,0xbf463f46,0xbf5abe19,0x3edebf72,0xbf69,0x3f75be97,0x3ede3f2d,0xbf5a3f2d,0xbf2d3f69,0xbf2dbe97,0x3e97bf75,0x3f690000,0x3f72bede,0x3e193f5a,0xbf463f46,0xbf10bf10,
0xbe973f69,0xbf693e97,0x3e19bf5a,0x3f72bede,0x3f75bf10,0x3f46,0xbf723f2d,0xbe19bf2d,0xbf2dbf10,0xbf2dbf46,0x3f10bf75,0x3f460000,0x3f5abe19,0xbede3f72,0xbf693e97,0x3e97bf69,
0xbf693f69,0xbe97be97,0x3f72bf5a,0x3e193ede,0x3f10,0xbf753f46,0x3e19bf2d,0x3f72bf2d,0xbf2dbf10,0xbf2d3f46,0x3f46bf75,0x3f100000,0x3ede3e19,0xbf5a3f72,0xbe97be97,0x3f69bf69,
0xbf463f10,0x3f10bf46,0x3edebe19,0xbf5a3f72,0xbf753f69,0xbe97,0x3f5abf2d,0xbede3f2d,0xbf2d3f69,0xbf2d3e97,0x3f69bf75,0x3e970000,0xbe193ede,0xbf723f5a,0x3f10bf46,0x3f46bf10,
0,0x3f75bf75,0xbf2d3f2d,0xbf2d3f2d,0,0x3f75bf75,0xbf2d3f2d,0xbf2d3f2d,0xbf2d0000,0xbf2dbf75,0x3f75bf75,0,0xbf2d3f2d,0xbf2d3f2d,0x3f75bf75,0,
0x3f46bf10,0x3f10bf46,0xbf5a3f72,0x3edebe19,0x3f75bf69,0xbe97,0xbede3f2d,0x3f5abf2d,0xbf2dbf69,0xbf2d3e97,0x3f69bf75,0xbe970000,0xbf723f5a,0xbe193ede,0x3f10bf46,0xbf463f10,
0x3f69bf69,0xbe97be97,0x3e193ede,0x3f72bf5a,0xbf10,0xbf753f46,0x3f72bf2d,0x3e19bf2d,0xbf2d3f10,0xbf2d3f46,0x3f46bf75,0xbf100000,0xbf5a3f72,0x3ede3e19,0xbe97be97,0xbf693f69,
0x3e97bf69,0xbf693e97,0x3f72bede,0x3e19bf5a,0xbf753f10,0x3f46,0xbe19bf2d,0xbf723f2d,0xbf2d3f10,0xbf2dbf46,0x3f10bf75,0xbf460000,0xbede3f72,0x3f5abe19,0xbf693e97,0xbe973f69,
0xbf10bf10,0xbf463f46,0x3edebf72,0xbf5abe19,0x3f69,0x3f75be97,0xbf5a3f2d,0x3ede3f2d,0xbf2dbf69,0xbf2dbe97,0x3e97bf75,0xbf690000,0x3e193f5a,0x3f72bede,0xbf463f46,0x3f103f10,
0xbf750000,0x3f75,0xbf2dbf2d,0xbf2d3f2d,0x3f750000,0xbf75,0x3f2d3f2d,0x3f2dbf2d,0xbf2d0000,0xbf2d3f75,0xbf75,0xbf750000,0x3f2d3f2d,0x3f2dbf2d,0x3f75,0x3f750000,
0xbf103f10,0x3f463f46,0xbf5a3e19,0x3ede3f72,0xbf69,0xbf75be97,0x3edebf2d,0xbf5abf2d,0xbf2d3f69,0xbf2dbe97,0xbe97bf75,0xbf690000,0x3f723ede,0x3e19bf5a,0x3f463f46,0x3f10bf10,
0x3e973f69,0x3f693e97,0x3e193f5a,0x3f723ede,0xbf75bf10,0x3f46,0xbf72bf2d,0xbe193f2d,0xbf2dbf10,0xbf2dbf46,0xbf10bf75,0xbf460000,0x3f5a3e19,0xbedebf72,0x3f693e97,0xbe97bf69,
0x3f693f69,0x3e97be97,0x3f723f5a,0x3e19bede,0x3f10,0x3f753f46,0x3e193f2d,0x3f723f2d,0xbf2dbf10,0xbf2d3f46,0xbf46bf75,0xbf100000,0x3edebe19,0xbf5abf72,0x3e97be97,0xbf69bf69,
0x3f463f10,0xbf10bf46,0x3ede3e19,0xbf5abf72,0x3f753f69,0xbe97,0x3f5a3f2d,0xbedebf2d,0xbf2d3f69,0xbf2d3e97,0xbf69bf75,0xbe970000,0xbe19bede,0xbf72bf5a,0xbf10bf46,0xbf46bf10,
0xbf10bf10,0xbf46bf46,0xbf72bf72,0x3e193e19,0xbf10bf10,0xbf46bf46,0xbf72bf72,0x3e193e19,0xbf72bf10,0x3e19bf46,0xbe97be97,0x3f693f69,0xbf72bf72,0x3e193e19,0xbe97be97,0x3f693f69,
0xbf75bf69,0xbe97,0xbe19bede,0x3f723f5a,0xbf46bf69,0x3f103e97,0x3ede3e19,0x3f5a3f72,0xbf72bf10,0x3e193f46,0xbe97,0x3f753f69,0xbf2dbf5a,0x3f2d3ede,0x3f103e97,0x3f463f69,
0xbf10bf69,0x3f463e97,0x3f5a3ede,0x3ede3f5a,0x3f100000,0x3f463f75,0x3f2d3f72,0xbf2dbe19,0xbf723f69,0x3e193e97,0x3e97be97,0x3f693f69,0xbe19bf2d,0x3f723f2d,0x3f753f46,0x3f10,
0x3e97bf10,0x3f693f46,0x3f2d3f72,0xbf2d3e19,0x3f463f69,0xbf103e97,0xbf5abe19,0xbedebf72,0xbf720000,0x3e19bf75,0x3f10be97,0x3f463f69,0x3edebede,0x3f5a3f5a,0x3f103f75,0xbf460000,
0xbe97be97,0xbf693f69,0x3f72bf2d,0x3e19bf2d,0xbf2d3f46,0xbf2d3f10,0x3f69bf69,0xbe97be97,0xbf5a3f72,0x3ede3e19,0xbf10,0xbf753f46,0x3e193ede,0x3f72bf5a,0xbf693f10,0xbe973f46,
0xbf693f46,0x3e973f10,0xbe19bf2d,0xbf723f2d,0xbf2d3e97,0xbf2dbf69,0x3f46bf69,0xbf10be97,0xbede3f72,0x3f5abe19,0xbf460000,0xbf103f75,0x3f72bede,0x3e19bf5a,0xbe973f69,0x3f69be97,
0x3e973f46,0x3f69bf10,0xbf5a3f2d,0x3ede3f2d,0xbf2dbf75,0xbf2d0000,0x3f10bf69,0xbf46be97,0x3e193f5a,0x3f72bede,0xbf693f10,0x3e973f46,0x3edebf72,0xbf5abe19,0x3f690000,0x3e97bf75,
0x3f69be97,0xbe97bf69,0x3f2d3f2d,0x3f2dbf2d,0xbf2d3e97,0xbf2d3f69,0x3e97bf69,0xbf69be97,0x3f2d3f2d,0x3f2dbf2d,0xbe973f69,0x3f693e97,0xbf2dbf2d,0xbf2d3f2d,0x3e97bf69,0xbf69be97,
0xbe97bf75,0xbf690000,0x3edebf2d,0xbf5abf2d,0xbf2d3f46,0xbf2dbf10,0xbf69,0xbf75be97,0x3f723ede,0x3e19bf5a,0x3f103f69,0x3f46be97,0xbf5a3e19,0x3ede3f72,0xbf69bf10,0xbe973f46,
0xbf69be97,0x3e973f69,0xbf72bf2d,0xbe193f2d,0xbf2dbf46,0xbf2dbf10,0xbe97bf69,0xbf69be97,0x3f5a3e19,0xbedebf72,0x3f753f10,0xbf46,0x3e193f5a,0x3f723ede,0xbe973f10,0x3f693f46,
0x3e973f46,0x3f693f10,0x3e193f2d,0x3f723f2d,0xbf2dbe97,0xbf2d3f69,0xbf10bf69,0xbf46be97,0x3edebe19,0xbf5abf72,0x3f100000,0xbf46bf75,0x3f723f5a,0x3e19bede,0x3f693f69,0x3e97be97,
0x3f693f46,0xbe97bf10,0x3f5a3f2d,0xbedebf2d,0xbf2d3f75,0xbf2d0000,0xbf46bf69,0xbf10be97,0xbe19bede,0xbf72bf5a,0xbe97bf10,0xbf69bf46,0x3ede3e19,0xbf5abf72,0x3e970000,0xbf69bf75,
0xbf75bf75,0,0xbf2dbf2d,0x3f2d3f2d,0xbf2dbf75,0x3f2d0000,0,0x3f753f75,0xbf2dbf2d,0x3f2d3f2d,0,0x3f753f75,0xbf2dbf2d,0x3f2d3f2d,0,0x3f753f75,
0xbe97,0x3f753f69,0x3f5a3f2d,0x3ede3f2d,0xbf2d3e97,0x3f2d3f69,0x3e970000,0x3f693f75,0xbe19bede,0x3f723f5a,0x3f463f10,0x3f103f46,0x3ede3e19,0x3f5a3f72,0x3f753f69,0x3e97,
0x3f753f46,0x3f10,0x3e193f2d,0xbf72bf2d,0xbf2d3f46,0x3f2dbf10,0x3f100000,0x3f463f75,0x3edebe19,0x3f5a3f72,0x3f693f69,0xbe973e97,0x3f723f5a,0xbe193ede,0x3f10,0xbf75bf46,
0x3f46,0xbf75bf10,0xbf72bf2d,0x3e19bf2d,0xbf2dbf46,0x3f2dbf10,0x3f460000,0x3f103f75,0x3f5a3e19,0x3ede3f72,0x3e973f69,0xbf69be97,0x3e193f5a,0xbf72bede,0xbf75bf10,0xbf46,
0xbf75be97,0xbf69,0x3edebf2d,0x3f5a3f2d,0xbf2dbe97,0x3f2d3f69,0x3f690000,0x3e973f75,0x3f723ede,0xbe193f5a,0xbf103f10,0xbf46bf46,0xbf5a3e19,0xbedebf72,0xbf69,0x3f753e97,
0xbf75,0x3f750000,0x3f2d3f2d,0xbf2d3f2d,0xbf2d3f75,0x3f2d0000,0x3f750000,0x3f75,0x3f2d3f2d,0xbf2d3f2d,0xbf750000,0xbf75,0xbf2dbf2d,0x3f2dbf2d,0x3f750000,0x3f75,
0x3f75be97,0x3f69,0xbf5a3f2d,0xbedebf2d,0xbf2dbe97,0x3f2dbf69,0x3f690000,0xbe973f75,0x3e193f5a,0xbf723ede,0xbf10bf10,0x3f46bf46,0x3edebf72,0x3f5a3e19,0x3f69,0xbf753e97,
0x3f46,0xbf753f10,0xbe19bf2d,0x3f72bf2d,0xbf2dbf46,0x3f2d3f10,0x3f460000,0xbf103f75,0xbede3f72,0xbf5a3e19,0x3e97bf69,0x3f69be97,0x3f72bede,0xbe193f5a,0xbf753f10,0xbf46,
0xbf753f46,0xbf10,0x3f72bf2d,0xbe193f2d,0xbf2d3f46,0x3f2d3f10,0x3f100000,0xbf463f75,0xbf5a3f72,0xbedebe19,0x3f69bf69,0x3e973e97,0x3e193ede,0xbf723f5a,0xbf10,0x3f75bf46,
0xbe97,0x3f75bf69,0xbede3f2d,0xbf5a3f2d,0xbf2d3e97,0x3f2dbf69,0x3e970000,0xbf693f75,0xbf723f5a,0x3e19bede,0x3f46bf10,0xbf103f46,0xbf5a3f72,0xbede3e19,0x3f75bf69,0x3e97,
0x3f75bf75,0,0xbf2d3f2d,0x3f2dbf2d,0xbf2dbf75,0x3f2d0000,0,0xbf753f75,0xbf2d3f2d,0x3f2dbf2d,0,0xbf753f75,0xbf2d3f2d,0x3f2dbf2d,0,0xbf753f75,
0xbe97,0xbf753f69,0x3f5abf2d,0x3edebf2d,0xbf2d3e97,0x3f2d3f69,0xbe970000,0xbf693f75,0xbe193ede,0x3f72bf5a,0xbf463f10,0xbf103f46,0x3edebe19,0x3f5abf72,0xbf753f69,0x3e97,
0xbf753f46,0x3f10,0x3e19bf2d,0xbf723f2d,0xbf2d3f46,0x3f2dbf10,0xbf100000,0xbf463f75,0x3ede3e19,0x3f5abf72,0xbf693f69,0x3e973e97,0x3f72bf5a,0xbe19bede,0x3f10,0x3f75bf46,
0x3f46,0x3f75bf10,0xbf723f2d,0x3e193f2d,0xbf2dbf46,0x3f2dbf10,0xbf460000,0xbf103f75,0x3f5abe19,0x3edebf72,0xbe973f69,0x3f69be97,0x3e19bf5a,0xbf723ede,0x3f75bf10,0xbf46,
0x3f75be97,0xbf69,0x3ede3f2d,0x3f5abf2d,0xbf2dbe97,0x3f2d3f69,0xbf690000,0xbe973f75,0x3f72bede,0xbe19bf5a,0x3f103f10,0x3f46bf46,0xbf5abe19,0xbede3f72,0xbf69,0xbf753e97,
0xbf75,0xbf750000,0x3f2dbf2d,0xbf2dbf2d,0xbf2d3f75,0x3f2d0000,0xbf750000,0x3f75,0x3f2dbf2d,0xbf2dbf2d,0x3f750000,0xbf75,0xbf2d3f2d,0x3f2d3f2d,0xbf750000,0x3f75,
0xbf75be97,0x3f69,0xbf5abf2d,0xbede3f2d,0xbf2dbe97,0x3f2dbf69,0xbf690000,0x3e973f75,0x3e19bf5a,0xbf72bede,0x3f10bf10,0xbf46bf46,0x3ede3f72,0x3f5abe19,0x3f69,0x3f753e97,
0x3f46,0x3f753f10,0xbe193f2d,0x3f723f2d,0xbf2dbf46,0x3f2d3f10,0xbf460000,0x3f103f75,0xbedebf72,0xbf5abe19,0xbe97bf69,0xbf69be97,0x3f723ede,0xbe19bf5a,0x3f753f10,0xbf46,
0x3f753f46,0xbf10,0x3f723f2d,0xbe19bf2d,0xbf2d3f46,0x3f2d3f10,0xbf100000,0x3f463f75,0xbf5abf72,0xbede3e19,0xbf69bf69,0xbe973e97,0x3e19bede,0xbf72bf5a,0xbf10,0xbf75bf46,
0xbe97,0xbf75bf69,0xbedebf2d,0xbf5abf2d,0xbf2d3e97,0x3f2dbf69,0xbe970000,0x3f693f75,0xbf72bf5a,0x3e193ede,0xbf46bf10,0x3f103f46,0xbf5abf72,0xbedebe19,0xbf75bf69,0x3e97,
0xbe97be97,0x3f693f69,0x3f2d3f2d,0x3f2d3f2d,0x3f2dbe97,0x3f2d3f69,0x3f693f69,0xbe97be97,0x3f2d3f2d,0x3f2d3f2d,0x3f693f69,0xbe97be97,0x3f2d3f2d,0x3f2d3f2d,0x3f693f69,0xbe97be97,
0x3f693f46,0x3e973f10,0x3ede3f2d,0xbf5abf2d,0x3f2d3f75,0x3f2d0000,0x3f463f69,0xbf10be97,0x3f723f5a,0x3e193ede,0x3e973f10,0xbf69bf46,0x3f5a3f72,0xbedebe19,0xbe970000,0xbf69bf75,
0x3e973f46,0xbf69bf10,0xbf72bf2d,0xbe19bf2d,0x3f2dbe97,0x3f2dbf69,0x3f103f69,0xbf46be97,0x3f5a3f72,0xbede3e19,0xbf100000,0xbf46bf75,0xbe193ede,0xbf72bf5a,0xbf69bf69,0x3e97be97,
0xbf69be97,0xbe97bf69,0x3e19bf2d,0x3f723f2d,0x3f2dbf46,0x3f2d3f10,0x3e973f69,0xbf69be97,0x3ede3f72,0xbf5abe19,0xbf75bf10,0xbf46,0xbf72bede,0xbe19bf5a,0x3e97bf10,0x3f693f46,
0,0,0x3f69,0xbe97,0,0,0,0,0,0,0,0,0,0,0,0,
0,0,0xbf10,0xbf46,0,0,0,0,0,0,0,0,0,0,0,0,
0,0,0xbf10,0x3f46,0,0,0,0,0,0,0,0,0,0,0,0,
0,0,0x3f69,0x3e97,0,0,0,0,0,0,0,0,0,0,0,0,
0,0,0,0xbf75,0,0,0,0,0,0,0,0,0,0,0,0,
0,0,0xbf69,0x3e97,0,0,0,0,0,0,0,0,0,0,0,0,
0,0,0x3f10,0x3f46,0,0,0,0,0,0,0,0,0,0,0,0,
0,0,0x3f10,0xbf46,0,0,0,0,0,0,0,0,0,0,0,0,
0,0,0,0x3f75,0,0,0,0,0,0,0,0,0,0,0,0,
0,0,0x3f69,0xbe97,0,0,0,0,0,0,0,0,0,0,0,0,
0,0,0xbf10,0xbf46,0,0,0,0,0,0,0,0,0,0,0,0,
0,0,0xbf10,0x3f46,0,0,0,0,0,0,0,0,0,0,0,0,
0,0,0x3f69,0x3e97,0,0,0,0,0,0,0,0,0,0,0,0,
0,0,0,0xbf75,0,0,0,0,0,0,0,0,0,0,0,0,
0,0,0xbf69,0x3e97,0,0,0,0,0,0,0,0,0,0,0,0,
0,0,0x3f10,0x3f46,0,0,0,0,0,0,0,0,0,0,0,0,
0,0,0x3f10,0xbf46,0,0,0,0,0,0,0,0,0,0,0,0,
0,0,0xbf69,0xbe97,0,0,0,0,0,0,0,0,0,0,0,0,
0,0,0,0x3f75,0,0,0,0,0,0,0,0,0,0,0,0,
0,0,0x3f69,0xbe97,0,0,0,0,0,0,0,0,0,0,0,0,
0,0,0xbf10,0xbf46,0,0,0,0,0,0,0,0,0,0,0,0,
0,0,0xbf10,0x3f46,0,0,0,0,0,0,0,0,0,0,0,0,
0,0,0x3f69,0x3e97,0,0,0,0,0,0,0,0,0,0,0,0,
0,0,0,0xbf75,0,0,0,0,0,0,0,0,0,0,0,0,
0,0,0xbf69,0x3e97,0,0,0,0,0,0,0,0,0,0,0,0,
0,0,0x3f10,0x3f46,0,0,0,0,0,0,0,0,0,0,0,0,
0,0,0x3f10,0xbf46,0,0,0,0,0,0,0,0,0,0,0,0,
0,0,0xbf69,0xbe97,0,0,0,0,0,0,0,0,0,0,0,0,
0,0,0x3f69,0xbe97,0,0,0,0,0,0,0,0,0,0,0,0,
0,0,0xbf10,0xbf46,0,0,0,0,0,0,0,0,0,0,0,0,
0,0,0xbf10,0x3f46,0,0,0,0,0,0,0,0,0,0,0,0,
0,0,0x3f69,0x3e97,0,0,0,0,0,0,0,0,0,0,0,0,
0x3e973f75,0xbf690000,0xbf5abf2d,0x3edebf2d,0xbf46bf46,0x3f10bf10,0x3f723e19,0x3e193f72,0x3f753e97,0x3f69,0xbf2d3ede,0xbf2dbf5a,0x3ede3e97,0xbf5abf69,0xbf69bf10,0x3e97bf46,
0x3f75,0xbf750000,0xbedebf5a,0x3f5abede,0xbf75,0x3f750000,0x3ede3f5a,0xbf5a3ede,0x3f75,0xbf750000,0xbedebf5a,0x3f5abede,0x3edebf75,0xbf5a0000,0xbf46bf10,0x3f10bf46,
0xbe973f75,0xbf690000,0x3e19bf72,0x3f72be19,0x3f46bf46,0x3f103f10,0xbf2d3f5a,0xbf2dbede,0xbf753e97,0xbf69,0x3f72bede,0x3e193f5a,0x3ede3e97,0xbf5a3f69,0xbf10bf10,0x3f46bf46,
0xbf103f75,0xbf460000,0x3f2dbf72,0x3f2d3e19,0x3f69be97,0xbe973f69,0xbf5a3e19,0x3edebf72,0xbf46,0x3f75bf10,0xbe193f5a,0xbf723ede,0x3ede3f46,0xbf5abf10,0xbe97bf10,0x3f69bf46,
0xbf463f75,0xbf100000,0x3f72bf5a,0x3e193ede,0x3e973e97,0xbf693f69,0x3e19bf2d,0x3f72bf2d,0x3f75bf46,0x3f10,0xbf5a3ede,0x3edebf5a,0x3edebf46,0xbf5abf10,0xbf10,0x3f75bf46,
0xbf693f75,0xbe970000,0x3f5abf2d,0xbede3f2d,0xbf103f46,0xbf463f10,0x3f72bf72,0x3e193e19,0x3e97,0xbf753f69,0x3f2dbf5a,0x3f2dbede,0x3edebe97,0xbf5a3f69,0x3e97bf10,0x3f69bf46,
0xbf753f75,0,0x3edebede,0xbf5a3f5a,0xbf753f75,0,0x3edebede,0xbf5a3f5a,0xbf753f75,0,0x3edebede,0xbf5a3f5a,0x3ede3f75,0xbf5a0000,0x3f10bf10,0x3f46bf46,
0xbf693f75,0x3e970000,0xbe19be19,0xbf723f72,0xbf103f46,0x3f46bf10,0xbf2d3ede,0xbf2d3f5a,0x3e97,0x3f75bf69,0xbf723f5a,0xbe193ede,0x3edebe97,0xbf5abf69,0x3f46bf10,0x3f10bf46,
0xbf463f75,0x3f100000,0xbf2d3e19,0xbf2d3f72,0x3e973e97,0x3f69bf69,0xbf5a3f72,0x3ede3e19,0x3f75bf46,0xbf10,0x3e193ede,0x3f72bf5a,0x3edebf46,0xbf5a3f10,0x3f69bf10,0x3e97bf46,
0xbf103f75,0x3f460000,0xbf723ede,0xbe193f5a,0x3f69be97,0x3e97bf69,0x3e193f2d,0x3f72bf2d,0xbf46,0xbf753f10,0x3f5abf5a,0xbedebede,0x3ede3f46,0xbf5a3f10,0x3f75bf10,0xbf46,
0xbe973f75,0x3f690000,0xbf5a3f2d,0x3ede3f2d,0x3f46bf46,0xbf10bf10,0x3f72be19,0x3e19bf72,0xbf753e97,0x3f69,0xbf2dbede,0xbf2d3f5a,0x3ede3e97,0xbf5abf69,0x3f69bf10,0xbe97bf46,
0x3f75,0x3f750000,0xbede3f5a,0x3f5a3ede,0xbf75,0xbf750000,0x3edebf5a,0xbf5abede,0x3f75,0x3f750000,0xbede3f5a,0x3f5a3ede,0x3edebf75,0xbf5a0000,0x3f46bf10,0xbf10bf46,
0x3e973f75,0x3f690000,0x3e193f72,0x3f723e19,0xbf46bf46,0xbf103f10,0xbf2dbf5a,0xbf2d3ede,0x3f753e97,0xbf69,0x3f723ede,0x3e19bf5a,0x3ede3e97,0xbf5a3f69,0x3f10bf10,0xbf46bf46,
0x3f103f75,0x3f460000,0x3f2d3f72,0x3f2dbe19,0xbf69be97,0x3e973f69,0xbf5abe19,0x3ede3f72,0xbf46,0xbf75bf10,0xbe19bf5a,0xbf72bede,0x3ede3f46,0xbf5abf10,0x3e97bf10,0xbf69bf46,
0x3f463f75,0x3f100000,0x3f723f5a,0x3e19bede,0xbe973e97,0x3f693f69,0x3e193f2d,0x3f723f2d,0xbf75bf46,0x3f10,0xbf5abede,0x3ede3f5a,0x3edebf46,0xbf5abf10,0xbf10,0xbf75bf46,
0x3f693f75,0x3e970000,0x3f5a3f2d,0xbedebf2d,0x3f103f46,0x3f463f10,0x3f723f72,0x3e19be19,0x3e97,0x3f753f69,0x3f2d3f5a,0x3f2d3ede,0x3edebe97,0xbf5a3f69,0xbe97bf10,0xbf69bf46,
0x3f753f75,0,0x3e193e19,0xbf72bf72,0x3f753f75,0,0x3e193e19,0xbf72bf72,0x3f753f75,0,0x3e193e19,0xbf72bf72,0x3e193f75,0xbf720000,0xbf69bf69,0xbe97be97,
0x3f693f75,0xbe970000,0xbedebe19,0xbf5abf72,0x3f103f46,0xbf46bf10,0xbf5abf2d,0xbedebf2d,0x3e97,0xbf75bf69,0xbf72bf72,0x3e19be19,0x3e19be97,0xbf72bf69,0xbf75bf69,0xbe97,
0x3f463f75,0xbf100000,0xbf5abede,0xbedebf5a,0xbe973e97,0xbf69bf69,0xbf2dbf72,0x3f2d3e19,0xbf75bf46,0xbf10,0x3edebe19,0x3f5a3f72,0x3e19bf46,0xbf723f10,0xbf69bf69,0x3e97be97,
0x3f103f75,0xbf460000,0xbf72bf2d,0x3e19bf2d,0xbf69be97,0xbe97bf69,0x3edebede,0x3f5a3f5a,0xbf46,0x3f753f10,0x3f2d3f72,0xbf2d3e19,0x3e193f46,0xbf723f10,0xbf46bf69,0x3f10be97,
0x3e973f75,0xbf690000,0xbf2dbf5a,0x3f2dbede,0xbf46bf46,0x3f10bf10,0x3f723ede,0xbe193f5a,0x3f753e97,0x3f69,0xbf5a3e19,0xbedebf72,0x3e193e97,0xbf72bf69,0xbf10bf69,0x3f46be97,
0x3f75,0xbf750000,0xbe19bf72,0x3f72be19,0xbf75,0x3f750000,0x3e193f72,0xbf723e19,0x3f75,0xbf750000,0xbe19bf72,0x3f72be19,0x3e19bf75,0xbf720000,0xbe97bf69,0x3f69be97,
0xbe973f75,0xbf690000,0x3edebf72,0x3f5a3e19,0x3f46bf46,0x3f103f10,0xbf5a3f2d,0xbedebf2d,0xbf753e97,0xbf69,0x3f72be19,0xbe193f72,0x3e193e97,0xbf723f69,0xbf69,0x3f75be97,
0xbf103f75,0xbf460000,0x3f5abf5a,0x3ede3ede,0x3f69be97,0xbe973f69,0xbf2dbe19,0x3f2dbf72,0xbf46,0x3f75bf10,0xbede3f72,0xbf5a3e19,0x3e193f46,0xbf72bf10,0x3e97bf69,0x3f69be97,
0xbf463f75,0xbf100000,0x3f72bf2d,0xbe193f2d,0x3e973e97,0xbf693f69,0x3edebf5a,0x3f5abede,0x3f75bf46,0x3f10,0xbf2d3e19,0x3f2dbf72,0x3e19bf46,0xbf72bf10,0x3f10bf69,0x3f46be97,
0xbf693f75,0xbe970000,0x3f2dbede,0xbf2d3f5a,0xbf103f46,0xbf463f10,0x3f72bf5a,0xbe193ede,0x3e97,0xbf753f69,0x3f5abf72,0x3edebe19,0x3e19be97,0xbf723f69,0x3f46bf69,0x3f10be97,
0xbf753f75,0,0x3e19be19,0xbf723f72,0xbf753f75,0,0x3e19be19,0xbf723f72,0xbf753f75,0,0x3e19be19,0xbf723f72,0x3e193f75,0xbf720000,0x3f69bf69,0x3e97be97,
0xbf693f75,0x3e970000,0xbede3e19,0xbf5a3f72,0xbf103f46,0x3f46bf10,0xbf5a3f2d,0xbede3f2d,0x3e97,0x3f75bf69,0xbf723f72,0x3e193e19,0x3e19be97,0xbf72bf69,0x3f75bf69,0xbe97,
0xbf463f75,0x3f100000,0xbf5a3ede,0xbede3f5a,0x3e973e97,0x3f69bf69,0xbf2d3f72,0x3f2dbe19,0x3f75bf46,0xbf10,0x3ede3e19,0x3f5abf72,0x3e19bf46,0xbf723f10,0x3f69bf69,0xbe97be97,
0xbf103f75,0x3f460000,0xbf723f2d,0x3e193f2d,0x3f69be97,0x3e97bf69,0x3ede3ede,0x3f5abf5a,0xbf46,0xbf753f10,0x3f2dbf72,0xbf2dbe19,0x3e193f46,0xbf723f10,0x3f46bf69,0xbf10be97,
0xbe973f75,0x3f690000,0xbf2d3f5a,0x3f2d3ede,0x3f46bf46,0xbf10bf10,0x3f72bede,0xbe19bf5a,0xbf753e97,0x3f69,0xbf5abe19,0xbede3f72,0x3e193e97,0xbf72bf69,0x3f10bf69,0xbf46be97,
0x3f75,0x3f750000,0xbe193f72,0x3f723e19,0xbf75,0xbf750000,0x3e19bf72,0xbf72be19,0x3f75,0x3f750000,0xbe193f72,0x3f723e19,0x3e19bf75,0xbf720000,0x3e97bf69,0xbf69be97,
0x3f690000,0x3e973f75,0xbede3f2d,0xbf5abf2d,0xbf103f10,0xbf46bf46,0xbe19bf72,0x3f723e19,0xbf72bf69,0x3e193e97,0x3f46be97,0x3f103f69,0x3f5abe19,0x3ede3f72,0xbe973f46,0xbf69bf10,
0x3f463f10,0xbf103f46,0xbf72be19,0x3e19bf72,0xbf46bf10,0x3f10bf46,0x3f723e19,0xbe193f72,0xbf723f10,0x3e193f46,0x3f69be97,0x3e973f69,0x3f723e19,0xbe193f72,0xbf693e97,0xbe97bf69,
0x3f69,0xbf753e97,0xbe19bf5a,0x3f72bede,0x3f10bf69,0x3f463e97,0xbede3f72,0xbf5abe19,0xbf723f10,0x3e19bf46,0x3f75be97,0x3f69,0x3f2d3ede,0xbf2d3f5a,0xbf46be97,0x3f10bf69,
0xbf463f69,0xbf10be97,0x3f5abf5a,0x3ede3ede,0x3f460000,0xbf103f75,0xbf2dbe19,0x3f2dbf72,0xbf72bf69,0x3e19be97,0x3f69be97,0xbe973f69,0x3e193f2d,0xbf723f2d,0xbf46,0x3f75bf10,
0xbf693f10,0x3e97bf46,0x3f2dbe19,0xbf2d3f72,0xbf103f69,0xbf463e97,0x3f5abf72,0x3ede3e19,0xbf720000,0x3e193f75,0x3f46be97,0xbf103f69,0xbede3f5a,0xbf5a3ede,0x3f46bf75,0x3f100000,
0xbe970000,0x3f69bf75,0xbede3f2d,0xbf5a3f2d,0xbf463f10,0x3f10bf46,0x3e193e19,0xbf723f72,0xbf723f69,0x3e19be97,0x3f10be97,0xbf463f69,0xbf5a3f72,0xbede3e19,0x3f69bf46,0xbe973f10,
0x3f10bf10,0x3f46bf46,0xbf723f72,0x3e19be19,0x3f10bf10,0x3f46bf46,0xbf723f72,0x3e19be19,0xbf72bf10,0x3e19bf46,0x3e97be97,0xbf693f69,0xbf723f72,0x3e19be19,0x3e97be97,0xbf693f69,
0x3f75bf69,0xbe97,0xbe193ede,0x3f72bf5a,0x3f46bf69,0xbf103e97,0x3edebe19,0x3f5abf72,0xbf72bf10,0x3e193f46,0xbe97,0xbf753f69,0xbf2d3f5a,0x3f2dbede,0xbf103e97,0xbf463f69,
0x3f10bf69,0xbf463e97,0x3f5abede,0x3edebf5a,0xbf100000,0xbf463f75,0x3f2dbf72,0xbf2d3e19,0xbf723f69,0x3e193e97,0xbe97be97,0xbf693f69,0xbe193f2d,0x3f72bf2d,0xbf753f46,0x3f10,
0xbe97bf10,0xbf693f46,0x3f2dbf72,0xbf2dbe19,0xbf463f69,0x3f103e97,0xbf5a3e19,0xbede3f72,0xbf720000,0x3e19bf75,0xbf10be97,0xbf463f69,0x3ede3ede,0x3f5abf5a,0xbf103f75,0x3f460000,
0xbf690000,0xbe973f75,0xbedebf2d,0xbf5a3f2d,0x3f103f10,0x3f46bf46,0xbe193f72,0x3f72be19,0xbf72bf69,0x3e193e97,0xbf46be97,0xbf103f69,0x3f5a3e19,0x3edebf72,0x3e973f46,0x3f69bf10,
0xbf463f10,0x3f103f46,0xbf723e19,0x3e193f72,0x3f46bf10,0xbf10bf46,0x3f72be19,0xbe19bf72,0xbf723f10,0x3e193f46,0xbf69be97,0xbe973f69,0x3f72be19,0xbe19bf72,0x3f693e97,0x3e97bf69,
0x3f69,0x3f753e97,0xbe193f5a,0x3f723ede,0xbf10bf69,0xbf463e97,0xbedebf72,0xbf5a3e19,0xbf723f10,0x3e19bf46,0xbf75be97,0x3f69,0x3f2dbede,0xbf2dbf5a,0x3f46be97,0xbf10bf69,
0x3f463f69,0x3f10be97,0x3f5a3f5a,0x3edebede,0xbf460000,0x3f103f75,0xbf2d3e19,0x3f2d3f72,0xbf72bf69,0x3e19be97,0xbf69be97,0x3e973f69,0x3e19bf2d,0xbf72bf2d,0xbf46,0xbf75bf10,
0x3f693f10,0xbe97bf46,0x3f2d3e19,0xbf2dbf72,0x3f103f69,0x3f463e97,0x3f5a3f72,0x3edebe19,0xbf720000,0x3e193f75,0xbf46be97,0x3f103f69,0xbedebf5a,0xbf5abede,0xbf46bf75,0xbf100000,
0x3e970000,0xbf69bf75,0xbedebf2d,0xbf5abf2d,0x3f463f10,0xbf10bf46,0x3e19be19,0xbf72bf72,0xbf723f69,0x3e19be97,0xbf10be97,0x3f463f69,0xbf5abf72,0xbedebe19,0xbf69bf46,0x3e973f10,
0xbf69bf69,0xbe97be97,0xbedebede,0x3f5a3f5a,0xbf69bf69,0xbe97be97,0xbedebede,0x3f5a3f5a,0xbedebf69,0x3f5abe97,0x3f463f46,0x3f103f10,0xbedebede,0x3f5a3f5a,0x3f463f46,0x3f103f10,
0xbf46bf69,0x3f103e97,0x3f2d3ede,0x3f2d3f5a,0xbe97bf10,0x3f693f46,0x3f723f5a,0x3e193ede,0xbede0000,0x3f5a3f75,0x3f693f46,0x3e973f10,0x3e19be19,0x3f723f72,0x3f693f75,0xbe970000,
0xbf10,0x3f753f46,0x3f5a3f72,0xbede3e19,0x3f693f10,0x3e973f46,0xbe193ede,0xbf72bf5a,0xbede3f69,0x3f5abe97,0x3f753f46,0x3f10,0x3f2d3e19,0x3f2d3f72,0x3e973f46,0xbf69bf10,
0x3f460000,0x3f103f75,0xbe193f2d,0xbf72bf2d,0x3e973f69,0xbf69be97,0xbf5abf5a,0x3edebede,0xbedebf10,0x3f5abf46,0x3f693f46,0xbe973f10,0x3f723ede,0x3e193f5a,0xbf103e97,0xbf46bf69,
0x3f693f10,0xbe973f46,0xbf72be19,0xbe19bf72,0xbf690000,0xbe97bf75,0x3f2dbede,0x3f2d3f5a,0xbedebf10,0x3f5a3f46,0x3f463f46,0xbf103f10,0x3f5a3f2d,0xbede3f2d,0xbf75be97,0xbf69,
0x3e973f69,0xbf693e97,0xbedebf5a,0x3f5abede,0xbe97bf69,0x3f69be97,0x3ede3f5a,0xbf5a3ede,0xbede3f69,0x3f5a3e97,0x3f103f46,0xbf463f10,0x3ede3f5a,0xbf5a3ede,0xbf10bf46,0x3f46bf10,
0xbf103f69,0xbf46be97,0x3f2dbf5a,0x3f2d3ede,0x3f69bf10,0x3e973f46,0xbf723ede,0xbe19bf5a,0xbede0000,0x3f5abf75,0x3e973f46,0xbf693f10,0xbe193f72,0xbf723e19,0x3e97bf75,0x3f690000,
0xbf753f10,0xbf46,0x3f5abe19,0xbede3f72,0x3e973f10,0xbf693f46,0x3e19bf5a,0x3f72bede,0xbedebf69,0x3f5a3e97,0x3f46,0xbf753f10,0xbf2d3f72,0xbf2dbe19,0x3f69bf46,0x3e973f10,
0xbf100000,0x3f46bf75,0xbe193f2d,0xbf723f2d,0xbf693f69,0xbe97be97,0x3f5abede,0xbede3f5a,0xbede3f10,0x3f5a3f46,0xbe973f46,0xbf693f10,0xbf723f5a,0xbe19bede,0x3f46be97,0xbf103f69,
0x3e97bf10,0x3f69bf46,0xbf723f72,0xbe19be19,0xbe970000,0x3f69bf75,0xbf2d3f5a,0xbf2d3ede,0xbede3f10,0x3f5abf46,0xbf103f46,0xbf463f10,0xbf5a3f2d,0x3edebf2d,0x3e97,0xbf753f69,
0x3f69bf69,0x3e97be97,0xbede3ede,0x3f5abf5a,0x3f69bf69,0x3e97be97,0xbede3ede,0x3f5abf5a,0xbedebf69,0x3f5abe97,0xbf463f46,0xbf103f10,0xbede3ede,0x3f5abf5a,0xbf463f46,0xbf103f10,
0x3f46bf69,0xbf103e97,0x3f2dbede,0x3f2dbf5a,0x3e97bf10,0xbf693f46,0x3f72bf5a,0x3e19bede,0xbede0000,0x3f5a3f75,0xbf693f46,0xbe973f10,0x3e193e19,0x3f72bf72,0xbf693f75,0x3e970000,
0xbf10,0xbf753f46,0x3f5abf72,0xbedebe19,0xbf693f10,0xbe973f46,0xbe19bede,0xbf723f5a,0xbede3f69,0x3f5abe97,0xbf753f46,0x3f10,0x3f2dbe19,0x3f2dbf72,0xbe973f46,0x3f69bf10,
0xbf460000,0xbf103f75,0xbe19bf2d,0xbf723f2d,0xbe973f69,0x3f69be97,0xbf5a3f5a,0x3ede3ede,0xbedebf10,0x3f5abf46,0xbf693f46,0x3e973f10,0x3f72bede,0x3e19bf5a,0x3f103e97,0x3f46bf69,
0xbf693f10,0x3e973f46,0xbf723e19,0xbe193f72,0x3f690000,0x3e97bf75,0x3f2d3ede,0x3f2dbf5a,0xbedebf10,0x3f5a3f46,0xbf463f46,0x3f103f10,0x3f5abf2d,0xbedebf2d,0x3f75be97,0xbf69,
0xbe973f69,0x3f693e97,0xbede3f5a,0x3f5a3ede,0x3e97bf69,0xbf69be97,0x3edebf5a,0xbf5abede,0xbede3f69,0x3f5a3e97,0xbf103f46,0x3f463f10,0x3edebf5a,0xbf5abede,0x3f10bf46,0xbf46bf10,
0xbe97bf75,0x3f690000,0x3f5a3f2d,0xbede3f2d,0x3f2d3f46,0x3f2d3f10,0x3f69,0xbf75be97,0xbe193f5a,0xbf72bede,0xbf10bf69,0x3f46be97,0xbedebf72,0x3f5abe19,0x3f693f10,0xbe973f46,
0x3f69be97,0x3e973f69,0xbf2d3f2d,0xbf2dbf2d,0x3f2d3e97,0x3f2dbf69,0xbe973f69,0xbf69be97,0xbf2d3f2d,0xbf2dbf2d,0x3e97bf69,0x3f693e97,0x3f2dbf2d,0x3f2d3f2d,0xbe973f69,0xbf69be97,
0x3e973f46,0xbf693f10,0xbedebf2d,0x3f5abf2d,0x3f2dbf75,0x3f2d0000,0xbf103f69,0xbf46be97,0xbf723ede,0xbe19bf5a,0x3f69bf10,0x3e973f46,0x3f5a3e19,0xbede3f72,0xbf690000,0x3e97bf75,
0xbf693f46,0xbe97bf10,0x3f72bf2d,0x3e193f2d,0x3f2d3e97,0x3f2d3f69,0xbf463f69,0xbf10be97,0xbf5a3e19,0x3edebf72,0x3f460000,0xbf103f75,0xbe193f5a,0xbf723ede,0x3e97bf69,0x3f69be97,
0xbe97be97,0x3f69bf69,0xbe193f2d,0xbf723f2d,0x3f2d3f46,0x3f2dbf10,0xbf693f69,0xbe97be97,0xbedebe19,0x3f5abf72,0x3f10,0xbf753f46,0xbf723f5a,0xbe19bede,0x3f69bf10,0xbe973f46,
0x3f69bf75,0x3e970000,0xbf5a3f2d,0x3edebf2d,0x3f2dbf46,0x3f2dbf10,0xbf753f69,0xbe97,0x3e19bede,0x3f72bf5a,0xbf463f69,0xbf103e97,0xbede3e19,0x3f5abf72,0xbe973f10,0xbf693f46,
0x3e97be97,0xbf693f69,0x3f2dbf2d,0x3f2dbf2d,0x3f2dbe97,0x3f2d3f69,0xbf693f69,0x3e97be97,0x3f2dbf2d,0x3f2dbf2d,0xbf693f69,0x3e97be97,0x3f2dbf2d,0x3f2dbf2d,0xbf693f69,0x3e97be97,
0xbf693f46,0xbe973f10,0x3edebf2d,0xbf5a3f2d,0x3f2d3f75,0x3f2d0000,0xbf463f69,0x3f10be97,0x3f72bf5a,0x3e19bede,0xbe973f10,0x3f69bf46,0x3f5abf72,0xbede3e19,0x3e970000,0x3f69bf75,
0xbe973f46,0x3f69bf10,0xbf723f2d,0xbe193f2d,0x3f2dbe97,0x3f2dbf69,0xbf103f69,0x3f46be97,0x3f5abf72,0xbedebe19,0x3f100000,0x3f46bf75,0xbe19bede,0xbf723f5a,0x3f69bf69,0xbe97be97,
0x3f69be97,0x3e97bf69,0x3e193f2d,0x3f72bf2d,0x3f2dbf46,0x3f2d3f10,0xbe973f69,0x3f69be97,0x3edebf72,0xbf5a3e19,0x3f75bf10,0xbf46,0xbf723ede,0xbe193f5a,0xbe97bf10,0xbf693f46,
0x3e97bf75,0xbf690000,0x3f5abf2d,0xbedebf2d,0x3f2d3f46,0x3f2d3f10,0x3f69,0x3f75be97,0xbe19bf5a,0xbf723ede,0x3f10bf69,0xbf46be97,0xbede3f72,0x3f5a3e19,0xbf693f10,0x3e973f46,
0xbf69be97,0xbe973f69,0xbf2dbf2d,0xbf2d3f2d,0x3f2d3e97,0x3f2dbf69,0x3e973f69,0x3f69be97,0xbf2dbf2d,0xbf2d3f2d,0xbe97bf69,0xbf693e97,0x3f2d3f2d,0x3f2dbf2d,0x3e973f69,0x3f69be97,
0xbe973f46,0x3f693f10,0xbede3f2d,0x3f5a3f2d,0x3f2dbf75,0x3f2d0000,0x3f103f69,0x3f46be97,0xbf72bede,0xbe193f5a,0xbf69bf10,0xbe973f46,0x3f5abe19,0xbedebf72,0x3f690000,0xbe97bf75,
0x3f693f46,0x3e97bf10,0x3f723f2d,0x3e19bf2d,0x3f2d3e97,0x3f2d3f69,0x3f463f69,0x3f10be97,0xbf5abe19,0x3ede3f72,0xbf460000,0x3f103f75,0xbe19bf5a,0xbf72bede,0xbe97bf69,0xbf69be97,
0x3e97be97,0xbf69bf69,0xbe19bf2d,0xbf72bf2d,0x3f2d3f46,0x3f2dbf10,0x3f693f69,0x3e97be97,0xbede3e19,0x3f5a3f72,0x3f10,0x3f753f46,0xbf72bf5a,0xbe193ede,0xbf69bf10,0x3e973f46,
0xbf69bf75,0xbe970000,0xbf5abf2d,0x3ede3f2d,0x3f2dbf46,0x3f2dbf10,0x3f753f69,0xbe97,0x3e193ede,0x3f723f5a,0x3f463f69,0x3f103e97,0xbedebe19,0x3f5a3f72,0x3e973f10,0x3f693f46,
0x3f463f46,0x3f103f10,0x3f2d3f2d,0xbf2dbf2d,0x3f2d3f46,0xbf2d3f10,0xbf10bf10,0xbf46bf46,0x3f2d3f2d,0xbf2dbf2d,0xbf10bf10,0xbf46bf46,0x3f2d3f2d,0xbf2dbf2d,0xbf10bf10,0xbf46bf46,
0x3f103f46,0xbf46bf10,0xbf5abf2d,0xbedebf2d,0x3f2d3e97,0xbf2dbf69,0xbf46bf10,0xbf10bf46,0x3e193ede,0xbf72bf5a,0xbf75bf69,0xbe97,0xbedebe19,0xbf5abf72,0xbf46bf69,0x3f103e97,
0xbf46be97,0xbf10bf69,0xbe19bf2d,0x3f723f2d,0x3f2dbf75,0xbf2d0000,0xbf69bf10,0xbe97bf46,0xbede3e19,0xbf5abf72,0xbf10bf69,0x3f463e97,0xbf72bf5a,0x3e19bede,0x3f100000,0x3f463f75,
0xbf10bf75,0x3f460000,0x3f723f2d,0xbe193f2d,0x3f2d3e97,0xbf2d3f69,0xbf75bf10,0xbf46,0xbf5abe19,0xbedebf72,0x3e97bf10,0x3f693f46,0xbe19bf5a,0x3f723ede,0x3f463f69,0xbf103e97,
0x3f46be97,0x3f103f69,0xbede3f2d,0xbf5abf2d,0x3f2d3f46,0xbf2dbf10,0xbf69bf10,0x3e97bf46,0xbf72bede,0x3e19bf5a,0x3f690000,0x3e973f75,0x3f5abe19,0x3ede3f72,0xbf103f10,0xbf46bf46,
0x3f103f46,0xbf463f10,0xbf2dbf2d,0x3f2dbf2d,0x3f2dbf46,0xbf2dbf10,0xbf46bf10,0x3f10bf46,0xbf2dbf2d,0x3f2dbf2d,0x3f463f10,0xbf103f46,0x3f2d3f2d,0xbf2d3f2d,0xbf46bf10,0x3f10bf46,
0xbf463f46,0xbf10bf10,0x3f5abf2d,0x3ede3f2d,0x3f2dbe97,0xbf2d3f69,0xbf10bf10,0x3f46bf46,0xbe19bf5a,0x3f72bede,0x3f69,0xbf753e97,0xbede3f72,0xbf5abe19,0x3f10bf69,0x3f463e97,
0xbf10be97,0x3f46bf69,0x3e193f2d,0xbf723f2d,0x3f2d3f75,0xbf2d0000,0xbe97bf10,0x3f69bf46,0x3edebf72,0x3f5abe19,0xbf463f69,0xbf10be97,0xbf723ede,0x3e19bf5a,0x3f460000,0xbf103f75,
0x3f46bf75,0x3f100000,0xbf723f2d,0x3e19bf2d,0x3f2dbe97,0xbf2dbf69,0xbf10,0x3f75bf46,0x3f5abf72,0x3ede3e19,0xbf693f10,0x3e97bf46,0xbe19bede,0x3f72bf5a,0xbf103f69,0xbf463e97,
0x3f10be97,0xbf463f69,0x3edebf2d,0x3f5abf2d,0x3f2dbf46,0xbf2d3f10,0x3e97bf10,0x3f69bf46,0x3f72bf5a,0xbe193ede,0xbe970000,0x3f69bf75,0x3f5abf72,0x3edebe19,0xbf463f10,0x3f10bf46,
0xbf463f46,0xbf103f10,0x3f2dbf2d,0xbf2d3f2d,0x3f2d3f46,0xbf2d3f10,0x3f10bf10,0x3f46bf46,0x3f2dbf2d,0xbf2d3f2d,0x3f10bf10,0x3f46bf46,0x3f2dbf2d,0xbf2d3f2d,0x3f10bf10,0x3f46bf46,
0xbf103f46,0x3f46bf10,0xbf5a3f2d,0xbede3f2d,0x3f2d3e97,0xbf2dbf69,0x3f46bf10,0x3f10bf46,0x3e19bede,0xbf723f5a,0x3f75bf69,0xbe97,0xbede3e19,0xbf5a3f72,0x3f46bf69,0xbf103e97,
0x3f46be97,0x3f10bf69,0xbe193f2d,0x3f72bf2d,0x3f2dbf75,0xbf2d0000,0x3f69bf10,0x3e97bf46,0xbedebe19,0xbf5a3f72,0x3f10bf69,0xbf463e97,0xbf723f5a,0x3e193ede,0xbf100000,0xbf463f75,
0x3f10bf75,0xbf460000,0x3f72bf2d,0xbe19bf2d,0x3f2d3e97,0xbf2d3f69,0x3f75bf10,0xbf46,0xbf5a3e19,0xbede3f72,0xbe97bf10,0xbf693f46,0xbe193f5a,0x3f72bede,0xbf463f69,0x3f103e97,
0xbf46be97,0xbf103f69,0xbedebf2d,0xbf5a3f2d,0x3f2d3f46,0xbf2dbf10,0x3f69bf10,0xbe97bf46,0xbf723ede,0x3e193f5a,0xbf690000,0xbe973f75,0x3f5a3e19,0x3edebf72,0x3f103f10,0x3f46bf46,
0xbf103f46,0x3f463f10,0xbf2d3f2d,0x3f2d3f2d,0x3f2dbf46,0xbf2dbf10,0x3f46bf10,0xbf10bf46,0xbf2d3f2d,0x3f2d3f2d,0xbf463f10,0x3f103f46,0x3f2dbf2d,0xbf2dbf2d,0x3f46bf10,0xbf10bf46,
0,0,0,0xbf75,0,0,0,0,0,0,0,0,0,0,0,0,
0,0,0xbf69,0x3e97,0,0,0,0,0,0,0,0,0,0,0,0,
0,0,0x3f10,0x3f46,0,0,0,0,0,0,0,0,0,0,0,0,
0,0,0x3f10,0xbf46,0,0,0,0,0,0,0,0,0,0,0,0,
0,0,0xbf69,0xbe97,0,0,0,0,0,0,0,0,0,0,0,0,
0,0,0,0x3f75,0,0,0,0,0,0,0,0,0,0,0,0,
0,0,0x3f69,0xbe97,0,0,0,0,0,0,0,0,0,0,0,0,
0,0,0xbf10,0xbf46,0,0,0,0,0,0,0,0,0,0,0,0,
0,0,0xbf10,0x3f46,0,0,0,0,0,0,0,0,0,0,0,0,
0,0,0x3f69,0x3e97,0,0,0,0,0,0,0,0,0,0,0,0,
0,0,0,0xbf75,0,0,0,0,0,0,0,0,0,0,0,0,
0,0,0xbf69,0x3e97,0,0,0,0,0,0,0,0,0,0,0,0,
0,0,0x3f10,0x3f46,0,0,0,0,0,0,0,0,0,0,0,0,
0,0,0x3f10,0xbf46,0,0,0,0,0,0,0,0,0,0,0,0,
0,0,0xbf69,0xbe97,0,0,0,0,0,0,0,0,0,0,0,0,
0,0,0,0x3f75,0,0,0,0,0,0,0,0,0,0,0,0,
0,0,0xbf10,0xbf46,0,0,0,0,0,0,0,0,0,0,0,0,
0,0,0xbf10,0x3f46,0,0,0,0,0,0,0,0,0,0,0,0,
0,0,0x3f69,0x3e97,0,0,0,0,0,0,0,0,0,0,0,0,
0,0,0,0xbf75,0,0,0,0,0,0,0,0,0,0,0,0,
0,0,0xbf69,0x3e97,0,0,0,0,0,0,0,0,0,0,0,0,
0,0,0x3f10,0x3f46,0,0,0,0,0,0,0,0,0,0,0,0,
0,0,0x3f10,0xbf46,0,0,0,0,0,0,0,0,0,0,0,0,
0,0,0xbf69,0xbe97,0,0,0,0,0,0,0,0,0,0,0,0,
0,0,0,0x3f75,0,0,0,0,0,0,0,0,0,0,0,0,
0,0,0x3f69,0xbe97,0,0,0,0,0,0,0,0,0,0,0,0,
0,0,0xbf10,0xbf46,0,0,0,0,0,0,0,0,0,0,0,0,
0,0,0xbf10,0x3f46,0,0,0,0,0,0,0,0,0,0,0,0,
0,0,0x3f69,0x3e97,0,0,0,0,0,0,0,0,0,0,0,0,
0,0,0,0xbf75,0,0,0,0,0,0,0,0,0,0,0,0,
0,0,0xbf69,0x3e97,0,0,0,0,0,0,0,0,0,0,0,0,
0,0,0x3f10,0x3f46,0,0,0,0,0,0,0,0,0,0,0,0,
0x3e973f75,0x3f690000,0x3ede3f72,0x3f5abe19,0xbf46bf46,0xbf103f10,0xbf5abf2d,0xbede3f2d,0x3f753e97,0xbf69,0x3f723e19,0xbe19bf72,0x3e193e97,0xbf723f69,0xbf69,0xbf75be97,
0x3f103f75,0x3f460000,0x3f5a3f5a,0x3edebede,0xbf69be97,0x3e973f69,0xbf2d3e19,0x3f2d3f72,0xbf46,0xbf75bf10,0xbedebf72,0xbf5abe19,0x3e193f46,0xbf72bf10,0xbe97bf69,0xbf69be97,
0x3f463f75,0x3f100000,0x3f723f2d,0xbe19bf2d,0xbe973e97,0x3f693f69,0x3ede3f5a,0x3f5a3ede,0xbf75bf46,0x3f10,0xbf2dbe19,0x3f2d3f72,0x3e19bf46,0xbf72bf10,0xbf10bf69,0xbf46be97,
0x3f693f75,0x3e970000,0x3f2d3ede,0xbf2dbf5a,0x3f103f46,0x3f463f10,0x3f723f5a,0xbe19bede,0x3e97,0x3f753f69,0x3f5a3f72,0x3ede3e19,0x3e19be97,0xbf723f69,0xbf46bf69,0xbf10be97,
0x3f753f75,0,0xbe19be19,0xbf72bf72,0x3f753f75,0,0xbe19be19,0xbf72bf72,0x3f753f75,0,0xbe19be19,0xbf72bf72,0xbe193f75,0xbf720000,0xbf69bf69,0x3e973e97,
0x3f693f75,0xbe970000,0xbf2dbede,0xbf2dbf5a,0x3f103f46,0xbf46bf10,0xbf72bf5a,0xbe19bede,0x3e97,0xbf75bf69,0xbf5abf72,0x3ede3e19,0xbe19be97,0xbf72bf69,0xbf46bf69,0x3f103e97,
0x3f463f75,0xbf100000,0xbf72bf2d,0xbe19bf2d,0xbe973e97,0xbf69bf69,0xbedebf5a,0x3f5a3ede,0xbf75bf46,0xbf10,0x3f2d3e19,0x3f2d3f72,0xbe19bf46,0xbf723f10,0xbf10bf69,0x3f463e97,
0x3f103f75,0xbf460000,0xbf5abf5a,0x3edebede,0xbf69be97,0xbe97bf69,0x3f2dbe19,0x3f2d3f72,0xbf46,0x3f753f10,0x3ede3f72,0xbf5abe19,0xbe193f46,0xbf723f10,0xbe97bf69,0x3f693e97,
0x3e973f75,0xbf690000,0xbedebf72,0x3f5abe19,0xbf46bf46,0x3f10bf10,0x3f5a3f2d,0xbede3f2d,0x3f753e97,0x3f69,0xbf72be19,0xbe19bf72,0xbe193e97,0xbf72bf69,0xbf69,0x3f753e97,
0x3f75,0xbf750000,0x3e19bf72,0x3f723e19,0xbf75,0x3f750000,0xbe193f72,0xbf72be19,0x3f75,0xbf750000,0x3e19bf72,0x3f723e19,0xbe19bf75,0xbf720000,0x3e97bf69,0x3f693e97,
0xbe973f75,0xbf690000,0x3f2dbf5a,0x3f2d3ede,0x3f46bf46,0x3f103f10,0xbf723ede,0xbe19bf5a,0xbf753e97,0xbf69,0x3f5a3e19,0xbede3f72,0xbe193e97,0xbf723f69,0x3f10bf69,0x3f463e97,
0xbf103f75,0xbf460000,0x3f72bf2d,0x3e193f2d,0x3f69be97,0xbe973f69,0xbedebede,0x3f5abf5a,0xbf46,0x3f75bf10,0xbf2d3f72,0xbf2dbe19,0xbe193f46,0xbf72bf10,0x3f46bf69,0x3f103e97,
0xbf463f75,0xbf100000,0x3f5abede,0xbede3f5a,0x3e973e97,0xbf693f69,0x3f2dbf72,0x3f2dbe19,0x3f75bf46,0x3f10,0xbedebe19,0x3f5abf72,0xbe19bf46,0xbf72bf10,0x3f69bf69,0x3e973e97,
0xbf693f75,0xbe970000,0x3edebe19,0xbf5a3f72,0xbf103f46,0xbf463f10,0x3f5abf2d,0xbede3f2d,0x3e97,0xbf753f69,0x3f72bf72,0x3e193e19,0xbe19be97,0xbf723f69,0x3f75bf69,0x3e97,
0xbf753f75,0,0xbe193e19,0xbf723f72,0xbf753f75,0,0xbe193e19,0xbf723f72,0xbf753f75,0,0xbe193e19,0xbf723f72,0xbe193f75,0xbf720000,0x3f69bf69,0xbe973e97,
0xbf693f75,0x3e970000,0xbf2d3ede,0xbf2d3f5a,0xbf103f46,0x3f46bf10,0xbf723f5a,0xbe193ede,0x3e97,0x3f75bf69,0xbf5a3f72,0x3edebe19,0xbe19be97,0xbf72bf69,0x3f46bf69,0xbf103e97,
0xbf463f75,0x3f100000,0xbf723f2d,0xbe193f2d,0x3e973e97,0x3f69bf69,0xbede3f5a,0x3f5abede,0x3f75bf46,0xbf10,0x3f2dbe19,0x3f2dbf72,0xbe19bf46,0xbf723f10,0x3f10bf69,0xbf463e97,
0xbf103f75,0x3f460000,0xbf5a3f5a,0x3ede3ede,0x3f69be97,0x3e97bf69,0x3f2d3e19,0x3f2dbf72,0xbf46,0xbf753f10,0x3edebf72,0xbf5a3e19,0xbe193f46,0xbf723f10,0x3e97bf69,0xbf693e97,
0xbe973f75,0x3f690000,0xbede3f72,0x3f5a3e19,0x3f46bf46,0xbf10bf10,0x3f5abf2d,0xbedebf2d,0xbf753e97,0x3f69,0xbf723e19,0xbe193f72,0xbe193e97,0xbf72bf69,0xbf69,0xbf753e97,
0x3f75,0x3f750000,0x3e193f72,0x3f72be19,0xbf75,0xbf750000,0xbe19bf72,0xbf723e19,0x3f75,0x3f750000,0x3e193f72,0x3f72be19,0xbe19bf75,0xbf720000,0xbe97bf69,0xbf693e97,
0x3e973f75,0x3f690000,0x3f2d3f5a,0x3f2dbede,0xbf46bf46,0xbf103f10,0xbf72bede,0xbe193f5a,0x3f753e97,0xbf69,0x3f5abe19,0xbedebf72,0xbe193e97,0xbf723f69,0xbf10bf69,0xbf463e97,
0x3f103f75,0x3f460000,0x3f723f2d,0x3e19bf2d,0xbf69be97,0x3e973f69,0xbede3ede,0x3f5a3f5a,0xbf46,0xbf75bf10,0xbf2dbf72,0xbf2d3e19,0xbe193f46,0xbf72bf10,0xbf46bf69,0xbf103e97,
0x3f463f75,0x3f100000,0x3f5a3ede,0xbedebf5a,0xbe973e97,0x3f693f69,0x3f2d3f72,0x3f2d3e19,0xbf75bf46,0x3f10,0xbede3e19,0x3f5a3f72,0xbe19bf46,0xbf72bf10,0xbf69bf69,0xbe973e97,
0x3f693f75,0x3e970000,0x3ede3e19,0xbf5abf72,0x3f103f46,0x3f463f10,0x3f5a3f2d,0xbedebf2d,0x3e97,0x3f753f69,0x3f723f72,0x3e19be19,0xbe19be97,0xbf723f69,0xbf75bf69,0x3e97,
0x3f753f75,0,0xbedebede,0xbf5abf5a,0x3f753f75,0,0xbedebede,0xbf5abf5a,0x3f753f75,0,0xbedebede,0xbf5abf5a,0xbede3f75,0xbf5a0000,0xbf10bf10,0x3f463f46,
0x3f693f75,0xbe970000,0xbf5abf2d,0xbedebf2d,0x3f103f46,0xbf46bf10,0xbf72bf72,0x3e19be19,0x3e97,0xbf75bf69,0xbf2dbf5a,0x3f2d3ede,0xbedebe97,0xbf5abf69,0xbe97bf10,0x3f693f46,
0x3f463f75,0xbf100000,0xbf72bf5a,0x3e19bede,0xbe973e97,0xbf69bf69,0xbe19bf2d,0x3f723f2d,0xbf75bf46,0xbf10,0x3f5a3ede,0x3ede3f5a,0xbedebf46,0xbf5a3f10,0xbf10,0x3f753f46,
0x3f103f75,0xbf460000,0xbf2dbf72,0x3f2dbe19,0xbf69be97,0xbe97bf69,0x3f5a3e19,0x3ede3f72,0xbf46,0x3f753f10,0x3e193f5a,0xbf72bede,0xbede3f46,0xbf5a3f10,0x3e97bf10,0x3f693f46,
0x3e973f75,0xbf690000,0xbe19bf72,0x3f723e19,0xbf46bf46,0x3f10bf10,0x3f2d3f5a,0xbf2d3ede,0x3f753e97,0x3f69,0xbf72bede,0x3e19bf5a,0xbede3e97,0xbf5abf69,0x3f10bf10,0x3f463f46,
0x3f75,0xbf750000,0x3edebf5a,0x3f5a3ede,0xbf75,0x3f750000,0xbede3f5a,0xbf5abede,0x3f75,0xbf750000,0x3edebf5a,0x3f5a3ede,0xbedebf75,0xbf5a0000,0x3f46bf10,0x3f103f46,
0xbe973f75,0xbf690000,0x3f5abf2d,0x3ede3f2d,0x3f46bf46,0x3f103f10,0xbf723e19,0x3e19bf72,0xbf753e97,0xbf69,0x3f2d3ede,0xbf2d3f5a,0xbede3e97,0xbf5a3f69,0x3f69bf10,0x3e973f46,
0xbf103f75,0xbf460000,0x3f72bede,0xbe193f5a,0x3f69be97,0xbe973f69,0xbe19bf2d,0x3f72bf2d,0xbf46,0x3f75bf10,0xbf5a3f5a,0xbedebede,0xbede3f46,0xbf5abf10,0x3f75bf10,0x3f46,
0x3f103f69,0x3f46be97,0x3f2d3f5a,0x3f2dbede,0xbf69bf10,0xbe973f46,0xbf72bede,0xbe193f5a,0xbede0000,0x3f5abf75,0xbe973f46,0x3f693f10,0xbe19bf72,0xbf72be19,0xbe97bf75,0xbf690000,
0x3f753f10,0xbf46,0x3f5a3e19,0xbedebf72,0xbe973f10,0x3f693f46,0x3e193f5a,0x3f723ede,0xbedebf69,0x3f5a3e97,0x3f46,0x3f753f10,0xbf2dbf72,0xbf2d3e19,0xbf69bf46,0xbe973f10,
0x3f100000,0xbf46bf75,0xbe19bf2d,0xbf72bf2d,0x3f693f69,0x3e97be97,0x3f5a3ede,0xbedebf5a,0xbede3f10,0x3f5a3f46,0x3e973f46,0x3f693f10,0xbf72bf5a,0xbe193ede,0xbf46be97,0x3f103f69,
0xbe97bf10,0xbf69bf46,0xbf72bf72,0xbe193e19,0x3e970000,0xbf69bf75,0xbf2dbf5a,0xbf2dbede,0xbede3f10,0x3f5abf46,0x3f103f46,0x3f463f10,0xbf5abf2d,0x3ede3f2d,0x3e97,0x3f753f69,
0xbf69bf69,0x3e973e97,0x3ede3ede,0x3f5a3f5a,0xbf69bf69,0x3e973e97,0x3ede3ede,0x3f5a3f5a,0x3edebf69,0x3f5a3e97,0x3f463f46,0xbf10bf10,0x3ede3ede,0x3f5a3f5a,0x3f463f46,0xbf10bf10,
0xbe97bf10,0x3f693f46,0x3f723f72,0xbe193e19,0x3e970000,0x3f693f75,0x3f2d3f5a,0xbf2dbede,0x3ede3f10,0x3f5a3f46,0x3f103f46,0xbf46bf10,0x3f5a3f2d,0x3ede3f2d,0x3e97,0xbf75bf69,
0x3f100000,0x3f463f75,0x3e193f2d,0xbf72bf2d,0x3f693f69,0xbe973e97,0xbf5abede,0xbedebf5a,0x3ede3f10,0x3f5abf46,0x3e973f46,0xbf69bf10,0x3f723f5a,0xbe193ede,0xbf46be97,0xbf10bf69,
0x3f753f10,0x3f46,0xbf5abe19,0xbedebf72,0xbe973f10,0xbf69bf46,0xbe19bf5a,0x3f723ede,0x3edebf69,0x3f5abe97,0x3f46,0xbf75bf10,0x3f2d3f72,0xbf2d3e19,0xbf69bf46,0x3e97bf10,
0x3f103f69,0xbf463e97,0xbf2dbf5a,0x3f2dbede,0xbf69bf10,0x3e97bf46,0x3f723ede,0xbe193f5a,0x3ede0000,0x3f5a3f75,0xbe973f46,0xbf69bf10,0x3e193f72,0xbf72be19,0xbe97bf75,0x3f690000,
0xbe973f69,0xbf69be97,0x3edebf5a,0x3f5a3ede,0x3e97bf69,0x3f693e97,0xbede3f5a,0xbf5abede,0x3ede3f69,0x3f5abe97,0xbf103f46,0xbf46bf10,0xbede3f5a,0xbf5abede,0x3f10bf46,0x3f463f10,
0xbf693f10,0xbe97bf46,0x3f72be19,0xbe193f72,0x3f690000,0xbe973f75,0xbf2dbede,0x3f2dbf5a,0x3edebf10,0x3f5abf46,0xbf463f46,0xbf10bf10,0xbf5a3f2d,0xbedebf2d,0x3f75be97,0x3f69,
0xbf460000,0x3f10bf75,0x3e193f2d,0xbf723f2d,0xbe973f69,0xbf693e97,0x3f5abf5a,0x3ede3ede,0x3edebf10,0x3f5a3f46,0xbf693f46,0xbe97bf10,0xbf723ede,0x3e19bf5a,0x3f103e97,0xbf463f69,
0xbf10,0x3f75bf46,0xbf5a3f72,0xbedebe19,0xbf693f10,0x3e97bf46,0x3e193ede,0xbf723f5a,0x3ede3f69,0x3f5a3e97,0xbf753f46,0xbf10,0xbf2d3e19,0x3f2dbf72,0xbe973f46,0xbf693f10,
0x3f46bf69,0x3f10be97,0xbf2d3ede,0x3f2dbf5a,0x3e97bf10,0x3f69bf46,0xbf723f5a,0x3e19bede,0x3ede0000,0x3f5abf75,0xbf693f46,0x3e97bf10,0xbe19be19,0x3f72bf72,0xbf693f75,0xbe970000,
0x3f69bf69,0xbe973e97,0x3edebede,0x3f5abf5a,0x3f69bf69,0xbe973e97,0x3edebede,0x3f5abf5a,0x3edebf69,0x3f5a3e97,0xbf463f46,0x3f10bf10,0x3edebede,0x3f5abf5a,0xbf463f46,0x3f10bf10,
0x3e97bf10,0xbf693f46,0x3f72bf72,0xbe19be19,0xbe970000,0xbf693f75,0x3f2dbf5a,0xbf2d3ede,0x3ede3f10,0x3f5a3f46,0xbf103f46,0x3f46bf10,0x3f5abf2d,0x3edebf2d,0x3e97,0x3f75bf69,
0xbf100000,0xbf463f75,0x3e19bf2d,0xbf723f2d,0xbf693f69,0x3e973e97,0xbf5a3ede,0xbede3f5a,0x3ede3f10,0x3f5abf46,0xbe973f46,0x3f69bf10,0x3f72bf5a,0xbe19bede,0x3f46be97,0x3f10bf69,
0xbf753f10,0x3f46,0xbf5a3e19,0xbede3f72,0x3e973f10,0x3f69bf46,0xbe193f5a,0x3f72bede,0x3edebf69,0x3f5abe97,0x3f46,0x3f75bf10,0x3f2dbf72,0xbf2dbe19,0x3f69bf46,0xbe97bf10,
0xbf103f69,0x3f463e97,0xbf2d3f5a,0x3f2d3ede,0x3f69bf10,0xbe97bf46,0x3f72bede,0xbe19bf5a,0x3ede0000,0x3f5a3f75,0x3e973f46,0x3f69bf10,0x3e19bf72,0xbf723e19,0x3e97bf75,0xbf690000,
0x3e973f69,0x3f69be97,0x3ede3f5a,0x3f5abede,0xbe97bf69,0xbf693e97,0xbedebf5a,0xbf5a3ede,0x3ede3f69,0x3f5abe97,0x3f103f46,0x3f46bf10,0xbedebf5a,0xbf5a3ede,0xbf10bf46,0xbf463f10,
0x3f693f10,0x3e97bf46,0x3f723e19,0xbe19bf72,0xbf690000,0x3e973f75,0xbf2d3ede,0x3f2d3f5a,0x3edebf10,0x3f5abf46,0x3f463f46,0x3f10bf10,0xbf5abf2d,0xbede3f2d,0xbf75be97,0x3f69,
0x3f460000,0xbf10bf75,0x3e19bf2d,0xbf72bf2d,0x3e973f69,0x3f693e97,0x3f5a3f5a,0x3edebede,0x3edebf10,0x3f5a3f46,0x3f693f46,0x3e97bf10,0xbf72bede,0x3e193f5a,0xbf103e97,0x3f463f69,
0xbf10,0xbf75bf46,0xbf5abf72,0xbede3e19,0x3f693f10,0xbe97bf46,0x3e19bede,0xbf72bf5a,0x3ede3f69,0x3f5a3e97,0x3f753f46,0xbf10,0xbf2dbe19,0x3f2d3f72,0x3e973f46,0x3f693f10,
0xbf46bf69,0xbf10be97,0xbf2dbede,0x3f2d3f5a,0xbe97bf10,0xbf69bf46,0xbf72bf5a,0x3e193ede,0x3ede0000,0x3f5abf75,0x3f693f46,0xbe97bf10,0xbe193e19,0x3f723f72,0x3f693f75,0x3e970000,
0xbf10bf10,0x3f463f46,0x3f723f72,0x3e193e19,0xbf10bf10,0x3f463f46,0x3f723f72,0x3e193e19,0x3f72bf10,0x3e193f46,0xbe97be97,0xbf69bf69,0x3f723f72,0x3e193e19,0xbe97be97,0xbf69bf69,
0x3e970000,0x3f693f75,0x3ede3f2d,0xbf5abf2d,0x3f463f10,0x3f103f46,0xbe193e19,0xbf72bf72,0x3f723f69,0x3e193e97,0xbf10be97,0xbf46bf69,0x3f5a3f72,0xbedebe19,0xbf69bf46,0xbe97bf10,
0x3f693f10,0x3e973f46,0xbf2dbe19,0xbf2dbf72,0x3f103f69,0xbf46be97,0xbf5abf72,0x3edebe19,0x3f720000,0x3e19bf75,0xbf46be97,0xbf10bf69,0x3ede3f5a,0xbf5abede,0xbf46bf75,0x3f100000,
0x3f463f69,0xbf103e97,0xbf5abf5a,0x3edebede,0xbf460000,0xbf10bf75,0x3f2dbe19,0x3f2d3f72,0x3f72bf69,0x3e193e97,0xbf69be97,0xbe97bf69,0xbe193f2d,0xbf72bf2d,0xbf46,0x3f753f10,
0x3f69,0xbf75be97,0x3e19bf5a,0x3f723ede,0xbf10bf69,0x3f46be97,0x3ede3f72,0xbf5a3e19,0x3f723f10,0x3e193f46,0xbf75be97,0xbf69,0xbf2d3ede,0xbf2dbf5a,0x3f46be97,0x3f103f69,
0xbf463f10,0xbf10bf46,0x3f72be19,0x3e193f72,0x3f46bf10,0x3f103f46,0xbf723e19,0xbe19bf72,0x3f723f10,0x3e19bf46,0xbf69be97,0x3e97bf69,0xbf723e19,0xbe19bf72,0x3f693e97,0xbe973f69,
0xbf690000,0x3e97bf75,0x3ede3f2d,0xbf5a3f2d,0x3f103f10,0xbf463f46,0x3e19bf72,0x3f72be19,0x3f72bf69,0x3e19be97,0xbf46be97,0x3f10bf69,0xbf5abe19,0x3edebf72,0x3e973f46,0xbf693f10,
0xbe97bf10,0x3f69bf46,0xbf2d3f72,0xbf2dbe19,0xbf463f69,0xbf10be97,0x3f5abe19,0xbede3f72,0x3f720000,0x3e193f75,0xbf10be97,0x3f46bf69,0xbedebede,0x3f5abf5a,0xbf103f75,0xbf460000,
0x3f463f46,0x3f10bf10,0x3f5a3f2d,0x3edebf2d,0x3f2dbe97,0xbf2d3f69,0x3f10bf10,0xbf46bf46,0xbe193f5a,0x3f723ede,0x3f69,0x3f753e97,0xbedebf72,0xbf5a3e19,0xbf10bf69,0xbf463e97,
0x3f10be97,0xbf46bf69,0x3e19bf2d,0xbf72bf2d,0x3f2d3f75,0xbf2d0000,0x3e97bf10,0xbf69bf46,0x3ede3f72,0x3f5a3e19,0x3f463f69,0x3f10be97,0xbf72bede,0x3e193f5a,0xbf460000,0x3f103f75,
0xbf46bf75,0xbf100000,0xbf72bf2d,0x3e193f2d,0x3f2dbe97,0xbf2dbf69,0xbf10,0xbf75bf46,0x3f5a3f72,0x3edebe19,0x3f693f10,0xbe97bf46,0xbe193ede,0x3f723f5a,0x3f103f69,0x3f463e97,
0xbf10be97,0x3f463f69,0x3ede3f2d,0x3f5a3f2d,0x3f2dbf46,0xbf2d3f10,0xbe97bf10,0xbf69bf46,0x3f723f5a,0xbe19bede,0x3e970000,0xbf69bf75,0x3f5a3f72,0x3ede3e19,0x3f463f10,0xbf10bf46,
0x3f463f46,0xbf10bf10,0xbf2dbf2d,0xbf2dbf2d,0xbf2d3f46,0xbf2dbf10,0xbf10bf10,0x3f463f46,0xbf2dbf2d,0xbf2dbf2d,0xbf10bf10,0x3f463f46,0xbf2dbf2d,0xbf2dbf2d,0xbf10bf10,0x3f463f46,
0xbf10be97,0xbf46bf69,0xbedebf2d,0x3f5a3f2d,0xbf2dbf46,0xbf2dbf10,0xbe97bf10,0x3f693f46,0xbf72bf5a,0xbe19bede,0x3e970000,0x3f693f75,0xbf5abf72,0x3ede3e19,0x3f463f10,0x3f103f46,
0xbf46bf75,0x3f100000,0x3f723f2d,0x3e193f2d,0xbf2dbe97,0xbf2d3f69,0xbf10,0x3f753f46,0xbf5abf72,0x3edebe19,0x3f693f10,0x3e973f46,0x3e19bede,0x3f723f5a,0x3f103f69,0xbf46be97,
0x3f10be97,0x3f463f69,0xbe193f2d,0xbf72bf2d,0xbf2d3f75,0xbf2d0000,0x3e97bf10,0x3f693f46,0xbedebf72,0x3f5a3e19,0x3f463f69,0xbf103e97,0x3f723ede,0x3e193f5a,0xbf460000,0xbf10bf75,
0x3f463f46,0xbf103f10,0xbf5abf2d,0x3edebf2d,0xbf2dbe97,0xbf2dbf69,0x3f10bf10,0x3f463f46,0x3e19bf5a,0x3f723ede,0x3f69,0xbf75be97,0x3ede3f72,0xbf5a3e19,0xbf10bf69,0x3f46be97,
0xbf103f46,0xbf46bf10,0x3f2dbf2d,0x3f2d3f2d,0xbf2dbf46,0xbf2d3f10,0x3f46bf10,0x3f103f46,0x3f2dbf2d,0x3f2d3f2d,0xbf463f10,0xbf10bf46,0xbf2d3f2d,0xbf2dbf2d,0x3f46bf10,0x3f103f46,
0xbf46be97,0x3f10bf69,0x3ede3f2d,0xbf5a3f2d,0xbf2d3f46,0xbf2d3f10,0x3f69bf10,0x3e973f46,0x3f72bede,0x3e193f5a,0xbf690000,0x3e97bf75,0xbf5abe19,0x3edebf72,0x3f103f10,0xbf463f46,
0x3f10bf75,0x3f460000,0xbf723f2d,0xbe19bf2d,0xbf2d3e97,0xbf2dbf69,0x3f75bf10,0x3f46,0x3f5abe19,0xbede3f72,0xbe97bf10,0x3f69bf46,0x3e19bf5a,0x3f72bede,0xbf463f69,0xbf10be97,
0x3f46be97,0xbf103f69,0x3e19bf2d,0x3f72bf2d,0xbf2dbf75,0xbf2d0000,0x3f69bf10,0xbe973f46,0x3ede3e19,0xbf5a3f72,0x3f10bf69,0x3f46be97,0x3f72bf5a,0x3e193ede,0xbf100000,0x3f46bf75,
0xbf103f46,0xbf463f10,0x3f5abf2d,0xbede3f2d,0xbf2d3e97,0xbf2d3f69,0x3f46bf10,0xbf103f46,0xbe193ede,0xbf723f5a,0x3f75bf69,0x3e97,0x3edebe19,0xbf5a3f72,0x3f46bf69,0x3f10be97,
0xbf463f46,0x3f10bf10,0xbf2d3f2d,0xbf2d3f2d,0xbf2d3f46,0xbf2dbf10,0x3f10bf10,0xbf463f46,0xbf2d3f2d,0xbf2d3f2d,0x3f10bf10,0xbf463f46,0xbf2d3f2d,0xbf2d3f2d,0x3f10bf10,0xbf463f46,
0x3f10be97,0x3f46bf69,0xbede3f2d,0x3f5abf2d,0xbf2dbf46,0xbf2dbf10,0x3e97bf10,0xbf693f46,0xbf723f5a,0xbe193ede,0xbe970000,0xbf693f75,0xbf5a3f72,0x3edebe19,0xbf463f10,0xbf103f46,
0x3f46bf75,0xbf100000,0x3f72bf2d,0x3e19bf2d,0xbf2dbe97,0xbf2d3f69,0xbf10,0xbf753f46,0xbf5a3f72,0x3ede3e19,0xbf693f10,0xbe973f46,0x3e193ede,0x3f72bf5a,0xbf103f69,0x3f46be97,
0xbf10be97,0xbf463f69,0xbe19bf2d,0xbf723f2d,0xbf2d3f75,0xbf2d0000,0xbe97bf10,0xbf693f46,0xbede3f72,0x3f5abe19,0xbf463f69,0x3f103e97,0x3f72bede,0x3e19bf5a,0x3f460000,0x3f10bf75,
0xbf463f46,0x3f103f10,0xbf5a3f2d,0x3ede3f2d,0xbf2dbe97,0xbf2dbf69,0xbf10bf10,0xbf463f46,0x3e193f5a,0x3f72bede,0x3f69,0x3f75be97,0x3edebf72,0xbf5abe19,0x3f10bf69,0xbf46be97,
0x3f103f46,0x3f46bf10,0x3f2d3f2d,0x3f2dbf2d,0xbf2dbf46,0xbf2d3f10,0xbf46bf10,0xbf103f46,0x3f2d3f2d,0x3f2dbf2d,0x3f463f10,0x3f10bf46,0xbf2dbf2d,0xbf2d3f2d,0xbf46bf10,0xbf103f46,
0x3f46be97,0xbf10bf69,0x3edebf2d,0xbf5abf2d,0xbf2d3f46,0xbf2d3f10,0xbf69bf10,0xbe973f46,0x3f723ede,0x3e19bf5a,0x3f690000,0xbe97bf75,0xbf5a3e19,0x3ede3f72,0xbf103f10,0x3f463f46,
0xbf10bf75,0xbf460000,0xbf72bf2d,0xbe193f2d,0xbf2d3e97,0xbf2dbf69,0xbf75bf10,0x3f46,0x3f5a3e19,0xbedebf72,0x3e97bf10,0xbf69bf46,0x3e193f5a,0x3f723ede,0x3f463f69,0x3f10be97,
0xbf46be97,0x3f103f69,0x3e193f2d,0x3f723f2d,0xbf2dbf75,0xbf2d0000,0xbf69bf10,0x3e973f46,0x3edebe19,0xbf5abf72,0xbf10bf69,0xbf46be97,0x3f723f5a,0x3e19bede,0x3f100000,0xbf46bf75,
0x3f103f46,0x3f463f10,0x3f5a3f2d,0xbedebf2d,0xbf2d3e97,0xbf2d3f69,0xbf46bf10,0x3f103f46,0xbe19bede,0xbf72bf5a,0xbf75bf69,0x3e97,0x3ede3e19,0xbf5abf72,0xbf46bf69,0xbf10be97,
0xbe97be97,0xbf69bf69,0xbf2dbf2d,0x3f2d3f2d,0xbf2dbe97,0x3f2dbf69,0x3f693f69,0x3e973e97,0xbf2dbf2d,0x3f2d3f2d,0x3f693f69,0x3e973e97,0xbf2dbf2d,0x3f2d3f2d,0x3f693f69,0x3e973e97,
0xbf69bf75,0x3e970000,0x3f5a3f2d,0x3ede3f2d,0xbf2dbf46,0x3f2d3f10,0x3f753f69,0x3e97,0xbe19bede,0x3f723f5a,0x3f463f69,0xbf10be97,0x3ede3e19,0x3f5a3f72,0x3e973f10,0xbf69bf46,
0x3e97be97,0x3f693f69,0x3e193f2d,0xbf72bf2d,0xbf2d3f46,0x3f2d3f10,0x3f693f69,0xbe973e97,0x3edebe19,0x3f5a3f72,0x3f10,0xbf75bf46,0x3f723f5a,0xbe193ede,0xbf69bf10,0xbe97bf46,
0x3f693f46,0xbe973f10,0xbf72bf2d,0x3e19bf2d,0xbf2d3e97,0x3f2dbf69,0x3f463f69,0xbf103e97,0x3f5a3e19,0x3ede3f72,0xbf460000,0xbf10bf75,0x3e193f5a,0xbf72bede,0xbe97bf69,0x3f693e97,
0xbe973f46,0xbf69bf10,0x3edebf2d,0x3f5a3f2d,0xbf2dbf75,0x3f2d0000,0x3f103f69,0xbf463e97,0x3f723ede,0xbe193f5a,0xbf69bf10,0x3e97bf46,0xbf5a3e19,0xbedebf72,0x3f690000,0x3e973f75,
0xbf69be97,0x3e97bf69,0x3f2d3f2d,0xbf2d3f2d,0xbf2d3e97,0x3f2d3f69,0x3e973f69,0xbf693e97,0x3f2d3f2d,0xbf2d3f2d,0xbe97bf69,0x3f69be97,0xbf2dbf2d,0x3f2dbf2d,0x3e973f69,0xbf693e97,
0x3e97bf75,0x3f690000,0xbf5a3f2d,0xbedebf2d,0xbf2d3f46,0x3f2dbf10,0x3f69,0xbf753e97,0x3e193f5a,0xbf723ede,0x3f10bf69,0x3f463e97,0x3edebf72,0x3f5a3e19,0xbf693f10,0xbe97bf46,
0x3f69be97,0xbe973f69,0xbe19bf2d,0x3f72bf2d,0xbf2dbf46,0x3f2dbf10,0xbe973f69,0xbf693e97,0xbede3f72,0xbf5a3e19,0x3f75bf10,0x3f46,0x3f72bede,0xbe193f5a,0xbe97bf10,0x3f69bf46,
0,0,0x3f10,0xbf46,0,0,0,0,0,0,0,0,0,0,0,0,
0,0,0xbf69,0xbe97,0,0,0,0,0,0,0,0,0,0,0,0,
0,0,0,0x3f75,0,0,0,0,0,0,0,0,0,0,0,0,
0,0,0x3f69,0xbe97,0,0,0,0,0,0,0,0,0,0,0,0,
0,0,0xbf10,0x3f46,0,0,0,0,0,0,0,0,0,0,0,0,
0,0,0x3f69,0x3e97,0,0,0,0,0,0,0,0,0,0,0,0,
0,0,0,0xbf75,0,0,0,0,0,0,0,0,0,0,0,0,
0,0,0xbf69,0x3e97,0,0,0,0,0,0,0,0,0,0,0,0,
0,0,0x3f10,0x3f46,0,0,0,0,0,0,0,0,0,0,0,0,
0,0,0x3f10,0xbf46,0,0,0,0,0,0,0,0,0,0,0,0,
0,0,0xbf69,0xbe97,0,0,0,0,0,0,0,0,0,0,0,0,
0,0,0,0x3f75,0,0,0,0,0,0,0,0,0,0,0,0,
0,0,0x3f69,0xbe97,0,0,0,0,0,0,0,0,0,0,0,0,
0,0,0xbf10,0xbf46,0,0,0,0,0,0,0,0,0,0,0,0,
0,0,0xbf10,0x3f46,0,0,0,0,0,0,0,0,0,0,0,0,
0,0,0x3f69,0x3e97,0,0,0,0,0,0,0,0,0,0,0,0,
0,0,0,0xbf75,0,0,0,0,0,0,0,0,0,0,0,0,
0,0,0xbf69,0x3e97,0,0,0,0,0,0,0,0,0,0,0,0,
0,0,0x3f10,0x3f46,0,0,0,0,0,0,0,0,0,0,0,0,
0,0,0x3f10,0xbf46,0,0,0,0,0,0,0,0,0,0,0,0,
0,0,0xbf69,0xbe97,0,0,0,0,0,0,0,0,0,0,0,0,
0,0,0,0x3f75,0,0,0,0,0,0,0,0,0,0,0,0,
0,0,0x3f69,0xbe97,0,0,0,0,0,0,0,0,0,0,0,0,
0,0,0xbf10,0xbf46,0,0,0,0,0,0,0,0,0,0,0,0,
0,0,0x3f69,0x3e97,0,0,0,0,0,0,0,0,0,0,0,0,
0,0,0,0xbf75,0,0,0,0,0,0,0,0,0,0,0,0,
0,0,0xbf69,0x3e97,0,0,0,0,0,0,0,0,0,0,0,0,
0,0,0x3f10,0x3f46,0,0,0,0,0,0,0,0,0,0,0,0,
0,0,0x3f10,0xbf46,0,0,0,0,0,0,0,0,0,0,0,0,
0,0,0xbf69,0xbe97,0,0,0,0,0,0,0,0,0,0,0,0,
0,0,0,0x3f75,0,0,0,0,0,0,0,0,0,0,0,0,
0,0,0x3f69,0xbe97,0,0,0,0,0,0,0,0,0,0,0,0,
0xbf463f75,0xbf100000,0x3f2dbe19,0xbf2d3f72,0x3e973e97,0xbf693f69,0x3f5abf72,0x3ede3e19,0x3f75bf46,0x3f10,0xbe19bede,0x3f72bf5a,0xbedebf46,0xbf5abf10,0x3f69bf10,0xbe973f46,
0xbf693f75,0xbe970000,0x3e193e19,0xbf723f72,0xbf103f46,0xbf463f10,0x3f2dbede,0xbf2d3f5a,0x3e97,0xbf753f69,0x3f72bf5a,0xbe193ede,0xbedebe97,0xbf5a3f69,0x3f46bf10,0xbf103f46,
0xbf753f75,0,0xbede3ede,0xbf5a3f5a,0xbf753f75,0,0xbede3ede,0xbf5a3f5a,0xbf753f75,0,0xbede3ede,0xbf5a3f5a,0xbede3f75,0xbf5a0000,0x3f10bf10,0xbf463f46,
0xbf693f75,0x3e970000,0xbf5a3f2d,0xbede3f2d,0xbf103f46,0x3f46bf10,0xbf723f72,0x3e193e19,0x3e97,0x3f75bf69,0xbf2d3f5a,0x3f2dbede,0xbedebe97,0xbf5abf69,0x3e97bf10,0xbf693f46,
0xbf463f75,0x3f100000,0xbf723f5a,0x3e193ede,0x3e973e97,0x3f69bf69,0xbe193f2d,0x3f72bf2d,0x3f75bf46,0xbf10,0x3f5abede,0x3edebf5a,0xbedebf46,0xbf5a3f10,0xbf10,0xbf753f46,
0xbf103f75,0x3f460000,0xbf2d3f72,0x3f2d3e19,0x3f69be97,0x3e97bf69,0x3f5abe19,0x3edebf72,0xbf46,0xbf753f10,0x3e19bf5a,0xbf723ede,0xbede3f46,0xbf5a3f10,0xbe97bf10,0xbf693f46,
0xbe973f75,0x3f690000,0xbe193f72,0x3f72be19,0x3f46bf46,0xbf10bf10,0x3f2dbf5a,0xbf2dbede,0xbf753e97,0x3f69,0xbf723ede,0x3e193f5a,0xbede3e97,0xbf5abf69,0xbf10bf10,0xbf463f46,
0x3f75,0x3f750000,0x3ede3f5a,0x3f5abede,0xbf75,0xbf750000,0xbedebf5a,0xbf5a3ede,0x3f75,0x3f750000,0x3ede3f5a,0x3f5abede,0xbedebf75,0xbf5a0000,0xbf46bf10,0xbf103f46,
0x3e973f75,0x3f690000,0x3f5a3f2d,0x3edebf2d,0xbf46bf46,0xbf103f10,0xbf72be19,0x3e193f72,0x3f753e97,0xbf69,0x3f2dbede,0xbf2dbf5a,0xbede3e97,0xbf5a3f69,0xbf69bf10,0xbe973f46,
0x3f103f75,0x3f460000,0x3f723ede,0xbe19bf5a,0xbf69be97,0x3e973f69,0xbe193f2d,0x3f723f2d,0xbf46,0xbf75bf10,0xbf5abf5a,0xbede3ede,0xbede3f46,0xbf5abf10,0xbf75bf10,0x3f46,
0x3f463f75,0x3f100000,0x3f2d3e19,0xbf2dbf72,0xbe973e97,0x3f693f69,0x3f5a3f72,0x3edebe19,0xbf75bf46,0x3f10,0xbe193ede,0x3f723f5a,0xbedebf46,0xbf5abf10,0xbf69bf10,0x3e973f46,
0x3f693f75,0x3e970000,0x3e19be19,0xbf72bf72,0x3f103f46,0x3f463f10,0x3f2d3ede,0xbf2dbf5a,0x3e97,0x3f753f69,0x3f723f5a,0xbe19bede,0xbedebe97,0xbf5a3f69,0xbf46bf10,0x3f103f46,
0x3f753f75,0,0xbf2dbf2d,0xbf2dbf2d,0x3f753f75,0,0xbf2dbf2d,0xbf2dbf2d,0x3f753f75,0,0xbf2dbf2d,0xbf2dbf2d,0xbf2d3f75,0xbf2d0000,0,0x3f753f75,
0x3f693f75,0xbe970000,0xbf72bf5a,0xbe19bede,0x3f103f46,0xbf46bf10,0xbf5abf72,0x3ede3e19,0x3e97,0xbf75bf69,0xbedebf2d,0x3f5a3f2d,0xbf2dbe97,0xbf2dbf69,0x3e970000,0x3f693f75,
0x3f463f75,0xbf100000,0xbf5abf72,0x3edebe19,0xbe973e97,0xbf69bf69,0x3e19bede,0x3f723f5a,0xbf75bf46,0xbf10,0x3f723f2d,0x3e193f2d,0xbf2dbf46,0xbf2d3f10,0x3f100000,0x3f463f75,
0x3f103f75,0xbf460000,0xbedebf72,0x3f5a3e19,0xbf69be97,0xbe97bf69,0x3f723ede,0x3e193f5a,0xbf46,0x3f753f10,0xbe193f2d,0xbf72bf2d,0xbf2d3f46,0xbf2d3f10,0x3f460000,0x3f103f75,
0x3e973f75,0xbf690000,0x3e19bf5a,0x3f723ede,0xbf46bf46,0x3f10bf10,0x3ede3f72,0xbf5a3e19,0x3f753e97,0x3f69,0xbf5abf2d,0x3edebf2d,0xbf2d3e97,0xbf2dbf69,0x3f690000,0x3e973f75,
0x3f75,0xbf750000,0x3f2dbf2d,0x3f2d3f2d,0xbf75,0x3f750000,0xbf2d3f2d,0xbf2dbf2d,0x3f75,0xbf750000,0x3f2dbf2d,0x3f2d3f2d,0xbf2dbf75,0xbf2d0000,0x3f750000,0x3f75,
0xbe973f75,0xbf690000,0x3f72bede,0x3e193f5a,0x3f46bf46,0x3f103f10,0xbf5abe19,0x3edebf72,0xbf753e97,0xbf69,0x3ede3f2d,0xbf5a3f2d,0xbf2d3e97,0xbf2d3f69,0x3f690000,0xbe973f75,
0xbf103f75,0xbf460000,0x3f5abe19,0xbede3f72,0x3f69be97,0xbe973f69,0x3e19bf5a,0x3f72bede,0xbf46,0x3f75bf10,0xbf723f2d,0xbe19bf2d,0xbf2d3f46,0xbf2dbf10,0x3f460000,0xbf103f75,
0xbf463f75,0xbf100000,0x3ede3e19,0xbf5a3f72,0x3e973e97,0xbf693f69,0x3f72bf5a,0x3e193ede,0x3f75bf46,0x3f10,0x3e19bf2d,0x3f72bf2d,0xbf2dbf46,0xbf2dbf10,0x3f100000,0xbf463f75,
0xbf693f75,0xbe970000,0xbe193ede,0xbf723f5a,0xbf103f46,0xbf463f10,0x3edebe19,0xbf5a3f72,0x3e97,0xbf753f69,0x3f5abf2d,0xbede3f2d,0xbf2dbe97,0xbf2d3f69,0x3e970000,0xbf693f75,
0xbf753f75,0,0xbf2d3f2d,0xbf2d3f2d,0xbf753f75,0,0xbf2d3f2d,0xbf2d3f2d,0xbf753f75,0,0xbf2d3f2d,0xbf2d3f2d,0xbf2d3f75,0xbf2d0000,0,0xbf753f75,
0xbf693f75,0x3e970000,0xbf723f5a,0xbe193ede,0xbf103f46,0x3f46bf10,0xbf5a3f72,0x3edebe19,0x3e97,0x3f75bf69,0xbede3f2d,0x3f5abf2d,0xbf2dbe97,0xbf2dbf69,0xbe970000,0xbf693f75,
0xbf463f75,0x3f100000,0xbf5a3f72,0x3ede3e19,0x3e973e97,0x3f69bf69,0x3e193ede,0x3f72bf5a,0x3f75bf46,0xbf10,0x3f72bf2d,0x3e19bf2d,0xbf2dbf46,0xbf2d3f10,0xbf100000,0xbf463f75,
0xbf103f75,0x3f460000,0xbede3f72,0x3f5abe19,0x3f69be97,0x3e97bf69,0x3f72bede,0x3e19bf5a,0xbf46,0xbf753f10,0xbe19bf2d,0xbf723f2d,0xbf2d3f46,0xbf2d3f10,0xbf460000,0xbf103f75,
0xbe973f75,0x3f690000,0x3e193f5a,0x3f72bede,0x3f46bf46,0xbf10bf10,0x3edebf72,0xbf5abe19,0xbf753e97,0x3f69,0xbf5a3f2d,0x3ede3f2d,0xbf2d3e97,0xbf2dbf69,0xbf690000,0xbe973f75,
0x3f75,0x3f750000,0x3f2d3f2d,0x3f2dbf2d,0xbf75,0xbf750000,0xbf2dbf2d,0xbf2d3f2d,0x3f75,0x3f750000,0x3f2d3f2d,0x3f2dbf2d,0xbf2dbf75,0xbf2d0000,0xbf750000,0x3f75,
0x3e973f75,0x3f690000,0x3f723ede,0x3e19bf5a,0xbf46bf46,0xbf103f10,0xbf5a3e19,0x3ede3f72,0x3f753e97,0xbf69,0x3edebf2d,0xbf5abf2d,0xbf2d3e97,0xbf2d3f69,0xbf690000,0x3e973f75,
0x3f103f75,0x3f460000,0x3f5a3e19,0xbedebf72,0xbf69be97,0x3e973f69,0x3e193f5a,0x3f723ede,0xbf46,0xbf75bf10,0xbf72bf2d,0xbe193f2d,0xbf2d3f46,0xbf2dbf10,0xbf460000,0x3f103f75,
0x3f463f75,0x3f100000,0x3edebe19,0xbf5abf72,0xbe973e97,0x3f693f69,0x3f723f5a,0x3e19bede,0xbf75bf46,0x3f10,0x3e193f2d,0x3f723f2d,0xbf2dbf46,0xbf2dbf10,0xbf100000,0x3f463f75,
0x3f693f75,0x3e970000,0xbe19bede,0xbf72bf5a,0x3f103f46,0x3f463f10,0x3ede3e19,0xbf5abf72,0x3e97,0x3f753f69,0x3f5a3f2d,0xbedebf2d,0xbf2dbe97,0xbf2d3f69,0xbe970000,0x3f693f75,
0x3f10bf69,0x3f46be97,0xbf5a3ede,0x3edebf5a,0xbf100000,0x3f46bf75,0xbf2d3f72,0xbf2d3e19,0x3f723f69,0x3e19be97,0xbe97be97,0x3f69bf69,0x3e19bf2d,0x3f72bf2d,0xbf753f46,0xbf10,
0x3f75bf69,0x3e97,0x3e19bede,0x3f72bf5a,0x3f46bf69,0x3f10be97,0xbede3e19,0x3f5abf72,0x3f72bf10,0x3e19bf46,0xbe97,0x3f75bf69,0x3f2dbf5a,0x3f2dbede,0xbf103e97,0x3f46bf69,
0x3f10bf10,0xbf463f46,0x3f72bf72,0x3e19be19,0x3f10bf10,0xbf463f46,0x3f72bf72,0x3e19be19,0x3f72bf10,0x3e193f46,0x3e97be97,0x3f69bf69,0x3f72bf72,0x3e19be19,0x3e97be97,0x3f69bf69,
0xbe970000,0xbf693f75,0x3edebf2d,0xbf5a3f2d,0xbf463f10,0xbf103f46,0xbe19be19,0xbf723f72,0x3f723f69,0x3e193e97,0x3f10be97,0x3f46bf69,0x3f5abf72,0xbede3e19,0x3f69bf46,0x3e97bf10,
0xbf693f10,0xbe973f46,0xbf2d3e19,0xbf2d3f72,0xbf103f69,0x3f46be97,0xbf5a3f72,0x3ede3e19,0x3f720000,0x3e19bf75,0x3f46be97,0x3f10bf69,0x3edebf5a,0xbf5a3ede,0x3f46bf75,0xbf100000,
0xbf463f69,0x3f103e97,0xbf5a3f5a,0x3ede3ede,0x3f460000,0x3f10bf75,0x3f2d3e19,0x3f2dbf72,0x3f72bf69,0x3e193e97,0x3f69be97,0x3e97bf69,0xbe19bf2d,0xbf723f2d,0xbf46,0xbf753f10,
0x3f69,0x3f75be97,0x3e193f5a,0x3f72bede,0x3f10bf69,0xbf46be97,0x3edebf72,0xbf5abe19,0x3f723f10,0x3e193f46,0x3f75be97,0xbf69,0xbf2dbede,0xbf2d3f5a,0xbf46be97,0xbf103f69,
0x3f463f10,0x3f10bf46,0x3f723e19,0x3e19bf72,0xbf46bf10,0xbf103f46,0xbf72be19,0xbe193f72,0x3f723f10,0x3e19bf46,0x3f69be97,0xbe97bf69,0xbf72be19,0xbe193f72,0xbf693e97,0x3e973f69,
0x3f690000,0xbe97bf75,0x3edebf2d,0xbf5abf2d,0xbf103f10,0x3f463f46,0x3e193f72,0x3f723e19,0x3f72bf69,0x3e19be97,0x3f46be97,0xbf10bf69,0xbf5a3e19,0x3ede3f72,0xbe973f46,0x3f693f10,
0x3e97bf10,0xbf69bf46,0xbf2dbf72,0xbf2d3e19,0x3f463f69,0x3f10be97,0x3f5a3e19,0xbedebf72,0x3f720000,0x3e193f75,0x3f10be97,0xbf46bf69,0xbede3ede,0x3f5a3f5a,0x3f103f75,0x3f460000,
0xbf10bf69,0xbf46be97,0xbf5abede,0x3ede3f5a,0x3f100000,0xbf46bf75,0xbf2dbf72,0xbf2dbe19,0x3f723f69,0x3e19be97,0x3e97be97,0xbf69bf69,0x3e193f2d,0x3f723f2d,0x3f753f46,0xbf10,
0xbf75bf69,0x3e97,0x3e193ede,0x3f723f5a,0xbf46bf69,0xbf10be97,0xbedebe19,0x3f5a3f72,0x3f72bf10,0x3e19bf46,0xbe97,0xbf75bf69,0x3f2d3f5a,0x3f2d3ede,0x3f103e97,0xbf46bf69,
0,0x3f753f75,0x3f2d3f2d,0xbf2dbf2d,0,0x3f753f75,0x3f2d3f2d,0xbf2dbf2d,0x3f2d0000,0xbf2d3f75,0xbf75bf75,0,0x3f2d3f2d,0xbf2dbf2d,0xbf75bf75,0,
0x3f463f10,0x3f103f46,0xbedebe19,0xbf5abf72,0x3f753f69,0x3e97,0xbf5abf2d,0xbedebf2d,0x3f2d3f69,0xbf2dbe97,0xbf69bf75,0x3e970000,0x3e193ede,0xbf72bf5a,0xbf10bf46,0x3f463f10,
0x3f693f69,0xbe973e97,0xbf72bf5a,0x3e19bede,0x3f10,0xbf75bf46,0xbe19bf2d,0x3f723f2d,0x3f2dbf10,0xbf2dbf46,0xbf46bf75,0x3f100000,0xbede3e19,0xbf5abf72,0x3e97be97,0x3f693f69,
0x3e973f69,0xbf69be97,0xbe19bf5a,0x3f723ede,0xbf75bf10,0xbf46,0x3f723f2d,0xbe193f2d,0x3f2dbf10,0xbf2d3f46,0xbf10bf75,0x3f460000,0xbf5abe19,0xbedebf72,0x3f693e97,0x3e973f69,
0xbf103f10,0xbf46bf46,0x3f5abe19,0x3ede3f72,0xbf69,0x3f753e97,0xbede3f2d,0xbf5abf2d,0x3f2d3f69,0xbf2d3e97,0xbe97bf75,0x3f690000,0xbf72bede,0x3e19bf5a,0x3f463f46,0xbf103f10,
0xbf750000,0xbf75,0x3f2d3f2d,0xbf2d3f2d,0x3f750000,0x3f75,0xbf2dbf2d,0x3f2dbf2d,0x3f2d0000,0xbf2dbf75,0xbf75,0x3f750000,0xbf2dbf2d,0x3f2dbf2d,0x3f75,0xbf750000,
0xbf10bf10,0x3f46bf46,0xbede3f72,0xbf5abe19,0x3f69,0xbf753e97,0x3f5abf2d,0x3ede3f2d,0x3f2dbf69,0xbf2d3e97,0x3e97bf75,0x3f690000,0xbe19bf5a,0x3f72bede,0xbf463f46,0xbf10bf10,
0x3e97bf69,0x3f69be97,0xbf723ede,0x3e19bf5a,0xbf753f10,0xbf46,0x3e193f2d,0xbf723f2d,0x3f2d3f10,0xbf2d3f46,0x3f10bf75,0x3f460000,0x3edebf72,0x3f5abe19,0xbf693e97,0x3e97bf69,
0x3f69bf69,0x3e973e97,0xbe19bede,0x3f72bf5a,0xbf10,0x3f75bf46,0xbf723f2d,0x3e19bf2d,0x3f2d3f10,0xbf2dbf46,0x3f46bf75,0x3f100000,0x3f5abf72,0x3ede3e19,0xbe97be97,0x3f69bf69,
0x3f46bf10,0xbf103f46,0x3f5abf72,0x3edebe19,0x3f75bf69,0x3e97,0x3edebf2d,0x3f5abf2d,0x3f2dbf69,0xbf2dbe97,0x3f69bf75,0x3e970000,0x3f72bf5a,0xbe193ede,0x3f10bf46,0x3f46bf10,
0,0xbf753f75,0x3f2dbf2d,0xbf2d3f2d,0,0xbf753f75,0x3f2dbf2d,0xbf2d3f2d,0x3f2d0000,0xbf2d3f75,0x3f75bf75,0,0x3f2dbf2d,0xbf2d3f2d,0x3f75bf75,0,
0xbf463f10,0xbf103f46,0xbede3e19,0xbf5a3f72,0xbf753f69,0x3e97,0xbf5a3f2d,0xbede3f2d,0x3f2d3f69,0xbf2dbe97,0x3f69bf75,0xbe970000,0x3e19bede,0xbf723f5a,0x3f10bf46,0xbf463f10,
0xbf693f69,0x3e973e97,0xbf723f5a,0x3e193ede,0x3f10,0x3f75bf46,0xbe193f2d,0x3f72bf2d,0x3f2dbf10,0xbf2dbf46,0x3f46bf75,0xbf100000,0xbedebe19,0xbf5a3f72,0xbe97be97,0xbf693f69,
0xbe973f69,0x3f69be97,0xbe193f5a,0x3f72bede,0x3f75bf10,0xbf46,0x3f72bf2d,0xbe19bf2d,0x3f2dbf10,0xbf2d3f46,0x3f10bf75,0xbf460000,0xbf5a3e19,0xbede3f72,0xbf693e97,0xbe973f69,
0x3f103f10,0x3f46bf46,0x3f5a3e19,0x3edebf72,0xbf69,0xbf753e97,0xbedebf2d,0xbf5a3f2d,0x3f2d3f69,0xbf2d3e97,0x3e97bf75,0xbf690000,0xbf723ede,0x3e193f5a,0xbf463f46,0x3f103f10,
0x3f750000,0xbf75,0x3f2dbf2d,0xbf2dbf2d,0xbf750000,0x3f75,0xbf2d3f2d,0x3f2d3f2d,0x3f2d0000,0xbf2dbf75,0xbf75,0xbf750000,0xbf2d3f2d,0x3f2d3f2d,0x3f75,0x3f750000,
0x3f10bf10,0xbf46bf46,0xbedebf72,0xbf5a3e19,0x3f69,0x3f753e97,0x3f5a3f2d,0x3edebf2d,0x3f2dbf69,0xbf2d3e97,0xbe97bf75,0xbf690000,0xbe193f5a,0x3f723ede,0x3f463f46,0x3f10bf10,
0xbe97bf69,0xbf69be97,0xbf72bede,0x3e193f5a,0x3f753f10,0xbf46,0x3e19bf2d,0xbf72bf2d,0x3f2d3f10,0xbf2d3f46,0xbf10bf75,0xbf460000,0x3ede3f72,0x3f5a3e19,0x3f693e97,0xbe97bf69,
0xbf69bf69,0xbe973e97,0xbe193ede,0x3f723f5a,0xbf10,0xbf75bf46,0xbf72bf2d,0x3e193f2d,0x3f2d3f10,0xbf2dbf46,0xbf46bf75,0xbf100000,0x3f5a3f72,0x3edebe19,0x3e97be97,0xbf69bf69,
0xbf46bf10,0x3f103f46,0x3f5a3f72,0x3ede3e19,0xbf75bf69,0x3e97,0x3ede3f2d,0x3f5a3f2d,0x3f2dbf69,0xbf2dbe97,0xbf69bf75,0xbe970000,0x3f723f5a,0xbe19bede,0xbf10bf46,0xbf46bf10,
0xbe973f46,0xbf693f10,0x3f72bf2d,0xbe193f2d,0xbf2dbe97,0x3f2d3f69,0xbf103f69,0xbf463e97,0xbf5a3f72,0xbedebe19,0x3f100000,0xbf463f75,0x3e193ede,0xbf723f5a,0x3f69bf69,0x3e973e97,
0xbf693f46,0x3e97bf10,0xbede3f2d,0xbf5a3f2d,0xbf2d3f75,0x3f2d0000,0xbf463f69,0xbf103e97,0xbf723f5a,0x3e19bede,0xbe973f10,0xbf693f46,0xbf5a3f72,0xbede3e19,0x3e970000,0xbf693f75,
0x3e97be97,0x3f69bf69,0xbf2d3f2d,0x3f2dbf2d,0xbf2dbe97,0x3f2dbf69,0xbf693f69,0xbe973e97,0xbf2d3f2d,0x3f2dbf2d,0xbf693f69,0xbe973e97,0xbf2d3f2d,0x3f2dbf2d,0xbf693f69,0xbe973e97,
0x3f69bf75,0xbe970000,0x3f5abf2d,0x3edebf2d,0xbf2dbf46,0x3f2d3f10,0xbf753f69,0x3e97,0xbe193ede,0x3f72bf5a,0xbf463f69,0x3f10be97,0x3edebe19,0x3f5abf72,0xbe973f10,0x3f69bf46,
0xbe97be97,0xbf693f69,0x3e19bf2d,0xbf723f2d,0xbf2d3f46,0x3f2d3f10,0xbf693f69,0x3e973e97,0x3ede3e19,0x3f5abf72,0x3f10,0x3f75bf46,0x3f72bf5a,0xbe19bede,0x3f69bf10,0x3e97bf46,
0xbf693f46,0x3e973f10,0xbf723f2d,0x3e193f2d,0xbf2d3e97,0x3f2dbf69,0xbf463f69,0x3f103e97,0x3f5abe19,0x3edebf72,0x3f460000,0x3f10bf75,0x3e19bf5a,0xbf723ede,0x3e97bf69,0xbf693e97,
0x3e973f46,0x3f69bf10,0x3ede3f2d,0x3f5abf2d,0xbf2dbf75,0x3f2d0000,0xbf103f69,0x3f463e97,0x3f72bede,0xbe19bf5a,0x3f69bf10,0xbe97bf46,0xbf5abe19,0xbede3f72,0xbf690000,0xbe973f75,
0x3f69be97,0xbe97bf69,0x3f2dbf2d,0xbf2dbf2d,0xbf2d3e97,0x3f2d3f69,0xbe973f69,0x3f693e97,0x3f2dbf2d,0xbf2dbf2d,0x3e97bf69,0xbf69be97,0xbf2d3f2d,0x3f2d3f2d,0xbe973f69,0x3f693e97,
0xbe97bf75,0xbf690000,0xbf5abf2d,0xbede3f2d,0xbf2d3f46,0x3f2dbf10,0x3f69,0x3f753e97,0x3e19bf5a,0xbf72bede,0xbf10bf69,0xbf463e97,0x3ede3f72,0x3f5abe19,0x3f693f10,0x3e97bf46,
0xbf69be97,0x3e973f69,0xbe193f2d,0x3f723f2d,0xbf2dbf46,0x3f2dbf10,0x3e973f69,0x3f693e97,0xbedebf72,0xbf5abe19,0xbf75bf10,0x3f46,0x3f723ede,0xbe19bf5a,0x3e97bf10,0xbf69bf46,
0x3e973f46,0x3f693f10,0x3f723f2d,0xbe19bf2d,0xbf2dbe97,0x3f2d3f69,0x3f103f69,0x3f463e97,0xbf5abf72,0xbede3e19,0xbf100000,0x3f463f75,0x3e19bede,0xbf72bf5a,0xbf69bf69,0xbe973e97,
0x3f693f46,0xbe97bf10,0xbedebf2d,0xbf5abf2d,0xbf2d3f75,0x3f2d0000,0x3f463f69,0x3f103e97,0xbf72bf5a,0x3e193ede,0x3e973f10,0x3f693f46,0xbf5abf72,0xbedebe19,0xbe970000,0x3f693f75,
0xbf75bf75,0,0x3f2d3f2d,0x3f2d3f2d,0x3f2dbf75,0x3f2d0000,0,0xbf75bf75,0x3f2d3f2d,0x3f2d3f2d,0,0xbf75bf75,0x3f2d3f2d,0x3f2d3f2d,0,0xbf75bf75,
0xbe97,0x3f753f69,0x3ede3f2d,0xbf5abf2d,0x3f2d3e97,0x3f2d3f69,0xbe970000,0xbf69bf75,0x3f723f5a,0x3e193ede,0xbf46bf10,0xbf10bf46,0x3f5a3f72,0xbedebe19,0xbf75bf69,0xbe97,
0x3f753f46,0x3f10,0xbf72bf2d,0xbe19bf2d,0x3f2d3f46,0x3f2dbf10,0xbf100000,0xbf46bf75,0x3f5a3f72,0xbede3e19,0xbf69bf69,0x3e97be97,0xbe193ede,0xbf72bf5a,0xbf10,0x3f753f46,
0x3f46,0xbf75bf10,0x3e19bf2d,0x3f723f2d,0x3f2dbf46,0x3f2dbf10,0xbf460000,0xbf10bf75,0x3ede3f72,0xbf5abe19,0xbe97bf69,0x3f693e97,0xbf72bede,0xbe19bf5a,0x3f753f10,0x3f46,
0xbf75be97,0xbf69,0x3f5a3f2d,0xbede3f2d,0x3f2dbe97,0x3f2d3f69,0xbf690000,0xbe97bf75,0xbe193f5a,0xbf72bede,0x3f10bf10,0x3f463f46,0xbedebf72,0x3f5abe19,0x3f69,0xbf75be97,
0xbf75,0x3f750000,0xbf2d3f2d,0xbf2dbf2d,0x3f2d3f75,0x3f2d0000,0xbf750000,0xbf75,0xbf2d3f2d,0xbf2dbf2d,0x3f750000,0x3f75,0x3f2dbf2d,0x3f2d3f2d,0xbf750000,0xbf75,
0x3f75be97,0x3f69,0xbedebf2d,0x3f5abf2d,0x3f2dbe97,0x3f2dbf69,0xbf690000,0x3e97bf75,0xbf723ede,0xbe19bf5a,0x3f103f10,0xbf463f46,0x3f5a3e19,0xbede3f72,0xbf69,0x3f75be97,
0x3f46,0xbf753f10,0x3f72bf2d,0x3e193f2d,0x3f2dbf46,0x3f2d3f10,0xbf460000,0x3f10bf75,0xbf5a3e19,0x3edebf72,0xbe973f69,0xbf693e97,0xbe193f5a,0xbf723ede,0x3f75bf10,0x3f46,
0xbf753f46,0xbf10,0xbe193f2d,0xbf723f2d,0x3f2d3f46,0x3f2d3f10,0xbf100000,0x3f46bf75,0xbedebe19,0x3f5abf72,0xbf693f69,0xbe97be97,0xbf723f5a,0xbe19bede,0x3f10,0xbf753f46,
0xbe97,0x3f75bf69,0xbf5a3f2d,0x3edebf2d,0x3f2d3e97,0x3f2dbf69,0xbe970000,0x3f69bf75,0x3e19bede,0x3f72bf5a,0xbf463f10,0x3f10bf46,0xbede3e19,0x3f5abf72,0xbf753f69,0xbe97,
0x3f75bf75,0,0x3f2dbf2d,0x3f2dbf2d,0x3f2dbf75,0x3f2d0000,0,0x3f75bf75,0x3f2dbf2d,0x3f2dbf2d,0,0x3f75bf75,0x3f2dbf2d,0x3f2dbf2d,0,0x3f75bf75,
0xbe97,0xbf753f69,0x3edebf2d,0xbf5a3f2d,0x3f2d3e97,0x3f2d3f69,0x3e970000,0x3f69bf75,0x3f72bf5a,0x3e19bede,0x3f46bf10,0x3f10bf46,0x3f5abf72,0xbede3e19,0x3f75bf69,0xbe97,
0xbf753f46,0x3f10,0xbf723f2d,0xbe193f2d,0x3f2d3f46,0x3f2dbf10,0x3f100000,0x3f46bf75,0x3f5abf72,0xbedebe19,0x3f69bf69,0xbe97be97,0xbe19bede,0xbf723f5a,0xbf10,0xbf753f46,
0x3f46,0x3f75bf10,0x3e193f2d,0x3f72bf2d,0x3f2dbf46,0x3f2dbf10,0x3f460000,0x3f10bf75,0x3edebf72,0xbf5a3e19,0x3e97bf69,0xbf693e97,0xbf723ede,0xbe193f5a,0xbf753f10,0x3f46,
0x3f75be97,0xbf69,0x3f5abf2d,0xbedebf2d,0x3f2dbe97,0x3f2d3f69,0x3f690000,0x3e97bf75,0xbe19bf5a,0xbf723ede,0xbf10bf10,0xbf463f46,0xbede3f72,0x3f5a3e19,0x3f69,0x3f75be97,
0xbf75,0xbf750000,0xbf2dbf2d,0xbf2d3f2d,0x3f2d3f75,0x3f2d0000,0x3f750000,0xbf75,0xbf2dbf2d,0xbf2d3f2d,0xbf750000,0x3f75,0x3f2d3f2d,0x3f2dbf2d,0x3f750000,0xbf75,
0xbf75be97,0x3f69,0xbede3f2d,0x3f5a3f2d,0x3f2dbe97,0x3f2dbf69,0x3f690000,0xbe97bf75,0xbf72bede,0xbe193f5a,0xbf103f10,0x3f463f46,0x3f5abe19,0xbedebf72,0xbf69,0xbf75be97,
0x3f46,0x3f753f10,0x3f723f2d,0x3e19bf2d,0x3f2dbf46,0x3f2d3f10,0x3f460000,0xbf10bf75,0xbf5abe19,0x3ede3f72,0x3e973f69,0x3f693e97,0xbe19bf5a,0xbf72bede,0xbf75bf10,0x3f46,
0x3f753f46,0xbf10,0xbe19bf2d,0xbf72bf2d,0x3f2d3f46,0x3f2d3f10,0x3f100000,0xbf46bf75,0xbede3e19,0x3f5a3f72,0x3f693f69,0x3e97be97,0xbf72bf5a,0xbe193ede,0x3f10,0x3f753f46,
0xbe97,0xbf75bf69,0xbf5abf2d,0x3ede3f2d,0x3f2d3e97,0x3f2dbf69,0x3e970000,0xbf69bf75,0x3e193ede,0x3f723f5a,0x3f463f10,0xbf10bf46,0xbedebe19,0x3f5a3f72,0x3f753f69,0xbe97,
0,0,0xbf10,0xbf46,0,0,0,0,0,0,0,0,0,0,0,0,
0,0,0xbf10,0x3f46,0,0,0,0,0,0,0,0,0,0,0,0,
0,0,0x3f69,0x3e97,0,0,0,0,0,0,0,0,0,0,0,0,
0,0,0,0xbf75,0,0,0,0,0,0,0,0,0,0,0,0,
0,0,0xbf69,0x3e97,0,0,0,0,0,0,0,0,0,0,0,0,
0,0,0x3f10,0x3f46,0,0,0,0,0,0,0,0,0,0,0,0,
0,0,0x3f10,0xbf46,0,0,0,0,0,0,0,0,0,0,0,0,
0,0,0xbf69,0xbe97,0,0,0,0,0,0,0,0,0,0,0,0,
0,0,0,0x3f75,0,0,0,0,0,0,0,0,0,0,0,0,
0,0,0x3f69,0xbe97,0,0,0,0,0,0,0,0,0,0,0,0,
0,0,0xbf10,0xbf46,0,0,0,0,0,0,0,0,0,0,0,0,
0,0,0xbf10,0x3f46,0,0,0,0,0,0,0,0,0,0,0,0,
0,0,0,0xbf75,0,0,0,0,0,0,0,0,0,0,0,0,
0,0,0xbf69,0x3e97,0,0,0,0,0,0,0,0,0,0,0,0,
0,0,0x3f10,0x3f46,0,0,0,0,0,0,0,0,0,0,0,0,
0,0,0x3f10,0xbf46,0,0,0,0,0,0,0,0,0,0,0,0,
0,0,0xbf69,0xbe97,0,0,0,0,0,0,0,0,0,0,0,0,
0,0,0,0x3f75,0,0,0,0,0,0,0,0,0,0,0,0,
0,0,0x3f69,0xbe97,0,0,0,0,0,0,0,0,0,0,0,0,
0,0,0xbf10,0xbf46,0,0,0,0,0,0,0,0,0,0,0,0,
0,0,0xbf10,0x3f46,0,0,0,0,0,0,0,0,0,0,0,0,
0,0,0x3f69,0x3e97,0,0,0,0,0,0,0,0,0,0,0,0,
0,0,0,0xbf75,0,0,0,0,0,0,0,0,0,0,0,0,
0,0,0xbf69,0x3e97,0,0,0,0,0,0,0,0,0,0,0,0,
0,0,0x3f10,0x3f46,0,0,0,0,0,0,0,0,0,0,0,0,
0,0,0x3f10,0xbf46,0,0,0,0,0,0,0,0,0,0,0,0,
0,0,0xbf69,0xbe97,0,0,0,0,0,0,0,0,0,0,0,0,
0,0,0,0x3f75,0,0,0,0,0,0,0,0,0,0,0,0,
0,0,0x3f69,0xbe97,0,0,0,0,0,0,0,0,0,0,0,0,
0,0,0xbf10,0xbf46,0,0,0,0,0,0,0,0,0,0,0,0,
0,0,0xbf10,0x3f46,0,0,0,0,0,0,0,0,0,0,0,0,
0,0,0x3f69,0x3e97,0,0,0,0,0,0,0,0,0,0,0,0,
0x3f753f75,0,0xbf5abf5a,0xbedebede,0x3f753f75,0,0xbf5abf5a,0xbedebede,0x3f753f75,0,0xbf5abf5a,0xbedebede,0xbf5a3f75,0xbede0000,0x3f103f10,0x3f463f46,
0x3f693f75,0xbe970000,0xbf72bf72,0x3e19be19,0x3f103f46,0xbf46bf10,0xbf2dbf5a,0x3f2d3ede,0x3e97,0xbf75bf69,0xbe19bede,0x3f723f5a,0xbf5abe97,0xbedebf69,0x3f463f10,0x3f103f46,
0x3f463f75,0xbf100000,0xbf2dbf72,0x3f2d3e19,0xbe973e97,0xbf69bf69,0x3edebe19,0x3f5a3f72,0xbf75bf46,0xbf10,0x3f723f5a,0xbe193ede,0xbf5abf46,0xbede3f10,0x3f693f10,0x3e973f46,
0x3f103f75,0xbf460000,0xbe19bf5a,0x3f723ede,0xbf69be97,0xbe97bf69,0x3f723f2d,0xbe193f2d,0xbf46,0x3f753f10,0xbede3ede,0xbf5abf5a,0xbf5a3f46,0xbede3f10,0x3f753f10,0x3f46,
0x3e973f75,0xbf690000,0x3edebf2d,0x3f5a3f2d,0xbf46bf46,0x3f10bf10,0x3e193f72,0xbf72be19,0x3f753e97,0x3f69,0xbf2dbf5a,0x3f2dbede,0xbf5a3e97,0xbedebf69,0x3f693f10,0xbe973f46,
0x3f75,0xbf750000,0x3f5abede,0x3ede3f5a,0xbf75,0x3f750000,0xbf5a3ede,0xbedebf5a,0x3f75,0xbf750000,0x3f5abede,0x3ede3f5a,0xbf5abf75,0xbede0000,0x3f463f10,0xbf103f46,
0xbe973f75,0xbf690000,0x3f72be19,0xbe193f72,0x3f46bf46,0x3f103f10,0xbf2dbede,0x3f2dbf5a,0xbf753e97,0xbf69,0x3e193f5a,0xbf723ede,0xbf5a3e97,0xbede3f69,0x3f103f10,0xbf463f46,
0xbf103f75,0xbf460000,0x3f2d3e19,0xbf2d3f72,0x3f69be97,0xbe973f69,0x3edebf72,0x3f5abe19,0xbf46,0x3f75bf10,0xbf723ede,0x3e19bf5a,0xbf5a3f46,0xbedebf10,0x3e973f10,0xbf693f46,
0xbf463f75,0xbf100000,0x3e193ede,0xbf723f5a,0x3e973e97,0xbf693f69,0x3f72bf2d,0xbe193f2d,0x3f75bf46,0x3f10,0x3edebf5a,0x3f5abede,0xbf5abf46,0xbedebf10,0x3f10,0xbf753f46,
0xbf693f75,0xbe970000,0xbede3f2d,0xbf5a3f2d,0xbf103f46,0xbf463f10,0x3e193e19,0xbf723f72,0x3e97,0xbf753f69,0x3f2dbede,0xbf2d3f5a,0xbf5abe97,0xbede3f69,0xbe973f10,0xbf693f46,
0xbf753f75,0,0xbf5a3f5a,0xbede3ede,0xbf753f75,0,0xbf5a3f5a,0xbede3ede,0xbf753f75,0,0xbf5a3f5a,0xbede3ede,0xbf5a3f75,0xbede0000,0xbf103f10,0xbf463f46,
0xbf693f75,0x3e970000,0xbf723f72,0x3e193e19,0xbf103f46,0x3f46bf10,0xbf2d3f5a,0x3f2dbede,0x3e97,0x3f75bf69,0xbe193ede,0x3f72bf5a,0xbf5abe97,0xbedebf69,0xbf463f10,0xbf103f46,
0xbf463f75,0x3f100000,0xbf2d3f72,0x3f2dbe19,0x3e973e97,0x3f69bf69,0x3ede3e19,0x3f5abf72,0x3f75bf46,0xbf10,0x3f72bf5a,0xbe19bede,0xbf5abf46,0xbede3f10,0xbf693f10,0xbe973f46,
0xbf103f75,0x3f460000,0xbe193f5a,0x3f72bede,0x3f69be97,0x3e97bf69,0x3f72bf2d,0xbe19bf2d,0xbf46,0xbf753f10,0xbedebede,0xbf5a3f5a,0xbf5a3f46,0xbede3f10,0xbf753f10,0x3f46,
0xbe973f75,0x3f690000,0x3ede3f2d,0x3f5abf2d,0x3f46bf46,0xbf10bf10,0x3e19bf72,0xbf723e19,0xbf753e97,0x3f69,0xbf2d3f5a,0x3f2d3ede,0xbf5a3e97,0xbedebf69,0xbf693f10,0x3e973f46,
0x3f75,0x3f750000,0x3f5a3ede,0x3edebf5a,0xbf75,0xbf750000,0xbf5abede,0xbede3f5a,0x3f75,0x3f750000,0x3f5a3ede,0x3edebf5a,0xbf5abf75,0xbede0000,0xbf463f10,0x3f103f46,
0x3e973f75,0x3f690000,0x3f723e19,0xbe19bf72,0xbf46bf46,0xbf103f10,0xbf2d3ede,0x3f2d3f5a,0x3f753e97,0xbf69,0x3e19bf5a,0xbf72bede,0xbf5a3e97,0xbede3f69,0xbf103f10,0x3f463f46,
0x3f103f75,0x3f460000,0x3f2dbe19,0xbf2dbf72,0xbf69be97,0x3e973f69,0x3ede3f72,0x3f5a3e19,0xbf46,0xbf75bf10,0xbf72bede,0x3e193f5a,0xbf5a3f46,0xbedebf10,0xbe973f10,0x3f693f46,
0x3f463f75,0x3f100000,0x3e19bede,0xbf72bf5a,0xbe973e97,0x3f693f69,0x3f723f2d,0xbe19bf2d,0xbf75bf46,0x3f10,0x3ede3f5a,0x3f5a3ede,0xbf5abf46,0xbedebf10,0x3f10,0x3f753f46,
0x3f693f75,0x3e970000,0xbedebf2d,0xbf5abf2d,0x3f103f46,0x3f463f10,0x3e19be19,0xbf72bf72,0x3e97,0x3f753f69,0x3f2d3ede,0xbf2dbf5a,0xbf5abe97,0xbede3f69,0x3e973f10,0x3f693f46,
0x3f753f75,0,0xbf72bf72,0xbe19be19,0x3f753f75,0,0xbf72bf72,0xbe19be19,0x3f753f75,0,0xbf72bf72,0xbe19be19,0xbf723f75,0xbe190000,0x3f693f69,0x3e973e97,
0x3f693f75,0xbe970000,0xbf5abf72,0x3ede3e19,0x3f103f46,0xbf46bf10,0xbedebf2d,0x3f5a3f2d,0x3e97,0xbf75bf69,0x3e19be19,0x3f723f72,0xbf72be97,0xbe19bf69,0x3f753f69,0x3e97,
0x3f463f75,0xbf100000,0xbedebf5a,0x3f5a3ede,0xbe973e97,0xbf69bf69,0x3f2d3e19,0x3f2d3f72,0xbf75bf46,0xbf10,0x3f5a3f72,0xbede3e19,0xbf72bf46,0xbe193f10,0x3f693f69,0xbe973e97,
0x3f103f75,0xbf460000,0x3e19bf2d,0x3f723f2d,0xbf69be97,0xbe97bf69,0x3f5a3f5a,0xbede3ede,0xbf46,0x3f753f10,0xbf2d3e19,0xbf2dbf72,0xbf723f46,0xbe193f10,0x3f463f69,0xbf103e97,
0x3e973f75,0xbf690000,0x3f2dbede,0x3f2d3f5a,0xbf46bf46,0x3f10bf10,0xbe193f5a,0xbf72bede,0x3f753e97,0x3f69,0xbedebf72,0x3f5abe19,0xbf723e97,0xbe19bf69,0x3f103f69,0xbf463e97,
0x3f75,0xbf750000,0x3f72be19,0x3e193f72,0xbf75,0x3f750000,0xbf723e19,0xbe19bf72,0x3f75,0xbf750000,0x3f72be19,0x3e193f72,0xbf72bf75,0xbe190000,0x3e973f69,0xbf693e97,
0xbe973f75,0xbf690000,0x3f5a3e19,0xbede3f72,0x3f46bf46,0x3f103f10,0xbedebf2d,0x3f5abf2d,0xbf753e97,0xbf69,0xbe193f72,0xbf723e19,0xbf723e97,0xbe193f69,0x3f69,0xbf753e97,
0xbf103f75,0xbf460000,0x3ede3ede,0xbf5a3f5a,0x3f69be97,0xbe973f69,0x3f2dbf72,0x3f2d3e19,0xbf46,0x3f75bf10,0xbf5a3e19,0x3edebf72,0xbf723f46,0xbe19bf10,0xbe973f69,0xbf693e97,
0xbf463f75,0xbf100000,0xbe193f2d,0xbf723f2d,0x3e973e97,0xbf693f69,0x3f5abede,0xbede3f5a,0x3f75bf46,0x3f10,0x3f2dbf72,0x3f2dbe19,0xbf72bf46,0xbe19bf10,0xbf103f69,0xbf463e97,
0xbf693f75,0xbe970000,0xbf2d3f5a,0xbf2d3ede,0xbf103f46,0xbf463f10,0xbe193ede,0xbf723f5a,0x3e97,0xbf753f69,0x3edebe19,0xbf5a3f72,0xbf72be97,0xbe193f69,0xbf463f69,0xbf103e97,
0xbf753f75,0,0xbf723f72,0xbe193e19,0xbf753f75,0,0xbf723f72,0xbe193e19,0xbf753f75,0,0xbf723f72,0xbe193e19,0xbf723f75,0xbe190000,0xbf693f69,0xbe973e97,
0xbf693f75,0x3e970000,0xbf5a3f72,0x3edebe19,0xbf103f46,0x3f46bf10,0xbede3f2d,0x3f5abf2d,0x3e97,0x3f75bf69,0x3e193e19,0x3f72bf72,0xbf72be97,0xbe19bf69,0xbf753f69,0x3e97,
0x3f103f10,0x3f463f46,0xbe19be19,0xbf72bf72,0x3f103f10,0x3f463f46,0xbe19be19,0xbf72bf72,0xbe193f10,0xbf723f46,0xbe97be97,0x3f693f69,0xbe19be19,0xbf72bf72,0xbe97be97,0x3f693f69,
0x3f753f69,0x3e97,0xbf72bf5a,0xbe19bede,0x3f463f69,0xbf10be97,0xbf5abf72,0x3ede3e19,0xbe193f10,0xbf72bf46,0xbe97,0x3f753f69,0xbf2dbede,0xbf2dbf5a,0x3f103e97,0x3f463f69,
0x3f103f69,0xbf46be97,0xbedebf5a,0x3f5a3ede,0xbf100000,0xbf46bf75,0x3f2d3e19,0x3f2d3f72,0xbe19bf69,0xbf72be97,0x3e97be97,0x3f693f69,0xbf72bf2d,0xbe19bf2d,0x3f753f46,0x3f10,
0xbe973f10,0xbf69bf46,0x3f2dbe19,0x3f2d3f72,0xbf46bf69,0x3f10be97,0x3ede3f72,0xbf5abe19,0xbe190000,0xbf723f75,0x3f10be97,0x3f463f69,0xbf5abf5a,0x3edebede,0x3f103f75,0xbf460000,
0xbf690000,0xbe97bf75,0x3f5a3f2d,0xbede3f2d,0x3f10bf10,0x3f463f46,0xbf72be19,0xbe19bf72,0xbe193f69,0xbf72be97,0x3f46be97,0x3f103f69,0xbedebf72,0x3f5abe19,0xbe973f46,0xbf69bf10,
0xbf46bf10,0x3f10bf46,0xbe193f72,0xbf72be19,0x3f463f10,0xbf103f46,0x3e19bf72,0x3f723e19,0xbe19bf10,0xbf72bf46,0x3f69be97,0x3e973f69,0x3e19bf72,0x3f723e19,0xbf693e97,0xbe97bf69,
0xbf69,0x3f75be97,0xbf723ede,0xbe19bf5a,0xbf103f69,0xbf46be97,0x3f5a3e19,0xbede3f72,0xbe19bf10,0xbf723f46,0x3f75be97,0x3f69,0x3f2dbf5a,0x3f2d3ede,0xbf46be97,0x3f10bf69,
0x3f46bf69,0x3f103e97,0xbedebede,0x3f5abf5a,0xbf460000,0x3f10bf75,0xbf2d3f72,0xbf2dbe19,0xbe193f69,0xbf723e97,0x3f69be97,0xbe973f69,0x3f72bf2d,0x3e193f2d,0xbf46,0x3f75bf10,
0x3f69bf10,0xbe973f46,0x3f2dbf72,0x3f2dbe19,0x3f10bf69,0x3f46be97,0xbedebe19,0x3f5abf72,0xbe190000,0xbf72bf75,0x3f46be97,0xbf103f69,0x3f5abede,0xbede3f5a,0x3f46bf75,0x3f100000,
0x3e970000,0xbf693f75,0x3f5abf2d,0xbede3f2d,0x3f46bf10,0xbf103f46,0x3f72bf72,0x3e193e19,0xbe19bf69,0xbf723e97,0x3f10be97,0xbf463f69,0x3edebe19,0xbf5a3f72,0x3f69bf46,0xbe973f10,
0xbf103f10,0xbf463f46,0xbe193e19,0xbf723f72,0xbf103f10,0xbf463f46,0xbe193e19,0xbf723f72,0xbe193f10,0xbf723f46,0x3e97be97,0xbf693f69,0xbe193e19,0xbf723f72,0x3e97be97,0xbf693f69,
0xbf753f69,0x3e97,0xbf723f5a,0xbe193ede,0xbf463f69,0x3f10be97,0xbf5a3f72,0x3edebe19,0xbe193f10,0xbf72bf46,0xbe97,0xbf753f69,0xbf2d3ede,0xbf2d3f5a,0xbf103e97,0xbf463f69,
0xbf103f69,0x3f46be97,0xbede3f5a,0x3f5abede,0x3f100000,0x3f46bf75,0x3f2dbe19,0x3f2dbf72,0xbe19bf69,0xbf72be97,0xbe97be97,0xbf693f69,0xbf723f2d,0xbe193f2d,0xbf753f46,0x3f10,
0x3e973f10,0x3f69bf46,0x3f2d3e19,0x3f2dbf72,0x3f46bf69,0xbf10be97,0x3edebf72,0xbf5a3e19,0xbe190000,0xbf723f75,0xbf10be97,0xbf463f69,0xbf5a3f5a,0x3ede3ede,0xbf103f75,0x3f460000,
0x3f690000,0x3e97bf75,0x3f5abf2d,0xbedebf2d,0xbf10bf10,0xbf463f46,0xbf723e19,0xbe193f72,0xbe193f69,0xbf72be97,0xbf46be97,0xbf103f69,0xbede3f72,0x3f5a3e19,0x3e973f46,0x3f69bf10,
0x3f46bf10,0xbf10bf46,0xbe19bf72,0xbf723e19,0xbf463f10,0x3f103f46,0x3e193f72,0x3f72be19,0xbe19bf10,0xbf72bf46,0xbf69be97,0xbe973f69,0x3e193f72,0x3f72be19,0x3f693e97,0x3e97bf69,
0xbf69,0xbf75be97,0xbf72bede,0xbe193f5a,0x3f103f69,0x3f46be97,0x3f5abe19,0xbedebf72,0xbe19bf10,0xbf723f46,0xbf75be97,0x3f69,0x3f2d3f5a,0x3f2dbede,0x3f46be97,0xbf10bf69,
0xbf46bf69,0xbf103e97,0xbede3ede,0x3f5a3f5a,0x3f460000,0xbf10bf75,0xbf2dbf72,0xbf2d3e19,0xbe193f69,0xbf723e97,0xbf69be97,0x3e973f69,0x3f723f2d,0x3e19bf2d,0xbf46,0xbf75bf10,
0xbf69bf10,0x3e973f46,0x3f2d3f72,0x3f2d3e19,0xbf10bf69,0xbf46be97,0xbede3e19,0x3f5a3f72,0xbe190000,0xbf72bf75,0xbf46be97,0x3f103f69,0x3f5a3ede,0xbedebf5a,0xbf46bf75,0xbf100000,
0xbe970000,0x3f693f75,0x3f5a3f2d,0xbedebf2d,0xbf46bf10,0x3f103f46,0x3f723f72,0x3e19be19,0xbe19bf69,0xbf723e97,0xbf10be97,0x3f463f69,0x3ede3e19,0xbf5abf72,0xbf69bf46,0x3e973f10,
0x3f693f69,0x3e973e97,0xbf5abf5a,0xbedebede,0x3f693f69,0x3e973e97,0xbf5abf5a,0xbedebede,0xbf5a3f69,0xbede3e97,0x3f463f46,0x3f103f10,0xbf5abf5a,0xbedebede,0x3f463f46,0x3f103f10,
0x3f463f69,0xbf10be97,0xbf2dbf5a,0x3f2d3ede,0x3e973f10,0xbf69bf46,0xbe19bede,0x3f723f5a,0xbf5a0000,0xbedebf75,0x3f693f46,0x3e973f10,0xbf72bf72,0x3e19be19,0x3f693f75,0xbe970000,
0x3f10,0xbf75bf46,0x3edebe19,0x3f5a3f72,0xbf69bf10,0xbe97bf46,0x3f723f5a,0xbe193ede,0xbf5abf69,0xbede3e97,0x3f753f46,0x3f10,0xbf2dbf72,0x3f2d3e19,0x3e973f46,0xbf69bf10,
0xbf460000,0xbf10bf75,0x3f723f2d,0xbe193f2d,0xbe97bf69,0x3f693e97,0xbede3ede,0xbf5abf5a,0xbf5a3f10,0xbede3f46,0x3f693f46,0xbe973f10,0xbe19bf5a,0x3f723ede,0xbf103e97,0xbf46bf69,
0xbf69bf10,0x3e97bf46,0x3e193f72,0xbf72be19,0x3f690000,0x3e973f75,0xbf2dbf5a,0x3f2dbede,0xbf5a3f10,0xbedebf46,0x3f463f46,0xbf103f10,0x3edebf2d,0x3f5a3f2d,0xbf75be97,0xbf69,
0xbe97bf69,0x3f69be97,0xbf5a3ede,0xbedebf5a,0x3e973f69,0xbf693e97,0x3f5abede,0x3ede3f5a,0xbf5abf69,0xbedebe97,0x3f103f46,0xbf463f10,0x3f5abede,0x3ede3f5a,0xbf10bf46,0x3f46bf10,
0x3f10bf69,0x3f463e97,0xbf2dbede,0x3f2dbf5a,0xbf693f10,0xbe97bf46,0x3e193f5a,0xbf723ede,0xbf5a0000,0xbede3f75,0x3e973f46,0xbf693f10,0x3f72be19,0xbe193f72,0x3e97bf75,0x3f690000,
0x3f75bf10,0x3f46,0x3edebf72,0x3f5abe19,0xbe97bf10,0x3f69bf46,0xbf723ede,0x3e19bf5a,0xbf5a3f69,0xbedebe97,0x3f46,0xbf753f10,0x3f2d3e19,0xbf2d3f72,0x3f69bf46,0x3e973f10,
0x3f100000,0xbf463f75,0x3f72bf2d,0xbe193f2d,0x3f69bf69,0x3e973e97,0x3edebf5a,0x3f5abede,0xbf5abf10,0xbedebf46,0xbe973f46,0xbf693f10,0x3e193ede,0xbf723f5a,0x3f46be97,0xbf103f69,
0xbe973f10,0xbf693f46,0x3e193e19,0xbf723f72,0x3e970000,0xbf693f75,0x3f2dbede,0xbf2d3f5a,0xbf5abf10,0xbede3f46,0xbf103f46,0xbf463f10,0xbede3f2d,0xbf5a3f2d,0x3e97,0xbf753f69,
0xbf693f69,0xbe973e97,0xbf5a3f5a,0xbede3ede,0xbf693f69,0xbe973e97,0xbf5a3f5a,0xbede3ede,0xbf5a3f69,0xbede3e97,0xbf463f46,0xbf103f10,0xbf5a3f5a,0xbede3ede,0xbf463f46,0xbf103f10,
0xbf463f69,0x3f10be97,0xbf2d3f5a,0x3f2dbede,0xbe973f10,0x3f69bf46,0xbe193ede,0x3f72bf5a,0xbf5a0000,0xbedebf75,0xbf693f46,0xbe973f10,0xbf723f72,0x3e193e19,0xbf693f75,0x3e970000,
0xbe97be97,0x3f693f69,0x3f2d3f2d,0xbf2dbf2d,0x3f2dbe97,0xbf2d3f69,0xbf69bf69,0x3e973e97,0x3f2d3f2d,0xbf2dbf2d,0xbf69bf69,0x3e973e97,0x3f2d3f2d,0xbf2dbf2d,0xbf69bf69,0x3e973e97,
0x3f693f46,0x3e973f10,0xbf5abf2d,0xbedebf2d,0x3f2d3f75,0xbf2d0000,0xbf46bf69,0x3f103e97,0x3e193ede,0xbf72bf5a,0xbe97bf10,0x3f693f46,0xbedebe19,0xbf5abf72,0x3e970000,0x3f693f75,
0x3e973f46,0xbf69bf10,0xbe19bf2d,0x3f723f2d,0x3f2dbe97,0xbf2dbf69,0xbf10bf69,0x3f463e97,0xbede3e19,0xbf5abf72,0x3f100000,0x3f463f75,0xbf72bf5a,0x3e19bede,0x3f693f69,0xbe973e97,
0xbf69be97,0xbe97bf69,0x3f723f2d,0xbe193f2d,0x3f2dbf46,0xbf2d3f10,0xbe97bf69,0x3f693e97,0xbf5abe19,0xbedebf72,0x3f753f10,0x3f46,0xbe19bf5a,0x3f723ede,0xbe973f10,0xbf69bf46,
0xbe97bf75,0x3f690000,0xbede3f2d,0xbf5abf2d,0x3f2d3f46,0xbf2d3f10,0xbf69,0x3f753e97,0xbf72bede,0x3e19bf5a,0x3f103f69,0xbf463e97,0x3f5abe19,0x3ede3f72,0xbf69bf10,0x3e97bf46,
0x3f69be97,0x3e973f69,0xbf2dbf2d,0x3f2dbf2d,0x3f2d3e97,0xbf2dbf69,0x3e97bf69,0x3f693e97,0xbf2dbf2d,0x3f2dbf2d,0xbe973f69,0xbf69be97,0x3f2d3f2d,0xbf2d3f2d,0x3e97bf69,0x3f693e97,
0x3e973f46,0xbf693f10,0x3f5abf2d,0x3ede3f2d,0x3f2dbf75,0xbf2d0000,0x3f10bf69,0x3f463e97,0xbe19bf5a,0x3f72bede,0xbf693f10,0xbe97bf46,0xbede3f72,0xbf5abe19,0x3f690000,0xbe973f75,
0xbf693f46,0xbe97bf10,0x3e193f2d,0xbf723f2d,0x3f2d3e97,0xbf2d3f69,0x3f46bf69,0x3f103e97,0x3edebf72,0x3f5abe19,0xbf460000,0x3f10bf75,0xbf723ede,0x3e19bf5a,0xbe973f69,0xbf693e97,
0xbe97be97,0x3f69bf69,0xbf723f2d,0x3e19bf2d,0x3f2d3f46,0xbf2dbf10,0x3f69bf69,0x3e973e97,0x3f5abf72,0x3ede3e19,0xbf10,0x3f75bf46,0xbe19bede,0x3f72bf5a,0xbf693f10,0x3e97bf46,
0x3f69bf75,0x3e970000,0x3edebf2d,0x3f5abf2d,0x3f2dbf46,0xbf2dbf10,0x3f75bf69,0x3e97,0x3f72bf5a,0xbe193ede,0x3f46bf69,0x3f10be97,0x3f5abf72,0x3edebe19,0x3e97bf10,0x3f69bf46,
0x3e97be97,0xbf693f69,0x3f2dbf2d,0xbf2d3f2d,0x3f2dbe97,0xbf2d3f69,0x3f69bf69,0xbe973e97,0x3f2dbf2d,0xbf2d3f2d,0x3f69bf69,0xbe973e97,0x3f2dbf2d,0xbf2d3f2d,0x3f69bf69,0xbe973e97,
0xbf693f46,0xbe973f10,0xbf5a3f2d,0xbede3f2d,0x3f2d3f75,0xbf2d0000,0x3f46bf69,0xbf103e97,0x3e19bede,0xbf723f5a,0x3e97bf10,0xbf693f46,0xbede3e19,0xbf5a3f72,0xbe970000,0xbf693f75,
0xbe973f46,0x3f69bf10,0xbe193f2d,0x3f72bf2d,0x3f2dbe97,0xbf2dbf69,0x3f10bf69,0xbf463e97,0xbedebe19,0xbf5a3f72,0xbf100000,0xbf463f75,0xbf723f5a,0x3e193ede,0xbf693f69,0x3e973e97,
0x3f69be97,0x3e97bf69,0x3f72bf2d,0xbe19bf2d,0x3f2dbf46,0xbf2d3f10,0x3e97bf69,0xbf693e97,0xbf5a3e19,0xbede3f72,0xbf753f10,0x3f46,0xbe193f5a,0x3f72bede,0x3e973f10,0x3f69bf46,
0x3e97bf75,0xbf690000,0xbedebf2d,0xbf5a3f2d,0x3f2d3f46,0xbf2d3f10,0xbf69,0xbf753e97,0xbf723ede,0x3e193f5a,0xbf103f69,0x3f463e97,0x3f5a3e19,0x3edebf72,0x3f69bf10,0xbe97bf46,
0xbf69be97,0xbe973f69,0xbf2d3f2d,0x3f2d3f2d,0x3f2d3e97,0xbf2dbf69,0xbe97bf69,0xbf693e97,0xbf2d3f2d,0x3f2d3f2d,0x3e973f69,0x3f69be97,0x3f2dbf2d,0xbf2dbf2d,0xbe97bf69,0xbf693e97,
0xbe973f46,0x3f693f10,0x3f5a3f2d,0x3edebf2d,0x3f2dbf75,0xbf2d0000,0xbf10bf69,0xbf463e97,0xbe193f5a,0x3f723ede,0x3f693f10,0x3e97bf46,0xbedebf72,0xbf5a3e19,0xbf690000,0x3e973f75,
0x3f693f46,0x3e97bf10,0x3e19bf2d,0xbf72bf2d,0x3f2d3e97,0xbf2d3f69,0xbf46bf69,0xbf103e97,0x3ede3f72,0x3f5a3e19,0x3f460000,0xbf10bf75,0xbf72bede,0x3e193f5a,0x3e973f69,0x3f693e97,
0x3e97be97,0xbf69bf69,0xbf72bf2d,0x3e193f2d,0x3f2d3f46,0xbf2dbf10,0xbf69bf69,0xbe973e97,0x3f5a3f72,0x3edebe19,0xbf10,0xbf75bf46,0xbe193ede,0x3f723f5a,0x3f693f10,0xbe97bf46,
0xbf69bf75,0xbe970000,0x3ede3f2d,0x3f5a3f2d,0x3f2dbf46,0xbf2dbf10,0xbf75bf69,0x3e97,0x3f723f5a,0xbe19bede,0xbf46bf69,0xbf10be97,0x3f5a3f72,0x3ede3e19,0xbe97bf10,0xbf69bf46,
0x3f463f46,0x3f103f10,0xbf2dbf2d,0xbf2dbf2d,0xbf2d3f46,0xbf2d3f10,0x3f103f10,0x3f463f46,0xbf2dbf2d,0xbf2dbf2d,0x3f103f10,0x3f463f46,0xbf2dbf2d,0xbf2dbf2d,0x3f103f10,0x3f463f46,
0x3f103f46,0xbf46bf10,0xbedebf2d,0x3f5a3f2d,0xbf2d3e97,0xbf2dbf69,0x3f463f10,0x3f103f46,0xbf72bf5a,0xbe19bede,0x3f753f69,0x3e97,0xbf5abf72,0x3ede3e19,0x3f463f69,0xbf10be97,
0xbf46be97,0xbf10bf69,0x3f723f2d,0x3e193f2d,0xbf2dbf75,0xbf2d0000,0x3f693f10,0x3e973f46,0xbf5abf72,0x3edebe19,0x3f103f69,0xbf46be97,0x3e19bede,0x3f723f5a,0xbf100000,0xbf46bf75,
0xbf10bf75,0x3f460000,0xbe193f2d,0xbf72bf2d,0xbf2d3e97,0xbf2d3f69,0x3f753f10,0x3f46,0xbedebf72,0x3f5a3e19,0xbe973f10,0xbf69bf46,0x3f723ede,0x3e193f5a,0xbf46bf69,0x3f10be97,
0x3f46be97,0x3f103f69,0xbf5abf2d,0x3edebf2d,0xbf2d3f46,0xbf2dbf10,0x3f693f10,0xbe973f46,0x3e19bf5a,0x3f723ede,0xbf690000,0xbe97bf75,0x3ede3f72,0xbf5a3e19,0x3f10bf10,0x3f463f46,
0x3f103f46,0xbf463f10,0x3f2dbf2d,0x3f2d3f2d,0xbf2dbf46,0xbf2dbf10,0x3f463f10,0xbf103f46,0x3f2dbf2d,0x3f2d3f2d,0xbf46bf10,0x3f10bf46,0xbf2d3f2d,0xbf2dbf2d,0x3f463f10,0xbf103f46,
0xbf463f46,0xbf10bf10,0x3ede3f2d,0xbf5a3f2d,0xbf2dbe97,0xbf2d3f69,0x3f103f10,0xbf463f46,0x3f72bede,0x3e193f5a,0xbf69,0x3f75be97,0xbf5abe19,0x3edebf72,0xbf103f69,0xbf46be97,
0xbf10be97,0x3f46bf69,0xbf723f2d,0xbe19bf2d,0xbf2d3f75,0xbf2d0000,0x3e973f10,0xbf693f46,0x3f5abe19,0xbede3f72,0x3f46bf69,0x3f103e97,0x3e19bf5a,0x3f72bede,0xbf460000,0x3f10bf75,
0x3f46bf75,0x3f100000,0x3e19bf2d,0x3f72bf2d,0xbf2dbe97,0xbf2dbf69,0x3f10,0xbf753f46,0x3ede3e19,0xbf5a3f72,0x3f69bf10,0xbe973f46,0x3f72bf5a,0x3e193ede,0x3f10bf69,0x3f46be97,
0x3f10be97,0xbf463f69,0x3f5abf2d,0xbede3f2d,0xbf2dbf46,0xbf2d3f10,0xbe973f10,0xbf693f46,0xbe193ede,0xbf723f5a,0x3e970000,0xbf693f75,0x3edebe19,0xbf5a3f72,0x3f46bf10,0xbf103f46,
0xbf463f46,0xbf103f10,0xbf2d3f2d,0xbf2d3f2d,0xbf2d3f46,0xbf2d3f10,0xbf103f10,0xbf463f46,0xbf2d3f2d,0xbf2d3f2d,0xbf103f10,0xbf463f46,0xbf2d3f2d,0xbf2d3f2d,0xbf103f10,0xbf463f46,
0xbf103f46,0x3f46bf10,0xbede3f2d,0x3f5abf2d,0xbf2d3e97,0xbf2dbf69,0xbf463f10,0xbf103f46,0xbf723f5a,0xbe193ede,0xbf753f69,0x3e97,0xbf5a3f72,0x3edebe19,0xbf463f69,0x3f10be97,
0,0,0xbf69,0x3e97,0,0,0,0,0,0,0,0,0,0,0,0,
0,0,0x3f10,0x3f46,0,0,0,0,0,0,0,0,0,0,0,0,
0,0,0x3f10,0xbf46,0,0,0,0,0,0,0,0,0,0,0,0,
0,0,0xbf69,0xbe97,0,0,0,0,0,0,0,0,0,0,0,0,
0,0,0,0x3f75,0,0,0,0,0,0,0,0,0,0,0,0,
0,0,0x3f69,0xbe97,0,0,0,0,0,0,0,0,0,0,0,0,
0,0,0xbf10,0xbf46,0,0,0,0,0,0,0,0,0,0,0,0,
0,0,0xbf10,0x3f46,0,0,0,0,0,0,0,0,0,0,0,0,
0,0,0x3f69,0x3e97,0,0,0,0,0,0,0,0,0,0,0,0,
0,0,0,0xbf75,0,0,0,0,0,0,0,0,0,0,0,0,
0,0,0xbf69,0x3e97,0,0,0,0,0,0,0,0,0,0,0,0,
0,0,0x3f10,0x3f46,0,0,0,0,0,0,0,0,0,0,0,0,
0,0,0x3f10,0xbf46,0,0,0,0,0,0,0,0,0,0,0,0,
0,0,0xbf69,0xbe97,0,0,0,0,0,0,0,0,0,0,0,0,
0,0,0,0x3f75,0,0,0,0,0,0,0,0,0,0,0,0,
0,0,0x3f69,0xbe97,0,0,0,0,0,0,0,0,0,0,0,0,
0,0,0xbf10,0xbf46,0,0,0,0,0,0,0,0,0,0,0,0,
0,0,0xbf10,0x3f46,0,0,0,0,0,0,0,0,0,0,0,0,
0,0,0x3f69,0x3e97,0,0,0,0,0,0,0,0,0,0,0,0,
0,0,0,0xbf75,0,0,0,0,0,0,0,0,0,0,0,0,
0,0,0x3f10,0x3f46,0,0,0,0,0,0,0,0,0,0,0,0,
0,0,0x3f10,0xbf46,0,0,0,0,0,0,0,0,0,0,0,0,
0,0,0xbf69,0xbe97,0,0,0,0,0,0,0,0,0,0,0,0,
0,0,0,0x3f75,0,0,0,0,0,0,0,0,0,0,0,0,
0,0,0x3f69,0xbe97,0,0,0,0,0,0,0,0,0,0,0,0,
0,0,0xbf10,0xbf46,0,0,0,0,0,0,0,0,0,0,0,0,
0,0,0xbf10,0x3f46,0,0,0,0,0,0,0,0,0,0,0,0,
0,0,0x3f69,0x3e97,0,0,0,0,0,0,0,0,0,0,0,0,
0,0,0,0xbf75,0,0,0,0,0,0,0,0,0,0,0,0,
0,0,0xbf69,0x3e97,0,0,0,0,0,0,0,0,0,0,0,0,
0,0,0x3f10,0x3f46,0,0,0,0,0,0,0,0,0,0,0,0,
0,0,0x3f10,0xbf46,0,0,0,0,0,0,0,0,0,0,0,0,
0xbf463f75,0x3f100000,0xbede3f5a,0x3f5abede,0x3e973e97,0x3f69bf69,0x3f2dbe19,0x3f2dbf72,0x3f75bf46,0xbf10,0x3f5abf72,0xbedebe19,0xbf72bf46,0xbe193f10,0xbf693f69,0x3e973e97,
0xbf103f75,0x3f460000,0x3e193f2d,0x3f72bf2d,0x3f69be97,0x3e97bf69,0x3f5abf5a,0xbedebede,0xbf46,0xbf753f10,0xbf2dbe19,0xbf2d3f72,0xbf723f46,0xbe193f10,0xbf463f69,0x3f103e97,
0xbe973f75,0x3f690000,0x3f2d3ede,0x3f2dbf5a,0x3f46bf46,0xbf10bf10,0xbe19bf5a,0xbf723ede,0xbf753e97,0x3f69,0xbede3f72,0x3f5a3e19,0xbf723e97,0xbe19bf69,0xbf103f69,0x3f463e97,
0x3f75,0x3f750000,0x3f723e19,0x3e19bf72,0xbf75,0xbf750000,0xbf72be19,0xbe193f72,0x3f75,0x3f750000,0x3f723e19,0x3e19bf72,0xbf72bf75,0xbe190000,0xbe973f69,0x3f693e97,
0x3e973f75,0x3f690000,0x3f5abe19,0xbedebf72,0xbf46bf46,0xbf103f10,0xbede3f2d,0x3f5a3f2d,0x3f753e97,0xbf69,0xbe19bf72,0xbf72be19,0xbf723e97,0xbe193f69,0x3f69,0x3f753e97,
0x3f103f75,0x3f460000,0x3edebede,0xbf5abf5a,0xbf69be97,0x3e973f69,0x3f2d3f72,0x3f2dbe19,0xbf46,0xbf75bf10,0xbf5abe19,0x3ede3f72,0xbf723f46,0xbe19bf10,0x3e973f69,0x3f693e97,
0x3f463f75,0x3f100000,0xbe19bf2d,0xbf72bf2d,0xbe973e97,0x3f693f69,0x3f5a3ede,0xbedebf5a,0xbf75bf46,0x3f10,0x3f2d3f72,0x3f2d3e19,0xbf72bf46,0xbe19bf10,0x3f103f69,0x3f463e97,
0x3f693f75,0x3e970000,0xbf2dbf5a,0xbf2dbede,0x3f103f46,0x3f463f10,0xbe19bede,0xbf72bf5a,0x3e97,0x3f753f69,0x3ede3e19,0xbf5abf72,0xbf72be97,0xbe193f69,0x3f463f69,0x3f103e97,
0,0,0,0,0,0,0,0,0,0,0,0,0,0,0,0,
0,0,0,0,0,0,0,0,0,0,0,0,0,0,0,0,
0,0,0,0,0,0,0,0,0,0,0,0,0,0,0,0,
0,0,0,0,0,0,0,0,0,0,0,0,0,0,0,0,
0,0,0,0,0,0,0,0,0,0,0,0,0,0,0,0,
0,0,0,0,0,0,0,0,0,0,0,0,0,0,0,0,
0,0,0,0,0,0,0,0,0,0,0,0,0,0,0,0,
0,0,0,0,0,0,0,0,0,0,0,0,0,0,0,0,
0,0,0,0,0,0,0,0,0,0,0,0,0,0,0,0,
0,0,0,0,0,0,0,0,0,0,0,0,0,0,0,0,
0,0,0,0,0,0,0,0,0,0,0,0,0,0,0,0,
0,0,0,0,0,0,0,0,0,0,0,0,0,0,0,0,
0,0,0,0,0,0,0,0,0,0,0,0,0,0,0,0,
0,0,0,0,0,0,0,0,0,0,0,0,0,0,0,0,
0,0,0,0,0,0,0,0,0,0,0,0,0,0,0,0,
0,0,0,0,0,0,0,0,0,0,0,0,0,0,0,0,
0,0,0,0,0,0,0,0,0,0,0,0,0,0,0,0,
0,0,0,0,0,0,0,0,0,0,0,0,0,0,0,0,
0,0,0,0,0,0,0,0,0,0,0,0,0,0,0,0,
0,0,0,0,0,0,0,0,0,0,0,0,0,0,0,0,
0,0,0,0,0,0,0,0,0,0,0,0,0,0,0,0,
0,0,0,0,0,0,0,0,0,0,0,0,0,0,0,0,
0,0,0,0,0,0,0,0,0,0,0,0,0,0,0,0,
0,0,0,0,0,0,0,0,0,0,0,0,0,0,0,0,
0x3f10,0x3f75bf46,0x3ede3e19,0x3f5abf72,0x3f69bf10,0x3e97bf46,0x3f72bf5a,0xbe19bede,0xbf5abf69,0xbede3e97,0xbf753f46,0x3f10,0xbf2d3f72,0x3f2dbe19,0xbe973f46,0x3f69bf10,
0x3f460000,0x3f10bf75,0x3f72bf2d,0xbe19bf2d,0x3e97bf69,0xbf693e97,0xbedebede,0xbf5a3f5a,0xbf5a3f10,0xbede3f46,0xbf693f46,0x3e973f10,0xbe193f5a,0x3f72bede,0x3f103e97,0x3f46bf69,
0x3f69bf10,0xbe97bf46,0x3e19bf72,0xbf723e19,0xbf690000,0xbe973f75,0xbf2d3f5a,0x3f2d3ede,0xbf5a3f10,0xbedebf46,0xbf463f46,0x3f103f10,0x3ede3f2d,0x3f5abf2d,0x3f75be97,0xbf69,
0x3e97bf69,0xbf69be97,0xbf5abede,0xbede3f5a,0xbe973f69,0x3f693e97,0x3f5a3ede,0x3edebf5a,0xbf5abf69,0xbedebe97,0xbf103f46,0x3f463f10,0x3f5a3ede,0x3edebf5a,0x3f10bf46,0xbf46bf10,
0xbf10bf69,0xbf463e97,0xbf2d3ede,0x3f2d3f5a,0x3f693f10,0x3e97bf46,0x3e19bf5a,0xbf72bede,0xbf5a0000,0xbede3f75,0xbe973f46,0x3f693f10,0x3f723e19,0xbe19bf72,0xbe97bf75,0xbf690000,
0xbf75bf10,0x3f46,0x3ede3f72,0x3f5a3e19,0x3e97bf10,0xbf69bf46,0xbf72bede,0x3e193f5a,0xbf5a3f69,0xbedebe97,0x3f46,0x3f753f10,0x3f2dbe19,0xbf2dbf72,0xbf69bf46,0xbe973f10,
0xbf100000,0x3f463f75,0x3f723f2d,0xbe19bf2d,0xbf69bf69,0xbe973e97,0x3ede3f5a,0x3f5a3ede,0xbf5abf10,0xbedebf46,0x3e973f46,0x3f693f10,0x3e19bede,0xbf72bf5a,0xbf46be97,0x3f103f69,
0x3e973f10,0x3f693f46,0x3e19be19,0xbf72bf72,0xbe970000,0x3f693f75,0x3f2d3ede,0xbf2dbf5a,0xbf5abf10,0xbede3f46,0x3f103f46,0x3f463f10,0xbedebf2d,0xbf5abf2d,0x3e97,0x3f753f69,
0,0,0,0,0,0,0,0,0,0,0,0,0,0,0,0,
0,0,0,0,0,0,0,0,0,0,0,0,0,0,0,0,
0,0,0,0,0,0,0,0,0,0,0,0,0,0,0,0,
0,0,0,0,0,0,0,0,0,0,0,0,0,0,0,0,
0,0,0,0,0,0,0,0,0,0,0,0,0,0,0,0,
0,0,0,0,0,0,0,0,0,0,0,0,0,0,0,0,
0,0,0,0,0,0,0,0,0,0,0,0,0,0,0,0,
0,0,0,0,0,0,0,0,0,0,0,0,0,0,0,0,
0,0,0,0,0,0,0,0,0,0,0,0,0,0,0,0,
0,0,0,0,0,0,0,0,0,0,0,0,0,0,0,0,
0,0,0,0,0,0,0,0,0,0,0,0,0,0,0,0,
0,0,0,0,0,0,0,0,0,0,0,0,0,0,0,0,
0,0,0,0,0,0,0,0,0,0,0,0,0,0,0,0,
0,0,0,0,0,0,0,0,0,0,0,0,0,0,0,0,
0,0,0,0,0,0,0,0,0,0,0,0,0,0,0,0,
0,0,0,0,0,0,0,0,0,0,0,0,0,0,0,0,
0,0,0,0,0,0,0,0,0,0,0,0,0,0,0,0,
0,0,0,0,0,0,0,0,0,0,0,0,0,0,0,0,
0,0,0,0,0,0,0,0,0,0,0,0,0,0,0,0,
0,0,0,0,0,0,0,0,0,0,0,0,0,0,0,0,
0,0,0,0,0,0,0,0,0,0,0,0,0,0,0,0,
0,0,0,0,0,0,0,0,0,0,0,0,0,0,0,0,
0,0,0,0,0,0,0,0,0,0,0,0,0,0,0,0,
0,0,0,0,0,0,0,0,0,0,0,0,0,0,0,0,
0x3f46be97,0x3f10bf69,0x3f72bf2d,0x3e19bf2d,0xbf2dbf75,0xbf2d0000,0xbf693f10,0xbe973f46,0xbf5a3f72,0x3ede3e19,0xbf103f69,0x3f46be97,0x3e193ede,0x3f72bf5a,0x3f100000,0x3f46bf75,
0x3f10bf75,0xbf460000,0xbe19bf2d,0xbf723f2d,0xbf2d3e97,0xbf2d3f69,0xbf753f10,0x3f46,0xbede3f72,0x3f5abe19,0x3e973f10,0x3f69bf46,0x3f72bede,0x3e19bf5a,0x3f46bf69,0xbf10be97,
0xbf46be97,0xbf103f69,0xbf5a3f2d,0x3ede3f2d,0xbf2d3f46,0xbf2dbf10,0xbf693f10,0x3e973f46,0x3e193f5a,0x3f72bede,0x3f690000,0x3e97bf75,0x3edebf72,0xbf5abe19,0xbf10bf10,0xbf463f46,
0xbf103f46,0x3f463f10,0x3f2d3f2d,0x3f2dbf2d,0xbf2dbf46,0xbf2dbf10,0xbf463f10,0x3f103f46,0x3f2d3f2d,0x3f2dbf2d,0x3f46bf10,0xbf10bf46,0xbf2dbf2d,0xbf2d3f2d,0xbf463f10,0x3f103f46,
0x3f463f46,0x3f10bf10,0x3edebf2d,0xbf5abf2d,0xbf2dbe97,0xbf2d3f69,0xbf103f10,0x3f463f46,0x3f723ede,0x3e19bf5a,0xbf69,0xbf75be97,0xbf5a3e19,0x3ede3f72,0x3f103f69,0x3f46be97,
0x3f10be97,0xbf46bf69,0xbf72bf2d,0xbe193f2d,0xbf2d3f75,0xbf2d0000,0xbe973f10,0x3f693f46,0x3f5a3e19,0xbedebf72,0xbf46bf69,0xbf103e97,0x3e193f5a,0x3f723ede,0x3f460000,0xbf10bf75,
0xbf46bf75,0xbf100000,0x3e193f2d,0x3f723f2d,0xbf2dbe97,0xbf2dbf69,0x3f10,0x3f753f46,0x3edebe19,0xbf5abf72,0xbf69bf10,0x3e973f46,0x3f723f5a,0x3e19bede,0xbf10bf69,0xbf46be97,
0xbf10be97,0x3f463f69,0x3f5a3f2d,0xbedebf2d,0xbf2dbf46,0xbf2d3f10,0x3e973f10,0x3f693f46,0xbe19bede,0xbf72bf5a,0xbe970000,0x3f693f75,0x3ede3e19,0xbf5abf72,0xbf46bf10,0x3f103f46,
0,0,0,0,0,0,0,0,0,0,0,0,0,0,0,0,
0,0,0,0,0,0,0,0,0,0,0,0,0,0,0,0,
0,0,0,0,0,0,0,0,0,0,0,0,0,0,0,0,
0,0,0,0,0,0,0,0,0,0,0,0,0,0,0,0,
0,0,0,0,0,0,0,0,0,0,0,0,0,0,0,0,
0,0,0,0,0,0,0,0,0,0,0,0,0,0,0,0,
0,0,0,0,0,0,0,0,0,0,0,0,0,0,0,0,
0,0,0,0,0,0,0,0,0,0,0,0,0,0,0,0,
0,0,0,0,0,0,0,0,0,0,0,0,0,0,0,0,
0,0,0,0,0,0,0,0,0,0,0,0,0,0,0,0,
0,0,0,0,0,0,0,0,0,0,0,0,0,0,0,0,
0,0,0,0,0,0,0,0,0,0,0,0,0,0,0,0,
0,0,0,0,0,0,0,0,0,0,0,0,0,0,0,0,
0,0,0,0,0,0,0,0,0,0,0,0,0,0,0,0,
0,0,0,0,0,0,0,0,0,0,0,0,0,0,0,0,
0,0,0,0,0,0,0,0,0,0,0,0,0,0,0,0,
0,0,0,0,0,0,0,0,0,0,0,0,0,0,0,0,
0,0,0,0,0,0,0,0,0,0,0,0,0,0,0,0,
0,0,0,0,0,0,0,0,0,0,0,0,0,0,0,0,
0,0,0,0,0,0,0,0,0,0,0,0,0,0,0,0,
0,0,0,0,0,0,0,0,0,0,0,0,0,0,0,0,
0,0,0,0,0,0,0,0,0,0,0,0,0,0,0,0,
0,0,0,0,0,0,0,0,0,0,0,0,0,0,0,0,
0,0,0,0,0,0,0,0,0,0,0,0,0,0,0,0,
0,0,0xbf69,0xbe97,0,0,0,0,0,0,0,0,0,0,0,0,
0,0,0,0x3f75,0,0,0,0,0,0,0,0,0,0,0,0,
0,0,0x3f69,0xbe97,0,0,0,0,0,0,0,0,0,0,0,0,
0,0,0xbf10,0xbf46,0,0,0,0,0,0,0,0,0,0,0,0,
0,0,0xbf10,0x3f46,0,0,0,0,0,0,0,0,0,0,0,0,
0,0,0x3f69,0x3e97,0,0,0,0,0,0,0,0,0,0,0,0,
0,0,0,0xbf75,0,0,0,0,0,0,0,0,0,0,0,0,
0,0,0xbf69,0x3e97,0,0,0,0,0,0,0,0,0,0,0,0,
0,0,0,0,0,0,0,0,0,0,0,0,0,0,0,0,
0,0,0,0,0,0,0,0,0,0,0,0,0,0,0,0,
0,0,0,0,0,0,0,0,0,0,0,0,0,0,0,0,
0,0,0,0,0,0,0,0,0,0,0,0,0,0,0,0,
0,0,0,0,0,0,0,0,0,0,0,0,0,0,0,0,
0,0,0,0,0,0,0,0,0,0,0,0,0,0,0,0,
0,0,0,0,0,0,0,0,0,0,0,0,0,0,0,0,
0,0,0,0,0,0,0,0,0,0,0,0,0,0,0,0,
0,0,0,0,0,0,0,0,0,0,0,0,0,0,0,0,
0,0,0,0,0,0,0,0,0,0,0,0,0,0,0,0,
0,0,0,0,0,0,0,0,0,0,0,0,0,0,0,0,
0,0,0,0,0,0,0,0,0,0,0,0,0,0,0,0,
0,0,0,0,0,0,0,0,0,0,0,0,0,0,0,0,
0,0,0,0,0,0,0,0,0,0,0,0,0,0,0,0,
0,0,0,0,0,0,0,0,0,0,0,0,0,0,0,0,
0,0,0,0,0,0,0,0,0,0,0,0,0,0,0,0,
0,0,0,0,0,0,0,0,0,0,0,0,0,0,0,0,
0,0,0,0,0,0,0,0,0,0,0,0,0,0,0,0,
0,0,0,0,0,0,0,0,0,0,0,0,0,0,0,0,
0,0,0,0,0,0,0,0,0,0,0,0,0,0,0,0,
0,0,0,0,0,0,0,0,0,0,0,0,0,0,0,0,
0,0,0,0,0,0,0,0,0,0,0,0,0,0,0,0,
0,0,0,0,0,0,0,0,0,0,0,0,0,0,0,0,
0,0,0,0,0,0,0,0,0,0,0,0,0,0,0,0,
};
constexpr float WSCALE = 1.119068645e-02f;

__device__ __forceinline__ void wgmma_ss_n80_z(float (&d)[40], uint64_t da, uint64_t db) {
  asm volatile("{\n.reg .pred p;\nsetp.ne.b32 p, 0, 0;\nwgmma.mma_async.sync.aligned.m64n80k16.f32.bf16.bf16 {%0,%1,%2,%3,%4,%5,%6,%7,%8,%9,%10,%11,%12,%13,%14,%15,%16,%17,%18,%19,%20,%21,%22,%23,%24,%25,%26,%27,%28,%29,%30,%31,%32,%33,%34,%35,%36,%37,%38,%39}, %40, %41, p, 1, 1, 1, 0;\n}\n"
    : "=f"(d[0]), "=f"(d[1]), "=f"(d[2]), "=f"(d[3]), "=f"(d[4]), "=f"(d[5]), "=f"(d[6]), "=f"(d[7]), "=f"(d[8]), "=f"(d[9]), "=f"(d[10]), "=f"(d[11]), "=f"(d[12]), "=f"(d[13]), "=f"(d[14]), "=f"(d[15]), "=f"(d[16]), "=f"(d[17]), "=f"(d[18]), "=f"(d[19]), "=f"(d[20]), "=f"(d[21]), "=f"(d[22]), "=f"(d[23]), "=f"(d[24]), "=f"(d[25]), "=f"(d[26]), "=f"(d[27]), "=f"(d[28]), "=f"(d[29]), "=f"(d[30]), "=f"(d[31]), "=f"(d[32]), "=f"(d[33]), "=f"(d[34]), "=f"(d[35]), "=f"(d[36]), "=f"(d[37]), "=f"(d[38]), "=f"(d[39])
    : "l"(da), "l"(db));
}
__device__ __forceinline__ void wgmma_ss_n80_a(float (&d)[40], uint64_t da, uint64_t db) {
  asm volatile("{\n.reg .pred p;\nsetp.ne.b32 p, 1, 0;\nwgmma.mma_async.sync.aligned.m64n80k16.f32.bf16.bf16 {%0,%1,%2,%3,%4,%5,%6,%7,%8,%9,%10,%11,%12,%13,%14,%15,%16,%17,%18,%19,%20,%21,%22,%23,%24,%25,%26,%27,%28,%29,%30,%31,%32,%33,%34,%35,%36,%37,%38,%39}, %40, %41, p, 1, 1, 1, 0;\n}\n"
    : "+f"(d[0]), "+f"(d[1]), "+f"(d[2]), "+f"(d[3]), "+f"(d[4]), "+f"(d[5]), "+f"(d[6]), "+f"(d[7]), "+f"(d[8]), "+f"(d[9]), "+f"(d[10]), "+f"(d[11]), "+f"(d[12]), "+f"(d[13]), "+f"(d[14]), "+f"(d[15]), "+f"(d[16]), "+f"(d[17]), "+f"(d[18]), "+f"(d[19]), "+f"(d[20]), "+f"(d[21]), "+f"(d[22]), "+f"(d[23]), "+f"(d[24]), "+f"(d[25]), "+f"(d[26]), "+f"(d[27]), "+f"(d[28]), "+f"(d[29]), "+f"(d[30]), "+f"(d[31]), "+f"(d[32]), "+f"(d[33]), "+f"(d[34]), "+f"(d[35]), "+f"(d[36]), "+f"(d[37]), "+f"(d[38]), "+f"(d[39])
    : "l"(da), "l"(db));
}

__device__ __forceinline__ void wgmma_rs_n40_z(float (&d)[20], uint32_t a0, uint32_t a1, uint32_t a2, uint32_t a3, uint64_t db) {
  asm volatile("{\n.reg .pred p;\nsetp.ne.b32 p, 0, 0;\nwgmma.mma_async.sync.aligned.m64n40k16.f32.bf16.bf16 {%0,%1,%2,%3,%4,%5,%6,%7,%8,%9,%10,%11,%12,%13,%14,%15,%16,%17,%18,%19}, {%20,%21,%22,%23}, %24, p, 1, 1, 0;\n}\n"
    : "=f"(d[0]), "=f"(d[1]), "=f"(d[2]), "=f"(d[3]), "=f"(d[4]), "=f"(d[5]), "=f"(d[6]), "=f"(d[7]), "=f"(d[8]), "=f"(d[9]), "=f"(d[10]), "=f"(d[11]), "=f"(d[12]), "=f"(d[13]), "=f"(d[14]), "=f"(d[15]), "=f"(d[16]), "=f"(d[17]), "=f"(d[18]), "=f"(d[19])
    : "r"(a0), "r"(a1), "r"(a2), "r"(a3), "l"(db));
}
__device__ __forceinline__ void wgmma_rs_n40_a(float (&d)[20], uint32_t a0, uint32_t a1, uint32_t a2, uint32_t a3, uint64_t db) {
  asm volatile("{\n.reg .pred p;\nsetp.ne.b32 p, 1, 0;\nwgmma.mma_async.sync.aligned.m64n40k16.f32.bf16.bf16 {%0,%1,%2,%3,%4,%5,%6,%7,%8,%9,%10,%11,%12,%13,%14,%15,%16,%17,%18,%19}, {%20,%21,%22,%23}, %24, p, 1, 1, 0;\n}\n"
    : "+f"(d[0]), "+f"(d[1]), "+f"(d[2]), "+f"(d[3]), "+f"(d[4]), "+f"(d[5]), "+f"(d[6]), "+f"(d[7]), "+f"(d[8]), "+f"(d[9]), "+f"(d[10]), "+f"(d[11]), "+f"(d[12]), "+f"(d[13]), "+f"(d[14]), "+f"(d[15]), "+f"(d[16]), "+f"(d[17]), "+f"(d[18]), "+f"(d[19])
    : "r"(a0), "r"(a1), "r"(a2), "r"(a3), "l"(db));
}

__device__ __forceinline__ void wgmma_rs_n64_z(float (&d)[32], uint32_t a0, uint32_t a1, uint32_t a2, uint32_t a3, uint64_t db) {
  asm volatile("{\n.reg .pred p;\nsetp.ne.b32 p, 0, 0;\nwgmma.mma_async.sync.aligned.m64n64k16.f32.bf16.bf16 {%0,%1,%2,%3,%4,%5,%6,%7,%8,%9,%10,%11,%12,%13,%14,%15,%16,%17,%18,%19,%20,%21,%22,%23,%24,%25,%26,%27,%28,%29,%30,%31}, {%32,%33,%34,%35}, %36, p, 1, 1, 1;\n}\n"
    : "=f"(d[0]), "=f"(d[1]), "=f"(d[2]), "=f"(d[3]), "=f"(d[4]), "=f"(d[5]), "=f"(d[6]), "=f"(d[7]), "=f"(d[8]), "=f"(d[9]), "=f"(d[10]), "=f"(d[11]), "=f"(d[12]), "=f"(d[13]), "=f"(d[14]), "=f"(d[15]), "=f"(d[16]), "=f"(d[17]), "=f"(d[18]), "=f"(d[19]), "=f"(d[20]), "=f"(d[21]), "=f"(d[22]), "=f"(d[23]), "=f"(d[24]), "=f"(d[25]), "=f"(d[26]), "=f"(d[27]), "=f"(d[28]), "=f"(d[29]), "=f"(d[30]), "=f"(d[31])
    : "r"(a0), "r"(a1), "r"(a2), "r"(a3), "l"(db));
}
__device__ __forceinline__ void wgmma_rs_n64_a(float (&d)[32], uint32_t a0, uint32_t a1, uint32_t a2, uint32_t a3, uint64_t db) {
  asm volatile("{\n.reg .pred p;\nsetp.ne.b32 p, 1, 0;\nwgmma.mma_async.sync.aligned.m64n64k16.f32.bf16.bf16 {%0,%1,%2,%3,%4,%5,%6,%7,%8,%9,%10,%11,%12,%13,%14,%15,%16,%17,%18,%19,%20,%21,%22,%23,%24,%25,%26,%27,%28,%29,%30,%31}, {%32,%33,%34,%35}, %36, p, 1, 1, 1;\n}\n"
    : "+f"(d[0]), "+f"(d[1]), "+f"(d[2]), "+f"(d[3]), "+f"(d[4]), "+f"(d[5]), "+f"(d[6]), "+f"(d[7]), "+f"(d[8]), "+f"(d[9]), "+f"(d[10]), "+f"(d[11]), "+f"(d[12]), "+f"(d[13]), "+f"(d[14]), "+f"(d[15]), "+f"(d[16]), "+f"(d[17]), "+f"(d[18]), "+f"(d[19]), "+f"(d[20]), "+f"(d[21]), "+f"(d[22]), "+f"(d[23]), "+f"(d[24]), "+f"(d[25]), "+f"(d[26]), "+f"(d[27]), "+f"(d[28]), "+f"(d[29]), "+f"(d[30]), "+f"(d[31])
    : "r"(a0), "r"(a1), "r"(a2), "r"(a3), "l"(db));
}

__device__ __forceinline__ void wgmma_rs_n88_z(float (&d)[44], uint32_t a0, uint32_t a1, uint32_t a2, uint32_t a3, uint64_t db) {
  asm volatile("{\n.reg .pred p;\nsetp.ne.b32 p, 0, 0;\nwgmma.mma_async.sync.aligned.m64n88k16.f32.bf16.bf16 {%0,%1,%2,%3,%4,%5,%6,%7,%8,%9,%10,%11,%12,%13,%14,%15,%16,%17,%18,%19,%20,%21,%22,%23,%24,%25,%26,%27,%28,%29,%30,%31,%32,%33,%34,%35,%36,%37,%38,%39,%40,%41,%42,%43}, {%44,%45,%46,%47}, %48, p, 1, 1, 0;\n}\n"
    : "=f"(d[0]), "=f"(d[1]), "=f"(d[2]), "=f"(d[3]), "=f"(d[4]), "=f"(d[5]), "=f"(d[6]), "=f"(d[7]), "=f"(d[8]), "=f"(d[9]), "=f"(d[10]), "=f"(d[11]), "=f"(d[12]), "=f"(d[13]), "=f"(d[14]), "=f"(d[15]), "=f"(d[16]), "=f"(d[17]), "=f"(d[18]), "=f"(d[19]), "=f"(d[20]), "=f"(d[21]), "=f"(d[22]), "=f"(d[23]), "=f"(d[24]), "=f"(d[25]), "=f"(d[26]), "=f"(d[27]), "=f"(d[28]), "=f"(d[29]), "=f"(d[30]), "=f"(d[31]), "=f"(d[32]), "=f"(d[33]), "=f"(d[34]), "=f"(d[35]), "=f"(d[36]), "=f"(d[37]), "=f"(d[38]), "=f"(d[39]), "=f"(d[40]), "=f"(d[41]), "=f"(d[42]), "=f"(d[43])
    : "r"(a0), "r"(a1), "r"(a2), "r"(a3), "l"(db));
}
__device__ __forceinline__ void wgmma_rs_n88_a(float (&d)[44], uint32_t a0, uint32_t a1, uint32_t a2, uint32_t a3, uint64_t db) {
  asm volatile("{\n.reg .pred p;\nsetp.ne.b32 p, 1, 0;\nwgmma.mma_async.sync.aligned.m64n88k16.f32.bf16.bf16 {%0,%1,%2,%3,%4,%5,%6,%7,%8,%9,%10,%11,%12,%13,%14,%15,%16,%17,%18,%19,%20,%21,%22,%23,%24,%25,%26,%27,%28,%29,%30,%31,%32,%33,%34,%35,%36,%37,%38,%39,%40,%41,%42,%43}, {%44,%45,%46,%47}, %48, p, 1, 1, 0;\n}\n"
    : "+f"(d[0]), "+f"(d[1]), "+f"(d[2]), "+f"(d[3]), "+f"(d[4]), "+f"(d[5]), "+f"(d[6]), "+f"(d[7]), "+f"(d[8]), "+f"(d[9]), "+f"(d[10]), "+f"(d[11]), "+f"(d[12]), "+f"(d[13]), "+f"(d[14]), "+f"(d[15]), "+f"(d[16]), "+f"(d[17]), "+f"(d[18]), "+f"(d[19]), "+f"(d[20]), "+f"(d[21]), "+f"(d[22]), "+f"(d[23]), "+f"(d[24]), "+f"(d[25]), "+f"(d[26]), "+f"(d[27]), "+f"(d[28]), "+f"(d[29]), "+f"(d[30]), "+f"(d[31]), "+f"(d[32]), "+f"(d[33]), "+f"(d[34]), "+f"(d[35]), "+f"(d[36]), "+f"(d[37]), "+f"(d[38]), "+f"(d[39]), "+f"(d[40]), "+f"(d[41]), "+f"(d[42]), "+f"(d[43])
    : "r"(a0), "r"(a1), "r"(a2), "r"(a3), "l"(db));
}

__device__ __forceinline__ void wgmma_ss_n32_z(float (&d)[16], uint64_t da, uint64_t db) {
  asm volatile("{\n.reg .pred p;\nsetp.ne.b32 p, 0, 0;\nwgmma.mma_async.sync.aligned.m64n32k16.f32.bf16.bf16 {%0,%1,%2,%3,%4,%5,%6,%7,%8,%9,%10,%11,%12,%13,%14,%15}, %16, %17, p, 1, 1, 1, 0;\n}\n"
    : "=f"(d[0]), "=f"(d[1]), "=f"(d[2]), "=f"(d[3]), "=f"(d[4]), "=f"(d[5]), "=f"(d[6]), "=f"(d[7]), "=f"(d[8]), "=f"(d[9]), "=f"(d[10]), "=f"(d[11]), "=f"(d[12]), "=f"(d[13]), "=f"(d[14]), "=f"(d[15])
    : "l"(da), "l"(db));
}
__device__ __forceinline__ void wgmma_ss_n32_a(float (&d)[16], uint64_t da, uint64_t db) {
  asm volatile("{\n.reg .pred p;\nsetp.ne.b32 p, 1, 0;\nwgmma.mma_async.sync.aligned.m64n32k16.f32.bf16.bf16 {%0,%1,%2,%3,%4,%5,%6,%7,%8,%9,%10,%11,%12,%13,%14,%15}, %16, %17, p, 1, 1, 1, 0;\n}\n"
    : "+f"(d[0]), "+f"(d[1]), "+f"(d[2]), "+f"(d[3]), "+f"(d[4]), "+f"(d[5]), "+f"(d[6]), "+f"(d[7]), "+f"(d[8]), "+f"(d[9]), "+f"(d[10]), "+f"(d[11]), "+f"(d[12]), "+f"(d[13]), "+f"(d[14]), "+f"(d[15])
    : "l"(da), "l"(db));
}

__device__ __forceinline__ void wgmma_rs_n56_z(float (&d)[28], uint32_t a0, uint32_t a1, uint32_t a2, uint32_t a3, uint64_t db) {
  asm volatile("{\n.reg .pred p;\nsetp.ne.b32 p, 0, 0;\nwgmma.mma_async.sync.aligned.m64n56k16.f32.bf16.bf16 {%0,%1,%2,%3,%4,%5,%6,%7,%8,%9,%10,%11,%12,%13,%14,%15,%16,%17,%18,%19,%20,%21,%22,%23,%24,%25,%26,%27}, {%28,%29,%30,%31}, %32, p, 1, 1, 0;\n}\n"
    : "=f"(d[0]), "=f"(d[1]), "=f"(d[2]), "=f"(d[3]), "=f"(d[4]), "=f"(d[5]), "=f"(d[6]), "=f"(d[7]), "=f"(d[8]), "=f"(d[9]), "=f"(d[10]), "=f"(d[11]), "=f"(d[12]), "=f"(d[13]), "=f"(d[14]), "=f"(d[15]), "=f"(d[16]), "=f"(d[17]), "=f"(d[18]), "=f"(d[19]), "=f"(d[20]), "=f"(d[21]), "=f"(d[22]), "=f"(d[23]), "=f"(d[24]), "=f"(d[25]), "=f"(d[26]), "=f"(d[27])
    : "r"(a0), "r"(a1), "r"(a2), "r"(a3), "l"(db));
}
__device__ __forceinline__ void wgmma_rs_n56_a(float (&d)[28], uint32_t a0, uint32_t a1, uint32_t a2, uint32_t a3, uint64_t db) {
  asm volatile("{\n.reg .pred p;\nsetp.ne.b32 p, 1, 0;\nwgmma.mma_async.sync.aligned.m64n56k16.f32.bf16.bf16 {%0,%1,%2,%3,%4,%5,%6,%7,%8,%9,%10,%11,%12,%13,%14,%15,%16,%17,%18,%19,%20,%21,%22,%23,%24,%25,%26,%27}, {%28,%29,%30,%31}, %32, p, 1, 1, 0;\n}\n"
    : "+f"(d[0]), "+f"(d[1]), "+f"(d[2]), "+f"(d[3]), "+f"(d[4]), "+f"(d[5]), "+f"(d[6]), "+f"(d[7]), "+f"(d[8]), "+f"(d[9]), "+f"(d[10]), "+f"(d[11]), "+f"(d[12]), "+f"(d[13]), "+f"(d[14]), "+f"(d[15]), "+f"(d[16]), "+f"(d[17]), "+f"(d[18]), "+f"(d[19]), "+f"(d[20]), "+f"(d[21]), "+f"(d[22]), "+f"(d[23]), "+f"(d[24]), "+f"(d[25]), "+f"(d[26]), "+f"(d[27])
    : "r"(a0), "r"(a1), "r"(a2), "r"(a3), "l"(db));
}

constexpr int NW = 126, NP1 = 384, NP2 = 600, NP3 = 384;
constexpr int SMEM_BYTES = 67584 + 128;
constexpr int BAR_OFF = 67584;

__device__ uint4 g_xf[200 * 3 * 256 * 8];
__device__ uint4 g_wf[200 * 3 * 6 * 128];
__device__ unsigned g_cnt[8 * 32];

struct Maps { CUtensorMap x6, x28, w, f, y4, y2; };

__device__ __forceinline__ uint32_t smem_u32(const void* p) { return (uint32_t)__cvta_generic_to_shared(p); }
__device__ __forceinline__ void mbar_init(uint32_t bar, uint32_t cnt) { asm volatile("mbarrier.init.shared::cta.b64 [%0], %1;" :: "r"(bar), "r"(cnt) : "memory"); }
__device__ __forceinline__ void mbar_expect_tx(uint32_t bar, uint32_t bytes) { asm volatile("mbarrier.arrive.expect_tx.shared::cta.b64 _, [%0], %1;" :: "r"(bar), "r"(bytes) : "memory"); }
__device__ __forceinline__ void mbar_wait(uint32_t bar, uint32_t parity) {
    uint32_t ok, it = 0;
    do {
        asm volatile("{\n.reg .pred p;\nmbarrier.try_wait.parity.shared::cta.b64 p, [%1], %2;\nselp.u32 %0, 1, 0, p;\n}" : "=r"(ok) : "r"(bar), "r"(parity) : "memory");
        if (++it > (1u << 22)) __trap();
    } while (!ok);
}
__device__ __forceinline__ void fence_async() { asm volatile("fence.proxy.async;" ::: "memory"); }
__device__ __forceinline__ void fence_async_smem() { asm volatile("fence.proxy.async.shared::cta;" ::: "memory"); }
__device__ __forceinline__ void bulk_g2s(uint32_t dst, const void* src, uint32_t bytes, uint32_t bar) {
    asm volatile("cp.async.bulk.shared::cluster.global.mbarrier::complete_tx::bytes [%0], [%1], %2, [%3];" :: "r"(dst), "l"(src), "r"(bytes), "r"(bar) : "memory");
}
__device__ __forceinline__ void bulk_s2g(void* dst, uint32_t src, uint32_t bytes) {
    asm volatile("cp.async.bulk.global.shared::cta.bulk_group [%0], [%1], %2;" :: "l"(dst), "r"(src), "r"(bytes) : "memory");
}
__device__ __forceinline__ void tma_ld3(uint32_t dst, const CUtensorMap* m, int c0, int c1, int c2, uint32_t bar) {
    asm volatile("cp.async.bulk.tensor.3d.shared::cluster.global.mbarrier::complete_tx::bytes [%0], [%1, {%3, %4, %5}], [%2];"
                 :: "r"(dst), "l"(m), "r"(bar), "r"(c0), "r"(c1), "r"(c2) : "memory");
}
__device__ __forceinline__ void tma_st3(const CUtensorMap* m, uint32_t src, int c0, int c1, int c2) {
    asm volatile("cp.async.bulk.tensor.3d.global.shared::cta.bulk_group [%0, {%2, %3, %4}], [%1];"
                 :: "l"(m), "r"(src), "r"(c0), "r"(c1), "r"(c2) : "memory");
}
__device__ __forceinline__ void bulk_commit() { asm volatile("cp.async.bulk.commit_group;" ::: "memory"); }
__device__ __forceinline__ void bulk_wait0() { asm volatile("cp.async.bulk.wait_group 0;" ::: "memory"); }
__device__ __forceinline__ void wg_fence() { asm volatile("wgmma.fence.sync.aligned;" ::: "memory"); }
__device__ __forceinline__ void wg_commit() { asm volatile("wgmma.commit_group.sync.aligned;" ::: "memory"); }
template <int N> __device__ __forceinline__ void wg_wait() { asm volatile("wgmma.wait_group.sync.aligned %0;" :: "n"(N) : "memory"); }
template <int N> __device__ __forceinline__ void reg_fence(float (&d)[N]) {
#pragma unroll
    for (int i = 0; i < N; i++) asm volatile("" : "+f"(d[i]) :: "memory");
}
__device__ __forceinline__ uint32_t pack2(float lo, float hi) {
    uint32_t r; asm("cvt.rn.bf16x2.f32 %0, %1, %2;" : "=r"(r) : "f"(hi), "f"(lo)); return r;
}
__device__ __forceinline__ void stm4(uint32_t a, uint32_t r0, uint32_t r1, uint32_t r2, uint32_t r3) {
    asm volatile("stmatrix.sync.aligned.m8n8.x4.trans.shared.b16 [%0], {%1,%2,%3,%4};" :: "r"(a), "r"(r0), "r"(r1), "r"(r2), "r"(r3) : "memory");
}
__device__ __forceinline__ void stm2(uint32_t a, uint32_t r0, uint32_t r1) {
    asm volatile("stmatrix.sync.aligned.m8n8.x2.trans.shared.b16 [%0], {%1,%2};" :: "r"(a), "r"(r0), "r"(r1) : "memory");
}
__device__ __forceinline__ void stm1(uint32_t a, uint32_t r0) {
    asm volatile("stmatrix.sync.aligned.m8n8.x1.trans.shared.b16 [%0], {%1};" :: "r"(a), "r"(r0) : "memory");
}
__device__ __forceinline__ uint64_t mkdesc(uint32_t addr, uint32_t lbo, uint32_t sbo, uint32_t swz) {
    return (uint64_t)((addr & 0x3FFFF) >> 4) | ((uint64_t)(lbo >> 4) << 16) | ((uint64_t)(sbo >> 4) << 32) | ((uint64_t)swz << 62);
}
__device__ __forceinline__ void cnt_add(int i) { asm volatile("red.release.gpu.global.add.u32 [%0], 1;" :: "l"(&g_cnt[i * 32]) : "memory"); }
__device__ __forceinline__ void cnt_wait(int i, unsigned target) {
    unsigned v, it = 0;
    while (true) {
        asm volatile("ld.acquire.gpu.global.u32 %0, [%1];" : "=r"(v) : "l"(&g_cnt[i * 32]) : "memory");
        if (v >= target) break;
        if (++it > (1u << 22)) __trap();
        __nanosleep(32);
    }
}

__device__ __forceinline__ void task_w(int t, uint32_t sb, const Maps& mp) {
    const int tid = threadIdx.x, w = tid >> 5, lane = tid & 31;
    const int mb = t / 18, nb = t % 18, s = nb / 3, b = nb % 3;
    const uint32_t bar = sb + BAR_OFF;
    if (tid == 0) {
        mbar_init(bar, 1); fence_async_smem();
        mbar_expect_tx(bar, 57344);
        tma_ld3(sb, &mp.w, 32 * b, 0, 16 * s, bar);
    }
    uint4 a[4];
#pragma unroll
    for (int j = 0; j < 4; j++) a[j] = __ldg(reinterpret_cast<const uint4*>(TAB_W) + (mb * 4 + j) * 128 + tid);
    __syncthreads();
    const int phi = 32 * mb + 8 * w + (lane >> 2), q = lane & 3;
    const bool swp = (phi & 1);
    uint4* dst = g_wf + ((phi * 3 + b) * 6 + s) * 128 + q;
    mbar_wait(bar, 0);
#pragma unroll 1
    for (int qp = 0; qp < 4; qp++) {
        float lo[32], hi[32];
        const uint64_t dl = mkdesc(sb + 2 * qp * 3584, 3584, 512, 2), dh = mkdesc(sb + (2 * qp + 8) * 3584, 3584, 512, 2);
        wg_fence();
        wgmma_rs_n64_z(lo, a[0].x, a[0].y, a[0].z, a[0].w, dl);
        wgmma_rs_n64_z(hi, a[0].x, a[0].y, a[0].z, a[0].w, dh);
        wgmma_rs_n64_a(lo, a[1].x, a[1].y, a[1].z, a[1].w, dl + (16 * 64 >> 4));
        wgmma_rs_n64_a(hi, a[1].x, a[1].y, a[1].z, a[1].w, dh + (16 * 64 >> 4));
        wgmma_rs_n64_a(lo, a[2].x, a[2].y, a[2].z, a[2].w, dl + (32 * 64 >> 4));
        wgmma_rs_n64_a(hi, a[2].x, a[2].y, a[2].z, a[2].w, dh + (32 * 64 >> 4));
        wgmma_rs_n64_a(lo, a[3].x, a[3].y, a[3].z, a[3].w, dl + (40 * 64 >> 4));
        wgmma_rs_n64_a(hi, a[3].x, a[3].y, a[3].z, a[3].w, dh + (40 * 64 >> 4));
        wg_commit();
        wg_wait<0>();
        reg_fence(lo); reg_fence(hi);
        if (phi < 200) {
#pragma unroll
            for (int j = 0; j < 4; j++)
#pragma unroll
                for (int e = 0; e < 2; e++) {
                    uint32_t l0 = pack2(lo[4 * j + e] * WSCALE, lo[16 + 4 * j + e] * WSCALE);
                    uint32_t l1 = pack2(lo[4 * j + 2 + e] * WSCALE, lo[16 + 4 * j + 2 + e] * WSCALE);
                    uint32_t h0 = pack2(hi[4 * j + e] * WSCALE, hi[16 + 4 * j + e] * WSCALE);
                    uint32_t h1 = pack2(hi[4 * j + 2 + e] * WSCALE, hi[16 + 4 * j + 2 + e] * WSCALE);
                    uint4 v = swp ? make_uint4(h0, h1, l0, l1) : make_uint4(l0, l1, h0, h1);
                    __stcg(dst + j * 32 + (e * 4 + qp) * 4, v);
                }
        }
    }
    __syncthreads();
    if (tid == 0) { __threadfence(); cnt_add(0); cnt_add(1); cnt_add(2); }
}

__device__ __forceinline__ void task_p1(int u, uint32_t sb, const Maps& mp) {
    const int tid = threadIdx.x, w = tid >> 5, lane = tid & 31;
    const int pair = u / 3, chunk = u % 3, tp = pair >> 4, tx = pair & 15;
    const uint32_t bar = sb + BAR_OFF, sB1 = sb + 43520, sB2 = sb + 56320;
    if (tid == 0) {
#pragma unroll
        for (int i = 0; i < 5; i++) mbar_init(bar + 8 * i, 1);
        fence_async_smem();
        const int r0 = tp == 0 ? 218 : 28 * tp - 6;
#pragma unroll
        for (int g = 0; g < 5; g++) {
            int col = 14 * tx - 8 + 4 * g; if (col < 0) col += 224;
            mbar_expect_tx(bar + 8 * g, g == 0 ? 8704 + 16640 : 8704);
            tma_ld3(sb + g * 8704, &mp.x6, 32 * chunk, col, r0, bar + 8 * g);
            tma_ld3(sb + g * 8704 + 1536, &mp.x28, 32 * chunk, col, 28 * tp, bar + 8 * g);
            if (g == 0) bulk_g2s(sB1, TAB_P1, 16640, bar);
        }
    }
    __syncthreads();
    uint32_t fr[5][10][2];
    {
        float acc[2][40];
        const uint64_t dA = mkdesc(sb, 3584, 512, 2), dB = mkdesc(sB1, 128, 256, 0);
        auto issue = [&](int g, float (&d)[40]) {
            mbar_wait(bar + 8 * g, 0);
            wg_fence();
            wgmma_ss_n80_z(d, dA + (g * 8704 >> 4), dB);
#pragma unroll
            for (int j = 1; j < 5; j++) wgmma_ss_n80_a(d, dA + ((g * 8704 + j * 1024) >> 4), dB + (j * 2560 >> 4));
            wg_commit();
        };
        issue(0, acc[0]);
#pragma unroll
        for (int g = 0; g < 5; g++) {
            if (g < 4) { issue(g + 1, acc[(g + 1) & 1]); wg_wait<1>(); } else wg_wait<0>();
            reg_fence(acc[g & 1]);
#pragma unroll
            for (int f = 0; f < 10; f++) {
                fr[g][f][0] = pack2(acc[g & 1][4 * f], acc[g & 1][4 * f + 1]);
                fr[g][f][1] = pack2(acc[g & 1][4 * f + 2], acc[g & 1][4 * f + 3]);
            }
        }
    }
    __syncthreads();
    {
        float acc[2][20];
        const uint64_t dB = mkdesc(sB2, 128, 256, 0);
        const int i = lane & 7, mi = lane >> 3, th = w >> 1, tz = (2 * pair + th) & 3;
        const uint32_t soff = sb + th * 2560 + (mi >> 1) * 512 + (i >> 1) * 128 + (i & 1) * 64 + (((2 * (w & 1) + (mi & 1)) ^ tz ^ (i >> 1)) << 4);
        auto issue = [&](int f, float (&d)[20]) {
            wg_fence();
            wgmma_rs_n40_z(d, fr[0][f][0], fr[0][f][1], fr[1][f][0], fr[1][f][1], dB);
            wgmma_rs_n40_a(d, fr[2][f][0], fr[2][f][1], fr[3][f][0], fr[3][f][1], dB + (1280 >> 4));
            wgmma_rs_n40_a(d, fr[4][f][0], fr[4][f][1], 0u, 0u, dB + (2560 >> 4));
            wg_commit();
        };
        issue(0, acc[0]);
#pragma unroll
        for (int f = 0; f < 10; f++) {
            if (f < 9) { issue(f + 1, acc[(f + 1) & 1]); wg_wait<1>(); } else wg_wait<0>();
            float (&d)[20] = acc[f & 1];
            reg_fence(d);
            const uint32_t a = soff + f * 5120;
            stm4(a, pack2(d[0], d[1]), pack2(d[2], d[3]), pack2(d[4], d[5]), pack2(d[6], d[7]));
            stm4(a + 1024, pack2(d[8], d[9]), pack2(d[10], d[11]), pack2(d[12], d[13]), pack2(d[14], d[15]));
            stm2(a + 2048, pack2(d[16], d[17]), pack2(d[18], d[19]));
            if (f & 1) {
                fence_async_smem();
                __syncthreads();
                if (tid == 0) {
                    tma_st3(&mp.f, sb + (f - 1) * 5120, 0, (f - 1) * 20, chunk * 256 + 2 * pair);
                    tma_st3(&mp.f, sb + f * 5120, 0, f * 20, chunk * 256 + 2 * pair);
                    bulk_commit();
                }
            }
        }
    }
    if (tid == 0) { bulk_wait0(); fence_async(); cnt_add(u / 132); }
}

__device__ __forceinline__ void task_p2(int t, uint32_t sb) {
    const int tid = threadIdx.x, w = tid >> 5, lane = tid & 31;
    const int g = t / 200, phi = t % 200, z = (phi % 20) & 3;
    const uint32_t bar = sb + BAR_OFF, sO = sb + 33792;
    char* gx = reinterpret_cast<char*>(g_xf) + ((size_t)phi * 768 + 88 * g) * 128;
    const uint32_t n1 = g == 2 ? 36 * 128 : 44 * 128;
    if (tid == 0) {
        mbar_init(bar, 1); mbar_init(bar + 8, 1); fence_async_smem();
        cnt_wait(g, NW + (g == 2 ? 120 : 132));
        fence_async();
        mbar_expect_tx(bar, 3 * 5632);
#pragma unroll
        for (int c = 0; c < 3; c++) bulk_g2s(sb + c * 11264, gx + c * 32768, 5632, bar);
        mbar_expect_tx(bar + 8, 3 * n1);
#pragma unroll
        for (int c = 0; c < 3; c++) bulk_g2s(sb + c * 11264 + 5632, gx + c * 32768 + 5632, n1, bar + 8);
    }
    __syncthreads();
    const uint4* gw = g_wf + phi * 18 * 128 + w * 32 + ((((lane >> 2) & 1) * 4 + (lane & 3)) * 4 + (lane >> 3));
    uint4 wa[2][6];
#pragma unroll
    for (int s = 0; s < 6; s++) wa[0][s] = __ldcg(gw + s * 128);
#pragma unroll
    for (int s = 0; s < 6; s++) wa[1][s] = __ldcg(gw + (6 + s) * 128);
    float acc[2][44];
    const uint64_t dB0 = mkdesc(sb + ((z >> 1) << 5), 16, 512, 2), dB1 = mkdesc(sb + (((z >> 1) ^ 1) << 5), 16, 512, 2);
    const int i = lane & 7, mi = lane >> 3;
    const uint32_t soff = sO + mi * 512 + (i >> 1) * 128 + (i & 1) * 64 + ((w ^ (i >> 1) ^ z) << 4);
    auto issue = [&](int st, float (&d)[44]) {
        const int h = st & 1;
        const uint4 (&a)[6] = wa[(st >> 1) & 1];
        if (st < 2) mbar_wait(bar + 8 * h, 0);
        wg_fence();
        wgmma_rs_n88_z(d, a[0].x, a[0].y, a[0].z, a[0].w, dB0 + (h * 5632 >> 4));
        wgmma_rs_n88_a(d, a[1].x, a[1].y, a[1].z, a[1].w, dB1 + (h * 5632 >> 4));
#pragma unroll
        for (int c = 1; c < 3; c++) {
            wgmma_rs_n88_a(d, a[2 * c].x, a[2 * c].y, a[2 * c].z, a[2 * c].w, dB0 + ((c * 11264 + h * 5632) >> 4));
            wgmma_rs_n88_a(d, a[2 * c + 1].x, a[2 * c + 1].y, a[2 * c + 1].z, a[2 * c + 1].w, dB1 + ((c * 11264 + h * 5632) >> 4));
        }
        wg_commit();
    };
    issue(0, acc[0]);
#pragma unroll
    for (int st = 0; st < 6; st++) {
        if (st < 5) { issue(st + 1, acc[(st + 1) & 1]); wg_wait<1>(); } else wg_wait<0>();
        float (&d)[44] = acc[st & 1];
        reg_fence(d);
        if (st == 1) {
#pragma unroll
            for (int s = 0; s < 6; s++) wa[0][s] = __ldcg(gw + (12 + s) * 128);
        }
        uint32_t p[11];
#pragma unroll
        for (int j = 0; j < 11; j++) p[j] = pack2(d[4 * j] - d[4 * j + 3], d[4 * j + 2] + d[4 * j + 1]);
        const uint32_t a = soff + st * 5632;
        stm4(a, p[0], p[1], p[2], p[3]);
        stm4(a + 2048, p[4], p[5], p[6], p[7]);
        stm2(a + 4096, p[8], p[9]);
        stm1(a + 5120, p[10]);
        fence_async_smem();
        __syncthreads();
        if (tid == 0) {
            bulk_s2g(gx + (st >> 1) * 32768 + (st & 1) * 5632, sO + st * 5632, (st & 1) ? n1 : 5632);
            bulk_commit();
        }
    }
    if (tid == 0) { bulk_wait0(); fence_async(); cnt_add(3 + g); }
}

__device__ __forceinline__ void task_p3(int u, uint32_t sb, const Maps& mp) {
    const int tid = threadIdx.x, w = tid >> 5, lane = tid & 31;
    const int pair = u / 3, chunk = u % 3, tp = pair >> 4, tx = pair & 15;
    const uint32_t bar = sb + BAR_OFF, sB3 = sb + 51200, sB4 = sb + 54272;
    if (tid == 0) {
#pragma unroll
        for (int i = 0; i < 5; i++) mbar_init(bar + 8 * i, 1);
        fence_async_smem();
        mbar_expect_tx(bar, 10240 + 12032);
        bulk_g2s(sB3, TAB_P3, 12032, bar);
        cnt_wait(3 + u / 132, 200);
        fence_async();
#pragma unroll
        for (int j = 0; j < 5; j++) {
            if (j) mbar_expect_tx(bar + 8 * j, 10240);
            tma_ld3(sb + j * 10240, &mp.f, 0, j * 40, chunk * 256 + 2 * pair, bar + 8 * j);
            tma_ld3(sb + j * 10240 + 5120, &mp.f, 0, j * 40 + 20, chunk * 256 + 2 * pair, bar + 8 * j);
        }
    }
    __syncthreads();
    uint32_t fr[10][4][2];
    {
        float acc[2][2][16];
        const uint64_t dA = mkdesc(sb, 2560, 512, 2), dB = mkdesc(sB3, 128, 256, 0);
        auto issue = [&](int j, float (&d)[2][16]) {
            mbar_wait(bar + 8 * j, 0);
            wg_fence();
#pragma unroll
            for (int e = 0; e < 2; e++) wgmma_ss_n32_z(d[e], dA + ((2 * j + e) * 5120 >> 4), dB);
#pragma unroll
            for (int e = 0; e < 2; e++) wgmma_ss_n32_a(d[e], dA + (((2 * j + e) * 5120 + 1024) >> 4), dB + (1024 >> 4));
#pragma unroll
            for (int e = 0; e < 2; e++) wgmma_ss_n32_a(d[e], dA + (((2 * j + e) * 5120 + 1536) >> 4), dB + (2048 >> 4));
            wg_commit();
        };
        issue(0, acc[0]);
#pragma unroll
        for (int j = 0; j < 5; j++) {
            if (j < 4) { issue(j + 1, acc[(j + 1) & 1]); wg_wait<1>(); } else wg_wait<0>();
#pragma unroll
            for (int e = 0; e < 2; e++) {
                float (&d)[16] = acc[j & 1][e];
                reg_fence(d);
#pragma unroll
                for (int g = 0; g < 4; g++) {
                    fr[2 * j + e][g][0] = pack2(d[4 * g], d[4 * g + 1]);
                    fr[2 * j + e][g][1] = pack2(d[4 * g + 2], d[4 * g + 3]);
                }
            }
        }
    }
    __syncthreads();
    {
        float acc[2][28];
        const uint64_t dB = mkdesc(sB4, 128, 256, 0);
        const int i = lane & 7, mi = lane >> 3, th = w >> 1, tz = (2 * pair + th) & 3;
        const int oct = (2 * (w & 1) + (mi & 1)) ^ tz;
        const uint32_t soff = sb + th * 3584 + (mi >> 1) * 512 + i * 64 + ((oct ^ (i >> 1)) << 4);
        auto issue = [&](int g, float (&d)[28]) {
            wg_fence();
            wgmma_rs_n56_z(d, fr[0][g][0], fr[0][g][1], fr[1][g][0], fr[1][g][1], dB);
#pragma unroll
            for (int s = 1; s < 5; s++) wgmma_rs_n56_a(d, fr[2 * s][g][0], fr[2 * s][g][1], fr[2 * s + 1][g][0], fr[2 * s + 1][g][1], dB + (s * 1792 >> 4));
            wg_commit();
        };
        issue(1, acc[1]);
#pragma unroll
        for (int gg = 1; gg < 5; gg++) {
            const int g = gg & 3;
            if (gg < 4) { issue((gg + 1) & 3, acc[(gg + 1) & 1]); wg_wait<1>(); } else wg_wait<0>();
            float (&d)[28] = acc[gg & 1];
            reg_fence(d);
            if (g) {
                const uint32_t a = soff + g * 7168;
#pragma unroll
                for (int j = 0; j < 3; j++)
                    stm4(a + j * 1024, pack2(d[8 * j], d[8 * j + 1]), pack2(d[8 * j + 2], d[8 * j + 3]), pack2(d[8 * j + 4], d[8 * j + 5]), pack2(d[8 * j + 6], d[8 * j + 7]));
                stm2(a + 3072, pack2(d[24], d[25]), pack2(d[26], d[27]));
            } else {
#pragma unroll
                for (int j = 0; j < 4; j++) {
                    const int row = th * 14 + 4 * j + 2 * (mi >> 1) + (i >> 2);
                    const uint32_t a = (i & 2) ? sb + row * 128 + (i & 1) * 64 + ((oct ^ (row & 3)) << 4) : sb + 4096 + lane * 16;
                    if (j < 3) stm4(a, pack2(d[8 * j], d[8 * j + 1]), pack2(d[8 * j + 2], d[8 * j + 3]), pack2(d[8 * j + 4], d[8 * j + 5]), pack2(d[8 * j + 6], d[8 * j + 7]));
                    else stm2(a, pack2(d[24], d[25]), pack2(d[26], d[27]));
                }
            }
            fence_async_smem();
            __syncthreads();
            if (tid == 0) {
                if (g) tma_st3(&mp.y4, sb + g * 7168, 32 * chunk, 14 * tx - 4 + 4 * g, 28 * tp);
                else tma_st3(&mp.y2, sb, 32 * chunk, tx == 0 ? 222 : 14 * tx - 2, 28 * tp);
                bulk_commit();
            }
        }
    }
    if (tid == 0) {
        unsigned old = atomicAdd(&g_cnt[6 * 32], 1u);
        if (old == NP3 - 1) {
#pragma unroll
            for (int k = 0; k < 7; k++) g_cnt[k * 32] = 0;
        }
        bulk_wait0();
    }
}

__global__ void __launch_bounds__(128, 3) fftconv_kernel(const __grid_constant__ Maps mp, int base) {
    extern __shared__ __align__(1024) uint8_t smem[];
    const uint32_t sb = smem_u32(smem);
    int b = blockIdx.x + base;
    if (b < NW) task_w(b, sb, mp);
    else if (b < NW + NP1) task_p1(b - NW, sb, mp);
    else if (b < NW + NP1 + NP2) task_p2(b - NW - NP1, sb);
    else task_p3(b - NW - NP1 - NP2, sb, mp);
}

typedef CUresult (*EncodeFn)(CUtensorMap*, CUtensorMapDataType, cuuint32_t, void*, const cuuint64_t*, const cuuint64_t*, const cuuint32_t*, const cuuint32_t*,
                             CUtensorMapInterleave, CUtensorMapSwizzle, CUtensorMapL2promotion, CUtensorMapFloatOOBfill);

static void encode3(EncodeFn fn, CUtensorMap* m, void* ptr, uint64_t d0, uint64_t d1, uint64_t d2, uint64_t s1, uint64_t s2,
                    uint32_t b0, uint32_t b1, uint32_t b2, CUtensorMapSwizzle sw) {
    cuuint64_t dims[3] = {d0, d1, d2}, strides[2] = {s1, s2};
    cuuint32_t box[3] = {b0, b1, b2}, es[3] = {1, 1, 1};
    fn(m, CU_TENSOR_MAP_DATA_TYPE_BFLOAT16, 3, ptr, dims, strides, box, es, CU_TENSOR_MAP_INTERLEAVE_NONE, sw,
       CU_TENSOR_MAP_L2_PROMOTION_NONE, CU_TENSOR_MAP_FLOAT_OOB_FILL_NONE);
}

extern "C" void kernel_launch(void* const* d_in, const int* in_sizes, int n_in, void* d_out, int out_size) {
    (void)in_sizes; (void)n_in; (void)out_size;
    void* fnp = nullptr; cudaDriverEntryPointQueryResult qr;
    cudaGetDriverEntryPoint("cuTensorMapEncodeTiled", &fnp, cudaEnableDefault, &qr);
    EncodeFn fn = (EncodeFn)fnp;
    void* xf = nullptr; cudaGetSymbolAddress(&xf, g_xf);
    Maps mp;
    encode3(fn, &mp.x6, d_in[0], 96, 224, 224, 192, 224 * 192, 32, 4, 6, CU_TENSOR_MAP_SWIZZLE_64B);
    encode3(fn, &mp.x28, d_in[0], 96, 224, 224, 192, 224 * 192, 32, 4, 28, CU_TENSOR_MAP_SWIZZLE_64B);
    encode3(fn, &mp.w, d_in[1], 96, 49, 96, 18432, 192, 32, 56, 16, CU_TENSOR_MAP_SWIZZLE_64B);
    encode3(fn, &mp.f, xf, 64, 200, 768, 98304, 128, 64, 20, 2, CU_TENSOR_MAP_SWIZZLE_NONE);
    encode3(fn, &mp.y4, d_out, 96, 224, 224, 192, 224 * 192, 32, 4, 28, CU_TENSOR_MAP_SWIZZLE_64B);
    encode3(fn, &mp.y2, d_out, 96, 224, 224, 192, 224 * 192, 32, 2, 28, CU_TENSOR_MAP_SWIZZLE_64B);
    cudaFuncSetAttribute(fftconv_kernel, cudaFuncAttributeMaxDynamicSharedMemorySize, SMEM_BYTES);
    fftconv_kernel<<<NW + NP1 + NP2 + NP3, 128, SMEM_BYTES>>>(mp, 0);
}
```

```cpp
#include <cuda_runtime.h>
#include <cuda_bf16.h>
#include <cuda.h>
#include <stdint.h>

__device__ __align__(128) const uint32_t TAB_P1[4480] = {
0x3e75,0,0x3e72,0,0x8000,0,0xbd19,0,0x3e750000,0,0x3e720000,0,0x80000000,0,0xbd190000,0,
0,0x3e75,0,0x3e72,0,0x8000,0,0xbd19,0,0x3e750000,0,0x3e720000,0,0x80000000,0,0xbd190000,
0x3e69,0,0x3e5a,0,0xbd97,0,0xbdde,0,0x3e690000,0,0x3e5a0000,0,0xbd970000,0,0xbdde0000,0,
0,0x3e69,0,0x3e5a,0,0xbd97,0,0xbdde,0,0x3e690000,0,0x3e5a0000,0,0xbd970000,0,0xbdde0000,
0x3e75,0,0x3e5a,0,0x8000,0,0xbdde,0,0x3e750000,0,0x3e5a0000,0,0x80000000,0,0xbdde0000,0,
0,0x3e75,0,0x3e5a,0,0x8000,0,0xbdde,0,0x3e750000,0,0x3e5a0000,0,0x80000000,0,0xbdde0000,
0x3e10,0,0x3d19,0,0xbe46,0,0xbe72,0,0x3e100000,0,0x3d190000,0,0xbe460000,0,0xbe720000,0,
0,0x3e10,0,0x3d19,0,0xbe46,0,0xbe72,0,0x3e100000,0,0x3d190000,0,0xbe460000,0,0xbe720000,
0x3e75,0,0x3e2d,0,0x8000,0,0xbe2d,0,0x3e750000,0,0x3e2d0000,0,0x80000000,0,0xbe2d0000,0,
0,0x3e75,0,0x3e2d,0,0x8000,0,0xbe2d,0,0x3e750000,0,0x3e2d0000,0,0x80000000,0,0xbe2d0000,
0,0,0xbe2d,0,0xbe75,0,0xbe2d,0,0,0,0xbe2d0000,0,0xbe750000,0,0xbe2d0000,0,
0,0,0,0xbe2d,0,0xbe75,0,0xbe2d,0,0,0,0xbe2d0000,0,0xbe750000,0,0xbe2d0000,
0x3e75,0,0x3dde,0,0x8000,0,0xbe5a,0,0x3e750000,0,0x3dde0000,0,0x80000000,0,0xbe5a0000,0,
0,0x3e75,0,0x3dde,0,0x8000,0,0xbe5a,0,0x3e750000,0,0x3dde0000,0,0x80000000,0,0xbe5a0000,
0xbe10,0,0xbe72,0,0xbe46,0,0x3d19,0,0xbe100000,0,0xbe720000,0,0xbe460000,0,0x3d190000,0,
0,0xbe10,0,0xbe72,0,0xbe46,0,0x3d19,0,0xbe100000,0,0xbe720000,0,0xbe460000,0,0x3d190000,
0x3e75,0,0x3d19,0,0x8000,0,0xbe72,0,0x3e750000,0,0x3d190000,0,0x80000000,0,0xbe720000,0,
0,0x3e75,0,0x3d19,0,0x8000,0,0xbe72,0,0x3e750000,0,0x3d190000,0,0x80000000,0,0xbe720000,
0xbe69,0,0xbdde,0,0xbd97,0,0x3e5a,0,0xbe690000,0,0xbdde0000,0,0xbd970000,0,0x3e5a0000,0,
0,0xbe69,0,0xbdde,0,0xbd97,0,0x3e5a,0,0xbe690000,0,0xbdde0000,0,0xbd970000,0,0x3e5a0000,
0x3e75,0,0xbd19,0,0x8000,0,0xbe72,0,0x3e750000,0,0xbd190000,0,0x80000000,0,0xbe720000,0,
0,0x3e75,0,0xbd19,0,0x8000,0,0xbe72,0,0x3e750000,0,0xbd190000,0,0x80000000,0,0xbe720000,
0xbe69,0,0x3dde,0,0x3d97,0,0x3e5a,0,0xbe690000,0,0x3dde0000,0,0x3d970000,0,0x3e5a0000,0,
0,0xbe69,0,0x3dde,0,0x3d97,0,0x3e5a,0,0xbe690000,0,0x3dde0000,0,0x3d970000,0,0x3e5a0000,
0x3e75,0,0xbdde,0,0x8000,0,0xbe5a,0,0x3e750000,0,0xbdde0000,0,0x80000000,0,0xbe5a0000,0,
0,0x3e75,0,0xbdde,0,0x8000,0,0xbe5a,0,0x3e750000,0,0xbdde0000,0,0x80000000,0,0xbe5a0000,
0xbe10,0,0x3e72,0,0x3e46,0,0x3d19,0,0xbe100000,0,0x3e720000,0,0x3e460000,0,0x3d190000,0,
0,0xbe10,0,0x3e72,0,0x3e46,0,0x3d19,0,0xbe100000,0,0x3e720000,0,0x3e460000,0,0x3d190000,
0x3e75,0,0xbe2d,0,0x8000,0,0xbe2d,0,0x3e750000,0,0xbe2d0000,0,0x80000000,0,0xbe2d0000,0,
0,0x3e75,0,0xbe2d,0,0x8000,0,0xbe2d,0,0x3e750000,0,0xbe2d0000,0,0x80000000,0,0xbe2d0000,
0,0,0x3e2d,0,0x3e75,0,0xbe2d,0,0,0,0x3e2d0000,0,0x3e750000,0,0xbe2d0000,0,
0,0,0,0x3e2d,0,0x3e75,0,0xbe2d,0,0,0,0x3e2d0000,0,0x3e750000,0,0xbe2d0000,
0x3e75,0,0xbe5a,0,0x8000,0,0xbdde,0,0x3e750000,0,0xbe5a0000,0,0x80000000,0,0xbdde0000,0,
0,0x3e75,0,0xbe5a,0,0x8000,0,0xbdde,0,0x3e750000,0,0xbe5a0000,0,0x80000000,0,0xbdde0000,
0x3e10,0,0xbd19,0,0x3e46,0,0xbe72,0,0x3e100000,0,0xbd190000,0,0x3e460000,0,0xbe720000,0,
0,0x3e10,0,0xbd19,0,0x3e46,0,0xbe72,0,0x3e100000,0,0xbd190000,0,0x3e460000,0,0xbe720000,
0x3e75,0,0xbe72,0,0x8000,0,0xbd19,0,0x3e750000,0,0xbe720000,0,0x80000000,0,0xbd190000,0,
0,0x3e75,0,0xbe72,0,0x8000,0,0xbd19,0,0x3e750000,0,0xbe720000,0,0x80000000,0,0xbd190000,
0x3e69,0,0xbe5a,0,0x3d97,0,0xbdde,0,0x3e690000,0,0xbe5a0000,0,0x3d970000,0,0xbdde0000,0,
0,0x3e69,0,0xbe5a,0,0x3d97,0,0xbdde,0,0x3e690000,0,0xbe5a0000,0,0x3d970000,0,0xbdde0000,
0x3e46,0,0x3e2d,0,0xbe10,0,0xbe2d,0,0x3e460000,0,0x3e2d0000,0,0xbe100000,0,0xbe2d0000,0,
0,0x3e46,0,0x3e2d,0,0xbe10,0,0xbe2d,0,0x3e460000,0,0x3e2d0000,0,0xbe100000,0,0xbe2d0000,
0x3e10,0,0x3dde,0,0xbe46,0,0xbe5a,0,0x3e100000,0,0x3dde0000,0,0xbe460000,0,0xbe5a0000,0,
0,0x3e10,0,0x3dde,0,0xbe46,0,0xbe5a,0,0x3e100000,0,0x3dde0000,0,0xbe460000,0,0xbe5a0000,
0xbd97,0,0xbe2d,0,0xbe69,0,0xbe2d,0,0xbd970000,0,0xbe2d0000,0,0xbe690000,0,0xbe2d0000,0,
0,0xbd97,0,0xbe2d,0,0xbe69,0,0xbe2d,0,0xbd970000,0,0xbe2d0000,0,0xbe690000,0,0xbe2d0000,
0xbe69,0,0xbe72,0,0xbd97,0,0x3d19,0,0xbe690000,0,0xbe720000,0,0xbd970000,0,0x3d190000,0,
0,0xbe69,0,0xbe72,0,0xbd97,0,0x3d19,0,0xbe690000,0,0xbe720000,0,0xbd970000,0,0x3d190000,
0xbe75,0,0xbe2d,0,0x8000,0,0x3e2d,0,0xbe750000,0,0xbe2d0000,0,0x80000000,0,0x3e2d0000,0,
0,0xbe75,0,0xbe2d,0,0x8000,0,0x3e2d,0,0xbe750000,0,0xbe2d0000,0,0x80000000,0,0x3e2d0000,
0,0,0x3e2d,0,0x3e75,0,0x3e2d,0,0,0,0x3e2d0000,0,0x3e750000,0,0x3e2d0000,0,
0,0,0,0x3e2d,0,0x3e75,0,0x3e2d,0,0,0,0x3e2d0000,0,0x3e750000,0,0x3e2d0000,
0xbd97,0,0x3e2d,0,0x3e69,0,0x3e2d,0,0xbd970000,0,0x3e2d0000,0,0x3e690000,0,0x3e2d0000,0,
0,0xbd97,0,0x3e2d,0,0x3e69,0,0x3e2d,0,0xbd970000,0,0x3e2d0000,0,0x3e690000,0,0x3e2d0000,
0x3e69,0,0x3d19,0,0xbd97,0,0xbe72,0,0x3e690000,0,0x3d190000,0,0xbd970000,0,0xbe720000,0,
0,0x3e69,0,0x3d19,0,0xbd97,0,0xbe72,0,0x3e690000,0,0x3d190000,0,0xbd970000,0,0xbe720000,
0x3e46,0,0x3e2d,0,0x3e10,0,0xbe2d,0,0x3e460000,0,0x3e2d0000,0,0x3e100000,0,0xbe2d0000,0,
0,0x3e46,0,0x3e2d,0,0x3e10,0,0xbe2d,0,0x3e460000,0,0x3e2d0000,0,0x3e100000,0,0xbe2d0000,
0xbe10,0,0xbe5a,0,0xbe46,0,0x3dde,0,0xbe100000,0,0xbe5a0000,0,0xbe460000,0,0x3dde0000,0,
0,0xbe10,0,0xbe5a,0,0xbe46,0,0x3dde,0,0xbe100000,0,0xbe5a0000,0,0xbe460000,0,0x3dde0000,
0x3e46,0,0xbe2d,0,0xbe10,0,0xbe2d,0,0x3e460000,0,0xbe2d0000,0,0xbe100000,0,0xbe2d0000,0,
0,0x3e46,0,0xbe2d,0,0xbe10,0,0xbe2d,0,0x3e460000,0,0xbe2d0000,0,0xbe100000,0,0xbe2d0000,
0xbe10,0,0x3e5a,0,0x3e46,0,0x3dde,0,0xbe100000,0,0x3e5a0000,0,0x3e460000,0,0x3dde0000,0,
0,0xbe10,0,0x3e5a,0,0x3e46,0,0x3dde,0,0xbe100000,0,0x3e5a0000,0,0x3e460000,0,0x3dde0000,
0xbd97,0,0xbe2d,0,0xbe69,0,0x3e2d,0,0xbd970000,0,0xbe2d0000,0,0xbe690000,0,0x3e2d0000,0,
0,0xbd97,0,0xbe2d,0,0xbe69,0,0x3e2d,0,0xbd970000,0,0xbe2d0000,0,0xbe690000,0,0x3e2d0000,
0x3e69,0,0xbd19,0,0x3d97,0,0xbe72,0,0x3e690000,0,0xbd190000,0,0x3d970000,0,0xbe720000,0,
0,0x3e69,0,0xbd19,0,0x3d97,0,0xbe72,0,0x3e690000,0,0xbd190000,0,0x3d970000,0,0xbe720000,
0xbe75,0,0x3e2d,0,0x8000,0,0x3e2d,0,0xbe750000,0,0x3e2d0000,0,0x80000000,0,0x3e2d0000,0,
0,0xbe75,0,0x3e2d,0,0x8000,0,0x3e2d,0,0xbe750000,0,0x3e2d0000,0,0x80000000,0,0x3e2d0000,
0,0,0xbe2d,0,0xbe75,0,0x3e2d,0,0,0,0xbe2d0000,0,0xbe750000,0,0x3e2d0000,0,
0,0,0,0xbe2d,0,0xbe75,0,0x3e2d,0,0,0,0xbe2d0000,0,0xbe750000,0,0x3e2d0000,
0xbd97,0,0x3e2d,0,0x3e69,0,0xbe2d,0,0xbd970000,0,0x3e2d0000,0,0x3e690000,0,0xbe2d0000,0,
0,0xbd97,0,0x3e2d,0,0x3e69,0,0xbe2d,0,0xbd970000,0,0x3e2d0000,0,0x3e690000,0,0xbe2d0000,
0xbe69,0,0x3e72,0,0x3d97,0,0x3d19,0,0xbe690000,0,0x3e720000,0,0x3d970000,0,0x3d190000,0,
0,0xbe69,0,0x3e72,0,0x3d97,0,0x3d19,0,0xbe690000,0,0x3e720000,0,0x3d970000,0,0x3d190000,
0x3e46,0,0xbe2d,0,0x3e10,0,0xbe2d,0,0x3e460000,0,0xbe2d0000,0,0x3e100000,0,0xbe2d0000,0,
0,0x3e46,0,0xbe2d,0,0x3e10,0,0xbe2d,0,0x3e460000,0,0xbe2d0000,0,0x3e100000,0,0xbe2d0000,
0x3e10,0,0xbdde,0,0x3e46,0,0xbe5a,0,0x3e100000,0,0xbdde0000,0,0x3e460000,0,0xbe5a0000,0,
0,0x3e10,0,0xbdde,0,0x3e46,0,0xbe5a,0,0x3e100000,0,0xbdde0000,0,0x3e460000,0,0xbe5a0000,
0x3d97,0,0x3d19,0,0xbe69,0,0xbe72,0,0x3d970000,0,0x3d190000,0,0xbe690000,0,0xbe720000,0,
0,0x3d97,0,0x3d19,0,0xbe69,0,0xbe72,0,0x3d970000,0,0x3d190000,0,0xbe690000,0,0xbe720000,
0,0,0xbd19,0,0xbe75,0,0xbe72,0,0,0,0xbd190000,0,0xbe750000,0,0xbe720000,0,
0,0,0,0xbd19,0,0xbe75,0,0xbe72,0,0,0,0xbd190000,0,0xbe750000,0,0xbe720000,
0xbe46,0,0xbdde,0,0x3e10,0,0x3e5a,0,0xbe460000,0,0xbdde0000,0,0x3e100000,0,0x3e5a0000,0,
0,0xbe46,0,0xbdde,0,0x3e10,0,0x3e5a,0,0xbe460000,0,0xbdde0000,0,0x3e100000,0,0x3e5a0000,
0,0,0x3dde,0,0x3e75,0,0x3e5a,0,0,0,0x3dde0000,0,0x3e750000,0,0x3e5a0000,0,
0,0,0,0x3dde,0,0x3e75,0,0x3e5a,0,0,0,0x3dde0000,0,0x3e750000,0,0x3e5a0000,
0x3e75,0,0x3e2d,0,0x8000,0,0xbe2d,0,0x3e750000,0,0x3e2d0000,0,0x80000000,0,0xbe2d0000,0,
0,0x3e75,0,0x3e2d,0,0x8000,0,0xbe2d,0,0x3e750000,0,0x3e2d0000,0,0x80000000,0,0xbe2d0000,
0,0,0xbe2d,0,0xbe75,0,0xbe2d,0,0,0,0xbe2d0000,0,0xbe750000,0,0xbe2d0000,0,
0,0,0,0xbe2d,0,0xbe75,0,0xbe2d,0,0,0,0xbe2d0000,0,0xbe750000,0,0xbe2d0000,
0xbe46,0,0xbe5a,0,0xbe10,0,0x3dde,0,0xbe460000,0,0xbe5a0000,0,0xbe100000,0,0x3dde0000,0,
0,0xbe46,0,0xbe5a,0,0xbe10,0,0x3dde,0,0xbe460000,0,0xbe5a0000,0,0xbe100000,0,0x3dde0000,
0,0,0x3e5a,0,0x3e75,0,0x3dde,0,0,0,0x3e5a0000,0,0x3e750000,0,0x3dde0000,0,
0,0,0,0x3e5a,0,0x3e75,0,0x3dde,0,0,0,0x3e5a0000,0,0x3e750000,0,0x3dde0000,
0x3d97,0,0x3e72,0,0x3e69,0,0xbd19,0,0x3d970000,0,0x3e720000,0,0x3e690000,0,0xbd190000,0,
0,0x3d97,0,0x3e72,0,0x3e69,0,0xbd19,0,0x3d970000,0,0x3e720000,0,0x3e690000,0,0xbd190000,
0,0,0xbe72,0,0xbe75,0,0xbd19,0,0,0,0xbe720000,0,0xbe750000,0,0xbd190000,0,
0,0,0,0xbe72,0,0xbe75,0,0xbd19,0,0,0,0xbe720000,0,0xbe750000,0,0xbd190000,
0x3d97,0,0xbe72,0,0xbe69,0,0xbd19,0,0x3d970000,0,0xbe720000,0,0xbe690000,0,0xbd190000,0,
0,0x3d97,0,0xbe72,0,0xbe69,0,0xbd19,0,0x3d970000,0,0xbe720000,0,0xbe690000,0,0xbd190000,
0,0,0x3e72,0,0x3e75,0,0xbd19,0,0,0,0x3e720000,0,0x3e750000,0,0xbd190000,0,
0,0,0,0x3e72,0,0x3e75,0,0xbd19,0,0,0,0x3e720000,0,0x3e750000,0,0xbd190000,
0xbe46,0,0x3e5a,0,0x3e10,0,0x3dde,0,0xbe460000,0,0x3e5a0000,0,0x3e100000,0,0x3dde0000,0,
0,0xbe46,0,0x3e5a,0,0x3e10,0,0x3dde,0,0xbe460000,0,0x3e5a0000,0,0x3e100000,0,0x3dde0000,
0,0,0xbe5a,0,0xbe75,0,0x3dde,0,0,0,0xbe5a0000,0,0xbe750000,0,0x3dde0000,0,
0,0,0,0xbe5a,0,0xbe75,0,0x3dde,0,0,0,0xbe5a0000,0,0xbe750000,0,0x3dde0000,
0x3e75,0,0xbe2d,0,0x8000,0,0xbe2d,0,0x3e750000,0,0xbe2d0000,0,0x80000000,0,0xbe2d0000,0,
0,0x3e75,0,0xbe2d,0,0x8000,0,0xbe2d,0,0x3e750000,0,0xbe2d0000,0,0x80000000,0,0xbe2d0000,
0,0,0x3e2d,0,0x3e75,0,0xbe2d,0,0,0,0x3e2d0000,0,0x3e750000,0,0xbe2d0000,0,
0,0,0,0x3e2d,0,0x3e75,0,0xbe2d,0,0,0,0x3e2d0000,0,0x3e750000,0,0xbe2d0000,
0xbe46,0,0x3dde,0,0xbe10,0,0x3e5a,0,0xbe460000,0,0x3dde0000,0,0xbe100000,0,0x3e5a0000,0,
0,0xbe46,0,0x3dde,0,0xbe10,0,0x3e5a,0,0xbe460000,0,0x3dde0000,0,0xbe100000,0,0x3e5a0000,
0,0,0xbdde,0,0xbe75,0,0x3e5a,0,0,0,0xbdde0000,0,0xbe750000,0,0x3e5a0000,0,
0,0,0,0xbdde,0,0xbe75,0,0x3e5a,0,0,0,0xbdde0000,0,0xbe750000,0,0x3e5a0000,
0x3d97,0,0xbd19,0,0x3e69,0,0xbe72,0,0x3d970000,0,0xbd190000,0,0x3e690000,0,0xbe720000,0,
0,0x3d97,0,0xbd19,0,0x3e69,0,0xbe72,0,0x3d970000,0,0xbd190000,0,0x3e690000,0,0xbe720000,
0,0,0x3d19,0,0x3e75,0,0xbe72,0,0,0,0x3d190000,0,0x3e750000,0,0xbe720000,0,
0,0,0,0x3d19,0,0x3e75,0,0xbe72,0,0,0,0x3d190000,0,0x3e750000,0,0xbe720000,
0xbd97,0,0xbdde,0,0xbe69,0,0xbe5a,0,0xbd970000,0,0xbdde0000,0,0xbe690000,0,0xbe5a0000,0,
0,0xbd97,0,0xbdde,0,0xbe69,0,0xbe5a,0,0xbd970000,0,0xbdde0000,0,0xbe690000,0,0xbe5a0000,
0xbe10,0,0xbe2d,0,0xbe46,0,0xbe2d,0,0xbe100000,0,0xbe2d0000,0,0xbe460000,0,0xbe2d0000,0,
0,0xbe10,0,0xbe2d,0,0xbe46,0,0xbe2d,0,0xbe100000,0,0xbe2d0000,0,0xbe460000,0,0xbe2d0000,
0x3e46,0,0x3e72,0,0x3e10,0,0x3d19,0,0x3e460000,0,0x3e720000,0,0x3e100000,0,0x3d190000,0,
0,0x3e46,0,0x3e72,0,0x3e10,0,0x3d19,0,0x3e460000,0,0x3e720000,0,0x3e100000,0,0x3d190000,
0x3e69,0,0x3e2d,0,0xbd97,0,0xbe2d,0,0x3e690000,0,0x3e2d0000,0,0xbd970000,0,0xbe2d0000,0,
0,0x3e69,0,0x3e2d,0,0xbd97,0,0xbe2d,0,0x3e690000,0,0x3e2d0000,0,0xbd970000,0,0xbe2d0000,
0xbe75,0,0xbe2d,0,0x8000,0,0x3e2d,0,0xbe750000,0,0xbe2d0000,0,0x80000000,0,0x3e2d0000,0,
0,0xbe75,0,0xbe2d,0,0x8000,0,0x3e2d,0,0xbe750000,0,0xbe2d0000,0,0x80000000,0,0x3e2d0000,
0,0,0x3e2d,0,0x3e75,0,0x3e2d,0,0,0,0x3e2d0000,0,0x3e750000,0,0x3e2d0000,0,
0,0,0,0x3e2d,0,0x3e75,0,0x3e2d,0,0,0,0x3e2d0000,0,0x3e750000,0,0x3e2d0000,
0x3e46,0,0xbd19,0,0xbe10,0,0xbe72,0,0x3e460000,0,0xbd190000,0,0xbe100000,0,0xbe720000,0,
0,0x3e46,0,0xbd19,0,0xbe10,0,0xbe72,0,0x3e460000,0,0xbd190000,0,0xbe100000,0,0xbe720000,
0xbe69,0,0xbe2d,0,0xbd97,0,0x3e2d,0,0xbe690000,0,0xbe2d0000,0,0xbd970000,0,0x3e2d0000,0,
0,0xbe69,0,0xbe2d,0,0xbd97,0,0x3e2d,0,0xbe690000,0,0xbe2d0000,0,0xbd970000,0,0x3e2d0000,
0xbd97,0,0x3e5a,0,0x3e69,0,0x3dde,0,0xbd970000,0,0x3e5a0000,0,0x3e690000,0,0x3dde0000,0,
0,0xbd97,0,0x3e5a,0,0x3e69,0,0x3dde,0,0xbd970000,0,0x3e5a0000,0,0x3e690000,0,0x3dde0000,
0x3e10,0,0xbe2d,0,0xbe46,0,0xbe2d,0,0x3e100000,0,0xbe2d0000,0,0xbe460000,0,0xbe2d0000,0,
0,0x3e10,0,0xbe2d,0,0xbe46,0,0xbe2d,0,0x3e100000,0,0xbe2d0000,0,0xbe460000,0,0xbe2d0000,
0xbd97,0,0xbe5a,0,0xbe69,0,0x3dde,0,0xbd970000,0,0xbe5a0000,0,0xbe690000,0,0x3dde0000,0,
0,0xbd97,0,0xbe5a,0,0xbe69,0,0x3dde,0,0xbd970000,0,0xbe5a0000,0,0xbe690000,0,0x3dde0000,
0x3e10,0,0x3e2d,0,0x3e46,0,0xbe2d,0,0x3e100000,0,0x3e2d0000,0,0x3e460000,0,0xbe2d0000,0,
0,0x3e10,0,0x3e2d,0,0x3e46,0,0xbe2d,0,0x3e100000,0,0x3e2d0000,0,0x3e460000,0,0xbe2d0000,
0x3e46,0,0x3d19,0,0x3e10,0,0xbe72,0,0x3e460000,0,0x3d190000,0,0x3e100000,0,0xbe720000,0,
0,0x3e46,0,0x3d19,0,0x3e10,0,0xbe72,0,0x3e460000,0,0x3d190000,0,0x3e100000,0,0xbe720000,
0xbe69,0,0x3e2d,0,0x3d97,0,0x3e2d,0,0xbe690000,0,0x3e2d0000,0,0x3d970000,0,0x3e2d0000,0,
0,0xbe69,0,0x3e2d,0,0x3d97,0,0x3e2d,0,0xbe690000,0,0x3e2d0000,0,0x3d970000,0,0x3e2d0000,
0xbe75,0,0x3e2d,0,0x8000,0,0x3e2d,0,0xbe750000,0,0x3e2d0000,0,0x80000000,0,0x3e2d0000,0,
0,0xbe75,0,0x3e2d,0,0x8000,0,0x3e2d,0,0xbe750000,0,0x3e2d0000,0,0x80000000,0,0x3e2d0000,
0,0,0xbe2d,0,0xbe75,0,0x3e2d,0,0,0,0xbe2d0000,0,0xbe750000,0,0x3e2d0000,0,
0,0,0,0xbe2d,0,0xbe75,0,0x3e2d,0,0,0,0xbe2d0000,0,0xbe750000,0,0x3e2d0000,
0x3e46,0,0xbe72,0,0xbe10,0,0x3d19,0,0x3e460000,0,0xbe720000,0,0xbe100000,0,0x3d190000,0,
0,0x3e46,0,0xbe72,0,0xbe10,0,0x3d19,0,0x3e460000,0,0xbe720000,0,0xbe100000,0,0x3d190000,
0x3e69,0,0xbe2d,0,0x3d97,0,0xbe2d,0,0x3e690000,0,0xbe2d0000,0,0x3d970000,0,0xbe2d0000,0,
0,0x3e69,0,0xbe2d,0,0x3d97,0,0xbe2d,0,0x3e690000,0,0xbe2d0000,0,0x3d970000,0,0xbe2d0000,
0xbd97,0,0x3dde,0,0x3e69,0,0xbe5a,0,0xbd970000,0,0x3dde0000,0,0x3e690000,0,0xbe5a0000,0,
0,0xbd97,0,0x3dde,0,0x3e69,0,0xbe5a,0,0xbd970000,0,0x3dde0000,0,0x3e690000,0,0xbe5a0000,
0xbe10,0,0x3e2d,0,0x3e46,0,0xbe2d,0,0xbe100000,0,0x3e2d0000,0,0x3e460000,0,0xbe2d0000,0,
0,0xbe10,0,0x3e2d,0,0x3e46,0,0xbe2d,0,0xbe100000,0,0x3e2d0000,0,0x3e460000,0,0xbe2d0000,
0xbe46,0,0xbe5a,0,0xbe10,0,0xbdde,0,0xbe460000,0,0xbe5a0000,0,0xbe100000,0,0xbdde0000,0,
0,0xbe46,0,0xbe5a,0,0xbe10,0,0xbdde,0,0xbe460000,0,0xbe5a0000,0,0xbe100000,0,0xbdde0000,
0xbe69,0,0xbe72,0,0xbd97,0,0xbd19,0,0xbe690000,0,0xbe720000,0,0xbd970000,0,0xbd190000,0,
0,0xbe69,0,0xbe72,0,0xbd97,0,0xbd19,0,0xbe690000,0,0xbe720000,0,0xbd970000,0,0xbd190000,
0x3d97,0,0xbd19,0,0xbe69,0,0xbe72,0,0x3d970000,0,0xbd190000,0,0xbe690000,0,0xbe720000,0,
0,0x3d97,0,0xbd19,0,0xbe69,0,0xbe72,0,0x3d970000,0,0xbd190000,0,0xbe690000,0,0xbe720000,
0xbe10,0,0xbe5a,0,0xbe46,0,0xbdde,0,0xbe100000,0,0xbe5a0000,0,0xbe460000,0,0xbdde0000,0,
0,0xbe10,0,0xbe5a,0,0xbe46,0,0xbdde,0,0xbe100000,0,0xbe5a0000,0,0xbe460000,0,0xbdde0000,
0x3e75,0,0x3e2d,0,0x8000,0,0xbe2d,0,0x3e750000,0,0x3e2d0000,0,0x80000000,0,0xbe2d0000,0,
0,0x3e75,0,0x3e2d,0,0x8000,0,0xbe2d,0,0x3e750000,0,0x3e2d0000,0,0x80000000,0,0xbe2d0000,
0,0,0xbe2d,0,0xbe75,0,0xbe2d,0,0,0,0xbe2d0000,0,0xbe750000,0,0xbe2d0000,0,
0,0,0,0xbe2d,0,0xbe75,0,0xbe2d,0,0,0,0xbe2d0000,0,0xbe750000,0,0xbe2d0000,
0x3d97,0,0x3e72,0,0x3e69,0,0x3d19,0,0x3d970000,0,0x3e720000,0,0x3e690000,0,0x3d190000,0,
0,0x3d97,0,0x3e72,0,0x3e69,0,0x3d19,0,0x3d970000,0,0x3e720000,0,0x3e690000,0,0x3d190000,
0x3e10,0,0xbdde,0,0xbe46,0,0xbe5a,0,0x3e100000,0,0xbdde0000,0,0xbe460000,0,0xbe5a0000,0,
0,0x3e10,0,0xbdde,0,0xbe46,0,0xbe5a,0,0x3e100000,0,0xbdde0000,0,0xbe460000,0,0xbe5a0000,
0xbe46,0,0x3dde,0,0x3e10,0,0x3e5a,0,0xbe460000,0,0x3dde0000,0,0x3e100000,0,0x3e5a0000,0,
0,0xbe46,0,0x3dde,0,0x3e10,0,0x3e5a,0,0xbe460000,0,0x3dde0000,0,0x3e100000,0,0x3e5a0000,
0x3e69,0,0xbd19,0,0xbd97,0,0xbe72,0,0x3e690000,0,0xbd190000,0,0xbd970000,0,0xbe720000,0,
0,0x3e69,0,0xbd19,0,0xbd97,0,0xbe72,0,0x3e690000,0,0xbd190000,0,0xbd970000,0,0xbe720000,
0xbe46,0,0xbdde,0,0xbe10,0,0x3e5a,0,0xbe460000,0,0xbdde0000,0,0xbe100000,0,0x3e5a0000,0,
0,0xbe46,0,0xbdde,0,0xbe10,0,0x3e5a,0,0xbe460000,0,0xbdde0000,0,0xbe100000,0,0x3e5a0000,
0x3e69,0,0x3d19,0,0x3d97,0,0xbe72,0,0x3e690000,0,0x3d190000,0,0x3d970000,0,0xbe720000,0,
0,0x3e69,0,0x3d19,0,0x3d97,0,0xbe72,0,0x3e690000,0,0x3d190000,0,0x3d970000,0,0xbe720000,
0x3d97,0,0xbe72,0,0xbe69,0,0x3d19,0,0x3d970000,0,0xbe720000,0,0xbe690000,0,0x3d190000,0,
0,0x3d97,0,0xbe72,0,0xbe69,0,0x3d19,0,0x3d970000,0,0xbe720000,0,0xbe690000,0,0x3d190000,
0x3e10,0,0x3dde,0,0x3e46,0,0xbe5a,0,0x3e100000,0,0x3dde0000,0,0x3e460000,0,0xbe5a0000,0,
0,0x3e10,0,0x3dde,0,0x3e46,0,0xbe5a,0,0x3e100000,0,0x3dde0000,0,0x3e460000,0,0xbe5a0000,
0x3e75,0,0xbe2d,0,0x8000,0,0xbe2d,0,0x3e750000,0,0xbe2d0000,0,0x80000000,0,0xbe2d0000,0,
0,0x3e75,0,0xbe2d,0,0x8000,0,0xbe2d,0,0x3e750000,0,0xbe2d0000,0,0x80000000,0,0xbe2d0000,
0,0,0x3e2d,0,0x3e75,0,0xbe2d,0,0,0,0x3e2d0000,0,0x3e750000,0,0xbe2d0000,0,
0,0,0,0x3e2d,0,0x3e75,0,0xbe2d,0,0,0,0x3e2d0000,0,0x3e750000,0,0xbe2d0000,
0x3d97,0,0x3d19,0,0x3e69,0,0xbe72,0,0x3d970000,0,0x3d190000,0,0x3e690000,0,0xbe720000,0,
0,0x3d97,0,0x3d19,0,0x3e69,0,0xbe72,0,0x3d970000,0,0x3d190000,0,0x3e690000,0,0xbe720000,
0xbe10,0,0x3e5a,0,0x3e46,0,0xbdde,0,0xbe100000,0,0x3e5a0000,0,0x3e460000,0,0xbdde0000,0,
0,0xbe10,0,0x3e5a,0,0x3e46,0,0xbdde,0,0xbe100000,0,0x3e5a0000,0,0x3e460000,0,0xbdde0000,
0xbe46,0,0x3e5a,0,0x3e10,0,0xbdde,0,0xbe460000,0,0x3e5a0000,0,0x3e100000,0,0xbdde0000,0,
0,0xbe46,0,0x3e5a,0,0x3e10,0,0xbdde,0,0xbe460000,0,0x3e5a0000,0,0x3e100000,0,0xbdde0000,
0xbe69,0,0x3e72,0,0x3d97,0,0xbd19,0,0xbe690000,0,0x3e720000,0,0x3d970000,0,0xbd190000,0,
0,0xbe69,0,0x3e72,0,0x3d97,0,0xbd19,0,0xbe690000,0,0x3e720000,0,0x3d970000,0,0xbd190000,
0x3eb7,0x3eb7,0x3eb7,0x3eb7,0x3eb78000,0x3eb78000,0x3eb78000,0x3eb78000,0x3eb7,0x3de23eae,0x3e573e94,0x3e943e57,0x3eb78000,0x3eaebde2,0x3e94be57,0x3e57be94,
0x3eb7,0x3e573e94,0x3eae3de2,0x3eaebde2,0x3eb78000,0x3e94be57,0x3de2beae,0xbde2beae,0x3eb7,0x3e943e57,0x3eaebde2,0x3de2beae,0x3eb78000,0x3e57be94,0xbde2beae,0xbeaebde2,
0x3eb7,0x3eb7,0x3eb7,0x3eb7,0x3eb78000,0x3eb78000,0x3eb78000,0x3eb78000,0x3eae3de2,0x3eb70000,0x3eaebde2,0x3e94be57,0x3de2beae,0xbeb7,0xbde2beae,0xbe57be94,
0x3e57be94,0xbeb7,0xbe57be94,0xbeaebde2,0xbe94be57,0xbeb78000,0xbe943e57,0xbde23eae,0xbe57be94,0xbeb70000,0xbe573e94,0x3de23eae,0xbe943e57,0x3eb7,0x3e943e57,0x3eaebde2,
0x3eb7,0x3eae3de2,0x3e57be94,0xbe57be94,0x3eb78000,0x3de2beae,0xbe94be57,0xbe943e57,0x3eb7,0x3eb70000,0xbeb7,0xbeb70000,0x3eb78000,0xbeb7,0xbeb78000,0x3eb7,
0x3eb7,0x3eaebde2,0xbe57be94,0xbe573e94,0x3eb78000,0xbde2beae,0xbe943e57,0x3e943e57,0x3eb7,0x3e94be57,0xbeaebde2,0x3de23eae,0x3eb78000,0xbe57be94,0xbde23eae,0x3eaebde2,
0xbeae3de2,0x3eb7,0x3eae3de2,0x3e57be94,0x3de23eae,0x3eb78000,0x3de2beae,0xbe94be57,0x3eb7,0x3eb70000,0xbeb7,0xbeb70000,0x3eb78000,0xbeb7,0xbeb78000,0x3eb7,
0x3eae3de2,0xbeb7,0xbeae3de2,0x3e573e94,0x3de2beae,0xbeb78000,0x3de23eae,0x3e94be57,0x3e57be94,0xbeb70000,0x3e573e94,0x3de2beae,0xbe94be57,0x3eb7,0x3e94be57,0xbeaebde2,
0x3eb7,0x3e57be94,0xbeae3de2,0x3eae3de2,0x3eb78000,0xbe94be57,0x3de23eae,0x3de2beae,0x3eb7,0x3de2beae,0xbe573e94,0x3e94be57,0x3eb78000,0xbeaebde2,0x3e943e57,0xbe57be94,
0x3eb7,0xbeb7,0x3eb7,0xbeb7,0x3eb78000,0xbeb78000,0x3eb78000,0xbeb78000,0x3eb7,0xbde2beae,0x3e573e94,0xbe94be57,0x3eb78000,0xbeae3de2,0x3e94be57,0xbe573e94,
0xbe57be94,0x3eb7,0x3e57be94,0xbeae3de2,0xbe943e57,0x3eb78000,0xbe94be57,0x3de23eae,0xbeae3de2,0x3eb70000,0xbeaebde2,0x3e943e57,0x3de23eae,0xbeb7,0xbde23eae,0x3e57be94,
0x3eb7,0xbeb7,0x3eb7,0xbeb7,0x3eb78000,0xbeb78000,0x3eb78000,0xbeb78000,0x3eae3de2,0xbeb70000,0x3eaebde2,0xbe943e57,0x3de2beae,0x3eb7,0xbde2beae,0x3e573e94,
0x3eb7,0xbe57be94,0x3eae3de2,0xbeae3de2,0x3eb78000,0xbe943e57,0x3de2beae,0x3de23eae,0x3eb7,0xbe94be57,0x3eaebde2,0xbde23eae,0x3eb78000,0xbe573e94,0xbde2beae,0x3eae3de2,
0x3eb7,0xbeaebde2,0x3e57be94,0x3e573e94,0x3eb78000,0xbde23eae,0xbe94be57,0x3e94be57,0x3eb7,0xbeb70000,0xbeb7,0x3eb70000,0x3eb78000,0x3eb7,0xbeb78000,0xbeb7,
0x3e57be94,0x3eb7,0xbe57be94,0x3eae3de2,0xbe94be57,0x3eb78000,0xbe943e57,0x3de2beae,0xbe57be94,0x3eb70000,0xbe573e94,0xbde2beae,0xbe943e57,0xbeb7,0x3e943e57,0xbeae3de2,
0xbeae3de2,0xbeb7,0x3eae3de2,0xbe573e94,0x3de23eae,0xbeb78000,0x3de2beae,0x3e943e57,0x3eb7,0xbeb70000,0xbeb7,0x3eb70000,0x3eb78000,0x3eb7,0xbeb78000,0xbeb7,
0x3eb7,0xbeae3de2,0xbe57be94,0x3e57be94,0x3eb78000,0x3de23eae,0xbe943e57,0xbe94be57,0x3eb7,0xbe943e57,0xbeaebde2,0xbde2beae,0x3eb78000,0x3e573e94,0xbde23eae,0xbeae3de2,
0x3eb7,0xbe573e94,0xbeae3de2,0xbeaebde2,0x3eb78000,0x3e943e57,0x3de23eae,0xbde23eae,0x3eb7,0xbde23eae,0xbe573e94,0xbe943e57,0x3eb78000,0x3eae3de2,0x3e943e57,0x3e573e94,
0x3eae3de2,0x3eb7,0xbeae3de2,0xbe57be94,0x3de2beae,0x3eb78000,0x3de23eae,0xbe943e57,0x3e57be94,0x3eb70000,0x3e573e94,0xbde23eae,0xbe94be57,0xbeb7,0x3e94be57,0x3eae3de2,
0xbe57be94,0xbeb7,0x3e57be94,0x3eaebde2,0xbe943e57,0xbeb78000,0xbe94be57,0xbde2beae,0xbeae3de2,0xbeb70000,0xbeaebde2,0xbe94be57,0x3de23eae,0x3eb7,0xbde23eae,0xbe573e94,
0x3eb7,0x3eb7,0x3eb7,0x3eb7,0x3eb78000,0x3eb78000,0x3eb78000,0x3eb78000,0x3e57be94,0x3de2beae,0xbeb7,0xbde2beae,0xbe94be57,0xbeaebde2,0xbeb78000,0xbeae3de2,
0xbeae3de2,0xbe573e94,0x3eb7,0x3e573e94,0x3de23eae,0x3e943e57,0x3eb78000,0x3e94be57,0x3eae3de2,0x3e94be57,0xbeb7,0xbe94be57,0x3de2beae,0xbe57be94,0xbeb78000,0xbe573e94,
0x3eb7,0x3eb7,0x3eb7,0x3eb7,0x3eb78000,0x3eb78000,0x3eb78000,0x3eb78000,0xbe57be94,0xbe94be57,0xbeaebde2,0xbeb70000,0xbe943e57,0xbe573e94,0xbde23eae,0x3eb7,
0x3eae3de2,0x3eaebde2,0x3e57be94,0xbeb7,0x3de2beae,0xbde2beae,0xbe94be57,0xbeb78000,0xbeae3de2,0xbde23eae,0x3e573e94,0x3eb70000,0x3de23eae,0x3eae3de2,0x3e94be57,0xbeb7,
0xbe57be94,0xbeae3de2,0x3eb7,0x3eae3de2,0xbe943e57,0x3de23eae,0x3eb78000,0x3de2beae,0x3eb7,0x3eb70000,0xbeb7,0xbeb70000,0x3eb78000,0xbeb7,0xbeb78000,0x3eb7,
0x3e57be94,0xbeaebde2,0x3eb7,0x3eaebde2,0xbe94be57,0xbde23eae,0x3eb78000,0xbde2beae,0xbeae3de2,0x3e943e57,0xbeb7,0xbe943e57,0x3de23eae,0x3e57be94,0xbeb78000,0x3e573e94,
0x3e57be94,0xbe57be94,0xbeae3de2,0x3eb7,0xbe94be57,0xbe943e57,0x3de23eae,0x3eb78000,0x3eb7,0x3eb70000,0xbeb7,0xbeb70000,0x3eb78000,0xbeb7,0xbeb78000,0x3eb7,
0xbe57be94,0xbe573e94,0x3eae3de2,0xbeb7,0xbe943e57,0x3e943e57,0x3de2beae,0xbeb78000,0x3eae3de2,0xbde2beae,0xbe573e94,0x3eb70000,0x3de2beae,0xbeae3de2,0x3e943e57,0xbeb7,
0x3eae3de2,0xbe57be94,0x3eb7,0x3e57be94,0x3de2beae,0xbe943e57,0x3eb78000,0xbe94be57,0xbe57be94,0x3de23eae,0xbeb7,0xbde23eae,0xbe943e57,0x3eaebde2,0xbeb78000,0x3eae3de2,
0x3eb7,0xbeb7,0x3eb7,0xbeb7,0x3eb78000,0xbeb78000,0x3eb78000,0xbeb78000,0x3e57be94,0xbde23eae,0xbeb7,0x3de23eae,0xbe94be57,0x3eae3de2,0xbeb78000,0x3eaebde2,
0xbeae3de2,0x3eae3de2,0xbe57be94,0x3eb7,0x3de23eae,0x3de2beae,0xbe943e57,0x3eb78000,0x3e57be94,0xbe943e57,0x3eaebde2,0xbeb70000,0xbe94be57,0x3e573e94,0xbde2beae,0x3eb7,
0x3eb7,0xbeb7,0x3eb7,0xbeb7,0x3eb78000,0xbeb78000,0x3eb78000,0xbeb78000,0xbe57be94,0x3e943e57,0xbeaebde2,0x3eb70000,0xbe943e57,0x3e57be94,0xbde23eae,0xbeb7,
0xbeae3de2,0x3e57be94,0x3eb7,0xbe57be94,0x3de23eae,0xbe94be57,0x3eb78000,0xbe943e57,0x3eae3de2,0xbe943e57,0xbeb7,0x3e943e57,0x3de2beae,0x3e573e94,0xbeb78000,0x3e57be94,
0xbe57be94,0x3eaebde2,0x3eb7,0xbeaebde2,0xbe943e57,0xbde2beae,0x3eb78000,0xbde23eae,0x3eb7,0xbeb70000,0xbeb7,0x3eb70000,0x3eb78000,0x3eb7,0xbeb78000,0xbeb7,
0x3eae3de2,0xbeae3de2,0x3e57be94,0x3eb7,0x3de2beae,0x3de23eae,0xbe94be57,0x3eb78000,0xbeae3de2,0x3de2beae,0x3e573e94,0xbeb70000,0x3de23eae,0xbeaebde2,0x3e94be57,0x3eb7,
0x3e57be94,0x3e573e94,0xbeae3de2,0xbeb7,0xbe94be57,0x3e94be57,0x3de23eae,0xbeb78000,0x3eb7,0xbeb70000,0xbeb7,0x3eb70000,0x3eb78000,0x3eb7,0xbeb78000,0xbeb7,
0x3e57be94,0x3eae3de2,0x3eb7,0xbeae3de2,0xbe94be57,0x3de2beae,0x3eb78000,0x3de23eae,0xbeae3de2,0xbe94be57,0xbeb7,0x3e94be57,0x3de23eae,0xbe573e94,0xbeb78000,0xbe57be94,
0x3eae3de2,0x3e573e94,0x3eb7,0xbe573e94,0x3de2beae,0x3e94be57,0x3eb78000,0x3e943e57,0xbe57be94,0xbde2beae,0xbeb7,0x3de2beae,0xbe943e57,0xbeae3de2,0xbeb78000,0xbeaebde2,
0xbe57be94,0x3e57be94,0x3eae3de2,0x3eb7,0xbe943e57,0xbe94be57,0x3de2beae,0x3eb78000,0x3eae3de2,0x3de23eae,0xbe573e94,0xbeb70000,0x3de2beae,0x3eaebde2,0x3e943e57,0x3eb7,
0xbeae3de2,0xbeaebde2,0xbe57be94,0xbeb7,0x3de23eae,0xbde23eae,0xbe943e57,0xbeb78000,0x3e57be94,0x3e94be57,0x3eaebde2,0x3eb70000,0xbe94be57,0xbe57be94,0xbde2beae,0xbeb7,
0x3eb7,0x3eb7,0x3eb7,0x3eb7,0x3eb78000,0x3eb78000,0x3eb78000,0x3eb78000,0xbeae3de2,0xbe943e57,0xbe573e94,0xbde23eae,0x3de23eae,0x3e573e94,0x3e943e57,0x3eae3de2,
0xbe57be94,0xbeaebde2,0xbeae3de2,0xbe573e94,0xbe943e57,0xbde23eae,0x3de23eae,0x3e943e57,0x3e57be94,0xbde2beae,0xbeaebde2,0xbe943e57,0xbe94be57,0xbeae3de2,0xbde23eae,0x3e573e94,
0,0,0,0,0,0,0,0,0,0,0,0,0,0,0,0,
0,0,0,0,0,0,0,0,0,0,0,0,0,0,0,0,
0x3eae3de2,0x3e57be94,0xbe57be94,0xbeae3de2,0x3de2beae,0xbe94be57,0xbe943e57,0x3de23eae,0x3eb7,0x3eb70000,0xbeb7,0xbeb70000,0x3eb78000,0xbeb7,0xbeb78000,0x3eb7,
0xbeae3de2,0x3e573e94,0x3e57be94,0xbeaebde2,0x3de23eae,0x3e94be57,0xbe94be57,0xbde23eae,0xbe57be94,0xbde23eae,0x3eaebde2,0xbe94be57,0xbe943e57,0x3eae3de2,0xbde2beae,0xbe573e94,
0,0,0,0,0,0,0,0,0,0,0,0,0,0,0,0,
0,0,0,0,0,0,0,0,0,0,0,0,0,0,0,0,
0x3e57be94,0xbeae3de2,0x3eae3de2,0xbe57be94,0xbe94be57,0x3de23eae,0x3de2beae,0xbe943e57,0x3eae3de2,0xbe94be57,0x3e573e94,0xbde2beae,0x3de2beae,0xbe573e94,0x3e94be57,0xbeae3de2,
0x3eb7,0xbeb7,0x3eb7,0xbeb7,0x3eb78000,0xbeb78000,0x3eb78000,0xbeb78000,0xbeae3de2,0x3e94be57,0xbe573e94,0x3de2beae,0x3de23eae,0xbe57be94,0x3e943e57,0xbeaebde2,
0,0,0,0,0,0,0,0,0,0,0,0,0,0,0,0,
0,0,0,0,0,0,0,0,0,0,0,0,0,0,0,0,
0xbe57be94,0x3eae3de2,0xbeae3de2,0x3e57be94,0xbe943e57,0x3de2beae,0x3de23eae,0xbe94be57,0x3e57be94,0x3de23eae,0xbeaebde2,0x3e94be57,0xbe94be57,0x3eaebde2,0xbde23eae,0xbe57be94,
0x3eae3de2,0xbe573e94,0xbe57be94,0x3eaebde2,0x3de2beae,0x3e943e57,0xbe943e57,0xbde2beae,0x3eb7,0xbeb70000,0xbeb7,0x3eb70000,0x3eb78000,0x3eb7,0xbeb78000,0xbeb7,
0,0,0,0,0,0,0,0,0,0,0,0,0,0,0,0,
0,0,0,0,0,0,0,0,0,0,0,0,0,0,0,0,
0xbeae3de2,0xbe57be94,0x3e57be94,0x3eae3de2,0x3de23eae,0xbe943e57,0xbe94be57,0x3de2beae,0xbe57be94,0x3de2beae,0x3eaebde2,0x3e943e57,0xbe943e57,0xbeaebde2,0xbde2beae,0x3e57be94,
0x3e57be94,0x3eaebde2,0x3eae3de2,0x3e573e94,0xbe94be57,0xbde2beae,0x3de2beae,0x3e94be57,0x3eae3de2,0x3e943e57,0x3e573e94,0x3de23eae,0x3de2beae,0x3e57be94,0x3e94be57,0x3eaebde2,
0,0,0,0,0,0,0,0,0,0,0,0,0,0,0,0,
0,0,0,0,0,0,0,0,0,0,0,0,0,0,0,0,
0,0,0,0,0,0,0,0,0,0,0,0,0,0,0,0,
0,0,0,0,0,0,0,0,0,0,0,0,0,0,0,0,
0x3eb7,0x3eb7,0x3eb7,0x3eb7,0x3eb78000,0x3eb78000,0x3eb78000,0x3eb78000,0xbeae3de2,0xbe943e57,0xbe573e94,0xbde23eae,0x3de23eae,0x3e573e94,0x3e943e57,0x3eae3de2,
0xbe57be94,0xbeaebde2,0xbeae3de2,0xbe573e94,0xbe943e57,0xbde23eae,0x3de23eae,0x3e943e57,0x3e57be94,0xbde2beae,0xbeaebde2,0xbe943e57,0xbe94be57,0xbeae3de2,0xbde23eae,0x3e573e94,
0,0,0,0,0,0,0,0,0,0,0,0,0,0,0,0,
0,0,0,0,0,0,0,0,0,0,0,0,0,0,0,0,
0x3eae3de2,0x3e57be94,0xbe57be94,0xbeae3de2,0x3de2beae,0xbe94be57,0xbe943e57,0x3de23eae,0x3eb7,0x3eb70000,0xbeb7,0xbeb70000,0x3eb78000,0xbeb7,0xbeb78000,0x3eb7,
0xbeae3de2,0x3e573e94,0x3e57be94,0xbeaebde2,0x3de23eae,0x3e94be57,0xbe94be57,0xbde23eae,0xbe57be94,0xbde23eae,0x3eaebde2,0xbe94be57,0xbe943e57,0x3eae3de2,0xbde2beae,0xbe573e94,
0,0,0,0,0,0,0,0,0,0,0,0,0,0,0,0,
0,0,0,0,0,0,0,0,0,0,0,0,0,0,0,0,
0x3e57be94,0xbeae3de2,0x3eae3de2,0xbe57be94,0xbe94be57,0x3de23eae,0x3de2beae,0xbe943e57,0x3eae3de2,0xbe94be57,0x3e573e94,0xbde2beae,0x3de2beae,0xbe573e94,0x3e94be57,0xbeae3de2,
0x3eb7,0xbeb7,0x3eb7,0xbeb7,0x3eb78000,0xbeb78000,0x3eb78000,0xbeb78000,0xbeae3de2,0x3e94be57,0xbe573e94,0x3de2beae,0x3de23eae,0xbe57be94,0x3e943e57,0xbeaebde2,
0,0,0,0,0,0,0,0,0,0,0,0,0,0,0,0,
0,0,0,0,0,0,0,0,0,0,0,0,0,0,0,0,
0xbe57be94,0x3eae3de2,0xbeae3de2,0x3e57be94,0xbe943e57,0x3de2beae,0x3de23eae,0xbe94be57,0x3e57be94,0x3de23eae,0xbeaebde2,0x3e94be57,0xbe94be57,0x3eaebde2,0xbde23eae,0xbe57be94,
0x3eae3de2,0xbe573e94,0xbe57be94,0x3eaebde2,0x3de2beae,0x3e943e57,0xbe943e57,0xbde2beae,0x3eb7,0xbeb70000,0xbeb7,0x3eb70000,0x3eb78000,0x3eb7,0xbeb78000,0xbeb7,
0,0,0,0,0,0,0,0,0,0,0,0,0,0,0,0,
0,0,0,0,0,0,0,0,0,0,0,0,0,0,0,0,
0xbeae3de2,0xbe57be94,0x3e57be94,0x3eae3de2,0x3de23eae,0xbe943e57,0xbe94be57,0x3de2beae,0xbe57be94,0x3de2beae,0x3eaebde2,0x3e943e57,0xbe943e57,0xbeaebde2,0xbde2beae,0x3e57be94,
0x3e57be94,0x3eaebde2,0x3eae3de2,0x3e573e94,0xbe94be57,0xbde2beae,0x3de2beae,0x3e94be57,0x3eae3de2,0x3e943e57,0x3e573e94,0x3de23eae,0x3de2beae,0x3e57be94,0x3e94be57,0x3eaebde2,
};
__device__ __align__(128) const uint32_t TAB_P3[3008] = {
0,0,0,0,0,0,0,0,0,0,0,0,0,0,0,0,
0x80003e83,0xbe79bda2,0x3e1abe54,0x3e1a3e54,0x3e830000,0xbda23e79,0xbe54be1a,0x3e54be1a,0x80003e83,0xbe54be1a,0x3e79bda2,0xbda23e79,0x3e830000,0xbe1a3e54,0xbda2be79,0x3e793da2,
0,0,0,0,0,0,0,0,0,0,0,0,0,0,0,0,
0xbe793da2,0x8000be83,0x3e793da2,0xbe1a3e54,0x3da23e79,0xbe830000,0x3da2be79,0x3e543e1a,0xbe1abe54,0x3e830000,0xbe1a3e54,0xbda2be79,0xbe543e1a,0xbe83,0x3e543e1a,0xbe793da2,
0x80003e83,0xbe1abe54,0x3e793da2,0xbe793da2,0x3e830000,0xbe543e1a,0x3da2be79,0x3da23e79,0x80003e83,0xbda2be79,0x3e1a3e54,0xbe54be1a,0x3e830000,0xbe793da2,0x3e54be1a,0xbe1a3e54,
0x80003e83,0x8000be83,0x80003e83,0x8000be83,0x3e830000,0xbe830000,0x3e830000,0xbe830000,0x80003e83,0x3da2be79,0xbe1a3e54,0x3e54be1a,0x3e830000,0xbe79bda2,0x3e543e1a,0xbe1abe54,
0x3e1abe54,0x80003e83,0xbe1abe54,0x3e793da2,0xbe54be1a,0x3e830000,0xbe543e1a,0x3da2be79,0x3e793da2,0xbe830000,0x3e79bda2,0xbe543e1a,0x3da2be79,0x3e83,0xbda2be79,0x3e1a3e54,
0x80003e83,0x8000be83,0x80003e83,0x8000be83,0x3e830000,0xbe830000,0x3e830000,0xbe830000,0xbe793da2,0x3e830000,0xbe79bda2,0x3e543e1a,0x3da23e79,0xbe83,0xbda23e79,0x3e1abe54,
0x80003e83,0x3e1abe54,0xbe793da2,0x3e793da2,0x3e830000,0xbe54be1a,0x3da23e79,0x3da2be79,0x80003e83,0x3e54be1a,0xbe79bda2,0x3da23e79,0x3e830000,0xbe1abe54,0xbda23e79,0x3e79bda2,
0x80003e83,0x3e79bda2,0xbe1abe54,0xbe1a3e54,0x3e830000,0xbda2be79,0xbe543e1a,0x3e543e1a,0x80003e83,0x3e830000,0x8000be83,0xbe830000,0x3e830000,0xbe83,0xbe830000,0x3e83,
0xbe1abe54,0x80003e83,0x3e1abe54,0xbe793da2,0xbe543e1a,0x3e830000,0xbe54be1a,0x3da23e79,0x3e1abe54,0xbe830000,0x3e1a3e54,0x3da2be79,0xbe54be1a,0x3e83,0x3e54be1a,0xbe79bda2,
0x3e793da2,0x8000be83,0xbe793da2,0x3e1a3e54,0x3da2be79,0xbe830000,0x3da23e79,0x3e54be1a,0x80003e83,0x3e830000,0x8000be83,0xbe830000,0x3e830000,0xbe83,0xbe830000,0x3e83,
0x80003e83,0x3e793da2,0x3e1abe54,0xbe1abe54,0x3e830000,0x3da2be79,0xbe54be1a,0xbe543e1a,0x80003e83,0x3e543e1a,0x3e79bda2,0x3da2be79,0x3e830000,0x3e1abe54,0xbda2be79,0xbe79bda2,
0x80003e83,0x3e1a3e54,0x3e793da2,0x3e79bda2,0x3e830000,0x3e54be1a,0x3da2be79,0xbda2be79,0x80003e83,0x3da23e79,0x3e1a3e54,0x3e543e1a,0x3e830000,0x3e79bda2,0x3e54be1a,0x3e1abe54,
0xbe793da2,0x80003e83,0x3e793da2,0x3e1abe54,0x3da23e79,0x3e830000,0x3da2be79,0xbe54be1a,0xbe1abe54,0xbe830000,0xbe1a3e54,0x3da23e79,0xbe543e1a,0x3e83,0x3e543e1a,0x3e79bda2,
0x3e1abe54,0x8000be83,0xbe1abe54,0xbe79bda2,0xbe54be1a,0xbe830000,0xbe543e1a,0xbda23e79,0x3e793da2,0x3e830000,0x3e79bda2,0x3e54be1a,0x3da2be79,0xbe83,0xbda2be79,0xbe1abe54,
0,0,0,0,0,0,0,0,0,0,0,0,0,0,0,0,
0xbe1abe54,0x3e79bda2,0x80003e83,0xbe79bda2,0xbe543e1a,0xbda2be79,0x3e830000,0xbda23e79,0x3e793da2,0xbe543e1a,0x8000be83,0x3e543e1a,0x3da2be79,0x3e1a3e54,0xbe830000,0x3e1abe54,
0,0,0,0,0,0,0,0,0,0,0,0,0,0,0,0,
0x3e1abe54,0x3e1a3e54,0xbe793da2,0x8000be83,0xbe54be1a,0x3e54be1a,0x3da23e79,0xbe830000,0xbe793da2,0x3da2be79,0x3e1a3e54,0xbe830000,0x3da23e79,0xbe79bda2,0x3e54be1a,0x3e83,
0xbe793da2,0x3e1abe54,0x80003e83,0xbe1abe54,0x3da23e79,0xbe54be1a,0x3e830000,0xbe543e1a,0x3e1abe54,0xbda23e79,0x8000be83,0x3da23e79,0xbe54be1a,0x3e793da2,0xbe830000,0x3e79bda2,
0x80003e83,0x8000be83,0x80003e83,0x8000be83,0x3e830000,0xbe830000,0x3e830000,0xbe830000,0xbe1abe54,0x3da23e79,0x8000be83,0xbda23e79,0xbe543e1a,0x3e79bda2,0xbe830000,0x3e793da2,
0x3e793da2,0xbe793da2,0x3e1abe54,0x80003e83,0x3da2be79,0x3da23e79,0xbe54be1a,0x3e830000,0xbe1abe54,0x3e543e1a,0xbe79bda2,0x3e830000,0xbe543e1a,0x3e1abe54,0xbda23e79,0xbe83,
0x80003e83,0x8000be83,0x80003e83,0x8000be83,0x3e830000,0xbe830000,0x3e830000,0xbe830000,0x3e1abe54,0xbe543e1a,0x3e79bda2,0xbe830000,0xbe54be1a,0x3e1a3e54,0xbda2be79,0x3e83,
0x3e793da2,0xbe1abe54,0x80003e83,0x3e1abe54,0x3da2be79,0xbe543e1a,0x3e830000,0xbe54be1a,0xbe793da2,0x3e543e1a,0x8000be83,0xbe543e1a,0x3da23e79,0x3e1abe54,0xbe830000,0x3e1a3e54,
0x3e1abe54,0xbe79bda2,0x80003e83,0x3e79bda2,0xbe54be1a,0xbda23e79,0x3e830000,0xbda2be79,0x80003e83,0x3e830000,0x8000be83,0xbe830000,0x3e830000,0xbe83,0xbe830000,0x3e83,
0xbe793da2,0x3e793da2,0xbe1abe54,0x80003e83,0x3da23e79,0x3da2be79,0xbe543e1a,0x3e830000,0x3e793da2,0xbda2be79,0xbe1a3e54,0x3e830000,0x3da2be79,0xbe793da2,0x3e543e1a,0xbe83,
0xbe1abe54,0xbe1a3e54,0x3e793da2,0x8000be83,0xbe543e1a,0x3e543e1a,0x3da2be79,0xbe830000,0x80003e83,0x3e830000,0x8000be83,0xbe830000,0x3e830000,0xbe83,0xbe830000,0x3e83,
0xbe1abe54,0xbe793da2,0x80003e83,0x3e793da2,0xbe543e1a,0x3da23e79,0x3e830000,0x3da2be79,0x3e793da2,0x3e54be1a,0x8000be83,0xbe54be1a,0x3da2be79,0xbe1abe54,0xbe830000,0xbe1a3e54,
0xbe793da2,0xbe1a3e54,0x80003e83,0x3e1a3e54,0x3da23e79,0x3e543e1a,0x3e830000,0x3e54be1a,0x3e1abe54,0x3da2be79,0x8000be83,0xbda2be79,0xbe54be1a,0xbe79bda2,0xbe830000,0xbe793da2,
0x3e1abe54,0xbe1abe54,0xbe793da2,0x80003e83,0xbe54be1a,0xbe543e1a,0x3da23e79,0x3e830000,0xbe793da2,0xbda23e79,0x3e1a3e54,0x3e830000,0x3da23e79,0x3e793da2,0x3e54be1a,0xbe83,
0x3e793da2,0x3e79bda2,0x3e1abe54,0x8000be83,0x3da2be79,0xbda2be79,0xbe54be1a,0xbe830000,0xbe1abe54,0xbe54be1a,0xbe79bda2,0xbe830000,0xbe543e1a,0xbe1a3e54,0xbda23e79,0x3e83,
0,0,0,0,0,0,0,0,0,0,0,0,0,0,0,0,
0,0,0,0,0,0,0,0,0,0,0,0,0,0,0,0,
0,0,0,0,0,0,0,0,0,0,0,0,0,0,0,0,
0x3e793da2,0xbe1a3e54,0xbe1abe54,0x3e79bda2,0x3da2be79,0x3e543e1a,0xbe543e1a,0xbda2be79,0x3e1abe54,0x3da23e79,0xbe79bda2,0x3e54be1a,0xbe54be1a,0x3e79bda2,0xbda23e79,0xbe1abe54,
0,0,0,0,0,0,0,0,0,0,0,0,0,0,0,0,
0,0,0,0,0,0,0,0,0,0,0,0,0,0,0,0,
0xbe1abe54,0x3e793da2,0xbe793da2,0x3e1abe54,0xbe543e1a,0x3da2be79,0x3da23e79,0xbe54be1a,0xbe793da2,0x3e54be1a,0xbe1a3e54,0x3da2be79,0x3da23e79,0xbe1abe54,0x3e543e1a,0xbe79bda2,
0x80003e83,0x8000be83,0x80003e83,0x8000be83,0x3e830000,0xbe830000,0x3e830000,0xbe830000,0x3e793da2,0xbe54be1a,0x3e1a3e54,0xbda2be79,0x3da2be79,0xbe1a3e54,0x3e54be1a,0xbe793da2,
0,0,0,0,0,0,0,0,0,0,0,0,0,0,0,0,
0,0,0,0,0,0,0,0,0,0,0,0,0,0,0,0,
0x3e1abe54,0xbe793da2,0x3e793da2,0xbe1abe54,0xbe54be1a,0x3da23e79,0x3da2be79,0xbe543e1a,0xbe1abe54,0xbda23e79,0x3e79bda2,0xbe54be1a,0xbe543e1a,0x3e793da2,0xbda2be79,0xbe1a3e54,
0xbe793da2,0x3e1a3e54,0x3e1abe54,0xbe79bda2,0x3da23e79,0x3e54be1a,0xbe54be1a,0xbda23e79,0x80003e83,0x3e830000,0x8000be83,0xbe830000,0x3e830000,0xbe83,0xbe830000,0x3e83,
0,0,0,0,0,0,0,0,0,0,0,0,0,0,0,0,
0,0,0,0,0,0,0,0,0,0,0,0,0,0,0,0,
0x3e793da2,0x3e1abe54,0xbe1abe54,0xbe793da2,0x3da2be79,0xbe54be1a,0xbe543e1a,0x3da23e79,0x3e1abe54,0xbda2be79,0xbe79bda2,0xbe543e1a,0xbe54be1a,0xbe793da2,0xbda23e79,0x3e1a3e54,
0xbe1abe54,0xbe79bda2,0xbe793da2,0xbe1a3e54,0xbe543e1a,0xbda23e79,0x3da23e79,0x3e543e1a,0xbe793da2,0xbe543e1a,0xbe1a3e54,0xbda23e79,0x3da23e79,0x3e1a3e54,0x3e543e1a,0x3e793da2,
0xbe163dda,0,0,0,0,0xbe163dda,0,0,0,0,0xbe163dda,0,0,0,0,0xbe163dda,
0xbe253da8,0,0,0,0,0xbe253da8,0,0,0,0,0xbe253da8,0,0,0,0,0xbe253da8,
0xbd65be30,0,0,0,0,0xbd65be30,0,0,0,0,0xbd65be30,0,0,0,0,0xbd65be30,
0x3ce8be37,0,0,0,0,0x3ce8be37,0,0,0,0,0x3ce8be37,0,0,0,0,0x3ce8be37,
0xbe303d65,0,0,0,0,0xbe303d65,0,0,0,0,0xbe303d65,0,0,0,0,0xbe303d65,
0xbe373ce8,0,0,0,0,0xbe373ce8,0,0,0,0,0xbe373ce8,0,0,0,0,0xbe373ce8,
0x3ddabe16,0,0,0,0,0x3ddabe16,0,0,0,0,0x3ddabe16,0,0,0,0,0x3ddabe16,
0x3e25bda8,0,0,0,0,0x3e25bda8,0,0,0,0,0x3e25bda8,0,0,0,0,0x3e25bda8,
0xbe390000,0,0,0,0,0xbe390000,0,0,0,0,0xbe390000,0,0,0,0,0xbe390000,
0xbe37bce8,0,0,0,0,0xbe37bce8,0,0,0,0,0xbe37bce8,0,0,0,0,0xbe37bce8,
0x3e390000,0,0,0,0,0x3e390000,0,0,0,0,0x3e390000,0,0,0,0,0x3e390000,
0x3e253da8,0,0,0,0,0x3e253da8,0,0,0,0,0x3e253da8,0,0,0,0,0x3e253da8,
0xbe30bd65,0,0,0,0,0xbe30bd65,0,0,0,0,0xbe30bd65,0,0,0,0,0xbe30bd65,
0xbe25bda8,0,0,0,0,0xbe25bda8,0,0,0,0,0xbe25bda8,0,0,0,0,0xbe25bda8,
0x3dda3e16,0,0,0,0,0x3dda3e16,0,0,0,0,0x3dda3e16,0,0,0,0,0x3dda3e16,
0x3ce83e37,0,0,0,0,0x3ce83e37,0,0,0,0,0x3ce83e37,0,0,0,0,0x3ce83e37,
0xbe16bdda,0,0,0,0,0xbe16bdda,0,0,0,0,0xbe16bdda,0,0,0,0,0xbe16bdda,
0xbe03be03,0,0,0,0,0xbe03be03,0,0,0,0,0xbe03be03,0,0,0,0,0xbe03be03,
0xbd653e30,0,0,0,0,0xbd653e30,0,0,0,0,0xbd653e30,0,0,0,0,0xbd653e30,
0xbe033e03,0,0,0,0,0xbe033e03,0,0,0,0,0xbe033e03,0,0,0,0,0xbe033e03,
0xbddabe16,0,0,0,0,0xbddabe16,0,0,0,0,0xbddabe16,0,0,0,0,0xbddabe16,
0xbda8be25,0,0,0,0,0xbda8be25,0,0,0,0,0xbda8be25,0,0,0,0,0xbda8be25,
0xbe303d65,0,0,0,0,0xbe303d65,0,0,0,0,0xbe303d65,0,0,0,0,0xbe303d65,
0xbe37bce8,0,0,0,0,0xbe37bce8,0,0,0,0,0xbe37bce8,0,0,0,0,0xbe37bce8,
0xbd65be30,0,0,0,0,0xbd65be30,0,0,0,0,0xbd65be30,0,0,0,0,0xbd65be30,
0xbce8be37,0,0,0,0,0xbce8be37,0,0,0,0,0xbce8be37,0,0,0,0,0xbce8be37,
0xbe16bdda,0,0,0,0,0xbe16bdda,0,0,0,0,0xbe16bdda,0,0,0,0,0xbe16bdda,
0xbda8be25,0,0,0,0,0xbda8be25,0,0,0,0,0xbda8be25,0,0,0,0,0xbda8be25,
0x3e390000,0,0,0,0,0x3e390000,0,0,0,0,0x3e390000,0,0,0,0,0x3e390000,
0x3e033e03,0,0,0,0,0x3e033e03,0,0,0,0,0x3e033e03,0,0,0,0,0x3e033e03,
0xbd653e30,0,0,0,0,0xbd653e30,0,0,0,0,0xbd653e30,0,0,0,0,0xbd653e30,
0xbe373ce8,0,0,0,0,0xbe373ce8,0,0,0,0,0xbe373ce8,0,0,0,0,0xbe373ce8,
0x80003e39,0,0,0,0,0x80003e39,0,0,0,0,0x80003e39,0,0,0,0,0x80003e39,
0xbe033e03,0,0,0,0,0xbe033e03,0,0,0,0,0xbe033e03,0,0,0,0,0xbe033e03,
0xbddabe16,0,0,0,0,0xbddabe16,0,0,0,0,0xbddabe16,0,0,0,0,0xbddabe16,
0x3da8be25,0,0,0,0,0x3da8be25,0,0,0,0,0x3da8be25,0,0,0,0,0x3da8be25,
0xbe390000,0,0,0,0,0xbe390000,0,0,0,0,0xbe390000,0,0,0,0,0xbe390000,
0xbe03be03,0,0,0,0,0xbe03be03,0,0,0,0,0xbe03be03,0,0,0,0,0xbe03be03,
0x3e390000,0,0,0,0,0x3e390000,0,0,0,0,0x3e390000,0,0,0,0,0x3e390000,
0x3da83e25,0,0,0,0,0x3da83e25,0,0,0,0,0x3da83e25,0,0,0,0,0x3da83e25,
0x8000be39,0,0,0,0,0x8000be39,0,0,0,0,0x8000be39,0,0,0,0,0x8000be39,
0x3e03be03,0,0,0,0,0x3e03be03,0,0,0,0,0x3e03be03,0,0,0,0,0x3e03be03,
0xbdda3e16,0,0,0,0,0xbdda3e16,0,0,0,0,0xbdda3e16,0,0,0,0,0xbdda3e16,
0xbe37bce8,0,0,0,0,0xbe37bce8,0,0,0,0,0xbe37bce8,0,0,0,0,0xbe37bce8,
0x3e390000,0,0,0,0,0x3e390000,0,0,0,0,0x3e390000,0,0,0,0,0x3e390000,
0x3e033e03,0,0,0,0,0x3e033e03,0,0,0,0,0x3e033e03,0,0,0,0,0x3e033e03,
0xbd65be30,0,0,0,0,0xbd65be30,0,0,0,0,0xbd65be30,0,0,0,0,0xbd65be30,
0x3e03be03,0,0,0,0,0x3e03be03,0,0,0,0,0x3e03be03,0,0,0,0,0x3e03be03,
0x80003e39,0,0,0,0,0x80003e39,0,0,0,0,0x80003e39,0,0,0,0,0x80003e39,
0xbe033e03,0,0,0,0,0xbe033e03,0,0,0,0,0xbe033e03,0,0,0,0,0xbe033e03,
0x3e303d65,0,0,0,0,0x3e303d65,0,0,0,0,0x3e303d65,0,0,0,0,0x3e303d65,
0x3ce83e37,0,0,0,0,0x3ce83e37,0,0,0,0,0x3ce83e37,0,0,0,0,0x3ce83e37,
0xbe390000,0,0,0,0,0xbe390000,0,0,0,0,0xbe390000,0,0,0,0,0xbe390000,
0xbe03be03,0,0,0,0,0xbe03be03,0,0,0,0,0xbe03be03,0,0,0,0,0xbe03be03,
0xbe163dda,0,0,0,0,0xbe163dda,0,0,0,0,0xbe163dda,0,0,0,0,0xbe163dda,
0xbe25bda8,0,0,0,0,0xbe25bda8,0,0,0,0,0xbe25bda8,0,0,0,0,0xbe25bda8,
0xbe16bdda,0,0,0,0,0xbe16bdda,0,0,0,0,0xbe16bdda,0,0,0,0,0xbe16bdda,
0x3da8be25,0,0,0,0,0x3da8be25,0,0,0,0,0x3da8be25,0,0,0,0,0x3da8be25,
0x3e16bdda,0,0,0,0,0x3e16bdda,0,0,0,0,0x3e16bdda,0,0,0,0,0x3e16bdda,
0x3da83e25,0,0,0,0,0x3da83e25,0,0,0,0,0x3da83e25,0,0,0,0,0x3da83e25,
0x3e303d65,0,0,0,0,0x3e303d65,0,0,0,0,0x3e303d65,0,0,0,0,0x3e303d65,
0xbce83e37,0,0,0,0,0xbce83e37,0,0,0,0,0xbce83e37,0,0,0,0,0xbce83e37,
0xbe303d65,0,0,0,0,0xbe303d65,0,0,0,0,0xbe303d65,0,0,0,0,0xbe303d65,
0xbce8be37,0,0,0,0,0xbce8be37,0,0,0,0,0xbce8be37,0,0,0,0,0xbce8be37,
0xbe390000,0,0,0,0,0xbe390000,0,0,0,0,0xbe390000,0,0,0,0,0xbe390000,
0xbce8be37,0,0,0,0,0xbce8be37,0,0,0,0,0xbce8be37,0,0,0,0,0xbce8be37,
0x3e390000,0,0,0,0,0x3e390000,0,0,0,0,0x3e390000,0,0,0,0,0x3e390000,
0xbce83e37,0,0,0,0,0xbce83e37,0,0,0,0,0xbce83e37,0,0,0,0,0xbce83e37,
0x3e30bd65,0,0,0,0,0x3e30bd65,0,0,0,0,0x3e30bd65,0,0,0,0,0x3e30bd65,
0x3da83e25,0,0,0,0,0x3da83e25,0,0,0,0,0x3da83e25,0,0,0,0,0x3da83e25,
0xbe30bd65,0,0,0,0,0xbe30bd65,0,0,0,0,0xbe30bd65,0,0,0,0,0xbe30bd65,
0x3da8be25,0,0,0,0,0x3da8be25,0,0,0,0,0x3da8be25,0,0,0,0,0x3da8be25,
0xbe163dda,0,0,0,0,0xbe163dda,0,0,0,0,0xbe163dda,0,0,0,0,0xbe163dda,
0xbe03be03,0,0,0,0,0xbe03be03,0,0,0,0,0xbe03be03,0,0,0,0,0xbe03be03,
0x3e163dda,0,0,0,0,0x3e163dda,0,0,0,0,0x3e163dda,0,0,0,0,0x3e163dda,
0xbe033e03,0,0,0,0,0xbe033e03,0,0,0,0,0xbe033e03,0,0,0,0,0xbe033e03,
0x3ddabe16,0,0,0,0,0x3ddabe16,0,0,0,0,0x3ddabe16,0,0,0,0,0x3ddabe16,
0x3e253da8,0,0,0,0,0x3e253da8,0,0,0,0,0x3e253da8,0,0,0,0,0x3e253da8,
0xbddabe16,0,0,0,0,0xbddabe16,0,0,0,0,0xbddabe16,0,0,0,0,0xbddabe16,
0x3e25bda8,0,0,0,0,0x3e25bda8,0,0,0,0,0x3e25bda8,0,0,0,0,0x3e25bda8,
0xbd653e30,0,0,0,0,0xbd653e30,0,0,0,0,0xbd653e30,0,0,0,0,0xbd653e30,
0xbe37bce8,0,0,0,0,0xbe37bce8,0,0,0,0,0xbe37bce8,0,0,0,0,0xbe37bce8,
0x3d653e30,0,0,0,0,0x3d653e30,0,0,0,0,0x3d653e30,0,0,0,0,0x3d653e30,
0xbe373ce8,0,0,0,0,0xbe373ce8,0,0,0,0,0xbe373ce8,0,0,0,0,0xbe373ce8,
0x3d653e30,0,0,0,0,0x3d653e30,0,0,0,0,0x3d653e30,0,0,0,0,0x3d653e30,
0xbe37bce8,0,0,0,0,0xbe37bce8,0,0,0,0,0xbe37bce8,0,0,0,0,0xbe37bce8,
0xbe390000,0,0,0,0,0xbe390000,0,0,0,0,0xbe390000,0,0,0,0,0xbe390000,
0x3e03be03,0,0,0,0,0x3e03be03,0,0,0,0,0x3e03be03,0,0,0,0,0x3e03be03,
0x3ddabe16,0,0,0,0,0x3ddabe16,0,0,0,0,0x3ddabe16,0,0,0,0,0x3ddabe16,
0x3da83e25,0,0,0,0,0x3da83e25,0,0,0,0,0x3da83e25,0,0,0,0,0x3da83e25,
0x80003e39,0,0,0,0,0x80003e39,0,0,0,0,0x80003e39,0,0,0,0,0x80003e39,
0xbe03be03,0,0,0,0,0xbe03be03,0,0,0,0,0xbe03be03,0,0,0,0,0xbe03be03,
0xbe390000,0,0,0,0,0xbe390000,0,0,0,0,0xbe390000,0,0,0,0,0xbe390000,
0x3da8be25,0,0,0,0,0x3da8be25,0,0,0,0,0x3da8be25,0,0,0,0,0x3da8be25,
0x3e390000,0,0,0,0,0x3e390000,0,0,0,0,0x3e390000,0,0,0,0,0x3e390000,
0xbe033e03,0,0,0,0,0xbe033e03,0,0,0,0,0xbe033e03,0,0,0,0,0xbe033e03,
0x3dda3e16,0,0,0,0,0x3dda3e16,0,0,0,0,0x3dda3e16,0,0,0,0,0x3dda3e16,
0xbe373ce8,0,0,0,0,0xbe373ce8,0,0,0,0,0xbe373ce8,0,0,0,0,0xbe373ce8,
0x8000be39,0,0,0,0,0x8000be39,0,0,0,0,0x8000be39,0,0,0,0,0x8000be39,
0x3e033e03,0,0,0,0,0x3e033e03,0,0,0,0,0x3e033e03,0,0,0,0,0x3e033e03,
0x3d65be30,0,0,0,0,0x3d65be30,0,0,0,0,0x3d65be30,0,0,0,0,0x3d65be30,
0x3e033e03,0,0,0,0,0x3e033e03,0,0,0,0,0x3e033e03,0,0,0,0,0x3e033e03,
0xbe390000,0,0,0,0,0xbe390000,0,0,0,0,0xbe390000,0,0,0,0,0xbe390000,
0x3e03be03,0,0,0,0,0x3e03be03,0,0,0,0,0x3e03be03,0,0,0,0,0x3e03be03,
0xbe303d65,0,0,0,0,0xbe303d65,0,0,0,0,0xbe303d65,0,0,0,0,0xbe303d65,
0x3ce8be37,0,0,0,0,0x3ce8be37,0,0,0,0,0x3ce8be37,0,0,0,0,0x3ce8be37,
0x80003e39,0,0,0,0,0x80003e39,0,0,0,0,0x80003e39,0,0,0,0,0x80003e39,
0xbe03be03,0,0,0,0,0xbe03be03,0,0,0,0,0xbe03be03,0,0,0,0,0xbe03be03,
0x3e163dda,0,0,0,0,0x3e163dda,0,0,0,0,0x3e163dda,0,0,0,0,0x3e163dda,
0xbe253da8,0,0,0,0,0xbe253da8,0,0,0,0,0xbe253da8,0,0,0,0,0xbe253da8,
0x3e390000,0,0,0,0,0x3e390000,0,0,0,0,0x3e390000,0,0,0,0,0x3e390000,
0xbe033e03,0,0,0,0,0xbe033e03,0,0,0,0,0xbe033e03,0,0,0,0,0xbe033e03,
0x3d65be30,0,0,0,0,0x3d65be30,0,0,0,0,0x3d65be30,0,0,0,0,0x3d65be30,
0x3ce83e37,0,0,0,0,0x3ce83e37,0,0,0,0,0x3ce83e37,0,0,0,0,0x3ce83e37,
0x3e163dda,0,0,0,0,0x3e163dda,0,0,0,0,0x3e163dda,0,0,0,0,0x3e163dda,
0xbe25bda8,0,0,0,0,0xbe25bda8,0,0,0,0,0xbe25bda8,0,0,0,0,0xbe25bda8,
0xbddabe16,0,0,0,0,0xbddabe16,0,0,0,0,0xbddabe16,0,0,0,0,0xbddabe16,
0x3e253da8,0,0,0,0,0x3e253da8,0,0,0,0,0x3e253da8,0,0,0,0,0x3e253da8,
0x3e303d65,0,0,0,0,0x3e303d65,0,0,0,0,0x3e303d65,0,0,0,0,0x3e303d65,
0xbe37bce8,0,0,0,0,0xbe37bce8,0,0,0,0,0xbe37bce8,0,0,0,0,0xbe37bce8,
0xbe390000,0,0,0,0,0xbe390000,0,0,0,0,0xbe390000,0,0,0,0,0xbe390000,
0x3e25bda8,0,0,0,0,0x3e25bda8,0,0,0,0,0x3e25bda8,0,0,0,0,0x3e25bda8,
0x3e390000,0,0,0,0,0x3e390000,0,0,0,0,0x3e390000,0,0,0,0,0x3e390000,
0xbe373ce8,0,0,0,0,0xbe373ce8,0,0,0,0,0xbe373ce8,0,0,0,0,0xbe373ce8,
0xbdda3e16,0,0,0,0,0xbdda3e16,0,0,0,0,0xbdda3e16,0,0,0,0,0xbdda3e16,
0x3ce8be37,0,0,0,0,0x3ce8be37,0,0,0,0,0x3ce8be37,0,0,0,0,0x3ce8be37,
0x3e30bd65,0,0,0,0,0x3e30bd65,0,0,0,0,0x3e30bd65,0,0,0,0,0x3e30bd65,
0xbe253da8,0,0,0,0,0xbe253da8,0,0,0,0,0xbe253da8,0,0,0,0,0xbe253da8,
0x3d653e30,0,0,0,0,0x3d653e30,0,0,0,0,0x3d653e30,0,0,0,0,0x3d653e30,
0xbe03be03,0,0,0,0,0xbe03be03,0,0,0,0,0xbe03be03,0,0,0,0,0xbe03be03,
0x3e16bdda,0,0,0,0,0x3e16bdda,0,0,0,0,0x3e16bdda,0,0,0,0,0x3e16bdda,
0xbe033e03,0,0,0,0,0xbe033e03,0,0,0,0,0xbe033e03,0,0,0,0,0xbe033e03,
0x3e303d65,0,0,0,0,0x3e303d65,0,0,0,0,0x3e303d65,0,0,0,0,0x3e303d65,
0xbe373ce8,0,0,0,0,0xbe373ce8,0,0,0,0,0xbe373ce8,0,0,0,0,0xbe373ce8,
0x3ddabe16,0,0,0,0,0x3ddabe16,0,0,0,0,0x3ddabe16,0,0,0,0,0x3ddabe16,
0xbda83e25,0,0,0,0,0xbda83e25,0,0,0,0,0xbda83e25,0,0,0,0,0xbda83e25,
0x3e16bdda,0,0,0,0,0x3e16bdda,0,0,0,0,0x3e16bdda,0,0,0,0,0x3e16bdda,
0xbda83e25,0,0,0,0,0xbda83e25,0,0,0,0,0xbda83e25,0,0,0,0,0xbda83e25,
0x3d65be30,0,0,0,0,0x3d65be30,0,0,0,0,0x3d65be30,0,0,0,0,0x3d65be30,
0xbce83e37,0,0,0,0,0xbce83e37,0,0,0,0,0xbce83e37,0,0,0,0,0xbce83e37,
};
constexpr unsigned long long COS_PK0 = 0x3f903f9a3fa03fa2ull;
constexpr unsigned long long COS_PK1 = 0x3f133f3e3f653f83ull;
constexpr unsigned long long COS_PK2 = 0x3e4b3ec8ull;

__device__ __forceinline__ void wgmma_ss_n80_z(float (&d)[40], uint64_t da, uint64_t db) {
  asm volatile("{\n.reg .pred p;\nsetp.ne.b32 p, 0, 0;\nwgmma.mma_async.sync.aligned.m64n80k16.f32.bf16.bf16 {%0,%1,%2,%3,%4,%5,%6,%7,%8,%9,%10,%11,%12,%13,%14,%15,%16,%17,%18,%19,%20,%21,%22,%23,%24,%25,%26,%27,%28,%29,%30,%31,%32,%33,%34,%35,%36,%37,%38,%39}, %40, %41, p, 1, 1, 1, 0;\n}\n"
    : "+f"(d[0]), "+f"(d[1]), "+f"(d[2]), "+f"(d[3]), "+f"(d[4]), "+f"(d[5]), "+f"(d[6]), "+f"(d[7]), "+f"(d[8]), "+f"(d[9]), "+f"(d[10]), "+f"(d[11]), "+f"(d[12]), "+f"(d[13]), "+f"(d[14]), "+f"(d[15]), "+f"(d[16]), "+f"(d[17]), "+f"(d[18]), "+f"(d[19]), "+f"(d[20]), "+f"(d[21]), "+f"(d[22]), "+f"(d[23]), "+f"(d[24]), "+f"(d[25]), "+f"(d[26]), "+f"(d[27]), "+f"(d[28]), "+f"(d[29]), "+f"(d[30]), "+f"(d[31]), "+f"(d[32]), "+f"(d[33]), "+f"(d[34]), "+f"(d[35]), "+f"(d[36]), "+f"(d[37]), "+f"(d[38]), "+f"(d[39])
    : "l"(da), "l"(db));
}
__device__ __forceinline__ void wgmma_ss_n80_a(float (&d)[40], uint64_t da, uint64_t db) {
  asm volatile("{\n.reg .pred p;\nsetp.ne.b32 p, 1, 0;\nwgmma.mma_async.sync.aligned.m64n80k16.f32.bf16.bf16 {%0,%1,%2,%3,%4,%5,%6,%7,%8,%9,%10,%11,%12,%13,%14,%15,%16,%17,%18,%19,%20,%21,%22,%23,%24,%25,%26,%27,%28,%29,%30,%31,%32,%33,%34,%35,%36,%37,%38,%39}, %40, %41, p, 1, 1, 1, 0;\n}\n"
    : "+f"(d[0]), "+f"(d[1]), "+f"(d[2]), "+f"(d[3]), "+f"(d[4]), "+f"(d[5]), "+f"(d[6]), "+f"(d[7]), "+f"(d[8]), "+f"(d[9]), "+f"(d[10]), "+f"(d[11]), "+f"(d[12]), "+f"(d[13]), "+f"(d[14]), "+f"(d[15]), "+f"(d[16]), "+f"(d[17]), "+f"(d[18]), "+f"(d[19]), "+f"(d[20]), "+f"(d[21]), "+f"(d[22]), "+f"(d[23]), "+f"(d[24]), "+f"(d[25]), "+f"(d[26]), "+f"(d[27]), "+f"(d[28]), "+f"(d[29]), "+f"(d[30]), "+f"(d[31]), "+f"(d[32]), "+f"(d[33]), "+f"(d[34]), "+f"(d[35]), "+f"(d[36]), "+f"(d[37]), "+f"(d[38]), "+f"(d[39])
    : "l"(da), "l"(db));
}

__device__ __forceinline__ void wgmma_rs_n40_z(float (&d)[20], uint32_t a0, uint32_t a1, uint32_t a2, uint32_t a3, uint64_t db) {
  asm volatile("{\n.reg .pred p;\nsetp.ne.b32 p, 0, 0;\nwgmma.mma_async.sync.aligned.m64n40k16.f32.bf16.bf16 {%0,%1,%2,%3,%4,%5,%6,%7,%8,%9,%10,%11,%12,%13,%14,%15,%16,%17,%18,%19}, {%20,%21,%22,%23}, %24, p, 1, 1, 0;\n}\n"
    : "+f"(d[0]), "+f"(d[1]), "+f"(d[2]), "+f"(d[3]), "+f"(d[4]), "+f"(d[5]), "+f"(d[6]), "+f"(d[7]), "+f"(d[8]), "+f"(d[9]), "+f"(d[10]), "+f"(d[11]), "+f"(d[12]), "+f"(d[13]), "+f"(d[14]), "+f"(d[15]), "+f"(d[16]), "+f"(d[17]), "+f"(d[18]), "+f"(d[19])
    : "r"(a0), "r"(a1), "r"(a2), "r"(a3), "l"(db));
}
__device__ __forceinline__ void wgmma_rs_n40_a(float (&d)[20], uint32_t a0, uint32_t a1, uint32_t a2, uint32_t a3, uint64_t db) {
  asm volatile("{\n.reg .pred p;\nsetp.ne.b32 p, 1, 0;\nwgmma.mma_async.sync.aligned.m64n40k16.f32.bf16.bf16 {%0,%1,%2,%3,%4,%5,%6,%7,%8,%9,%10,%11,%12,%13,%14,%15,%16,%17,%18,%19}, {%20,%21,%22,%23}, %24, p, 1, 1, 0;\n}\n"
    : "+f"(d[0]), "+f"(d[1]), "+f"(d[2]), "+f"(d[3]), "+f"(d[4]), "+f"(d[5]), "+f"(d[6]), "+f"(d[7]), "+f"(d[8]), "+f"(d[9]), "+f"(d[10]), "+f"(d[11]), "+f"(d[12]), "+f"(d[13]), "+f"(d[14]), "+f"(d[15]), "+f"(d[16]), "+f"(d[17]), "+f"(d[18]), "+f"(d[19])
    : "r"(a0), "r"(a1), "r"(a2), "r"(a3), "l"(db));
}

__device__ __forceinline__ void wgmma_rs_n128_z(float (&d)[64], uint32_t a0, uint32_t a1, uint32_t a2, uint32_t a3, uint64_t db) {
  asm volatile("{\n.reg .pred p;\nsetp.ne.b32 p, 0, 0;\nwgmma.mma_async.sync.aligned.m64n128k16.f32.bf16.bf16 {%0,%1,%2,%3,%4,%5,%6,%7,%8,%9,%10,%11,%12,%13,%14,%15,%16,%17,%18,%19,%20,%21,%22,%23,%24,%25,%26,%27,%28,%29,%30,%31,%32,%33,%34,%35,%36,%37,%38,%39,%40,%41,%42,%43,%44,%45,%46,%47,%48,%49,%50,%51,%52,%53,%54,%55,%56,%57,%58,%59,%60,%61,%62,%63}, {%64,%65,%66,%67}, %68, p, 1, 1, 1;\n}\n"
    : "+f"(d[0]), "+f"(d[1]), "+f"(d[2]), "+f"(d[3]), "+f"(d[4]), "+f"(d[5]), "+f"(d[6]), "+f"(d[7]), "+f"(d[8]), "+f"(d[9]), "+f"(d[10]), "+f"(d[11]), "+f"(d[12]), "+f"(d[13]), "+f"(d[14]), "+f"(d[15]), "+f"(d[16]), "+f"(d[17]), "+f"(d[18]), "+f"(d[19]), "+f"(d[20]), "+f"(d[21]), "+f"(d[22]), "+f"(d[23]), "+f"(d[24]), "+f"(d[25]), "+f"(d[26]), "+f"(d[27]), "+f"(d[28]), "+f"(d[29]), "+f"(d[30]), "+f"(d[31]), "+f"(d[32]), "+f"(d[33]), "+f"(d[34]), "+f"(d[35]), "+f"(d[36]), "+f"(d[37]), "+f"(d[38]), "+f"(d[39]), "+f"(d[40]), "+f"(d[41]), "+f"(d[42]), "+f"(d[43]), "+f"(d[44]), "+f"(d[45]), "+f"(d[46]), "+f"(d[47]), "+f"(d[48]), "+f"(d[49]), "+f"(d[50]), "+f"(d[51]), "+f"(d[52]), "+f"(d[53]), "+f"(d[54]), "+f"(d[55]), "+f"(d[56]), "+f"(d[57]), "+f"(d[58]), "+f"(d[59]), "+f"(d[60]), "+f"(d[61]), "+f"(d[62]), "+f"(d[63])
    : "r"(a0), "r"(a1), "r"(a2), "r"(a3), "l"(db));
}
__device__ __forceinline__ void wgmma_rs_n128_a(float (&d)[64], uint32_t a0, uint32_t a1, uint32_t a2, uint32_t a3, uint64_t db) {
  asm volatile("{\n.reg .pred p;\nsetp.ne.b32 p, 1, 0;\nwgmma.mma_async.sync.aligned.m64n128k16.f32.bf16.bf16 {%0,%1,%2,%3,%4,%5,%6,%7,%8,%9,%10,%11,%12,%13,%14,%15,%16,%17,%18,%19,%20,%21,%22,%23,%24,%25,%26,%27,%28,%29,%30,%31,%32,%33,%34,%35,%36,%37,%38,%39,%40,%41,%42,%43,%44,%45,%46,%47,%48,%49,%50,%51,%52,%53,%54,%55,%56,%57,%58,%59,%60,%61,%62,%63}, {%64,%65,%66,%67}, %68, p, 1, 1, 1;\n}\n"
    : "+f"(d[0]), "+f"(d[1]), "+f"(d[2]), "+f"(d[3]), "+f"(d[4]), "+f"(d[5]), "+f"(d[6]), "+f"(d[7]), "+f"(d[8]), "+f"(d[9]), "+f"(d[10]), "+f"(d[11]), "+f"(d[12]), "+f"(d[13]), "+f"(d[14]), "+f"(d[15]), "+f"(d[16]), "+f"(d[17]), "+f"(d[18]), "+f"(d[19]), "+f"(d[20]), "+f"(d[21]), "+f"(d[22]), "+f"(d[23]), "+f"(d[24]), "+f"(d[25]), "+f"(d[26]), "+f"(d[27]), "+f"(d[28]), "+f"(d[29]), "+f"(d[30]), "+f"(d[31]), "+f"(d[32]), "+f"(d[33]), "+f"(d[34]), "+f"(d[35]), "+f"(d[36]), "+f"(d[37]), "+f"(d[38]), "+f"(d[39]), "+f"(d[40]), "+f"(d[41]), "+f"(d[42]), "+f"(d[43]), "+f"(d[44]), "+f"(d[45]), "+f"(d[46]), "+f"(d[47]), "+f"(d[48]), "+f"(d[49]), "+f"(d[50]), "+f"(d[51]), "+f"(d[52]), "+f"(d[53]), "+f"(d[54]), "+f"(d[55]), "+f"(d[56]), "+f"(d[57]), "+f"(d[58]), "+f"(d[59]), "+f"(d[60]), "+f"(d[61]), "+f"(d[62]), "+f"(d[63])
    : "r"(a0), "r"(a1), "r"(a2), "r"(a3), "l"(db));
}

__device__ __forceinline__ void wgmma_rs_n48_z(float (&d)[24], uint32_t a0, uint32_t a1, uint32_t a2, uint32_t a3, uint64_t db) {
  asm volatile("{\n.reg .pred p;\nsetp.ne.b32 p, 0, 0;\nwgmma.mma_async.sync.aligned.m64n48k16.f32.bf16.bf16 {%0,%1,%2,%3,%4,%5,%6,%7,%8,%9,%10,%11,%12,%13,%14,%15,%16,%17,%18,%19,%20,%21,%22,%23}, {%24,%25,%26,%27}, %28, p, 1, 1, 0;\n}\n"
    : "+f"(d[0]), "+f"(d[1]), "+f"(d[2]), "+f"(d[3]), "+f"(d[4]), "+f"(d[5]), "+f"(d[6]), "+f"(d[7]), "+f"(d[8]), "+f"(d[9]), "+f"(d[10]), "+f"(d[11]), "+f"(d[12]), "+f"(d[13]), "+f"(d[14]), "+f"(d[15]), "+f"(d[16]), "+f"(d[17]), "+f"(d[18]), "+f"(d[19]), "+f"(d[20]), "+f"(d[21]), "+f"(d[22]), "+f"(d[23])
    : "r"(a0), "r"(a1), "r"(a2), "r"(a3), "l"(db));
}
__device__ __forceinline__ void wgmma_rs_n48_a(float (&d)[24], uint32_t a0, uint32_t a1, uint32_t a2, uint32_t a3, uint64_t db) {
  asm volatile("{\n.reg .pred p;\nsetp.ne.b32 p, 1, 0;\nwgmma.mma_async.sync.aligned.m64n48k16.f32.bf16.bf16 {%0,%1,%2,%3,%4,%5,%6,%7,%8,%9,%10,%11,%12,%13,%14,%15,%16,%17,%18,%19,%20,%21,%22,%23}, {%24,%25,%26,%27}, %28, p, 1, 1, 0;\n}\n"
    : "+f"(d[0]), "+f"(d[1]), "+f"(d[2]), "+f"(d[3]), "+f"(d[4]), "+f"(d[5]), "+f"(d[6]), "+f"(d[7]), "+f"(d[8]), "+f"(d[9]), "+f"(d[10]), "+f"(d[11]), "+f"(d[12]), "+f"(d[13]), "+f"(d[14]), "+f"(d[15]), "+f"(d[16]), "+f"(d[17]), "+f"(d[18]), "+f"(d[19]), "+f"(d[20]), "+f"(d[21]), "+f"(d[22]), "+f"(d[23])
    : "r"(a0), "r"(a1), "r"(a2), "r"(a3), "l"(db));
}

__device__ __forceinline__ void wgmma_ss_n32_z(float (&d)[16], uint64_t da, uint64_t db) {
  asm volatile("{\n.reg .pred p;\nsetp.ne.b32 p, 0, 0;\nwgmma.mma_async.sync.aligned.m64n32k16.f32.bf16.bf16 {%0,%1,%2,%3,%4,%5,%6,%7,%8,%9,%10,%11,%12,%13,%14,%15}, %16, %17, p, 1, 1, 1, 0;\n}\n"
    : "+f"(d[0]), "+f"(d[1]), "+f"(d[2]), "+f"(d[3]), "+f"(d[4]), "+f"(d[5]), "+f"(d[6]), "+f"(d[7]), "+f"(d[8]), "+f"(d[9]), "+f"(d[10]), "+f"(d[11]), "+f"(d[12]), "+f"(d[13]), "+f"(d[14]), "+f"(d[15])
    : "l"(da), "l"(db));
}
__device__ __forceinline__ void wgmma_ss_n32_a(float (&d)[16], uint64_t da, uint64_t db) {
  asm volatile("{\n.reg .pred p;\nsetp.ne.b32 p, 1, 0;\nwgmma.mma_async.sync.aligned.m64n32k16.f32.bf16.bf16 {%0,%1,%2,%3,%4,%5,%6,%7,%8,%9,%10,%11,%12,%13,%14,%15}, %16, %17, p, 1, 1, 1, 0;\n}\n"
    : "+f"(d[0]), "+f"(d[1]), "+f"(d[2]), "+f"(d[3]), "+f"(d[4]), "+f"(d[5]), "+f"(d[6]), "+f"(d[7]), "+f"(d[8]), "+f"(d[9]), "+f"(d[10]), "+f"(d[11]), "+f"(d[12]), "+f"(d[13]), "+f"(d[14]), "+f"(d[15])
    : "l"(da), "l"(db));
}

__device__ __forceinline__ void wgmma_ss_n40_z(float (&d)[20], uint64_t da, uint64_t db) {
  asm volatile("{\n.reg .pred p;\nsetp.ne.b32 p, 0, 0;\nwgmma.mma_async.sync.aligned.m64n40k16.f32.bf16.bf16 {%0,%1,%2,%3,%4,%5,%6,%7,%8,%9,%10,%11,%12,%13,%14,%15,%16,%17,%18,%19}, %20, %21, p, 1, 1, 1, 0;\n}\n"
    : "+f"(d[0]), "+f"(d[1]), "+f"(d[2]), "+f"(d[3]), "+f"(d[4]), "+f"(d[5]), "+f"(d[6]), "+f"(d[7]), "+f"(d[8]), "+f"(d[9]), "+f"(d[10]), "+f"(d[11]), "+f"(d[12]), "+f"(d[13]), "+f"(d[14]), "+f"(d[15]), "+f"(d[16]), "+f"(d[17]), "+f"(d[18]), "+f"(d[19])
    : "l"(da), "l"(db));
}
__device__ __forceinline__ void wgmma_ss_n40_a(float (&d)[20], uint64_t da, uint64_t db) {
  asm volatile("{\n.reg .pred p;\nsetp.ne.b32 p, 1, 0;\nwgmma.mma_async.sync.aligned.m64n40k16.f32.bf16.bf16 {%0,%1,%2,%3,%4,%5,%6,%7,%8,%9,%10,%11,%12,%13,%14,%15,%16,%17,%18,%19}, %20, %21, p, 1, 1, 1, 0;\n}\n"
    : "+f"(d[0]), "+f"(d[1]), "+f"(d[2]), "+f"(d[3]), "+f"(d[4]), "+f"(d[5]), "+f"(d[6]), "+f"(d[7]), "+f"(d[8]), "+f"(d[9]), "+f"(d[10]), "+f"(d[11]), "+f"(d[12]), "+f"(d[13]), "+f"(d[14]), "+f"(d[15]), "+f"(d[16]), "+f"(d[17]), "+f"(d[18]), "+f"(d[19])
    : "l"(da), "l"(db));
}

__device__ __forceinline__ void wgmma_rs_n56_z(float (&d)[28], uint32_t a0, uint32_t a1, uint32_t a2, uint32_t a3, uint64_t db) {
  asm volatile("{\n.reg .pred p;\nsetp.ne.b32 p, 0, 0;\nwgmma.mma_async.sync.aligned.m64n56k16.f32.bf16.bf16 {%0,%1,%2,%3,%4,%5,%6,%7,%8,%9,%10,%11,%12,%13,%14,%15,%16,%17,%18,%19,%20,%21,%22,%23,%24,%25,%26,%27}, {%28,%29,%30,%31}, %32, p, 1, 1, 0;\n}\n"
    : "+f"(d[0]), "+f"(d[1]), "+f"(d[2]), "+f"(d[3]), "+f"(d[4]), "+f"(d[5]), "+f"(d[6]), "+f"(d[7]), "+f"(d[8]), "+f"(d[9]), "+f"(d[10]), "+f"(d[11]), "+f"(d[12]), "+f"(d[13]), "+f"(d[14]), "+f"(d[15]), "+f"(d[16]), "+f"(d[17]), "+f"(d[18]), "+f"(d[19]), "+f"(d[20]), "+f"(d[21]), "+f"(d[22]), "+f"(d[23]), "+f"(d[24]), "+f"(d[25]), "+f"(d[26]), "+f"(d[27])
    : "r"(a0), "r"(a1), "r"(a2), "r"(a3), "l"(db));
}
__device__ __forceinline__ void wgmma_rs_n56_a(float (&d)[28], uint32_t a0, uint32_t a1, uint32_t a2, uint32_t a3, uint64_t db) {
  asm volatile("{\n.reg .pred p;\nsetp.ne.b32 p, 1, 0;\nwgmma.mma_async.sync.aligned.m64n56k16.f32.bf16.bf16 {%0,%1,%2,%3,%4,%5,%6,%7,%8,%9,%10,%11,%12,%13,%14,%15,%16,%17,%18,%19,%20,%21,%22,%23,%24,%25,%26,%27}, {%28,%29,%30,%31}, %32, p, 1, 1, 0;\n}\n"
    : "+f"(d[0]), "+f"(d[1]), "+f"(d[2]), "+f"(d[3]), "+f"(d[4]), "+f"(d[5]), "+f"(d[6]), "+f"(d[7]), "+f"(d[8]), "+f"(d[9]), "+f"(d[10]), "+f"(d[11]), "+f"(d[12]), "+f"(d[13]), "+f"(d[14]), "+f"(d[15]), "+f"(d[16]), "+f"(d[17]), "+f"(d[18]), "+f"(d[19]), "+f"(d[20]), "+f"(d[21]), "+f"(d[22]), "+f"(d[23]), "+f"(d[24]), "+f"(d[25]), "+f"(d[26]), "+f"(d[27])
    : "r"(a0), "r"(a1), "r"(a2), "r"(a3), "l"(db));
}

constexpr int NSM = 132;
constexpr int S0 = 0, C3 = 153600, RG = 165888;
constexpr int C1 = RG, WP = RG + 18432, TBL = RG + 47104;
constexpr int BARS = RG + 50688;
constexpr int WST = 102400;
constexpr int SMEM_BYTES = BARS + 176 * 8;
constexpr int B_XF = 0, B_CF1 = 15, B_CF3 = 16, B_WF = 17, B_P1D = 18, B_WRDY = 19, B_WFREE = 20;
constexpr int B_RF = 24, B_RE = 34, B_YF = 44, B_WCH = 59, B_RDY = 64, B_SIG = 121, B_SFREE = 128, B_WRD = 160;
constexpr int CNT_P1 = 0, CNT_P2 = 3, CNT_W = 6, CNT_DONE = 7;
#define PACE 0
#define PACE_SLACK 0
#define XWIN 15

__device__ uint4 g_xf[200 * 3 * 256 * 8];
__device__ uint4 g_wf[200 * 3 * 6 * 128];
__device__ unsigned g_cnt[8 * 32];

#define PROF(k)
#define PROFW(k)
struct Maps { CUtensorMap w, x34, x6, x28, wst, fst, fld, f2, y4, y2; };

__device__ __forceinline__ uint32_t smem_u32(const void* p) { return (uint32_t)__cvta_generic_to_shared(p); }
__device__ __forceinline__ void mbar_init(uint32_t bar, uint32_t cnt) { asm volatile("mbarrier.init.shared::cta.b64 [%0], %1;" :: "r"(bar), "r"(cnt) : "memory"); }
__device__ __forceinline__ void mbar_expect_tx(uint32_t bar, uint32_t bytes) { asm volatile("mbarrier.arrive.expect_tx.shared::cta.b64 _, [%0], %1;" :: "r"(bar), "r"(bytes) : "memory"); }
__device__ __forceinline__ void mbar_wait(uint32_t bar, uint32_t parity) {
    uint32_t ok, it = 0;
    do {
        asm volatile("{\n.reg .pred p;\nmbarrier.try_wait.parity.shared::cta.b64 p, [%1], %2;\nselp.u32 %0, 1, 0, p;\n}" : "=r"(ok) : "r"(bar), "r"(parity) : "memory");
        if (++it > (1u << 22)) break;
    } while (!ok);
}
__device__ __forceinline__ void fence_async() { asm volatile("fence.proxy.async;" ::: "memory"); }
__device__ __forceinline__ void fence_async_smem() { asm volatile("fence.proxy.async.shared::cta;" ::: "memory"); }
__device__ __forceinline__ void bulk_g2s(uint32_t dst, const void* src, uint32_t bytes, uint32_t bar) {
    asm volatile("cp.async.bulk.shared::cluster.global.mbarrier::complete_tx::bytes [%0], [%1], %2, [%3];" :: "r"(dst), "l"(src), "r"(bytes), "r"(bar) : "memory");
}
__device__ __forceinline__ void bulk_s2g(void* dst, uint32_t src, uint32_t bytes) {
    asm volatile("cp.async.bulk.global.shared::cta.bulk_group [%0], [%1], %2;" :: "l"(dst), "r"(src), "r"(bytes) : "memory");
}
__device__ __forceinline__ void tma_ld3(uint32_t dst, const CUtensorMap* m, int c0, int c1, int c2, uint32_t bar) {
    asm volatile("cp.async.bulk.tensor.3d.shared::cluster.global.mbarrier::complete_tx::bytes [%0], [%1, {%3, %4, %5}], [%2];"
                 :: "r"(dst), "l"(m), "r"(bar), "r"(c0), "r"(c1), "r"(c2) : "memory");
}
__device__ __forceinline__ void tma_st3(const CUtensorMap* m, uint32_t src, int c0, int c1, int c2) {
    asm volatile("cp.async.bulk.tensor.3d.global.shared::cta.bulk_group [%0, {%2, %3, %4}], [%1];"
                 :: "l"(m), "r"(src), "r"(c0), "r"(c1), "r"(c2) : "memory");
}
__device__ __forceinline__ void bulk_commit() { asm volatile("cp.async.bulk.commit_group;" ::: "memory"); }
__device__ __forceinline__ void bulk_wait0() { asm volatile("cp.async.bulk.wait_group 0;" ::: "memory"); }
__device__ __forceinline__ void wg_fence() { asm volatile("wgmma.fence.sync.aligned;" ::: "memory"); }
__device__ __forceinline__ void wg_commit() { asm volatile("wgmma.commit_group.sync.aligned;" ::: "memory"); }
template <int N> __device__ __forceinline__ void wg_wait() { asm volatile("wgmma.wait_group.sync.aligned %0;" :: "n"(N) : "memory"); }
template <int N> __device__ __forceinline__ void reg_fence(float (&d)[N]) {
#pragma unroll
    for (int i = 0; i < N; i++) asm volatile("" : "+f"(d[i]) :: "memory");
}
template <int N, int O, int M> __device__ __forceinline__ float (&sub(float (&d)[M]))[N] { return *reinterpret_cast<float (*)[N]>(&d[O]); }
template <int N> __device__ __forceinline__ void zero(float (&d)[N]) {
#pragma unroll
    for (int i = 0; i < N; i++) d[i] = 0.f;
}
__device__ __forceinline__ uint32_t pack2(float lo, float hi) {
    uint32_t r; asm("cvt.rn.bf16x2.f32 %0, %1, %2;" : "=r"(r) : "f"(hi), "f"(lo)); return r;
}
__device__ __forceinline__ void stm4(uint32_t a, uint32_t r0, uint32_t r1, uint32_t r2, uint32_t r3) {
    asm volatile("stmatrix.sync.aligned.m8n8.x4.trans.shared.b16 [%0], {%1,%2,%3,%4};" :: "r"(a), "r"(r0), "r"(r1), "r"(r2), "r"(r3) : "memory");
}
__device__ __forceinline__ void stm2(uint32_t a, uint32_t r0, uint32_t r1) {
    asm volatile("stmatrix.sync.aligned.m8n8.x2.trans.shared.b16 [%0], {%1,%2};" :: "r"(a), "r"(r0), "r"(r1) : "memory");
}
__device__ __forceinline__ void stm1(uint32_t a, uint32_t r0) {
    asm volatile("stmatrix.sync.aligned.m8n8.x1.trans.shared.b16 [%0], {%1};" :: "r"(a), "r"(r0) : "memory");
}
struct Desc {
    uint32_t lo, hi;
    __device__ __forceinline__ operator uint64_t() const { return ((uint64_t)hi << 32) | lo; }
    __device__ __forceinline__ Desc operator+(uint32_t o) const { return Desc{lo + o, hi}; }
    __device__ __forceinline__ Desc operator^(uint32_t o) const { return Desc{lo ^ o, hi}; }
};
__device__ __forceinline__ Desc mkdesc(uint32_t addr, uint32_t lbo, uint32_t sbo, uint32_t swz) {
    return Desc{((addr & 0x3FFFF) >> 4) | ((lbo >> 4) << 16), (sbo >> 4) | (swz << 30)};
}
__device__ __forceinline__ void cnt_add(int i) { asm volatile("red.release.gpu.global.add.u32 [%0], 1;" :: "l"(&g_cnt[i * 32]) : "memory"); }
__device__ __forceinline__ void cnt_wait(int i, unsigned target) {
    unsigned v, it = 0;
    while (true) {
        asm volatile("ld.acquire.gpu.global.u32 %0, [%1];" : "=r"(v) : "l"(&g_cnt[i * 32]) : "memory");
        if (v >= target) break;
        if (++it > (1u << 22)) break;
        __nanosleep(32);
    }
}

__device__ __forceinline__ void mbar_arrive(uint32_t bar) { asm volatile("mbarrier.arrive.shared::cta.b64 _, [%0];" :: "r"(bar) : "memory"); }
__device__ __forceinline__ bool mbar_test(uint32_t bar, uint32_t parity) {
    uint32_t ok;
    asm volatile("{\n.reg .pred p;\nmbarrier.test_wait.parity.shared::cta.b64 p, [%1], %2;\nselp.u32 %0, 1, 0, p;\n}" : "=r"(ok) : "r"(bar), "r"(parity) : "memory");
    return ok;
}
__device__ __forceinline__ void warp_arrive(uint32_t bar) { __syncwarp(); if ((threadIdx.x & 31) == 0) mbar_arrive(bar); }
__device__ __forceinline__ void wg_bar(int id) { asm volatile("bar.sync %0, 128;" :: "r"(id) : "memory"); }
template <int N> __device__ __forceinline__ void bulk_wait() { asm volatile("cp.async.bulk.wait_group %0;" :: "n"(N) : "memory"); }
template <int N> __device__ __forceinline__ void bulk_wait_read() { asm volatile("cp.async.bulk.wait_group.read %0;" :: "n"(N) : "memory"); }
__device__ __forceinline__ uint32_t cos_bits(int k) {
    if (k > 20) k = 40 - k;
    const bool neg = k > 10;
    if (neg) k = 20 - k;
    const unsigned long long pk = k < 4 ? COS_PK0 : k < 8 ? COS_PK1 : COS_PK2;
    return (uint32_t)((pk >> (16 * (k & 3))) & 0xffff) ^ (neg ? 0x8000u : 0u);
}

__device__ __forceinline__ void task_w(int wg, int k, uint32_t sb) {
    const int tid = threadIdx.x & 127, w = tid >> 5, lane = tid & 31, q = lane & 3;
    const int tb = 14 * k, t1 = min(tb + 14, 1800), cb0 = tb / 25;
    float acc[64];
    zero(acc);
    int cnt, at = 0;
#pragma unroll 1
    for (int t = tb; t < t1; t += cnt, at++) {
        const int cb = t / 25, oc = t - 25 * cb;
        cnt = min(min(4, 25 - oc), t1 - t);
        if ((at ? 2 - (at & 1) : 0) != wg) continue;
        const Desc dB = mkdesc(sb + WP + (cb - cb0) * 14336, 3584, 512, 2);
        const int phi = 8 * (oc + w) + (lane >> 2), f = phi / 20, ca = (2 * f + 1) * 4, cbb = (phi - 20 * f) * 8;
        uint32_t a[4][4];
#pragma unroll
        for (int j = 0; j < 3; j++)
#pragma unroll
            for (int h = 0; h < 2; h++) {
                uint32_t v[2];
#pragma unroll
                for (int e = 0; e < 2; e++) {
                    const int tap = 16 * j + 8 * h + 2 * q + e, kh = (tap * 37) >> 8, kw = tap - 7 * kh;
                    asm volatile("ld.shared.u32 %0, [%1];" : "=r"(v[e]) : "r"(sb + TBL + ca * kh + cbb * kw));
                }
                a[j][2 * h] = __byte_perm(v[0], v[1], 0x5410);
                a[j][2 * h + 1] = __byte_perm(v[0], v[1], 0x7632);
            }
        {
            uint32_t v;
            asm volatile("ld.shared.u32 %0, [%1];" : "=r"(v) : "r"(sb + TBL + (ca + cbb) * 6));
            if (q) v = 0;
            a[3][0] = 0; a[3][1] = 0; a[3][2] = v & 0xffff; a[3][3] = v >> 16;
        }
        if (at == 0 && threadIdx.x == 0) PROF(124);
        mbar_wait(sb + BARS + 8 * B_WF, 0);
        if (at) mbar_wait(sb + BARS + 8 * (B_WCH + at - 1), 0);
        if (at == 0 && threadIdx.x == 0) PROF(125);
        wg_fence();
        wgmma_rs_n128_z(acc, a[0][0], a[0][1], a[0][2], a[0][3], dB);
        wgmma_rs_n128_a(acc, a[1][0], a[1][1], a[1][2], a[1][3], dB + (uint32_t)(16 * 64 >> 4));
        wgmma_rs_n128_a(acc, a[2][0], a[2][1], a[2][2], a[2][3], dB + (uint32_t)(32 * 64 >> 4));
        wgmma_rs_n128_a(acc, a[3][0], a[3][1], a[3][2], a[3][3], dB + (uint32_t)(40 * 64 >> 4));
        wg_commit();
        wg_wait<0>();
        reg_fence(acc);
        if (lane == 0) mbar_arrive(sb + BARS + 8 * (B_WCH + at));
        if (w < cnt) {
            const uint32_t dst = sb + WST + (t - tb + w) * 4096 + (lane >> 2) * 512 + q * 16;
#pragma unroll
            for (int j = 0; j < 4; j++)
#pragma unroll
                for (int e = 0; e < 2; e++)
                    asm volatile("st.shared.v4.u32 [%0], {%1,%2,%3,%4};" :: "r"(dst + j * 128 + e * 64),
                                 "r"(pack2(acc[4 * j + e], acc[16 + 4 * j + e])), "r"(pack2(acc[4 * j + 2 + e], acc[16 + 4 * j + 2 + e])),
                                 "r"(pack2(acc[32 + 4 * j + e], acc[48 + 4 * j + e])), "r"(pack2(acc[32 + 4 * j + 2 + e], acc[48 + 4 * j + 2 + e])) : "memory");
            fence_async_smem();
            warp_arrive(sb + BARS + 8 * (B_WRD + t - tb + w));
        }
    }
}

__device__ __forceinline__ void task_p1(int wg, int pair, uint32_t sb) {
    const int tid = threadIdx.x & 127, w = tid >> 5, lane = tid & 31;
    const uint32_t buf = sb + wg * 51200, bars = sb + BARS;
    uint32_t fr[5][10][2];
    float A[40], d[20];
    zero(A);
    {
        const Desc dA = mkdesc(buf, 3584, 512, 2), dB = mkdesc(sb + C1, 128, 256, 0);
        auto issue = [&](int g, float (&d)[40]) {
            mbar_wait(bars + 8 * (B_XF + wg * 5 + g), 0);
            wg_fence();
            wgmma_ss_n80_z(d, dA + (uint32_t)(g * 8704 >> 4), dB);
#pragma unroll
            for (int j = 1; j < 5; j++) wgmma_ss_n80_a(d, dA + (uint32_t)((g * 8704 + j * 1024) >> 4), dB + (uint32_t)(j * 2560 >> 4));
            wg_commit();
        };
        auto pack = [&](int g, float (&d)[40]) {
            reg_fence(d);
#pragma unroll
            for (int f = 0; f < 10; f++) {
                fr[g][f][0] = pack2(d[4 * f], d[4 * f + 1]);
                fr[g][f][1] = pack2(d[4 * f + 2], d[4 * f + 3]);
            }
        };
        mbar_wait(bars + 8 * B_CF1, 0);
#pragma unroll
        for (int g = 0; g < 4; g++) { issue(g, A); if (g == 0) PROFW(8 + wg * 8 + 1); wg_wait<0>(); pack(g, A); }
        zero(d);
        mbar_wait(bars + 8 * (B_XF + wg * 5 + 4), 0);
#pragma unroll
        for (int h = 0; h < 2; h++) {
            wg_fence();
            wgmma_ss_n40_z(d, dA + (uint32_t)(4 * 8704 >> 4), dB + (uint32_t)(h * 1280 >> 4));
#pragma unroll
            for (int j = 1; j < 5; j++) wgmma_ss_n40_a(d, dA + (uint32_t)((4 * 8704 + j * 1024) >> 4), dB + (uint32_t)((j * 2560 + h * 1280) >> 4));
            wg_commit(); wg_wait<0>(); reg_fence(d);
#pragma unroll
            for (int f = 0; f < 5; f++) { fr[4][5 * h + f][0] = pack2(d[4 * f], d[4 * f + 1]); fr[4][5 * h + f][1] = pack2(d[4 * f + 2], d[4 * f + 3]); }
        }
    }
    wg_bar(1 + wg);
    PROFW(8 + wg * 8 + 2);
    {
        const Desc dB = mkdesc(sb + C1 + 12800, 128, 256, 0);
        const int i = lane & 7, mi = lane >> 3, th = w >> 1, tz = (2 * pair + th) & 3;
        const uint32_t soff = buf + th * 2560 + (mi >> 1) * 512 + (i >> 1) * 128 + (i & 1) * 64 + (((2 * (w & 1) + (mi & 1)) ^ tz ^ (i >> 1)) << 4);
        auto issue = [&](int f, float (&d)[20]) {
            wg_fence();
            wgmma_rs_n40_z(d, fr[0][f][0], fr[0][f][1], fr[1][f][0], fr[1][f][1], dB);
            wgmma_rs_n40_a(d, fr[2][f][0], fr[2][f][1], fr[3][f][0], fr[3][f][1], dB + (uint32_t)(1280 >> 4));
            wgmma_rs_n40_a(d, fr[4][f % 5][0], fr[4][f % 5][1], fr[4][f % 5 + 5][0], fr[4][f % 5 + 5][1], dB + (uint32_t)((2560 + (f / 5) * 1280) >> 4));
            wg_commit();
        };
#pragma unroll
        for (int f = 0; f < 10; f++) {
                        issue(f, d); wg_wait<0>(); reg_fence(d);
            const uint32_t a = soff + f * 5120;
            stm4(a, pack2(d[0], d[1]), pack2(d[2], d[3]), pack2(d[4], d[5]), pack2(d[6], d[7]));
            stm4(a + 1024, pack2(d[8], d[9]), pack2(d[10], d[11]), pack2(d[12], d[13]), pack2(d[14], d[15]));
            stm2(a + 2048, pack2(d[16], d[17]), pack2(d[18], d[19]));
            if (f & 1) { fence_async_smem(); warp_arrive(bars + 8 * (B_RDY + wg * 5 + (f >> 1))); }
        }
    }
}

__device__ __forceinline__ void task_p2(int wg, int k, uint32_t sb) {
    const int tid = threadIdx.x & 127, w = tid >> 5, lane = tid & 31;
    const uint32_t bars = sb + BARS;
    const int phiA = 3 * (k >> 1) + 2 * (k & 1), phiB = 3 * (k >> 1) + 1, phiE = 198 + ((k >> 1) & 1);
    const int gE = k >= 120 ? (k - 120) >> 2 : -1;
    const uint4* gw = g_wf + wg * 6 * 128 + (lane & 3) * 32 + w * 8 + ((lane >> 2) & 1) * 4 + (lane >> 3);
    uint4 wA[6], wB[6];
    auto ldw = [&](uint4 (&a)[6], int phi) {
#pragma unroll
        for (int s = 0; s < 6; s++) a[s] = __ldcg(gw + phi * 18 * 128 + s * 128);
    };
    auto fixw = [&](uint4 (&a)[6], int phi) {
        if (phi & 1) {
#pragma unroll
            for (int s = 0; s < 6; s++) a[s] = make_uint4(a[s].z, a[s].w, a[s].x, a[s].y);
        }
    };
    mbar_wait(bars + 8 * B_WRDY, 0);
    ldw(wA, phiA); ldw(wB, phiB);
    const int i = lane & 7, mi = lane >> 3;
    const uint32_t soff = sb + S0 + wg * 5632 + mi * 512 + (i >> 1) * 128 + (i & 1) * 64;
    const int xo = w ^ (i >> 1);
    float p0[24], p1[20];
    zero(p0); zero(p1);
    auto issue0 = [&](int n, int slot, const uint4 (&a)[6], int z) {
        const Desc d0 = mkdesc(sb + RG + slot * 16896 + ((z >> 1) << 5), 16, 512, 2), d1 = d0 ^ 2u;
        mbar_wait(bars + 8 * (B_RF + n), 0);
        wg_fence();
        wgmma_rs_n48_z(p0, a[0].x, a[0].y, a[0].z, a[0].w, d0);
        wgmma_rs_n48_a(p0, a[1].x, a[1].y, a[1].z, a[1].w, d1);
#pragma unroll
        for (int c = 1; c < 3; c++) {
            wgmma_rs_n48_a(p0, a[2 * c].x, a[2 * c].y, a[2 * c].z, a[2 * c].w, d0 + (uint32_t)(c * 5632 >> 4));
            wgmma_rs_n48_a(p0, a[2 * c + 1].x, a[2 * c + 1].y, a[2 * c + 1].z, a[2 * c + 1].w, d1 + (uint32_t)(c * 5632 >> 4));
        }
        wg_commit();
    };
    auto issue1 = [&](int slot, const uint4 (&a)[6], int z) {
        const Desc d0 = mkdesc(sb + RG + slot * 16896 + 3072 + ((z >> 1) << 5), 16, 512, 2), d1 = d0 ^ 2u;
        wg_fence();
        wgmma_rs_n40_z(p1, a[0].x, a[0].y, a[0].z, a[0].w, d0);
        wgmma_rs_n40_a(p1, a[1].x, a[1].y, a[1].z, a[1].w, d1);
#pragma unroll
        for (int c = 1; c < 3; c++) {
            wgmma_rs_n40_a(p1, a[2 * c].x, a[2 * c].y, a[2 * c].z, a[2 * c].w, d0 + (uint32_t)(c * 5632 >> 4));
            wgmma_rs_n40_a(p1, a[2 * c + 1].x, a[2 * c + 1].y, a[2 * c + 1].z, a[2 * c + 1].w, d1 + (uint32_t)(c * 5632 >> 4));
        }
        wg_commit();
    };
    auto epi0 = [&](int n, int slot, int z) {
        reg_fence(p0);
        uint32_t p[6];
#pragma unroll
        for (int j = 0; j < 6; j++) p[j] = pack2(p0[4 * j] - p0[4 * j + 3], p0[4 * j + 2] + p0[4 * j + 1]);
        if (n >= 3) mbar_wait(bars + 8 * (B_SFREE + (n - 3) * 3 + wg), 0);
        const uint32_t a = soff + slot * 16896 + ((xo ^ z) << 4);
        stm4(a, p[0], p[1], p[2], p[3]);
        stm2(a + 2048, p[4], p[5]);
    };
    auto epi1 = [&](int n, int slot, int z) {
        reg_fence(p1);
        if (lane == 0) mbar_arrive(bars + 8 * (B_RE + n));
        uint32_t p[5];
#pragma unroll
        for (int j = 0; j < 5; j++) p[j] = pack2(p1[4 * j] - p1[4 * j + 3], p1[4 * j + 2] + p1[4 * j + 1]);
        const uint32_t a = soff + slot * 16896 + ((xo ^ z) << 4);
        stm4(a + 3072, p[0], p[1], p[2], p[3]);
        stm1(a + 5120, p[4]);
        fence_async_smem();
        warp_arrive(bars + 8 * (B_RDY + 15 + n * 3 + wg));
    };
    const int zA = (phiA % 20) & 3, zB = (phiB % 20) & 3, zE = (phiE % 20) & 3;
    int n = 0, s0 = 0, s1 = 1, s2 = 2;
    uint4 wE[6];
    if (gE >= 0) { ldw(wE, phiE); fixw(wE, phiE); }
    fixw(wA, phiA); fixw(wB, phiB);
#pragma unroll 1
    for (int g = 0; g < 3; g++) {
        issue0(n, s0, wA, zA);
        issue1(s0, wA, zA);         wg_wait<1>(); epi0(n, s0, zA);
        issue0(n + 1, s1, wB, zB);  wg_wait<1>(); epi1(n, s0, zA);
        PROFW(40 + wg * 8 + g * 2);
        issue1(s1, wB, zB);         wg_wait<1>(); epi0(n + 1, s1, zB);
        issue0(n + 2, s2, wA, zA);  wg_wait<1>(); epi1(n + 1, s1, zB);
        issue1(s2, wA, zA);         wg_wait<1>(); epi0(n + 2, s2, zA);
        wg_wait<0>(); epi1(n + 2, s2, zA);
        n += 3;
        if (g == gE) {
            issue0(n, s0, wE, zE);
            issue1(s0, wE, zE);     wg_wait<1>(); epi0(n, s0, zE);
            wg_wait<0>(); epi1(n, s0, zE);
            n++; s0 = 1; s1 = 2; s2 = 0;
        }
        PROFW(40 + wg * 8 + g * 2 + 1);
    }
}

__device__ __forceinline__ void task_p3(int wg, int pair, uint32_t sb) {
    const int tid = threadIdx.x & 127, w = tid >> 5, lane = tid & 31;
    const uint32_t buf = sb + (wg == 2 ? 0 : (wg + 1) * 51200), bars = sb + BARS;
    uint32_t fr[10][4][2];
    float A[32];
    zero(A);
    {
        const Desc dA = mkdesc(buf, 5120, 512, 2), dB = mkdesc(sb + C3, 128, 256, 0);
        float (&d0)[16] = sub<16, 0>(A);
        float (&d1)[16] = sub<16, 16>(A);
        mbar_wait(bars + 8 * B_CF3, 0);
#pragma unroll
        for (int j = 0; j < 5; j++) {
            mbar_wait(bars + 8 * (B_YF + wg * 5 + j), 0);
            if (j == 0) PROFW(64 + wg * 8 + 1);
            wg_fence();
            wgmma_ss_n32_z(d0, dA + (uint32_t)(j * 10240 >> 4), dB);
            wgmma_ss_n32_z(d1, dA + (uint32_t)((j * 10240 + 2560) >> 4), dB);
            wgmma_ss_n32_a(d0, dA + (uint32_t)((j * 10240 + 1024) >> 4), dB + (uint32_t)(1024 >> 4));
            wgmma_ss_n32_a(d1, dA + (uint32_t)((j * 10240 + 2560 + 1024) >> 4), dB + (uint32_t)(1024 >> 4));
            wgmma_ss_n32_a(d0, dA + (uint32_t)((j * 10240 + 1536) >> 4), dB + (uint32_t)(2048 >> 4));
            wgmma_ss_n32_a(d1, dA + (uint32_t)((j * 10240 + 2560 + 1536) >> 4), dB + (uint32_t)(2048 >> 4));
            wg_commit(); wg_wait<0>(); reg_fence(A);
#pragma unroll
            for (int e = 0; e < 2; e++)
#pragma unroll
                for (int g = 0; g < 4; g++) {
                    fr[2 * j + e][g][0] = pack2(A[16 * e + 4 * g], A[16 * e + 4 * g + 1]);
                    fr[2 * j + e][g][1] = pack2(A[16 * e + 4 * g + 2], A[16 * e + 4 * g + 3]);
                }
        }
    }
    wg_bar(1 + wg);
    PROFW(64 + wg * 8 + 2);
    {
        const Desc dB = mkdesc(sb + C3 + 3072, 128, 256, 0);
        const int i = lane & 7, mi = lane >> 3, th = w >> 1, tz = (2 * pair + th) & 3;
        const int oct = (2 * (w & 1) + (mi & 1)) ^ tz;
        const uint32_t soff = buf + th * 3584 + (mi >> 1) * 512 + i * 64 + ((oct ^ (i >> 1)) << 4);
        float d[28]; zero(d);
        auto issue = [&](int g, float (&d)[28]) {
            wg_fence();
            wgmma_rs_n56_z(d, fr[0][g][0], fr[0][g][1], fr[1][g][0], fr[1][g][1], dB);
#pragma unroll
            for (int s = 1; s < 5; s++) wgmma_rs_n56_a(d, fr[2 * s][g][0], fr[2 * s][g][1], fr[2 * s + 1][g][0], fr[2 * s + 1][g][1], dB + (uint32_t)(s * 1792 >> 4));
            wg_commit();
        };
#pragma unroll
        for (int gg = 1; gg < 5; gg++) {
            const int g = gg & 3;
                        issue(g, d); wg_wait<0>(); reg_fence(d);
            if (g) {
                const uint32_t a = soff + g * 7168;
#pragma unroll
                for (int j = 0; j < 3; j++)
                    stm4(a + j * 1024, pack2(d[8 * j], d[8 * j + 1]), pack2(d[8 * j + 2], d[8 * j + 3]), pack2(d[8 * j + 4], d[8 * j + 5]), pack2(d[8 * j + 6], d[8 * j + 7]));
                stm2(a + 3072, pack2(d[24], d[25]), pack2(d[26], d[27]));
            } else {
#pragma unroll
                for (int j = 0; j < 4; j++) {
                    const int row = th * 14 + 4 * j + 2 * (mi >> 1) + (i >> 2);
                    const uint32_t a = (i & 2) ? buf + row * 128 + (i & 1) * 64 + ((oct ^ (row & 3)) << 4) : buf + 4096 + lane * 16;
                    if (j < 3) stm4(a, pack2(d[8 * j], d[8 * j + 1]), pack2(d[8 * j + 2], d[8 * j + 3]), pack2(d[8 * j + 4], d[8 * j + 5]), pack2(d[8 * j + 6], d[8 * j + 7]));
                    else stm2(a, pack2(d[24], d[25]), pack2(d[26], d[27]));
                }
            }
            fence_async_smem();
            warp_arrive(bars + 8 * (B_RDY + 45 + wg * 4 + gg - 1));
        }
    }
}

__device__ __forceinline__ void p2_unit(int k, int g, int j, int& phi, int& h) {
    phi = j == 3 ? 198 + ((k >> 1) & 1) : 3 * (k >> 1) + (j == 1 ? 1 : 2 * (k & 1));
    h = (j & 1) ? (k & 1) : (j >> 1);
}

__device__ __forceinline__ void load_x(int k, int u, uint32_t sb, const Maps& mp) {
    const uint32_t bars = sb + BARS;
    const int unit = u * NSM + k, pair = unit / 3, chunk = unit - 3 * pair, tp = pair >> 4, tx = pair & 15;
#pragma unroll 1
    for (int g = 0; g < 5; g++) {
        const int bi = u * 5 + g;
        if (bi >= XWIN) mbar_wait(bars + 8 * (B_XF + bi - XWIN), 0);
        int col = 14 * tx - 8 + 4 * g; if (col < 0) col += 224;
        const uint32_t bar = bars + 8 * (B_XF + bi), dst = sb + u * 51200 + g * 8704;
        mbar_expect_tx(bar, 8704);
        if (tp) tma_ld3(dst, &mp.x34, 32 * chunk, col, 28 * tp - 6, bar);
        else { tma_ld3(dst, &mp.x6, 32 * chunk, col, 218, bar); tma_ld3(dst + 1536, &mp.x28, 32 * chunk, col, 0, bar); }
        if (bi == 0) { mbar_expect_tx(bars + 8 * B_CF1, 17920); bulk_g2s(sb + C1, TAB_P1, 17920, bars + 8 * B_CF1); }
    }
}

__device__ __forceinline__ void load_first(int k, uint32_t sb, const Maps& mp) {
    const uint32_t bars = sb + BARS;
    PROF(122);
    if (k < 129) {
        const int cb0 = 14 * k / 25, cb1 = min((14 * k + 13) / 25, 71);
        mbar_expect_tx(bars + 8 * B_WF, (cb1 - cb0 + 1) * 14336);
#pragma unroll 1
        for (int cb = cb0; cb <= cb1; cb++) {
            const int b = cb / 24, i0 = 16 * ((cb >> 2) - 6 * b) + 2 * (cb & 3);
            tma_ld3(sb + WP + (cb - cb0) * 14336, &mp.w, 32 * b, 0, i0, bars + 8 * B_WF);
            tma_ld3(sb + WP + (cb - cb0) * 14336 + 7168, &mp.w, 32 * b, 0, i0 + 8, bars + 8 * B_WF);
        }
    }
    load_x(k, 0, sb, mp);
    PROF(123);
}

__device__ __forceinline__ void load_warp(int k, uint32_t sb, const Maps& mp) {
    const uint32_t bars = sb + BARS;
    load_x(k, 1, sb, mp);
    mbar_wait(bars + 8 * B_WFREE, 0);
    if (k < 120) load_x(k, 2, sb, mp);
    mbar_expect_tx(bars + 8 * B_CF3, 12032); bulk_g2s(sb + C3, TAB_P3, 12032, bars + 8 * B_CF3);
    PROF(1);
    cnt_wait(CNT_W, NSM);
    mbar_arrive(bars + 8 * B_WRDY);
    PROF(2);
    mbar_wait(bars + 8 * B_P1D, 0);
    const int gE = k >= 120 ? (k - 120) >> 2 : -1;
    int n = 0, slot = 0;
#pragma unroll 1
    for (int g = 0; g < 3; g++) {
        cnt_wait(CNT_P1 + g, g == 2 ? 120 : NSM);
        PROF(3 + g);
        const int nj = g == gE ? 4 : 3;
#pragma unroll 1
        for (int j = 0; j < nj; j++) {
            int phi, h; p2_unit(k, g, j, phi, h);
            if (n >= 3) mbar_wait(bars + 8 * (B_RE + n - 3), 0);
            mbar_expect_tx(bars + 8 * (B_RF + n), 16896);
            tma_ld3(sb + RG + slot * 16896, &mp.f2, 0, 88 * g + 44 * h, 3 * phi, bars + 8 * (B_RF + n));
            n++; slot = slot == 2 ? 0 : slot + 1;
        }
    }
}

__device__ __forceinline__ void load3_warp(int k, uint32_t sb, const Maps& mp) {
    const uint32_t bars = sb + BARS;
    const int nu = k < 120 ? 3 : 2;
    mbar_wait(bars + 8 * B_P1D, 0);
#pragma unroll 1
    for (int u = 0; u < nu; u++) {
        const int unit = u * NSM + k, pair = unit / 3, chunk = unit - 3 * pair;
        const uint32_t buf = sb + (u == 2 ? 0 : (u + 1) * 51200);
        cnt_wait(CNT_P2 + u, NSM);
        PROF(64 + u * 8);
#pragma unroll 1
        for (int j = 0; j < 5; j++) {
            const uint32_t bar = bars + 8 * (B_YF + u * 5 + j);
            mbar_expect_tx(bar, 10240);
            tma_ld3(buf + j * 10240, &mp.fld, 0, j * 40, chunk * 256 + 2 * pair, bar);
        }
    }
}

__device__ __forceinline__ void store_warp(int k, uint32_t sb, const Maps& mp) {
    const uint32_t bars = sb + BARS;
    const int nu = k < 120 ? 3 : 2;
    uint32_t pa = 0, pb = 0;
    auto flush = [&]() { if (pa) mbar_arrive(pa); if (pb) mbar_arrive(pb); pa = pb = 0; };
    auto pre = [&](int rdy) {
        const uint32_t bar = bars + 8 * (B_RDY + rdy);
        if (!mbar_test(bar, 0)) { bulk_wait_read<0>(); flush(); mbar_wait(bar, 0); }
    };
    auto post = [&](uint32_t fr) { bulk_commit(); bulk_wait_read<1>(); flush(); pa = fr; };
    auto pace = [&](uint32_t bytes) {
    };
    {
        int cb = 14 * k / 25, oc = 14 * k - 25 * cb;
#pragma unroll 1
        for (int i = 0; i < 14 && cb < 72; i++) {
            pre(B_WRD - B_RDY + i);
            if (i == 0) PROF(6);
            pace(4096);
            tma_st3(&mp.wst, sb + WST + i * 4096, 0, 8 * oc, cb);
            post(0);
            if (++oc == 25) { oc = 0; cb++; }
        }
        pa = bars + 8 * B_WFREE; pb = bars + 8 * (B_SIG + CNT_W);
    }
#pragma unroll 1
    for (int u = 0; u < nu; u++) {
        const int unit = u * NSM + k, pair = unit / 3, chunk = unit - 3 * pair;
#pragma unroll 1
        for (int f = 0; f < 10; f++) {
            pre(u * 5 + (f >> 1));
            if (f == 0) PROF(104 + u);
            pace(5120);
            tma_st3(&mp.fst, sb + u * 51200 + f * 5120, 0, f * 20, chunk * 256 + 2 * pair);
            post(0);
        }
        pb = bars + 8 * (B_SIG + CNT_P1 + u);
    }
    const int gE = k >= 120 ? (k - 120) >> 2 : -1;
    int n = 0, slot = 0;
#pragma unroll 1
    for (int g = 0; g < 3; g++) {
        const int nj = g == gE ? 4 : 3;
#pragma unroll 1
        for (int j = 0; j < nj; j++) {
            int phi, h; p2_unit(k, g, j, phi, h);
            char* gx = reinterpret_cast<char*>(g_xf) + ((size_t)phi * 768 + 88 * g + 44 * h) * 128;
            const uint32_t bytes = (g == 2 && h) ? 36 * 128 : 44 * 128;
#pragma unroll 1
            for (int b = 0; b < 3; b++) {
                pre(15 + n * 3 + b);
                if (j == 0 && b == 0) PROF(107 + g);
                pace(bytes);
                bulk_s2g(gx + b * 32768, sb + S0 + slot * 16896 + b * 5632, bytes);
                post(bars + 8 * (B_SFREE + n * 3 + b));
            }
            n++; slot = slot == 2 ? 0 : slot + 1;
        }
        pb = bars + 8 * (B_SIG + CNT_P2 + g);
    }
#pragma unroll 1
    for (int u = 0; u < nu; u++) {
        const int unit = u * NSM + k, pair = unit / 3, chunk = unit - 3 * pair, tp = pair >> 4, tx = pair & 15;
        const uint32_t buf = sb + (u == 2 ? 0 : (u + 1) * 51200);
#pragma unroll 1
        for (int gg = 1; gg < 5; gg++) {
            pre(45 + u * 4 + gg - 1);
            if (gg == 1) PROF(110 + u);
            pace(gg < 4 ? 7168 : 3584);
            if (gg < 4) tma_st3(&mp.y4, buf + gg * 7168, 32 * chunk, 14 * tx - 4 + 4 * gg, 28 * tp);
            else tma_st3(&mp.y2, buf, 32 * chunk, tx == 0 ? 222 : 14 * tx - 2, 28 * tp);
            post(0);
        }
    }
    bulk_wait_read<0>();
    PROF(113);
}

__device__ __forceinline__ void signal_warp(int k, uint32_t sb) {
    const uint32_t bars = sb + BARS;
#pragma unroll 1
    for (int cc = 0; cc < 7; cc++) {
        const int c = cc ? cc - 1 : CNT_W;
        if (c == CNT_P1 + 2 && k >= 120) continue;
        mbar_wait(bars + 8 * (B_SIG + c), 0);
        PROF(114 + c);
        fence_async();
        asm volatile("red.relaxed.gpu.global.add.u32 [%0], 1;" :: "l"(&g_cnt[c * 32]) : "memory");
        PROF(96 + c);
    }
    mbar_wait(bars + 8 * (B_YF + (k < 120 ? 14 : 9)), 0);
    unsigned old;
    asm volatile("atom.add.acq_rel.gpu.global.u32 %0, [%1], 1;" : "=r"(old) : "l"(&g_cnt[CNT_DONE * 32]) : "memory");
    if (old == NSM - 1) {
#pragma unroll
        for (int c = 0; c < 8; c++) g_cnt[c * 32] = 0;
    }
}

__global__ void __launch_bounds__(512, 1) fftconv_kernel(const __grid_constant__ Maps mp) {
    extern __shared__ __align__(1024) uint8_t smem[];
    const uint32_t sb = smem_u32(smem);
    const int tid = threadIdx.x, wg = __shfl_sync(0xffffffffu, tid >> 7, 0), k = blockIdx.x;
    auto bar_init = [&](int i) {
        uint32_t c = 1;
        if (i == B_P1D || (i >= B_RE && i < B_RE + 10)) c = 12;
        else if (i >= B_WCH && i < B_SIG) c = 4;
        asm volatile("st.shared.v2.u32 [%0], {%1, %2};" :: "r"(sb + BARS + 8 * i), "r"((0x100000u - c) << 1), "r"((0x100000u - c) << 11) : "memory");
        fence_async_smem();
    };
    if ((tid >> 5) == 12) {
        bar_init(tid & 31);
        __syncwarp();
        asm volatile("bar.arrive 4, 512;" ::: "memory");
        if ((tid & 31) == 0) load_first(k, sb, mp);
        __syncwarp();
        asm volatile("bar.sync 5, 512;" ::: "memory");
    } else {
        if (tid >= 32 && tid < 176) bar_init(tid);
        else if (tid < 10) asm volatile("prefetch.tensormap [%0];" :: "l"(reinterpret_cast<const CUtensorMap*>(&mp) + tid) : "memory");
        if (tid < 384) {
            const int r = tid % 40;
            asm volatile("st.shared.u32 [%0], %1;" :: "r"(sb + TBL + 4 * tid), "r"(cos_bits(r) | (cos_bits(r < 30 ? r + 10 : r - 30) << 16)) : "memory");
        }
        __syncwarp();
        asm volatile("bar.arrive 5, 512;" ::: "memory");
        asm volatile("bar.sync 4, 512;" ::: "memory");
    }
    if (tid == 64) PROF(121);
    if (wg == 3) {
        asm volatile("setmaxnreg.dec.sync.aligned.u32 32;");
        if ((tid & 31) == 0) {
            const int w = (tid >> 5) & 3;
            if (w == 0) load_warp(k, sb, mp);
            else if (w == 1) store_warp(k, sb, mp);
            else if (w == 2) load3_warp(k, sb, mp);
            else signal_warp(k, sb);
        }
    } else {
        asm volatile("setmaxnreg.inc.sync.aligned.u32 160;");
        task_w(wg, k, sb);
        const int unit = wg * NSM + k;
        PROFW(8 + wg * 8);
        if (unit < 384) task_p1(wg, unit / 3, sb);
        warp_arrive(sb + BARS + 8 * B_P1D);
        PROFW(8 + wg * 8 + 3);
        task_p2(wg, k, sb);
        if (unit < 384) task_p3(wg, unit / 3, sb);
        PROFW(64 + wg * 8 + 3);
    }
}

typedef CUresult (*EncodeFn)(CUtensorMap*, CUtensorMapDataType, cuuint32_t, void*, const cuuint64_t*, const cuuint64_t*, const cuuint32_t*, const cuuint32_t*,
                             CUtensorMapInterleave, CUtensorMapSwizzle, CUtensorMapL2promotion, CUtensorMapFloatOOBfill);

static void encode3(EncodeFn fn, CUtensorMap* m, void* ptr, uint64_t d0, uint64_t d1, uint64_t d2, uint64_t s1, uint64_t s2,
                    uint32_t b0, uint32_t b1, uint32_t b2, CUtensorMapSwizzle sw) {
    cuuint64_t dims[3] = {d0, d1, d2}, strides[2] = {s1, s2};
    cuuint32_t box[3] = {b0, b1, b2}, es[3] = {1, 1, 1};
    fn(m, CU_TENSOR_MAP_DATA_TYPE_BFLOAT16, 3, ptr, dims, strides, box, es, CU_TENSOR_MAP_INTERLEAVE_NONE, sw,
       CU_TENSOR_MAP_L2_PROMOTION_NONE, CU_TENSOR_MAP_FLOAT_OOB_FILL_NONE);
}

extern "C" void kernel_launch(void* const* d_in, const int* in_sizes, int n_in, void* d_out, int out_size) {
    (void)in_sizes; (void)n_in; (void)out_size;
    void* fnp = nullptr; cudaDriverEntryPointQueryResult qr;
    cudaGetDriverEntryPoint("cuTensorMapEncodeTiled", &fnp, cudaEnableDefault, &qr);
    EncodeFn fn = (EncodeFn)fnp;
    void* xf = nullptr; cudaGetSymbolAddress(&xf, g_xf);
    void* wf = nullptr; cudaGetSymbolAddress(&wf, g_wf);
    Maps mp;
    encode3(fn, &mp.x6, d_in[0], 96, 224, 224, 192, 224 * 192, 32, 4, 6, CU_TENSOR_MAP_SWIZZLE_64B);
    encode3(fn, &mp.x34, d_in[0], 96, 224, 224, 192, 224 * 192, 32, 4, 34, CU_TENSOR_MAP_SWIZZLE_64B);
    encode3(fn, &mp.wst, wf, 256, 200, 72, 36864, 512, 256, 8, 1, CU_TENSOR_MAP_SWIZZLE_NONE);
    encode3(fn, &mp.x28, d_in[0], 96, 224, 224, 192, 224 * 192, 32, 4, 28, CU_TENSOR_MAP_SWIZZLE_64B);
    encode3(fn, &mp.w, d_in[1], 96, 49, 96, 18432, 192, 32, 56, 2, CU_TENSOR_MAP_SWIZZLE_64B);
    encode3(fn, &mp.fst, xf, 64, 200, 768, 98304, 128, 64, 20, 2, CU_TENSOR_MAP_SWIZZLE_NONE);
    encode3(fn, &mp.fld, xf, 64, 200, 768, 98304, 128, 64, 40, 2, CU_TENSOR_MAP_SWIZZLE_NONE);
    encode3(fn, &mp.f2, xf, 64, 256, 600, 128, 32768, 64, 44, 3, CU_TENSOR_MAP_SWIZZLE_NONE);
    encode3(fn, &mp.y4, d_out, 96, 224, 224, 192, 224 * 192, 32, 4, 28, CU_TENSOR_MAP_SWIZZLE_64B);
    encode3(fn, &mp.y2, d_out, 96, 224, 224, 192, 224 * 192, 32, 2, 28, CU_TENSOR_MAP_SWIZZLE_64B);
    cudaFuncSetAttribute(fftconv_kernel, cudaFuncAttributeMaxDynamicSharedMemorySize, SMEM_BYTES);
    fftconv_kernel<<<NSM, 512, SMEM_BYTES>>>(mp);
}
```

```cpp
#include <cuda_runtime.h>
#include <cuda_bf16.h>
#include <cuda.h>
#include <stdint.h>

__device__ __align__(128) const uint32_t TAB_P1[4480] = {
0x3e75,0,0x3e72,0,0x8000,0,0xbd19,0,0x3e750000,0,0x3e720000,0,0x80000000,0,0xbd190000,0,
0,0x3e75,0,0x3e72,0,0x8000,0,0xbd19,0,0x3e750000,0,0x3e720000,0,0x80000000,0,0xbd190000,
0x3e69,0,0x3e5a,0,0xbd97,0,0xbdde,0,0x3e690000,0,0x3e5a0000,0,0xbd970000,0,0xbdde0000,0,
0,0x3e69,0,0x3e5a,0,0xbd97,0,0xbdde,0,0x3e690000,0,0x3e5a0000,0,0xbd970000,0,0xbdde0000,
0x3e75,0,0x3e5a,0,0x8000,0,0xbdde,0,0x3e750000,0,0x3e5a0000,0,0x80000000,0,0xbdde0000,0,
0,0x3e75,0,0x3e5a,0,0x8000,0,0xbdde,0,0x3e750000,0,0x3e5a0000,0,0x80000000,0,0xbdde0000,
0x3e10,0,0x3d19,0,0xbe46,0,0xbe72,0,0x3e100000,0,0x3d190000,0,0xbe460000,0,0xbe720000,0,
0,0x3e10,0,0x3d19,0,0xbe46,0,0xbe72,0,0x3e100000,0,0x3d190000,0,0xbe460000,0,0xbe720000,
0x3e75,0,0x3e2d,0,0x8000,0,0xbe2d,0,0x3e750000,0,0x3e2d0000,0,0x80000000,0,0xbe2d0000,0,
0,0x3e75,0,0x3e2d,0,0x8000,0,0xbe2d,0,0x3e750000,0,0x3e2d0000,0,0x80000000,0,0xbe2d0000,
0,0,0xbe2d,0,0xbe75,0,0xbe2d,0,0,0,0xbe2d0000,0,0xbe750000,0,0xbe2d0000,0,
0,0,0,0xbe2d,0,0xbe75,0,0xbe2d,0,0,0,0xbe2d0000,0,0xbe750000,0,0xbe2d0000,
0x3e75,0,0x3dde,0,0x8000,0,0xbe5a,0,0x3e750000,0,0x3dde0000,0,0x80000000,0,0xbe5a0000,0,
0,0x3e75,0,0x3dde,0,0x8000,0,0xbe5a,0,0x3e750000,0,0x3dde0000,0,0x80000000,0,0xbe5a0000,
0xbe10,0,0xbe72,0,0xbe46,0,0x3d19,0,0xbe100000,0,0xbe720000,0,0xbe460000,0,0x3d190000,0,
0,0xbe10,0,0xbe72,0,0xbe46,0,0x3d19,0,0xbe100000,0,0xbe720000,0,0xbe460000,0,0x3d190000,
0x3e75,0,0x3d19,0,0x8000,0,0xbe72,0,0x3e750000,0,0x3d190000,0,0x80000000,0,0xbe720000,0,
0,0x3e75,0,0x3d19,0,0x8000,0,0xbe72,0,0x3e750000,0,0x3d190000,0,0x80000000,0,0xbe720000,
0xbe69,0,0xbdde,0,0xbd97,0,0x3e5a,0,0xbe690000,0,0xbdde0000,0,0xbd970000,0,0x3e5a0000,0,
0,0xbe69,0,0xbdde,0,0xbd97,0,0x3e5a,0,0xbe690000,0,0xbdde0000,0,0xbd970000,0,0x3e5a0000,
0x3e75,0,0xbd19,0,0x8000,0,0xbe72,0,0x3e750000,0,0xbd190000,0,0x80000000,0,0xbe720000,0,
0,0x3e75,0,0xbd19,0,0x8000,0,0xbe72,0,0x3e750000,0,0xbd190000,0,0x80000000,0,0xbe720000,
0xbe69,0,0x3dde,0,0x3d97,0,0x3e5a,0,0xbe690000,0,0x3dde0000,0,0x3d970000,0,0x3e5a0000,0,
0,0xbe69,0,0x3dde,0,0x3d97,0,0x3e5a,0,0xbe690000,0,0x3dde0000,0,0x3d970000,0,0x3e5a0000,
0x3e75,0,0xbdde,0,0x8000,0,0xbe5a,0,0x3e750000,0,0xbdde0000,0,0x80000000,0,0xbe5a0000,0,
0,0x3e75,0,0xbdde,0,0x8000,0,0xbe5a,0,0x3e750000,0,0xbdde0000,0,0x80000000,0,0xbe5a0000,
0xbe10,0,0x3e72,0,0x3e46,0,0x3d19,0,0xbe100000,0,0x3e720000,0,0x3e460000,0,0x3d190000,0,
0,0xbe10,0,0x3e72,0,0x3e46,0,0x3d19,0,0xbe100000,0,0x3e720000,0,0x3e460000,0,0x3d190000,
0x3e75,0,0xbe2d,0,0x8000,0,0xbe2d,0,0x3e750000,0,0xbe2d0000,0,0x80000000,0,0xbe2d0000,0,
0,0x3e75,0,0xbe2d,0,0x8000,0,0xbe2d,0,0x3e750000,0,0xbe2d0000,0,0x80000000,0,0xbe2d0000,
0,0,0x3e2d,0,0x3e75,0,0xbe2d,0,0,0,0x3e2d0000,0,0x3e750000,0,0xbe2d0000,0,
0,0,0,0x3e2d,0,0x3e75,0,0xbe2d,0,0,0,0x3e2d0000,0,0x3e750000,0,0xbe2d0000,
0x3e75,0,0xbe5a,0,0x8000,0,0xbdde,0,0x3e750000,0,0xbe5a0000,0,0x80000000,0,0xbdde0000,0,
0,0x3e75,0,0xbe5a,0,0x8000,0,0xbdde,0,0x3e750000,0,0xbe5a0000,0,0x80000000,0,0xbdde0000,
0x3e10,0,0xbd19,0,0x3e46,0,0xbe72,0,0x3e100000,0,0xbd190000,0,0x3e460000,0,0xbe720000,0,
0,0x3e10,0,0xbd19,0,0x3e46,0,0xbe72,0,0x3e100000,0,0xbd190000,0,0x3e460000,0,0xbe720000,
0x3e75,0,0xbe72,0,0x8000,0,0xbd19,0,0x3e750000,0,0xbe720000,0,0x80000000,0,0xbd190000,0,
0,0x3e75,0,0xbe72,0,0x8000,0,0xbd19,0,0x3e750000,0,0xbe720000,0,0x80000000,0,0xbd190000,
0x3e69,0,0xbe5a,0,0x3d97,0,0xbdde,0,0x3e690000,0,0xbe5a0000,0,0x3d970000,0,0xbdde0000,0,
0,0x3e69,0,0xbe5a,0,0x3d97,0,0xbdde,0,0x3e690000,0,0xbe5a0000,0,0x3d970000,0,0xbdde0000,
0x3e46,0,0x3e2d,0,0xbe10,0,0xbe2d,0,0x3e460000,0,0x3e2d0000,0,0xbe100000,0,0xbe2d0000,0,
0,0x3e46,0,0x3e2d,0,0xbe10,0,0xbe2d,0,0x3e460000,0,0x3e2d0000,0,0xbe100000,0,0xbe2d0000,
0x3e10,0,0x3dde,0,0xbe46,0,0xbe5a,0,0x3e100000,0,0x3dde0000,0,0xbe460000,0,0xbe5a0000,0,
0,0x3e10,0,0x3dde,0,0xbe46,0,0xbe5a,0,0x3e100000,0,0x3dde0000,0,0xbe460000,0,0xbe5a0000,
0xbd97,0,0xbe2d,0,0xbe69,0,0xbe2d,0,0xbd970000,0,0xbe2d0000,0,0xbe690000,0,0xbe2d0000,0,
0,0xbd97,0,0xbe2d,0,0xbe69,0,0xbe2d,0,0xbd970000,0,0xbe2d0000,0,0xbe690000,0,0xbe2d0000,
0xbe69,0,0xbe72,0,0xbd97,0,0x3d19,0,0xbe690000,0,0xbe720000,0,0xbd970000,0,0x3d190000,0,
0,0xbe69,0,0xbe72,0,0xbd97,0,0x3d19,0,0xbe690000,0,0xbe720000,0,0xbd970000,0,0x3d190000,
0xbe75,0,0xbe2d,0,0x8000,0,0x3e2d,0,0xbe750000,0,0xbe2d0000,0,0x80000000,0,0x3e2d0000,0,
0,0xbe75,0,0xbe2d,0,0x8000,0,0x3e2d,0,0xbe750000,0,0xbe2d0000,0,0x80000000,0,0x3e2d0000,
0,0,0x3e2d,0,0x3e75,0,0x3e2d,0,0,0,0x3e2d0000,0,0x3e750000,0,0x3e2d0000,0,
0,0,0,0x3e2d,0,0x3e75,0,0x3e2d,0,0,0,0x3e2d0000,0,0x3e750000,0,0x3e2d0000,
0xbd97,0,0x3e2d,0,0x3e69,0,0x3e2d,0,0xbd970000,0,0x3e2d0000,0,0x3e690000,0,0x3e2d0000,0,
0,0xbd97,0,0x3e2d,0,0x3e69,0,0x3e2d,0,0xbd970000,0,0x3e2d0000,0,0x3e690000,0,0x3e2d0000,
0x3e69,0,0x3d19,0,0xbd97,0,0xbe72,0,0x3e690000,0,0x3d190000,0,0xbd970000,0,0xbe720000,0,
0,0x3e69,0,0x3d19,0,0xbd97,0,0xbe72,0,0x3e690000,0,0x3d190000,0,0xbd970000,0,0xbe720000,
0x3e46,0,0x3e2d,0,0x3e10,0,0xbe2d,0,0x3e460000,0,0x3e2d0000,0,0x3e100000,0,0xbe2d0000,0,
0,0x3e46,0,0x3e2d,0,0x3e10,0,0xbe2d,0,0x3e460000,0,0x3e2d0000,0,0x3e100000,0,0xbe2d0000,
0xbe10,0,0xbe5a,0,0xbe46,0,0x3dde,0,0xbe100000,0,0xbe5a0000,0,0xbe460000,0,0x3dde0000,0,
0,0xbe10,0,0xbe5a,0,0xbe46,0,0x3dde,0,0xbe100000,0,0xbe5a0000,0,0xbe460000,0,0x3dde0000,
0x3e46,0,0xbe2d,0,0xbe10,0,0xbe2d,0,0x3e460000,0,0xbe2d0000,0,0xbe100000,0,0xbe2d0000,0,
0,0x3e46,0,0xbe2d,0,0xbe10,0,0xbe2d,0,0x3e460000,0,0xbe2d0000,0,0xbe100000,0,0xbe2d0000,
0xbe10,0,0x3e5a,0,0x3e46,0,0x3dde,0,0xbe100000,0,0x3e5a0000,0,0x3e460000,0,0x3dde0000,0,
0,0xbe10,0,0x3e5a,0,0x3e46,0,0x3dde,0,0xbe100000,0,0x3e5a0000,0,0x3e460000,0,0x3dde0000,
0xbd97,0,0xbe2d,0,0xbe69,0,0x3e2d,0,0xbd970000,0,0xbe2d0000,0,0xbe690000,0,0x3e2d0000,0,
0,0xbd97,0,0xbe2d,0,0xbe69,0,0x3e2d,0,0xbd970000,0,0xbe2d0000,0,0xbe690000,0,0x3e2d0000,
0x3e69,0,0xbd19,0,0x3d97,0,0xbe72,0,0x3e690000,0,0xbd190000,0,0x3d970000,0,0xbe720000,0,
0,0x3e69,0,0xbd19,0,0x3d97,0,0xbe72,0,0x3e690000,0,0xbd190000,0,0x3d970000,0,0xbe720000,
0xbe75,0,0x3e2d,0,0x8000,0,0x3e2d,0,0xbe750000,0,0x3e2d0000,0,0x80000000,0,0x3e2d0000,0,
0,0xbe75,0,0x3e2d,0,0x8000,0,0x3e2d,0,0xbe750000,0,0x3e2d0000,0,0x80000000,0,0x3e2d0000,
0,0,0xbe2d,0,0xbe75,0,0x3e2d,0,0,0,0xbe2d0000,0,0xbe750000,0,0x3e2d0000,0,
0,0,0,0xbe2d,0,0xbe75,0,0x3e2d,0,0,0,0xbe2d0000,0,0xbe750000,0,0x3e2d0000,
0xbd97,0,0x3e2d,0,0x3e69,0,0xbe2d,0,0xbd970000,0,0x3e2d0000,0,0x3e690000,0,0xbe2d0000,0,
0,0xbd97,0,0x3e2d,0,0x3e69,0,0xbe2d,0,0xbd970000,0,0x3e2d0000,0,0x3e690000,0,0xbe2d0000,
0xbe69,0,0x3e72,0,0x3d97,0,0x3d19,0,0xbe690000,0,0x3e720000,0,0x3d970000,0,0x3d190000,0,
0,0xbe69,0,0x3e72,0,0x3d97,0,0x3d19,0,0xbe690000,0,0x3e720000,0,0x3d970000,0,0x3d190000,
0x3e46,0,0xbe2d,0,0x3e10,0,0xbe2d,0,0x3e460000,0,0xbe2d0000,0,0x3e100000,0,0xbe2d0000,0,
0,0x3e46,0,0xbe2d,0,0x3e10,0,0xbe2d,0,0x3e460000,0,0xbe2d0000,0,0x3e100000,0,0xbe2d0000,
0x3e10,0,0xbdde,0,0x3e46,0,0xbe5a,0,0x3e100000,0,0xbdde0000,0,0x3e460000,0,0xbe5a0000,0,
0,0x3e10,0,0xbdde,0,0x3e46,0,0xbe5a,0,0x3e100000,0,0xbdde0000,0,0x3e460000,0,0xbe5a0000,
0x3d97,0,0x3d19,0,0xbe69,0,0xbe72,0,0x3d970000,0,0x3d190000,0,0xbe690000,0,0xbe720000,0,
0,0x3d97,0,0x3d19,0,0xbe69,0,0xbe72,0,0x3d970000,0,0x3d190000,0,0xbe690000,0,0xbe720000,
0,0,0xbd19,0,0xbe75,0,0xbe72,0,0,0,0xbd190000,0,0xbe750000,0,0xbe720000,0,
0,0,0,0xbd19,0,0xbe75,0,0xbe72,0,0,0,0xbd190000,0,0xbe750000,0,0xbe720000,
0xbe46,0,0xbdde,0,0x3e10,0,0x3e5a,0,0xbe460000,0,0xbdde0000,0,0x3e100000,0,0x3e5a0000,0,
0,0xbe46,0,0xbdde,0,0x3e10,0,0x3e5a,0,0xbe460000,0,0xbdde0000,0,0x3e100000,0,0x3e5a0000,
0,0,0x3dde,0,0x3e75,0,0x3e5a,0,0,0,0x3dde0000,0,0x3e750000,0,0x3e5a0000,0,
0,0,0,0x3dde,0,0x3e75,0,0x3e5a,0,0,0,0x3dde0000,0,0x3e750000,0,0x3e5a0000,
0x3e75,0,0x3e2d,0,0x8000,0,0xbe2d,0,0x3e750000,0,0x3e2d0000,0,0x80000000,0,0xbe2d0000,0,
0,0x3e75,0,0x3e2d,0,0x8000,0,0xbe2d,0,0x3e750000,0,0x3e2d0000,0,0x80000000,0,0xbe2d0000,
0,0,0xbe2d,0,0xbe75,0,0xbe2d,0,0,0,0xbe2d0000,0,0xbe750000,0,0xbe2d0000,0,
0,0,0,0xbe2d,0,0xbe75,0,0xbe2d,0,0,0,0xbe2d0000,0,0xbe750000,0,0xbe2d0000,
0xbe46,0,0xbe5a,0,0xbe10,0,0x3dde,0,0xbe460000,0,0xbe5a0000,0,0xbe100000,0,0x3dde0000,0,
0,0xbe46,0,0xbe5a,0,0xbe10,0,0x3dde,0,0xbe460000,0,0xbe5a0000,0,0xbe100000,0,0x3dde0000,
0,0,0x3e5a,0,0x3e75,0,0x3dde,0,0,0,0x3e5a0000,0,0x3e750000,0,0x3dde0000,0,
0,0,0,0x3e5a,0,0x3e75,0,0x3dde,0,0,0,0x3e5a0000,0,0x3e750000,0,0x3dde0000,
0x3d97,0,0x3e72,0,0x3e69,0,0xbd19,0,0x3d970000,0,0x3e720000,0,0x3e690000,0,0xbd190000,0,
0,0x3d97,0,0x3e72,0,0x3e69,0,0xbd19,0,0x3d970000,0,0x3e720000,0,0x3e690000,0,0xbd190000,
0,0,0xbe72,0,0xbe75,0,0xbd19,0,0,0,0xbe720000,0,0xbe750000,0,0xbd190000,0,
0,0,0,0xbe72,0,0xbe75,0,0xbd19,0,0,0,0xbe720000,0,0xbe750000,0,0xbd190000,
0x3d97,0,0xbe72,0,0xbe69,0,0xbd19,0,0x3d970000,0,0xbe720000,0,0xbe690000,0,0xbd190000,0,
0,0x3d97,0,0xbe72,0,0xbe69,0,0xbd19,0,0x3d970000,0,0xbe720000,0,0xbe690000,0,0xbd190000,
0,0,0x3e72,0,0x3e75,0,0xbd19,0,0,0,0x3e720000,0,0x3e750000,0,0xbd190000,0,
0,0,0,0x3e72,0,0x3e75,0,0xbd19,0,0,0,0x3e720000,0,0x3e750000,0,0xbd190000,
0xbe46,0,0x3e5a,0,0x3e10,0,0x3dde,0,0xbe460000,0,0x3e5a0000,0,0x3e100000,0,0x3dde0000,0,
0,0xbe46,0,0x3e5a,0,0x3e10,0,0x3dde,0,0xbe460000,0,0x3e5a0000,0,0x3e100000,0,0x3dde0000,
0,0,0xbe5a,0,0xbe75,0,0x3dde,0,0,0,0xbe5a0000,0,0xbe750000,0,0x3dde0000,0,
0,0,0,0xbe5a,0,0xbe75,0,0x3dde,0,0,0,0xbe5a0000,0,0xbe750000,0,0x3dde0000,
0x3e75,0,0xbe2d,0,0x8000,0,0xbe2d,0,0x3e750000,0,0xbe2d0000,0,0x80000000,0,0xbe2d0000,0,
0,0x3e75,0,0xbe2d,0,0x8000,0,0xbe2d,0,0x3e750000,0,0xbe2d0000,0,0x80000000,0,0xbe2d0000,
0,0,0x3e2d,0,0x3e75,0,0xbe2d,0,0,0,0x3e2d0000,0,0x3e750000,0,0xbe2d0000,0,
0,0,0,0x3e2d,0,0x3e75,0,0xbe2d,0,0,0,0x3e2d0000,0,0x3e750000,0,0xbe2d0000,
0xbe46,0,0x3dde,0,0xbe10,0,0x3e5a,0,0xbe460000,0,0x3dde0000,0,0xbe100000,0,0x3e5a0000,0,
0,0xbe46,0,0x3dde,0,0xbe10,0,0x3e5a,0,0xbe460000,0,0x3dde0000,0,0xbe100000,0,0x3e5a0000,
0,0,0xbdde,0,0xbe75,0,0x3e5a,0,0,0,0xbdde0000,0,0xbe750000,0,0x3e5a0000,0,
0,0,0,0xbdde,0,0xbe75,0,0x3e5a,0,0,0,0xbdde0000,0,0xbe750000,0,0x3e5a0000,
0x3d97,0,0xbd19,0,0x3e69,0,0xbe72,0,0x3d970000,0,0xbd190000,0,0x3e690000,0,0xbe720000,0,
0,0x3d97,0,0xbd19,0,0x3e69,0,0xbe72,0,0x3d970000,0,0xbd190000,0,0x3e690000,0,0xbe720000,
0,0,0x3d19,0,0x3e75,0,0xbe72,0,0,0,0x3d190000,0,0x3e750000,0,0xbe720000,0,
0,0,0,0x3d19,0,0x3e75,0,0xbe72,0,0,0,0x3d190000,0,0x3e750000,0,0xbe720000,
0xbd97,0,0xbdde,0,0xbe69,0,0xbe5a,0,0xbd970000,0,0xbdde0000,0,0xbe690000,0,0xbe5a0000,0,
0,0xbd97,0,0xbdde,0,0xbe69,0,0xbe5a,0,0xbd970000,0,0xbdde0000,0,0xbe690000,0,0xbe5a0000,
0xbe10,0,0xbe2d,0,0xbe46,0,0xbe2d,0,0xbe100000,0,0xbe2d0000,0,0xbe460000,0,0xbe2d0000,0,
0,0xbe10,0,0xbe2d,0,0xbe46,0,0xbe2d,0,0xbe100000,0,0xbe2d0000,0,0xbe460000,0,0xbe2d0000,
0x3e46,0,0x3e72,0,0x3e10,0,0x3d19,0,0x3e460000,0,0x3e720000,0,0x3e100000,0,0x3d190000,0,
0,0x3e46,0,0x3e72,0,0x3e10,0,0x3d19,0,0x3e460000,0,0x3e720000,0,0x3e100000,0,0x3d190000,
0x3e69,0,0x3e2d,0,0xbd97,0,0xbe2d,0,0x3e690000,0,0x3e2d0000,0,0xbd970000,0,0xbe2d0000,0,
0,0x3e69,0,0x3e2d,0,0xbd97,0,0xbe2d,0,0x3e690000,0,0x3e2d0000,0,0xbd970000,0,0xbe2d0000,
0xbe75,0,0xbe2d,0,0x8000,0,0x3e2d,0,0xbe750000,0,0xbe2d0000,0,0x80000000,0,0x3e2d0000,0,
0,0xbe75,0,0xbe2d,0,0x8000,0,0x3e2d,0,0xbe750000,0,0xbe2d0000,0,0x80000000,0,0x3e2d0000,
0,0,0x3e2d,0,0x3e75,0,0x3e2d,0,0,0,0x3e2d0000,0,0x3e750000,0,0x3e2d0000,0,
0,0,0,0x3e2d,0,0x3e75,0,0x3e2d,0,0,0,0x3e2d0000,0,0x3e750000,0,0x3e2d0000,
0x3e46,0,0xbd19,0,0xbe10,0,0xbe72,0,0x3e460000,0,0xbd190000,0,0xbe100000,0,0xbe720000,0,
0,0x3e46,0,0xbd19,0,0xbe10,0,0xbe72,0,0x3e460000,0,0xbd190000,0,0xbe100000,0,0xbe720000,
0xbe69,0,0xbe2d,0,0xbd97,0,0x3e2d,0,0xbe690000,0,0xbe2d0000,0,0xbd970000,0,0x3e2d0000,0,
0,0xbe69,0,0xbe2d,0,0xbd97,0,0x3e2d,0,0xbe690000,0,0xbe2d0000,0,0xbd970000,0,0x3e2d0000,
0xbd97,0,0x3e5a,0,0x3e69,0,0x3dde,0,0xbd970000,0,0x3e5a0000,0,0x3e690000,0,0x3dde0000,0,
0,0xbd97,0,0x3e5a,0,0x3e69,0,0x3dde,0,0xbd970000,0,0x3e5a0000,0,0x3e690000,0,0x3dde0000,
0x3e10,0,0xbe2d,0,0xbe46,0,0xbe2d,0,0x3e100000,0,0xbe2d0000,0,0xbe460000,0,0xbe2d0000,0,
0,0x3e10,0,0xbe2d,0,0xbe46,0,0xbe2d,0,0x3e100000,0,0xbe2d0000,0,0xbe460000,0,0xbe2d0000,
0xbd97,0,0xbe5a,0,0xbe69,0,0x3dde,0,0xbd970000,0,0xbe5a0000,0,0xbe690000,0,0x3dde0000,0,
0,0xbd97,0,0xbe5a,0,0xbe69,0,0x3dde,0,0xbd970000,0,0xbe5a0000,0,0xbe690000,0,0x3dde0000,
0x3e10,0,0x3e2d,0,0x3e46,0,0xbe2d,0,0x3e100000,0,0x3e2d0000,0,0x3e460000,0,0xbe2d0000,0,
0,0x3e10,0,0x3e2d,0,0x3e46,0,0xbe2d,0,0x3e100000,0,0x3e2d0000,0,0x3e460000,0,0xbe2d0000,
0x3e46,0,0x3d19,0,0x3e10,0,0xbe72,0,0x3e460000,0,0x3d190000,0,0x3e100000,0,0xbe720000,0,
0,0x3e46,0,0x3d19,0,0x3e10,0,0xbe72,0,0x3e460000,0,0x3d190000,0,0x3e100000,0,0xbe720000,
0xbe69,0,0x3e2d,0,0x3d97,0,0x3e2d,0,0xbe690000,0,0x3e2d0000,0,0x3d970000,0,0x3e2d0000,0,
0,0xbe69,0,0x3e2d,0,0x3d97,0,0x3e2d,0,0xbe690000,0,0x3e2d0000,0,0x3d970000,0,0x3e2d0000,
0xbe75,0,0x3e2d,0,0x8000,0,0x3e2d,0,0xbe750000,0,0x3e2d0000,0,0x80000000,0,0x3e2d0000,0,
0,0xbe75,0,0x3e2d,0,0x8000,0,0x3e2d,0,0xbe750000,0,0x3e2d0000,0,0x80000000,0,0x3e2d0000,
0,0,0xbe2d,0,0xbe75,0,0x3e2d,0,0,0,0xbe2d0000,0,0xbe750000,0,0x3e2d0000,0,
0,0,0,0xbe2d,0,0xbe75,0,0x3e2d,0,0,0,0xbe2d0000,0,0xbe750000,0,0x3e2d0000,
0x3e46,0,0xbe72,0,0xbe10,0,0x3d19,0,0x3e460000,0,0xbe720000,0,0xbe100000,0,0x3d190000,0,
0,0x3e46,0,0xbe72,0,0xbe10,0,0x3d19,0,0x3e460000,0,0xbe720000,0,0xbe100000,0,0x3d190000,
0x3e69,0,0xbe2d,0,0x3d97,0,0xbe2d,0,0x3e690000,0,0xbe2d0000,0,0x3d970000,0,0xbe2d0000,0,
0,0x3e69,0,0xbe2d,0,0x3d97,0,0xbe2d,0,0x3e690000,0,0xbe2d0000,0,0x3d970000,0,0xbe2d0000,
0xbd97,0,0x3dde,0,0x3e69,0,0xbe5a,0,0xbd970000,0,0x3dde0000,0,0x3e690000,0,0xbe5a0000,0,
0,0xbd97,0,0x3dde,0,0x3e69,0,0xbe5a,0,0xbd970000,0,0x3dde0000,0,0x3e690000,0,0xbe5a0000,
0xbe10,0,0x3e2d,0,0x3e46,0,0xbe2d,0,0xbe100000,0,0x3e2d0000,0,0x3e460000,0,0xbe2d0000,0,
0,0xbe10,0,0x3e2d,0,0x3e46,0,0xbe2d,0,0xbe100000,0,0x3e2d0000,0,0x3e460000,0,0xbe2d0000,
0xbe46,0,0xbe5a,0,0xbe10,0,0xbdde,0,0xbe460000,0,0xbe5a0000,0,0xbe100000,0,0xbdde0000,0,
0,0xbe46,0,0xbe5a,0,0xbe10,0,0xbdde,0,0xbe460000,0,0xbe5a0000,0,0xbe100000,0,0xbdde0000,
0xbe69,0,0xbe72,0,0xbd97,0,0xbd19,0,0xbe690000,0,0xbe720000,0,0xbd970000,0,0xbd190000,0,
0,0xbe69,0,0xbe72,0,0xbd97,0,0xbd19,0,0xbe690000,0,0xbe720000,0,0xbd970000,0,0xbd190000,
0x3d97,0,0xbd19,0,0xbe69,0,0xbe72,0,0x3d970000,0,0xbd190000,0,0xbe690000,0,0xbe720000,0,
0,0x3d97,0,0xbd19,0,0xbe69,0,0xbe72,0,0x3d970000,0,0xbd190000,0,0xbe690000,0,0xbe720000,
0xbe10,0,0xbe5a,0,0xbe46,0,0xbdde,0,0xbe100000,0,0xbe5a0000,0,0xbe460000,0,0xbdde0000,0,
0,0xbe10,0,0xbe5a,0,0xbe46,0,0xbdde,0,0xbe100000,0,0xbe5a0000,0,0xbe460000,0,0xbdde0000,
0x3e75,0,0x3e2d,0,0x8000,0,0xbe2d,0,0x3e750000,0,0x3e2d0000,0,0x80000000,0,0xbe2d0000,0,
0,0x3e75,0,0x3e2d,0,0x8000,0,0xbe2d,0,0x3e750000,0,0x3e2d0000,0,0x80000000,0,0xbe2d0000,
0,0,0xbe2d,0,0xbe75,0,0xbe2d,0,0,0,0xbe2d0000,0,0xbe750000,0,0xbe2d0000,0,
0,0,0,0xbe2d,0,0xbe75,0,0xbe2d,0,0,0,0xbe2d0000,0,0xbe750000,0,0xbe2d0000,
0x3d97,0,0x3e72,0,0x3e69,0,0x3d19,0,0x3d970000,0,0x3e720000,0,0x3e690000,0,0x3d190000,0,
0,0x3d97,0,0x3e72,0,0x3e69,0,0x3d19,0,0x3d970000,0,0x3e720000,0,0x3e690000,0,0x3d190000,
0x3e10,0,0xbdde,0,0xbe46,0,0xbe5a,0,0x3e100000,0,0xbdde0000,0,0xbe460000,0,0xbe5a0000,0,
0,0x3e10,0,0xbdde,0,0xbe46,0,0xbe5a,0,0x3e100000,0,0xbdde0000,0,0xbe460000,0,0xbe5a0000,
0xbe46,0,0x3dde,0,0x3e10,0,0x3e5a,0,0xbe460000,0,0x3dde0000,0,0x3e100000,0,0x3e5a0000,0,
0,0xbe46,0,0x3dde,0,0x3e10,0,0x3e5a,0,0xbe460000,0,0x3dde0000,0,0x3e100000,0,0x3e5a0000,
0x3e69,0,0xbd19,0,0xbd97,0,0xbe72,0,0x3e690000,0,0xbd190000,0,0xbd970000,0,0xbe720000,0,
0,0x3e69,0,0xbd19,0,0xbd97,0,0xbe72,0,0x3e690000,0,0xbd190000,0,0xbd970000,0,0xbe720000,
0xbe46,0,0xbdde,0,0xbe10,0,0x3e5a,0,0xbe460000,0,0xbdde0000,0,0xbe100000,0,0x3e5a0000,0,
0,0xbe46,0,0xbdde,0,0xbe10,0,0x3e5a,0,0xbe460000,0,0xbdde0000,0,0xbe100000,0,0x3e5a0000,
0x3e69,0,0x3d19,0,0x3d97,0,0xbe72,0,0x3e690000,0,0x3d190000,0,0x3d970000,0,0xbe720000,0,
0,0x3e69,0,0x3d19,0,0x3d97,0,0xbe72,0,0x3e690000,0,0x3d190000,0,0x3d970000,0,0xbe720000,
0x3d97,0,0xbe72,0,0xbe69,0,0x3d19,0,0x3d970000,0,0xbe720000,0,0xbe690000,0,0x3d190000,0,
0,0x3d97,0,0xbe72,0,0xbe69,0,0x3d19,0,0x3d970000,0,0xbe720000,0,0xbe690000,0,0x3d190000,
0x3e10,0,0x3dde,0,0x3e46,0,0xbe5a,0,0x3e100000,0,0x3dde0000,0,0x3e460000,0,0xbe5a0000,0,
0,0x3e10,0,0x3dde,0,0x3e46,0,0xbe5a,0,0x3e100000,0,0x3dde0000,0,0x3e460000,0,0xbe5a0000,
0x3e75,0,0xbe2d,0,0x8000,0,0xbe2d,0,0x3e750000,0,0xbe2d0000,0,0x80000000,0,0xbe2d0000,0,
0,0x3e75,0,0xbe2d,0,0x8000,0,0xbe2d,0,0x3e750000,0,0xbe2d0000,0,0x80000000,0,0xbe2d0000,
0,0,0x3e2d,0,0x3e75,0,0xbe2d,0,0,0,0x3e2d0000,0,0x3e750000,0,0xbe2d0000,0,
0,0,0,0x3e2d,0,0x3e75,0,0xbe2d,0,0,0,0x3e2d0000,0,0x3e750000,0,0xbe2d0000,
0x3d97,0,0x3d19,0,0x3e69,0,0xbe72,0,0x3d970000,0,0x3d190000,0,0x3e690000,0,0xbe720000,0,
0,0x3d97,0,0x3d19,0,0x3e69,0,0xbe72,0,0x3d970000,0,0x3d190000,0,0x3e690000,0,0xbe720000,
0xbe10,0,0x3e5a,0,0x3e46,0,0xbdde,0,0xbe100000,0,0x3e5a0000,0,0x3e460000,0,0xbdde0000,0,
0,0xbe10,0,0x3e5a,0,0x3e46,0,0xbdde,0,0xbe100000,0,0x3e5a0000,0,0x3e460000,0,0xbdde0000,
0xbe46,0,0x3e5a,0,0x3e10,0,0xbdde,0,0xbe460000,0,0x3e5a0000,0,0x3e100000,0,0xbdde0000,0,
0,0xbe46,0,0x3e5a,0,0x3e10,0,0xbdde,0,0xbe460000,0,0x3e5a0000,0,0x3e100000,0,0xbdde0000,
0xbe69,0,0x3e72,0,0x3d97,0,0xbd19,0,0xbe690000,0,0x3e720000,0,0x3d970000,0,0xbd190000,0,
0,0xbe69,0,0x3e72,0,0x3d97,0,0xbd19,0,0xbe690000,0,0x3e720000,0,0x3d970000,0,0xbd190000,
0x3eb7,0x3eb7,0x3eb7,0x3eb7,0x3eb78000,0x3eb78000,0x3eb78000,0x3eb78000,0x3eb7,0x3de23eae,0x3e573e94,0x3e943e57,0x3eb78000,0x3eaebde2,0x3e94be57,0x3e57be94,
0x3eb7,0x3e573e94,0x3eae3de2,0x3eaebde2,0x3eb78000,0x3e94be57,0x3de2beae,0xbde2beae,0x3eb7,0x3e943e57,0x3eaebde2,0x3de2beae,0x3eb78000,0x3e57be94,0xbde2beae,0xbeaebde2,
0x3eb7,0x3eb7,0x3eb7,0x3eb7,0x3eb78000,0x3eb78000,0x3eb78000,0x3eb78000,0x3eae3de2,0x3eb70000,0x3eaebde2,0x3e94be57,0x3de2beae,0xbeb7,0xbde2beae,0xbe57be94,
0x3e57be94,0xbeb7,0xbe57be94,0xbeaebde2,0xbe94be57,0xbeb78000,0xbe943e57,0xbde23eae,0xbe57be94,0xbeb70000,0xbe573e94,0x3de23eae,0xbe943e57,0x3eb7,0x3e943e57,0x3eaebde2,
0x3eb7,0x3eae3de2,0x3e57be94,0xbe57be94,0x3eb78000,0x3de2beae,0xbe94be57,0xbe943e57,0x3eb7,0x3eb70000,0xbeb7,0xbeb70000,0x3eb78000,0xbeb7,0xbeb78000,0x3eb7,
0x3eb7,0x3eaebde2,0xbe57be94,0xbe573e94,0x3eb78000,0xbde2beae,0xbe943e57,0x3e943e57,0x3eb7,0x3e94be57,0xbeaebde2,0x3de23eae,0x3eb78000,0xbe57be94,0xbde23eae,0x3eaebde2,
0xbeae3de2,0x3eb7,0x3eae3de2,0x3e57be94,0x3de23eae,0x3eb78000,0x3de2beae,0xbe94be57,0x3eb7,0x3eb70000,0xbeb7,0xbeb70000,0x3eb78000,0xbeb7,0xbeb78000,0x3eb7,
0x3eae3de2,0xbeb7,0xbeae3de2,0x3e573e94,0x3de2beae,0xbeb78000,0x3de23eae,0x3e94be57,0x3e57be94,0xbeb70000,0x3e573e94,0x3de2beae,0xbe94be57,0x3eb7,0x3e94be57,0xbeaebde2,
0x3eb7,0x3e57be94,0xbeae3de2,0x3eae3de2,0x3eb78000,0xbe94be57,0x3de23eae,0x3de2beae,0x3eb7,0x3de2beae,0xbe573e94,0x3e94be57,0x3eb78000,0xbeaebde2,0x3e943e57,0xbe57be94,
0x3eb7,0xbeb7,0x3eb7,0xbeb7,0x3eb78000,0xbeb78000,0x3eb78000,0xbeb78000,0x3eb7,0xbde2beae,0x3e573e94,0xbe94be57,0x3eb78000,0xbeae3de2,0x3e94be57,0xbe573e94,
0xbe57be94,0x3eb7,0x3e57be94,0xbeae3de2,0xbe943e57,0x3eb78000,0xbe94be57,0x3de23eae,0xbeae3de2,0x3eb70000,0xbeaebde2,0x3e943e57,0x3de23eae,0xbeb7,0xbde23eae,0x3e57be94,
0x3eb7,0xbeb7,0x3eb7,0xbeb7,0x3eb78000,0xbeb78000,0x3eb78000,0xbeb78000,0x3eae3de2,0xbeb70000,0x3eaebde2,0xbe943e57,0x3de2beae,0x3eb7,0xbde2beae,0x3e573e94,
0x3eb7,0xbe57be94,0x3eae3de2,0xbeae3de2,0x3eb78000,0xbe943e57,0x3de2beae,0x3de23eae,0x3eb7,0xbe94be57,0x3eaebde2,0xbde23eae,0x3eb78000,0xbe573e94,0xbde2beae,0x3eae3de2,
0x3eb7,0xbeaebde2,0x3e57be94,0x3e573e94,0x3eb78000,0xbde23eae,0xbe94be57,0x3e94be57,0x3eb7,0xbeb70000,0xbeb7,0x3eb70000,0x3eb78000,0x3eb7,0xbeb78000,0xbeb7,
0x3e57be94,0x3eb7,0xbe57be94,0x3eae3de2,0xbe94be57,0x3eb78000,0xbe943e57,0x3de2beae,0xbe57be94,0x3eb70000,0xbe573e94,0xbde2beae,0xbe943e57,0xbeb7,0x3e943e57,0xbeae3de2,
0xbeae3de2,0xbeb7,0x3eae3de2,0xbe573e94,0x3de23eae,0xbeb78000,0x3de2beae,0x3e943e57,0x3eb7,0xbeb70000,0xbeb7,0x3eb70000,0x3eb78000,0x3eb7,0xbeb78000,0xbeb7,
0x3eb7,0xbeae3de2,0xbe57be94,0x3e57be94,0x3eb78000,0x3de23eae,0xbe943e57,0xbe94be57,0x3eb7,0xbe943e57,0xbeaebde2,0xbde2beae,0x3eb78000,0x3e573e94,0xbde23eae,0xbeae3de2,
0x3eb7,0xbe573e94,0xbeae3de2,0xbeaebde2,0x3eb78000,0x3e943e57,0x3de23eae,0xbde23eae,0x3eb7,0xbde23eae,0xbe573e94,0xbe943e57,0x3eb78000,0x3eae3de2,0x3e943e57,0x3e573e94,
0x3eae3de2,0x3eb7,0xbeae3de2,0xbe57be94,0x3de2beae,0x3eb78000,0x3de23eae,0xbe943e57,0x3e57be94,0x3eb70000,0x3e573e94,0xbde23eae,0xbe94be57,0xbeb7,0x3e94be57,0x3eae3de2,
0xbe57be94,0xbeb7,0x3e57be94,0x3eaebde2,0xbe943e57,0xbeb78000,0xbe94be57,0xbde2beae,0xbeae3de2,0xbeb70000,0xbeaebde2,0xbe94be57,0x3de23eae,0x3eb7,0xbde23eae,0xbe573e94,
0x3eb7,0x3eb7,0x3eb7,0x3eb7,0x3eb78000,0x3eb78000,0x3eb78000,0x3eb78000,0x3e57be94,0x3de2beae,0xbeb7,0xbde2beae,0xbe94be57,0xbeaebde2,0xbeb78000,0xbeae3de2,
0xbeae3de2,0xbe573e94,0x3eb7,0x3e573e94,0x3de23eae,0x3e943e57,0x3eb78000,0x3e94be57,0x3eae3de2,0x3e94be57,0xbeb7,0xbe94be57,0x3de2beae,0xbe57be94,0xbeb78000,0xbe573e94,
0x3eb7,0x3eb7,0x3eb7,0x3eb7,0x3eb78000,0x3eb78000,0x3eb78000,0x3eb78000,0xbe57be94,0xbe94be57,0xbeaebde2,0xbeb70000,0xbe943e57,0xbe573e94,0xbde23eae,0x3eb7,
0x3eae3de2,0x3eaebde2,0x3e57be94,0xbeb7,0x3de2beae,0xbde2beae,0xbe94be57,0xbeb78000,0xbeae3de2,0xbde23eae,0x3e573e94,0x3eb70000,0x3de23eae,0x3eae3de2,0x3e94be57,0xbeb7,
0xbe57be94,0xbeae3de2,0x3eb7,0x3eae3de2,0xbe943e57,0x3de23eae,0x3eb78000,0x3de2beae,0x3eb7,0x3eb70000,0xbeb7,0xbeb70000,0x3eb78000,0xbeb7,0xbeb78000,0x3eb7,
0x3e57be94,0xbeaebde2,0x3eb7,0x3eaebde2,0xbe94be57,0xbde23eae,0x3eb78000,0xbde2beae,0xbeae3de2,0x3e943e57,0xbeb7,0xbe943e57,0x3de23eae,0x3e57be94,0xbeb78000,0x3e573e94,
0x3e57be94,0xbe57be94,0xbeae3de2,0x3eb7,0xbe94be57,0xbe943e57,0x3de23eae,0x3eb78000,0x3eb7,0x3eb70000,0xbeb7,0xbeb70000,0x3eb78000,0xbeb7,0xbeb78000,0x3eb7,
0xbe57be94,0xbe573e94,0x3eae3de2,0xbeb7,0xbe943e57,0x3e943e57,0x3de2beae,0xbeb78000,0x3eae3de2,0xbde2beae,0xbe573e94,0x3eb70000,0x3de2beae,0xbeae3de2,0x3e943e57,0xbeb7,
0x3eae3de2,0xbe57be94,0x3eb7,0x3e57be94,0x3de2beae,0xbe943e57,0x3eb78000,0xbe94be57,0xbe57be94,0x3de23eae,0xbeb7,0xbde23eae,0xbe943e57,0x3eaebde2,0xbeb78000,0x3eae3de2,
0x3eb7,0xbeb7,0x3eb7,0xbeb7,0x3eb78000,0xbeb78000,0x3eb78000,0xbeb78000,0x3e57be94,0xbde23eae,0xbeb7,0x3de23eae,0xbe94be57,0x3eae3de2,0xbeb78000,0x3eaebde2,
0xbeae3de2,0x3eae3de2,0xbe57be94,0x3eb7,0x3de23eae,0x3de2beae,0xbe943e57,0x3eb78000,0x3e57be94,0xbe943e57,0x3eaebde2,0xbeb70000,0xbe94be57,0x3e573e94,0xbde2beae,0x3eb7,
0x3eb7,0xbeb7,0x3eb7,0xbeb7,0x3eb78000,0xbeb78000,0x3eb78000,0xbeb78000,0xbe57be94,0x3e943e57,0xbeaebde2,0x3eb70000,0xbe943e57,0x3e57be94,0xbde23eae,0xbeb7,
0xbeae3de2,0x3e57be94,0x3eb7,0xbe57be94,0x3de23eae,0xbe94be57,0x3eb78000,0xbe943e57,0x3eae3de2,0xbe943e57,0xbeb7,0x3e943e57,0x3de2beae,0x3e573e94,0xbeb78000,0x3e57be94,
0xbe57be94,0x3eaebde2,0x3eb7,0xbeaebde2,0xbe943e57,0xbde2beae,0x3eb78000,0xbde23eae,0x3eb7,0xbeb70000,0xbeb7,0x3eb70000,0x3eb78000,0x3eb7,0xbeb78000,0xbeb7,
0x3eae3de2,0xbeae3de2,0x3e57be94,0x3eb7,0x3de2beae,0x3de23eae,0xbe94be57,0x3eb78000,0xbeae3de2,0x3de2beae,0x3e573e94,0xbeb70000,0x3de23eae,0xbeaebde2,0x3e94be57,0x3eb7,
0x3e57be94,0x3e573e94,0xbeae3de2,0xbeb7,0xbe94be57,0x3e94be57,0x3de23eae,0xbeb78000,0x3eb7,0xbeb70000,0xbeb7,0x3eb70000,0x3eb78000,0x3eb7,0xbeb78000,0xbeb7,
0x3e57be94,0x3eae3de2,0x3eb7,0xbeae3de2,0xbe94be57,0x3de2beae,0x3eb78000,0x3de23eae,0xbeae3de2,0xbe94be57,0xbeb7,0x3e94be57,0x3de23eae,0xbe573e94,0xbeb78000,0xbe57be94,
0x3eae3de2,0x3e573e94,0x3eb7,0xbe573e94,0x3de2beae,0x3e94be57,0x3eb78000,0x3e943e57,0xbe57be94,0xbde2beae,0xbeb7,0x3de2beae,0xbe943e57,0xbeae3de2,0xbeb78000,0xbeaebde2,
0xbe57be94,0x3e57be94,0x3eae3de2,0x3eb7,0xbe943e57,0xbe94be57,0x3de2beae,0x3eb78000,0x3eae3de2,0x3de23eae,0xbe573e94,0xbeb70000,0x3de2beae,0x3eaebde2,0x3e943e57,0x3eb7,
0xbeae3de2,0xbeaebde2,0xbe57be94,0xbeb7,0x3de23eae,0xbde23eae,0xbe943e57,0xbeb78000,0x3e57be94,0x3e94be57,0x3eaebde2,0x3eb70000,0xbe94be57,0xbe57be94,0xbde2beae,0xbeb7,
0x3eb7,0x3eb7,0x3eb7,0x3eb7,0x3eb78000,0x3eb78000,0x3eb78000,0x3eb78000,0xbeae3de2,0xbe943e57,0xbe573e94,0xbde23eae,0x3de23eae,0x3e573e94,0x3e943e57,0x3eae3de2,
0xbe57be94,0xbeaebde2,0xbeae3de2,0xbe573e94,0xbe943e57,0xbde23eae,0x3de23eae,0x3e943e57,0x3e57be94,0xbde2beae,0xbeaebde2,0xbe943e57,0xbe94be57,0xbeae3de2,0xbde23eae,0x3e573e94,
0,0,0,0,0,0,0,0,0,0,0,0,0,0,0,0,
0,0,0,0,0,0,0,0,0,0,0,0,0,0,0,0,
0x3eae3de2,0x3e57be94,0xbe57be94,0xbeae3de2,0x3de2beae,0xbe94be57,0xbe943e57,0x3de23eae,0x3eb7,0x3eb70000,0xbeb7,0xbeb70000,0x3eb78000,0xbeb7,0xbeb78000,0x3eb7,
0xbeae3de2,0x3e573e94,0x3e57be94,0xbeaebde2,0x3de23eae,0x3e94be57,0xbe94be57,0xbde23eae,0xbe57be94,0xbde23eae,0x3eaebde2,0xbe94be57,0xbe943e57,0x3eae3de2,0xbde2beae,0xbe573e94,
0,0,0,0,0,0,0,0,0,0,0,0,0,0,0,0,
0,0,0,0,0,0,0,0,0,0,0,0,0,0,0,0,
0x3e57be94,0xbeae3de2,0x3eae3de2,0xbe57be94,0xbe94be57,0x3de23eae,0x3de2beae,0xbe943e57,0x3eae3de2,0xbe94be57,0x3e573e94,0xbde2beae,0x3de2beae,0xbe573e94,0x3e94be57,0xbeae3de2,
0x3eb7,0xbeb7,0x3eb7,0xbeb7,0x3eb78000,0xbeb78000,0x3eb78000,0xbeb78000,0xbeae3de2,0x3e94be57,0xbe573e94,0x3de2beae,0x3de23eae,0xbe57be94,0x3e943e57,0xbeaebde2,
0,0,0,0,0,0,0,0,0,0,0,0,0,0,0,0,
0,0,0,0,0,0,0,0,0,0,0,0,0,0,0,0,
0xbe57be94,0x3eae3de2,0xbeae3de2,0x3e57be94,0xbe943e57,0x3de2beae,0x3de23eae,0xbe94be57,0x3e57be94,0x3de23eae,0xbeaebde2,0x3e94be57,0xbe94be57,0x3eaebde2,0xbde23eae,0xbe57be94,
0x3eae3de2,0xbe573e94,0xbe57be94,0x3eaebde2,0x3de2beae,0x3e943e57,0xbe943e57,0xbde2beae,0x3eb7,0xbeb70000,0xbeb7,0x3eb70000,0x3eb78000,0x3eb7,0xbeb78000,0xbeb7,
0,0,0,0,0,0,0,0,0,0,0,0,0,0,0,0,
0,0,0,0,0,0,0,0,0,0,0,0,0,0,0,0,
0xbeae3de2,0xbe57be94,0x3e57be94,0x3eae3de2,0x3de23eae,0xbe943e57,0xbe94be57,0x3de2beae,0xbe57be94,0x3de2beae,0x3eaebde2,0x3e943e57,0xbe943e57,0xbeaebde2,0xbde2beae,0x3e57be94,
0x3e57be94,0x3eaebde2,0x3eae3de2,0x3e573e94,0xbe94be57,0xbde2beae,0x3de2beae,0x3e94be57,0x3eae3de2,0x3e943e57,0x3e573e94,0x3de23eae,0x3de2beae,0x3e57be94,0x3e94be57,0x3eaebde2,
0,0,0,0,0,0,0,0,0,0,0,0,0,0,0,0,
0,0,0,0,0,0,0,0,0,0,0,0,0,0,0,0,
0,0,0,0,0,0,0,0,0,0,0,0,0,0,0,0,
0,0,0,0,0,0,0,0,0,0,0,0,0,0,0,0,
0x3eb7,0x3eb7,0x3eb7,0x3eb7,0x3eb78000,0x3eb78000,0x3eb78000,0x3eb78000,0xbeae3de2,0xbe943e57,0xbe573e94,0xbde23eae,0x3de23eae,0x3e573e94,0x3e943e57,0x3eae3de2,
0xbe57be94,0xbeaebde2,0xbeae3de2,0xbe573e94,0xbe943e57,0xbde23eae,0x3de23eae,0x3e943e57,0x3e57be94,0xbde2beae,0xbeaebde2,0xbe943e57,0xbe94be57,0xbeae3de2,0xbde23eae,0x3e573e94,
0,0,0,0,0,0,0,0,0,0,0,0,0,0,0,0,
0,0,0,0,0,0,0,0,0,0,0,0,0,0,0,0,
0x3eae3de2,0x3e57be94,0xbe57be94,0xbeae3de2,0x3de2beae,0xbe94be57,0xbe943e57,0x3de23eae,0x3eb7,0x3eb70000,0xbeb7,0xbeb70000,0x3eb78000,0xbeb7,0xbeb78000,0x3eb7,
0xbeae3de2,0x3e573e94,0x3e57be94,0xbeaebde2,0x3de23eae,0x3e94be57,0xbe94be57,0xbde23eae,0xbe57be94,0xbde23eae,0x3eaebde2,0xbe94be57,0xbe943e57,0x3eae3de2,0xbde2beae,0xbe573e94,
0,0,0,0,0,0,0,0,0,0,0,0,0,0,0,0,
0,0,0,0,0,0,0,0,0,0,0,0,0,0,0,0,
0x3e57be94,0xbeae3de2,0x3eae3de2,0xbe57be94,0xbe94be57,0x3de23eae,0x3de2beae,0xbe943e57,0x3eae3de2,0xbe94be57,0x3e573e94,0xbde2beae,0x3de2beae,0xbe573e94,0x3e94be57,0xbeae3de2,
0x3eb7,0xbeb7,0x3eb7,0xbeb7,0x3eb78000,0xbeb78000,0x3eb78000,0xbeb78000,0xbeae3de2,0x3e94be57,0xbe573e94,0x3de2beae,0x3de23eae,0xbe57be94,0x3e943e57,0xbeaebde2,
0,0,0,0,0,0,0,0,0,0,0,0,0,0,0,0,
0,0,0,0,0,0,0,0,0,0,0,0,0,0,0,0,
0xbe57be94,0x3eae3de2,0xbeae3de2,0x3e57be94,0xbe943e57,0x3de2beae,0x3de23eae,0xbe94be57,0x3e57be94,0x3de23eae,0xbeaebde2,0x3e94be57,0xbe94be57,0x3eaebde2,0xbde23eae,0xbe57be94,
0x3eae3de2,0xbe573e94,0xbe57be94,0x3eaebde2,0x3de2beae,0x3e943e57,0xbe943e57,0xbde2beae,0x3eb7,0xbeb70000,0xbeb7,0x3eb70000,0x3eb78000,0x3eb7,0xbeb78000,0xbeb7,
0,0,0,0,0,0,0,0,0,0,0,0,0,0,0,0,
0,0,0,0,0,0,0,0,0,0,0,0,0,0,0,0,
0xbeae3de2,0xbe57be94,0x3e57be94,0x3eae3de2,0x3de23eae,0xbe943e57,0xbe94be57,0x3de2beae,0xbe57be94,0x3de2beae,0x3eaebde2,0x3e943e57,0xbe943e57,0xbeaebde2,0xbde2beae,0x3e57be94,
0x3e57be94,0x3eaebde2,0x3eae3de2,0x3e573e94,0xbe94be57,0xbde2beae,0x3de2beae,0x3e94be57,0x3eae3de2,0x3e943e57,0x3e573e94,0x3de23eae,0x3de2beae,0x3e57be94,0x3e94be57,0x3eaebde2,
};
__device__ __align__(128) const uint32_t TAB_P3[3008] = {
0,0,0,0,0,0,0,0,0,0,0,0,0,0,0,0,
0x80003e83,0xbe79bda2,0x3e1abe54,0x3e1a3e54,0x3e830000,0xbda23e79,0xbe54be1a,0x3e54be1a,0x80003e83,0xbe54be1a,0x3e79bda2,0xbda23e79,0x3e830000,0xbe1a3e54,0xbda2be79,0x3e793da2,
0,0,0,0,0,0,0,0,0,0,0,0,0,0,0,0,
0xbe793da2,0x8000be83,0x3e793da2,0xbe1a3e54,0x3da23e79,0xbe830000,0x3da2be79,0x3e543e1a,0xbe1abe54,0x3e830000,0xbe1a3e54,0xbda2be79,0xbe543e1a,0xbe83,0x3e543e1a,0xbe793da2,
0x80003e83,0xbe1abe54,0x3e793da2,0xbe793da2,0x3e830000,0xbe543e1a,0x3da2be79,0x3da23e79,0x80003e83,0xbda2be79,0x3e1a3e54,0xbe54be1a,0x3e830000,0xbe793da2,0x3e54be1a,0xbe1a3e54,
0x80003e83,0x8000be83,0x80003e83,0x8000be83,0x3e830000,0xbe830000,0x3e830000,0xbe830000,0x80003e83,0x3da2be79,0xbe1a3e54,0x3e54be1a,0x3e830000,0xbe79bda2,0x3e543e1a,0xbe1abe54,
0x3e1abe54,0x80003e83,0xbe1abe54,0x3e793da2,0xbe54be1a,0x3e830000,0xbe543e1a,0x3da2be79,0x3e793da2,0xbe830000,0x3e79bda2,0xbe543e1a,0x3da2be79,0x3e83,0xbda2be79,0x3e1a3e54,
0x80003e83,0x8000be83,0x80003e83,0x8000be83,0x3e830000,0xbe830000,0x3e830000,0xbe830000,0xbe793da2,0x3e830000,0xbe79bda2,0x3e543e1a,0x3da23e79,0xbe83,0xbda23e79,0x3e1abe54,
0x80003e83,0x3e1abe54,0xbe793da2,0x3e793da2,0x3e830000,0xbe54be1a,0x3da23e79,0x3da2be79,0x80003e83,0x3e54be1a,0xbe79bda2,0x3da23e79,0x3e830000,0xbe1abe54,0xbda23e79,0x3e79bda2,
0x80003e83,0x3e79bda2,0xbe1abe54,0xbe1a3e54,0x3e830000,0xbda2be79,0xbe543e1a,0x3e543e1a,0x80003e83,0x3e830000,0x8000be83,0xbe830000,0x3e830000,0xbe83,0xbe830000,0x3e83,
0xbe1abe54,0x80003e83,0x3e1abe54,0xbe793da2,0xbe543e1a,0x3e830000,0xbe54be1a,0x3da23e79,0x3e1abe54,0xbe830000,0x3e1a3e54,0x3da2be79,0xbe54be1a,0x3e83,0x3e54be1a,0xbe79bda2,
0x3e793da2,0x8000be83,0xbe793da2,0x3e1a3e54,0x3da2be79,0xbe830000,0x3da23e79,0x3e54be1a,0x80003e83,0x3e830000,0x8000be83,0xbe830000,0x3e830000,0xbe83,0xbe830000,0x3e83,
0x80003e83,0x3e793da2,0x3e1abe54,0xbe1abe54,0x3e830000,0x3da2be79,0xbe54be1a,0xbe543e1a,0x80003e83,0x3e543e1a,0x3e79bda2,0x3da2be79,0x3e830000,0x3e1abe54,0xbda2be79,0xbe79bda2,
0x80003e83,0x3e1a3e54,0x3e793da2,0x3e79bda2,0x3e830000,0x3e54be1a,0x3da2be79,0xbda2be79,0x80003e83,0x3da23e79,0x3e1a3e54,0x3e543e1a,0x3e830000,0x3e79bda2,0x3e54be1a,0x3e1abe54,
0xbe793da2,0x80003e83,0x3e793da2,0x3e1abe54,0x3da23e79,0x3e830000,0x3da2be79,0xbe54be1a,0xbe1abe54,0xbe830000,0xbe1a3e54,0x3da23e79,0xbe543e1a,0x3e83,0x3e543e1a,0x3e79bda2,
0x3e1abe54,0x8000be83,0xbe1abe54,0xbe79bda2,0xbe54be1a,0xbe830000,0xbe543e1a,0xbda23e79,0x3e793da2,0x3e830000,0x3e79bda2,0x3e54be1a,0x3da2be79,0xbe83,0xbda2be79,0xbe1abe54,
0,0,0,0,0,0,0,0,0,0,0,0,0,0,0,0,
0,0,0,0,0,0,0,0,0,0,0,0,0,0,0,0,
0,0,0,0,0,0,0,0,0,0,0,0,0,0,0,0,
0xbe1abe54,0x3e79bda2,0x80003e83,0xbe79bda2,0xbe543e1a,0xbda2be79,0x3e830000,0xbda23e79,0x3e793da2,0xbe543e1a,0x8000be83,0x3e543e1a,0x3da2be79,0x3e1a3e54,0xbe830000,0x3e1abe54,
0,0,0,0,0,0,0,0,0,0,0,0,0,0,0,0,
0,0,0,0,0,0,0,0,0,0,0,0,0,0,0,0,
0xbe793da2,0x3e1abe54,0x80003e83,0xbe1abe54,0x3da23e79,0xbe54be1a,0x3e830000,0xbe543e1a,0x3e1abe54,0xbda23e79,0x8000be83,0x3da23e79,0xbe54be1a,0x3e793da2,0xbe830000,0x3e79bda2,
0x80003e83,0x8000be83,0x80003e83,0x8000be83,0x3e830000,0xbe830000,0x3e830000,0xbe830000,0xbe1abe54,0x3da23e79,0x8000be83,0xbda23e79,0xbe543e1a,0x3e79bda2,0xbe830000,0x3e793da2,
0,0,0,0,0,0,0,0,0,0,0,0,0,0,0,0,
0,0,0,0,0,0,0,0,0,0,0,0,0,0,0,0,
0x3e793da2,0xbe1abe54,0x80003e83,0x3e1abe54,0x3da2be79,0xbe543e1a,0x3e830000,0xbe54be1a,0xbe793da2,0x3e543e1a,0x8000be83,0xbe543e1a,0x3da23e79,0x3e1abe54,0xbe830000,0x3e1a3e54,
0x3e1abe54,0xbe79bda2,0x80003e83,0x3e79bda2,0xbe54be1a,0xbda23e79,0x3e830000,0xbda2be79,0x80003e83,0x3e830000,0x8000be83,0xbe830000,0x3e830000,0xbe83,0xbe830000,0x3e83,
0,0,0,0,0,0,0,0,0,0,0,0,0,0,0,0,
0,0,0,0,0,0,0,0,0,0,0,0,0,0,0,0,
0xbe1abe54,0xbe793da2,0x80003e83,0x3e793da2,0xbe543e1a,0x3da23e79,0x3e830000,0x3da2be79,0x3e793da2,0x3e54be1a,0x8000be83,0xbe54be1a,0x3da2be79,0xbe1abe54,0xbe830000,0xbe1a3e54,
0xbe793da2,0xbe1a3e54,0x80003e83,0x3e1a3e54,0x3da23e79,0x3e543e1a,0x3e830000,0x3e54be1a,0x3e1abe54,0x3da2be79,0x8000be83,0xbda2be79,0xbe54be1a,0xbe79bda2,0xbe830000,0xbe793da2,
0,0,0,0,0,0,0,0,0,0,0,0,0,0,0,0,
0x3e1abe54,0x3e1a3e54,0xbe793da2,0x8000be83,0xbe54be1a,0x3e54be1a,0x3da23e79,0xbe830000,0xbe793da2,0x3da2be79,0x3e1a3e54,0xbe830000,0x3da23e79,0xbe79bda2,0x3e54be1a,0x3e83,
0,0,0,0,0,0,0,0,0,0,0,0,0,0,0,0,
0x3e793da2,0xbe1a3e54,0xbe1abe54,0x3e79bda2,0x3da2be79,0x3e543e1a,0xbe543e1a,0xbda2be79,0x3e1abe54,0x3da23e79,0xbe79bda2,0x3e54be1a,0xbe54be1a,0x3e79bda2,0xbda23e79,0xbe1abe54,
0x3e793da2,0xbe793da2,0x3e1abe54,0x80003e83,0x3da2be79,0x3da23e79,0xbe54be1a,0x3e830000,0xbe1abe54,0x3e543e1a,0xbe79bda2,0x3e830000,0xbe543e1a,0x3e1abe54,0xbda23e79,0xbe83,
0x80003e83,0x8000be83,0x80003e83,0x8000be83,0x3e830000,0xbe830000,0x3e830000,0xbe830000,0x3e1abe54,0xbe543e1a,0x3e79bda2,0xbe830000,0xbe54be1a,0x3e1a3e54,0xbda2be79,0x3e83,
0xbe1abe54,0x3e793da2,0xbe793da2,0x3e1abe54,0xbe543e1a,0x3da2be79,0x3da23e79,0xbe54be1a,0xbe793da2,0x3e54be1a,0xbe1a3e54,0x3da2be79,0x3da23e79,0xbe1abe54,0x3e543e1a,0xbe79bda2,
0x80003e83,0x8000be83,0x80003e83,0x8000be83,0x3e830000,0xbe830000,0x3e830000,0xbe830000,0x3e793da2,0xbe54be1a,0x3e1a3e54,0xbda2be79,0x3da2be79,0xbe1a3e54,0x3e54be1a,0xbe793da2,
0xbe793da2,0x3e793da2,0xbe1abe54,0x80003e83,0x3da23e79,0x3da2be79,0xbe543e1a,0x3e830000,0x3e793da2,0xbda2be79,0xbe1a3e54,0x3e830000,0x3da2be79,0xbe793da2,0x3e543e1a,0xbe83,
0xbe1abe54,0xbe1a3e54,0x3e793da2,0x8000be83,0xbe543e1a,0x3e543e1a,0x3da2be79,0xbe830000,0x80003e83,0x3e830000,0x8000be83,0xbe830000,0x3e830000,0xbe83,0xbe830000,0x3e83,
0x3e1abe54,0xbe793da2,0x3e793da2,0xbe1abe54,0xbe54be1a,0x3da23e79,0x3da2be79,0xbe543e1a,0xbe1abe54,0xbda23e79,0x3e79bda2,0xbe54be1a,0xbe543e1a,0x3e793da2,0xbda2be79,0xbe1a3e54,
0xbe793da2,0x3e1a3e54,0x3e1abe54,0xbe79bda2,0x3da23e79,0x3e54be1a,0xbe54be1a,0xbda23e79,0x80003e83,0x3e830000,0x8000be83,0xbe830000,0x3e830000,0xbe83,0xbe830000,0x3e83,
0x3e1abe54,0xbe1abe54,0xbe793da2,0x80003e83,0xbe54be1a,0xbe543e1a,0x3da23e79,0x3e830000,0xbe793da2,0xbda23e79,0x3e1a3e54,0x3e830000,0x3da23e79,0x3e793da2,0x3e54be1a,0xbe83,
0x3e793da2,0x3e79bda2,0x3e1abe54,0x8000be83,0x3da2be79,0xbda2be79,0xbe54be1a,0xbe830000,0xbe1abe54,0xbe54be1a,0xbe79bda2,0xbe830000,0xbe543e1a,0xbe1a3e54,0xbda23e79,0x3e83,
0x3e793da2,0x3e1abe54,0xbe1abe54,0xbe793da2,0x3da2be79,0xbe54be1a,0xbe543e1a,0x3da23e79,0x3e1abe54,0xbda2be79,0xbe79bda2,0xbe543e1a,0xbe54be1a,0xbe793da2,0xbda23e79,0x3e1a3e54,
0xbe1abe54,0xbe79bda2,0xbe793da2,0xbe1a3e54,0xbe543e1a,0xbda23e79,0x3da23e79,0x3e543e1a,0xbe793da2,0xbe543e1a,0xbe1a3e54,0xbda23e79,0x3da23e79,0x3e1a3e54,0x3e543e1a,0x3e793da2,
0xbe163dda,0,0,0,0,0xbe163dda,0,0,0,0,0xbe163dda,0,0,0,0,0xbe163dda,
0xbe253da8,0,0,0,0,0xbe253da8,0,0,0,0,0xbe253da8,0,0,0,0,0xbe253da8,
0xbd65be30,0,0,0,0,0xbd65be30,0,0,0,0,0xbd65be30,0,0,0,0,0xbd65be30,
0x3ce8be37,0,0,0,0,0x3ce8be37,0,0,0,0,0x3ce8be37,0,0,0,0,0x3ce8be37,
0xbe303d65,0,0,0,0,0xbe303d65,0,0,0,0,0xbe303d65,0,0,0,0,0xbe303d65,
0xbe373ce8,0,0,0,0,0xbe373ce8,0,0,0,0,0xbe373ce8,0,0,0,0,0xbe373ce8,
0x3ddabe16,0,0,0,0,0x3ddabe16,0,0,0,0,0x3ddabe16,0,0,0,0,0x3ddabe16,
0x3e25bda8,0,0,0,0,0x3e25bda8,0,0,0,0,0x3e25bda8,0,0,0,0,0x3e25bda8,
0xbe390000,0,0,0,0,0xbe390000,0,0,0,0,0xbe390000,0,0,0,0,0xbe390000,
0xbe37bce8,0,0,0,0,0xbe37bce8,0,0,0,0,0xbe37bce8,0,0,0,0,0xbe37bce8,
0x3e390000,0,0,0,0,0x3e390000,0,0,0,0,0x3e390000,0,0,0,0,0x3e390000,
0x3e253da8,0,0,0,0,0x3e253da8,0,0,0,0,0x3e253da8,0,0,0,0,0x3e253da8,
0xbe30bd65,0,0,0,0,0xbe30bd65,0,0,0,0,0xbe30bd65,0,0,0,0,0xbe30bd65,
0xbe25bda8,0,0,0,0,0xbe25bda8,0,0,0,0,0xbe25bda8,0,0,0,0,0xbe25bda8,
0x3dda3e16,0,0,0,0,0x3dda3e16,0,0,0,0,0x3dda3e16,0,0,0,0,0x3dda3e16,
0x3ce83e37,0,0,0,0,0x3ce83e37,0,0,0,0,0x3ce83e37,0,0,0,0,0x3ce83e37,
0xbe16bdda,0,0,0,0,0xbe16bdda,0,0,0,0,0xbe16bdda,0,0,0,0,0xbe16bdda,
0xbe03be03,0,0,0,0,0xbe03be03,0,0,0,0,0xbe03be03,0,0,0,0,0xbe03be03,
0xbd653e30,0,0,0,0,0xbd653e30,0,0,0,0,0xbd653e30,0,0,0,0,0xbd653e30,
0xbe033e03,0,0,0,0,0xbe033e03,0,0,0,0,0xbe033e03,0,0,0,0,0xbe033e03,
0xbddabe16,0,0,0,0,0xbddabe16,0,0,0,0,0xbddabe16,0,0,0,0,0xbddabe16,
0xbda8be25,0,0,0,0,0xbda8be25,0,0,0,0,0xbda8be25,0,0,0,0,0xbda8be25,
0xbe303d65,0,0,0,0,0xbe303d65,0,0,0,0,0xbe303d65,0,0,0,0,0xbe303d65,
0xbe37bce8,0,0,0,0,0xbe37bce8,0,0,0,0,0xbe37bce8,0,0,0,0,0xbe37bce8,
0xbd65be30,0,0,0,0,0xbd65be30,0,0,0,0,0xbd65be30,0,0,0,0,0xbd65be30,
0xbce8be37,0,0,0,0,0xbce8be37,0,0,0,0,0xbce8be37,0,0,0,0,0xbce8be37,
0xbe16bdda,0,0,0,0,0xbe16bdda,0,0,0,0,0xbe16bdda,0,0,0,0,0xbe16bdda,
0xbda8be25,0,0,0,0,0xbda8be25,0,0,0,0,0xbda8be25,0,0,0,0,0xbda8be25,
0x3e390000,0,0,0,0,0x3e390000,0,0,0,0,0x3e390000,0,0,0,0,0x3e390000,
0x3e033e03,0,0,0,0,0x3e033e03,0,0,0,0,0x3e033e03,0,0,0,0,0x3e033e03,
0xbd653e30,0,0,0,0,0xbd653e30,0,0,0,0,0xbd653e30,0,0,0,0,0xbd653e30,
0xbe373ce8,0,0,0,0,0xbe373ce8,0,0,0,0,0xbe373ce8,0,0,0,0,0xbe373ce8,
0x80003e39,0,0,0,0,0x80003e39,0,0,0,0,0x80003e39,0,0,0,0,0x80003e39,
0xbe033e03,0,0,0,0,0xbe033e03,0,0,0,0,0xbe033e03,0,0,0,0,0xbe033e03,
0xbddabe16,0,0,0,0,0xbddabe16,0,0,0,0,0xbddabe16,0,0,0,0,0xbddabe16,
0x3da8be25,0,0,0,0,0x3da8be25,0,0,0,0,0x3da8be25,0,0,0,0,0x3da8be25,
0xbe390000,0,0,0,0,0xbe390000,0,0,0,0,0xbe390000,0,0,0,0,0xbe390000,
0xbe03be03,0,0,0,0,0xbe03be03,0,0,0,0,0xbe03be03,0,0,0,0,0xbe03be03,
0x3e390000,0,0,0,0,0x3e390000,0,0,0,0,0x3e390000,0,0,0,0,0x3e390000,
0x3da83e25,0,0,0,0,0x3da83e25,0,0,0,0,0x3da83e25,0,0,0,0,0x3da83e25,
0x8000be39,0,0,0,0,0x8000be39,0,0,0,0,0x8000be39,0,0,0,0,0x8000be39,
0x3e03be03,0,0,0,0,0x3e03be03,0,0,0,0,0x3e03be03,0,0,0,0,0x3e03be03,
0xbdda3e16,0,0,0,0,0xbdda3e16,0,0,0,0,0xbdda3e16,0,0,0,0,0xbdda3e16,
0xbe37bce8,0,0,0,0,0xbe37bce8,0,0,0,0,0xbe37bce8,0,0,0,0,0xbe37bce8,
0x3e390000,0,0,0,0,0x3e390000,0,0,0,0,0x3e390000,0,0,0,0,0x3e390000,
0x3e033e03,0,0,0,0,0x3e033e03,0,0,0,0,0x3e033e03,0,0,0,0,0x3e033e03,
0xbd65be30,0,0,0,0,0xbd65be30,0,0,0,0,0xbd65be30,0,0,0,0,0xbd65be30,
0x3e03be03,0,0,0,0,0x3e03be03,0,0,0,0,0x3e03be03,0,0,0,0,0x3e03be03,
0x80003e39,0,0,0,0,0x80003e39,0,0,0,0,0x80003e39,0,0,0,0,0x80003e39,
0xbe033e03,0,0,0,0,0xbe033e03,0,0,0,0,0xbe033e03,0,0,0,0,0xbe033e03,
0x3e303d65,0,0,0,0,0x3e303d65,0,0,0,0,0x3e303d65,0,0,0,0,0x3e303d65,
0x3ce83e37,0,0,0,0,0x3ce83e37,0,0,0,0,0x3ce83e37,0,0,0,0,0x3ce83e37,
0xbe390000,0,0,0,0,0xbe390000,0,0,0,0,0xbe390000,0,0,0,0,0xbe390000,
0xbe03be03,0,0,0,0,0xbe03be03,0,0,0,0,0xbe03be03,0,0,0,0,0xbe03be03,
0xbe163dda,0,0,0,0,0xbe163dda,0,0,0,0,0xbe163dda,0,0,0,0,0xbe163dda,
0xbe25bda8,0,0,0,0,0xbe25bda8,0,0,0,0,0xbe25bda8,0,0,0,0,0xbe25bda8,
0xbe16bdda,0,0,0,0,0xbe16bdda,0,0,0,0,0xbe16bdda,0,0,0,0,0xbe16bdda,
0x3da8be25,0,0,0,0,0x3da8be25,0,0,0,0,0x3da8be25,0,0,0,0,0x3da8be25,
0x3e16bdda,0,0,0,0,0x3e16bdda,0,0,0,0,0x3e16bdda,0,0,0,0,0x3e16bdda,
0x3da83e25,0,0,0,0,0x3da83e25,0,0,0,0,0x3da83e25,0,0,0,0,0x3da83e25,
0x3e303d65,0,0,0,0,0x3e303d65,0,0,0,0,0x3e303d65,0,0,0,0,0x3e303d65,
0xbce83e37,0,0,0,0,0xbce83e37,0,0,0,0,0xbce83e37,0,0,0,0,0xbce83e37,
0xbe303d65,0,0,0,0,0xbe303d65,0,0,0,0,0xbe303d65,0,0,0,0,0xbe303d65,
0xbce8be37,0,0,0,0,0xbce8be37,0,0,0,0,0xbce8be37,0,0,0,0,0xbce8be37,
0xbe390000,0,0,0,0,0xbe390000,0,0,0,0,0xbe390000,0,0,0,0,0xbe390000,
0xbce8be37,0,0,0,0,0xbce8be37,0,0,0,0,0xbce8be37,0,0,0,0,0xbce8be37,
0x3e390000,0,0,0,0,0x3e390000,0,0,0,0,0x3e390000,0,0,0,0,0x3e390000,
0xbce83e37,0,0,0,0,0xbce83e37,0,0,0,0,0xbce83e37,0,0,0,0,0xbce83e37,
0x3e30bd65,0,0,0,0,0x3e30bd65,0,0,0,0,0x3e30bd65,0,0,0,0,0x3e30bd65,
0x3da83e25,0,0,0,0,0x3da83e25,0,0,0,0,0x3da83e25,0,0,0,0,0x3da83e25,
0xbe30bd65,0,0,0,0,0xbe30bd65,0,0,0,0,0xbe30bd65,0,0,0,0,0xbe30bd65,
0x3da8be25,0,0,0,0,0x3da8be25,0,0,0,0,0x3da8be25,0,0,0,0,0x3da8be25,
0xbe163dda,0,0,0,0,0xbe163dda,0,0,0,0,0xbe163dda,0,0,0,0,0xbe163dda,
0xbe03be03,0,0,0,0,0xbe03be03,0,0,0,0,0xbe03be03,0,0,0,0,0xbe03be03,
0x3e163dda,0,0,0,0,0x3e163dda,0,0,0,0,0x3e163dda,0,0,0,0,0x3e163dda,
0xbe033e03,0,0,0,0,0xbe033e03,0,0,0,0,0xbe033e03,0,0,0,0,0xbe033e03,
0x3ddabe16,0,0,0,0,0x3ddabe16,0,0,0,0,0x3ddabe16,0,0,0,0,0x3ddabe16,
0x3e253da8,0,0,0,0,0x3e253da8,0,0,0,0,0x3e253da8,0,0,0,0,0x3e253da8,
0xbddabe16,0,0,0,0,0xbddabe16,0,0,0,0,0xbddabe16,0,0,0,0,0xbddabe16,
0x3e25bda8,0,0,0,0,0x3e25bda8,0,0,0,0,0x3e25bda8,0,0,0,0,0x3e25bda8,
0xbd653e30,0,0,0,0,0xbd653e30,0,0,0,0,0xbd653e30,0,0,0,0,0xbd653e30,
0xbe37bce8,0,0,0,0,0xbe37bce8,0,0,0,0,0xbe37bce8,0,0,0,0,0xbe37bce8,
0x3d653e30,0,0,0,0,0x3d653e30,0,0,0,0,0x3d653e30,0,0,0,0,0x3d653e30,
0xbe373ce8,0,0,0,0,0xbe373ce8,0,0,0,0,0xbe373ce8,0,0,0,0,0xbe373ce8,
0x3d653e30,0,0,0,0,0x3d653e30,0,0,0,0,0x3d653e30,0,0,0,0,0x3d653e30,
0xbe37bce8,0,0,0,0,0xbe37bce8,0,0,0,0,0xbe37bce8,0,0,0,0,0xbe37bce8,
0xbe390000,0,0,0,0,0xbe390000,0,0,0,0,0xbe390000,0,0,0,0,0xbe390000,
0x3e03be03,0,0,0,0,0x3e03be03,0,0,0,0,0x3e03be03,0,0,0,0,0x3e03be03,
0x3ddabe16,0,0,0,0,0x3ddabe16,0,0,0,0,0x3ddabe16,0,0,0,0,0x3ddabe16,
0x3da83e25,0,0,0,0,0x3da83e25,0,0,0,0,0x3da83e25,0,0,0,0,0x3da83e25,
0x80003e39,0,0,0,0,0x80003e39,0,0,0,0,0x80003e39,0,0,0,0,0x80003e39,
0xbe03be03,0,0,0,0,0xbe03be03,0,0,0,0,0xbe03be03,0,0,0,0,0xbe03be03,
0xbe390000,0,0,0,0,0xbe390000,0,0,0,0,0xbe390000,0,0,0,0,0xbe390000,
0x3da8be25,0,0,0,0,0x3da8be25,0,0,0,0,0x3da8be25,0,0,0,0,0x3da8be25,
0x3e390000,0,0,0,0,0x3e390000,0,0,0,0,0x3e390000,0,0,0,0,0x3e390000,
0xbe033e03,0,0,0,0,0xbe033e03,0,0,0,0,0xbe033e03,0,0,0,0,0xbe033e03,
0x3dda3e16,0,0,0,0,0x3dda3e16,0,0,0,0,0x3dda3e16,0,0,0,0,0x3dda3e16,
0xbe373ce8,0,0,0,0,0xbe373ce8,0,0,0,0,0xbe373ce8,0,0,0,0,0xbe373ce8,
0x8000be39,0,0,0,0,0x8000be39,0,0,0,0,0x8000be39,0,0,0,0,0x8000be39,
0x3e033e03,0,0,0,0,0x3e033e03,0,0,0,0,0x3e033e03,0,0,0,0,0x3e033e03,
0x3d65be30,0,0,0,0,0x3d65be30,0,0,0,0,0x3d65be30,0,0,0,0,0x3d65be30,
0x3e033e03,0,0,0,0,0x3e033e03,0,0,0,0,0x3e033e03,0,0,0,0,0x3e033e03,
0xbe390000,0,0,0,0,0xbe390000,0,0,0,0,0xbe390000,0,0,0,0,0xbe390000,
0x3e03be03,0,0,0,0,0x3e03be03,0,0,0,0,0x3e03be03,0,0,0,0,0x3e03be03,
0xbe303d65,0,0,0,0,0xbe303d65,0,0,0,0,0xbe303d65,0,0,0,0,0xbe303d65,
0x3ce8be37,0,0,0,0,0x3ce8be37,0,0,0,0,0x3ce8be37,0,0,0,0,0x3ce8be37,
0x80003e39,0,0,0,0,0x80003e39,0,0,0,0,0x80003e39,0,0,0,0,0x80003e39,
0xbe03be03,0,0,0,0,0xbe03be03,0,0,0,0,0xbe03be03,0,0,0,0,0xbe03be03,
0x3e163dda,0,0,0,0,0x3e163dda,0,0,0,0,0x3e163dda,0,0,0,0,0x3e163dda,
0xbe253da8,0,0,0,0,0xbe253da8,0,0,0,0,0xbe253da8,0,0,0,0,0xbe253da8,
0x3e390000,0,0,0,0,0x3e390000,0,0,0,0,0x3e390000,0,0,0,0,0x3e390000,
0xbe033e03,0,0,0,0,0xbe033e03,0,0,0,0,0xbe033e03,0,0,0,0,0xbe033e03,
0x3d65be30,0,0,0,0,0x3d65be30,0,0,0,0,0x3d65be30,0,0,0,0,0x3d65be30,
0x3ce83e37,0,0,0,0,0x3ce83e37,0,0,0,0,0x3ce83e37,0,0,0,0,0x3ce83e37,
0x3e163dda,0,0,0,0,0x3e163dda,0,0,0,0,0x3e163dda,0,0,0,0,0x3e163dda,
0xbe25bda8,0,0,0,0,0xbe25bda8,0,0,0,0,0xbe25bda8,0,0,0,0,0xbe25bda8,
0xbddabe16,0,0,0,0,0xbddabe16,0,0,0,0,0xbddabe16,0,0,0,0,0xbddabe16,
0x3e253da8,0,0,0,0,0x3e253da8,0,0,0,0,0x3e253da8,0,0,0,0,0x3e253da8,
0x3e303d65,0,0,0,0,0x3e303d65,0,0,0,0,0x3e303d65,0,0,0,0,0x3e303d65,
0xbe37bce8,0,0,0,0,0xbe37bce8,0,0,0,0,0xbe37bce8,0,0,0,0,0xbe37bce8,
0xbe390000,0,0,0,0,0xbe390000,0,0,0,0,0xbe390000,0,0,0,0,0xbe390000,
0x3e25bda8,0,0,0,0,0x3e25bda8,0,0,0,0,0x3e25bda8,0,0,0,0,0x3e25bda8,
0x3e390000,0,0,0,0,0x3e390000,0,0,0,0,0x3e390000,0,0,0,0,0x3e390000,
0xbe373ce8,0,0,0,0,0xbe373ce8,0,0,0,0,0xbe373ce8,0,0,0,0,0xbe373ce8,
0xbdda3e16,0,0,0,0,0xbdda3e16,0,0,0,0,0xbdda3e16,0,0,0,0,0xbdda3e16,
0x3ce8be37,0,0,0,0,0x3ce8be37,0,0,0,0,0x3ce8be37,0,0,0,0,0x3ce8be37,
0x3e30bd65,0,0,0,0,0x3e30bd65,0,0,0,0,0x3e30bd65,0,0,0,0,0x3e30bd65,
0xbe253da8,0,0,0,0,0xbe253da8,0,0,0,0,0xbe253da8,0,0,0,0,0xbe253da8,
0x3d653e30,0,0,0,0,0x3d653e30,0,0,0,0,0x3d653e30,0,0,0,0,0x3d653e30,
0xbe03be03,0,0,0,0,0xbe03be03,0,0,0,0,0xbe03be03,0,0,0,0,0xbe03be03,
0x3e16bdda,0,0,0,0,0x3e16bdda,0,0,0,0,0x3e16bdda,0,0,0,0,0x3e16bdda,
0xbe033e03,0,0,0,0,0xbe033e03,0,0,0,0,0xbe033e03,0,0,0,0,0xbe033e03,
0x3e303d65,0,0,0,0,0x3e303d65,0,0,0,0,0x3e303d65,0,0,0,0,0x3e303d65,
0xbe373ce8,0,0,0,0,0xbe373ce8,0,0,0,0,0xbe373ce8,0,0,0,0,0xbe373ce8,
0x3ddabe16,0,0,0,0,0x3ddabe16,0,0,0,0,0x3ddabe16,0,0,0,0,0x3ddabe16,
0xbda83e25,0,0,0,0,0xbda83e25,0,0,0,0,0xbda83e25,0,0,0,0,0xbda83e25,
0x3e16bdda,0,0,0,0,0x3e16bdda,0,0,0,0,0x3e16bdda,0,0,0,0,0x3e16bdda,
0xbda83e25,0,0,0,0,0xbda83e25,0,0,0,0,0xbda83e25,0,0,0,0,0xbda83e25,
0x3d65be30,0,0,0,0,0x3d65be30,0,0,0,0,0x3d65be30,0,0,0,0,0x3d65be30,
0xbce83e37,0,0,0,0,0xbce83e37,0,0,0,0,0xbce83e37,0,0,0,0,0xbce83e37,
};
constexpr unsigned long long COS_PK0 = 0x3f903f9a3fa03fa2ull;
constexpr unsigned long long COS_PK1 = 0x3f133f3e3f653f83ull;
constexpr unsigned long long COS_PK2 = 0x3e4b3ec8ull;

__device__ __forceinline__ void wgmma_ss_n80_z(float (&d)[40], uint64_t da, uint64_t db) {
  asm volatile("{\n.reg .pred p;\nsetp.ne.b32 p, 0, 0;\nwgmma.mma_async.sync.aligned.m64n80k16.f32.bf16.bf16 {%0,%1,%2,%3,%4,%5,%6,%7,%8,%9,%10,%11,%12,%13,%14,%15,%16,%17,%18,%19,%20,%21,%22,%23,%24,%25,%26,%27,%28,%29,%30,%31,%32,%33,%34,%35,%36,%37,%38,%39}, %40, %41, p, 1, 1, 1, 0;\n}\n"
    : "+f"(d[0]), "+f"(d[1]), "+f"(d[2]), "+f"(d[3]), "+f"(d[4]), "+f"(d[5]), "+f"(d[6]), "+f"(d[7]), "+f"(d[8]), "+f"(d[9]), "+f"(d[10]), "+f"(d[11]), "+f"(d[12]), "+f"(d[13]), "+f"(d[14]), "+f"(d[15]), "+f"(d[16]), "+f"(d[17]), "+f"(d[18]), "+f"(d[19]), "+f"(d[20]), "+f"(d[21]), "+f"(d[22]), "+f"(d[23]), "+f"(d[24]), "+f"(d[25]), "+f"(d[26]), "+f"(d[27]), "+f"(d[28]), "+f"(d[29]), "+f"(d[30]), "+f"(d[31]), "+f"(d[32]), "+f"(d[33]), "+f"(d[34]), "+f"(d[35]), "+f"(d[36]), "+f"(d[37]), "+f"(d[38]), "+f"(d[39])
    : "l"(da), "l"(db));
}
__device__ __forceinline__ void wgmma_ss_n80_a(float (&d)[40], uint64_t da, uint64_t db) {
  asm volatile("{\n.reg .pred p;\nsetp.ne.b32 p, 1, 0;\nwgmma.mma_async.sync.aligned.m64n80k16.f32.bf16.bf16 {%0,%1,%2,%3,%4,%5,%6,%7,%8,%9,%10,%11,%12,%13,%14,%15,%16,%17,%18,%19,%20,%21,%22,%23,%24,%25,%26,%27,%28,%29,%30,%31,%32,%33,%34,%35,%36,%37,%38,%39}, %40, %41, p, 1, 1, 1, 0;\n}\n"
    : "+f"(d[0]), "+f"(d[1]), "+f"(d[2]), "+f"(d[3]), "+f"(d[4]), "+f"(d[5]), "+f"(d[6]), "+f"(d[7]), "+f"(d[8]), "+f"(d[9]), "+f"(d[10]), "+f"(d[11]), "+f"(d[12]), "+f"(d[13]), "+f"(d[14]), "+f"(d[15]), "+f"(d[16]), "+f"(d[17]), "+f"(d[18]), "+f"(d[19]), "+f"(d[20]), "+f"(d[21]), "+f"(d[22]), "+f"(d[23]), "+f"(d[24]), "+f"(d[25]), "+f"(d[26]), "+f"(d[27]), "+f"(d[28]), "+f"(d[29]), "+f"(d[30]), "+f"(d[31]), "+f"(d[32]), "+f"(d[33]), "+f"(d[34]), "+f"(d[35]), "+f"(d[36]), "+f"(d[37]), "+f"(d[38]), "+f"(d[39])
    : "l"(da), "l"(db));
}

__device__ __forceinline__ void wgmma_rs_n40_z(float (&d)[20], uint32_t a0, uint32_t a1, uint32_t a2, uint32_t a3, uint64_t db) {
  asm volatile("{\n.reg .pred p;\nsetp.ne.b32 p, 0, 0;\nwgmma.mma_async.sync.aligned.m64n40k16.f32.bf16.bf16 {%0,%1,%2,%3,%4,%5,%6,%7,%8,%9,%10,%11,%12,%13,%14,%15,%16,%17,%18,%19}, {%20,%21,%22,%23}, %24, p, 1, 1, 0;\n}\n"
    : "+f"(d[0]), "+f"(d[1]), "+f"(d[2]), "+f"(d[3]), "+f"(d[4]), "+f"(d[5]), "+f"(d[6]), "+f"(d[7]), "+f"(d[8]), "+f"(d[9]), "+f"(d[10]), "+f"(d[11]), "+f"(d[12]), "+f"(d[13]), "+f"(d[14]), "+f"(d[15]), "+f"(d[16]), "+f"(d[17]), "+f"(d[18]), "+f"(d[19])
    : "r"(a0), "r"(a1), "r"(a2), "r"(a3), "l"(db));
}
__device__ __forceinline__ void wgmma_rs_n40_a(float (&d)[20], uint32_t a0, uint32_t a1, uint32_t a2, uint32_t a3, uint64_t db) {
  asm volatile("{\n.reg .pred p;\nsetp.ne.b32 p, 1, 0;\nwgmma.mma_async.sync.aligned.m64n40k16.f32.bf16.bf16 {%0,%1,%2,%3,%4,%5,%6,%7,%8,%9,%10,%11,%12,%13,%14,%15,%16,%17,%18,%19}, {%20,%21,%22,%23}, %24, p, 1, 1, 0;\n}\n"
    : "+f"(d[0]), "+f"(d[1]), "+f"(d[2]), "+f"(d[3]), "+f"(d[4]), "+f"(d[5]), "+f"(d[6]), "+f"(d[7]), "+f"(d[8]), "+f"(d[9]), "+f"(d[10]), "+f"(d[11]), "+f"(d[12]), "+f"(d[13]), "+f"(d[14]), "+f"(d[15]), "+f"(d[16]), "+f"(d[17]), "+f"(d[18]), "+f"(d[19])
    : "r"(a0), "r"(a1), "r"(a2), "r"(a3), "l"(db));
}

__device__ __forceinline__ void wgmma_rs_n128_z(float (&d)[64], uint32_t a0, uint32_t a1, uint32_t a2, uint32_t a3, uint64_t db) {
  asm volatile("{\n.reg .pred p;\nsetp.ne.b32 p, 0, 0;\nwgmma.mma_async.sync.aligned.m64n128k16.f32.bf16.bf16 {%0,%1,%2,%3,%4,%5,%6,%7,%8,%9,%10,%11,%12,%13,%14,%15,%16,%17,%18,%19,%20,%21,%22,%23,%24,%25,%26,%27,%28,%29,%30,%31,%32,%33,%34,%35,%36,%37,%38,%39,%40,%41,%42,%43,%44,%45,%46,%47,%48,%49,%50,%51,%52,%53,%54,%55,%56,%57,%58,%59,%60,%61,%62,%63}, {%64,%65,%66,%67}, %68, p, 1, 1, 1;\n}\n"
    : "+f"(d[0]), "+f"(d[1]), "+f"(d[2]), "+f"(d[3]), "+f"(d[4]), "+f"(d[5]), "+f"(d[6]), "+f"(d[7]), "+f"(d[8]), "+f"(d[9]), "+f"(d[10]), "+f"(d[11]), "+f"(d[12]), "+f"(d[13]), "+f"(d[14]), "+f"(d[15]), "+f"(d[16]), "+f"(d[17]), "+f"(d[18]), "+f"(d[19]), "+f"(d[20]), "+f"(d[21]), "+f"(d[22]), "+f"(d[23]), "+f"(d[24]), "+f"(d[25]), "+f"(d[26]), "+f"(d[27]), "+f"(d[28]), "+f"(d[29]), "+f"(d[30]), "+f"(d[31]), "+f"(d[32]), "+f"(d[33]), "+f"(d[34]), "+f"(d[35]), "+f"(d[36]), "+f"(d[37]), "+f"(d[38]), "+f"(d[39]), "+f"(d[40]), "+f"(d[41]), "+f"(d[42]), "+f"(d[43]), "+f"(d[44]), "+f"(d[45]), "+f"(d[46]), "+f"(d[47]), "+f"(d[48]), "+f"(d[49]), "+f"(d[50]), "+f"(d[51]), "+f"(d[52]), "+f"(d[53]), "+f"(d[54]), "+f"(d[55]), "+f"(d[56]), "+f"(d[57]), "+f"(d[58]), "+f"(d[59]), "+f"(d[60]), "+f"(d[61]), "+f"(d[62]), "+f"(d[63])
    : "r"(a0), "r"(a1), "r"(a2), "r"(a3), "l"(db));
}
__device__ __forceinline__ void wgmma_rs_n128_a(float (&d)[64], uint32_t a0, uint32_t a1, uint32_t a2, uint32_t a3, uint64_t db) {
  asm volatile("{\n.reg .pred p;\nsetp.ne.b32 p, 1, 0;\nwgmma.mma_async.sync.aligned.m64n128k16.f32.bf16.bf16 {%0,%1,%2,%3,%4,%5,%6,%7,%8,%9,%10,%11,%12,%13,%14,%15,%16,%17,%18,%19,%20,%21,%22,%23,%24,%25,%26,%27,%28,%29,%30,%31,%32,%33,%34,%35,%36,%37,%38,%39,%40,%41,%42,%43,%44,%45,%46,%47,%48,%49,%50,%51,%52,%53,%54,%55,%56,%57,%58,%59,%60,%61,%62,%63}, {%64,%65,%66,%67}, %68, p, 1, 1, 1;\n}\n"
    : "+f"(d[0]), "+f"(d[1]), "+f"(d[2]), "+f"(d[3]), "+f"(d[4]), "+f"(d[5]), "+f"(d[6]), "+f"(d[7]), "+f"(d[8]), "+f"(d[9]), "+f"(d[10]), "+f"(d[11]), "+f"(d[12]), "+f"(d[13]), "+f"(d[14]), "+f"(d[15]), "+f"(d[16]), "+f"(d[17]), "+f"(d[18]), "+f"(d[19]), "+f"(d[20]), "+f"(d[21]), "+f"(d[22]), "+f"(d[23]), "+f"(d[24]), "+f"(d[25]), "+f"(d[26]), "+f"(d[27]), "+f"(d[28]), "+f"(d[29]), "+f"(d[30]), "+f"(d[31]), "+f"(d[32]), "+f"(d[33]), "+f"(d[34]), "+f"(d[35]), "+f"(d[36]), "+f"(d[37]), "+f"(d[38]), "+f"(d[39]), "+f"(d[40]), "+f"(d[41]), "+f"(d[42]), "+f"(d[43]), "+f"(d[44]), "+f"(d[45]), "+f"(d[46]), "+f"(d[47]), "+f"(d[48]), "+f"(d[49]), "+f"(d[50]), "+f"(d[51]), "+f"(d[52]), "+f"(d[53]), "+f"(d[54]), "+f"(d[55]), "+f"(d[56]), "+f"(d[57]), "+f"(d[58]), "+f"(d[59]), "+f"(d[60]), "+f"(d[61]), "+f"(d[62]), "+f"(d[63])
    : "r"(a0), "r"(a1), "r"(a2), "r"(a3), "l"(db));
}

__device__ __forceinline__ void wgmma_rs_n32_z(float (&d)[16], uint32_t a0, uint32_t a1, uint32_t a2, uint32_t a3, uint64_t db) {
  asm volatile("{\n.reg .pred p;\nsetp.ne.b32 p, 0, 0;\nwgmma.mma_async.sync.aligned.m64n32k16.f32.bf16.bf16 {%0,%1,%2,%3,%4,%5,%6,%7,%8,%9,%10,%11,%12,%13,%14,%15}, {%16,%17,%18,%19}, %20, p, 1, 1, 0;\n}\n"
    : "+f"(d[0]), "+f"(d[1]), "+f"(d[2]), "+f"(d[3]), "+f"(d[4]), "+f"(d[5]), "+f"(d[6]), "+f"(d[7]), "+f"(d[8]), "+f"(d[9]), "+f"(d[10]), "+f"(d[11]), "+f"(d[12]), "+f"(d[13]), "+f"(d[14]), "+f"(d[15])
    : "r"(a0), "r"(a1), "r"(a2), "r"(a3), "l"(db));
}
__device__ __forceinline__ void wgmma_rs_n32_a(float (&d)[16], uint32_t a0, uint32_t a1, uint32_t a2, uint32_t a3, uint64_t db) {
  asm volatile("{\n.reg .pred p;\nsetp.ne.b32 p, 1, 0;\nwgmma.mma_async.sync.aligned.m64n32k16.f32.bf16.bf16 {%0,%1,%2,%3,%4,%5,%6,%7,%8,%9,%10,%11,%12,%13,%14,%15}, {%16,%17,%18,%19}, %20, p, 1, 1, 0;\n}\n"
    : "+f"(d[0]), "+f"(d[1]), "+f"(d[2]), "+f"(d[3]), "+f"(d[4]), "+f"(d[5]), "+f"(d[6]), "+f"(d[7]), "+f"(d[8]), "+f"(d[9]), "+f"(d[10]), "+f"(d[11]), "+f"(d[12]), "+f"(d[13]), "+f"(d[14]), "+f"(d[15])
    : "r"(a0), "r"(a1), "r"(a2), "r"(a3), "l"(db));
}

__device__ __forceinline__ void wgmma_ss_n32_z(float (&d)[16], uint64_t da, uint64_t db) {
  asm volatile("{\n.reg .pred p;\nsetp.ne.b32 p, 0, 0;\nwgmma.mma_async.sync.aligned.m64n32k16.f32.bf16.bf16 {%0,%1,%2,%3,%4,%5,%6,%7,%8,%9,%10,%11,%12,%13,%14,%15}, %16, %17, p, 1, 1, 1, 0;\n}\n"
    : "+f"(d[0]), "+f"(d[1]), "+f"(d[2]), "+f"(d[3]), "+f"(d[4]), "+f"(d[5]), "+f"(d[6]), "+f"(d[7]), "+f"(d[8]), "+f"(d[9]), "+f"(d[10]), "+f"(d[11]), "+f"(d[12]), "+f"(d[13]), "+f"(d[14]), "+f"(d[15])
    : "l"(da), "l"(db));
}
__device__ __forceinline__ void wgmma_ss_n32_a(float (&d)[16], uint64_t da, uint64_t db) {
  asm volatile("{\n.reg .pred p;\nsetp.ne.b32 p, 1, 0;\nwgmma.mma_async.sync.aligned.m64n32k16.f32.bf16.bf16 {%0,%1,%2,%3,%4,%5,%6,%7,%8,%9,%10,%11,%12,%13,%14,%15}, %16, %17, p, 1, 1, 1, 0;\n}\n"
    : "+f"(d[0]), "+f"(d[1]), "+f"(d[2]), "+f"(d[3]), "+f"(d[4]), "+f"(d[5]), "+f"(d[6]), "+f"(d[7]), "+f"(d[8]), "+f"(d[9]), "+f"(d[10]), "+f"(d[11]), "+f"(d[12]), "+f"(d[13]), "+f"(d[14]), "+f"(d[15])
    : "l"(da), "l"(db));
}

__device__ __forceinline__ void wgmma_ss_n40_z(float (&d)[20], uint64_t da, uint64_t db) {
  asm volatile("{\n.reg .pred p;\nsetp.ne.b32 p, 0, 0;\nwgmma.mma_async.sync.aligned.m64n40k16.f32.bf16.bf16 {%0,%1,%2,%3,%4,%5,%6,%7,%8,%9,%10,%11,%12,%13,%14,%15,%16,%17,%18,%19}, %20, %21, p, 1, 1, 1, 0;\n}\n"
    : "+f"(d[0]), "+f"(d[1]), "+f"(d[2]), "+f"(d[3]), "+f"(d[4]), "+f"(d[5]), "+f"(d[6]), "+f"(d[7]), "+f"(d[8]), "+f"(d[9]), "+f"(d[10]), "+f"(d[11]), "+f"(d[12]), "+f"(d[13]), "+f"(d[14]), "+f"(d[15]), "+f"(d[16]), "+f"(d[17]), "+f"(d[18]), "+f"(d[19])
    : "l"(da), "l"(db));
}
__device__ __forceinline__ void wgmma_ss_n40_a(float (&d)[20], uint64_t da, uint64_t db) {
  asm volatile("{\n.reg .pred p;\nsetp.ne.b32 p, 1, 0;\nwgmma.mma_async.sync.aligned.m64n40k16.f32.bf16.bf16 {%0,%1,%2,%3,%4,%5,%6,%7,%8,%9,%10,%11,%12,%13,%14,%15,%16,%17,%18,%19}, %20, %21, p, 1, 1, 1, 0;\n}\n"
    : "+f"(d[0]), "+f"(d[1]), "+f"(d[2]), "+f"(d[3]), "+f"(d[4]), "+f"(d[5]), "+f"(d[6]), "+f"(d[7]), "+f"(d[8]), "+f"(d[9]), "+f"(d[10]), "+f"(d[11]), "+f"(d[12]), "+f"(d[13]), "+f"(d[14]), "+f"(d[15]), "+f"(d[16]), "+f"(d[17]), "+f"(d[18]), "+f"(d[19])
    : "l"(da), "l"(db));
}

__device__ __forceinline__ void wgmma_rs_n56_z(float (&d)[28], uint32_t a0, uint32_t a1, uint32_t a2, uint32_t a3, uint64_t db) {
  asm volatile("{\n.reg .pred p;\nsetp.ne.b32 p, 0, 0;\nwgmma.mma_async.sync.aligned.m64n56k16.f32.bf16.bf16 {%0,%1,%2,%3,%4,%5,%6,%7,%8,%9,%10,%11,%12,%13,%14,%15,%16,%17,%18,%19,%20,%21,%22,%23,%24,%25,%26,%27}, {%28,%29,%30,%31}, %32, p, 1, 1, 0;\n}\n"
    : "+f"(d[0]), "+f"(d[1]), "+f"(d[2]), "+f"(d[3]), "+f"(d[4]), "+f"(d[5]), "+f"(d[6]), "+f"(d[7]), "+f"(d[8]), "+f"(d[9]), "+f"(d[10]), "+f"(d[11]), "+f"(d[12]), "+f"(d[13]), "+f"(d[14]), "+f"(d[15]), "+f"(d[16]), "+f"(d[17]), "+f"(d[18]), "+f"(d[19]), "+f"(d[20]), "+f"(d[21]), "+f"(d[22]), "+f"(d[23]), "+f"(d[24]), "+f"(d[25]), "+f"(d[26]), "+f"(d[27])
    : "r"(a0), "r"(a1), "r"(a2), "r"(a3), "l"(db));
}
__device__ __forceinline__ void wgmma_rs_n56_a(float (&d)[28], uint32_t a0, uint32_t a1, uint32_t a2, uint32_t a3, uint64_t db) {
  asm volatile("{\n.reg .pred p;\nsetp.ne.b32 p, 1, 0;\nwgmma.mma_async.sync.aligned.m64n56k16.f32.bf16.bf16 {%0,%1,%2,%3,%4,%5,%6,%7,%8,%9,%10,%11,%12,%13,%14,%15,%16,%17,%18,%19,%20,%21,%22,%23,%24,%25,%26,%27}, {%28,%29,%30,%31}, %32, p, 1, 1, 0;\n}\n"
    : "+f"(d[0]), "+f"(d[1]), "+f"(d[2]), "+f"(d[3]), "+f"(d[4]), "+f"(d[5]), "+f"(d[6]), "+f"(d[7]), "+f"(d[8]), "+f"(d[9]), "+f"(d[10]), "+f"(d[11]), "+f"(d[12]), "+f"(d[13]), "+f"(d[14]), "+f"(d[15]), "+f"(d[16]), "+f"(d[17]), "+f"(d[18]), "+f"(d[19]), "+f"(d[20]), "+f"(d[21]), "+f"(d[22]), "+f"(d[23]), "+f"(d[24]), "+f"(d[25]), "+f"(d[26]), "+f"(d[27])
    : "r"(a0), "r"(a1), "r"(a2), "r"(a3), "l"(db));
}

constexpr int NSM = 132, NH = 66;
constexpr int S0 = 0, S1 = 51200, C3 = 153600, RG = 165888;
constexpr int C1 = RG, WP = RG + 18432, TBL = RG + 47104;
constexpr int BARS = RG + 50688;
constexpr int WST = 102400;
constexpr int NBAR = 224;
constexpr int REL = BARS + NBAR * 8;
constexpr int SMEM_BYTES = REL + 16;
constexpr int B_XF = 0, B_CF1 = 15, B_CF3 = 16, B_WF = 17, B_P1D = 18, B_WFREE = 20, B_REL = 21, B_SIG = 24;
constexpr int B_RF = 32, B_RE = 45, B_YF = 58, B_WRD = 73, B_SFREE = 87, B_WCH = 126, B_RDY = 131, B_WE = 197, B_WL = 209;
constexpr int CNT_P1 = 0, CNT_P2 = 4, CNT_W = 8, NCLS = 9, CNT_DONE = 0, CNT_REL = 1, NCNT = 2;
constexpr int SIG_W = 0, SIG_P1 = 1, SIG_P2 = 4;
#define PROBES 2
#define WB 100
#define PACE 0
#define PACE_SLACK 300
#define SWIN 2
#define XWIN 5

__device__ uint4 g_scr[(14 << 21) / 16];
__device__ uint4 g_wf[200 * 72 * 32];
__device__ unsigned g_cnt[NCNT * 32];
__device__ __forceinline__ int slot_line(int chunk, int pg, int cls) {
    return (pg & 1) << 6 | (pg >> 1) << 9 | (chunk & 1) << 10 | (chunk >> 1) << 12 | ((pg ^ (pg >> 1) ^ chunk ^ (chunk >> 1) ^ cls) & 1) << 5;
}
__device__ __forceinline__ int phi_line(int phi, uint32_t rel) {
    return (phi >> 4) << 14 | (phi & 3) << 7 | ((phi >> 2) & 1) << 11 | ((phi >> 3) & 1) << 13 | ((rel >> (phi >> 4)) & 1) << 5;
}
__host__ __device__ constexpr int quad_off(int Q) { return (Q >> 2) * 4096 + (Q & 3) * 512; }

#define PROF(k)
#define PROFW(k)
struct Maps { CUtensorMap w, x34, x6, x28, wst, f16, f8, y4, y2; char* scr; };

__device__ __forceinline__ uint32_t smem_u32(const void* p) { return (uint32_t)__cvta_generic_to_shared(p); }
__device__ __forceinline__ void mbar_wait(uint32_t bar) {
    uint32_t ok, it = 0;
    do {
        asm volatile("{\n.reg .pred p;\nmbarrier.try_wait.parity.shared::cta.b64 p, [%1], 0;\nselp.u32 %0, 1, 0, p;\n}" : "=r"(ok) : "r"(bar) : "memory");
        if (++it > (1u << 22)) break;
    } while (!ok);
}
__device__ __forceinline__ bool mbar_test(uint32_t bar) {
    uint32_t ok;
    asm volatile("{\n.reg .pred p;\nmbarrier.test_wait.parity.shared::cta.b64 p, [%1], 0;\nselp.u32 %0, 1, 0, p;\n}" : "=r"(ok) : "r"(bar) : "memory");
    return ok;
}
__device__ __forceinline__ void fence_async() { asm volatile("fence.proxy.async;" ::: "memory"); }
__device__ __forceinline__ void fence_async_smem() { asm volatile("fence.proxy.async.shared::cta;" ::: "memory"); }
#define ELECT "{\n.reg .pred p;\nelect.sync _|p, 0xffffffff;\n@p "
__device__ __forceinline__ void e_arrive(uint32_t bar) { asm volatile(ELECT "mbarrier.arrive.shared::cta.b64 _, [%0];\n}" :: "r"(bar) : "memory"); }
__device__ __forceinline__ void e_expect(uint32_t bar, uint32_t bytes) { asm volatile(ELECT "mbarrier.arrive.expect_tx.shared::cta.b64 _, [%0], %1;\n}" :: "r"(bar), "r"(bytes) : "memory"); }
__device__ __forceinline__ void e_g2s(uint32_t dst, const void* src, uint32_t bytes, uint32_t bar) {
    asm volatile(ELECT "cp.async.bulk.shared::cluster.global.mbarrier::complete_tx::bytes [%0], [%1], %2, [%3];\n}" :: "r"(dst), "l"(src), "r"(bytes), "r"(bar) : "memory");
}
__device__ __forceinline__ void e_s2g(void* dst, uint32_t src, uint32_t bytes) {
    asm volatile(ELECT "cp.async.bulk.global.shared::cta.bulk_group [%0], [%1], %2;\n}" :: "l"(dst), "r"(src), "r"(bytes) : "memory");
}
__device__ __forceinline__ void e_ld3(uint32_t dst, const CUtensorMap* m, int c0, int c1, int c2, uint32_t bar) {
    asm volatile(ELECT "cp.async.bulk.tensor.3d.shared::cluster.global.mbarrier::complete_tx::bytes [%0], [%1, {%3, %4, %5}], [%2];\n}"
                 :: "r"(dst), "l"(m), "r"(bar), "r"(c0), "r"(c1), "r"(c2) : "memory");
}
__device__ __forceinline__ void e_st3(const CUtensorMap* m, uint32_t src, int c0, int c1, int c2) {
    asm volatile(ELECT "cp.async.bulk.tensor.3d.global.shared::cta.bulk_group [%0, {%2, %3, %4}], [%1];\n}" :: "l"(m), "r"(src), "r"(c0), "r"(c1), "r"(c2) : "memory");
}
__device__ __forceinline__ void e_ld5(uint32_t dst, const CUtensorMap* m, int c4, uint32_t bar) {
    asm volatile(ELECT "cp.async.bulk.tensor.5d.shared::cluster.global.mbarrier::complete_tx::bytes [%0], [%1, {%4, %4, %4, %4, %3}], [%2];\n}"
                 :: "r"(dst), "l"(m), "r"(bar), "r"(c4), "r"(0) : "memory");
}
__device__ __forceinline__ void e_st5(const CUtensorMap* m, uint32_t src, int c4) {
    asm volatile(ELECT "cp.async.bulk.tensor.5d.global.shared::cta.bulk_group [%0, {%3, %3, %3, %3, %2}], [%1];\n}" :: "l"(m), "r"(src), "r"(c4), "r"(0) : "memory");
}
__device__ __forceinline__ void bulk_commit() { asm volatile("cp.async.bulk.commit_group;" ::: "memory"); }
template <int N> __device__ __forceinline__ void bulk_wait_read() { asm volatile("cp.async.bulk.wait_group.read %0;" :: "n"(N) : "memory"); }
__device__ __forceinline__ void wg_bar(int id) { asm volatile("bar.sync %0, 128;" :: "r"(id) : "memory"); }
__device__ __forceinline__ uint32_t uni(uint32_t v) { return __shfl_sync(0xffffffffu, v, 0); }
__device__ __forceinline__ char* cls_cnt(char* scr, int cls, uint32_t rel) { return scr + (slot_line(3, 2, cls) ^ (rel & 1) << 5) * 128; }
__device__ __forceinline__ uint32_t cnt_wait(const void* p, unsigned target) {
    unsigned v, it = 0;
    while (true) {
        asm volatile("ld.acquire.gpu.global.u32 %0, [%1];" : "=r"(v) : "l"(p) : "memory");
        v = uni(v);
        if (v >= target || ++it > (1u << 22)) break;
    }
    return v;
}
__device__ __forceinline__ void wg_fence() { asm volatile("wgmma.fence.sync.aligned;" ::: "memory"); }
__device__ __forceinline__ void wg_commit() { asm volatile("wgmma.commit_group.sync.aligned;" ::: "memory"); }
template <int N> __device__ __forceinline__ void wg_wait() { asm volatile("wgmma.wait_group.sync.aligned %0;" :: "n"(N) : "memory"); }
template <int N> __device__ __forceinline__ void reg_fence(float (&d)[N]) {
#pragma unroll
    for (int i = 0; i < N; i++) asm volatile("" : "+f"(d[i]) :: "memory");
}
template <int N, int O, int M> __device__ __forceinline__ float (&sub(float (&d)[M]))[N] { return *reinterpret_cast<float (*)[N]>(&d[O]); }
template <int N> __device__ __forceinline__ void zero(float (&d)[N]) {
#pragma unroll
    for (int i = 0; i < N; i++) d[i] = 0.f;
}
__device__ __forceinline__ uint32_t pack2(float lo, float hi) {
    uint32_t r; asm("cvt.rn.bf16x2.f32 %0, %1, %2;" : "=r"(r) : "f"(hi), "f"(lo)); return r;
}
__device__ __forceinline__ void stm4(uint32_t a, uint32_t r0, uint32_t r1, uint32_t r2, uint32_t r3) {
    asm volatile("stmatrix.sync.aligned.m8n8.x4.trans.shared.b16 [%0], {%1,%2,%3,%4};" :: "r"(a), "r"(r0), "r"(r1), "r"(r2), "r"(r3) : "memory");
}
__device__ __forceinline__ void stm2(uint32_t a, uint32_t r0, uint32_t r1) {
    asm volatile("stmatrix.sync.aligned.m8n8.x2.trans.shared.b16 [%0], {%1,%2};" :: "r"(a), "r"(r0), "r"(r1) : "memory");
}
__device__ __forceinline__ void stm1(uint32_t a, uint32_t r0) {
    asm volatile("stmatrix.sync.aligned.m8n8.x1.trans.shared.b16 [%0], {%1};" :: "r"(a), "r"(r0) : "memory");
}
struct Desc {
    uint32_t lo, hi;
    __device__ __forceinline__ operator uint64_t() const { return ((uint64_t)hi << 32) | lo; }
    __device__ __forceinline__ Desc operator+(uint32_t o) const { return Desc{lo + o, hi}; }
    __device__ __forceinline__ Desc operator^(uint32_t o) const { return Desc{lo ^ o, hi}; }
};
__device__ __forceinline__ Desc mkdesc(uint32_t addr, uint32_t lbo, uint32_t sbo, uint32_t swz) {
    return Desc{((addr & 0x3FFFF) >> 4) | ((lbo >> 4) << 16), (sbo >> 4) | (swz << 30)};
}
__device__ __forceinline__ uint32_t cos_bits(int k) {
    if (k > 20) k = 40 - k;
    const bool neg = k > 10;
    if (neg) k = 20 - k;
    const unsigned long long pk = k < 4 ? COS_PK0 : k < 8 ? COS_PK1 : COS_PK2;
    return (uint32_t)((pk >> (16 * (k & 3))) & 0xffff) ^ (neg ? 0x8000u : 0u);
}

__device__ __forceinline__ void task_w(int wg, int k, uint32_t sb) {
    const int tid = threadIdx.x & 127, w = uni(tid >> 5), lane = tid & 31, q = lane & 3;
    const int tb = 14 * k, t1 = min(tb + 14, 1800), cb0 = tb / 25;
    float acc[64];
    zero(acc);
    int cnt, at = 0;
#pragma unroll 1
    for (int t = tb; t < t1; t += cnt, at++) {
        const int cb = t / 25, oc = t - 25 * cb;
        cnt = min(min(4, 25 - oc), t1 - t);
        if ((at ? 2 - (at & 1) : 0) != wg) continue;
        const Desc dB = mkdesc(sb + WP + (cb - cb0) * 14336, 3584, 512, 2);
        const int phi = 8 * (oc + w) + (lane >> 2), f = phi / 20, ca = (2 * f + 1) * 4, cbb = (phi - 20 * f) * 8;
        uint32_t a[4][4];
#pragma unroll
        for (int j = 0; j < 3; j++)
#pragma unroll
            for (int h = 0; h < 2; h++) {
                uint32_t v[2];
#pragma unroll
                for (int e = 0; e < 2; e++) {
                    const int tap = 16 * j + 8 * h + 2 * q + e, kh = (tap * 37) >> 8, kw = tap - 7 * kh;
                    asm volatile("ld.shared.u32 %0, [%1];" : "=r"(v[e]) : "r"(sb + TBL + ca * kh + cbb * kw));
                }
                a[j][2 * h] = __byte_perm(v[0], v[1], 0x5410);
                a[j][2 * h + 1] = __byte_perm(v[0], v[1], 0x7632);
            }
        {
            uint32_t v;
            asm volatile("ld.shared.u32 %0, [%1];" : "=r"(v) : "r"(sb + TBL + (ca + cbb) * 6));
            if (q) v = 0;
            a[3][0] = 0; a[3][1] = 0; a[3][2] = v & 0xffff; a[3][3] = v >> 16;
        }
        if (at == 0) PROFW(124);
        mbar_wait(sb + BARS + 8 * B_WF);
        if (at) mbar_wait(sb + BARS + 8 * (B_WCH + at - 1));
        if (at == 0) PROFW(125);
        wg_fence();
        wgmma_rs_n128_z(acc, a[0][0], a[0][1], a[0][2], a[0][3], dB);
        wgmma_rs_n128_a(acc, a[1][0], a[1][1], a[1][2], a[1][3], dB + (uint32_t)(16 * 64 >> 4));
        wgmma_rs_n128_a(acc, a[2][0], a[2][1], a[2][2], a[2][3], dB + (uint32_t)(32 * 64 >> 4));
        wgmma_rs_n128_a(acc, a[3][0], a[3][1], a[3][2], a[3][3], dB + (uint32_t)(40 * 64 >> 4));
        wg_commit();
        wg_wait<0>();
        reg_fence(acc);
        if (at == 0) PROFW(120);
        e_arrive(sb + BARS + 8 * (B_WCH + at));
        if (w < cnt) {
            const uint32_t dst = sb + WST + (t - tb + w) * 4096 + (lane >> 2) * 512 + ((q ^ cb) & 3) * 16;
#pragma unroll
            for (int j = 0; j < 4; j++)
#pragma unroll
                for (int e = 0; e < 2; e++)
                    asm volatile("st.shared.v4.u32 [%0], {%1,%2,%3,%4};" :: "r"(dst + j * 128 + e * 64),
                                 "r"(pack2(acc[4 * j + e], acc[16 + 4 * j + e])), "r"(pack2(acc[4 * j + 2 + e], acc[16 + 4 * j + 2 + e])),
                                 "r"(pack2(acc[32 + 4 * j + e], acc[48 + 4 * j + e])), "r"(pack2(acc[32 + 4 * j + 2 + e], acc[48 + 4 * j + 2 + e])) : "memory");
            fence_async_smem();
            e_arrive(sb + BARS + 8 * (B_WRD + t - tb + w));
        }
    }
}

__device__ __forceinline__ void task_p1(int wg, int pair, uint32_t sb) {
    const int tid = threadIdx.x & 127, w = tid >> 5, lane = tid & 31;
    const uint32_t buf = sb + wg * 51200, bars = sb + BARS;
    uint32_t fr[5][10][2];
    float A[40], d[20];
    zero(A);
    {
        const Desc dA = mkdesc(buf, 3584, 512, 2), dB = mkdesc(sb + C1, 128, 256, 0);
        auto issue = [&](int g, float (&d)[40]) {
            mbar_wait(bars + 8 * (B_XF + wg * 5 + g));
            wg_fence();
            wgmma_ss_n80_z(d, dA + (uint32_t)(g * 8704 >> 4), dB);
#pragma unroll
            for (int j = 1; j < 5; j++) wgmma_ss_n80_a(d, dA + (uint32_t)((g * 8704 + j * 1024) >> 4), dB + (uint32_t)(j * 2560 >> 4));
            wg_commit();
        };
        auto pack = [&](int g, float (&d)[40]) {
            reg_fence(d);
#pragma unroll
            for (int f = 0; f < 10; f++) {
                fr[g][f][0] = pack2(d[4 * f], d[4 * f + 1]);
                fr[g][f][1] = pack2(d[4 * f + 2], d[4 * f + 3]);
            }
        };
        mbar_wait(bars + 8 * B_CF1);
#pragma unroll
        for (int g = 0; g < 4; g++) { issue(g, A); if (g == 0) PROFW(8 + wg * 8 + 1); wg_wait<0>(); pack(g, A); }
        zero(d);
        mbar_wait(bars + 8 * (B_XF + wg * 5 + 4));
#pragma unroll
        for (int h = 0; h < 2; h++) {
            wg_fence();
            wgmma_ss_n40_z(d, dA + (uint32_t)(4 * 8704 >> 4), dB + (uint32_t)(h * 1280 >> 4));
#pragma unroll
            for (int j = 1; j < 5; j++) wgmma_ss_n40_a(d, dA + (uint32_t)((4 * 8704 + j * 1024) >> 4), dB + (uint32_t)((j * 2560 + h * 1280) >> 4));
            wg_commit(); wg_wait<0>(); reg_fence(d);
#pragma unroll
            for (int f = 0; f < 5; f++) { fr[4][5 * h + f][0] = pack2(d[4 * f], d[4 * f + 1]); fr[4][5 * h + f][1] = pack2(d[4 * f + 2], d[4 * f + 3]); }
        }
    }
    wg_bar(1 + wg);
    PROFW(8 + wg * 8 + 2);
    {
        const Desc dB = mkdesc(sb + C1 + 12800, 128, 256, 0);
        const int i = lane & 7, mi = lane >> 3, th = w >> 1, tz = (2 * pair + th) & 3;
        const uint32_t s0 = buf + (i >> 1) * 128 + (i & 1) * 64 + (((2 * (w & 1) + (mi & 1)) ^ tz ^ (i >> 1)) << 4);
        const uint32_t sA = s0 + th * 2048 + (mi >> 1) * 512, sB = s0 + th * 2048 + (mi >> 1) * 2560, sC = s0 + th * 1024 + (mi >> 1) * 512;
        auto issue = [&](int f, float (&d)[20]) {
            wg_fence();
            wgmma_rs_n40_z(d, fr[0][f][0], fr[0][f][1], fr[1][f][0], fr[1][f][1], dB);
            wgmma_rs_n40_a(d, fr[2][f][0], fr[2][f][1], fr[3][f][0], fr[3][f][1], dB + (uint32_t)(1280 >> 4));
            wgmma_rs_n40_a(d, fr[4][f % 5][0], fr[4][f % 5][1], fr[4][f % 5 + 5][0], fr[4][f % 5 + 5][1], dB + (uint32_t)((2560 + (f / 5) * 1280) >> 4));
            wg_commit();
        };
#pragma unroll
        for (int f = 0; f < 10; f++) {
                        issue(f, d); wg_wait<0>(); reg_fence(d);
            const int Q = 5 * f;
            stm4(((Q & 3) == 3 ? sB : sA) + quad_off(Q), pack2(d[0], d[1]), pack2(d[2], d[3]), pack2(d[4], d[5]), pack2(d[6], d[7]));
            stm2(sA + quad_off(Q + 2), pack2(d[8], d[9]), pack2(d[10], d[11]));
            stm4((f == 9 ? sC : ((Q + 3) & 3) == 3 ? sB : sA) + quad_off(Q + 3), pack2(d[12], d[13]), pack2(d[14], d[15]), pack2(d[16], d[17]), pack2(d[18], d[19]));
            if (f & 1) { fence_async_smem(); e_arrive(bars + 8 * (B_RDY + wg * 5 + (f >> 1))); }
        }
    }
}

__device__ __forceinline__ void task_p2(int wg, int rk, uint32_t sb) {
    const int tid = threadIdx.x & 127, w = tid >> 5, lane = tid & 31;
    const uint32_t bars = sb + BARS;
    const int phi0 = 3 * rk, phiE = 198 + ((rk - 58) >> 2), pgE = rk >= 58 ? (rk - 58) & 3 : -1;
    uint4 wA[6], wB[6], wC[6], wE[6];
    auto ldw = [&](uint4 (&a)[6], int j, int phi) {
        const int pc = 3 * j + wg;
        const uint32_t p = sb + S0 + (pc & 3) * 12288 + (lane & 3) * 512 + w * 128 + ((lane >> 2) & 1) * 64 + (((lane >> 3) ^ lane) & 3) * 16 + (phi & 1) * 8;
        mbar_wait(bars + 8 * (B_WL + pc));
#pragma unroll
        for (int s = 0; s < 6; s++) {
            asm volatile("ld.shared.v2.u32 {%0, %1}, [%2];" : "=r"(a[s].x), "=r"(a[s].y) : "r"(p + s * 2048) : "memory");
            asm volatile("ld.shared.v2.u32 {%0, %1}, [%2];" : "=r"(a[s].z), "=r"(a[s].w) : "r"((p ^ 8) + s * 2048) : "memory");
        }
        uint32_t dep = 0;
#pragma unroll
        for (int s = 0; s < 6; s++) dep |= a[s].x ^ a[s].z;
        asm volatile("{\n.reg .pred p;\nsetp.eq.u32 p, %0, 0x7fc17fc1;\n@p nanosleep.u32 0;\n}" :: "r"(dep) : "memory");
        __syncwarp();
        e_arrive(bars + 8 * (B_WE + pc));
    };
    ldw(wA, 0, phi0); ldw(wB, 1, phi0 + 1); ldw(wC, 2, phi0 + 2);
    if (pgE >= 0) ldw(wE, 3, phiE);
    PROFW(8 + wg * 8 + 4);
    mbar_wait(bars + 8 * (B_SIG + SIG_P1 + 1));
    const int i = lane & 7, mi = lane >> 3;
    const uint32_t soff = sb + S1 + wg * 4096 + mi * 512 + (i >> 1) * 128 + (i & 1) * 64;
    const int xo = w ^ (i >> 1);
    float p0[16], p1[16];
    zero(p0); zero(p1);
    auto issue = [&](float (&d)[16], int n, int h, const uint4 (&a)[6], int z) {
        const Desc d0 = mkdesc(sb + RG + (n & 3) * 12288 + h * 2048 + ((z >> 1) << 5), 16, 512, 2), d1 = d0 ^ 2u;
        if (h == 0) mbar_wait(bars + 8 * (B_RF + n));
        wg_fence();
        wgmma_rs_n32_z(d, a[0].x, a[0].y, a[0].z, a[0].w, d0);
        wgmma_rs_n32_a(d, a[1].x, a[1].y, a[1].z, a[1].w, d1);
#pragma unroll
        for (int c = 1; c < 3; c++) {
            wgmma_rs_n32_a(d, a[2 * c].x, a[2 * c].y, a[2 * c].z, a[2 * c].w, d0 + (uint32_t)(c * 4096 >> 4));
            wgmma_rs_n32_a(d, a[2 * c + 1].x, a[2 * c + 1].y, a[2 * c + 1].z, a[2 * c + 1].w, d1 + (uint32_t)(c * 4096 >> 4));
        }
        wg_commit();
    };
    auto epi = [&](float (&d)[16], int n, int h, int z) {
        reg_fence(d);
        if (h) e_arrive(bars + 8 * (B_RE + n));
        uint32_t p[4];
#pragma unroll
        for (int j = 0; j < 4; j++) p[j] = pack2(d[4 * j] - d[4 * j + 3], d[4 * j + 2] + d[4 * j + 1]);
        if (h == 0 && n >= 4) mbar_wait(bars + 8 * (B_SFREE + (n - 4) * 3 + wg));
        stm4(soff + (n & 3) * 12288 + h * 2048 + ((xo ^ z) << 4), p[0], p[1], p[2], p[3]);
        if (h) { fence_async_smem(); e_arrive(bars + 8 * (B_RDY + 15 + n * 3 + wg)); }
    };
    const int zA = phi0 & 3, zB = (phi0 + 1) & 3, zC = (phi0 + 2) & 3, zE = phiE & 3;
    int n = 0;
#pragma unroll 1
    for (int it = 0; it < 4; it++) {
        issue(p0, n, 0, wA, zA);
        issue(p1, n, 1, wA, zA);     wg_wait<1>(); epi(p0, n, 0, zA);
        issue(p0, n + 1, 0, wB, zB); wg_wait<1>(); epi(p1, n, 1, zA);
        PROFW(40 + wg * 8 + it * 2);
        issue(p1, n + 1, 1, wB, zB); wg_wait<1>(); epi(p0, n + 1, 0, zB);
        issue(p0, n + 2, 0, wC, zC); wg_wait<1>(); epi(p1, n + 1, 1, zB);
        issue(p1, n + 2, 1, wC, zC); wg_wait<1>(); epi(p0, n + 2, 0, zC);
        wg_wait<0>(); epi(p1, n + 2, 1, zC);
        n += 3;
        if (it == pgE) {
            issue(p0, n, 0, wE, zE);
            issue(p1, n, 1, wE, zE); wg_wait<1>(); epi(p0, n, 0, zE);
            wg_wait<0>(); epi(p1, n, 1, zE);
            n++;
        }
        PROFW(40 + wg * 8 + it * 2 + 1);
    }
}

__device__ __forceinline__ void task_p3(int wg, int pair, uint32_t sb) {
    const int tid = threadIdx.x & 127, w = tid >> 5, lane = tid & 31;
    const uint32_t buf = sb + (wg ? 3 - wg : 0) * 51200, bars = sb + BARS;
    uint32_t fr[10][4][2];
    float A[32];
    zero(A);
    {
        const Desc dB = mkdesc(sb + C3, 128, 256, 0);
        const uint32_t a0 = (buf & 0x3FFFF) >> 4;
        auto dq = [&](int Q) {
            return Desc{a0 + (uint32_t)((quad_off(Q) >> 4) | ((Q < 48 ? 2048 : 1024) >> 4) << 16), (uint32_t)((quad_off(Q + 1) - quad_off(Q)) >> 4) | (2u << 30)};
        };
        float (&d0)[16] = sub<16, 0>(A);
        float (&d1)[16] = sub<16, 16>(A);
        mbar_wait(bars + 8 * B_CF3);
#pragma unroll
        for (int j = 0; j < 5; j++) {
            mbar_wait(bars + 8 * (B_YF + wg * 5 + j));
            if (j == 0) PROFW(64 + wg * 8 + 1);
            wg_fence();
            wgmma_ss_n32_z(d0, dq(10 * j), dB);
            wgmma_ss_n32_z(d1, dq(10 * j + 5), dB);
            wgmma_ss_n32_a(d0, dq(10 * j + 1), dB + (uint32_t)(1024 >> 4));
            wgmma_ss_n32_a(d1, dq(10 * j + 6), dB + (uint32_t)(1024 >> 4));
            wgmma_ss_n32_a(d0, dq(10 * j + 3), dB + (uint32_t)(2048 >> 4));
            wgmma_ss_n32_a(d1, dq(10 * j + 8), dB + (uint32_t)(2048 >> 4));
            wg_commit(); wg_wait<0>(); reg_fence(A);
#pragma unroll
            for (int e = 0; e < 2; e++)
#pragma unroll
                for (int g = 0; g < 4; g++) {
                    fr[2 * j + e][g][0] = pack2(A[16 * e + 4 * g], A[16 * e + 4 * g + 1]);
                    fr[2 * j + e][g][1] = pack2(A[16 * e + 4 * g + 2], A[16 * e + 4 * g + 3]);
                }
        }
    }
    wg_bar(1 + wg);
    PROFW(64 + wg * 8 + 2);
    {
        const Desc dB = mkdesc(sb + C3 + 3072, 128, 256, 0);
        const int i = lane & 7, mi = lane >> 3, th = w >> 1, tz = (2 * pair + th) & 3;
        const int oct = (2 * (w & 1) + (mi & 1)) ^ tz;
        const uint32_t soff = buf + th * 3584 + (mi >> 1) * 512 + i * 64 + ((oct ^ (i >> 1)) << 4);
        float d[28]; zero(d);
        auto issue = [&](int g, float (&d)[28]) {
            wg_fence();
            wgmma_rs_n56_z(d, fr[0][g][0], fr[0][g][1], fr[1][g][0], fr[1][g][1], dB);
#pragma unroll
            for (int s = 1; s < 5; s++) wgmma_rs_n56_a(d, fr[2 * s][g][0], fr[2 * s][g][1], fr[2 * s + 1][g][0], fr[2 * s + 1][g][1], dB + (uint32_t)(s * 1792 >> 4));
            wg_commit();
        };
#pragma unroll
        for (int gg = 1; gg < 5; gg++) {
            const int g = gg & 3;
                        issue(g, d); wg_wait<0>(); reg_fence(d);
            if (g) {
                const uint32_t a = soff + g * 7168;
#pragma unroll
                for (int j = 0; j < 3; j++)
                    stm4(a + j * 1024, pack2(d[8 * j], d[8 * j + 1]), pack2(d[8 * j + 2], d[8 * j + 3]), pack2(d[8 * j + 4], d[8 * j + 5]), pack2(d[8 * j + 6], d[8 * j + 7]));
                stm2(a + 3072, pack2(d[24], d[25]), pack2(d[26], d[27]));
            } else {
#pragma unroll
                for (int j = 0; j < 4; j++) {
                    const int row = th * 14 + 4 * j + 2 * (mi >> 1) + (i >> 2);
                    const uint32_t a = (i & 2) ? buf + row * 128 + (i & 1) * 64 + ((oct ^ (row & 3)) << 4) : buf + 4096 + lane * 16;
                    if (j < 3) stm4(a, pack2(d[8 * j], d[8 * j + 1]), pack2(d[8 * j + 2], d[8 * j + 3]), pack2(d[8 * j + 4], d[8 * j + 5]), pack2(d[8 * j + 6], d[8 * j + 7]));
                    else stm2(a, pack2(d[24], d[25]), pack2(d[26], d[27]));
                }
            }
            fence_async_smem();
            e_arrive(bars + 8 * (B_RDY + 54 + wg * 4 + gg - 1));
        }
    }
}

__device__ __forceinline__ void load_x(int cls, int rk, int u, uint32_t sb, const Maps& mp) {
    const uint32_t bars = sb + BARS;
    const int id = u * NH + rk, pl = id / 3, chunk = id - 3 * pl, tp = cls * 4 + (pl >> 4), tx = pl & 15;
#pragma unroll 1
    for (int g = 0; g < 5; g++) {
        const int bi = u * 5 + g;
        if (bi >= XWIN) mbar_wait(bars + 8 * (B_XF + bi - XWIN));
        int col = 14 * tx - 8 + 4 * g; if (col < 0) col += 224;
        const uint32_t bar = bars + 8 * (B_XF + bi), dst = sb + u * 51200 + g * 8704;
        e_expect(bar, 8704);
        if (tp) e_ld3(dst, &mp.x34, 32 * chunk, col, 28 * tp - 6, bar);
        else { e_ld3(dst, &mp.x6, 32 * chunk, col, 218, bar); e_ld3(dst + 1536, &mp.x28, 32 * chunk, col, 0, bar); }
        if (bi == 0) { e_expect(bars + 8 * B_CF1, 17920); e_g2s(sb + C1, TAB_P1, 17920, bars + 8 * B_CF1); }
    }
}

__device__ __forceinline__ void load_first(int cls, int rk, uint32_t sb, const Maps& mp) {
    const uint32_t bars = sb + BARS;
    const int k = cls * NH + rk;
    PROF(122);
    if (k < 129) {
        const int cb0 = 14 * k / 25, cb1 = min((14 * k + 13) / 25, 71);
        e_expect(bars + 8 * B_WF, (cb1 - cb0 + 1) * 14336);
#pragma unroll 1
        for (int cb = cb0; cb <= cb1; cb++) {
            const int b = cb / 24, i0 = 16 * ((cb >> 2) - 6 * b) + 2 * (cb & 3);
            e_ld3(sb + WP + (cb - cb0) * 14336, &mp.w, 32 * b, 0, i0, bars + 8 * B_WF);
            e_ld3(sb + WP + (cb - cb0) * 14336 + 7168, &mp.w, 32 * b, 0, i0 + 8, bars + 8 * B_WF);
        }
    }
    load_x(cls, rk, 0, sb, mp);
    PROF(123);
}

__device__ __forceinline__ uint32_t get_rel(uint32_t sb) {
    mbar_wait(sb + BARS + 8 * B_REL);
    uint32_t v; asm volatile("ld.shared.u32 %0, [%1];" : "=r"(v) : "r"(sb + REL) : "memory");
    return uni(v);
}

__device__ __forceinline__ void load_warp(int cls, int rk, uint32_t sb, const Maps& mp) {
    const uint32_t bars = sb + BARS;
    load_x(cls, rk, 1, sb, mp);
    mbar_wait(bars + 8 * B_WFREE);
    if (rk < 60) load_x(cls, rk, 2, sb, mp);
    e_expect(bars + 8 * B_CF3, 12032); e_g2s(sb + C3, TAB_P3, 12032, bars + 8 * B_CF3);
    PROF(1);
    const uint32_t rel = get_rel(sb);
    const char* cnt = cls_cnt(mp.scr, cls, rel);
    const int pgE = rk >= 58 ? (rk - 58) & 3 : -1;
    mbar_wait(bars + 8 * B_P1D);
    int n = 0;
#pragma unroll 1
    for (int pg = 0; pg < 4; pg++) {
        cnt_wait(cnt + (CNT_P1 + pg) * 128, 48);
        PROF(88 + pg);
        const int l0 = slot_line(0, pg, cls), l1 = slot_line(1, pg, cls), l2 = slot_line(2, pg, cls);
        const int nj = pg == pgE ? 4 : 3;
#pragma unroll 1
        for (int j = 0; j < nj; j++) {
            const int lp = phi_line(j == 3 ? 198 + ((rk - 58) >> 2) : 3 * rk + j, rel);
            const uint32_t bar = bars + 8 * (B_RF + n), dst = sb + RG + (n & 3) * 12288;
            if (n >= 4) mbar_wait(bars + 8 * (B_RE + n - 4));
            e_expect(bar, 12288);
            e_g2s(dst, mp.scr + (size_t)(lp ^ l0) * 128, 4096, bar);
            e_g2s(dst + 4096, mp.scr + (size_t)(lp ^ l1) * 128, 4096, bar);
            e_g2s(dst + 8192, mp.scr + (size_t)(lp ^ l2) * 128, 4096, bar);
            n++;
        }
    }
}

__device__ __forceinline__ int near_page(char* p) {
#pragma unroll
    for (int e = 0; e < 4; e++) asm volatile("st.relaxed.gpu.global.v4.u32 [%0], {%1, %1, %1, %1};" :: "l"(p + (e >> 1) * 4096 + (e & 1) * 16), "r"(0) : "memory");
    int score = 0;
#pragma unroll 1
    for (int r = 0; r < PROBES; r++) {
        uint32_t v0, v1, t0, t1;
        asm volatile("atom.relaxed.gpu.global.exch.b32 %0, [%1], 1;" : "=r"(v0) : "l"(p + (r & 1) * 4096) : "memory");
        asm volatile("atom.relaxed.gpu.global.exch.b32 %0, [%1], 1;" : "=r"(v1) : "l"(p + (~r & 1) * 4096) : "memory");
        asm volatile("{\n.reg .pred p;\nsetp.ne.u32 p, %1, 0xffffffff;\nmov.u32 %0, 0;\n@p mov.u32 %0, %%clock;\n}" : "=r"(t0) : "r"(v0) : "memory");
        asm volatile("{\n.reg .pred p;\nsetp.ne.u32 p, %1, 0xffffffff;\nmov.u32 %0, 0;\n@p mov.u32 %0, %%clock;\n}" : "=r"(t1) : "r"(v1) : "memory");
        const int gap = min((int)(t1 - t0), 220) - 110;
        score += (r & 1) ? gap : -gap;
    }
    return score > 0;
}

__device__ __forceinline__ void probe(int cls, int rk, char* scr) {
    const int G = cls * NH + rk - 59;
    if (G >= 0 && G < 13) {
        const int sel = near_page(scr + ((size_t)G << 21) + slot_line(3, 3, 0) * 128);
        asm volatile("red.relaxed.gpu.global.add.u32 [%0], %1;" :: "l"(&g_cnt[CNT_REL * 32]), "r"(0x10000u | (uint32_t)(sel ^ cls) << G) : "memory");
        PROF(4);
    }
}

__device__ __forceinline__ void load3_warp(int cls, int rk, uint32_t sb, const Maps& mp) {
    const uint32_t bars = sb + BARS;
    uint32_t rel = 0;
    mbar_wait(bars + 8 * B_XF);
    rel = cnt_wait(&g_cnt[CNT_REL * 32], 13u << 16);
    asm volatile("st.shared.u32 [%0], %1;" :: "r"(sb + REL), "r"(rel) : "memory");
    __syncwarp();
    e_arrive(bars + 8 * B_REL);
    PROF(7);
    mbar_wait(bars + 8 * (B_SIG + SIG_W));
    cnt_wait(cls_cnt(mp.scr, cls, rel) + CNT_W * 128, NSM);
    PROF(2);
    mbar_wait(bars + 8 * (B_SIG + SIG_P1));
    {
        const int np = rk >= 58 ? 12 : 9;
#pragma unroll 1
        for (int pc = 0; pc < np; pc++) {
            if (pc >= 4) mbar_wait(bars + 8 * (B_WE + pc - 4));
            e_expect(bars + 8 * (B_WL + pc), 12288);
            e_g2s(sb + S0 + (pc & 3) * 12288, g_wf + (pc < 9 ? 9 * rk + pc : 3 * (198 + ((rk - 58) >> 2)) + pc - 9) * 768, 12288, bars + 8 * (B_WL + pc));
        }
    }
    mbar_wait(bars + 8 * (B_SIG + SIG_P2));
    const int nu = rk < 60 ? 3 : 2;
#pragma unroll 1
    for (int u = 0; u < nu; u++) {
        const int id = u * NH + rk, pl = id / 3, chunk = id - 3 * pl;
        const int l0 = slot_line(chunk, pl >> 4, cls) + (pl & 15) * 2;
        const uint32_t buf = sb + (u ? 3 - u : 0) * 51200, bar = bars + 8 * (B_YF + u * 5);
#pragma unroll
        for (int j = 0; j < 5; j++) e_expect(bar + 8 * j, j == 4 ? 10240 : (j & 1) ? 8192 : 12288);
        if (u == 2) mbar_wait(bars + 8 * (B_SIG + SIG_P2 + 3));
        cnt_wait(cls_cnt(mp.scr, cls, rel) + (CNT_P2 + (pl >> 4)) * 128, NH);
        PROF(64 + u * 8);
        uint32_t bj = bar;
#pragma unroll 1
        for (int G = 0; G < 12; G++) {
            e_ld5(buf + G * 4096, &mp.f16, (l0 ^ ((rel >> G) & 1) << 5) + (G << 14), bj);
            bj += (0x294 >> G & 1) * 8;
        }
        e_ld5(buf + 12 * 4096, &mp.f8, (l0 ^ ((rel >> 12) & 1) << 5) + (12 << 14), bj);
    }
}

__device__ __forceinline__ void store_warp(int cls, int rk, uint32_t sb, const Maps& mp) {
    const uint32_t bars = sb + BARS;
    const int nu = rk < 60 ? 3 : 2, k = cls * NH + rk;
    uint32_t pa = 0, pb = 0, qa = 0, qb = 0;
    auto arr2 = [&](uint32_t& a, uint32_t& b) { if (a) e_arrive(a); if (b) e_arrive(b); a = b = 0; };
    auto pre = [&](int idx) {
        const uint32_t bar = bars + 8 * idx;
        if (!mbar_test(bar)) { bulk_wait_read<0>(); arr2(qa, qb); arr2(pa, pb); mbar_wait(bar); }
    };
    auto post = [&](uint32_t fr) {
        bulk_commit(); bulk_wait_read<SWIN - 1>();
        if (SWIN == 3) { arr2(qa, qb); qa = pa; qb = pb; pb = 0; } else arr2(pa, pb);
        pa = fr;
    };
    auto after = [&](uint32_t a, uint32_t b) { if (a) pa = a; pb = b; };
    auto pace = [&](uint32_t) {};
    {
        int cb = 14 * k / 25, oc = 14 * k - 25 * cb;
#pragma unroll 1
        for (int i = 0; i < 14 && cb < 72; i++) {
            pre(B_WRD + i);
            if (i == 0) PROF(6);
            pace(4 * PACE);
            e_st3(&mp.wst, sb + WST + i * 4096, 0, 8 * oc, cb);
            post(0);
            if (++oc == 25) { oc = 0; cb++; }
        }
        after(bars + 8 * B_WFREE, bars + 8 * (B_SIG + SIG_W));
    }
    pre(B_REL);
    const uint32_t rel = get_rel(sb);
#pragma unroll 1
    for (int u = 0; u < nu; u++) {
        const int id = u * NH + rk, pl = id / 3, chunk = id - 3 * pl;
        const int l0 = slot_line(chunk, pl >> 4, cls) + (pl & 15) * 2;
        int j = B_RDY + u * 5;
#pragma unroll 1
        for (int G = 0; G < 13; G++) {
            if (0x4a5 >> G & 1) pre(j++);
            if (G == 0) PROF(104 + u);
            pace(G < 12 ? 4 * PACE : 2 * PACE);
            e_st5(G < 12 ? &mp.f16 : &mp.f8, sb + u * 51200 + G * 4096, (l0 ^ ((rel >> G) & 1) << 5) + (G << 14));
            post(0);
        }
        after(0, bars + 8 * (B_SIG + SIG_P1 + u));
    }
    const int pgE = rk >= 58 ? (rk - 58) & 3 : -1;
    int n = 0;
#pragma unroll 1
    for (int pg = 0; pg < 4; pg++) {
        const int nj = pg == pgE ? 4 : 3;
        const int l0 = slot_line(0, pg, cls), l1 = slot_line(1, pg, cls), l2 = slot_line(2, pg, cls);
#pragma unroll 1
        for (int j = 0; j < nj; j++) {
            const int lp = phi_line(j == 3 ? 198 + ((rk - 58) >> 2) : 3 * rk + j, rel);
#pragma unroll
            for (int b = 0; b < 3; b++) {
                pre(B_RDY + 15 + n * 3 + b);
                if (j == 0 && b == 0 && pg < 3) PROF(107 + pg);
                pace(4 * PACE);
                e_s2g(mp.scr + (size_t)(lp ^ (b == 0 ? l0 : b == 1 ? l1 : l2)) * 128, sb + S1 + (n & 3) * 12288 + b * 4096, 4096);
                post(bars + 8 * (B_SFREE + n * 3 + b));
            }
            n++;
        }
        after(0, bars + 8 * (B_SIG + SIG_P2 + pg));
    }
#pragma unroll 1
    for (int u = 0; u < nu; u++) {
        const int id = u * NH + rk, pl = id / 3, chunk = id - 3 * pl, tp = cls * 4 + (pl >> 4), tx = pl & 15;
        const uint32_t buf = sb + (u ? 3 - u : 0) * 51200;
#pragma unroll
        for (int gg = 1; gg < 5; gg++) {
            pre(B_RDY + 54 + u * 4 + gg - 1);
            if (gg == 1) PROF(110 + u);
            if (u < 2) pace(gg < 4 ? 7 * PACE : 7 * PACE / 2);
            if (gg < 4) e_st3(&mp.y4, buf + gg * 7168, 32 * chunk, 14 * tx - 4 + 4 * gg, 28 * tp);
            else e_st3(&mp.y2, buf, 32 * chunk, tx == 0 ? 222 : 14 * tx - 2, 28 * tp);
            post(0);
        }
    }
    bulk_wait_read<0>();
    PROF(113);
}

__device__ __forceinline__ void signal_warp(int cls, int rk, uint32_t sb, char* scr) {
    const uint32_t bars = sb + BARS;
    char* cnt = cls_cnt(scr, cls, get_rel(sb));
    if (threadIdx.x & 31) return;
#pragma unroll 1
    for (int c = 0; c < 8; c++) {
        if (c == SIG_P1 + 2 && rk >= 60) continue;
        char* ctr = cnt + (c == SIG_W ? CNT_W : c < SIG_P2 ? CNT_P1 + ((c - SIG_P1) * NH + rk) / 48 : CNT_P2 + c - SIG_P2) * 128;
        mbar_wait(bars + 8 * (B_SIG + c));
        PROF(32 + c);
        fence_async();
        asm volatile("red.relaxed.gpu.global.add.u32 [%0], 1;" :: "l"(ctr) : "memory");
        if (c == SIG_W) asm volatile("red.relaxed.gpu.global.add.u32 [%0], 1;" :: "l"((uintptr_t)ctr ^ 4096) : "memory");
        PROF(96 + c);
    }
    mbar_wait(bars + 8 * (B_YF + (rk < 60 ? 14 : 9)));
    unsigned old;
    asm volatile("atom.add.acq_rel.gpu.global.u32 %0, [%1], 1;" : "=r"(old) : "l"(&g_cnt[CNT_DONE * 32]) : "memory");
    if (old == NSM - 1) {
#pragma unroll
        for (int c = 0; c < NCNT; c++) g_cnt[c * 32] = 0;
#pragma unroll 1
        for (int c = 0; c < NCLS; c++) { *reinterpret_cast<unsigned*>(cnt + c * 128) = 0; *reinterpret_cast<unsigned*>(((uintptr_t)cnt ^ 4096) + c * 128) = 0; }
    }
}

template <bool USE_SMID>
__global__ void __launch_bounds__(512, 1) fftconv_kernel(const __grid_constant__ Maps mp) {
    extern __shared__ __align__(1024) uint8_t smem[];
    const uint32_t sb = smem_u32(smem);
    const int tid = threadIdx.x, warp = uni(tid >> 5), wg = warp >> 2;
    int cls, rk;
    {
        uint32_t id = blockIdx.x;
        if (USE_SMID) asm("mov.u32 %0, %%smid;" : "=r"(id));
        constexpr unsigned long long M = 0x8E8E8E8Eull | (unsigned long long)(0x47u | 0x47u << 7 | 0x47u << 14 | 0x47u << 21 | 1u << 29) << 32;
        const uint32_t t = id >> 1;
        const int ones = t < 64 ? __popcll(M & ((1ull << t) - 1)) : 33;
        cls = t < 64 ? (int)(M >> t) & 1 : 0;
        rk = 2 * (cls ? ones : (int)t - ones) + (id & 1);
    }
    auto bar_init = [&](int i) {
        uint32_t c = 1;
        if (i == B_P1D || (i >= B_RE && i < B_RE + 13)) c = 12;
        else if (i >= B_WCH && i < B_WL) c = 4;
        asm volatile("st.shared.v2.u32 [%0], {%1, %2};" :: "r"(sb + BARS + 8 * i), "r"((0x100000u - c) << 1), "r"((0x100000u - c) << 11) : "memory");
        fence_async_smem();
    };
    if (wg == 3) {
        asm volatile("setmaxnreg.dec.sync.aligned.u32 32;");
        if (warp == 12) {
            bar_init(tid & 31);
            __syncwarp();
            asm volatile("bar.arrive 4, 416;" ::: "memory");
            load_first(cls, rk, sb, mp);
            asm volatile("bar.sync 5, 416;" ::: "memory");
            load_warp(cls, rk, sb, mp);
        } else if (warp == 13) {
            if ((tid & 31) < 8) asm volatile("prefetch.tensormap [%0];" :: "l"(reinterpret_cast<const CUtensorMap*>(&mp) + 1 + (tid & 31)) : "memory");
            __syncwarp();
            asm volatile("bar.sync 6, 416;" ::: "memory");
            store_warp(cls, rk, sb, mp);
        } else if (warp == 14) {
            asm volatile("bar.sync 7, 416;" ::: "memory");
            load3_warp(cls, rk, sb, mp);
        } else {
            if ((tid & 31) == 0) probe(cls, rk, mp.scr);
            __syncwarp();
            asm volatile("bar.sync 8, 416;" ::: "memory");
            signal_warp(cls, rk, sb, mp.scr);
        }
    } else {
        if (tid >= 32 && tid < NBAR) bar_init(tid);
        {
            const int r = tid % 40;
            asm volatile("st.shared.u32 [%0], %1;" :: "r"(sb + TBL + 4 * tid), "r"(cos_bits(r) | (cos_bits(r < 30 ? r + 10 : r - 30) << 16)) : "memory");
        }
        __syncwarp();
        asm volatile("bar.sync 4, 416;" ::: "memory");
        asm volatile("bar.arrive 5, 416;" ::: "memory");
        asm volatile("bar.arrive 6, 416;" ::: "memory");
        asm volatile("bar.arrive 7, 416;" ::: "memory");
        asm volatile("bar.arrive 8, 416;" ::: "memory");
        if (tid == 64) PROF(121);
        asm volatile("setmaxnreg.inc.sync.aligned.u32 160;");
        task_w(wg, cls * NH + rk, sb);
        const int id = wg * NH + rk;
        PROFW(8 + wg * 8);
        if (id < 192) task_p1(wg, id / 3, sb);
        e_arrive(sb + BARS + 8 * B_P1D);
        PROFW(8 + wg * 8 + 3);
        task_p2(wg, rk, sb);
        if (id < 192) task_p3(wg, id / 3, sb);
        PROFW(64 + wg * 8 + 3);
    }
}

typedef CUresult (*EncodeFn)(CUtensorMap*, CUtensorMapDataType, cuuint32_t, void*, const cuuint64_t*, const cuuint64_t*, const cuuint32_t*, const cuuint32_t*,
                             CUtensorMapInterleave, CUtensorMapSwizzle, CUtensorMapL2promotion, CUtensorMapFloatOOBfill);

static void encode3(EncodeFn fn, CUtensorMap* m, void* ptr, uint64_t d0, uint64_t d1, uint64_t d2, uint64_t s1, uint64_t s2,
                    uint32_t b0, uint32_t b1, uint32_t b2, CUtensorMapSwizzle sw) {
    cuuint64_t dims[3] = {d0, d1, d2}, strides[2] = {s1, s2};
    cuuint32_t box[3] = {b0, b1, b2}, es[3] = {1, 1, 1};
    fn(m, CU_TENSOR_MAP_DATA_TYPE_BFLOAT16, 3, ptr, dims, strides, box, es, CU_TENSOR_MAP_INTERLEAVE_NONE, sw,
       CU_TENSOR_MAP_L2_PROMOTION_NONE, CU_TENSOR_MAP_FLOAT_OOB_FILL_NONE);
}

extern "C" void kernel_launch(void* const* d_in, const int* in_sizes, int n_in, void* d_out, int out_size) {
    (void)in_sizes; (void)n_in; (void)out_size;
    void* fnp = nullptr; cudaDriverEntryPointQueryResult qr;
    cudaGetDriverEntryPoint("cuTensorMapEncodeTiled", &fnp, cudaEnableDefault, &qr);
    EncodeFn fn = (EncodeFn)fnp;
    void* xf = nullptr; cudaGetSymbolAddress(&xf, g_scr);
    xf = (void*)(((uintptr_t)xf + (1u << 21) - 1) & ~(uintptr_t)((1u << 21) - 1));
    void* wf = nullptr; cudaGetSymbolAddress(&wf, g_wf);
    Maps mp;
    mp.scr = (char*)xf;
    {
        cuuint32_t b16[5] = {64, 4, 2, 2, 2}, b8[5] = {64, 4, 2, 1, 2}, es[5] = {1, 1, 1, 1, 1};
        cuuint64_t d[5] = {64, 4, 2, 2, 13 << 14}, st[4] = {16384, 262144, 1048576, 128};
        fn(&mp.f16, CU_TENSOR_MAP_DATA_TYPE_BFLOAT16, 5, xf, d, st, b16, es, CU_TENSOR_MAP_INTERLEAVE_NONE, CU_TENSOR_MAP_SWIZZLE_NONE, CU_TENSOR_MAP_L2_PROMOTION_NONE, CU_TENSOR_MAP_FLOAT_OOB_FILL_NONE);
        fn(&mp.f8, CU_TENSOR_MAP_DATA_TYPE_BFLOAT16, 5, xf, d, st, b8, es, CU_TENSOR_MAP_INTERLEAVE_NONE, CU_TENSOR_MAP_SWIZZLE_NONE, CU_TENSOR_MAP_L2_PROMOTION_NONE, CU_TENSOR_MAP_FLOAT_OOB_FILL_NONE);
    }
    encode3(fn, &mp.x6, d_in[0], 96, 224, 224, 192, 224 * 192, 32, 4, 6, CU_TENSOR_MAP_SWIZZLE_64B);
    encode3(fn, &mp.x34, d_in[0], 96, 224, 224, 192, 224 * 192, 32, 4, 34, CU_TENSOR_MAP_SWIZZLE_64B);
    encode3(fn, &mp.x28, d_in[0], 96, 224, 224, 192, 224 * 192, 32, 4, 28, CU_TENSOR_MAP_SWIZZLE_64B);
    encode3(fn, &mp.w, d_in[1], 96, 49, 96, 18432, 192, 32, 56, 2, CU_TENSOR_MAP_SWIZZLE_64B);
    encode3(fn, &mp.wst, wf, 256, 200, 72, 36864, 512, 256, 8, 1, CU_TENSOR_MAP_SWIZZLE_NONE);
    encode3(fn, &mp.y4, d_out, 96, 224, 224, 192, 224 * 192, 32, 4, 28, CU_TENSOR_MAP_SWIZZLE_64B);
    encode3(fn, &mp.y2, d_out, 96, 224, 224, 192, 224 * 192, 32, 2, 28, CU_TENSOR_MAP_SWIZZLE_64B);
    int dev = 0, nsm = 0;
    cudaGetDevice(&dev);
    cudaDeviceGetAttribute(&nsm, cudaDevAttrMultiProcessorCount, dev);
    auto kern = nsm == NSM ? fftconv_kernel<true> : fftconv_kernel<false>;
    cudaFuncSetAttribute(kern, cudaFuncAttributeMaxDynamicSharedMemorySize, SMEM_BYTES);
    kern<<<NSM, 512, SMEM_BYTES>>>(mp);
}
```

```cpp
#include <cuda_runtime.h>
#include <cuda_bf16.h>
#include <cuda.h>
#include <stdint.h>

__device__ __align__(128) const uint32_t TAB_P1[4480] = {
0x3e75,0,0x3e72,0,0x8000,0,0xbd19,0,0x3e750000,0,0x3e720000,0,0x80000000,0,0xbd190000,0,
0,0x3e75,0,0x3e72,0,0x8000,0,0xbd19,0,0x3e750000,0,0x3e720000,0,0x80000000,0,0xbd190000,
0x3e69,0,0x3e5a,0,0xbd97,0,0xbdde,0,0x3e690000,0,0x3e5a0000,0,0xbd970000,0,0xbdde0000,0,
0,0x3e69,0,0x3e5a,0,0xbd97,0,0xbdde,0,0x3e690000,0,0x3e5a0000,0,0xbd970000,0,0xbdde0000,
0x3e75,0,0x3e5a,0,0x8000,0,0xbdde,0,0x3e750000,0,0x3e5a0000,0,0x80000000,0,0xbdde0000,0,
0,0x3e75,0,0x3e5a,0,0x8000,0,0xbdde,0,0x3e750000,0,0x3e5a0000,0,0x80000000,0,0xbdde0000,
0x3e10,0,0x3d19,0,0xbe46,0,0xbe72,0,0x3e100000,0,0x3d190000,0,0xbe460000,0,0xbe720000,0,
0,0x3e10,0,0x3d19,0,0xbe46,0,0xbe72,0,0x3e100000,0,0x3d190000,0,0xbe460000,0,0xbe720000,
0x3e75,0,0x3e2d,0,0x8000,0,0xbe2d,0,0x3e750000,0,0x3e2d0000,0,0x80000000,0,0xbe2d0000,0,
0,0x3e75,0,0x3e2d,0,0x8000,0,0xbe2d,0,0x3e750000,0,0x3e2d0000,0,0x80000000,0,0xbe2d0000,
0,0,0xbe2d,0,0xbe75,0,0xbe2d,0,0,0,0xbe2d0000,0,0xbe750000,0,0xbe2d0000,0,
0,0,0,0xbe2d,0,0xbe75,0,0xbe2d,0,0,0,0xbe2d0000,0,0xbe750000,0,0xbe2d0000,
0x3e75,0,0x3dde,0,0x8000,0,0xbe5a,0,0x3e750000,0,0x3dde0000,0,0x80000000,0,0xbe5a0000,0,
0,0x3e75,0,0x3dde,0,0x8000,0,0xbe5a,0,0x3e750000,0,0x3dde0000,0,0x80000000,0,0xbe5a0000,
0xbe10,0,0xbe72,0,0xbe46,0,0x3d19,0,0xbe100000,0,0xbe720000,0,0xbe460000,0,0x3d190000,0,
0,0xbe10,0,0xbe72,0,0xbe46,0,0x3d19,0,0xbe100000,0,0xbe720000,0,0xbe460000,0,0x3d190000,
0x3e75,0,0x3d19,0,0x8000,0,0xbe72,0,0x3e750000,0,0x3d190000,0,0x80000000,0,0xbe720000,0,
0,0x3e75,0,0x3d19,0,0x8000,0,0xbe72,0,0x3e750000,0,0x3d190000,0,0x80000000,0,0xbe720000,
0xbe69,0,0xbdde,0,0xbd97,0,0x3e5a,0,0xbe690000,0,0xbdde0000,0,0xbd970000,0,0x3e5a0000,0,
0,0xbe69,0,0xbdde,0,0xbd97,0,0x3e5a,0,0xbe690000,0,0xbdde0000,0,0xbd970000,0,0x3e5a0000,
0x3e75,0,0xbd19,0,0x8000,0,0xbe72,0,0x3e750000,0,0xbd190000,0,0x80000000,0,0xbe720000,0,
0,0x3e75,0,0xbd19,0,0x8000,0,0xbe72,0,0x3e750000,0,0xbd190000,0,0x80000000,0,0xbe720000,
0xbe69,0,0x3dde,0,0x3d97,0,0x3e5a,0,0xbe690000,0,0x3dde0000,0,0x3d970000,0,0x3e5a0000,0,
0,0xbe69,0,0x3dde,0,0x3d97,0,0x3e5a,0,0xbe690000,0,0x3dde0000,0,0x3d970000,0,0x3e5a0000,
0x3e75,0,0xbdde,0,0x8000,0,0xbe5a,0,0x3e750000,0,0xbdde0000,0,0x80000000,0,0xbe5a0000,0,
0,0x3e75,0,0xbdde,0,0x8000,0,0xbe5a,0,0x3e750000,0,0xbdde0000,0,0x80000000,0,0xbe5a0000,
0xbe10,0,0x3e72,0,0x3e46,0,0x3d19,0,0xbe100000,0,0x3e720000,0,0x3e460000,0,0x3d190000,0,
0,0xbe10,0,0x3e72,0,0x3e46,0,0x3d19,0,0xbe100000,0,0x3e720000,0,0x3e460000,0,0x3d190000,
0x3e75,0,0xbe2d,0,0x8000,0,0xbe2d,0,0x3e750000,0,0xbe2d0000,0,0x80000000,0,0xbe2d0000,0,
0,0x3e75,0,0xbe2d,0,0x8000,0,0xbe2d,0,0x3e750000,0,0xbe2d0000,0,0x80000000,0,0xbe2d0000,
0,0,0x3e2d,0,0x3e75,0,0xbe2d,0,0,0,0x3e2d0000,0,0x3e750000,0,0xbe2d0000,0,
0,0,0,0x3e2d,0,0x3e75,0,0xbe2d,0,0,0,0x3e2d0000,0,0x3e750000,0,0xbe2d0000,
0x3e75,0,0xbe5a,0,0x8000,0,0xbdde,0,0x3e750000,0,0xbe5a0000,0,0x80000000,0,0xbdde0000,0,
0,0x3e75,0,0xbe5a,0,0x8000,0,0xbdde,0,0x3e750000,0,0xbe5a0000,0,0x80000000,0,0xbdde0000,
0x3e10,0,0xbd19,0,0x3e46,0,0xbe72,0,0x3e100000,0,0xbd190000,0,0x3e460000,0,0xbe720000,0,
0,0x3e10,0,0xbd19,0,0x3e46,0,0xbe72,0,0x3e100000,0,0xbd190000,0,0x3e460000,0,0xbe720000,
0x3e75,0,0xbe72,0,0x8000,0,0xbd19,0,0x3e750000,0,0xbe720000,0,0x80000000,0,0xbd190000,0,
0,0x3e75,0,0xbe72,0,0x8000,0,0xbd19,0,0x3e750000,0,0xbe720000,0,0x80000000,0,0xbd190000,
0x3e69,0,0xbe5a,0,0x3d97,0,0xbdde,0,0x3e690000,0,0xbe5a0000,0,0x3d970000,0,0xbdde0000,0,
0,0x3e69,0,0xbe5a,0,0x3d97,0,0xbdde,0,0x3e690000,0,0xbe5a0000,0,0x3d970000,0,0xbdde0000,
0x3e46,0,0x3e2d,0,0xbe10,0,0xbe2d,0,0x3e460000,0,0x3e2d0000,0,0xbe100000,0,0xbe2d0000,0,
0,0x3e46,0,0x3e2d,0,0xbe10,0,0xbe2d,0,0x3e460000,0,0x3e2d0000,0,0xbe100000,0,0xbe2d0000,
0x3e10,0,0x3dde,0,0xbe46,0,0xbe5a,0,0x3e100000,0,0x3dde0000,0,0xbe460000,0,0xbe5a0000,0,
0,0x3e10,0,0x3dde,0,0xbe46,0,0xbe5a,0,0x3e100000,0,0x3dde0000,0,0xbe460000,0,0xbe5a0000,
0xbd97,0,0xbe2d,0,0xbe69,0,0xbe2d,0,0xbd970000,0,0xbe2d0000,0,0xbe690000,0,0xbe2d0000,0,
0,0xbd97,0,0xbe2d,0,0xbe69,0,0xbe2d,0,0xbd970000,0,0xbe2d0000,0,0xbe690000,0,0xbe2d0000,
0xbe69,0,0xbe72,0,0xbd97,0,0x3d19,0,0xbe690000,0,0xbe720000,0,0xbd970000,0,0x3d190000,0,
0,0xbe69,0,0xbe72,0,0xbd97,0,0x3d19,0,0xbe690000,0,0xbe720000,0,0xbd970000,0,0x3d190000,
0xbe75,0,0xbe2d,0,0x8000,0,0x3e2d,0,0xbe750000,0,0xbe2d0000,0,0x80000000,0,0x3e2d0000,0,
0,0xbe75,0,0xbe2d,0,0x8000,0,0x3e2d,0,0xbe750000,0,0xbe2d0000,0,0x80000000,0,0x3e2d0000,
0,0,0x3e2d,0,0x3e75,0,0x3e2d,0,0,0,0x3e2d0000,0,0x3e750000,0,0x3e2d0000,0,
0,0,0,0x3e2d,0,0x3e75,0,0x3e2d,0,0,0,0x3e2d0000,0,0x3e750000,0,0x3e2d0000,
0xbd97,0,0x3e2d,0,0x3e69,0,0x3e2d,0,0xbd970000,0,0x3e2d0000,0,0x3e690000,0,0x3e2d0000,0,
0,0xbd97,0,0x3e2d,0,0x3e69,0,0x3e2d,0,0xbd970000,0,0x3e2d0000,0,0x3e690000,0,0x3e2d0000,
0x3e69,0,0x3d19,0,0xbd97,0,0xbe72,0,0x3e690000,0,0x3d190000,0,0xbd970000,0,0xbe720000,0,
0,0x3e69,0,0x3d19,0,0xbd97,0,0xbe72,0,0x3e690000,0,0x3d190000,0,0xbd970000,0,0xbe720000,
0x3e46,0,0x3e2d,0,0x3e10,0,0xbe2d,0,0x3e460000,0,0x3e2d0000,0,0x3e100000,0,0xbe2d0000,0,
0,0x3e46,0,0x3e2d,0,0x3e10,0,0xbe2d,0,0x3e460000,0,0x3e2d0000,0,0x3e100000,0,0xbe2d0000,
0xbe10,0,0xbe5a,0,0xbe46,0,0x3dde,0,0xbe100000,0,0xbe5a0000,0,0xbe460000,0,0x3dde0000,0,
0,0xbe10,0,0xbe5a,0,0xbe46,0,0x3dde,0,0xbe100000,0,0xbe5a0000,0,0xbe460000,0,0x3dde0000,
0x3e46,0,0xbe2d,0,0xbe10,0,0xbe2d,0,0x3e460000,0,0xbe2d0000,0,0xbe100000,0,0xbe2d0000,0,
0,0x3e46,0,0xbe2d,0,0xbe10,0,0xbe2d,0,0x3e460000,0,0xbe2d0000,0,0xbe100000,0,0xbe2d0000,
0xbe10,0,0x3e5a,0,0x3e46,0,0x3dde,0,0xbe100000,0,0x3e5a0000,0,0x3e460000,0,0x3dde0000,0,
0,0xbe10,0,0x3e5a,0,0x3e46,0,0x3dde,0,0xbe100000,0,0x3e5a0000,0,0x3e460000,0,0x3dde0000,
0xbd97,0,0xbe2d,0,0xbe69,0,0x3e2d,0,0xbd970000,0,0xbe2d0000,0,0xbe690000,0,0x3e2d0000,0,
0,0xbd97,0,0xbe2d,0,0xbe69,0,0x3e2d,0,0xbd970000,0,0xbe2d0000,0,0xbe690000,0,0x3e2d0000,
0x3e69,0,0xbd19,0,0x3d97,0,0xbe72,0,0x3e690000,0,0xbd190000,0,0x3d970000,0,0xbe720000,0,
0,0x3e69,0,0xbd19,0,0x3d97,0,0xbe72,0,0x3e690000,0,0xbd190000,0,0x3d970000,0,0xbe720000,
0xbe75,0,0x3e2d,0,0x8000,0,0x3e2d,0,0xbe750000,0,0x3e2d0000,0,0x80000000,0,0x3e2d0000,0,
0,0xbe75,0,0x3e2d,0,0x8000,0,0x3e2d,0,0xbe750000,0,0x3e2d0000,0,0x80000000,0,0x3e2d0000,
0,0,0xbe2d,0,0xbe75,0,0x3e2d,0,0,0,0xbe2d0000,0,0xbe750000,0,0x3e2d0000,0,
0,0,0,0xbe2d,0,0xbe75,0,0x3e2d,0,0,0,0xbe2d0000,0,0xbe750000,0,0x3e2d0000,
0xbd97,0,0x3e2d,0,0x3e69,0,0xbe2d,0,0xbd970000,0,0x3e2d0000,0,0x3e690000,0,0xbe2d0000,0,
0,0xbd97,0,0x3e2d,0,0x3e69,0,0xbe2d,0,0xbd970000,0,0x3e2d0000,0,0x3e690000,0,0xbe2d0000,
0xbe69,0,0x3e72,0,0x3d97,0,0x3d19,0,0xbe690000,0,0x3e720000,0,0x3d970000,0,0x3d190000,0,
0,0xbe69,0,0x3e72,0,0x3d97,0,0x3d19,0,0xbe690000,0,0x3e720000,0,0x3d970000,0,0x3d190000,
0x3e46,0,0xbe2d,0,0x3e10,0,0xbe2d,0,0x3e460000,0,0xbe2d0000,0,0x3e100000,0,0xbe2d0000,0,
0,0x3e46,0,0xbe2d,0,0x3e10,0,0xbe2d,0,0x3e460000,0,0xbe2d0000,0,0x3e100000,0,0xbe2d0000,
0x3e10,0,0xbdde,0,0x3e46,0,0xbe5a,0,0x3e100000,0,0xbdde0000,0,0x3e460000,0,0xbe5a0000,0,
0,0x3e10,0,0xbdde,0,0x3e46,0,0xbe5a,0,0x3e100000,0,0xbdde0000,0,0x3e460000,0,0xbe5a0000,
0x3d97,0,0x3d19,0,0xbe69,0,0xbe72,0,0x3d970000,0,0x3d190000,0,0xbe690000,0,0xbe720000,0,
0,0x3d97,0,0x3d19,0,0xbe69,0,0xbe72,0,0x3d970000,0,0x3d190000,0,0xbe690000,0,0xbe720000,
0,0,0xbd19,0,0xbe75,0,0xbe72,0,0,0,0xbd190000,0,0xbe750000,0,0xbe720000,0,
0,0,0,0xbd19,0,0xbe75,0,0xbe72,0,0,0,0xbd190000,0,0xbe750000,0,0xbe720000,
0xbe46,0,0xbdde,0,0x3e10,0,0x3e5a,0,0xbe460000,0,0xbdde0000,0,0x3e100000,0,0x3e5a0000,0,
0,0xbe46,0,0xbdde,0,0x3e10,0,0x3e5a,0,0xbe460000,0,0xbdde0000,0,0x3e100000,0,0x3e5a0000,
0,0,0x3dde,0,0x3e75,0,0x3e5a,0,0,0,0x3dde0000,0,0x3e750000,0,0x3e5a0000,0,
0,0,0,0x3dde,0,0x3e75,0,0x3e5a,0,0,0,0x3dde0000,0,0x3e750000,0,0x3e5a0000,
0x3e75,0,0x3e2d,0,0x8000,0,0xbe2d,0,0x3e750000,0,0x3e2d0000,0,0x80000000,0,0xbe2d0000,0,
0,0x3e75,0,0x3e2d,0,0x8000,0,0xbe2d,0,0x3e750000,0,0x3e2d0000,0,0x80000000,0,0xbe2d0000,
0,0,0xbe2d,0,0xbe75,0,0xbe2d,0,0,0,0xbe2d0000,0,0xbe750000,0,0xbe2d0000,0,
0,0,0,0xbe2d,0,0xbe75,0,0xbe2d,0,0,0,0xbe2d0000,0,0xbe750000,0,0xbe2d0000,
0xbe46,0,0xbe5a,0,0xbe10,0,0x3dde,0,0xbe460000,0,0xbe5a0000,0,0xbe100000,0,0x3dde0000,0,
0,0xbe46,0,0xbe5a,0,0xbe10,0,0x3dde,0,0xbe460000,0,0xbe5a0000,0,0xbe100000,0,0x3dde0000,
0,0,0x3e5a,0,0x3e75,0,0x3dde,0,0,0,0x3e5a0000,0,0x3e750000,0,0x3dde0000,0,
0,0,0,0x3e5a,0,0x3e75,0,0x3dde,0,0,0,0x3e5a0000,0,0x3e750000,0,0x3dde0000,
0x3d97,0,0x3e72,0,0x3e69,0,0xbd19,0,0x3d970000,0,0x3e720000,0,0x3e690000,0,0xbd190000,0,
0,0x3d97,0,0x3e72,0,0x3e69,0,0xbd19,0,0x3d970000,0,0x3e720000,0,0x3e690000,0,0xbd190000,
0,0,0xbe72,0,0xbe75,0,0xbd19,0,0,0,0xbe720000,0,0xbe750000,0,0xbd190000,0,
0,0,0,0xbe72,0,0xbe75,0,0xbd19,0,0,0,0xbe720000,0,0xbe750000,0,0xbd190000,
0x3d97,0,0xbe72,0,0xbe69,0,0xbd19,0,0x3d970000,0,0xbe720000,0,0xbe690000,0,0xbd190000,0,
0,0x3d97,0,0xbe72,0,0xbe69,0,0xbd19,0,0x3d970000,0,0xbe720000,0,0xbe690000,0,0xbd190000,
0,0,0x3e72,0,0x3e75,0,0xbd19,0,0,0,0x3e720000,0,0x3e750000,0,0xbd190000,0,
0,0,0,0x3e72,0,0x3e75,0,0xbd19,0,0,0,0x3e720000,0,0x3e750000,0,0xbd190000,
0xbe46,0,0x3e5a,0,0x3e10,0,0x3dde,0,0xbe460000,0,0x3e5a0000,0,0x3e100000,0,0x3dde0000,0,
0,0xbe46,0,0x3e5a,0,0x3e10,0,0x3dde,0,0xbe460000,0,0x3e5a0000,0,0x3e100000,0,0x3dde0000,
0,0,0xbe5a,0,0xbe75,0,0x3dde,0,0,0,0xbe5a0000,0,0xbe750000,0,0x3dde0000,0,
0,0,0,0xbe5a,0,0xbe75,0,0x3dde,0,0,0,0xbe5a0000,0,0xbe750000,0,0x3dde0000,
0x3e75,0,0xbe2d,0,0x8000,0,0xbe2d,0,0x3e750000,0,0xbe2d0000,0,0x80000000,0,0xbe2d0000,0,
0,0x3e75,0,0xbe2d,0,0x8000,0,0xbe2d,0,0x3e750000,0,0xbe2d0000,0,0x80000000,0,0xbe2d0000,
0,0,0x3e2d,0,0x3e75,0,0xbe2d,0,0,0,0x3e2d0000,0,0x3e750000,0,0xbe2d0000,0,
0,0,0,0x3e2d,0,0x3e75,0,0xbe2d,0,0,0,0x3e2d0000,0,0x3e750000,0,0xbe2d0000,
0xbe46,0,0x3dde,0,0xbe10,0,0x3e5a,0,0xbe460000,0,0x3dde0000,0,0xbe100000,0,0x3e5a0000,0,
0,0xbe46,0,0x3dde,0,0xbe10,0,0x3e5a,0,0xbe460000,0,0x3dde0000,0,0xbe100000,0,0x3e5a0000,
0,0,0xbdde,0,0xbe75,0,0x3e5a,0,0,0,0xbdde0000,0,0xbe750000,0,0x3e5a0000,0,
0,0,0,0xbdde,0,0xbe75,0,0x3e5a,0,0,0,0xbdde0000,0,0xbe750000,0,0x3e5a0000,
0x3d97,0,0xbd19,0,0x3e69,0,0xbe72,0,0x3d970000,0,0xbd190000,0,0x3e690000,0,0xbe720000,0,
0,0x3d97,0,0xbd19,0,0x3e69,0,0xbe72,0,0x3d970000,0,0xbd190000,0,0x3e690000,0,0xbe720000,
0,0,0x3d19,0,0x3e75,0,0xbe72,0,0,0,0x3d190000,0,0x3e750000,0,0xbe720000,0,
0,0,0,0x3d19,0,0x3e75,0,0xbe72,0,0,0,0x3d190000,0,0x3e750000,0,0xbe720000,
0xbd97,0,0xbdde,0,0xbe69,0,0xbe5a,0,0xbd970000,0,0xbdde0000,0,0xbe690000,0,0xbe5a0000,0,
0,0xbd97,0,0xbdde,0,0xbe69,0,0xbe5a,0,0xbd970000,0,0xbdde0000,0,0xbe690000,0,0xbe5a0000,
0xbe10,0,0xbe2d,0,0xbe46,0,0xbe2d,0,0xbe100000,0,0xbe2d0000,0,0xbe460000,0,0xbe2d0000,0,
0,0xbe10,0,0xbe2d,0,0xbe46,0,0xbe2d,0,0xbe100000,0,0xbe2d0000,0,0xbe460000,0,0xbe2d0000,
0x3e46,0,0x3e72,0,0x3e10,0,0x3d19,0,0x3e460000,0,0x3e720000,0,0x3e100000,0,0x3d190000,0,
0,0x3e46,0,0x3e72,0,0x3e10,0,0x3d19,0,0x3e460000,0,0x3e720000,0,0x3e100000,0,0x3d190000,
0x3e69,0,0x3e2d,0,0xbd97,0,0xbe2d,0,0x3e690000,0,0x3e2d0000,0,0xbd970000,0,0xbe2d0000,0,
0,0x3e69,0,0x3e2d,0,0xbd97,0,0xbe2d,0,0x3e690000,0,0x3e2d0000,0,0xbd970000,0,0xbe2d0000,
0xbe75,0,0xbe2d,0,0x8000,0,0x3e2d,0,0xbe750000,0,0xbe2d0000,0,0x80000000,0,0x3e2d0000,0,
0,0xbe75,0,0xbe2d,0,0x8000,0,0x3e2d,0,0xbe750000,0,0xbe2d0000,0,0x80000000,0,0x3e2d0000,
0,0,0x3e2d,0,0x3e75,0,0x3e2d,0,0,0,0x3e2d0000,0,0x3e750000,0,0x3e2d0000,0,
0,0,0,0x3e2d,0,0x3e75,0,0x3e2d,0,0,0,0x3e2d0000,0,0x3e750000,0,0x3e2d0000,
0x3e46,0,0xbd19,0,0xbe10,0,0xbe72,0,0x3e460000,0,0xbd190000,0,0xbe100000,0,0xbe720000,0,
0,0x3e46,0,0xbd19,0,0xbe10,0,0xbe72,0,0x3e460000,0,0xbd190000,0,0xbe100000,0,0xbe720000,
0xbe69,0,0xbe2d,0,0xbd97,0,0x3e2d,0,0xbe690000,0,0xbe2d0000,0,0xbd970000,0,0x3e2d0000,0,
0,0xbe69,0,0xbe2d,0,0xbd97,0,0x3e2d,0,0xbe690000,0,0xbe2d0000,0,0xbd970000,0,0x3e2d0000,
0xbd97,0,0x3e5a,0,0x3e69,0,0x3dde,0,0xbd970000,0,0x3e5a0000,0,0x3e690000,0,0x3dde0000,0,
0,0xbd97,0,0x3e5a,0,0x3e69,0,0x3dde,0,0xbd970000,0,0x3e5a0000,0,0x3e690000,0,0x3dde0000,
0x3e10,0,0xbe2d,0,0xbe46,0,0xbe2d,0,0x3e100000,0,0xbe2d0000,0,0xbe460000,0,0xbe2d0000,0,
0,0x3e10,0,0xbe2d,0,0xbe46,0,0xbe2d,0,0x3e100000,0,0xbe2d0000,0,0xbe460000,0,0xbe2d0000,
0xbd97,0,0xbe5a,0,0xbe69,0,0x3dde,0,0xbd970000,0,0xbe5a0000,0,0xbe690000,0,0x3dde0000,0,
0,0xbd97,0,0xbe5a,0,0xbe69,0,0x3dde,0,0xbd970000,0,0xbe5a0000,0,0xbe690000,0,0x3dde0000,
0x3e10,0,0x3e2d,0,0x3e46,0,0xbe2d,0,0x3e100000,0,0x3e2d0000,0,0x3e460000,0,0xbe2d0000,0,
0,0x3e10,0,0x3e2d,0,0x3e46,0,0xbe2d,0,0x3e100000,0,0x3e2d0000,0,0x3e460000,0,0xbe2d0000,
0x3e46,0,0x3d19,0,0x3e10,0,0xbe72,0,0x3e460000,0,0x3d190000,0,0x3e100000,0,0xbe720000,0,
0,0x3e46,0,0x3d19,0,0x3e10,0,0xbe72,0,0x3e460000,0,0x3d190000,0,0x3e100000,0,0xbe720000,
0xbe69,0,0x3e2d,0,0x3d97,0,0x3e2d,0,0xbe690000,0,0x3e2d0000,0,0x3d970000,0,0x3e2d0000,0,
0,0xbe69,0,0x3e2d,0,0x3d97,0,0x3e2d,0,0xbe690000,0,0x3e2d0000,0,0x3d970000,0,0x3e2d0000,
0xbe75,0,0x3e2d,0,0x8000,0,0x3e2d,0,0xbe750000,0,0x3e2d0000,0,0x80000000,0,0x3e2d0000,0,
0,0xbe75,0,0x3e2d,0,0x8000,0,0x3e2d,0,0xbe750000,0,0x3e2d0000,0,0x80000000,0,0x3e2d0000,
0,0,0xbe2d,0,0xbe75,0,0x3e2d,0,0,0,0xbe2d0000,0,0xbe750000,0,0x3e2d0000,0,
0,0,0,0xbe2d,0,0xbe75,0,0x3e2d,0,0,0,0xbe2d0000,0,0xbe750000,0,0x3e2d0000,
0x3e46,0,0xbe72,0,0xbe10,0,0x3d19,0,0x3e460000,0,0xbe720000,0,0xbe100000,0,0x3d190000,0,
0,0x3e46,0,0xbe72,0,0xbe10,0,0x3d19,0,0x3e460000,0,0xbe720000,0,0xbe100000,0,0x3d190000,
0x3e69,0,0xbe2d,0,0x3d97,0,0xbe2d,0,0x3e690000,0,0xbe2d0000,0,0x3d970000,0,0xbe2d0000,0,
0,0x3e69,0,0xbe2d,0,0x3d97,0,0xbe2d,0,0x3e690000,0,0xbe2d0000,0,0x3d970000,0,0xbe2d0000,
0xbd97,0,0x3dde,0,0x3e69,0,0xbe5a,0,0xbd970000,0,0x3dde0000,0,0x3e690000,0,0xbe5a0000,0,
0,0xbd97,0,0x3dde,0,0x3e69,0,0xbe5a,0,0xbd970000,0,0x3dde0000,0,0x3e690000,0,0xbe5a0000,
0xbe10,0,0x3e2d,0,0x3e46,0,0xbe2d,0,0xbe100000,0,0x3e2d0000,0,0x3e460000,0,0xbe2d0000,0,
0,0xbe10,0,0x3e2d,0,0x3e46,0,0xbe2d,0,0xbe100000,0,0x3e2d0000,0,0x3e460000,0,0xbe2d0000,
0xbe46,0,0xbe5a,0,0xbe10,0,0xbdde,0,0xbe460000,0,0xbe5a0000,0,0xbe100000,0,0xbdde0000,0,
0,0xbe46,0,0xbe5a,0,0xbe10,0,0xbdde,0,0xbe460000,0,0xbe5a0000,0,0xbe100000,0,0xbdde0000,
0xbe69,0,0xbe72,0,0xbd97,0,0xbd19,0,0xbe690000,0,0xbe720000,0,0xbd970000,0,0xbd190000,0,
0,0xbe69,0,0xbe72,0,0xbd97,0,0xbd19,0,0xbe690000,0,0xbe720000,0,0xbd970000,0,0xbd190000,
0x3d97,0,0xbd19,0,0xbe69,0,0xbe72,0,0x3d970000,0,0xbd190000,0,0xbe690000,0,0xbe720000,0,
0,0x3d97,0,0xbd19,0,0xbe69,0,0xbe72,0,0x3d970000,0,0xbd190000,0,0xbe690000,0,0xbe720000,
0xbe10,0,0xbe5a,0,0xbe46,0,0xbdde,0,0xbe100000,0,0xbe5a0000,0,0xbe460000,0,0xbdde0000,0,
0,0xbe10,0,0xbe5a,0,0xbe46,0,0xbdde,0,0xbe100000,0,0xbe5a0000,0,0xbe460000,0,0xbdde0000,
0x3e75,0,0x3e2d,0,0x8000,0,0xbe2d,0,0x3e750000,0,0x3e2d0000,0,0x80000000,0,0xbe2d0000,0,
0,0x3e75,0,0x3e2d,0,0x8000,0,0xbe2d,0,0x3e750000,0,0x3e2d0000,0,0x80000000,0,0xbe2d0000,
0,0,0xbe2d,0,0xbe75,0,0xbe2d,0,0,0,0xbe2d0000,0,0xbe750000,0,0xbe2d0000,0,
0,0,0,0xbe2d,0,0xbe75,0,0xbe2d,0,0,0,0xbe2d0000,0,0xbe750000,0,0xbe2d0000,
0x3d97,0,0x3e72,0,0x3e69,0,0x3d19,0,0x3d970000,0,0x3e720000,0,0x3e690000,0,0x3d190000,0,
0,0x3d97,0,0x3e72,0,0x3e69,0,0x3d19,0,0x3d970000,0,0x3e720000,0,0x3e690000,0,0x3d190000,
0x3e10,0,0xbdde,0,0xbe46,0,0xbe5a,0,0x3e100000,0,0xbdde0000,0,0xbe460000,0,0xbe5a0000,0,
0,0x3e10,0,0xbdde,0,0xbe46,0,0xbe5a,0,0x3e100000,0,0xbdde0000,0,0xbe460000,0,0xbe5a0000,
0xbe46,0,0x3dde,0,0x3e10,0,0x3e5a,0,0xbe460000,0,0x3dde0000,0,0x3e100000,0,0x3e5a0000,0,
0,0xbe46,0,0x3dde,0,0x3e10,0,0x3e5a,0,0xbe460000,0,0x3dde0000,0,0x3e100000,0,0x3e5a0000,
0x3e69,0,0xbd19,0,0xbd97,0,0xbe72,0,0x3e690000,0,0xbd190000,0,0xbd970000,0,0xbe720000,0,
0,0x3e69,0,0xbd19,0,0xbd97,0,0xbe72,0,0x3e690000,0,0xbd190000,0,0xbd970000,0,0xbe720000,
0xbe46,0,0xbdde,0,0xbe10,0,0x3e5a,0,0xbe460000,0,0xbdde0000,0,0xbe100000,0,0x3e5a0000,0,
0,0xbe46,0,0xbdde,0,0xbe10,0,0x3e5a,0,0xbe460000,0,0xbdde0000,0,0xbe100000,0,0x3e5a0000,
0x3e69,0,0x3d19,0,0x3d97,0,0xbe72,0,0x3e690000,0,0x3d190000,0,0x3d970000,0,0xbe720000,0,
0,0x3e69,0,0x3d19,0,0x3d97,0,0xbe72,0,0x3e690000,0,0x3d190000,0,0x3d970000,0,0xbe720000,
0x3d97,0,0xbe72,0,0xbe69,0,0x3d19,0,0x3d970000,0,0xbe720000,0,0xbe690000,0,0x3d190000,0,
0,0x3d97,0,0xbe72,0,0xbe69,0,0x3d19,0,0x3d970000,0,0xbe720000,0,0xbe690000,0,0x3d190000,
0x3e10,0,0x3dde,0,0x3e46,0,0xbe5a,0,0x3e100000,0,0x3dde0000,0,0x3e460000,0,0xbe5a0000,0,
0,0x3e10,0,0x3dde,0,0x3e46,0,0xbe5a,0,0x3e100000,0,0x3dde0000,0,0x3e460000,0,0xbe5a0000,
0x3e75,0,0xbe2d,0,0x8000,0,0xbe2d,0,0x3e750000,0,0xbe2d0000,0,0x80000000,0,0xbe2d0000,0,
0,0x3e75,0,0xbe2d,0,0x8000,0,0xbe2d,0,0x3e750000,0,0xbe2d0000,0,0x80000000,0,0xbe2d0000,
0,0,0x3e2d,0,0x3e75,0,0xbe2d,0,0,0,0x3e2d0000,0,0x3e750000,0,0xbe2d0000,0,
0,0,0,0x3e2d,0,0x3e75,0,0xbe2d,0,0,0,0x3e2d0000,0,0x3e750000,0,0xbe2d0000,
0x3d97,0,0x3d19,0,0x3e69,0,0xbe72,0,0x3d970000,0,0x3d190000,0,0x3e690000,0,0xbe720000,0,
0,0x3d97,0,0x3d19,0,0x3e69,0,0xbe72,0,0x3d970000,0,0x3d190000,0,0x3e690000,0,0xbe720000,
0xbe10,0,0x3e5a,0,0x3e46,0,0xbdde,0,0xbe100000,0,0x3e5a0000,0,0x3e460000,0,0xbdde0000,0,
0,0xbe10,0,0x3e5a,0,0x3e46,0,0xbdde,0,0xbe100000,0,0x3e5a0000,0,0x3e460000,0,0xbdde0000,
0xbe46,0,0x3e5a,0,0x3e10,0,0xbdde,0,0xbe460000,0,0x3e5a0000,0,0x3e100000,0,0xbdde0000,0,
0,0xbe46,0,0x3e5a,0,0x3e10,0,0xbdde,0,0xbe460000,0,0x3e5a0000,0,0x3e100000,0,0xbdde0000,
0xbe69,0,0x3e72,0,0x3d97,0,0xbd19,0,0xbe690000,0,0x3e720000,0,0x3d970000,0,0xbd190000,0,
0,0xbe69,0,0x3e72,0,0x3d97,0,0xbd19,0,0xbe690000,0,0x3e720000,0,0x3d970000,0,0xbd190000,
0x3eb7,0x3eb7,0x3eb7,0x3eb7,0x3eb78000,0x3eb78000,0x3eb78000,0x3eb78000,0x3eb7,0x3de23eae,0x3e573e94,0x3e943e57,0x3eb78000,0x3eaebde2,0x3e94be57,0x3e57be94,
0x3eb7,0x3e573e94,0x3eae3de2,0x3eaebde2,0x3eb78000,0x3e94be57,0x3de2beae,0xbde2beae,0x3eb7,0x3e943e57,0x3eaebde2,0x3de2beae,0x3eb78000,0x3e57be94,0xbde2beae,0xbeaebde2,
0x3eb7,0x3eb7,0x3eb7,0x3eb7,0x3eb78000,0x3eb78000,0x3eb78000,0x3eb78000,0x3eae3de2,0x3eb70000,0x3eaebde2,0x3e94be57,0x3de2beae,0xbeb7,0xbde2beae,0xbe57be94,
0x3e57be94,0xbeb7,0xbe57be94,0xbeaebde2,0xbe94be57,0xbeb78000,0xbe943e57,0xbde23eae,0xbe57be94,0xbeb70000,0xbe573e94,0x3de23eae,0xbe943e57,0x3eb7,0x3e943e57,0x3eaebde2,
0x3eb7,0x3eae3de2,0x3e57be94,0xbe57be94,0x3eb78000,0x3de2beae,0xbe94be57,0xbe943e57,0x3eb7,0x3eb70000,0xbeb7,0xbeb70000,0x3eb78000,0xbeb7,0xbeb78000,0x3eb7,
0x3eb7,0x3eaebde2,0xbe57be94,0xbe573e94,0x3eb78000,0xbde2beae,0xbe943e57,0x3e943e57,0x3eb7,0x3e94be57,0xbeaebde2,0x3de23eae,0x3eb78000,0xbe57be94,0xbde23eae,0x3eaebde2,
0xbeae3de2,0x3eb7,0x3eae3de2,0x3e57be94,0x3de23eae,0x3eb78000,0x3de2beae,0xbe94be57,0x3eb7,0x3eb70000,0xbeb7,0xbeb70000,0x3eb78000,0xbeb7,0xbeb78000,0x3eb7,
0x3eae3de2,0xbeb7,0xbeae3de2,0x3e573e94,0x3de2beae,0xbeb78000,0x3de23eae,0x3e94be57,0x3e57be94,0xbeb70000,0x3e573e94,0x3de2beae,0xbe94be57,0x3eb7,0x3e94be57,0xbeaebde2,
0x3eb7,0x3e57be94,0xbeae3de2,0x3eae3de2,0x3eb78000,0xbe94be57,0x3de23eae,0x3de2beae,0x3eb7,0x3de2beae,0xbe573e94,0x3e94be57,0x3eb78000,0xbeaebde2,0x3e943e57,0xbe57be94,
0x3eb7,0xbeb7,0x3eb7,0xbeb7,0x3eb78000,0xbeb78000,0x3eb78000,0xbeb78000,0x3eb7,0xbde2beae,0x3e573e94,0xbe94be57,0x3eb78000,0xbeae3de2,0x3e94be57,0xbe573e94,
0xbe57be94,0x3eb7,0x3e57be94,0xbeae3de2,0xbe943e57,0x3eb78000,0xbe94be57,0x3de23eae,0xbeae3de2,0x3eb70000,0xbeaebde2,0x3e943e57,0x3de23eae,0xbeb7,0xbde23eae,0x3e57be94,
0x3eb7,0xbeb7,0x3eb7,0xbeb7,0x3eb78000,0xbeb78000,0x3eb78000,0xbeb78000,0x3eae3de2,0xbeb70000,0x3eaebde2,0xbe943e57,0x3de2beae,0x3eb7,0xbde2beae,0x3e573e94,
0x3eb7,0xbe57be94,0x3eae3de2,0xbeae3de2,0x3eb78000,0xbe943e57,0x3de2beae,0x3de23eae,0x3eb7,0xbe94be57,0x3eaebde2,0xbde23eae,0x3eb78000,0xbe573e94,0xbde2beae,0x3eae3de2,
0x3eb7,0xbeaebde2,0x3e57be94,0x3e573e94,0x3eb78000,0xbde23eae,0xbe94be57,0x3e94be57,0x3eb7,0xbeb70000,0xbeb7,0x3eb70000,0x3eb78000,0x3eb7,0xbeb78000,0xbeb7,
0x3e57be94,0x3eb7,0xbe57be94,0x3eae3de2,0xbe94be57,0x3eb78000,0xbe943e57,0x3de2beae,0xbe57be94,0x3eb70000,0xbe573e94,0xbde2beae,0xbe943e57,0xbeb7,0x3e943e57,0xbeae3de2,
0xbeae3de2,0xbeb7,0x3eae3de2,0xbe573e94,0x3de23eae,0xbeb78000,0x3de2beae,0x3e943e57,0x3eb7,0xbeb70000,0xbeb7,0x3eb70000,0x3eb78000,0x3eb7,0xbeb78000,0xbeb7,
0x3eb7,0xbeae3de2,0xbe57be94,0x3e57be94,0x3eb78000,0x3de23eae,0xbe943e57,0xbe94be57,0x3eb7,0xbe943e57,0xbeaebde2,0xbde2beae,0x3eb78000,0x3e573e94,0xbde23eae,0xbeae3de2,
0x3eb7,0xbe573e94,0xbeae3de2,0xbeaebde2,0x3eb78000,0x3e943e57,0x3de23eae,0xbde23eae,0x3eb7,0xbde23eae,0xbe573e94,0xbe943e57,0x3eb78000,0x3eae3de2,0x3e943e57,0x3e573e94,
0x3eae3de2,0x3eb7,0xbeae3de2,0xbe57be94,0x3de2beae,0x3eb78000,0x3de23eae,0xbe943e57,0x3e57be94,0x3eb70000,0x3e573e94,0xbde23eae,0xbe94be57,0xbeb7,0x3e94be57,0x3eae3de2,
0xbe57be94,0xbeb7,0x3e57be94,0x3eaebde2,0xbe943e57,0xbeb78000,0xbe94be57,0xbde2beae,0xbeae3de2,0xbeb70000,0xbeaebde2,0xbe94be57,0x3de23eae,0x3eb7,0xbde23eae,0xbe573e94,
0x3eb7,0x3eb7,0x3eb7,0x3eb7,0x3eb78000,0x3eb78000,0x3eb78000,0x3eb78000,0x3e57be94,0x3de2beae,0xbeb7,0xbde2beae,0xbe94be57,0xbeaebde2,0xbeb78000,0xbeae3de2,
0xbeae3de2,0xbe573e94,0x3eb7,0x3e573e94,0x3de23eae,0x3e943e57,0x3eb78000,0x3e94be57,0x3eae3de2,0x3e94be57,0xbeb7,0xbe94be57,0x3de2beae,0xbe57be94,0xbeb78000,0xbe573e94,
0x3eb7,0x3eb7,0x3eb7,0x3eb7,0x3eb78000,0x3eb78000,0x3eb78000,0x3eb78000,0xbe57be94,0xbe94be57,0xbeaebde2,0xbeb70000,0xbe943e57,0xbe573e94,0xbde23eae,0x3eb7,
0x3eae3de2,0x3eaebde2,0x3e57be94,0xbeb7,0x3de2beae,0xbde2beae,0xbe94be57,0xbeb78000,0xbeae3de2,0xbde23eae,0x3e573e94,0x3eb70000,0x3de23eae,0x3eae3de2,0x3e94be57,0xbeb7,
0xbe57be94,0xbeae3de2,0x3eb7,0x3eae3de2,0xbe943e57,0x3de23eae,0x3eb78000,0x3de2beae,0x3eb7,0x3eb70000,0xbeb7,0xbeb70000,0x3eb78000,0xbeb7,0xbeb78000,0x3eb7,
0x3e57be94,0xbeaebde2,0x3eb7,0x3eaebde2,0xbe94be57,0xbde23eae,0x3eb78000,0xbde2beae,0xbeae3de2,0x3e943e57,0xbeb7,0xbe943e57,0x3de23eae,0x3e57be94,0xbeb78000,0x3e573e94,
0x3e57be94,0xbe57be94,0xbeae3de2,0x3eb7,0xbe94be57,0xbe943e57,0x3de23eae,0x3eb78000,0x3eb7,0x3eb70000,0xbeb7,0xbeb70000,0x3eb78000,0xbeb7,0xbeb78000,0x3eb7,
0xbe57be94,0xbe573e94,0x3eae3de2,0xbeb7,0xbe943e57,0x3e943e57,0x3de2beae,0xbeb78000,0x3eae3de2,0xbde2beae,0xbe573e94,0x3eb70000,0x3de2beae,0xbeae3de2,0x3e943e57,0xbeb7,
0x3eae3de2,0xbe57be94,0x3eb7,0x3e57be94,0x3de2beae,0xbe943e57,0x3eb78000,0xbe94be57,0xbe57be94,0x3de23eae,0xbeb7,0xbde23eae,0xbe943e57,0x3eaebde2,0xbeb78000,0x3eae3de2,
0x3eb7,0xbeb7,0x3eb7,0xbeb7,0x3eb78000,0xbeb78000,0x3eb78000,0xbeb78000,0x3e57be94,0xbde23eae,0xbeb7,0x3de23eae,0xbe94be57,0x3eae3de2,0xbeb78000,0x3eaebde2,
0xbeae3de2,0x3eae3de2,0xbe57be94,0x3eb7,0x3de23eae,0x3de2beae,0xbe943e57,0x3eb78000,0x3e57be94,0xbe943e57,0x3eaebde2,0xbeb70000,0xbe94be57,0x3e573e94,0xbde2beae,0x3eb7,
0x3eb7,0xbeb7,0x3eb7,0xbeb7,0x3eb78000,0xbeb78000,0x3eb78000,0xbeb78000,0xbe57be94,0x3e943e57,0xbeaebde2,0x3eb70000,0xbe943e57,0x3e57be94,0xbde23eae,0xbeb7,
0xbeae3de2,0x3e57be94,0x3eb7,0xbe57be94,0x3de23eae,0xbe94be57,0x3eb78000,0xbe943e57,0x3eae3de2,0xbe943e57,0xbeb7,0x3e943e57,0x3de2beae,0x3e573e94,0xbeb78000,0x3e57be94,
0xbe57be94,0x3eaebde2,0x3eb7,0xbeaebde2,0xbe943e57,0xbde2beae,0x3eb78000,0xbde23eae,0x3eb7,0xbeb70000,0xbeb7,0x3eb70000,0x3eb78000,0x3eb7,0xbeb78000,0xbeb7,
0x3eae3de2,0xbeae3de2,0x3e57be94,0x3eb7,0x3de2beae,0x3de23eae,0xbe94be57,0x3eb78000,0xbeae3de2,0x3de2beae,0x3e573e94,0xbeb70000,0x3de23eae,0xbeaebde2,0x3e94be57,0x3eb7,
0x3e57be94,0x3e573e94,0xbeae3de2,0xbeb7,0xbe94be57,0x3e94be57,0x3de23eae,0xbeb78000,0x3eb7,0xbeb70000,0xbeb7,0x3eb70000,0x3eb78000,0x3eb7,0xbeb78000,0xbeb7,
0x3e57be94,0x3eae3de2,0x3eb7,0xbeae3de2,0xbe94be57,0x3de2beae,0x3eb78000,0x3de23eae,0xbeae3de2,0xbe94be57,0xbeb7,0x3e94be57,0x3de23eae,0xbe573e94,0xbeb78000,0xbe57be94,
0x3eae3de2,0x3e573e94,0x3eb7,0xbe573e94,0x3de2beae,0x3e94be57,0x3eb78000,0x3e943e57,0xbe57be94,0xbde2beae,0xbeb7,0x3de2beae,0xbe943e57,0xbeae3de2,0xbeb78000,0xbeaebde2,
0xbe57be94,0x3e57be94,0x3eae3de2,0x3eb7,0xbe943e57,0xbe94be57,0x3de2beae,0x3eb78000,0x3eae3de2,0x3de23eae,0xbe573e94,0xbeb70000,0x3de2beae,0x3eaebde2,0x3e943e57,0x3eb7,
0xbeae3de2,0xbeaebde2,0xbe57be94,0xbeb7,0x3de23eae,0xbde23eae,0xbe943e57,0xbeb78000,0x3e57be94,0x3e94be57,0x3eaebde2,0x3eb70000,0xbe94be57,0xbe57be94,0xbde2beae,0xbeb7,
0x3eb7,0x3eb7,0x3eb7,0x3eb7,0x3eb78000,0x3eb78000,0x3eb78000,0x3eb78000,0xbeae3de2,0xbe943e57,0xbe573e94,0xbde23eae,0x3de23eae,0x3e573e94,0x3e943e57,0x3eae3de2,
0xbe57be94,0xbeaebde2,0xbeae3de2,0xbe573e94,0xbe943e57,0xbde23eae,0x3de23eae,0x3e943e57,0x3e57be94,0xbde2beae,0xbeaebde2,0xbe943e57,0xbe94be57,0xbeae3de2,0xbde23eae,0x3e573e94,
0,0,0,0,0,0,0,0,0,0,0,0,0,0,0,0,
0,0,0,0,0,0,0,0,0,0,0,0,0,0,0,0,
0x3eae3de2,0x3e57be94,0xbe57be94,0xbeae3de2,0x3de2beae,0xbe94be57,0xbe943e57,0x3de23eae,0x3eb7,0x3eb70000,0xbeb7,0xbeb70000,0x3eb78000,0xbeb7,0xbeb78000,0x3eb7,
0xbeae3de2,0x3e573e94,0x3e57be94,0xbeaebde2,0x3de23eae,0x3e94be57,0xbe94be57,0xbde23eae,0xbe57be94,0xbde23eae,0x3eaebde2,0xbe94be57,0xbe943e57,0x3eae3de2,0xbde2beae,0xbe573e94,
0,0,0,0,0,0,0,0,0,0,0,0,0,0,0,0,
0,0,0,0,0,0,0,0,0,0,0,0,0,0,0,0,
0x3e57be94,0xbeae3de2,0x3eae3de2,0xbe57be94,0xbe94be57,0x3de23eae,0x3de2beae,0xbe943e57,0x3eae3de2,0xbe94be57,0x3e573e94,0xbde2beae,0x3de2beae,0xbe573e94,0x3e94be57,0xbeae3de2,
0x3eb7,0xbeb7,0x3eb7,0xbeb7,0x3eb78000,0xbeb78000,0x3eb78000,0xbeb78000,0xbeae3de2,0x3e94be57,0xbe573e94,0x3de2beae,0x3de23eae,0xbe57be94,0x3e943e57,0xbeaebde2,
0,0,0,0,0,0,0,0,0,0,0,0,0,0,0,0,
0,0,0,0,0,0,0,0,0,0,0,0,0,0,0,0,
0xbe57be94,0x3eae3de2,0xbeae3de2,0x3e57be94,0xbe943e57,0x3de2beae,0x3de23eae,0xbe94be57,0x3e57be94,0x3de23eae,0xbeaebde2,0x3e94be57,0xbe94be57,0x3eaebde2,0xbde23eae,0xbe57be94,
0x3eae3de2,0xbe573e94,0xbe57be94,0x3eaebde2,0x3de2beae,0x3e943e57,0xbe943e57,0xbde2beae,0x3eb7,0xbeb70000,0xbeb7,0x3eb70000,0x3eb78000,0x3eb7,0xbeb78000,0xbeb7,
0,0,0,0,0,0,0,0,0,0,0,0,0,0,0,0,
0,0,0,0,0,0,0,0,0,0,0,0,0,0,0,0,
0xbeae3de2,0xbe57be94,0x3e57be94,0x3eae3de2,0x3de23eae,0xbe943e57,0xbe94be57,0x3de2beae,0xbe57be94,0x3de2beae,0x3eaebde2,0x3e943e57,0xbe943e57,0xbeaebde2,0xbde2beae,0x3e57be94,
0x3e57be94,0x3eaebde2,0x3eae3de2,0x3e573e94,0xbe94be57,0xbde2beae,0x3de2beae,0x3e94be57,0x3eae3de2,0x3e943e57,0x3e573e94,0x3de23eae,0x3de2beae,0x3e57be94,0x3e94be57,0x3eaebde2,
0,0,0,0,0,0,0,0,0,0,0,0,0,0,0,0,
0,0,0,0,0,0,0,0,0,0,0,0,0,0,0,0,
0,0,0,0,0,0,0,0,0,0,0,0,0,0,0,0,
0,0,0,0,0,0,0,0,0,0,0,0,0,0,0,0,
0x3eb7,0x3eb7,0x3eb7,0x3eb7,0x3eb78000,0x3eb78000,0x3eb78000,0x3eb78000,0xbeae3de2,0xbe943e57,0xbe573e94,0xbde23eae,0x3de23eae,0x3e573e94,0x3e943e57,0x3eae3de2,
0xbe57be94,0xbeaebde2,0xbeae3de2,0xbe573e94,0xbe943e57,0xbde23eae,0x3de23eae,0x3e943e57,0x3e57be94,0xbde2beae,0xbeaebde2,0xbe943e57,0xbe94be57,0xbeae3de2,0xbde23eae,0x3e573e94,
0,0,0,0,0,0,0,0,0,0,0,0,0,0,0,0,
0,0,0,0,0,0,0,0,0,0,0,0,0,0,0,0,
0x3eae3de2,0x3e57be94,0xbe57be94,0xbeae3de2,0x3de2beae,0xbe94be57,0xbe943e57,0x3de23eae,0x3eb7,0x3eb70000,0xbeb7,0xbeb70000,0x3eb78000,0xbeb7,0xbeb78000,0x3eb7,
0xbeae3de2,0x3e573e94,0x3e57be94,0xbeaebde2,0x3de23eae,0x3e94be57,0xbe94be57,0xbde23eae,0xbe57be94,0xbde23eae,0x3eaebde2,0xbe94be57,0xbe943e57,0x3eae3de2,0xbde2beae,0xbe573e94,
0,0,0,0,0,0,0,0,0,0,0,0,0,0,0,0,
0,0,0,0,0,0,0,0,0,0,0,0,0,0,0,0,
0x3e57be94,0xbeae3de2,0x3eae3de2,0xbe57be94,0xbe94be57,0x3de23eae,0x3de2beae,0xbe943e57,0x3eae3de2,0xbe94be57,0x3e573e94,0xbde2beae,0x3de2beae,0xbe573e94,0x3e94be57,0xbeae3de2,
0x3eb7,0xbeb7,0x3eb7,0xbeb7,0x3eb78000,0xbeb78000,0x3eb78000,0xbeb78000,0xbeae3de2,0x3e94be57,0xbe573e94,0x3de2beae,0x3de23eae,0xbe57be94,0x3e943e57,0xbeaebde2,
0,0,0,0,0,0,0,0,0,0,0,0,0,0,0,0,
0,0,0,0,0,0,0,0,0,0,0,0,0,0,0,0,
0xbe57be94,0x3eae3de2,0xbeae3de2,0x3e57be94,0xbe943e57,0x3de2beae,0x3de23eae,0xbe94be57,0x3e57be94,0x3de23eae,0xbeaebde2,0x3e94be57,0xbe94be57,0x3eaebde2,0xbde23eae,0xbe57be94,
0x3eae3de2,0xbe573e94,0xbe57be94,0x3eaebde2,0x3de2beae,0x3e943e57,0xbe943e57,0xbde2beae,0x3eb7,0xbeb70000,0xbeb7,0x3eb70000,0x3eb78000,0x3eb7,0xbeb78000,0xbeb7,
0,0,0,0,0,0,0,0,0,0,0,0,0,0,0,0,
0,0,0,0,0,0,0,0,0,0,0,0,0,0,0,0,
0xbeae3de2,0xbe57be94,0x3e57be94,0x3eae3de2,0x3de23eae,0xbe943e57,0xbe94be57,0x3de2beae,0xbe57be94,0x3de2beae,0x3eaebde2,0x3e943e57,0xbe943e57,0xbeaebde2,0xbde2beae,0x3e57be94,
0x3e57be94,0x3eaebde2,0x3eae3de2,0x3e573e94,0xbe94be57,0xbde2beae,0x3de2beae,0x3e94be57,0x3eae3de2,0x3e943e57,0x3e573e94,0x3de23eae,0x3de2beae,0x3e57be94,0x3e94be57,0x3eaebde2,
};
__device__ __align__(128) const uint32_t TAB_P3[3008] = {
0,0,0,0,0,0,0,0,0,0,0,0,0,0,0,0,
0x80003e83,0xbe79bda2,0x3e1abe54,0x3e1a3e54,0x3e830000,0xbda23e79,0xbe54be1a,0x3e54be1a,0x80003e83,0xbe54be1a,0x3e79bda2,0xbda23e79,0x3e830000,0xbe1a3e54,0xbda2be79,0x3e793da2,
0,0,0,0,0,0,0,0,0,0,0,0,0,0,0,0,
0xbe793da2,0x8000be83,0x3e793da2,0xbe1a3e54,0x3da23e79,0xbe830000,0x3da2be79,0x3e543e1a,0xbe1abe54,0x3e830000,0xbe1a3e54,0xbda2be79,0xbe543e1a,0xbe83,0x3e543e1a,0xbe793da2,
0x80003e83,0xbe1abe54,0x3e793da2,0xbe793da2,0x3e830000,0xbe543e1a,0x3da2be79,0x3da23e79,0x80003e83,0xbda2be79,0x3e1a3e54,0xbe54be1a,0x3e830000,0xbe793da2,0x3e54be1a,0xbe1a3e54,
0x80003e83,0x8000be83,0x80003e83,0x8000be83,0x3e830000,0xbe830000,0x3e830000,0xbe830000,0x80003e83,0x3da2be79,0xbe1a3e54,0x3e54be1a,0x3e830000,0xbe79bda2,0x3e543e1a,0xbe1abe54,
0x3e1abe54,0x80003e83,0xbe1abe54,0x3e793da2,0xbe54be1a,0x3e830000,0xbe543e1a,0x3da2be79,0x3e793da2,0xbe830000,0x3e79bda2,0xbe543e1a,0x3da2be79,0x3e83,0xbda2be79,0x3e1a3e54,
0x80003e83,0x8000be83,0x80003e83,0x8000be83,0x3e830000,0xbe830000,0x3e830000,0xbe830000,0xbe793da2,0x3e830000,0xbe79bda2,0x3e543e1a,0x3da23e79,0xbe83,0xbda23e79,0x3e1abe54,
0x80003e83,0x3e1abe54,0xbe793da2,0x3e793da2,0x3e830000,0xbe54be1a,0x3da23e79,0x3da2be79,0x80003e83,0x3e54be1a,0xbe79bda2,0x3da23e79,0x3e830000,0xbe1abe54,0xbda23e79,0x3e79bda2,
0x80003e83,0x3e79bda2,0xbe1abe54,0xbe1a3e54,0x3e830000,0xbda2be79,0xbe543e1a,0x3e543e1a,0x80003e83,0x3e830000,0x8000be83,0xbe830000,0x3e830000,0xbe83,0xbe830000,0x3e83,
0xbe1abe54,0x80003e83,0x3e1abe54,0xbe793da2,0xbe543e1a,0x3e830000,0xbe54be1a,0x3da23e79,0x3e1abe54,0xbe830000,0x3e1a3e54,0x3da2be79,0xbe54be1a,0x3e83,0x3e54be1a,0xbe79bda2,
0x3e793da2,0x8000be83,0xbe793da2,0x3e1a3e54,0x3da2be79,0xbe830000,0x3da23e79,0x3e54be1a,0x80003e83,0x3e830000,0x8000be83,0xbe830000,0x3e830000,0xbe83,0xbe830000,0x3e83,
0x80003e83,0x3e793da2,0x3e1abe54,0xbe1abe54,0x3e830000,0x3da2be79,0xbe54be1a,0xbe543e1a,0x80003e83,0x3e543e1a,0x3e79bda2,0x3da2be79,0x3e830000,0x3e1abe54,0xbda2be79,0xbe79bda2,
0x80003e83,0x3e1a3e54,0x3e793da2,0x3e79bda2,0x3e830000,0x3e54be1a,0x3da2be79,0xbda2be79,0x80003e83,0x3da23e79,0x3e1a3e54,0x3e543e1a,0x3e830000,0x3e79bda2,0x3e54be1a,0x3e1abe54,
0xbe793da2,0x80003e83,0x3e793da2,0x3e1abe54,0x3da23e79,0x3e830000,0x3da2be79,0xbe54be1a,0xbe1abe54,0xbe830000,0xbe1a3e54,0x3da23e79,0xbe543e1a,0x3e83,0x3e543e1a,0x3e79bda2,
0x3e1abe54,0x8000be83,0xbe1abe54,0xbe79bda2,0xbe54be1a,0xbe830000,0xbe543e1a,0xbda23e79,0x3e793da2,0x3e830000,0x3e79bda2,0x3e54be1a,0x3da2be79,0xbe83,0xbda2be79,0xbe1abe54,
0,0,0,0,0,0,0,0,0,0,0,0,0,0,0,0,
0,0,0,0,0,0,0,0,0,0,0,0,0,0,0,0,
0,0,0,0,0,0,0,0,0,0,0,0,0,0,0,0,
0xbe1abe54,0x3e79bda2,0x80003e83,0xbe79bda2,0xbe543e1a,0xbda2be79,0x3e830000,0xbda23e79,0x3e793da2,0xbe543e1a,0x8000be83,0x3e543e1a,0x3da2be79,0x3e1a3e54,0xbe830000,0x3e1abe54,
0,0,0,0,0,0,0,0,0,0,0,0,0,0,0,0,
0,0,0,0,0,0,0,0,0,0,0,0,0,0,0,0,
0xbe793da2,0x3e1abe54,0x80003e83,0xbe1abe54,0x3da23e79,0xbe54be1a,0x3e830000,0xbe543e1a,0x3e1abe54,0xbda23e79,0x8000be83,0x3da23e79,0xbe54be1a,0x3e793da2,0xbe830000,0x3e79bda2,
0x80003e83,0x8000be83,0x80003e83,0x8000be83,0x3e830000,0xbe830000,0x3e830000,0xbe830000,0xbe1abe54,0x3da23e79,0x8000be83,0xbda23e79,0xbe543e1a,0x3e79bda2,0xbe830000,0x3e793da2,
0,0,0,0,0,0,0,0,0,0,0,0,0,0,0,0,
0,0,0,0,0,0,0,0,0,0,0,0,0,0,0,0,
0x3e793da2,0xbe1abe54,0x80003e83,0x3e1abe54,0x3da2be79,0xbe543e1a,0x3e830000,0xbe54be1a,0xbe793da2,0x3e543e1a,0x8000be83,0xbe543e1a,0x3da23e79,0x3e1abe54,0xbe830000,0x3e1a3e54,
0x3e1abe54,0xbe79bda2,0x80003e83,0x3e79bda2,0xbe54be1a,0xbda23e79,0x3e830000,0xbda2be79,0x80003e83,0x3e830000,0x8000be83,0xbe830000,0x3e830000,0xbe83,0xbe830000,0x3e83,
0,0,0,0,0,0,0,0,0,0,0,0,0,0,0,0,
0,0,0,0,0,0,0,0,0,0,0,0,0,0,0,0,
0xbe1abe54,0xbe793da2,0x80003e83,0x3e793da2,0xbe543e1a,0x3da23e79,0x3e830000,0x3da2be79,0x3e793da2,0x3e54be1a,0x8000be83,0xbe54be1a,0x3da2be79,0xbe1abe54,0xbe830000,0xbe1a3e54,
0xbe793da2,0xbe1a3e54,0x80003e83,0x3e1a3e54,0x3da23e79,0x3e543e1a,0x3e830000,0x3e54be1a,0x3e1abe54,0x3da2be79,0x8000be83,0xbda2be79,0xbe54be1a,0xbe79bda2,0xbe830000,0xbe793da2,
0,0,0,0,0,0,0,0,0,0,0,0,0,0,0,0,
0x3e1abe54,0x3e1a3e54,0xbe793da2,0x8000be83,0xbe54be1a,0x3e54be1a,0x3da23e79,0xbe830000,0xbe793da2,0x3da2be79,0x3e1a3e54,0xbe830000,0x3da23e79,0xbe79bda2,0x3e54be1a,0x3e83,
0,0,0,0,0,0,0,0,0,0,0,0,0,0,0,0,
0x3e793da2,0xbe1a3e54,0xbe1abe54,0x3e79bda2,0x3da2be79,0x3e543e1a,0xbe543e1a,0xbda2be79,0x3e1abe54,0x3da23e79,0xbe79bda2,0x3e54be1a,0xbe54be1a,0x3e79bda2,0xbda23e79,0xbe1abe54,
0x3e793da2,0xbe793da2,0x3e1abe54,0x80003e83,0x3da2be79,0x3da23e79,0xbe54be1a,0x3e830000,0xbe1abe54,0x3e543e1a,0xbe79bda2,0x3e830000,0xbe543e1a,0x3e1abe54,0xbda23e79,0xbe83,
0x80003e83,0x8000be83,0x80003e83,0x8000be83,0x3e830000,0xbe830000,0x3e830000,0xbe830000,0x3e1abe54,0xbe543e1a,0x3e79bda2,0xbe830000,0xbe54be1a,0x3e1a3e54,0xbda2be79,0x3e83,
0xbe1abe54,0x3e793da2,0xbe793da2,0x3e1abe54,0xbe543e1a,0x3da2be79,0x3da23e79,0xbe54be1a,0xbe793da2,0x3e54be1a,0xbe1a3e54,0x3da2be79,0x3da23e79,0xbe1abe54,0x3e543e1a,0xbe79bda2,
0x80003e83,0x8000be83,0x80003e83,0x8000be83,0x3e830000,0xbe830000,0x3e830000,0xbe830000,0x3e793da2,0xbe54be1a,0x3e1a3e54,0xbda2be79,0x3da2be79,0xbe1a3e54,0x3e54be1a,0xbe793da2,
0xbe793da2,0x3e793da2,0xbe1abe54,0x80003e83,0x3da23e79,0x3da2be79,0xbe543e1a,0x3e830000,0x3e793da2,0xbda2be79,0xbe1a3e54,0x3e830000,0x3da2be79,0xbe793da2,0x3e543e1a,0xbe83,
0xbe1abe54,0xbe1a3e54,0x3e793da2,0x8000be83,0xbe543e1a,0x3e543e1a,0x3da2be79,0xbe830000,0x80003e83,0x3e830000,0x8000be83,0xbe830000,0x3e830000,0xbe83,0xbe830000,0x3e83,
0x3e1abe54,0xbe793da2,0x3e793da2,0xbe1abe54,0xbe54be1a,0x3da23e79,0x3da2be79,0xbe543e1a,0xbe1abe54,0xbda23e79,0x3e79bda2,0xbe54be1a,0xbe543e1a,0x3e793da2,0xbda2be79,0xbe1a3e54,
0xbe793da2,0x3e1a3e54,0x3e1abe54,0xbe79bda2,0x3da23e79,0x3e54be1a,0xbe54be1a,0xbda23e79,0x80003e83,0x3e830000,0x8000be83,0xbe830000,0x3e830000,0xbe83,0xbe830000,0x3e83,
0x3e1abe54,0xbe1abe54,0xbe793da2,0x80003e83,0xbe54be1a,0xbe543e1a,0x3da23e79,0x3e830000,0xbe793da2,0xbda23e79,0x3e1a3e54,0x3e830000,0x3da23e79,0x3e793da2,0x3e54be1a,0xbe83,
0x3e793da2,0x3e79bda2,0x3e1abe54,0x8000be83,0x3da2be79,0xbda2be79,0xbe54be1a,0xbe830000,0xbe1abe54,0xbe54be1a,0xbe79bda2,0xbe830000,0xbe543e1a,0xbe1a3e54,0xbda23e79,0x3e83,
0x3e793da2,0x3e1abe54,0xbe1abe54,0xbe793da2,0x3da2be79,0xbe54be1a,0xbe543e1a,0x3da23e79,0x3e1abe54,0xbda2be79,0xbe79bda2,0xbe543e1a,0xbe54be1a,0xbe793da2,0xbda23e79,0x3e1a3e54,
0xbe1abe54,0xbe79bda2,0xbe793da2,0xbe1a3e54,0xbe543e1a,0xbda23e79,0x3da23e79,0x3e543e1a,0xbe793da2,0xbe543e1a,0xbe1a3e54,0xbda23e79,0x3da23e79,0x3e1a3e54,0x3e543e1a,0x3e793da2,
0xbe163dda,0,0,0,0,0xbe163dda,0,0,0,0,0xbe163dda,0,0,0,0,0xbe163dda,
0xbe253da8,0,0,0,0,0xbe253da8,0,0,0,0,0xbe253da8,0,0,0,0,0xbe253da8,
0xbd65be30,0,0,0,0,0xbd65be30,0,0,0,0,0xbd65be30,0,0,0,0,0xbd65be30,
0x3ce8be37,0,0,0,0,0x3ce8be37,0,0,0,0,0x3ce8be37,0,0,0,0,0x3ce8be37,
0xbe303d65,0,0,0,0,0xbe303d65,0,0,0,0,0xbe303d65,0,0,0,0,0xbe303d65,
0xbe373ce8,0,0,0,0,0xbe373ce8,0,0,0,0,0xbe373ce8,0,0,0,0,0xbe373ce8,
0x3ddabe16,0,0,0,0,0x3ddabe16,0,0,0,0,0x3ddabe16,0,0,0,0,0x3ddabe16,
0x3e25bda8,0,0,0,0,0x3e25bda8,0,0,0,0,0x3e25bda8,0,0,0,0,0x3e25bda8,
0xbe390000,0,0,0,0,0xbe390000,0,0,0,0,0xbe390000,0,0,0,0,0xbe390000,
0xbe37bce8,0,0,0,0,0xbe37bce8,0,0,0,0,0xbe37bce8,0,0,0,0,0xbe37bce8,
0x3e390000,0,0,0,0,0x3e390000,0,0,0,0,0x3e390000,0,0,0,0,0x3e390000,
0x3e253da8,0,0,0,0,0x3e253da8,0,0,0,0,0x3e253da8,0,0,0,0,0x3e253da8,
0xbe30bd65,0,0,0,0,0xbe30bd65,0,0,0,0,0xbe30bd65,0,0,0,0,0xbe30bd65,
0xbe25bda8,0,0,0,0,0xbe25bda8,0,0,0,0,0xbe25bda8,0,0,0,0,0xbe25bda8,
0x3dda3e16,0,0,0,0,0x3dda3e16,0,0,0,0,0x3dda3e16,0,0,0,0,0x3dda3e16,
0x3ce83e37,0,0,0,0,0x3ce83e37,0,0,0,0,0x3ce83e37,0,0,0,0,0x3ce83e37,
0xbe16bdda,0,0,0,0,0xbe16bdda,0,0,0,0,0xbe16bdda,0,0,0,0,0xbe16bdda,
0xbe03be03,0,0,0,0,0xbe03be03,0,0,0,0,0xbe03be03,0,0,0,0,0xbe03be03,
0xbd653e30,0,0,0,0,0xbd653e30,0,0,0,0,0xbd653e30,0,0,0,0,0xbd653e30,
0xbe033e03,0,0,0,0,0xbe033e03,0,0,0,0,0xbe033e03,0,0,0,0,0xbe033e03,
0xbddabe16,0,0,0,0,0xbddabe16,0,0,0,0,0xbddabe16,0,0,0,0,0xbddabe16,
0xbda8be25,0,0,0,0,0xbda8be25,0,0,0,0,0xbda8be25,0,0,0,0,0xbda8be25,
0xbe303d65,0,0,0,0,0xbe303d65,0,0,0,0,0xbe303d65,0,0,0,0,0xbe303d65,
0xbe37bce8,0,0,0,0,0xbe37bce8,0,0,0,0,0xbe37bce8,0,0,0,0,0xbe37bce8,
0xbd65be30,0,0,0,0,0xbd65be30,0,0,0,0,0xbd65be30,0,0,0,0,0xbd65be30,
0xbce8be37,0,0,0,0,0xbce8be37,0,0,0,0,0xbce8be37,0,0,0,0,0xbce8be37,
0xbe16bdda,0,0,0,0,0xbe16bdda,0,0,0,0,0xbe16bdda,0,0,0,0,0xbe16bdda,
0xbda8be25,0,0,0,0,0xbda8be25,0,0,0,0,0xbda8be25,0,0,0,0,0xbda8be25,
0x3e390000,0,0,0,0,0x3e390000,0,0,0,0,0x3e390000,0,0,0,0,0x3e390000,
0x3e033e03,0,0,0,0,0x3e033e03,0,0,0,0,0x3e033e03,0,0,0,0,0x3e033e03,
0xbd653e30,0,0,0,0,0xbd653e30,0,0,0,0,0xbd653e30,0,0,0,0,0xbd653e30,
0xbe373ce8,0,0,0,0,0xbe373ce8,0,0,0,0,0xbe373ce8,0,0,0,0,0xbe373ce8,
0x80003e39,0,0,0,0,0x80003e39,0,0,0,0,0x80003e39,0,0,0,0,0x80003e39,
0xbe033e03,0,0,0,0,0xbe033e03,0,0,0,0,0xbe033e03,0,0,0,0,0xbe033e03,
0xbddabe16,0,0,0,0,0xbddabe16,0,0,0,0,0xbddabe16,0,0,0,0,0xbddabe16,
0x3da8be25,0,0,0,0,0x3da8be25,0,0,0,0,0x3da8be25,0,0,0,0,0x3da8be25,
0xbe390000,0,0,0,0,0xbe390000,0,0,0,0,0xbe390000,0,0,0,0,0xbe390000,
0xbe03be03,0,0,0,0,0xbe03be03,0,0,0,0,0xbe03be03,0,0,0,0,0xbe03be03,
0x3e390000,0,0,0,0,0x3e390000,0,0,0,0,0x3e390000,0,0,0,0,0x3e390000,
0x3da83e25,0,0,0,0,0x3da83e25,0,0,0,0,0x3da83e25,0,0,0,0,0x3da83e25,
0x8000be39,0,0,0,0,0x8000be39,0,0,0,0,0x8000be39,0,0,0,0,0x8000be39,
0x3e03be03,0,0,0,0,0x3e03be03,0,0,0,0,0x3e03be03,0,0,0,0,0x3e03be03,
0xbdda3e16,0,0,0,0,0xbdda3e16,0,0,0,0,0xbdda3e16,0,0,0,0,0xbdda3e16,
0xbe37bce8,0,0,0,0,0xbe37bce8,0,0,0,0,0xbe37bce8,0,0,0,0,0xbe37bce8,
0x3e390000,0,0,0,0,0x3e390000,0,0,0,0,0x3e390000,0,0,0,0,0x3e390000,
0x3e033e03,0,0,0,0,0x3e033e03,0,0,0,0,0x3e033e03,0,0,0,0,0x3e033e03,
0xbd65be30,0,0,0,0,0xbd65be30,0,0,0,0,0xbd65be30,0,0,0,0,0xbd65be30,
0x3e03be03,0,0,0,0,0x3e03be03,0,0,0,0,0x3e03be03,0,0,0,0,0x3e03be03,
0x80003e39,0,0,0,0,0x80003e39,0,0,0,0,0x80003e39,0,0,0,0,0x80003e39,
0xbe033e03,0,0,0,0,0xbe033e03,0,0,0,0,0xbe033e03,0,0,0,0,0xbe033e03,
0x3e303d65,0,0,0,0,0x3e303d65,0,0,0,0,0x3e303d65,0,0,0,0,0x3e303d65,
0x3ce83e37,0,0,0,0,0x3ce83e37,0,0,0,0,0x3ce83e37,0,0,0,0,0x3ce83e37,
0xbe390000,0,0,0,0,0xbe390000,0,0,0,0,0xbe390000,0,0,0,0,0xbe390000,
0xbe03be03,0,0,0,0,0xbe03be03,0,0,0,0,0xbe03be03,0,0,0,0,0xbe03be03,
0xbe163dda,0,0,0,0,0xbe163dda,0,0,0,0,0xbe163dda,0,0,0,0,0xbe163dda,
0xbe25bda8,0,0,0,0,0xbe25bda8,0,0,0,0,0xbe25bda8,0,0,0,0,0xbe25bda8,
0xbe16bdda,0,0,0,0,0xbe16bdda,0,0,0,0,0xbe16bdda,0,0,0,0,0xbe16bdda,
0x3da8be25,0,0,0,0,0x3da8be25,0,0,0,0,0x3da8be25,0,0,0,0,0x3da8be25,
0x3e16bdda,0,0,0,0,0x3e16bdda,0,0,0,0,0x3e16bdda,0,0,0,0,0x3e16bdda,
0x3da83e25,0,0,0,0,0x3da83e25,0,0,0,0,0x3da83e25,0,0,0,0,0x3da83e25,
0x3e303d65,0,0,0,0,0x3e303d65,0,0,0,0,0x3e303d65,0,0,0,0,0x3e303d65,
0xbce83e37,0,0,0,0,0xbce83e37,0,0,0,0,0xbce83e37,0,0,0,0,0xbce83e37,
0xbe303d65,0,0,0,0,0xbe303d65,0,0,0,0,0xbe303d65,0,0,0,0,0xbe303d65,
0xbce8be37,0,0,0,0,0xbce8be37,0,0,0,0,0xbce8be37,0,0,0,0,0xbce8be37,
0xbe390000,0,0,0,0,0xbe390000,0,0,0,0,0xbe390000,0,0,0,0,0xbe390000,
0xbce8be37,0,0,0,0,0xbce8be37,0,0,0,0,0xbce8be37,0,0,0,0,0xbce8be37,
0x3e390000,0,0,0,0,0x3e390000,0,0,0,0,0x3e390000,0,0,0,0,0x3e390000,
0xbce83e37,0,0,0,0,0xbce83e37,0,0,0,0,0xbce83e37,0,0,0,0,0xbce83e37,
0x3e30bd65,0,0,0,0,0x3e30bd65,0,0,0,0,0x3e30bd65,0,0,0,0,0x3e30bd65,
0x3da83e25,0,0,0,0,0x3da83e25,0,0,0,0,0x3da83e25,0,0,0,0,0x3da83e25,
0xbe30bd65,0,0,0,0,0xbe30bd65,0,0,0,0,0xbe30bd65,0,0,0,0,0xbe30bd65,
0x3da8be25,0,0,0,0,0x3da8be25,0,0,0,0,0x3da8be25,0,0,0,0,0x3da8be25,
0xbe163dda,0,0,0,0,0xbe163dda,0,0,0,0,0xbe163dda,0,0,0,0,0xbe163dda,
0xbe03be03,0,0,0,0,0xbe03be03,0,0,0,0,0xbe03be03,0,0,0,0,0xbe03be03,
0x3e163dda,0,0,0,0,0x3e163dda,0,0,0,0,0x3e163dda,0,0,0,0,0x3e163dda,
0xbe033e03,0,0,0,0,0xbe033e03,0,0,0,0,0xbe033e03,0,0,0,0,0xbe033e03,
0x3ddabe16,0,0,0,0,0x3ddabe16,0,0,0,0,0x3ddabe16,0,0,0,0,0x3ddabe16,
0x3e253da8,0,0,0,0,0x3e253da8,0,0,0,0,0x3e253da8,0,0,0,0,0x3e253da8,
0xbddabe16,0,0,0,0,0xbddabe16,0,0,0,0,0xbddabe16,0,0,0,0,0xbddabe16,
0x3e25bda8,0,0,0,0,0x3e25bda8,0,0,0,0,0x3e25bda8,0,0,0,0,0x3e25bda8,
0xbd653e30,0,0,0,0,0xbd653e30,0,0,0,0,0xbd653e30,0,0,0,0,0xbd653e30,
0xbe37bce8,0,0,0,0,0xbe37bce8,0,0,0,0,0xbe37bce8,0,0,0,0,0xbe37bce8,
0x3d653e30,0,0,0,0,0x3d653e30,0,0,0,0,0x3d653e30,0,0,0,0,0x3d653e30,
0xbe373ce8,0,0,0,0,0xbe373ce8,0,0,0,0,0xbe373ce8,0,0,0,0,0xbe373ce8,
0x3d653e30,0,0,0,0,0x3d653e30,0,0,0,0,0x3d653e30,0,0,0,0,0x3d653e30,
0xbe37bce8,0,0,0,0,0xbe37bce8,0,0,0,0,0xbe37bce8,0,0,0,0,0xbe37bce8,
0xbe390000,0,0,0,0,0xbe390000,0,0,0,0,0xbe390000,0,0,0,0,0xbe390000,
0x3e03be03,0,0,0,0,0x3e03be03,0,0,0,0,0x3e03be03,0,0,0,0,0x3e03be03,
0x3ddabe16,0,0,0,0,0x3ddabe16,0,0,0,0,0x3ddabe16,0,0,0,0,0x3ddabe16,
0x3da83e25,0,0,0,0,0x3da83e25,0,0,0,0,0x3da83e25,0,0,0,0,0x3da83e25,
0x80003e39,0,0,0,0,0x80003e39,0,0,0,0,0x80003e39,0,0,0,0,0x80003e39,
0xbe03be03,0,0,0,0,0xbe03be03,0,0,0,0,0xbe03be03,0,0,0,0,0xbe03be03,
0xbe390000,0,0,0,0,0xbe390000,0,0,0,0,0xbe390000,0,0,0,0,0xbe390000,
0x3da8be25,0,0,0,0,0x3da8be25,0,0,0,0,0x3da8be25,0,0,0,0,0x3da8be25,
0x3e390000,0,0,0,0,0x3e390000,0,0,0,0,0x3e390000,0,0,0,0,0x3e390000,
0xbe033e03,0,0,0,0,0xbe033e03,0,0,0,0,0xbe033e03,0,0,0,0,0xbe033e03,
0x3dda3e16,0,0,0,0,0x3dda3e16,0,0,0,0,0x3dda3e16,0,0,0,0,0x3dda3e16,
0xbe373ce8,0,0,0,0,0xbe373ce8,0,0,0,0,0xbe373ce8,0,0,0,0,0xbe373ce8,
0x8000be39,0,0,0,0,0x8000be39,0,0,0,0,0x8000be39,0,0,0,0,0x8000be39,
0x3e033e03,0,0,0,0,0x3e033e03,0,0,0,0,0x3e033e03,0,0,0,0,0x3e033e03,
0x3d65be30,0,0,0,0,0x3d65be30,0,0,0,0,0x3d65be30,0,0,0,0,0x3d65be30,
0x3e033e03,0,0,0,0,0x3e033e03,0,0,0,0,0x3e033e03,0,0,0,0,0x3e033e03,
0xbe390000,0,0,0,0,0xbe390000,0,0,0,0,0xbe390000,0,0,0,0,0xbe390000,
0x3e03be03,0,0,0,0,0x3e03be03,0,0,0,0,0x3e03be03,0,0,0,0,0x3e03be03,
0xbe303d65,0,0,0,0,0xbe303d65,0,0,0,0,0xbe303d65,0,0,0,0,0xbe303d65,
0x3ce8be37,0,0,0,0,0x3ce8be37,0,0,0,0,0x3ce8be37,0,0,0,0,0x3ce8be37,
0x80003e39,0,0,0,0,0x80003e39,0,0,0,0,0x80003e39,0,0,0,0,0x80003e39,
0xbe03be03,0,0,0,0,0xbe03be03,0,0,0,0,0xbe03be03,0,0,0,0,0xbe03be03,
0x3e163dda,0,0,0,0,0x3e163dda,0,0,0,0,0x3e163dda,0,0,0,0,0x3e163dda,
0xbe253da8,0,0,0,0,0xbe253da8,0,0,0,0,0xbe253da8,0,0,0,0,0xbe253da8,
0x3e390000,0,0,0,0,0x3e390000,0,0,0,0,0x3e390000,0,0,0,0,0x3e390000,
0xbe033e03,0,0,0,0,0xbe033e03,0,0,0,0,0xbe033e03,0,0,0,0,0xbe033e03,
0x3d65be30,0,0,0,0,0x3d65be30,0,0,0,0,0x3d65be30,0,0,0,0,0x3d65be30,
0x3ce83e37,0,0,0,0,0x3ce83e37,0,0,0,0,0x3ce83e37,0,0,0,0,0x3ce83e37,
0x3e163dda,0,0,0,0,0x3e163dda,0,0,0,0,0x3e163dda,0,0,0,0,0x3e163dda,
0xbe25bda8,0,0,0,0,0xbe25bda8,0,0,0,0,0xbe25bda8,0,0,0,0,0xbe25bda8,
0xbddabe16,0,0,0,0,0xbddabe16,0,0,0,0,0xbddabe16,0,0,0,0,0xbddabe16,
0x3e253da8,0,0,0,0,0x3e253da8,0,0,0,0,0x3e253da8,0,0,0,0,0x3e253da8,
0x3e303d65,0,0,0,0,0x3e303d65,0,0,0,0,0x3e303d65,0,0,0,0,0x3e303d65,
0xbe37bce8,0,0,0,0,0xbe37bce8,0,0,0,0,0xbe37bce8,0,0,0,0,0xbe37bce8,
0xbe390000,0,0,0,0,0xbe390000,0,0,0,0,0xbe390000,0,0,0,0,0xbe390000,
0x3e25bda8,0,0,0,0,0x3e25bda8,0,0,0,0,0x3e25bda8,0,0,0,0,0x3e25bda8,
0x3e390000,0,0,0,0,0x3e390000,0,0,0,0,0x3e390000,0,0,0,0,0x3e390000,
0xbe373ce8,0,0,0,0,0xbe373ce8,0,0,0,0,0xbe373ce8,0,0,0,0,0xbe373ce8,
0xbdda3e16,0,0,0,0,0xbdda3e16,0,0,0,0,0xbdda3e16,0,0,0,0,0xbdda3e16,
0x3ce8be37,0,0,0,0,0x3ce8be37,0,0,0,0,0x3ce8be37,0,0,0,0,0x3ce8be37,
0x3e30bd65,0,0,0,0,0x3e30bd65,0,0,0,0,0x3e30bd65,0,0,0,0,0x3e30bd65,
0xbe253da8,0,0,0,0,0xbe253da8,0,0,0,0,0xbe253da8,0,0,0,0,0xbe253da8,
0x3d653e30,0,0,0,0,0x3d653e30,0,0,0,0,0x3d653e30,0,0,0,0,0x3d653e30,
0xbe03be03,0,0,0,0,0xbe03be03,0,0,0,0,0xbe03be03,0,0,0,0,0xbe03be03,
0x3e16bdda,0,0,0,0,0x3e16bdda,0,0,0,0,0x3e16bdda,0,0,0,0,0x3e16bdda,
0xbe033e03,0,0,0,0,0xbe033e03,0,0,0,0,0xbe033e03,0,0,0,0,0xbe033e03,
0x3e303d65,0,0,0,0,0x3e303d65,0,0,0,0,0x3e303d65,0,0,0,0,0x3e303d65,
0xbe373ce8,0,0,0,0,0xbe373ce8,0,0,0,0,0xbe373ce8,0,0,0,0,0xbe373ce8,
0x3ddabe16,0,0,0,0,0x3ddabe16,0,0,0,0,0x3ddabe16,0,0,0,0,0x3ddabe16,
0xbda83e25,0,0,0,0,0xbda83e25,0,0,0,0,0xbda83e25,0,0,0,0,0xbda83e25,
0x3e16bdda,0,0,0,0,0x3e16bdda,0,0,0,0,0x3e16bdda,0,0,0,0,0x3e16bdda,
0xbda83e25,0,0,0,0,0xbda83e25,0,0,0,0,0xbda83e25,0,0,0,0,0xbda83e25,
0x3d65be30,0,0,0,0,0x3d65be30,0,0,0,0,0x3d65be30,0,0,0,0,0x3d65be30,
0xbce83e37,0,0,0,0,0xbce83e37,0,0,0,0,0xbce83e37,0,0,0,0,0xbce83e37,
};
constexpr unsigned long long COS_PK0 = 0x3f903f9a3fa03fa2ull;
constexpr unsigned long long COS_PK1 = 0x3f133f3e3f653f83ull;
constexpr unsigned long long COS_PK2 = 0x3e4b3ec8ull;

__device__ __forceinline__ void wgmma_ss_n80_z(float (&d)[40], uint64_t da, uint64_t db) {
  asm volatile("{\n.reg .pred p;\nsetp.ne.b32 p, 0, 0;\nwgmma.mma_async.sync.aligned.m64n80k16.f32.bf16.bf16 {%0,%1,%2,%3,%4,%5,%6,%7,%8,%9,%10,%11,%12,%13,%14,%15,%16,%17,%18,%19,%20,%21,%22,%23,%24,%25,%26,%27,%28,%29,%30,%31,%32,%33,%34,%35,%36,%37,%38,%39}, %40, %41, p, 1, 1, 1, 0;\n}\n"
    : "+f"(d[0]), "+f"(d[1]), "+f"(d[2]), "+f"(d[3]), "+f"(d[4]), "+f"(d[5]), "+f"(d[6]), "+f"(d[7]), "+f"(d[8]), "+f"(d[9]), "+f"(d[10]), "+f"(d[11]), "+f"(d[12]), "+f"(d[13]), "+f"(d[14]), "+f"(d[15]), "+f"(d[16]), "+f"(d[17]), "+f"(d[18]), "+f"(d[19]), "+f"(d[20]), "+f"(d[21]), "+f"(d[22]), "+f"(d[23]), "+f"(d[24]), "+f"(d[25]), "+f"(d[26]), "+f"(d[27]), "+f"(d[28]), "+f"(d[29]), "+f"(d[30]), "+f"(d[31]), "+f"(d[32]), "+f"(d[33]), "+f"(d[34]), "+f"(d[35]), "+f"(d[36]), "+f"(d[37]), "+f"(d[38]), "+f"(d[39])
    : "l"(da), "l"(db));
}
__device__ __forceinline__ void wgmma_ss_n80_a(float (&d)[40], uint64_t da, uint64_t db) {
  asm volatile("{\n.reg .pred p;\nsetp.ne.b32 p, 1, 0;\nwgmma.mma_async.sync.aligned.m64n80k16.f32.bf16.bf16 {%0,%1,%2,%3,%4,%5,%6,%7,%8,%9,%10,%11,%12,%13,%14,%15,%16,%17,%18,%19,%20,%21,%22,%23,%24,%25,%26,%27,%28,%29,%30,%31,%32,%33,%34,%35,%36,%37,%38,%39}, %40, %41, p, 1, 1, 1, 0;\n}\n"
    : "+f"(d[0]), "+f"(d[1]), "+f"(d[2]), "+f"(d[3]), "+f"(d[4]), "+f"(d[5]), "+f"(d[6]), "+f"(d[7]), "+f"(d[8]), "+f"(d[9]), "+f"(d[10]), "+f"(d[11]), "+f"(d[12]), "+f"(d[13]), "+f"(d[14]), "+f"(d[15]), "+f"(d[16]), "+f"(d[17]), "+f"(d[18]), "+f"(d[19]), "+f"(d[20]), "+f"(d[21]), "+f"(d[22]), "+f"(d[23]), "+f"(d[24]), "+f"(d[25]), "+f"(d[26]), "+f"(d[27]), "+f"(d[28]), "+f"(d[29]), "+f"(d[30]), "+f"(d[31]), "+f"(d[32]), "+f"(d[33]), "+f"(d[34]), "+f"(d[35]), "+f"(d[36]), "+f"(d[37]), "+f"(d[38]), "+f"(d[39])
    : "l"(da), "l"(db));
}

__device__ __forceinline__ void wgmma_rs_n40_z(float (&d)[20], uint32_t a0, uint32_t a1, uint32_t a2, uint32_t a3, uint64_t db) {
  asm volatile("{\n.reg .pred p;\nsetp.ne.b32 p, 0, 0;\nwgmma.mma_async.sync.aligned.m64n40k16.f32.bf16.bf16 {%0,%1,%2,%3,%4,%5,%6,%7,%8,%9,%10,%11,%12,%13,%14,%15,%16,%17,%18,%19}, {%20,%21,%22,%23}, %24, p, 1, 1, 0;\n}\n"
    : "+f"(d[0]), "+f"(d[1]), "+f"(d[2]), "+f"(d[3]), "+f"(d[4]), "+f"(d[5]), "+f"(d[6]), "+f"(d[7]), "+f"(d[8]), "+f"(d[9]), "+f"(d[10]), "+f"(d[11]), "+f"(d[12]), "+f"(d[13]), "+f"(d[14]), "+f"(d[15]), "+f"(d[16]), "+f"(d[17]), "+f"(d[18]), "+f"(d[19])
    : "r"(a0), "r"(a1), "r"(a2), "r"(a3), "l"(db));
}
__device__ __forceinline__ void wgmma_rs_n40_a(float (&d)[20], uint32_t a0, uint32_t a1, uint32_t a2, uint32_t a3, uint64_t db) {
  asm volatile("{\n.reg .pred p;\nsetp.ne.b32 p, 1, 0;\nwgmma.mma_async.sync.aligned.m64n40k16.f32.bf16.bf16 {%0,%1,%2,%3,%4,%5,%6,%7,%8,%9,%10,%11,%12,%13,%14,%15,%16,%17,%18,%19}, {%20,%21,%22,%23}, %24, p, 1, 1, 0;\n}\n"
    : "+f"(d[0]), "+f"(d[1]), "+f"(d[2]), "+f"(d[3]), "+f"(d[4]), "+f"(d[5]), "+f"(d[6]), "+f"(d[7]), "+f"(d[8]), "+f"(d[9]), "+f"(d[10]), "+f"(d[11]), "+f"(d[12]), "+f"(d[13]), "+f"(d[14]), "+f"(d[15]), "+f"(d[16]), "+f"(d[17]), "+f"(d[18]), "+f"(d[19])
    : "r"(a0), "r"(a1), "r"(a2), "r"(a3), "l"(db));
}

__device__ __forceinline__ void wgmma_rs_n128_z(float (&d)[64], uint32_t a0, uint32_t a1, uint32_t a2, uint32_t a3, uint64_t db) {
  asm volatile("{\n.reg .pred p;\nsetp.ne.b32 p, 0, 0;\nwgmma.mma_async.sync.aligned.m64n128k16.f32.bf16.bf16 {%0,%1,%2,%3,%4,%5,%6,%7,%8,%9,%10,%11,%12,%13,%14,%15,%16,%17,%18,%19,%20,%21,%22,%23,%24,%25,%26,%27,%28,%29,%30,%31,%32,%33,%34,%35,%36,%37,%38,%39,%40,%41,%42,%43,%44,%45,%46,%47,%48,%49,%50,%51,%52,%53,%54,%55,%56,%57,%58,%59,%60,%61,%62,%63}, {%64,%65,%66,%67}, %68, p, 1, 1, 1;\n}\n"
    : "+f"(d[0]), "+f"(d[1]), "+f"(d[2]), "+f"(d[3]), "+f"(d[4]), "+f"(d[5]), "+f"(d[6]), "+f"(d[7]), "+f"(d[8]), "+f"(d[9]), "+f"(d[10]), "+f"(d[11]), "+f"(d[12]), "+f"(d[13]), "+f"(d[14]), "+f"(d[15]), "+f"(d[16]), "+f"(d[17]), "+f"(d[18]), "+f"(d[19]), "+f"(d[20]), "+f"(d[21]), "+f"(d[22]), "+f"(d[23]), "+f"(d[24]), "+f"(d[25]), "+f"(d[26]), "+f"(d[27]), "+f"(d[28]), "+f"(d[29]), "+f"(d[30]), "+f"(d[31]), "+f"(d[32]), "+f"(d[33]), "+f"(d[34]), "+f"(d[35]), "+f"(d[36]), "+f"(d[37]), "+f"(d[38]), "+f"(d[39]), "+f"(d[40]), "+f"(d[41]), "+f"(d[42]), "+f"(d[43]), "+f"(d[44]), "+f"(d[45]), "+f"(d[46]), "+f"(d[47]), "+f"(d[48]), "+f"(d[49]), "+f"(d[50]), "+f"(d[51]), "+f"(d[52]), "+f"(d[53]), "+f"(d[54]), "+f"(d[55]), "+f"(d[56]), "+f"(d[57]), "+f"(d[58]), "+f"(d[59]), "+f"(d[60]), "+f"(d[61]), "+f"(d[62]), "+f"(d[63])
    : "r"(a0), "r"(a1), "r"(a2), "r"(a3), "l"(db));
}
__device__ __forceinline__ void wgmma_rs_n128_a(float (&d)[64], uint32_t a0, uint32_t a1, uint32_t a2, uint32_t a3, uint64_t db) {
  asm volatile("{\n.reg .pred p;\nsetp.ne.b32 p, 1, 0;\nwgmma.mma_async.sync.aligned.m64n128k16.f32.bf16.bf16 {%0,%1,%2,%3,%4,%5,%6,%7,%8,%9,%10,%11,%12,%13,%14,%15,%16,%17,%18,%19,%20,%21,%22,%23,%24,%25,%26,%27,%28,%29,%30,%31,%32,%33,%34,%35,%36,%37,%38,%39,%40,%41,%42,%43,%44,%45,%46,%47,%48,%49,%50,%51,%52,%53,%54,%55,%56,%57,%58,%59,%60,%61,%62,%63}, {%64,%65,%66,%67}, %68, p, 1, 1, 1;\n}\n"
    : "+f"(d[0]), "+f"(d[1]), "+f"(d[2]), "+f"(d[3]), "+f"(d[4]), "+f"(d[5]), "+f"(d[6]), "+f"(d[7]), "+f"(d[8]), "+f"(d[9]), "+f"(d[10]), "+f"(d[11]), "+f"(d[12]), "+f"(d[13]), "+f"(d[14]), "+f"(d[15]), "+f"(d[16]), "+f"(d[17]), "+f"(d[18]), "+f"(d[19]), "+f"(d[20]), "+f"(d[21]), "+f"(d[22]), "+f"(d[23]), "+f"(d[24]), "+f"(d[25]), "+f"(d[26]), "+f"(d[27]), "+f"(d[28]), "+f"(d[29]), "+f"(d[30]), "+f"(d[31]), "+f"(d[32]), "+f"(d[33]), "+f"(d[34]), "+f"(d[35]), "+f"(d[36]), "+f"(d[37]), "+f"(d[38]), "+f"(d[39]), "+f"(d[40]), "+f"(d[41]), "+f"(d[42]), "+f"(d[43]), "+f"(d[44]), "+f"(d[45]), "+f"(d[46]), "+f"(d[47]), "+f"(d[48]), "+f"(d[49]), "+f"(d[50]), "+f"(d[51]), "+f"(d[52]), "+f"(d[53]), "+f"(d[54]), "+f"(d[55]), "+f"(d[56]), "+f"(d[57]), "+f"(d[58]), "+f"(d[59]), "+f"(d[60]), "+f"(d[61]), "+f"(d[62]), "+f"(d[63])
    : "r"(a0), "r"(a1), "r"(a2), "r"(a3), "l"(db));
}

__device__ __forceinline__ void wgmma_rs_n32_z(float (&d)[16], uint32_t a0, uint32_t a1, uint32_t a2, uint32_t a3, uint64_t db) {
  asm volatile("{\n.reg .pred p;\nsetp.ne.b32 p, 0, 0;\nwgmma.mma_async.sync.aligned.m64n32k16.f32.bf16.bf16 {%0,%1,%2,%3,%4,%5,%6,%7,%8,%9,%10,%11,%12,%13,%14,%15}, {%16,%17,%18,%19}, %20, p, 1, 1, 0;\n}\n"
    : "+f"(d[0]), "+f"(d[1]), "+f"(d[2]), "+f"(d[3]), "+f"(d[4]), "+f"(d[5]), "+f"(d[6]), "+f"(d[7]), "+f"(d[8]), "+f"(d[9]), "+f"(d[10]), "+f"(d[11]), "+f"(d[12]), "+f"(d[13]), "+f"(d[14]), "+f"(d[15])
    : "r"(a0), "r"(a1), "r"(a2), "r"(a3), "l"(db));
}
__device__ __forceinline__ void wgmma_rs_n32_a(float (&d)[16], uint32_t a0, uint32_t a1, uint32_t a2, uint32_t a3, uint64_t db) {
  asm volatile("{\n.reg .pred p;\nsetp.ne.b32 p, 1, 0;\nwgmma.mma_async.sync.aligned.m64n32k16.f32.bf16.bf16 {%0,%1,%2,%3,%4,%5,%6,%7,%8,%9,%10,%11,%12,%13,%14,%15}, {%16,%17,%18,%19}, %20, p, 1, 1, 0;\n}\n"
    : "+f"(d[0]), "+f"(d[1]), "+f"(d[2]), "+f"(d[3]), "+f"(d[4]), "+f"(d[5]), "+f"(d[6]), "+f"(d[7]), "+f"(d[8]), "+f"(d[9]), "+f"(d[10]), "+f"(d[11]), "+f"(d[12]), "+f"(d[13]), "+f"(d[14]), "+f"(d[15])
    : "r"(a0), "r"(a1), "r"(a2), "r"(a3), "l"(db));
}

__device__ __forceinline__ void wgmma_ss_n32_z(float (&d)[16], uint64_t da, uint64_t db) {
  asm volatile("{\n.reg .pred p;\nsetp.ne.b32 p, 0, 0;\nwgmma.mma_async.sync.aligned.m64n32k16.f32.bf16.bf16 {%0,%1,%2,%3,%4,%5,%6,%7,%8,%9,%10,%11,%12,%13,%14,%15}, %16, %17, p, 1, 1, 1, 0;\n}\n"
    : "+f"(d[0]), "+f"(d[1]), "+f"(d[2]), "+f"(d[3]), "+f"(d[4]), "+f"(d[5]), "+f"(d[6]), "+f"(d[7]), "+f"(d[8]), "+f"(d[9]), "+f"(d[10]), "+f"(d[11]), "+f"(d[12]), "+f"(d[13]), "+f"(d[14]), "+f"(d[15])
    : "l"(da), "l"(db));
}
__device__ __forceinline__ void wgmma_ss_n32_a(float (&d)[16], uint64_t da, uint64_t db) {
  asm volatile("{\n.reg .pred p;\nsetp.ne.b32 p, 1, 0;\nwgmma.mma_async.sync.aligned.m64n32k16.f32.bf16.bf16 {%0,%1,%2,%3,%4,%5,%6,%7,%8,%9,%10,%11,%12,%13,%14,%15}, %16, %17, p, 1, 1, 1, 0;\n}\n"
    : "+f"(d[0]), "+f"(d[1]), "+f"(d[2]), "+f"(d[3]), "+f"(d[4]), "+f"(d[5]), "+f"(d[6]), "+f"(d[7]), "+f"(d[8]), "+f"(d[9]), "+f"(d[10]), "+f"(d[11]), "+f"(d[12]), "+f"(d[13]), "+f"(d[14]), "+f"(d[15])
    : "l"(da), "l"(db));
}

__device__ __forceinline__ void wgmma_ss_n40_z(float (&d)[20], uint64_t da, uint64_t db) {
  asm volatile("{\n.reg .pred p;\nsetp.ne.b32 p, 0, 0;\nwgmma.mma_async.sync.aligned.m64n40k16.f32.bf16.bf16 {%0,%1,%2,%3,%4,%5,%6,%7,%8,%9,%10,%11,%12,%13,%14,%15,%16,%17,%18,%19}, %20, %21, p, 1, 1, 1, 0;\n}\n"
    : "+f"(d[0]), "+f"(d[1]), "+f"(d[2]), "+f"(d[3]), "+f"(d[4]), "+f"(d[5]), "+f"(d[6]), "+f"(d[7]), "+f"(d[8]), "+f"(d[9]), "+f"(d[10]), "+f"(d[11]), "+f"(d[12]), "+f"(d[13]), "+f"(d[14]), "+f"(d[15]), "+f"(d[16]), "+f"(d[17]), "+f"(d[18]), "+f"(d[19])
    : "l"(da), "l"(db));
}
__device__ __forceinline__ void wgmma_ss_n40_a(float (&d)[20], uint64_t da, uint64_t db) {
  asm volatile("{\n.reg .pred p;\nsetp.ne.b32 p, 1, 0;\nwgmma.mma_async.sync.aligned.m64n40k16.f32.bf16.bf16 {%0,%1,%2,%3,%4,%5,%6,%7,%8,%9,%10,%11,%12,%13,%14,%15,%16,%17,%18,%19}, %20, %21, p, 1, 1, 1, 0;\n}\n"
    : "+f"(d[0]), "+f"(d[1]), "+f"(d[2]), "+f"(d[3]), "+f"(d[4]), "+f"(d[5]), "+f"(d[6]), "+f"(d[7]), "+f"(d[8]), "+f"(d[9]), "+f"(d[10]), "+f"(d[11]), "+f"(d[12]), "+f"(d[13]), "+f"(d[14]), "+f"(d[15]), "+f"(d[16]), "+f"(d[17]), "+f"(d[18]), "+f"(d[19])
    : "l"(da), "l"(db));
}

__device__ __forceinline__ void wgmma_rs_n56_z(float (&d)[28], uint32_t a0, uint32_t a1, uint32_t a2, uint32_t a3, uint64_t db) {
  asm volatile("{\n.reg .pred p;\nsetp.ne.b32 p, 0, 0;\nwgmma.mma_async.sync.aligned.m64n56k16.f32.bf16.bf16 {%0,%1,%2,%3,%4,%5,%6,%7,%8,%9,%10,%11,%12,%13,%14,%15,%16,%17,%18,%19,%20,%21,%22,%23,%24,%25,%26,%27}, {%28,%29,%30,%31}, %32, p, 1, 1, 0;\n}\n"
    : "+f"(d[0]), "+f"(d[1]), "+f"(d[2]), "+f"(d[3]), "+f"(d[4]), "+f"(d[5]), "+f"(d[6]), "+f"(d[7]), "+f"(d[8]), "+f"(d[9]), "+f"(d[10]), "+f"(d[11]), "+f"(d[12]), "+f"(d[13]), "+f"(d[14]), "+f"(d[15]), "+f"(d[16]), "+f"(d[17]), "+f"(d[18]), "+f"(d[19]), "+f"(d[20]), "+f"(d[21]), "+f"(d[22]), "+f"(d[23]), "+f"(d[24]), "+f"(d[25]), "+f"(d[26]), "+f"(d[27])
    : "r"(a0), "r"(a1), "r"(a2), "r"(a3), "l"(db));
}
__device__ __forceinline__ void wgmma_rs_n56_a(float (&d)[28], uint32_t a0, uint32_t a1, uint32_t a2, uint32_t a3, uint64_t db) {
  asm volatile("{\n.reg .pred p;\nsetp.ne.b32 p, 1, 0;\nwgmma.mma_async.sync.aligned.m64n56k16.f32.bf16.bf16 {%0,%1,%2,%3,%4,%5,%6,%7,%8,%9,%10,%11,%12,%13,%14,%15,%16,%17,%18,%19,%20,%21,%22,%23,%24,%25,%26,%27}, {%28,%29,%30,%31}, %32, p, 1, 1, 0;\n}\n"
    : "+f"(d[0]), "+f"(d[1]), "+f"(d[2]), "+f"(d[3]), "+f"(d[4]), "+f"(d[5]), "+f"(d[6]), "+f"(d[7]), "+f"(d[8]), "+f"(d[9]), "+f"(d[10]), "+f"(d[11]), "+f"(d[12]), "+f"(d[13]), "+f"(d[14]), "+f"(d[15]), "+f"(d[16]), "+f"(d[17]), "+f"(d[18]), "+f"(d[19]), "+f"(d[20]), "+f"(d[21]), "+f"(d[22]), "+f"(d[23]), "+f"(d[24]), "+f"(d[25]), "+f"(d[26]), "+f"(d[27])
    : "r"(a0), "r"(a1), "r"(a2), "r"(a3), "l"(db));
}

constexpr int NSM = 132, NH = 66;
constexpr int S0 = 0, S1 = 51200, C3 = 153600, RG = 165888;
constexpr int C1 = RG, WP = RG + 18432, TBL = RG + 47104;
constexpr int BARS = RG + 50688;
constexpr int WST = 102400;
constexpr int NBAR = 224;
constexpr int REL = BARS + NBAR * 8;
constexpr int SMEM_BYTES = REL + 16;
constexpr int B_XF = 0, B_CF1 = 15, B_CF3 = 16, B_WF = 17, B_P1D = 18, B_WFREE = 20, B_REL = 21, B_ROLE = 22, B_SIG = 24;
constexpr int B_RF = 32, B_RE = 45, B_YF = 58, B_WRD = 73, B_SFREE = 87, B_WCH = 126, B_RDY = 131, B_WE = 197, B_WL = 209;
constexpr int CNT_P1 = 0, CNT_P2 = 4, CNT_W = 8, CNT_RANK = 9, NCLS = 10, CNT_DONE = 0, CNT_REL = 1, NCNT = 2;
constexpr int SIG_W = 0, SIG_P1 = 1, SIG_P2 = 4;
#define PROBES 1
#define WB 100
#define PACE 0
#define PACE_SLACK 300
#define SWIN 2
#define XWIN 5

__device__ uint4 g_scr[(14 << 21) / 16];
__device__ uint4 g_wf[200 * 72 * 32];
__device__ unsigned g_cnt[NCNT * 32];
__device__ __forceinline__ int slot_line(int chunk, int pg, int cls) {
    return (pg & 1) << 6 | (pg >> 1) << 9 | (chunk & 1) << 10 | (chunk >> 1) << 12 | ((pg ^ (pg >> 1) ^ chunk ^ (chunk >> 1) ^ cls) & 1) << 5;
}
__device__ __forceinline__ int phi_line(int phi, uint32_t rel) {
    return (phi >> 4) << 14 | (phi & 3) << 7 | ((phi >> 2) & 1) << 11 | ((phi >> 3) & 1) << 13 | ((rel >> (phi >> 4)) & 1) << 5;
}
__host__ __device__ constexpr int quad_off(int Q) { return (Q >> 2) * 4096 + (Q & 3) * 512; }

#define PROF(k)
#define PROFW(k)
struct Maps { CUtensorMap w, x34, x6, x28, wst, f16, f8, y4, y2; char* scr; };

__device__ __forceinline__ uint32_t smem_u32(const void* p) { return (uint32_t)__cvta_generic_to_shared(p); }
__device__ __forceinline__ void mbar_wait(uint32_t bar) {
    uint32_t ok, it = 0;
    do {
        asm volatile("{\n.reg .pred p;\nmbarrier.try_wait.parity.shared::cta.b64 p, [%1], 0;\nselp.u32 %0, 1, 0, p;\n}" : "=r"(ok) : "r"(bar) : "memory");
        if (++it > (1u << 22)) break;
    } while (!ok);
}
__device__ __forceinline__ bool mbar_test(uint32_t bar) {
    uint32_t ok;
    asm volatile("{\n.reg .pred p;\nmbarrier.test_wait.parity.shared::cta.b64 p, [%1], 0;\nselp.u32 %0, 1, 0, p;\n}" : "=r"(ok) : "r"(bar) : "memory");
    return ok;
}
__device__ __forceinline__ void fence_async() { asm volatile("fence.proxy.async;" ::: "memory"); }
__device__ __forceinline__ void fence_async_smem() { asm volatile("fence.proxy.async.shared::cta;" ::: "memory"); }
#define ELECT "{\n.reg .pred p;\nelect.sync _|p, 0xffffffff;\n@p "
__device__ __forceinline__ void e_arrive(uint32_t bar) { asm volatile(ELECT "mbarrier.arrive.shared::cta.b64 _, [%0];\n}" :: "r"(bar) : "memory"); }
__device__ __forceinline__ void e_expect(uint32_t bar, uint32_t bytes) { asm volatile(ELECT "mbarrier.arrive.expect_tx.shared::cta.b64 _, [%0], %1;\n}" :: "r"(bar), "r"(bytes) : "memory"); }
__device__ __forceinline__ void e_g2s(uint32_t dst, const void* src, uint32_t bytes, uint32_t bar) {
    asm volatile(ELECT "cp.async.bulk.shared::cluster.global.mbarrier::complete_tx::bytes [%0], [%1], %2, [%3];\n}" :: "r"(dst), "l"(src), "r"(bytes), "r"(bar) : "memory");
}
__device__ __forceinline__ void e_s2g(void* dst, uint32_t src, uint32_t bytes) {
    asm volatile(ELECT "cp.async.bulk.global.shared::cta.bulk_group [%0], [%1], %2;\n}" :: "l"(dst), "r"(src), "r"(bytes) : "memory");
}
__device__ __forceinline__ void e_ld3(uint32_t dst, const CUtensorMap* m, int c0, int c1, int c2, uint32_t bar) {
    asm volatile(ELECT "cp.async.bulk.tensor.3d.shared::cluster.global.mbarrier::complete_tx::bytes [%0], [%1, {%3, %4, %5}], [%2];\n}"
                 :: "r"(dst), "l"(m), "r"(bar), "r"(c0), "r"(c1), "r"(c2) : "memory");
}
__device__ __forceinline__ void e_st3(const CUtensorMap* m, uint32_t src, int c0, int c1, int c2) {
    asm volatile(ELECT "cp.async.bulk.tensor.3d.global.shared::cta.bulk_group [%0, {%2, %3, %4}], [%1];\n}" :: "l"(m), "r"(src), "r"(c0), "r"(c1), "r"(c2) : "memory");
}
__device__ __forceinline__ void e_ld5(uint32_t dst, const CUtensorMap* m, int c4, uint32_t bar) {
    asm volatile(ELECT "cp.async.bulk.tensor.5d.shared::cluster.global.mbarrier::complete_tx::bytes [%0], [%1, {%4, %4, %4, %4, %3}], [%2];\n}"
                 :: "r"(dst), "l"(m), "r"(bar), "r"(c4), "r"(0) : "memory");
}
__device__ __forceinline__ void e_st5(const CUtensorMap* m, uint32_t src, int c4) {
    asm volatile(ELECT "cp.async.bulk.tensor.5d.global.shared::cta.bulk_group [%0, {%3, %3, %3, %3, %2}], [%1];\n}" :: "l"(m), "r"(src), "r"(c4), "r"(0) : "memory");
}
__device__ __forceinline__ void bulk_commit() { asm volatile("cp.async.bulk.commit_group;" ::: "memory"); }
template <int N> __device__ __forceinline__ void bulk_wait_read() { asm volatile("cp.async.bulk.wait_group.read %0;" :: "n"(N) : "memory"); }
__device__ __forceinline__ void wg_bar(int id) { asm volatile("bar.sync %0, 128;" :: "r"(id) : "memory"); }
__device__ __forceinline__ uint32_t uni(uint32_t v) { return __shfl_sync(0xffffffffu, v, 0); }
__device__ __forceinline__ char* cls_cnt(char* scr, int cls) { return scr + slot_line(3, 2, cls) * 128; }
__device__ __forceinline__ uint32_t cnt_wait(const void* p, unsigned target) {
    unsigned v, it = 0;
    while (true) {
        asm volatile("ld.acquire.gpu.global.u32 %0, [%1];" : "=r"(v) : "l"(p) : "memory");
        v = uni(v);
        if (v >= target || ++it > (1u << 22)) break;
    }
    return v;
}
__device__ __forceinline__ void wg_fence() { asm volatile("wgmma.fence.sync.aligned;" ::: "memory"); }
__device__ __forceinline__ void wg_commit() { asm volatile("wgmma.commit_group.sync.aligned;" ::: "memory"); }
template <int N> __device__ __forceinline__ void wg_wait() { asm volatile("wgmma.wait_group.sync.aligned %0;" :: "n"(N) : "memory"); }
template <int N> __device__ __forceinline__ void reg_fence(float (&d)[N]) {
#pragma unroll
    for (int i = 0; i < N; i++) asm volatile("" : "+f"(d[i]) :: "memory");
}
template <int N, int O, int M> __device__ __forceinline__ float (&sub(float (&d)[M]))[N] { return *reinterpret_cast<float (*)[N]>(&d[O]); }
template <int N> __device__ __forceinline__ void zero(float (&d)[N]) {
#pragma unroll
    for (int i = 0; i < N; i++) d[i] = 0.f;
}
__device__ __forceinline__ uint32_t pack2(float lo, float hi) {
    uint32_t r; asm("cvt.rn.bf16x2.f32 %0, %1, %2;" : "=r"(r) : "f"(hi), "f"(lo)); return r;
}
__device__ __forceinline__ void stm4(uint32_t a, uint32_t r0, uint32_t r1, uint32_t r2, uint32_t r3) {
    asm volatile("stmatrix.sync.aligned.m8n8.x4.trans.shared.b16 [%0], {%1,%2,%3,%4};" :: "r"(a), "r"(r0), "r"(r1), "r"(r2), "r"(r3) : "memory");
}
__device__ __forceinline__ void stm2(uint32_t a, uint32_t r0, uint32_t r1) {
    asm volatile("stmatrix.sync.aligned.m8n8.x2.trans.shared.b16 [%0], {%1,%2};" :: "r"(a), "r"(r0), "r"(r1) : "memory");
}
__device__ __forceinline__ void stm1(uint32_t a, uint32_t r0) {
    asm volatile("stmatrix.sync.aligned.m8n8.x1.trans.shared.b16 [%0], {%1};" :: "r"(a), "r"(r0) : "memory");
}
struct Desc {
    uint32_t lo, hi;
    __device__ __forceinline__ operator uint64_t() const { return ((uint64_t)hi << 32) | lo; }
    __device__ __forceinline__ Desc operator+(uint32_t o) const { return Desc{lo + o, hi}; }
    __device__ __forceinline__ Desc operator^(uint32_t o) const { return Desc{lo ^ o, hi}; }
};
__device__ __forceinline__ Desc mkdesc(uint32_t addr, uint32_t lbo, uint32_t sbo, uint32_t swz) {
    return Desc{((addr & 0x3FFFF) >> 4) | ((lbo >> 4) << 16), (sbo >> 4) | (swz << 30)};
}
__device__ __forceinline__ uint32_t cos_bits(int k) {
    if (k > 20) k = 40 - k;
    const bool neg = k > 10;
    if (neg) k = 20 - k;
    const unsigned long long pk = k < 4 ? COS_PK0 : k < 8 ? COS_PK1 : COS_PK2;
    return (uint32_t)((pk >> (16 * (k & 3))) & 0xffff) ^ (neg ? 0x8000u : 0u);
}

__device__ __forceinline__ void task_w(int wg, int k, uint32_t sb) {
    const int tid = threadIdx.x & 127, w = uni(tid >> 5), lane = tid & 31, q = lane & 3;
    const int tb = 14 * k, t1 = min(tb + 14, 1800), cb0 = tb / 25;
    float acc[64];
    zero(acc);
    int cnt, at = 0;
#pragma unroll 1
    for (int t = tb; t < t1; t += cnt, at++) {
        const int cb = t / 25, oc = t - 25 * cb;
        cnt = min(min(4, 25 - oc), t1 - t);
        if ((at ? 2 - (at & 1) : 0) != wg) continue;
        const Desc dB = mkdesc(sb + WP + (cb - cb0) * 14336, 3584, 512, 2);
        const int phi = 8 * (oc + w) + (lane >> 2), f = phi / 20, ca = (2 * f + 1) * 4, cbb = (phi - 20 * f) * 8;
        uint32_t a[4][4];
#pragma unroll
        for (int j = 0; j < 3; j++)
#pragma unroll
            for (int h = 0; h < 2; h++) {
                uint32_t v[2];
#pragma unroll
                for (int e = 0; e < 2; e++) {
                    const int tap = 16 * j + 8 * h + 2 * q + e, kh = (tap * 37) >> 8, kw = tap - 7 * kh;
                    asm volatile("ld.shared.u32 %0, [%1];" : "=r"(v[e]) : "r"(sb + TBL + ca * kh + cbb * kw));
                }
                a[j][2 * h] = __byte_perm(v[0], v[1], 0x5410);
                a[j][2 * h + 1] = __byte_perm(v[0], v[1], 0x7632);
            }
        {
            uint32_t v;
            asm volatile("ld.shared.u32 %0, [%1];" : "=r"(v) : "r"(sb + TBL + (ca + cbb) * 6));
            if (q) v = 0;
            a[3][0] = 0; a[3][1] = 0; a[3][2] = v & 0xffff; a[3][3] = v >> 16;
        }
        if (at == 0) PROFW(124);
        mbar_wait(sb + BARS + 8 * B_WF);
        if (at) mbar_wait(sb + BARS + 8 * (B_WCH + at - 1));
        if (at == 0) PROFW(125);
        wg_fence();
        wgmma_rs_n128_z(acc, a[0][0], a[0][1], a[0][2], a[0][3], dB);
        wgmma_rs_n128_a(acc, a[1][0], a[1][1], a[1][2], a[1][3], dB + (uint32_t)(16 * 64 >> 4));
        wgmma_rs_n128_a(acc, a[2][0], a[2][1], a[2][2], a[2][3], dB + (uint32_t)(32 * 64 >> 4));
        wgmma_rs_n128_a(acc, a[3][0], a[3][1], a[3][2], a[3][3], dB + (uint32_t)(40 * 64 >> 4));
        wg_commit();
        wg_wait<0>();
        reg_fence(acc);
        if (at == 0) PROFW(120);
        e_arrive(sb + BARS + 8 * (B_WCH + at));
        if (w < cnt) {
            const uint32_t dst = sb + WST + (t - tb + w) * 4096 + (lane >> 2) * 512 + ((q ^ cb) & 3) * 16;
#pragma unroll
            for (int j = 0; j < 4; j++)
#pragma unroll
                for (int e = 0; e < 2; e++)
                    asm volatile("st.shared.v4.u32 [%0], {%1,%2,%3,%4};" :: "r"(dst + j * 128 + e * 64),
                                 "r"(pack2(acc[4 * j + e], acc[16 + 4 * j + e])), "r"(pack2(acc[4 * j + 2 + e], acc[16 + 4 * j + 2 + e])),
                                 "r"(pack2(acc[32 + 4 * j + e], acc[48 + 4 * j + e])), "r"(pack2(acc[32 + 4 * j + 2 + e], acc[48 + 4 * j + 2 + e])) : "memory");
            fence_async_smem();
            e_arrive(sb + BARS + 8 * (B_WRD + t - tb + w));
        }
    }
}

__device__ __forceinline__ void task_p1(int wg, int pair, uint32_t sb) {
    const int tid = threadIdx.x & 127, w = tid >> 5, lane = tid & 31;
    const uint32_t buf = sb + wg * 51200, bars = sb + BARS;
    uint32_t fr[5][10][2];
    float A[40], d[20];
    zero(A);
    {
        const Desc dA = mkdesc(buf, 3584, 512, 2), dB = mkdesc(sb + C1, 128, 256, 0);
        auto issue = [&](int g, float (&d)[40]) {
            mbar_wait(bars + 8 * (B_XF + wg * 5 + g));
            wg_fence();
            wgmma_ss_n80_z(d, dA + (uint32_t)(g * 8704 >> 4), dB);
#pragma unroll
            for (int j = 1; j < 5; j++) wgmma_ss_n80_a(d, dA + (uint32_t)((g * 8704 + j * 1024) >> 4), dB + (uint32_t)(j * 2560 >> 4));
            wg_commit();
        };
        auto pack = [&](int g, float (&d)[40]) {
            reg_fence(d);
#pragma unroll
            for (int f = 0; f < 10; f++) {
                fr[g][f][0] = pack2(d[4 * f], d[4 * f + 1]);
                fr[g][f][1] = pack2(d[4 * f + 2], d[4 * f + 3]);
            }
        };
        mbar_wait(bars + 8 * B_CF1);
#pragma unroll
        for (int g = 0; g < 4; g++) { issue(g, A); if (g == 0) PROFW(8 + wg * 8 + 1); wg_wait<0>(); pack(g, A); }
        zero(d);
        mbar_wait(bars + 8 * (B_XF + wg * 5 + 4));
#pragma unroll
        for (int h = 0; h < 2; h++) {
            wg_fence();
            wgmma_ss_n40_z(d, dA + (uint32_t)(4 * 8704 >> 4), dB + (uint32_t)(h * 1280 >> 4));
#pragma unroll
            for (int j = 1; j < 5; j++) wgmma_ss_n40_a(d, dA + (uint32_t)((4 * 8704 + j * 1024) >> 4), dB + (uint32_t)((j * 2560 + h * 1280) >> 4));
            wg_commit(); wg_wait<0>(); reg_fence(d);
#pragma unroll
            for (int f = 0; f < 5; f++) { fr[4][5 * h + f][0] = pack2(d[4 * f], d[4 * f + 1]); fr[4][5 * h + f][1] = pack2(d[4 * f + 2], d[4 * f + 3]); }
        }
    }
    wg_bar(1 + wg);
    PROFW(8 + wg * 8 + 2);
    {
        const Desc dB = mkdesc(sb + C1 + 12800, 128, 256, 0);
        const int i = lane & 7, mi = lane >> 3, th = w >> 1, tz = (2 * pair + th) & 3;
        const uint32_t s0 = buf + (i >> 1) * 128 + (i & 1) * 64 + (((2 * (w & 1) + (mi & 1)) ^ tz ^ (i >> 1)) << 4);
        const uint32_t sA = s0 + th * 2048 + (mi >> 1) * 512, sB = s0 + th * 2048 + (mi >> 1) * 2560, sC = s0 + th * 1024 + (mi >> 1) * 512;
        auto issue = [&](int f, float (&d)[20]) {
            wg_fence();
            wgmma_rs_n40_z(d, fr[0][f][0], fr[0][f][1], fr[1][f][0], fr[1][f][1], dB);
            wgmma_rs_n40_a(d, fr[2][f][0], fr[2][f][1], fr[3][f][0], fr[3][f][1], dB + (uint32_t)(1280 >> 4));
            wgmma_rs_n40_a(d, fr[4][f % 5][0], fr[4][f % 5][1], fr[4][f % 5 + 5][0], fr[4][f % 5 + 5][1], dB + (uint32_t)((2560 + (f / 5) * 1280) >> 4));
            wg_commit();
        };
#pragma unroll
        for (int f = 0; f < 10; f++) {
                        issue(f, d); wg_wait<0>(); reg_fence(d);
            const int Q = 5 * f;
            stm4(((Q & 3) == 3 ? sB : sA) + quad_off(Q), pack2(d[0], d[1]), pack2(d[2], d[3]), pack2(d[4], d[5]), pack2(d[6], d[7]));
            stm2(sA + quad_off(Q + 2), pack2(d[8], d[9]), pack2(d[10], d[11]));
            stm4((f == 9 ? sC : ((Q + 3) & 3) == 3 ? sB : sA) + quad_off(Q + 3), pack2(d[12], d[13]), pack2(d[14], d[15]), pack2(d[16], d[17]), pack2(d[18], d[19]));
            if (f & 1) { fence_async_smem(); e_arrive(bars + 8 * (B_RDY + wg * 5 + (f >> 1))); }
        }
    }
}

__device__ __forceinline__ void task_p2(int wg, int rk, uint32_t sb) {
    const int tid = threadIdx.x & 127, w = tid >> 5, lane = tid & 31;
    const uint32_t bars = sb + BARS;
    const int phi0 = 3 * rk, phiE = 198 + ((rk - 58) >> 2), pgE = rk >= 58 ? (rk - 58) & 3 : -1;
    uint4 wA[6], wB[6], wC[6], wE[6];
    auto ldw = [&](uint4 (&a)[6], int j, int phi) {
        const int pc = 3 * j + wg;
        const uint32_t p = sb + S0 + (pc & 3) * 12288 + (lane & 3) * 512 + w * 128 + ((lane >> 2) & 1) * 64 + (((lane >> 3) ^ lane) & 3) * 16 + (phi & 1) * 8;
        mbar_wait(bars + 8 * (B_WL + pc));
#pragma unroll
        for (int s = 0; s < 6; s++) {
            asm volatile("ld.shared.v2.u32 {%0, %1}, [%2];" : "=r"(a[s].x), "=r"(a[s].y) : "r"(p + s * 2048) : "memory");
            asm volatile("ld.shared.v2.u32 {%0, %1}, [%2];" : "=r"(a[s].z), "=r"(a[s].w) : "r"((p ^ 8) + s * 2048) : "memory");
        }
        uint32_t dep = 0;
#pragma unroll
        for (int s = 0; s < 6; s++) dep |= a[s].x ^ a[s].z;
        asm volatile("{\n.reg .pred p;\nsetp.eq.u32 p, %0, 0x7fc17fc1;\n@p nanosleep.u32 0;\n}" :: "r"(dep) : "memory");
        __syncwarp();
        e_arrive(bars + 8 * (B_WE + pc));
    };
    ldw(wA, 0, phi0); ldw(wB, 1, phi0 + 1); ldw(wC, 2, phi0 + 2);
    if (pgE >= 0) ldw(wE, 3, phiE);
    PROFW(8 + wg * 8 + 4);
    mbar_wait(bars + 8 * (B_SIG + SIG_P1 + 1));
    const int i = lane & 7, mi = lane >> 3;
    const uint32_t soff = sb + S1 + wg * 4096 + mi * 512 + (i >> 1) * 128 + (i & 1) * 64;
    const int xo = w ^ (i >> 1);
    float p0[16], p1[16];
    zero(p0); zero(p1);
    auto issue = [&](float (&d)[16], int n, int h, const uint4 (&a)[6], int z) {
        const Desc d0 = mkdesc(sb + RG + (n & 3) * 12288 + h * 2048 + ((z >> 1) << 5), 16, 512, 2), d1 = d0 ^ 2u;
        if (h == 0) mbar_wait(bars + 8 * (B_RF + n));
        wg_fence();
        wgmma_rs_n32_z(d, a[0].x, a[0].y, a[0].z, a[0].w, d0);
        wgmma_rs_n32_a(d, a[1].x, a[1].y, a[1].z, a[1].w, d1);
#pragma unroll
        for (int c = 1; c < 3; c++) {
            wgmma_rs_n32_a(d, a[2 * c].x, a[2 * c].y, a[2 * c].z, a[2 * c].w, d0 + (uint32_t)(c * 4096 >> 4));
            wgmma_rs_n32_a(d, a[2 * c + 1].x, a[2 * c + 1].y, a[2 * c + 1].z, a[2 * c + 1].w, d1 + (uint32_t)(c * 4096 >> 4));
        }
        wg_commit();
    };
    auto epi = [&](float (&d)[16], int n, int h, int z) {
        reg_fence(d);
        if (h) e_arrive(bars + 8 * (B_RE + n));
        uint32_t p[4];
#pragma unroll
        for (int j = 0; j < 4; j++) p[j] = pack2(d[4 * j] - d[4 * j + 3], d[4 * j + 2] + d[4 * j + 1]);
        if (h == 0 && n >= 4) mbar_wait(bars + 8 * (B_SFREE + (n - 4) * 3 + wg));
        stm4(soff + (n & 3) * 12288 + h * 2048 + ((xo ^ z) << 4), p[0], p[1], p[2], p[3]);
        if (h) { fence_async_smem(); e_arrive(bars + 8 * (B_RDY + 15 + n * 3 + wg)); }
    };
    const int zA = phi0 & 3, zB = (phi0 + 1) & 3, zC = (phi0 + 2) & 3, zE = phiE & 3;
    int n = 0;
#pragma unroll 1
    for (int it = 0; it < 4; it++) {
        issue(p0, n, 0, wA, zA);
        issue(p1, n, 1, wA, zA);     wg_wait<1>(); epi(p0, n, 0, zA);
        issue(p0, n + 1, 0, wB, zB); wg_wait<1>(); epi(p1, n, 1, zA);
        PROFW(40 + wg * 8 + it * 2);
        issue(p1, n + 1, 1, wB, zB); wg_wait<1>(); epi(p0, n + 1, 0, zB);
        issue(p0, n + 2, 0, wC, zC); wg_wait<1>(); epi(p1, n + 1, 1, zB);
        issue(p1, n + 2, 1, wC, zC); wg_wait<1>(); epi(p0, n + 2, 0, zC);
        wg_wait<0>(); epi(p1, n + 2, 1, zC);
        n += 3;
        if (it == pgE) {
            issue(p0, n, 0, wE, zE);
            issue(p1, n, 1, wE, zE); wg_wait<1>(); epi(p0, n, 0, zE);
            wg_wait<0>(); epi(p1, n, 1, zE);
            n++;
        }
        PROFW(40 + wg * 8 + it * 2 + 1);
    }
}

__device__ __forceinline__ void task_p3(int wg, int pair, uint32_t sb) {
    const int tid = threadIdx.x & 127, w = tid >> 5, lane = tid & 31;
    const uint32_t buf = sb + (wg ? 3 - wg : 0) * 51200, bars = sb + BARS;
    uint32_t fr[10][4][2];
    float A[32];
    zero(A);
    {
        const Desc dB = mkdesc(sb + C3, 128, 256, 0);
        const uint32_t a0 = (buf & 0x3FFFF) >> 4;
        auto dq = [&](int Q) {
            return Desc{a0 + (uint32_t)((quad_off(Q) >> 4) | ((Q < 48 ? 2048 : 1024) >> 4) << 16), (uint32_t)((quad_off(Q + 1) - quad_off(Q)) >> 4) | (2u << 30)};
        };
        float (&d0)[16] = sub<16, 0>(A);
        float (&d1)[16] = sub<16, 16>(A);
        mbar_wait(bars + 8 * B_CF3);
#pragma unroll
        for (int j = 0; j < 5; j++) {
            mbar_wait(bars + 8 * (B_YF + wg * 5 + j));
            if (j == 0) PROFW(64 + wg * 8 + 1);
            wg_fence();
            wgmma_ss_n32_z(d0, dq(10 * j), dB);
            wgmma_ss_n32_z(d1, dq(10 * j + 5), dB);
            wgmma_ss_n32_a(d0, dq(10 * j + 1), dB + (uint32_t)(1024 >> 4));
            wgmma_ss_n32_a(d1, dq(10 * j + 6), dB + (uint32_t)(1024 >> 4));
            wgmma_ss_n32_a(d0, dq(10 * j + 3), dB + (uint32_t)(2048 >> 4));
            wgmma_ss_n32_a(d1, dq(10 * j + 8), dB + (uint32_t)(2048 >> 4));
            wg_commit(); wg_wait<0>(); reg_fence(A);
#pragma unroll
            for (int e = 0; e < 2; e++)
#pragma unroll
                for (int g = 0; g < 4; g++) {
                    fr[2 * j + e][g][0] = pack2(A[16 * e + 4 * g], A[16 * e + 4 * g + 1]);
                    fr[2 * j + e][g][1] = pack2(A[16 * e + 4 * g + 2], A[16 * e + 4 * g + 3]);
                }
        }
    }
    wg_bar(1 + wg);
    PROFW(64 + wg * 8 + 2);
    {
        const Desc dB = mkdesc(sb + C3 + 3072, 128, 256, 0);
        const int i = lane & 7, mi = lane >> 3, th = w >> 1, tz = (2 * pair + th) & 3;
        const int oct = (2 * (w & 1) + (mi & 1)) ^ tz;
        const uint32_t soff = buf + th * 3584 + (mi >> 1) * 512 + i * 64 + ((oct ^ (i >> 1)) << 4);
        float d[28]; zero(d);
        auto issue = [&](int g, float (&d)[28]) {
            wg_fence();
            wgmma_rs_n56_z(d, fr[0][g][0], fr[0][g][1], fr[1][g][0], fr[1][g][1], dB);
#pragma unroll
            for (int s = 1; s < 5; s++) wgmma_rs_n56_a(d, fr[2 * s][g][0], fr[2 * s][g][1], fr[2 * s + 1][g][0], fr[2 * s + 1][g][1], dB + (uint32_t)(s * 1792 >> 4));
            wg_commit();
        };
#pragma unroll
        for (int gg = 1; gg < 5; gg++) {
            const int g = gg & 3;
                        issue(g, d); wg_wait<0>(); reg_fence(d);
            if (g) {
                const uint32_t a = soff + g * 7168;
#pragma unroll
                for (int j = 0; j < 3; j++)
                    stm4(a + j * 1024, pack2(d[8 * j], d[8 * j + 1]), pack2(d[8 * j + 2], d[8 * j + 3]), pack2(d[8 * j + 4], d[8 * j + 5]), pack2(d[8 * j + 6], d[8 * j + 7]));
                stm2(a + 3072, pack2(d[24], d[25]), pack2(d[26], d[27]));
            } else {
#pragma unroll
                for (int j = 0; j < 4; j++) {
                    const int row = th * 14 + 4 * j + 2 * (mi >> 1) + (i >> 2);
                    const uint32_t a = (i & 2) ? buf + row * 128 + (i & 1) * 64 + ((oct ^ (row & 3)) << 4) : buf + 4096 + lane * 16;
                    if (j < 3) stm4(a, pack2(d[8 * j], d[8 * j + 1]), pack2(d[8 * j + 2], d[8 * j + 3]), pack2(d[8 * j + 4], d[8 * j + 5]), pack2(d[8 * j + 6], d[8 * j + 7]));
                    else stm2(a, pack2(d[24], d[25]), pack2(d[26], d[27]));
                }
            }
            fence_async_smem();
            e_arrive(bars + 8 * (B_RDY + 54 + wg * 4 + gg - 1));
        }
    }
}

__device__ __forceinline__ void load_x(int cls, int rk, int u, uint32_t sb, const Maps& mp) {
    const uint32_t bars = sb + BARS;
    const int id = u * NH + rk, pl = id / 3, chunk = id - 3 * pl, tp = cls * 4 + (pl >> 4), tx = pl & 15;
#pragma unroll 1
    for (int g = 0; g < 5; g++) {
        const int bi = u * 5 + g;
        if (bi >= XWIN) mbar_wait(bars + 8 * (B_XF + bi - XWIN));
        int col = 14 * tx - 8 + 4 * g; if (col < 0) col += 224;
        const uint32_t bar = bars + 8 * (B_XF + bi), dst = sb + u * 51200 + g * 8704;
        e_expect(bar, 8704);
        if (tp) e_ld3(dst, &mp.x34, 32 * chunk, col, 28 * tp - 6, bar);
        else { e_ld3(dst, &mp.x6, 32 * chunk, col, 218, bar); e_ld3(dst + 1536, &mp.x28, 32 * chunk, col, 0, bar); }
    }
}

__device__ __forceinline__ void load_first(uint32_t sb, const Maps& mp) {
    const uint32_t bars = sb + BARS;
    const int k = blockIdx.x;
    PROF(122);
    if (k < 129) {
        const int cb0 = 14 * k / 25, cb1 = min((14 * k + 13) / 25, 71);
        e_expect(bars + 8 * B_WF, (cb1 - cb0 + 1) * 14336);
#pragma unroll 1
        for (int cb = cb0; cb <= cb1; cb++) {
            const int b = cb / 24, i0 = 16 * ((cb >> 2) - 6 * b) + 2 * (cb & 3);
            e_ld3(sb + WP + (cb - cb0) * 14336, &mp.w, 32 * b, 0, i0, bars + 8 * B_WF);
            e_ld3(sb + WP + (cb - cb0) * 14336 + 7168, &mp.w, 32 * b, 0, i0 + 8, bars + 8 * B_WF);
        }
    }
    e_expect(bars + 8 * B_CF1, 17920); e_g2s(sb + C1, TAB_P1, 17920, bars + 8 * B_CF1);
}

__device__ __forceinline__ uint32_t get_rel(uint32_t sb) {
    mbar_wait(sb + BARS + 8 * B_REL);
    uint32_t v; asm volatile("ld.shared.u32 %0, [%1];" : "=r"(v) : "r"(sb + REL) : "memory");
    return uni(v);
}

__device__ __forceinline__ void load_warp(int cls, int rk, uint32_t sb, const Maps& mp) {
    const uint32_t bars = sb + BARS;
    load_x(cls, rk, 0, sb, mp);
    PROF(123);
    load_x(cls, rk, 1, sb, mp);
    mbar_wait(bars + 8 * B_WFREE);
    if (rk < 60) load_x(cls, rk, 2, sb, mp);
    e_expect(bars + 8 * B_CF3, 12032); e_g2s(sb + C3, TAB_P3, 12032, bars + 8 * B_CF3);
    PROF(1);
    const uint32_t rel = get_rel(sb);
    const char* cnt = cls_cnt(mp.scr, cls);
    const int pgE = rk >= 58 ? (rk - 58) & 3 : -1;
    mbar_wait(bars + 8 * B_P1D);
    int n = 0;
#pragma unroll 1
    for (int pg = 0; pg < 4; pg++) {
        cnt_wait(cnt + (CNT_P1 + pg) * 128, 48);
        PROF(88 + pg);
        const int l0 = slot_line(0, pg, cls), l1 = slot_line(1, pg, cls), l2 = slot_line(2, pg, cls);
        const int nj = pg == pgE ? 4 : 3;
#pragma unroll 1
        for (int j = 0; j < nj; j++) {
            const int lp = phi_line(j == 3 ? 198 + ((rk - 58) >> 2) : 3 * rk + j, rel);
            const uint32_t bar = bars + 8 * (B_RF + n), dst = sb + RG + (n & 3) * 12288;
            if (n >= 4) mbar_wait(bars + 8 * (B_RE + n - 4));
            e_expect(bar, 12288);
            e_g2s(dst, mp.scr + (size_t)(lp ^ l0) * 128, 4096, bar);
            e_g2s(dst + 4096, mp.scr + (size_t)(lp ^ l1) * 128, 4096, bar);
            e_g2s(dst + 8192, mp.scr + (size_t)(lp ^ l2) * 128, 4096, bar);
            n++;
        }
    }
}

__device__ __forceinline__ int near_page(char* p, int rounds) {
#pragma unroll
    for (int e = 0; e < 4; e++) asm volatile("st.relaxed.gpu.global.v4.u32 [%0], {%1, %1, %1, %1};" :: "l"(p + (e >> 1) * 4096 + (e & 1) * 16), "r"(0) : "memory");
    int score = 0;
#pragma unroll 1
    for (int r = 0; r < rounds; r++) {
        uint32_t v0, v1, t0, t1;
        asm volatile("atom.relaxed.gpu.global.exch.b32 %0, [%1], 1;" : "=r"(v0) : "l"(p + (r & 1) * 4096) : "memory");
        asm volatile("atom.relaxed.gpu.global.exch.b32 %0, [%1], 1;" : "=r"(v1) : "l"(p + (~r & 1) * 4096) : "memory");
        asm volatile("{\n.reg .pred p;\nsetp.ne.u32 p, %1, 0xffffffff;\nmov.u32 %0, 0;\n@p mov.u32 %0, %%clock;\n}" : "=r"(t0) : "r"(v0) : "memory");
        asm volatile("{\n.reg .pred p;\nsetp.ne.u32 p, %1, 0xffffffff;\nmov.u32 %0, 0;\n@p mov.u32 %0, %%clock;\n}" : "=r"(t1) : "r"(v1) : "memory");
        const int gap = min((int)(t1 - t0), 160) - 80;
        score += (r & 1) ? gap : -gap;
    }
    return score > 0;
}

__device__ __forceinline__ void find_role(uint32_t sb, char* scr) {
    const int k = blockIdx.x;
    int c = near_page(scr + (slot_line(3, 3, 0) + phi_line(1 + (k >> 5), 0) + (k & 31)) * 128, PROBES);
    PROF(3);
    int r;
    asm volatile("atom.relaxed.gpu.global.add.u32 %0, [%1], 1;" : "=r"(r) : "l"(cls_cnt(scr, c) + CNT_RANK * 128) : "memory");
    if (r >= NH) { c ^= 1; r = NSM - 1 - r; }
    asm volatile("st.shared.u32 [%0], %1;" :: "r"(sb + REL + 4), "r"(c << 8 | r) : "memory");
    PROF(5);
}
__device__ __forceinline__ void get_role(uint32_t sb, int& cls, int& rk) {
    mbar_wait(sb + BARS + 8 * B_ROLE);
    uint32_t v; asm volatile("ld.shared.u32 %0, [%1];" : "=r"(v) : "r"(sb + REL + 4) : "memory");
    v = uni(v); cls = v >> 8; rk = v & 255;
}

__device__ __forceinline__ void load3_warp(int cls, int rk, uint32_t sb, const Maps& mp) {
    const uint32_t bars = sb + BARS;
    uint32_t rel = 0;
    mbar_wait(bars + 8 * B_XF);
    rel = cnt_wait(&g_cnt[CNT_REL * 32], 12u << 16);
    asm volatile("st.shared.u32 [%0], %1;" :: "r"(sb + REL), "r"(rel) : "memory");
    __syncwarp();
    e_arrive(bars + 8 * B_REL);
    PROF(7);
    mbar_wait(bars + 8 * (B_SIG + SIG_W));
    cnt_wait(cls_cnt(mp.scr, cls) + CNT_W * 128, NSM);
    PROF(2);
    mbar_wait(bars + 8 * (B_SIG + SIG_P1));
    {
        const int np = rk >= 58 ? 12 : 9;
#pragma unroll 1
        for (int pc = 0; pc < np; pc++) {
            if (pc >= 4) mbar_wait(bars + 8 * (B_WE + pc - 4));
            e_expect(bars + 8 * (B_WL + pc), 12288);
            e_g2s(sb + S0 + (pc & 3) * 12288, g_wf + (pc < 9 ? 9 * rk + pc : 3 * (198 + ((rk - 58) >> 2)) + pc - 9) * 768, 12288, bars + 8 * (B_WL + pc));
        }
    }
    mbar_wait(bars + 8 * (B_SIG + SIG_P2));
    const int nu = rk < 60 ? 3 : 2;
#pragma unroll 1
    for (int u = 0; u < nu; u++) {
        const int id = u * NH + rk, pl = id / 3, chunk = id - 3 * pl;
        const int l0 = slot_line(chunk, pl >> 4, cls) + (pl & 15) * 2;
        const uint32_t buf = sb + (u ? 3 - u : 0) * 51200, bar = bars + 8 * (B_YF + u * 5);
#pragma unroll
        for (int j = 0; j < 5; j++) e_expect(bar + 8 * j, j == 4 ? 10240 : (j & 1) ? 8192 : 12288);
        if (u == 2) mbar_wait(bars + 8 * (B_SIG + SIG_P2 + 3));
        cnt_wait(cls_cnt(mp.scr, cls) + (CNT_P2 + (pl >> 4)) * 128, NH);
        PROF(64 + u * 8);
        uint32_t bj = bar;
#pragma unroll 1
        for (int G = 0; G < 12; G++) {
            e_ld5(buf + G * 4096, &mp.f16, (l0 ^ ((rel >> G) & 1) << 5) + (G << 14), bj);
            bj += (0x294 >> G & 1) * 8;
        }
        e_ld5(buf + 12 * 4096, &mp.f8, (l0 ^ ((rel >> 12) & 1) << 5) + (12 << 14), bj);
    }
}

__device__ __forceinline__ void store_warp(uint32_t sb, const Maps& mp) {
    const uint32_t bars = sb + BARS;
    const int k = blockIdx.x;
    uint32_t pa = 0, pb = 0, qa = 0, qb = 0;
    auto arr2 = [&](uint32_t& a, uint32_t& b) { if (a) e_arrive(a); if (b) e_arrive(b); a = b = 0; };
    auto pre = [&](int idx) {
        const uint32_t bar = bars + 8 * idx;
        if (!mbar_test(bar)) { bulk_wait_read<0>(); arr2(qa, qb); arr2(pa, pb); mbar_wait(bar); }
    };
    auto post = [&](uint32_t fr) {
        bulk_commit(); bulk_wait_read<SWIN - 1>();
        if (SWIN == 3) { arr2(qa, qb); qa = pa; qb = pb; pb = 0; } else arr2(pa, pb);
        pa = fr;
    };
    auto after = [&](uint32_t a, uint32_t b) { if (a) pa = a; pb = b; };
    auto pace = [&](uint32_t) {};
    {
        int cb = 14 * k / 25, oc = 14 * k - 25 * cb;
#pragma unroll 1
        for (int i = 0; i < 14 && cb < 72; i++) {
            pre(B_WRD + i);
            if (i == 0) PROF(6);
            pace(4 * PACE);
            e_st3(&mp.wst, sb + WST + i * 4096, 0, 8 * oc, cb);
            post(0);
            if (++oc == 25) { oc = 0; cb++; }
        }
        after(bars + 8 * B_WFREE, bars + 8 * (B_SIG + SIG_W));
    }
    pre(B_REL);
    const uint32_t rel = get_rel(sb);
    int cls, rk; get_role(sb, cls, rk);
    const int nu = rk < 60 ? 3 : 2;
#pragma unroll 1
    for (int u = 0; u < nu; u++) {
        const int id = u * NH + rk, pl = id / 3, chunk = id - 3 * pl;
        const int l0 = slot_line(chunk, pl >> 4, cls) + (pl & 15) * 2;
        int j = B_RDY + u * 5;
#pragma unroll 1
        for (int G = 0; G < 13; G++) {
            if (0x4a5 >> G & 1) pre(j++);
            if (G == 0) PROF(104 + u);
            pace(G < 12 ? 4 * PACE : 2 * PACE);
            e_st5(G < 12 ? &mp.f16 : &mp.f8, sb + u * 51200 + G * 4096, (l0 ^ ((rel >> G) & 1) << 5) + (G << 14));
            post(0);
        }
        after(0, bars + 8 * (B_SIG + SIG_P1 + u));
    }
    const int pgE = rk >= 58 ? (rk - 58) & 3 : -1;
    int n = 0;
#pragma unroll 1
    for (int pg = 0; pg < 4; pg++) {
        const int nj = pg == pgE ? 4 : 3;
        const int l0 = slot_line(0, pg, cls), l1 = slot_line(1, pg, cls), l2 = slot_line(2, pg, cls);
#pragma unroll 1
        for (int j = 0; j < nj; j++) {
            const int lp = phi_line(j == 3 ? 198 + ((rk - 58) >> 2) : 3 * rk + j, rel);
#pragma unroll
            for (int b = 0; b < 3; b++) {
                pre(B_RDY + 15 + n * 3 + b);
                if (j == 0 && b == 0 && pg < 3) PROF(107 + pg);
                pace(4 * PACE);
                e_s2g(mp.scr + (size_t)(lp ^ (b == 0 ? l0 : b == 1 ? l1 : l2)) * 128, sb + S1 + (n & 3) * 12288 + b * 4096, 4096);
                post(bars + 8 * (B_SFREE + n * 3 + b));
            }
            n++;
        }
        after(0, bars + 8 * (B_SIG + SIG_P2 + pg));
    }
#pragma unroll 1
    for (int u = 0; u < nu; u++) {
        const int id = u * NH + rk, pl = id / 3, chunk = id - 3 * pl, tp = cls * 4 + (pl >> 4), tx = pl & 15;
        const uint32_t buf = sb + (u ? 3 - u : 0) * 51200;
#pragma unroll
        for (int gg = 1; gg < 5; gg++) {
            pre(B_RDY + 54 + u * 4 + gg - 1);
            if (gg == 1) PROF(110 + u);
            if (u < 2) pace(gg < 4 ? 7 * PACE : 7 * PACE / 2);
            if (gg < 4) e_st3(&mp.y4, buf + gg * 7168, 32 * chunk, 14 * tx - 4 + 4 * gg, 28 * tp);
            else e_st3(&mp.y2, buf, 32 * chunk, tx == 0 ? 222 : 14 * tx - 2, 28 * tp);
            post(0);
        }
    }
    bulk_wait_read<0>();
    PROF(113);
}

__device__ __forceinline__ void signal_warp(int cls, int rk, uint32_t sb, char* scr) {
    const uint32_t bars = sb + BARS;
    char* cnt = cls_cnt(scr, cls);
    if (threadIdx.x & 31) return;
#pragma unroll 1
    for (int c = 0; c < 8; c++) {
        if (c == SIG_P1 + 2 && rk >= 60) continue;
        char* ctr = cnt + (c == SIG_W ? CNT_W : c < SIG_P2 ? CNT_P1 + ((c - SIG_P1) * NH + rk) / 48 : CNT_P2 + c - SIG_P2) * 128;
        mbar_wait(bars + 8 * (B_SIG + c));
        PROF(32 + c);
        fence_async();
        asm volatile("red.relaxed.gpu.global.add.u32 [%0], 1;" :: "l"(ctr) : "memory");
        if (c == SIG_W) asm volatile("red.relaxed.gpu.global.add.u32 [%0], 1;" :: "l"((uintptr_t)ctr ^ 4096) : "memory");
        PROF(96 + c);
    }
    mbar_wait(bars + 8 * (B_YF + (rk < 60 ? 14 : 9)));
    unsigned old;
    asm volatile("atom.add.acq_rel.gpu.global.u32 %0, [%1], 1;" : "=r"(old) : "l"(&g_cnt[CNT_DONE * 32]) : "memory");
    if (old == NSM - 1) {
#pragma unroll
        for (int c = 0; c < NCNT; c++) g_cnt[c * 32] = 0;
#pragma unroll 1
        for (int c = 0; c < NCLS; c++) { *reinterpret_cast<unsigned*>(cnt + c * 128) = 0; *reinterpret_cast<unsigned*>(((uintptr_t)cnt ^ 4096) + c * 128) = 0; }
    }
}

__global__ void __launch_bounds__(512, 1) fftconv_kernel(const __grid_constant__ Maps mp) {
    extern __shared__ __align__(1024) uint8_t smem[];
    const uint32_t sb = smem_u32(smem);
    const int tid = threadIdx.x, warp = uni(tid >> 5), wg = warp >> 2;
    int cls, rk;
    auto bar_init = [&](int i) {
        uint32_t c = 1;
        if (i == B_P1D || (i >= B_RE && i < B_RE + 13)) c = 12;
        else if (i >= B_WCH && i < B_WL) c = 4;
        asm volatile("st.shared.v2.u32 [%0], {%1, %2};" :: "r"(sb + BARS + 8 * i), "r"((0x100000u - c) << 1), "r"((0x100000u - c) << 11) : "memory");
        fence_async_smem();
    };
    if (wg == 3) {
        asm volatile("setmaxnreg.dec.sync.aligned.u32 32;");
        if (warp == 12) {
            bar_init(tid & 31);
            __syncwarp();
            asm volatile("bar.arrive 4, 416;" ::: "memory");
            load_first(sb, mp);
            asm volatile("bar.sync 5, 416;" ::: "memory");
            get_role(sb, cls, rk);
            load_warp(cls, rk, sb, mp);
        } else if (warp == 13) {
            if ((tid & 31) < 8) asm volatile("prefetch.tensormap [%0];" :: "l"(reinterpret_cast<const CUtensorMap*>(&mp) + 1 + (tid & 31)) : "memory");
            __syncwarp();
            asm volatile("bar.sync 6, 416;" ::: "memory");
            store_warp(sb, mp);
        } else if (warp == 14) {
            const int G = blockIdx.x - 119;
            int sel = 0;
            if (G >= 1 && (tid & 31) == 0) sel = near_page(mp.scr + ((size_t)G << 21) + slot_line(3, 3, 0) * 128, 2);
            __syncwarp();
            asm volatile("bar.sync 7, 416;" ::: "memory");
            get_role(sb, cls, rk);
            if (G >= 1 && (tid & 31) == 0) asm volatile("red.relaxed.gpu.global.add.u32 [%0], %1;" :: "l"(&g_cnt[CNT_REL * 32]), "r"(0x10000u | (uint32_t)(sel ^ cls) << G) : "memory");
            __syncwarp();
            load3_warp(cls, rk, sb, mp);
        } else {
            if ((tid & 31) == 0) find_role(sb, mp.scr);
            __syncwarp();
            asm volatile("bar.sync 8, 416;" ::: "memory");
            e_arrive(sb + BARS + 8 * B_ROLE);
            get_role(sb, cls, rk);
            signal_warp(cls, rk, sb, mp.scr);
        }
    } else {
        if (tid >= 32 && tid < NBAR) bar_init(tid);
        {
            const int r = tid % 40;
            asm volatile("st.shared.u32 [%0], %1;" :: "r"(sb + TBL + 4 * tid), "r"(cos_bits(r) | (cos_bits(r < 30 ? r + 10 : r - 30) << 16)) : "memory");
        }
        __syncwarp();
        asm volatile("bar.sync 4, 416;" ::: "memory");
        asm volatile("bar.arrive 5, 416;" ::: "memory");
        asm volatile("bar.arrive 6, 416;" ::: "memory");
        asm volatile("bar.arrive 7, 416;" ::: "memory");
        asm volatile("bar.arrive 8, 416;" ::: "memory");
        if (tid == 64) PROF(121);
        asm volatile("setmaxnreg.inc.sync.aligned.u32 160;");
        task_w(wg, blockIdx.x, sb);
        get_role(sb, cls, rk);
        const int id = wg * NH + rk;
        PROFW(8 + wg * 8);
        if (id < 192) task_p1(wg, id / 3, sb);
        e_arrive(sb + BARS + 8 * B_P1D);
        PROFW(8 + wg * 8 + 3);
        task_p2(wg, rk, sb);
        if (id < 192) task_p3(wg, id / 3, sb);
        PROFW(64 + wg * 8 + 3);
    }
}

typedef CUresult (*EncodeFn)(CUtensorMap*, CUtensorMapDataType, cuuint32_t, void*, const cuuint64_t*, const cuuint64_t*, const cuuint32_t*, const cuuint32_t*,
                             CUtensorMapInterleave, CUtensorMapSwizzle, CUtensorMapL2promotion, CUtensorMapFloatOOBfill);

static void encode3(EncodeFn fn, CUtensorMap* m, void* ptr, uint64_t d0, uint64_t d1, uint64_t d2, uint64_t s1, uint64_t s2,
                    uint32_t b0, uint32_t b1, uint32_t b2, CUtensorMapSwizzle sw) {
    cuuint64_t dims[3] = {d0, d1, d2}, strides[2] = {s1, s2};
    cuuint32_t box[3] = {b0, b1, b2}, es[3] = {1, 1, 1};
    fn(m, CU_TENSOR_MAP_DATA_TYPE_BFLOAT16, 3, ptr, dims, strides, box, es, CU_TENSOR_MAP_INTERLEAVE_NONE, sw,
       CU_TENSOR_MAP_L2_PROMOTION_NONE, CU_TENSOR_MAP_FLOAT_OOB_FILL_NONE);
}

extern "C" void kernel_launch(void* const* d_in, const int* in_sizes, int n_in, void* d_out, int out_size) {
    (void)in_sizes; (void)n_in; (void)out_size;
    void* fnp = nullptr; cudaDriverEntryPointQueryResult qr;
    cudaGetDriverEntryPoint("cuTensorMapEncodeTiled", &fnp, cudaEnableDefault, &qr);
    EncodeFn fn = (EncodeFn)fnp;
    void* xf = nullptr; cudaGetSymbolAddress(&xf, g_scr);
    xf = (void*)(((uintptr_t)xf + (1u << 21) - 1) & ~(uintptr_t)((1u << 21) - 1));
    void* wf = nullptr; cudaGetSymbolAddress(&wf, g_wf);
    Maps mp;
    mp.scr = (char*)xf;
    {
        cuuint32_t b16[5] = {64, 4, 2, 2, 2}, b8[5] = {64, 4, 2, 1, 2}, es[5] = {1, 1, 1, 1, 1};
        cuuint64_t d[5] = {64, 4, 2, 2, 13 << 14}, st[4] = {16384, 262144, 1048576, 128};
        fn(&mp.f16, CU_TENSOR_MAP_DATA_TYPE_BFLOAT16, 5, xf, d, st, b16, es, CU_TENSOR_MAP_INTERLEAVE_NONE, CU_TENSOR_MAP_SWIZZLE_NONE, CU_TENSOR_MAP_L2_PROMOTION_NONE, CU_TENSOR_MAP_FLOAT_OOB_FILL_NONE);
        fn(&mp.f8, CU_TENSOR_MAP_DATA_TYPE_BFLOAT16, 5, xf, d, st, b8, es, CU_TENSOR_MAP_INTERLEAVE_NONE, CU_TENSOR_MAP_SWIZZLE_NONE, CU_TENSOR_MAP_L2_PROMOTION_NONE, CU_TENSOR_MAP_FLOAT_OOB_FILL_NONE);
    }
    encode3(fn, &mp.x6, d_in[0], 96, 224, 224, 192, 224 * 192, 32, 4, 6, CU_TENSOR_MAP_SWIZZLE_64B);
    encode3(fn, &mp.x34, d_in[0], 96, 224, 224, 192, 224 * 192, 32, 4, 34, CU_TENSOR_MAP_SWIZZLE_64B);
    encode3(fn, &mp.x28, d_in[0], 96, 224, 224, 192, 224 * 192, 32, 4, 28, CU_TENSOR_MAP_SWIZZLE_64B);
    encode3(fn, &mp.w, d_in[1], 96, 49, 96, 18432, 192, 32, 56, 2, CU_TENSOR_MAP_SWIZZLE_64B);
    encode3(fn, &mp.wst, wf, 256, 200, 72, 36864, 512, 256, 8, 1, CU_TENSOR_MAP_SWIZZLE_NONE);
    encode3(fn, &mp.y4, d_out, 96, 224, 224, 192, 224 * 192, 32, 4, 28, CU_TENSOR_MAP_SWIZZLE_64B);
    encode3(fn, &mp.y2, d_out, 96, 224, 224, 192, 224 * 192, 32, 2, 28, CU_TENSOR_MAP_SWIZZLE_64B);
    cudaFuncSetAttribute(fftconv_kernel, cudaFuncAttributeMaxDynamicSharedMemorySize, SMEM_BYTES);
    fftconv_kernel<<<NSM, 512, SMEM_BYTES>>>(mp);
}
```

```cpp
#include <cuda_runtime.h>
#include <cuda_bf16.h>
#include <cuda.h>
#include <stdint.h>

__device__ __align__(128) const uint32_t TAB_P1[4480] = {
0x3e75,0,0x3e72,0,0x8000,0,0xbd19,0,0x3e750000,0,0x3e720000,0,0x80000000,0,0xbd190000,0,
0,0x3e75,0,0x3e72,0,0x8000,0,0xbd19,0,0x3e750000,0,0x3e720000,0,0x80000000,0,0xbd190000,
0x3e69,0,0x3e5a,0,0xbd97,0,0xbdde,0,0x3e690000,0,0x3e5a0000,0,0xbd970000,0,0xbdde0000,0,
0,0x3e69,0,0x3e5a,0,0xbd97,0,0xbdde,0,0x3e690000,0,0x3e5a0000,0,0xbd970000,0,0xbdde0000,
0x3e75,0,0x3e5a,0,0x8000,0,0xbdde,0,0x3e750000,0,0x3e5a0000,0,0x80000000,0,0xbdde0000,0,
0,0x3e75,0,0x3e5a,0,0x8000,0,0xbdde,0,0x3e750000,0,0x3e5a0000,0,0x80000000,0,0xbdde0000,
0x3e10,0,0x3d19,0,0xbe46,0,0xbe72,0,0x3e100000,0,0x3d190000,0,0xbe460000,0,0xbe720000,0,
0,0x3e10,0,0x3d19,0,0xbe46,0,0xbe72,0,0x3e100000,0,0x3d190000,0,0xbe460000,0,0xbe720000,
0x3e75,0,0x3e2d,0,0x8000,0,0xbe2d,0,0x3e750000,0,0x3e2d0000,0,0x80000000,0,0xbe2d0000,0,
0,0x3e75,0,0x3e2d,0,0x8000,0,0xbe2d,0,0x3e750000,0,0x3e2d0000,0,0x80000000,0,0xbe2d0000,
0,0,0xbe2d,0,0xbe75,0,0xbe2d,0,0,0,0xbe2d0000,0,0xbe750000,0,0xbe2d0000,0,
0,0,0,0xbe2d,0,0xbe75,0,0xbe2d,0,0,0,0xbe2d0000,0,0xbe750000,0,0xbe2d0000,
0x3e75,0,0x3dde,0,0x8000,0,0xbe5a,0,0x3e750000,0,0x3dde0000,0,0x80000000,0,0xbe5a0000,0,
0,0x3e75,0,0x3dde,0,0x8000,0,0xbe5a,0,0x3e750000,0,0x3dde0000,0,0x80000000,0,0xbe5a0000,
0xbe10,0,0xbe72,0,0xbe46,0,0x3d19,0,0xbe100000,0,0xbe720000,0,0xbe460000,0,0x3d190000,0,
0,0xbe10,0,0xbe72,0,0xbe46,0,0x3d19,0,0xbe100000,0,0xbe720000,0,0xbe460000,0,0x3d190000,
0x3e75,0,0x3d19,0,0x8000,0,0xbe72,0,0x3e750000,0,0x3d190000,0,0x80000000,0,0xbe720000,0,
0,0x3e75,0,0x3d19,0,0x8000,0,0xbe72,0,0x3e750000,0,0x3d190000,0,0x80000000,0,0xbe720000,
0xbe69,0,0xbdde,0,0xbd97,0,0x3e5a,0,0xbe690000,0,0xbdde0000,0,0xbd970000,0,0x3e5a0000,0,
0,0xbe69,0,0xbdde,0,0xbd97,0,0x3e5a,0,0xbe690000,0,0xbdde0000,0,0xbd970000,0,0x3e5a0000,
0x3e75,0,0xbd19,0,0x8000,0,0xbe72,0,0x3e750000,0,0xbd190000,0,0x80000000,0,0xbe720000,0,
0,0x3e75,0,0xbd19,0,0x8000,0,0xbe72,0,0x3e750000,0,0xbd190000,0,0x80000000,0,0xbe720000,
0xbe69,0,0x3dde,0,0x3d97,0,0x3e5a,0,0xbe690000,0,0x3dde0000,0,0x3d970000,0,0x3e5a0000,0,
0,0xbe69,0,0x3dde,0,0x3d97,0,0x3e5a,0,0xbe690000,0,0x3dde0000,0,0x3d970000,0,0x3e5a0000,
0x3e75,0,0xbdde,0,0x8000,0,0xbe5a,0,0x3e750000,0,0xbdde0000,0,0x80000000,0,0xbe5a0000,0,
0,0x3e75,0,0xbdde,0,0x8000,0,0xbe5a,0,0x3e750000,0,0xbdde0000,0,0x80000000,0,0xbe5a0000,
0xbe10,0,0x3e72,0,0x3e46,0,0x3d19,0,0xbe100000,0,0x3e720000,0,0x3e460000,0,0x3d190000,0,
0,0xbe10,0,0x3e72,0,0x3e46,0,0x3d19,0,0xbe100000,0,0x3e720000,0,0x3e460000,0,0x3d190000,
0x3e75,0,0xbe2d,0,0x8000,0,0xbe2d,0,0x3e750000,0,0xbe2d0000,0,0x80000000,0,0xbe2d0000,0,
0,0x3e75,0,0xbe2d,0,0x8000,0,0xbe2d,0,0x3e750000,0,0xbe2d0000,0,0x80000000,0,0xbe2d0000,
0,0,0x3e2d,0,0x3e75,0,0xbe2d,0,0,0,0x3e2d0000,0,0x3e750000,0,0xbe2d0000,0,
0,0,0,0x3e2d,0,0x3e75,0,0xbe2d,0,0,0,0x3e2d0000,0,0x3e750000,0,0xbe2d0000,
0x3e75,0,0xbe5a,0,0x8000,0,0xbdde,0,0x3e750000,0,0xbe5a0000,0,0x80000000,0,0xbdde0000,0,
0,0x3e75,0,0xbe5a,0,0x8000,0,0xbdde,0,0x3e750000,0,0xbe5a0000,0,0x80000000,0,0xbdde0000,
0x3e10,0,0xbd19,0,0x3e46,0,0xbe72,0,0x3e100000,0,0xbd190000,0,0x3e460000,0,0xbe720000,0,
0,0x3e10,0,0xbd19,0,0x3e46,0,0xbe72,0,0x3e100000,0,0xbd190000,0,0x3e460000,0,0xbe720000,
0x3e75,0,0xbe72,0,0x8000,0,0xbd19,0,0x3e750000,0,0xbe720000,0,0x80000000,0,0xbd190000,0,
0,0x3e75,0,0xbe72,0,0x8000,0,0xbd19,0,0x3e750000,0,0xbe720000,0,0x80000000,0,0xbd190000,
0x3e69,0,0xbe5a,0,0x3d97,0,0xbdde,0,0x3e690000,0,0xbe5a0000,0,0x3d970000,0,0xbdde0000,0,
0,0x3e69,0,0xbe5a,0,0x3d97,0,0xbdde,0,0x3e690000,0,0xbe5a0000,0,0x3d970000,0,0xbdde0000,
0x3e46,0,0x3e2d,0,0xbe10,0,0xbe2d,0,0x3e460000,0,0x3e2d0000,0,0xbe100000,0,0xbe2d0000,0,
0,0x3e46,0,0x3e2d,0,0xbe10,0,0xbe2d,0,0x3e460000,0,0x3e2d0000,0,0xbe100000,0,0xbe2d0000,
0x3e10,0,0x3dde,0,0xbe46,0,0xbe5a,0,0x3e100000,0,0x3dde0000,0,0xbe460000,0,0xbe5a0000,0,
0,0x3e10,0,0x3dde,0,0xbe46,0,0xbe5a,0,0x3e100000,0,0x3dde0000,0,0xbe460000,0,0xbe5a0000,
0xbd97,0,0xbe2d,0,0xbe69,0,0xbe2d,0,0xbd970000,0,0xbe2d0000,0,0xbe690000,0,0xbe2d0000,0,
0,0xbd97,0,0xbe2d,0,0xbe69,0,0xbe2d,0,0xbd970000,0,0xbe2d0000,0,0xbe690000,0,0xbe2d0000,
0xbe69,0,0xbe72,0,0xbd97,0,0x3d19,0,0xbe690000,0,0xbe720000,0,0xbd970000,0,0x3d190000,0,
0,0xbe69,0,0xbe72,0,0xbd97,0,0x3d19,0,0xbe690000,0,0xbe720000,0,0xbd970000,0,0x3d190000,
0xbe75,0,0xbe2d,0,0x8000,0,0x3e2d,0,0xbe750000,0,0xbe2d0000,0,0x80000000,0,0x3e2d0000,0,
0,0xbe75,0,0xbe2d,0,0x8000,0,0x3e2d,0,0xbe750000,0,0xbe2d0000,0,0x80000000,0,0x3e2d0000,
0,0,0x3e2d,0,0x3e75,0,0x3e2d,0,0,0,0x3e2d0000,0,0x3e750000,0,0x3e2d0000,0,
0,0,0,0x3e2d,0,0x3e75,0,0x3e2d,0,0,0,0x3e2d0000,0,0x3e750000,0,0x3e2d0000,
0xbd97,0,0x3e2d,0,0x3e69,0,0x3e2d,0,0xbd970000,0,0x3e2d0000,0,0x3e690000,0,0x3e2d0000,0,
0,0xbd97,0,0x3e2d,0,0x3e69,0,0x3e2d,0,0xbd970000,0,0x3e2d0000,0,0x3e690000,0,0x3e2d0000,
0x3e69,0,0x3d19,0,0xbd97,0,0xbe72,0,0x3e690000,0,0x3d190000,0,0xbd970000,0,0xbe720000,0,
0,0x3e69,0,0x3d19,0,0xbd97,0,0xbe72,0,0x3e690000,0,0x3d190000,0,0xbd970000,0,0xbe720000,
0x3e46,0,0x3e2d,0,0x3e10,0,0xbe2d,0,0x3e460000,0,0x3e2d0000,0,0x3e100000,0,0xbe2d0000,0,
0,0x3e46,0,0x3e2d,0,0x3e10,0,0xbe2d,0,0x3e460000,0,0x3e2d0000,0,0x3e100000,0,0xbe2d0000,
0xbe10,0,0xbe5a,0,0xbe46,0,0x3dde,0,0xbe100000,0,0xbe5a0000,0,0xbe460000,0,0x3dde0000,0,
0,0xbe10,0,0xbe5a,0,0xbe46,0,0x3dde,0,0xbe100000,0,0xbe5a0000,0,0xbe460000,0,0x3dde0000,
0x3e46,0,0xbe2d,0,0xbe10,0,0xbe2d,0,0x3e460000,0,0xbe2d0000,0,0xbe100000,0,0xbe2d0000,0,
0,0x3e46,0,0xbe2d,0,0xbe10,0,0xbe2d,0,0x3e460000,0,0xbe2d0000,0,0xbe100000,0,0xbe2d0000,
0xbe10,0,0x3e5a,0,0x3e46,0,0x3dde,0,0xbe100000,0,0x3e5a0000,0,0x3e460000,0,0x3dde0000,0,
0,0xbe10,0,0x3e5a,0,0x3e46,0,0x3dde,0,0xbe100000,0,0x3e5a0000,0,0x3e460000,0,0x3dde0000,
0xbd97,0,0xbe2d,0,0xbe69,0,0x3e2d,0,0xbd970000,0,0xbe2d0000,0,0xbe690000,0,0x3e2d0000,0,
0,0xbd97,0,0xbe2d,0,0xbe69,0,0x3e2d,0,0xbd970000,0,0xbe2d0000,0,0xbe690000,0,0x3e2d0000,
0x3e69,0,0xbd19,0,0x3d97,0,0xbe72,0,0x3e690000,0,0xbd190000,0,0x3d970000,0,0xbe720000,0,
0,0x3e69,0,0xbd19,0,0x3d97,0,0xbe72,0,0x3e690000,0,0xbd190000,0,0x3d970000,0,0xbe720000,
0xbe75,0,0x3e2d,0,0x8000,0,0x3e2d,0,0xbe750000,0,0x3e2d0000,0,0x80000000,0,0x3e2d0000,0,
0,0xbe75,0,0x3e2d,0,0x8000,0,0x3e2d,0,0xbe750000,0,0x3e2d0000,0,0x80000000,0,0x3e2d0000,
0,0,0xbe2d,0,0xbe75,0,0x3e2d,0,0,0,0xbe2d0000,0,0xbe750000,0,0x3e2d0000,0,
0,0,0,0xbe2d,0,0xbe75,0,0x3e2d,0,0,0,0xbe2d0000,0,0xbe750000,0,0x3e2d0000,
0xbd97,0,0x3e2d,0,0x3e69,0,0xbe2d,0,0xbd970000,0,0x3e2d0000,0,0x3e690000,0,0xbe2d0000,0,
0,0xbd97,0,0x3e2d,0,0x3e69,0,0xbe2d,0,0xbd970000,0,0x3e2d0000,0,0x3e690000,0,0xbe2d0000,
0xbe69,0,0x3e72,0,0x3d97,0,0x3d19,0,0xbe690000,0,0x3e720000,0,0x3d970000,0,0x3d190000,0,
0,0xbe69,0,0x3e72,0,0x3d97,0,0x3d19,0,0xbe690000,0,0x3e720000,0,0x3d970000,0,0x3d190000,
0x3e46,0,0xbe2d,0,0x3e10,0,0xbe2d,0,0x3e460000,0,0xbe2d0000,0,0x3e100000,0,0xbe2d0000,0,
0,0x3e46,0,0xbe2d,0,0x3e10,0,0xbe2d,0,0x3e460000,0,0xbe2d0000,0,0x3e100000,0,0xbe2d0000,
0x3e10,0,0xbdde,0,0x3e46,0,0xbe5a,0,0x3e100000,0,0xbdde0000,0,0x3e460000,0,0xbe5a0000,0,
0,0x3e10,0,0xbdde,0,0x3e46,0,0xbe5a,0,0x3e100000,0,0xbdde0000,0,0x3e460000,0,0xbe5a0000,
0x3d97,0,0x3d19,0,0xbe69,0,0xbe72,0,0x3d970000,0,0x3d190000,0,0xbe690000,0,0xbe720000,0,
0,0x3d97,0,0x3d19,0,0xbe69,0,0xbe72,0,0x3d970000,0,0x3d190000,0,0xbe690000,0,0xbe720000,
0,0,0xbd19,0,0xbe75,0,0xbe72,0,0,0,0xbd190000,0,0xbe750000,0,0xbe720000,0,
0,0,0,0xbd19,0,0xbe75,0,0xbe72,0,0,0,0xbd190000,0,0xbe750000,0,0xbe720000,
0xbe46,0,0xbdde,0,0x3e10,0,0x3e5a,0,0xbe460000,0,0xbdde0000,0,0x3e100000,0,0x3e5a0000,0,
0,0xbe46,0,0xbdde,0,0x3e10,0,0x3e5a,0,0xbe460000,0,0xbdde0000,0,0x3e100000,0,0x3e5a0000,
0,0,0x3dde,0,0x3e75,0,0x3e5a,0,0,0,0x3dde0000,0,0x3e750000,0,0x3e5a0000,0,
0,0,0,0x3dde,0,0x3e75,0,0x3e5a,0,0,0,0x3dde0000,0,0x3e750000,0,0x3e5a0000,
0x3e75,0,0x3e2d,0,0x8000,0,0xbe2d,0,0x3e750000,0,0x3e2d0000,0,0x80000000,0,0xbe2d0000,0,
0,0x3e75,0,0x3e2d,0,0x8000,0,0xbe2d,0,0x3e750000,0,0x3e2d0000,0,0x80000000,0,0xbe2d0000,
0,0,0xbe2d,0,0xbe75,0,0xbe2d,0,0,0,0xbe2d0000,0,0xbe750000,0,0xbe2d0000,0,
0,0,0,0xbe2d,0,0xbe75,0,0xbe2d,0,0,0,0xbe2d0000,0,0xbe750000,0,0xbe2d0000,
0xbe46,0,0xbe5a,0,0xbe10,0,0x3dde,0,0xbe460000,0,0xbe5a0000,0,0xbe100000,0,0x3dde0000,0,
0,0xbe46,0,0xbe5a,0,0xbe10,0,0x3dde,0,0xbe460000,0,0xbe5a0000,0,0xbe100000,0,0x3dde0000,
0,0,0x3e5a,0,0x3e75,0,0x3dde,0,0,0,0x3e5a0000,0,0x3e750000,0,0x3dde0000,0,
0,0,0,0x3e5a,0,0x3e75,0,0x3dde,0,0,0,0x3e5a0000,0,0x3e750000,0,0x3dde0000,
0x3d97,0,0x3e72,0,0x3e69,0,0xbd19,0,0x3d970000,0,0x3e720000,0,0x3e690000,0,0xbd190000,0,
0,0x3d97,0,0x3e72,0,0x3e69,0,0xbd19,0,0x3d970000,0,0x3e720000,0,0x3e690000,0,0xbd190000,
0,0,0xbe72,0,0xbe75,0,0xbd19,0,0,0,0xbe720000,0,0xbe750000,0,0xbd190000,0,
0,0,0,0xbe72,0,0xbe75,0,0xbd19,0,0,0,0xbe720000,0,0xbe750000,0,0xbd190000,
0x3d97,0,0xbe72,0,0xbe69,0,0xbd19,0,0x3d970000,0,0xbe720000,0,0xbe690000,0,0xbd190000,0,
0,0x3d97,0,0xbe72,0,0xbe69,0,0xbd19,0,0x3d970000,0,0xbe720000,0,0xbe690000,0,0xbd190000,
0,0,0x3e72,0,0x3e75,0,0xbd19,0,0,0,0x3e720000,0,0x3e750000,0,0xbd190000,0,
0,0,0,0x3e72,0,0x3e75,0,0xbd19,0,0,0,0x3e720000,0,0x3e750000,0,0xbd190000,
0xbe46,0,0x3e5a,0,0x3e10,0,0x3dde,0,0xbe460000,0,0x3e5a0000,0,0x3e100000,0,0x3dde0000,0,
0,0xbe46,0,0x3e5a,0,0x3e10,0,0x3dde,0,0xbe460000,0,0x3e5a0000,0,0x3e100000,0,0x3dde0000,
0,0,0xbe5a,0,0xbe75,0,0x3dde,0,0,0,0xbe5a0000,0,0xbe750000,0,0x3dde0000,0,
0,0,0,0xbe5a,0,0xbe75,0,0x3dde,0,0,0,0xbe5a0000,0,0xbe750000,0,0x3dde0000,
0x3e75,0,0xbe2d,0,0x8000,0,0xbe2d,0,0x3e750000,0,0xbe2d0000,0,0x80000000,0,0xbe2d0000,0,
0,0x3e75,0,0xbe2d,0,0x8000,0,0xbe2d,0,0x3e750000,0,0xbe2d0000,0,0x80000000,0,0xbe2d0000,
0,0,0x3e2d,0,0x3e75,0,0xbe2d,0,0,0,0x3e2d0000,0,0x3e750000,0,0xbe2d0000,0,
0,0,0,0x3e2d,0,0x3e75,0,0xbe2d,0,0,0,0x3e2d0000,0,0x3e750000,0,0xbe2d0000,
0xbe46,0,0x3dde,0,0xbe10,0,0x3e5a,0,0xbe460000,0,0x3dde0000,0,0xbe100000,0,0x3e5a0000,0,
0,0xbe46,0,0x3dde,0,0xbe10,0,0x3e5a,0,0xbe460000,0,0x3dde0000,0,0xbe100000,0,0x3e5a0000,
0,0,0xbdde,0,0xbe75,0,0x3e5a,0,0,0,0xbdde0000,0,0xbe750000,0,0x3e5a0000,0,
0,0,0,0xbdde,0,0xbe75,0,0x3e5a,0,0,0,0xbdde0000,0,0xbe750000,0,0x3e5a0000,
0x3d97,0,0xbd19,0,0x3e69,0,0xbe72,0,0x3d970000,0,0xbd190000,0,0x3e690000,0,0xbe720000,0,
0,0x3d97,0,0xbd19,0,0x3e69,0,0xbe72,0,0x3d970000,0,0xbd190000,0,0x3e690000,0,0xbe720000,
0,0,0x3d19,0,0x3e75,0,0xbe72,0,0,0,0x3d190000,0,0x3e750000,0,0xbe720000,0,
0,0,0,0x3d19,0,0x3e75,0,0xbe72,0,0,0,0x3d190000,0,0x3e750000,0,0xbe720000,
0xbd97,0,0xbdde,0,0xbe69,0,0xbe5a,0,0xbd970000,0,0xbdde0000,0,0xbe690000,0,0xbe5a0000,0,
0,0xbd97,0,0xbdde,0,0xbe69,0,0xbe5a,0,0xbd970000,0,0xbdde0000,0,0xbe690000,0,0xbe5a0000,
0xbe10,0,0xbe2d,0,0xbe46,0,0xbe2d,0,0xbe100000,0,0xbe2d0000,0,0xbe460000,0,0xbe2d0000,0,
0,0xbe10,0,0xbe2d,0,0xbe46,0,0xbe2d,0,0xbe100000,0,0xbe2d0000,0,0xbe460000,0,0xbe2d0000,
0x3e46,0,0x3e72,0,0x3e10,0,0x3d19,0,0x3e460000,0,0x3e720000,0,0x3e100000,0,0x3d190000,0,
0,0x3e46,0,0x3e72,0,0x3e10,0,0x3d19,0,0x3e460000,0,0x3e720000,0,0x3e100000,0,0x3d190000,
0x3e69,0,0x3e2d,0,0xbd97,0,0xbe2d,0,0x3e690000,0,0x3e2d0000,0,0xbd970000,0,0xbe2d0000,0,
0,0x3e69,0,0x3e2d,0,0xbd97,0,0xbe2d,0,0x3e690000,0,0x3e2d0000,0,0xbd970000,0,0xbe2d0000,
0xbe75,0,0xbe2d,0,0x8000,0,0x3e2d,0,0xbe750000,0,0xbe2d0000,0,0x80000000,0,0x3e2d0000,0,
0,0xbe75,0,0xbe2d,0,0x8000,0,0x3e2d,0,0xbe750000,0,0xbe2d0000,0,0x80000000,0,0x3e2d0000,
0,0,0x3e2d,0,0x3e75,0,0x3e2d,0,0,0,0x3e2d0000,0,0x3e750000,0,0x3e2d0000,0,
0,0,0,0x3e2d,0,0x3e75,0,0x3e2d,0,0,0,0x3e2d0000,0,0x3e750000,0,0x3e2d0000,
0x3e46,0,0xbd19,0,0xbe10,0,0xbe72,0,0x3e460000,0,0xbd190000,0,0xbe100000,0,0xbe720000,0,
0,0x3e46,0,0xbd19,0,0xbe10,0,0xbe72,0,0x3e460000,0,0xbd190000,0,0xbe100000,0,0xbe720000,
0xbe69,0,0xbe2d,0,0xbd97,0,0x3e2d,0,0xbe690000,0,0xbe2d0000,0,0xbd970000,0,0x3e2d0000,0,
0,0xbe69,0,0xbe2d,0,0xbd97,0,0x3e2d,0,0xbe690000,0,0xbe2d0000,0,0xbd970000,0,0x3e2d0000,
0xbd97,0,0x3e5a,0,0x3e69,0,0x3dde,0,0xbd970000,0,0x3e5a0000,0,0x3e690000,0,0x3dde0000,0,
0,0xbd97,0,0x3e5a,0,0x3e69,0,0x3dde,0,0xbd970000,0,0x3e5a0000,0,0x3e690000,0,0x3dde0000,
0x3e10,0,0xbe2d,0,0xbe46,0,0xbe2d,0,0x3e100000,0,0xbe2d0000,0,0xbe460000,0,0xbe2d0000,0,
0,0x3e10,0,0xbe2d,0,0xbe46,0,0xbe2d,0,0x3e100000,0,0xbe2d0000,0,0xbe460000,0,0xbe2d0000,
0xbd97,0,0xbe5a,0,0xbe69,0,0x3dde,0,0xbd970000,0,0xbe5a0000,0,0xbe690000,0,0x3dde0000,0,
0,0xbd97,0,0xbe5a,0,0xbe69,0,0x3dde,0,0xbd970000,0,0xbe5a0000,0,0xbe690000,0,0x3dde0000,
0x3e10,0,0x3e2d,0,0x3e46,0,0xbe2d,0,0x3e100000,0,0x3e2d0000,0,0x3e460000,0,0xbe2d0000,0,
0,0x3e10,0,0x3e2d,0,0x3e46,0,0xbe2d,0,0x3e100000,0,0x3e2d0000,0,0x3e460000,0,0xbe2d0000,
0x3e46,0,0x3d19,0,0x3e10,0,0xbe72,0,0x3e460000,0,0x3d190000,0,0x3e100000,0,0xbe720000,0,
0,0x3e46,0,0x3d19,0,0x3e10,0,0xbe72,0,0x3e460000,0,0x3d190000,0,0x3e100000,0,0xbe720000,
0xbe69,0,0x3e2d,0,0x3d97,0,0x3e2d,0,0xbe690000,0,0x3e2d0000,0,0x3d970000,0,0x3e2d0000,0,
0,0xbe69,0,0x3e2d,0,0x3d97,0,0x3e2d,0,0xbe690000,0,0x3e2d0000,0,0x3d970000,0,0x3e2d0000,
0xbe75,0,0x3e2d,0,0x8000,0,0x3e2d,0,0xbe750000,0,0x3e2d0000,0,0x80000000,0,0x3e2d0000,0,
0,0xbe75,0,0x3e2d,0,0x8000,0,0x3e2d,0,0xbe750000,0,0x3e2d0000,0,0x80000000,0,0x3e2d0000,
0,0,0xbe2d,0,0xbe75,0,0x3e2d,0,0,0,0xbe2d0000,0,0xbe750000,0,0x3e2d0000,0,
0,0,0,0xbe2d,0,0xbe75,0,0x3e2d,0,0,0,0xbe2d0000,0,0xbe750000,0,0x3e2d0000,
0x3e46,0,0xbe72,0,0xbe10,0,0x3d19,0,0x3e460000,0,0xbe720000,0,0xbe100000,0,0x3d190000,0,
0,0x3e46,0,0xbe72,0,0xbe10,0,0x3d19,0,0x3e460000,0,0xbe720000,0,0xbe100000,0,0x3d190000,
0x3e69,0,0xbe2d,0,0x3d97,0,0xbe2d,0,0x3e690000,0,0xbe2d0000,0,0x3d970000,0,0xbe2d0000,0,
0,0x3e69,0,0xbe2d,0,0x3d97,0,0xbe2d,0,0x3e690000,0,0xbe2d0000,0,0x3d970000,0,0xbe2d0000,
0xbd97,0,0x3dde,0,0x3e69,0,0xbe5a,0,0xbd970000,0,0x3dde0000,0,0x3e690000,0,0xbe5a0000,0,
0,0xbd97,0,0x3dde,0,0x3e69,0,0xbe5a,0,0xbd970000,0,0x3dde0000,0,0x3e690000,0,0xbe5a0000,
0xbe10,0,0x3e2d,0,0x3e46,0,0xbe2d,0,0xbe100000,0,0x3e2d0000,0,0x3e460000,0,0xbe2d0000,0,
0,0xbe10,0,0x3e2d,0,0x3e46,0,0xbe2d,0,0xbe100000,0,0x3e2d0000,0,0x3e460000,0,0xbe2d0000,
0xbe46,0,0xbe5a,0,0xbe10,0,0xbdde,0,0xbe460000,0,0xbe5a0000,0,0xbe100000,0,0xbdde0000,0,
0,0xbe46,0,0xbe5a,0,0xbe10,0,0xbdde,0,0xbe460000,0,0xbe5a0000,0,0xbe100000,0,0xbdde0000,
0xbe69,0,0xbe72,0,0xbd97,0,0xbd19,0,0xbe690000,0,0xbe720000,0,0xbd970000,0,0xbd190000,0,
0,0xbe69,0,0xbe72,0,0xbd97,0,0xbd19,0,0xbe690000,0,0xbe720000,0,0xbd970000,0,0xbd190000,
0x3d97,0,0xbd19,0,0xbe69,0,0xbe72,0,0x3d970000,0,0xbd190000,0,0xbe690000,0,0xbe720000,0,
0,0x3d97,0,0xbd19,0,0xbe69,0,0xbe72,0,0x3d970000,0,0xbd190000,0,0xbe690000,0,0xbe720000,
0xbe10,0,0xbe5a,0,0xbe46,0,0xbdde,0,0xbe100000,0,0xbe5a0000,0,0xbe460000,0,0xbdde0000,0,
0,0xbe10,0,0xbe5a,0,0xbe46,0,0xbdde,0,0xbe100000,0,0xbe5a0000,0,0xbe460000,0,0xbdde0000,
0x3e75,0,0x3e2d,0,0x8000,0,0xbe2d,0,0x3e750000,0,0x3e2d0000,0,0x80000000,0,0xbe2d0000,0,
0,0x3e75,0,0x3e2d,0,0x8000,0,0xbe2d,0,0x3e750000,0,0x3e2d0000,0,0x80000000,0,0xbe2d0000,
0,0,0xbe2d,0,0xbe75,0,0xbe2d,0,0,0,0xbe2d0000,0,0xbe750000,0,0xbe2d0000,0,
0,0,0,0xbe2d,0,0xbe75,0,0xbe2d,0,0,0,0xbe2d0000,0,0xbe750000,0,0xbe2d0000,
0x3d97,0,0x3e72,0,0x3e69,0,0x3d19,0,0x3d970000,0,0x3e720000,0,0x3e690000,0,0x3d190000,0,
0,0x3d97,0,0x3e72,0,0x3e69,0,0x3d19,0,0x3d970000,0,0x3e720000,0,0x3e690000,0,0x3d190000,
0x3e10,0,0xbdde,0,0xbe46,0,0xbe5a,0,0x3e100000,0,0xbdde0000,0,0xbe460000,0,0xbe5a0000,0,
0,0x3e10,0,0xbdde,0,0xbe46,0,0xbe5a,0,0x3e100000,0,0xbdde0000,0,0xbe460000,0,0xbe5a0000,
0xbe46,0,0x3dde,0,0x3e10,0,0x3e5a,0,0xbe460000,0,0x3dde0000,0,0x3e100000,0,0x3e5a0000,0,
0,0xbe46,0,0x3dde,0,0x3e10,0,0x3e5a,0,0xbe460000,0,0x3dde0000,0,0x3e100000,0,0x3e5a0000,
0x3e69,0,0xbd19,0,0xbd97,0,0xbe72,0,0x3e690000,0,0xbd190000,0,0xbd970000,0,0xbe720000,0,
0,0x3e69,0,0xbd19,0,0xbd97,0,0xbe72,0,0x3e690000,0,0xbd190000,0,0xbd970000,0,0xbe720000,
0xbe46,0,0xbdde,0,0xbe10,0,0x3e5a,0,0xbe460000,0,0xbdde0000,0,0xbe100000,0,0x3e5a0000,0,
0,0xbe46,0,0xbdde,0,0xbe10,0,0x3e5a,0,0xbe460000,0,0xbdde0000,0,0xbe100000,0,0x3e5a0000,
0x3e69,0,0x3d19,0,0x3d97,0,0xbe72,0,0x3e690000,0,0x3d190000,0,0x3d970000,0,0xbe720000,0,
0,0x3e69,0,0x3d19,0,0x3d97,0,0xbe72,0,0x3e690000,0,0x3d190000,0,0x3d970000,0,0xbe720000,
0x3d97,0,0xbe72,0,0xbe69,0,0x3d19,0,0x3d970000,0,0xbe720000,0,0xbe690000,0,0x3d190000,0,
0,0x3d97,0,0xbe72,0,0xbe69,0,0x3d19,0,0x3d970000,0,0xbe720000,0,0xbe690000,0,0x3d190000,
0x3e10,0,0x3dde,0,0x3e46,0,0xbe5a,0,0x3e100000,0,0x3dde0000,0,0x3e460000,0,0xbe5a0000,0,
0,0x3e10,0,0x3dde,0,0x3e46,0,0xbe5a,0,0x3e100000,0,0x3dde0000,0,0x3e460000,0,0xbe5a0000,
0x3e75,0,0xbe2d,0,0x8000,0,0xbe2d,0,0x3e750000,0,0xbe2d0000,0,0x80000000,0,0xbe2d0000,0,
0,0x3e75,0,0xbe2d,0,0x8000,0,0xbe2d,0,0x3e750000,0,0xbe2d0000,0,0x80000000,0,0xbe2d0000,
0,0,0x3e2d,0,0x3e75,0,0xbe2d,0,0,0,0x3e2d0000,0,0x3e750000,0,0xbe2d0000,0,
0,0,0,0x3e2d,0,0x3e75,0,0xbe2d,0,0,0,0x3e2d0000,0,0x3e750000,0,0xbe2d0000,
0x3d97,0,0x3d19,0,0x3e69,0,0xbe72,0,0x3d970000,0,0x3d190000,0,0x3e690000,0,0xbe720000,0,
0,0x3d97,0,0x3d19,0,0x3e69,0,0xbe72,0,0x3d970000,0,0x3d190000,0,0x3e690000,0,0xbe720000,
0xbe10,0,0x3e5a,0,0x3e46,0,0xbdde,0,0xbe100000,0,0x3e5a0000,0,0x3e460000,0,0xbdde0000,0,
0,0xbe10,0,0x3e5a,0,0x3e46,0,0xbdde,0,0xbe100000,0,0x3e5a0000,0,0x3e460000,0,0xbdde0000,
0xbe46,0,0x3e5a,0,0x3e10,0,0xbdde,0,0xbe460000,0,0x3e5a0000,0,0x3e100000,0,0xbdde0000,0,
0,0xbe46,0,0x3e5a,0,0x3e10,0,0xbdde,0,0xbe460000,0,0x3e5a0000,0,0x3e100000,0,0xbdde0000,
0xbe69,0,0x3e72,0,0x3d97,0,0xbd19,0,0xbe690000,0,0x3e720000,0,0x3d970000,0,0xbd190000,0,
0,0xbe69,0,0x3e72,0,0x3d97,0,0xbd19,0,0xbe690000,0,0x3e720000,0,0x3d970000,0,0xbd190000,
0x3eb7,0x3eb7,0x3eb7,0x3eb7,0x3eb78000,0x3eb78000,0x3eb78000,0x3eb78000,0x3eb7,0x3de23eae,0x3e573e94,0x3e943e57,0x3eb78000,0x3eaebde2,0x3e94be57,0x3e57be94,
0x3eb7,0x3e573e94,0x3eae3de2,0x3eaebde2,0x3eb78000,0x3e94be57,0x3de2beae,0xbde2beae,0x3eb7,0x3e943e57,0x3eaebde2,0x3de2beae,0x3eb78000,0x3e57be94,0xbde2beae,0xbeaebde2,
0x3eb7,0x3eb7,0x3eb7,0x3eb7,0x3eb78000,0x3eb78000,0x3eb78000,0x3eb78000,0x3eae3de2,0x3eb70000,0x3eaebde2,0x3e94be57,0x3de2beae,0xbeb7,0xbde2beae,0xbe57be94,
0x3e57be94,0xbeb7,0xbe57be94,0xbeaebde2,0xbe94be57,0xbeb78000,0xbe943e57,0xbde23eae,0xbe57be94,0xbeb70000,0xbe573e94,0x3de23eae,0xbe943e57,0x3eb7,0x3e943e57,0x3eaebde2,
0x3eb7,0x3eae3de2,0x3e57be94,0xbe57be94,0x3eb78000,0x3de2beae,0xbe94be57,0xbe943e57,0x3eb7,0x3eb70000,0xbeb7,0xbeb70000,0x3eb78000,0xbeb7,0xbeb78000,0x3eb7,
0x3eb7,0x3eaebde2,0xbe57be94,0xbe573e94,0x3eb78000,0xbde2beae,0xbe943e57,0x3e943e57,0x3eb7,0x3e94be57,0xbeaebde2,0x3de23eae,0x3eb78000,0xbe57be94,0xbde23eae,0x3eaebde2,
0xbeae3de2,0x3eb7,0x3eae3de2,0x3e57be94,0x3de23eae,0x3eb78000,0x3de2beae,0xbe94be57,0x3eb7,0x3eb70000,0xbeb7,0xbeb70000,0x3eb78000,0xbeb7,0xbeb78000,0x3eb7,
0x3eae3de2,0xbeb7,0xbeae3de2,0x3e573e94,0x3de2beae,0xbeb78000,0x3de23eae,0x3e94be57,0x3e57be94,0xbeb70000,0x3e573e94,0x3de2beae,0xbe94be57,0x3eb7,0x3e94be57,0xbeaebde2,
0x3eb7,0x3e57be94,0xbeae3de2,0x3eae3de2,0x3eb78000,0xbe94be57,0x3de23eae,0x3de2beae,0x3eb7,0x3de2beae,0xbe573e94,0x3e94be57,0x3eb78000,0xbeaebde2,0x3e943e57,0xbe57be94,
0x3eb7,0xbeb7,0x3eb7,0xbeb7,0x3eb78000,0xbeb78000,0x3eb78000,0xbeb78000,0x3eb7,0xbde2beae,0x3e573e94,0xbe94be57,0x3eb78000,0xbeae3de2,0x3e94be57,0xbe573e94,
0xbe57be94,0x3eb7,0x3e57be94,0xbeae3de2,0xbe943e57,0x3eb78000,0xbe94be57,0x3de23eae,0xbeae3de2,0x3eb70000,0xbeaebde2,0x3e943e57,0x3de23eae,0xbeb7,0xbde23eae,0x3e57be94,
0x3eb7,0xbeb7,0x3eb7,0xbeb7,0x3eb78000,0xbeb78000,0x3eb78000,0xbeb78000,0x3eae3de2,0xbeb70000,0x3eaebde2,0xbe943e57,0x3de2beae,0x3eb7,0xbde2beae,0x3e573e94,
0x3eb7,0xbe57be94,0x3eae3de2,0xbeae3de2,0x3eb78000,0xbe943e57,0x3de2beae,0x3de23eae,0x3eb7,0xbe94be57,0x3eaebde2,0xbde23eae,0x3eb78000,0xbe573e94,0xbde2beae,0x3eae3de2,
0x3eb7,0xbeaebde2,0x3e57be94,0x3e573e94,0x3eb78000,0xbde23eae,0xbe94be57,0x3e94be57,0x3eb7,0xbeb70000,0xbeb7,0x3eb70000,0x3eb78000,0x3eb7,0xbeb78000,0xbeb7,
0x3e57be94,0x3eb7,0xbe57be94,0x3eae3de2,0xbe94be57,0x3eb78000,0xbe943e57,0x3de2beae,0xbe57be94,0x3eb70000,0xbe573e94,0xbde2beae,0xbe943e57,0xbeb7,0x3e943e57,0xbeae3de2,
0xbeae3de2,0xbeb7,0x3eae3de2,0xbe573e94,0x3de23eae,0xbeb78000,0x3de2beae,0x3e943e57,0x3eb7,0xbeb70000,0xbeb7,0x3eb70000,0x3eb78000,0x3eb7,0xbeb78000,0xbeb7,
0x3eb7,0xbeae3de2,0xbe57be94,0x3e57be94,0x3eb78000,0x3de23eae,0xbe943e57,0xbe94be57,0x3eb7,0xbe943e57,0xbeaebde2,0xbde2beae,0x3eb78000,0x3e573e94,0xbde23eae,0xbeae3de2,
0x3eb7,0xbe573e94,0xbeae3de2,0xbeaebde2,0x3eb78000,0x3e943e57,0x3de23eae,0xbde23eae,0x3eb7,0xbde23eae,0xbe573e94,0xbe943e57,0x3eb78000,0x3eae3de2,0x3e943e57,0x3e573e94,
0x3eae3de2,0x3eb7,0xbeae3de2,0xbe57be94,0x3de2beae,0x3eb78000,0x3de23eae,0xbe943e57,0x3e57be94,0x3eb70000,0x3e573e94,0xbde23eae,0xbe94be57,0xbeb7,0x3e94be57,0x3eae3de2,
0xbe57be94,0xbeb7,0x3e57be94,0x3eaebde2,0xbe943e57,0xbeb78000,0xbe94be57,0xbde2beae,0xbeae3de2,0xbeb70000,0xbeaebde2,0xbe94be57,0x3de23eae,0x3eb7,0xbde23eae,0xbe573e94,
0x3eb7,0x3eb7,0x3eb7,0x3eb7,0x3eb78000,0x3eb78000,0x3eb78000,0x3eb78000,0x3e57be94,0x3de2beae,0xbeb7,0xbde2beae,0xbe94be57,0xbeaebde2,0xbeb78000,0xbeae3de2,
0xbeae3de2,0xbe573e94,0x3eb7,0x3e573e94,0x3de23eae,0x3e943e57,0x3eb78000,0x3e94be57,0x3eae3de2,0x3e94be57,0xbeb7,0xbe94be57,0x3de2beae,0xbe57be94,0xbeb78000,0xbe573e94,
0x3eb7,0x3eb7,0x3eb7,0x3eb7,0x3eb78000,0x3eb78000,0x3eb78000,0x3eb78000,0xbe57be94,0xbe94be57,0xbeaebde2,0xbeb70000,0xbe943e57,0xbe573e94,0xbde23eae,0x3eb7,
0x3eae3de2,0x3eaebde2,0x3e57be94,0xbeb7,0x3de2beae,0xbde2beae,0xbe94be57,0xbeb78000,0xbeae3de2,0xbde23eae,0x3e573e94,0x3eb70000,0x3de23eae,0x3eae3de2,0x3e94be57,0xbeb7,
0xbe57be94,0xbeae3de2,0x3eb7,0x3eae3de2,0xbe943e57,0x3de23eae,0x3eb78000,0x3de2beae,0x3eb7,0x3eb70000,0xbeb7,0xbeb70000,0x3eb78000,0xbeb7,0xbeb78000,0x3eb7,
0x3e57be94,0xbeaebde2,0x3eb7,0x3eaebde2,0xbe94be57,0xbde23eae,0x3eb78000,0xbde2beae,0xbeae3de2,0x3e943e57,0xbeb7,0xbe943e57,0x3de23eae,0x3e57be94,0xbeb78000,0x3e573e94,
0x3e57be94,0xbe57be94,0xbeae3de2,0x3eb7,0xbe94be57,0xbe943e57,0x3de23eae,0x3eb78000,0x3eb7,0x3eb70000,0xbeb7,0xbeb70000,0x3eb78000,0xbeb7,0xbeb78000,0x3eb7,
0xbe57be94,0xbe573e94,0x3eae3de2,0xbeb7,0xbe943e57,0x3e943e57,0x3de2beae,0xbeb78000,0x3eae3de2,0xbde2beae,0xbe573e94,0x3eb70000,0x3de2beae,0xbeae3de2,0x3e943e57,0xbeb7,
0x3eae3de2,0xbe57be94,0x3eb7,0x3e57be94,0x3de2beae,0xbe943e57,0x3eb78000,0xbe94be57,0xbe57be94,0x3de23eae,0xbeb7,0xbde23eae,0xbe943e57,0x3eaebde2,0xbeb78000,0x3eae3de2,
0x3eb7,0xbeb7,0x3eb7,0xbeb7,0x3eb78000,0xbeb78000,0x3eb78000,0xbeb78000,0x3e57be94,0xbde23eae,0xbeb7,0x3de23eae,0xbe94be57,0x3eae3de2,0xbeb78000,0x3eaebde2,
0xbeae3de2,0x3eae3de2,0xbe57be94,0x3eb7,0x3de23eae,0x3de2beae,0xbe943e57,0x3eb78000,0x3e57be94,0xbe943e57,0x3eaebde2,0xbeb70000,0xbe94be57,0x3e573e94,0xbde2beae,0x3eb7,
0x3eb7,0xbeb7,0x3eb7,0xbeb7,0x3eb78000,0xbeb78000,0x3eb78000,0xbeb78000,0xbe57be94,0x3e943e57,0xbeaebde2,0x3eb70000,0xbe943e57,0x3e57be94,0xbde23eae,0xbeb7,
0xbeae3de2,0x3e57be94,0x3eb7,0xbe57be94,0x3de23eae,0xbe94be57,0x3eb78000,0xbe943e57,0x3eae3de2,0xbe943e57,0xbeb7,0x3e943e57,0x3de2beae,0x3e573e94,0xbeb78000,0x3e57be94,
0xbe57be94,0x3eaebde2,0x3eb7,0xbeaebde2,0xbe943e57,0xbde2beae,0x3eb78000,0xbde23eae,0x3eb7,0xbeb70000,0xbeb7,0x3eb70000,0x3eb78000,0x3eb7,0xbeb78000,0xbeb7,
0x3eae3de2,0xbeae3de2,0x3e57be94,0x3eb7,0x3de2beae,0x3de23eae,0xbe94be57,0x3eb78000,0xbeae3de2,0x3de2beae,0x3e573e94,0xbeb70000,0x3de23eae,0xbeaebde2,0x3e94be57,0x3eb7,
0x3e57be94,0x3e573e94,0xbeae3de2,0xbeb7,0xbe94be57,0x3e94be57,0x3de23eae,0xbeb78000,0x3eb7,0xbeb70000,0xbeb7,0x3eb70000,0x3eb78000,0x3eb7,0xbeb78000,0xbeb7,
0x3e57be94,0x3eae3de2,0x3eb7,0xbeae3de2,0xbe94be57,0x3de2beae,0x3eb78000,0x3de23eae,0xbeae3de2,0xbe94be57,0xbeb7,0x3e94be57,0x3de23eae,0xbe573e94,0xbeb78000,0xbe57be94,
0x3eae3de2,0x3e573e94,0x3eb7,0xbe573e94,0x3de2beae,0x3e94be57,0x3eb78000,0x3e943e57,0xbe57be94,0xbde2beae,0xbeb7,0x3de2beae,0xbe943e57,0xbeae3de2,0xbeb78000,0xbeaebde2,
0xbe57be94,0x3e57be94,0x3eae3de2,0x3eb7,0xbe943e57,0xbe94be57,0x3de2beae,0x3eb78000,0x3eae3de2,0x3de23eae,0xbe573e94,0xbeb70000,0x3de2beae,0x3eaebde2,0x3e943e57,0x3eb7,
0xbeae3de2,0xbeaebde2,0xbe57be94,0xbeb7,0x3de23eae,0xbde23eae,0xbe943e57,0xbeb78000,0x3e57be94,0x3e94be57,0x3eaebde2,0x3eb70000,0xbe94be57,0xbe57be94,0xbde2beae,0xbeb7,
0x3eb7,0x3eb7,0x3eb7,0x3eb7,0x3eb78000,0x3eb78000,0x3eb78000,0x3eb78000,0xbeae3de2,0xbe943e57,0xbe573e94,0xbde23eae,0x3de23eae,0x3e573e94,0x3e943e57,0x3eae3de2,
0xbe57be94,0xbeaebde2,0xbeae3de2,0xbe573e94,0xbe943e57,0xbde23eae,0x3de23eae,0x3e943e57,0x3e57be94,0xbde2beae,0xbeaebde2,0xbe943e57,0xbe94be57,0xbeae3de2,0xbde23eae,0x3e573e94,
0,0,0,0,0,0,0,0,0,0,0,0,0,0,0,0,
0,0,0,0,0,0,0,0,0,0,0,0,0,0,0,0,
0x3eae3de2,0x3e57be94,0xbe57be94,0xbeae3de2,0x3de2beae,0xbe94be57,0xbe943e57,0x3de23eae,0x3eb7,0x3eb70000,0xbeb7,0xbeb70000,0x3eb78000,0xbeb7,0xbeb78000,0x3eb7,
0xbeae3de2,0x3e573e94,0x3e57be94,0xbeaebde2,0x3de23eae,0x3e94be57,0xbe94be57,0xbde23eae,0xbe57be94,0xbde23eae,0x3eaebde2,0xbe94be57,0xbe943e57,0x3eae3de2,0xbde2beae,0xbe573e94,
0,0,0,0,0,0,0,0,0,0,0,0,0,0,0,0,
0,0,0,0,0,0,0,0,0,0,0,0,0,0,0,0,
0x3e57be94,0xbeae3de2,0x3eae3de2,0xbe57be94,0xbe94be57,0x3de23eae,0x3de2beae,0xbe943e57,0x3eae3de2,0xbe94be57,0x3e573e94,0xbde2beae,0x3de2beae,0xbe573e94,0x3e94be57,0xbeae3de2,
0x3eb7,0xbeb7,0x3eb7,0xbeb7,0x3eb78000,0xbeb78000,0x3eb78000,0xbeb78000,0xbeae3de2,0x3e94be57,0xbe573e94,0x3de2beae,0x3de23eae,0xbe57be94,0x3e943e57,0xbeaebde2,
0,0,0,0,0,0,0,0,0,0,0,0,0,0,0,0,
0,0,0,0,0,0,0,0,0,0,0,0,0,0,0,0,
0xbe57be94,0x3eae3de2,0xbeae3de2,0x3e57be94,0xbe943e57,0x3de2beae,0x3de23eae,0xbe94be57,0x3e57be94,0x3de23eae,0xbeaebde2,0x3e94be57,0xbe94be57,0x3eaebde2,0xbde23eae,0xbe57be94,
0x3eae3de2,0xbe573e94,0xbe57be94,0x3eaebde2,0x3de2beae,0x3e943e57,0xbe943e57,0xbde2beae,0x3eb7,0xbeb70000,0xbeb7,0x3eb70000,0x3eb78000,0x3eb7,0xbeb78000,0xbeb7,
0,0,0,0,0,0,0,0,0,0,0,0,0,0,0,0,
0,0,0,0,0,0,0,0,0,0,0,0,0,0,0,0,
0xbeae3de2,0xbe57be94,0x3e57be94,0x3eae3de2,0x3de23eae,0xbe943e57,0xbe94be57,0x3de2beae,0xbe57be94,0x3de2beae,0x3eaebde2,0x3e943e57,0xbe943e57,0xbeaebde2,0xbde2beae,0x3e57be94,
0x3e57be94,0x3eaebde2,0x3eae3de2,0x3e573e94,0xbe94be57,0xbde2beae,0x3de2beae,0x3e94be57,0x3eae3de2,0x3e943e57,0x3e573e94,0x3de23eae,0x3de2beae,0x3e57be94,0x3e94be57,0x3eaebde2,
0,0,0,0,0,0,0,0,0,0,0,0,0,0,0,0,
0,0,0,0,0,0,0,0,0,0,0,0,0,0,0,0,
0,0,0,0,0,0,0,0,0,0,0,0,0,0,0,0,
0,0,0,0,0,0,0,0,0,0,0,0,0,0,0,0,
0x3eb7,0x3eb7,0x3eb7,0x3eb7,0x3eb78000,0x3eb78000,0x3eb78000,0x3eb78000,0xbeae3de2,0xbe943e57,0xbe573e94,0xbde23eae,0x3de23eae,0x3e573e94,0x3e943e57,0x3eae3de2,
0xbe57be94,0xbeaebde2,0xbeae3de2,0xbe573e94,0xbe943e57,0xbde23eae,0x3de23eae,0x3e943e57,0x3e57be94,0xbde2beae,0xbeaebde2,0xbe943e57,0xbe94be57,0xbeae3de2,0xbde23eae,0x3e573e94,
0,0,0,0,0,0,0,0,0,0,0,0,0,0,0,0,
0,0,0,0,0,0,0,0,0,0,0,0,0,0,0,0,
0x3eae3de2,0x3e57be94,0xbe57be94,0xbeae3de2,0x3de2beae,0xbe94be57,0xbe943e57,0x3de23eae,0x3eb7,0x3eb70000,0xbeb7,0xbeb70000,0x3eb78000,0xbeb7,0xbeb78000,0x3eb7,
0xbeae3de2,0x3e573e94,0x3e57be94,0xbeaebde2,0x3de23eae,0x3e94be57,0xbe94be57,0xbde23eae,0xbe57be94,0xbde23eae,0x3eaebde2,0xbe94be57,0xbe943e57,0x3eae3de2,0xbde2beae,0xbe573e94,
0,0,0,0,0,0,0,0,0,0,0,0,0,0,0,0,
0,0,0,0,0,0,0,0,0,0,0,0,0,0,0,0,
0x3e57be94,0xbeae3de2,0x3eae3de2,0xbe57be94,0xbe94be57,0x3de23eae,0x3de2beae,0xbe943e57,0x3eae3de2,0xbe94be57,0x3e573e94,0xbde2beae,0x3de2beae,0xbe573e94,0x3e94be57,0xbeae3de2,
0x3eb7,0xbeb7,0x3eb7,0xbeb7,0x3eb78000,0xbeb78000,0x3eb78000,0xbeb78000,0xbeae3de2,0x3e94be57,0xbe573e94,0x3de2beae,0x3de23eae,0xbe57be94,0x3e943e57,0xbeaebde2,
0,0,0,0,0,0,0,0,0,0,0,0,0,0,0,0,
0,0,0,0,0,0,0,0,0,0,0,0,0,0,0,0,
0xbe57be94,0x3eae3de2,0xbeae3de2,0x3e57be94,0xbe943e57,0x3de2beae,0x3de23eae,0xbe94be57,0x3e57be94,0x3de23eae,0xbeaebde2,0x3e94be57,0xbe94be57,0x3eaebde2,0xbde23eae,0xbe57be94,
0x3eae3de2,0xbe573e94,0xbe57be94,0x3eaebde2,0x3de2beae,0x3e943e57,0xbe943e57,0xbde2beae,0x3eb7,0xbeb70000,0xbeb7,0x3eb70000,0x3eb78000,0x3eb7,0xbeb78000,0xbeb7,
0,0,0,0,0,0,0,0,0,0,0,0,0,0,0,0,
0,0,0,0,0,0,0,0,0,0,0,0,0,0,0,0,
0xbeae3de2,0xbe57be94,0x3e57be94,0x3eae3de2,0x3de23eae,0xbe943e57,0xbe94be57,0x3de2beae,0xbe57be94,0x3de2beae,0x3eaebde2,0x3e943e57,0xbe943e57,0xbeaebde2,0xbde2beae,0x3e57be94,
0x3e57be94,0x3eaebde2,0x3eae3de2,0x3e573e94,0xbe94be57,0xbde2beae,0x3de2beae,0x3e94be57,0x3eae3de2,0x3e943e57,0x3e573e94,0x3de23eae,0x3de2beae,0x3e57be94,0x3e94be57,0x3eaebde2,
};
__device__ __align__(128) const uint32_t TAB_P3[4288] = {
0,0,0,0,0,0,0,0,0,0,0,0,0,0,0,0,
0x80003e83,0xbe79bda2,0x3e1abe54,0x3e1a3e54,0x3e830000,0xbda23e79,0xbe54be1a,0x3e54be1a,0x80003e83,0xbe54be1a,0x3e79bda2,0xbda23e79,0x3e830000,0xbe1a3e54,0xbda2be79,0x3e793da2,
0,0,0,0,0,0,0,0,0,0,0,0,0,0,0,0,
0xbe793da2,0x8000be83,0x3e793da2,0xbe1a3e54,0x3da23e79,0xbe830000,0x3da2be79,0x3e543e1a,0xbe1abe54,0x3e830000,0xbe1a3e54,0xbda2be79,0xbe543e1a,0xbe83,0x3e543e1a,0xbe793da2,
0x80003e83,0xbe1abe54,0x3e793da2,0xbe793da2,0x3e830000,0xbe543e1a,0x3da2be79,0x3da23e79,0x80003e83,0xbda2be79,0x3e1a3e54,0xbe54be1a,0x3e830000,0xbe793da2,0x3e54be1a,0xbe1a3e54,
0x80003e83,0x8000be83,0x80003e83,0x8000be83,0x3e830000,0xbe830000,0x3e830000,0xbe830000,0x80003e83,0x3da2be79,0xbe1a3e54,0x3e54be1a,0x3e830000,0xbe79bda2,0x3e543e1a,0xbe1abe54,
0x3e1abe54,0x80003e83,0xbe1abe54,0x3e793da2,0xbe54be1a,0x3e830000,0xbe543e1a,0x3da2be79,0x3e793da2,0xbe830000,0x3e79bda2,0xbe543e1a,0x3da2be79,0x3e83,0xbda2be79,0x3e1a3e54,
0x80003e83,0x8000be83,0x80003e83,0x8000be83,0x3e830000,0xbe830000,0x3e830000,0xbe830000,0xbe793da2,0x3e830000,0xbe79bda2,0x3e543e1a,0x3da23e79,0xbe83,0xbda23e79,0x3e1abe54,
0x80003e83,0x3e1abe54,0xbe793da2,0x3e793da2,0x3e830000,0xbe54be1a,0x3da23e79,0x3da2be79,0x80003e83,0x3e54be1a,0xbe79bda2,0x3da23e79,0x3e830000,0xbe1abe54,0xbda23e79,0x3e79bda2,
0x80003e83,0x3e79bda2,0xbe1abe54,0xbe1a3e54,0x3e830000,0xbda2be79,0xbe543e1a,0x3e543e1a,0x80003e83,0x3e830000,0x8000be83,0xbe830000,0x3e830000,0xbe83,0xbe830000,0x3e83,
0xbe1abe54,0x80003e83,0x3e1abe54,0xbe793da2,0xbe543e1a,0x3e830000,0xbe54be1a,0x3da23e79,0x3e1abe54,0xbe830000,0x3e1a3e54,0x3da2be79,0xbe54be1a,0x3e83,0x3e54be1a,0xbe79bda2,
0x3e793da2,0x8000be83,0xbe793da2,0x3e1a3e54,0x3da2be79,0xbe830000,0x3da23e79,0x3e54be1a,0x80003e83,0x3e830000,0x8000be83,0xbe830000,0x3e830000,0xbe83,0xbe830000,0x3e83,
0x80003e83,0x3e793da2,0x3e1abe54,0xbe1abe54,0x3e830000,0x3da2be79,0xbe54be1a,0xbe543e1a,0x80003e83,0x3e543e1a,0x3e79bda2,0x3da2be79,0x3e830000,0x3e1abe54,0xbda2be79,0xbe79bda2,
0x80003e83,0x3e1a3e54,0x3e793da2,0x3e79bda2,0x3e830000,0x3e54be1a,0x3da2be79,0xbda2be79,0x80003e83,0x3da23e79,0x3e1a3e54,0x3e543e1a,0x3e830000,0x3e79bda2,0x3e54be1a,0x3e1abe54,
0xbe793da2,0x80003e83,0x3e793da2,0x3e1abe54,0x3da23e79,0x3e830000,0x3da2be79,0xbe54be1a,0xbe1abe54,0xbe830000,0xbe1a3e54,0x3da23e79,0xbe543e1a,0x3e83,0x3e543e1a,0x3e79bda2,
0x3e1abe54,0x8000be83,0xbe1abe54,0xbe79bda2,0xbe54be1a,0xbe830000,0xbe543e1a,0xbda23e79,0x3e793da2,0x3e830000,0x3e79bda2,0x3e54be1a,0x3da2be79,0xbe83,0xbda2be79,0xbe1abe54,
0,0,0,0,0,0,0,0,0,0,0,0,0,0,0,0,
0,0,0,0,0,0,0,0,0,0,0,0,0,0,0,0,
0,0,0,0,0,0,0,0,0,0,0,0,0,0,0,0,
0xbe1abe54,0x3e79bda2,0x80003e83,0xbe79bda2,0xbe543e1a,0xbda2be79,0x3e830000,0xbda23e79,0x3e793da2,0xbe543e1a,0x8000be83,0x3e543e1a,0x3da2be79,0x3e1a3e54,0xbe830000,0x3e1abe54,
0,0,0,0,0,0,0,0,0,0,0,0,0,0,0,0,
0,0,0,0,0,0,0,0,0,0,0,0,0,0,0,0,
0xbe793da2,0x3e1abe54,0x80003e83,0xbe1abe54,0x3da23e79,0xbe54be1a,0x3e830000,0xbe543e1a,0x3e1abe54,0xbda23e79,0x8000be83,0x3da23e79,0xbe54be1a,0x3e793da2,0xbe830000,0x3e79bda2,
0x80003e83,0x8000be83,0x80003e83,0x8000be83,0x3e830000,0xbe830000,0x3e830000,0xbe830000,0xbe1abe54,0x3da23e79,0x8000be83,0xbda23e79,0xbe543e1a,0x3e79bda2,0xbe830000,0x3e793da2,
0,0,0,0,0,0,0,0,0,0,0,0,0,0,0,0,
0,0,0,0,0,0,0,0,0,0,0,0,0,0,0,0,
0x3e793da2,0xbe1abe54,0x80003e83,0x3e1abe54,0x3da2be79,0xbe543e1a,0x3e830000,0xbe54be1a,0xbe793da2,0x3e543e1a,0x8000be83,0xbe543e1a,0x3da23e79,0x3e1abe54,0xbe830000,0x3e1a3e54,
0x3e1abe54,0xbe79bda2,0x80003e83,0x3e79bda2,0xbe54be1a,0xbda23e79,0x3e830000,0xbda2be79,0x80003e83,0x3e830000,0x8000be83,0xbe830000,0x3e830000,0xbe83,0xbe830000,0x3e83,
0,0,0,0,0,0,0,0,0,0,0,0,0,0,0,0,
0,0,0,0,0,0,0,0,0,0,0,0,0,0,0,0,
0xbe1abe54,0xbe793da2,0x80003e83,0x3e793da2,0xbe543e1a,0x3da23e79,0x3e830000,0x3da2be79,0x3e793da2,0x3e54be1a,0x8000be83,0xbe54be1a,0x3da2be79,0xbe1abe54,0xbe830000,0xbe1a3e54,
0xbe793da2,0xbe1a3e54,0x80003e83,0x3e1a3e54,0x3da23e79,0x3e543e1a,0x3e830000,0x3e54be1a,0x3e1abe54,0x3da2be79,0x8000be83,0xbda2be79,0xbe54be1a,0xbe79bda2,0xbe830000,0xbe793da2,
0,0,0,0,0,0,0,0,0,0,0,0,0,0,0,0,
0x3e1abe54,0x3e1a3e54,0xbe793da2,0x8000be83,0xbe54be1a,0x3e54be1a,0x3da23e79,0xbe830000,0xbe793da2,0x3da2be79,0x3e1a3e54,0xbe830000,0x3da23e79,0xbe79bda2,0x3e54be1a,0x3e83,
0,0,0,0,0,0,0,0,0,0,0,0,0,0,0,0,
0x3e793da2,0xbe1a3e54,0xbe1abe54,0x3e79bda2,0x3da2be79,0x3e543e1a,0xbe543e1a,0xbda2be79,0x3e1abe54,0x3da23e79,0xbe79bda2,0x3e54be1a,0xbe54be1a,0x3e79bda2,0xbda23e79,0xbe1abe54,
0x3e793da2,0xbe793da2,0x3e1abe54,0x80003e83,0x3da2be79,0x3da23e79,0xbe54be1a,0x3e830000,0xbe1abe54,0x3e543e1a,0xbe79bda2,0x3e830000,0xbe543e1a,0x3e1abe54,0xbda23e79,0xbe83,
0x80003e83,0x8000be83,0x80003e83,0x8000be83,0x3e830000,0xbe830000,0x3e830000,0xbe830000,0x3e1abe54,0xbe543e1a,0x3e79bda2,0xbe830000,0xbe54be1a,0x3e1a3e54,0xbda2be79,0x3e83,
0xbe1abe54,0x3e793da2,0xbe793da2,0x3e1abe54,0xbe543e1a,0x3da2be79,0x3da23e79,0xbe54be1a,0xbe793da2,0x3e54be1a,0xbe1a3e54,0x3da2be79,0x3da23e79,0xbe1abe54,0x3e543e1a,0xbe79bda2,
0x80003e83,0x8000be83,0x80003e83,0x8000be83,0x3e830000,0xbe830000,0x3e830000,0xbe830000,0x3e793da2,0xbe54be1a,0x3e1a3e54,0xbda2be79,0x3da2be79,0xbe1a3e54,0x3e54be1a,0xbe793da2,
0xbe793da2,0x3e793da2,0xbe1abe54,0x80003e83,0x3da23e79,0x3da2be79,0xbe543e1a,0x3e830000,0x3e793da2,0xbda2be79,0xbe1a3e54,0x3e830000,0x3da2be79,0xbe793da2,0x3e543e1a,0xbe83,
0xbe1abe54,0xbe1a3e54,0x3e793da2,0x8000be83,0xbe543e1a,0x3e543e1a,0x3da2be79,0xbe830000,0x80003e83,0x3e830000,0x8000be83,0xbe830000,0x3e830000,0xbe83,0xbe830000,0x3e83,
0x3e1abe54,0xbe793da2,0x3e793da2,0xbe1abe54,0xbe54be1a,0x3da23e79,0x3da2be79,0xbe543e1a,0xbe1abe54,0xbda23e79,0x3e79bda2,0xbe54be1a,0xbe543e1a,0x3e793da2,0xbda2be79,0xbe1a3e54,
0xbe793da2,0x3e1a3e54,0x3e1abe54,0xbe79bda2,0x3da23e79,0x3e54be1a,0xbe54be1a,0xbda23e79,0x80003e83,0x3e830000,0x8000be83,0xbe830000,0x3e830000,0xbe83,0xbe830000,0x3e83,
0x3e1abe54,0xbe1abe54,0xbe793da2,0x80003e83,0xbe54be1a,0xbe543e1a,0x3da23e79,0x3e830000,0xbe793da2,0xbda23e79,0x3e1a3e54,0x3e830000,0x3da23e79,0x3e793da2,0x3e54be1a,0xbe83,
0x3e793da2,0x3e79bda2,0x3e1abe54,0x8000be83,0x3da2be79,0xbda2be79,0xbe54be1a,0xbe830000,0xbe1abe54,0xbe54be1a,0xbe79bda2,0xbe830000,0xbe543e1a,0xbe1a3e54,0xbda23e79,0x3e83,
0x3e793da2,0x3e1abe54,0xbe1abe54,0xbe793da2,0x3da2be79,0xbe54be1a,0xbe543e1a,0x3da23e79,0x3e1abe54,0xbda2be79,0xbe79bda2,0xbe543e1a,0xbe54be1a,0xbe793da2,0xbda23e79,0x3e1a3e54,
0xbe1abe54,0xbe79bda2,0xbe793da2,0xbe1a3e54,0xbe543e1a,0xbda23e79,0x3da23e79,0x3e543e1a,0xbe793da2,0xbe543e1a,0xbe1a3e54,0xbda23e79,0x3da23e79,0x3e1a3e54,0x3e543e1a,0x3e793da2,
0xbe163dda,0,0,0,0,0xbe163dda,0,0,0,0,0xbe163dda,0,0,0,0,0xbe163dda,
0xbe253da8,0,0,0,0,0xbe253da8,0,0,0,0,0xbe253da8,0,0,0,0,0xbe253da8,
0xbd65be30,0,0,0,0,0xbd65be30,0,0,0,0,0xbd65be30,0,0,0,0,0xbd65be30,
0x3ce8be37,0,0,0,0,0x3ce8be37,0,0,0,0,0x3ce8be37,0,0,0,0,0x3ce8be37,
0xbe303d65,0,0,0,0,0xbe303d65,0,0,0,0,0xbe303d65,0,0,0,0,0xbe303d65,
0xbe373ce8,0,0,0,0,0xbe373ce8,0,0,0,0,0xbe373ce8,0,0,0,0,0xbe373ce8,
0x3ddabe16,0,0,0,0,0x3ddabe16,0,0,0,0,0x3ddabe16,0,0,0,0,0x3ddabe16,
0x3e25bda8,0,0,0,0,0x3e25bda8,0,0,0,0,0x3e25bda8,0,0,0,0,0x3e25bda8,
0xbe390000,0,0,0,0,0xbe390000,0,0,0,0,0xbe390000,0,0,0,0,0xbe390000,
0xbe37bce8,0,0,0,0,0xbe37bce8,0,0,0,0,0xbe37bce8,0,0,0,0,0xbe37bce8,
0x3e390000,0,0,0,0,0x3e390000,0,0,0,0,0x3e390000,0,0,0,0,0x3e390000,
0x3e253da8,0,0,0,0,0x3e253da8,0,0,0,0,0x3e253da8,0,0,0,0,0x3e253da8,
0xbe30bd65,0,0,0,0,0xbe30bd65,0,0,0,0,0xbe30bd65,0,0,0,0,0xbe30bd65,
0xbe25bda8,0,0,0,0,0xbe25bda8,0,0,0,0,0xbe25bda8,0,0,0,0,0xbe25bda8,
0x3dda3e16,0,0,0,0,0x3dda3e16,0,0,0,0,0x3dda3e16,0,0,0,0,0x3dda3e16,
0x3ce83e37,0,0,0,0,0x3ce83e37,0,0,0,0,0x3ce83e37,0,0,0,0,0x3ce83e37,
0xbe16bdda,0,0,0,0,0xbe16bdda,0,0,0,0,0xbe16bdda,0,0,0,0,0xbe16bdda,
0xbe03be03,0,0,0,0,0xbe03be03,0,0,0,0,0xbe03be03,0,0,0,0,0xbe03be03,
0xbd653e30,0,0,0,0,0xbd653e30,0,0,0,0,0xbd653e30,0,0,0,0,0xbd653e30,
0xbe033e03,0,0,0,0,0xbe033e03,0,0,0,0,0xbe033e03,0,0,0,0,0xbe033e03,
0xbddabe16,0,0,0,0,0xbddabe16,0,0,0,0,0xbddabe16,0,0,0,0,0xbddabe16,
0xbda8be25,0,0,0,0,0xbda8be25,0,0,0,0,0xbda8be25,0,0,0,0,0xbda8be25,
0xbe303d65,0,0,0,0,0xbe303d65,0,0,0,0,0xbe303d65,0,0,0,0,0xbe303d65,
0xbe37bce8,0,0,0,0,0xbe37bce8,0,0,0,0,0xbe37bce8,0,0,0,0,0xbe37bce8,
0xbd65be30,0,0,0,0,0xbd65be30,0,0,0,0,0xbd65be30,0,0,0,0,0xbd65be30,
0xbce8be37,0,0,0,0,0xbce8be37,0,0,0,0,0xbce8be37,0,0,0,0,0xbce8be37,
0xbe16bdda,0,0,0,0,0xbe16bdda,0,0,0,0,0xbe16bdda,0,0,0,0,0xbe16bdda,
0xbda8be25,0,0,0,0,0xbda8be25,0,0,0,0,0xbda8be25,0,0,0,0,0xbda8be25,
0x3e390000,0,0,0,0,0x3e390000,0,0,0,0,0x3e390000,0,0,0,0,0x3e390000,
0x3e033e03,0,0,0,0,0x3e033e03,0,0,0,0,0x3e033e03,0,0,0,0,0x3e033e03,
0xbd653e30,0,0,0,0,0xbd653e30,0,0,0,0,0xbd653e30,0,0,0,0,0xbd653e30,
0xbe373ce8,0,0,0,0,0xbe373ce8,0,0,0,0,0xbe373ce8,0,0,0,0,0xbe373ce8,
0x80003e39,0,0,0,0,0x80003e39,0,0,0,0,0x80003e39,0,0,0,0,0x80003e39,
0xbe033e03,0,0,0,0,0xbe033e03,0,0,0,0,0xbe033e03,0,0,0,0,0xbe033e03,
0xbddabe16,0,0,0,0,0xbddabe16,0,0,0,0,0xbddabe16,0,0,0,0,0xbddabe16,
0x3da8be25,0,0,0,0,0x3da8be25,0,0,0,0,0x3da8be25,0,0,0,0,0x3da8be25,
0xbe390000,0,0,0,0,0xbe390000,0,0,0,0,0xbe390000,0,0,0,0,0xbe390000,
0xbe03be03,0,0,0,0,0xbe03be03,0,0,0,0,0xbe03be03,0,0,0,0,0xbe03be03,
0x3e390000,0,0,0,0,0x3e390000,0,0,0,0,0x3e390000,0,0,0,0,0x3e390000,
0x3da83e25,0,0,0,0,0x3da83e25,0,0,0,0,0x3da83e25,0,0,0,0,0x3da83e25,
0x8000be39,0,0,0,0,0x8000be39,0,0,0,0,0x8000be39,0,0,0,0,0x8000be39,
0x3e03be03,0,0,0,0,0x3e03be03,0,0,0,0,0x3e03be03,0,0,0,0,0x3e03be03,
0xbdda3e16,0,0,0,0,0xbdda3e16,0,0,0,0,0xbdda3e16,0,0,0,0,0xbdda3e16,
0xbe37bce8,0,0,0,0,0xbe37bce8,0,0,0,0,0xbe37bce8,0,0,0,0,0xbe37bce8,
0x3e390000,0,0,0,0,0x3e390000,0,0,0,0,0x3e390000,0,0,0,0,0x3e390000,
0x3e033e03,0,0,0,0,0x3e033e03,0,0,0,0,0x3e033e03,0,0,0,0,0x3e033e03,
0xbd65be30,0,0,0,0,0xbd65be30,0,0,0,0,0xbd65be30,0,0,0,0,0xbd65be30,
0x3e03be03,0,0,0,0,0x3e03be03,0,0,0,0,0x3e03be03,0,0,0,0,0x3e03be03,
0x80003e39,0,0,0,0,0x80003e39,0,0,0,0,0x80003e39,0,0,0,0,0x80003e39,
0xbe033e03,0,0,0,0,0xbe033e03,0,0,0,0,0xbe033e03,0,0,0,0,0xbe033e03,
0x3e303d65,0,0,0,0,0x3e303d65,0,0,0,0,0x3e303d65,0,0,0,0,0x3e303d65,
0x3ce83e37,0,0,0,0,0x3ce83e37,0,0,0,0,0x3ce83e37,0,0,0,0,0x3ce83e37,
0xbe390000,0,0,0,0,0xbe390000,0,0,0,0,0xbe390000,0,0,0,0,0xbe390000,
0xbe03be03,0,0,0,0,0xbe03be03,0,0,0,0,0xbe03be03,0,0,0,0,0xbe03be03,
0xbe163dda,0,0,0,0,0xbe163dda,0,0,0,0,0xbe163dda,0,0,0,0,0xbe163dda,
0xbe25bda8,0,0,0,0,0xbe25bda8,0,0,0,0,0xbe25bda8,0,0,0,0,0xbe25bda8,
0xbe16bdda,0,0,0,0,0xbe16bdda,0,0,0,0,0xbe16bdda,0,0,0,0,0xbe16bdda,
0x3da8be25,0,0,0,0,0x3da8be25,0,0,0,0,0x3da8be25,0,0,0,0,0x3da8be25,
0x3e16bdda,0,0,0,0,0x3e16bdda,0,0,0,0,0x3e16bdda,0,0,0,0,0x3e16bdda,
0x3da83e25,0,0,0,0,0x3da83e25,0,0,0,0,0x3da83e25,0,0,0,0,0x3da83e25,
0x3e303d65,0,0,0,0,0x3e303d65,0,0,0,0,0x3e303d65,0,0,0,0,0x3e303d65,
0xbce83e37,0,0,0,0,0xbce83e37,0,0,0,0,0xbce83e37,0,0,0,0,0xbce83e37,
0xbe303d65,0,0,0,0,0xbe303d65,0,0,0,0,0xbe303d65,0,0,0,0,0xbe303d65,
0xbce8be37,0,0,0,0,0xbce8be37,0,0,0,0,0xbce8be37,0,0,0,0,0xbce8be37,
0xbe390000,0,0,0,0,0xbe390000,0,0,0,0,0xbe390000,0,0,0,0,0xbe390000,
0xbce8be37,0,0,0,0,0xbce8be37,0,0,0,0,0xbce8be37,0,0,0,0,0xbce8be37,
0x3e390000,0,0,0,0,0x3e390000,0,0,0,0,0x3e390000,0,0,0,0,0x3e390000,
0xbce83e37,0,0,0,0,0xbce83e37,0,0,0,0,0xbce83e37,0,0,0,0,0xbce83e37,
0x3e30bd65,0,0,0,0,0x3e30bd65,0,0,0,0,0x3e30bd65,0,0,0,0,0x3e30bd65,
0x3da83e25,0,0,0,0,0x3da83e25,0,0,0,0,0x3da83e25,0,0,0,0,0x3da83e25,
0xbe30bd65,0,0,0,0,0xbe30bd65,0,0,0,0,0xbe30bd65,0,0,0,0,0xbe30bd65,
0x3da8be25,0,0,0,0,0x3da8be25,0,0,0,0,0x3da8be25,0,0,0,0,0x3da8be25,
0xbe163dda,0,0,0,0,0xbe163dda,0,0,0,0,0xbe163dda,0,0,0,0,0xbe163dda,
0xbe03be03,0,0,0,0,0xbe03be03,0,0,0,0,0xbe03be03,0,0,0,0,0xbe03be03,
0x3e163dda,0,0,0,0,0x3e163dda,0,0,0,0,0x3e163dda,0,0,0,0,0x3e163dda,
0xbe033e03,0,0,0,0,0xbe033e03,0,0,0,0,0xbe033e03,0,0,0,0,0xbe033e03,
0x3ddabe16,0,0,0,0,0x3ddabe16,0,0,0,0,0x3ddabe16,0,0,0,0,0x3ddabe16,
0x3e253da8,0,0,0,0,0x3e253da8,0,0,0,0,0x3e253da8,0,0,0,0,0x3e253da8,
0xbddabe16,0,0,0,0,0xbddabe16,0,0,0,0,0xbddabe16,0,0,0,0,0xbddabe16,
0x3e25bda8,0,0,0,0,0x3e25bda8,0,0,0,0,0x3e25bda8,0,0,0,0,0x3e25bda8,
0xbd653e30,0,0,0,0,0xbd653e30,0,0,0,0,0xbd653e30,0,0,0,0,0xbd653e30,
0xbe37bce8,0,0,0,0,0xbe37bce8,0,0,0,0,0xbe37bce8,0,0,0,0,0xbe37bce8,
0x3d653e30,0,0,0,0,0x3d653e30,0,0,0,0,0x3d653e30,0,0,0,0,0x3d653e30,
0xbe373ce8,0,0,0,0,0xbe373ce8,0,0,0,0,0xbe373ce8,0,0,0,0,0xbe373ce8,
0x3d653e30,0,0,0,0,0x3d653e30,0,0,0,0,0x3d653e30,0,0,0,0,0x3d653e30,
0xbe37bce8,0,0,0,0,0xbe37bce8,0,0,0,0,0xbe37bce8,0,0,0,0,0xbe37bce8,
0xbe390000,0,0,0,0,0xbe390000,0,0,0,0,0xbe390000,0,0,0,0,0xbe390000,
0x3e03be03,0,0,0,0,0x3e03be03,0,0,0,0,0x3e03be03,0,0,0,0,0x3e03be03,
0x3ddabe16,0,0,0,0,0x3ddabe16,0,0,0,0,0x3ddabe16,0,0,0,0,0x3ddabe16,
0x3da83e25,0,0,0,0,0x3da83e25,0,0,0,0,0x3da83e25,0,0,0,0,0x3da83e25,
0x80003e39,0,0,0,0,0x80003e39,0,0,0,0,0x80003e39,0,0,0,0,0x80003e39,
0xbe03be03,0,0,0,0,0xbe03be03,0,0,0,0,0xbe03be03,0,0,0,0,0xbe03be03,
0xbe390000,0,0,0,0,0xbe390000,0,0,0,0,0xbe390000,0,0,0,0,0xbe390000,
0x3da8be25,0,0,0,0,0x3da8be25,0,0,0,0,0x3da8be25,0,0,0,0,0x3da8be25,
0x3e390000,0,0,0,0,0x3e390000,0,0,0,0,0x3e390000,0,0,0,0,0x3e390000,
0xbe033e03,0,0,0,0,0xbe033e03,0,0,0,0,0xbe033e03,0,0,0,0,0xbe033e03,
0x3dda3e16,0,0,0,0,0x3dda3e16,0,0,0,0,0x3dda3e16,0,0,0,0,0x3dda3e16,
0xbe373ce8,0,0,0,0,0xbe373ce8,0,0,0,0,0xbe373ce8,0,0,0,0,0xbe373ce8,
0x8000be39,0,0,0,0,0x8000be39,0,0,0,0,0x8000be39,0,0,0,0,0x8000be39,
0x3e033e03,0,0,0,0,0x3e033e03,0,0,0,0,0x3e033e03,0,0,0,0,0x3e033e03,
0x3d65be30,0,0,0,0,0x3d65be30,0,0,0,0,0x3d65be30,0,0,0,0,0x3d65be30,
0x3e033e03,0,0,0,0,0x3e033e03,0,0,0,0,0x3e033e03,0,0,0,0,0x3e033e03,
0xbe390000,0,0,0,0,0xbe390000,0,0,0,0,0xbe390000,0,0,0,0,0xbe390000,
0x3e03be03,0,0,0,0,0x3e03be03,0,0,0,0,0x3e03be03,0,0,0,0,0x3e03be03,
0xbe303d65,0,0,0,0,0xbe303d65,0,0,0,0,0xbe303d65,0,0,0,0,0xbe303d65,
0x3ce8be37,0,0,0,0,0x3ce8be37,0,0,0,0,0x3ce8be37,0,0,0,0,0x3ce8be37,
0x80003e39,0,0,0,0,0x80003e39,0,0,0,0,0x80003e39,0,0,0,0,0x80003e39,
0xbe03be03,0,0,0,0,0xbe03be03,0,0,0,0,0xbe03be03,0,0,0,0,0xbe03be03,
0x3e163dda,0,0,0,0,0x3e163dda,0,0,0,0,0x3e163dda,0,0,0,0,0x3e163dda,
0xbe253da8,0,0,0,0,0xbe253da8,0,0,0,0,0xbe253da8,0,0,0,0,0xbe253da8,
0x3e390000,0,0,0,0,0x3e390000,0,0,0,0,0x3e390000,0,0,0,0,0x3e390000,
0xbe033e03,0,0,0,0,0xbe033e03,0,0,0,0,0xbe033e03,0,0,0,0,0xbe033e03,
0x3d65be30,0,0,0,0,0x3d65be30,0,0,0,0,0x3d65be30,0,0,0,0,0x3d65be30,
0x3ce83e37,0,0,0,0,0x3ce83e37,0,0,0,0,0x3ce83e37,0,0,0,0,0x3ce83e37,
0x3e163dda,0,0,0,0,0x3e163dda,0,0,0,0,0x3e163dda,0,0,0,0,0x3e163dda,
0xbe25bda8,0,0,0,0,0xbe25bda8,0,0,0,0,0xbe25bda8,0,0,0,0,0xbe25bda8,
0xbddabe16,0,0,0,0,0xbddabe16,0,0,0,0,0xbddabe16,0,0,0,0,0xbddabe16,
0x3e253da8,0,0,0,0,0x3e253da8,0,0,0,0,0x3e253da8,0,0,0,0,0x3e253da8,
0x3e303d65,0,0,0,0,0x3e303d65,0,0,0,0,0x3e303d65,0,0,0,0,0x3e303d65,
0xbe37bce8,0,0,0,0,0xbe37bce8,0,0,0,0,0xbe37bce8,0,0,0,0,0xbe37bce8,
0xbe390000,0,0,0,0,0xbe390000,0,0,0,0,0xbe390000,0,0,0,0,0xbe390000,
0x3e25bda8,0,0,0,0,0x3e25bda8,0,0,0,0,0x3e25bda8,0,0,0,0,0x3e25bda8,
0x3e390000,0,0,0,0,0x3e390000,0,0,0,0,0x3e390000,0,0,0,0,0x3e390000,
0xbe373ce8,0,0,0,0,0xbe373ce8,0,0,0,0,0xbe373ce8,0,0,0,0,0xbe373ce8,
0xbdda3e16,0,0,0,0,0xbdda3e16,0,0,0,0,0xbdda3e16,0,0,0,0,0xbdda3e16,
0x3ce8be37,0,0,0,0,0x3ce8be37,0,0,0,0,0x3ce8be37,0,0,0,0,0x3ce8be37,
0x3e30bd65,0,0,0,0,0x3e30bd65,0,0,0,0,0x3e30bd65,0,0,0,0,0x3e30bd65,
0xbe253da8,0,0,0,0,0xbe253da8,0,0,0,0,0xbe253da8,0,0,0,0,0xbe253da8,
0x3d653e30,0,0,0,0,0x3d653e30,0,0,0,0,0x3d653e30,0,0,0,0,0x3d653e30,
0xbe03be03,0,0,0,0,0xbe03be03,0,0,0,0,0xbe03be03,0,0,0,0,0xbe03be03,
0x3e16bdda,0,0,0,0,0x3e16bdda,0,0,0,0,0x3e16bdda,0,0,0,0,0x3e16bdda,
0xbe033e03,0,0,0,0,0xbe033e03,0,0,0,0,0xbe033e03,0,0,0,0,0xbe033e03,
0x3e303d65,0,0,0,0,0x3e303d65,0,0,0,0,0x3e303d65,0,0,0,0,0x3e303d65,
0xbe373ce8,0,0,0,0,0xbe373ce8,0,0,0,0,0xbe373ce8,0,0,0,0,0xbe373ce8,
0x3ddabe16,0,0,0,0,0x3ddabe16,0,0,0,0,0x3ddabe16,0,0,0,0,0x3ddabe16,
0xbda83e25,0,0,0,0,0xbda83e25,0,0,0,0,0xbda83e25,0,0,0,0,0xbda83e25,
0x3e16bdda,0,0,0,0,0x3e16bdda,0,0,0,0,0x3e16bdda,0,0,0,0,0x3e16bdda,
0xbda83e25,0,0,0,0,0xbda83e25,0,0,0,0,0xbda83e25,0,0,0,0,0xbda83e25,
0x3d65be30,0,0,0,0,0x3d65be30,0,0,0,0,0x3d65be30,0,0,0,0,0x3d65be30,
0xbce83e37,0,0,0,0,0xbce83e37,0,0,0,0,0xbce83e37,0,0,0,0,0xbce83e37,
0,0,0xbe163dda,0,0,0,0,0xbe163dda,0,0,0xbe253da8,0,0,0,0,0xbe253da8,
0,0,0xbe303d65,0,0,0,0,0xbe303d65,0,0,0xbe373ce8,0,0,0,0,0xbe373ce8,
0,0,0xbd65be30,0,0,0,0,0xbd65be30,0,0,0x3ce8be37,0,0,0,0,0x3ce8be37,
0,0,0x3ddabe16,0,0,0,0,0x3ddabe16,0,0,0x3e25bda8,0,0,0,0,0x3e25bda8,
0,0,0xbe390000,0,0,0,0,0xbe390000,0,0,0xbe37bce8,0,0,0,0,0xbe37bce8,
0,0,0xbe30bd65,0,0,0,0,0xbe30bd65,0,0,0xbe25bda8,0,0,0,0,0xbe25bda8,
0,0,0x3e390000,0,0,0,0,0x3e390000,0,0,0x3e253da8,0,0,0,0,0x3e253da8,
0,0,0x3dda3e16,0,0,0,0,0x3dda3e16,0,0,0x3ce83e37,0,0,0,0,0x3ce83e37,
0,0,0xbe16bdda,0,0,0,0,0xbe16bdda,0,0,0xbe03be03,0,0,0,0,0xbe03be03,
0,0,0xbddabe16,0,0,0,0,0xbddabe16,0,0,0xbda8be25,0,0,0,0,0xbda8be25,
0,0,0xbd653e30,0,0,0,0,0xbd653e30,0,0,0xbe033e03,0,0,0,0,0xbe033e03,
0,0,0xbe303d65,0,0,0,0,0xbe303d65,0,0,0xbe37bce8,0,0,0,0,0xbe37bce8,
0,0,0xbd65be30,0,0,0,0,0xbd65be30,0,0,0xbce8be37,0,0,0,0,0xbce8be37,
0,0,0,0,0,0,0,0,0,0,0,0,0,0,0,0,
0,0,0xbe16bdda,0,0,0,0,0xbe16bdda,0,0,0xbda8be25,0,0,0,0,0xbda8be25,
0,0,0,0,0,0,0,0,0,0,0,0,0,0,0,0,
0,0,0x3e390000,0,0,0,0,0x3e390000,0,0,0x3e033e03,0,0,0,0,0x3e033e03,
0,0,0x80003e39,0,0,0,0,0x80003e39,0,0,0xbe033e03,0,0,0,0,0xbe033e03,
0,0,0xbd653e30,0,0,0,0,0xbd653e30,0,0,0xbe373ce8,0,0,0,0,0xbe373ce8,
0,0,0xbddabe16,0,0,0,0,0xbddabe16,0,0,0x3da8be25,0,0,0,0,0x3da8be25,
0,0,0xbe390000,0,0,0,0,0xbe390000,0,0,0xbe03be03,0,0,0,0,0xbe03be03,
0,0,0x8000be39,0,0,0,0,0x8000be39,0,0,0x3e03be03,0,0,0,0,0x3e03be03,
0,0,0x3e390000,0,0,0,0,0x3e390000,0,0,0x3da83e25,0,0,0,0,0x3da83e25,
0,0,0xbdda3e16,0,0,0,0,0xbdda3e16,0,0,0xbe37bce8,0,0,0,0,0xbe37bce8,
0,0,0x3e390000,0,0,0,0,0x3e390000,0,0,0x3e033e03,0,0,0,0,0x3e033e03,
0,0,0x80003e39,0,0,0,0,0x80003e39,0,0,0xbe033e03,0,0,0,0,0xbe033e03,
0,0,0xbd65be30,0,0,0,0,0xbd65be30,0,0,0x3e03be03,0,0,0,0,0x3e03be03,
0,0,0x3e303d65,0,0,0,0,0x3e303d65,0,0,0x3ce83e37,0,0,0,0,0x3ce83e37,
0,0,0xbe390000,0,0,0,0,0xbe390000,0,0,0xbe03be03,0,0,0,0,0xbe03be03,
0,0,0,0,0,0,0,0,0,0,0,0,0,0,0,0,
0,0,0xbe163dda,0,0,0,0,0xbe163dda,0,0,0xbe25bda8,0,0,0,0,0xbe25bda8,
0,0,0,0,0,0,0,0,0,0,0,0,0,0,0,0,
0,0,0xbe16bdda,0,0,0,0,0xbe16bdda,0,0,0x3da8be25,0,0,0,0,0x3da8be25,
0,0,0x3e303d65,0,0,0,0,0x3e303d65,0,0,0xbce83e37,0,0,0,0,0xbce83e37,
0,0,0x3e16bdda,0,0,0,0,0x3e16bdda,0,0,0x3da83e25,0,0,0,0,0x3da83e25,
0,0,0xbe303d65,0,0,0,0,0xbe303d65,0,0,0xbce8be37,0,0,0,0,0xbce8be37,
0,0,0xbe390000,0,0,0,0,0xbe390000,0,0,0xbce8be37,0,0,0,0,0xbce8be37,
0,0,0x3e30bd65,0,0,0,0,0x3e30bd65,0,0,0x3da83e25,0,0,0,0,0x3da83e25,
0,0,0x3e390000,0,0,0,0,0x3e390000,0,0,0xbce83e37,0,0,0,0,0xbce83e37,
0,0,0xbe30bd65,0,0,0,0,0xbe30bd65,0,0,0x3da8be25,0,0,0,0,0x3da8be25,
0,0,0xbe163dda,0,0,0,0,0xbe163dda,0,0,0xbe03be03,0,0,0,0,0xbe03be03,
0,0,0x3ddabe16,0,0,0,0,0x3ddabe16,0,0,0x3e253da8,0,0,0,0,0x3e253da8,
0,0,0x3e163dda,0,0,0,0,0x3e163dda,0,0,0xbe033e03,0,0,0,0,0xbe033e03,
0,0,0xbddabe16,0,0,0,0,0xbddabe16,0,0,0x3e25bda8,0,0,0,0,0x3e25bda8,
0,0,0xbd653e30,0,0,0,0,0xbd653e30,0,0,0xbe37bce8,0,0,0,0,0xbe37bce8,
0,0,0,0,0,0,0,0,0,0,0,0,0,0,0,0,
0,0,0x3d653e30,0,0,0,0,0x3d653e30,0,0,0xbe373ce8,0,0,0,0,0xbe373ce8,
0,0,0,0,0,0,0,0,0,0,0,0,0,0,0,0,
0,0,0x3d653e30,0,0,0,0,0x3d653e30,0,0,0xbe37bce8,0,0,0,0,0xbe37bce8,
0,0,0x3ddabe16,0,0,0,0,0x3ddabe16,0,0,0x3da83e25,0,0,0,0,0x3da83e25,
0,0,0xbe390000,0,0,0,0,0xbe390000,0,0,0x3e03be03,0,0,0,0,0x3e03be03,
0,0,0x80003e39,0,0,0,0,0x80003e39,0,0,0xbe03be03,0,0,0,0,0xbe03be03,
0,0,0xbe390000,0,0,0,0,0xbe390000,0,0,0x3da8be25,0,0,0,0,0x3da8be25,
0,0,0x3dda3e16,0,0,0,0,0x3dda3e16,0,0,0xbe373ce8,0,0,0,0,0xbe373ce8,
0,0,0x3e390000,0,0,0,0,0x3e390000,0,0,0xbe033e03,0,0,0,0,0xbe033e03,
0,0,0x8000be39,0,0,0,0,0x8000be39,0,0,0x3e033e03,0,0,0,0,0x3e033e03,
0,0,0x3d65be30,0,0,0,0,0x3d65be30,0,0,0x3e033e03,0,0,0,0,0x3e033e03,
0,0,0xbe303d65,0,0,0,0,0xbe303d65,0,0,0x3ce8be37,0,0,0,0,0x3ce8be37,
0,0,0xbe390000,0,0,0,0,0xbe390000,0,0,0x3e03be03,0,0,0,0,0x3e03be03,
0,0,0x80003e39,0,0,0,0,0x80003e39,0,0,0xbe03be03,0,0,0,0,0xbe03be03,
0,0,0x3e163dda,0,0,0,0,0x3e163dda,0,0,0xbe253da8,0,0,0,0,0xbe253da8,
0,0,0,0,0,0,0,0,0,0,0,0,0,0,0,0,
0,0,0x3e390000,0,0,0,0,0x3e390000,0,0,0xbe033e03,0,0,0,0,0xbe033e03,
0,0,0,0,0,0,0,0,0,0,0,0,0,0,0,0,
0,0,0x3d65be30,0,0,0,0,0x3d65be30,0,0,0x3ce83e37,0,0,0,0,0x3ce83e37,
0,0,0xbddabe16,0,0,0,0,0xbddabe16,0,0,0x3e253da8,0,0,0,0,0x3e253da8,
0,0,0x3e163dda,0,0,0,0,0x3e163dda,0,0,0xbe25bda8,0,0,0,0,0xbe25bda8,
0,0,0x3e303d65,0,0,0,0,0x3e303d65,0,0,0xbe37bce8,0,0,0,0,0xbe37bce8,
0,0,0xbe390000,0,0,0,0,0xbe390000,0,0,0x3e25bda8,0,0,0,0,0x3e25bda8,
0,0,0xbdda3e16,0,0,0,0,0xbdda3e16,0,0,0x3ce8be37,0,0,0,0,0x3ce8be37,
0,0,0x3e390000,0,0,0,0,0x3e390000,0,0,0xbe373ce8,0,0,0,0,0xbe373ce8,
0,0,0x3e30bd65,0,0,0,0,0x3e30bd65,0,0,0xbe253da8,0,0,0,0,0xbe253da8,
0,0,0x3d653e30,0,0,0,0,0x3d653e30,0,0,0xbe03be03,0,0,0,0,0xbe03be03,
0,0,0x3e303d65,0,0,0,0,0x3e303d65,0,0,0xbe373ce8,0,0,0,0,0xbe373ce8,
0,0,0x3e16bdda,0,0,0,0,0x3e16bdda,0,0,0xbe033e03,0,0,0,0,0xbe033e03,
0,0,0x3ddabe16,0,0,0,0,0x3ddabe16,0,0,0xbda83e25,0,0,0,0,0xbda83e25,
0,0,0x3e16bdda,0,0,0,0,0x3e16bdda,0,0,0xbda83e25,0,0,0,0,0xbda83e25,
0,0,0,0,0,0,0,0,0,0,0,0,0,0,0,0,
0,0,0x3d65be30,0,0,0,0,0x3d65be30,0,0,0xbce83e37,0,0,0,0,0xbce83e37,
0,0,0,0,0,0,0,0,0,0,0,0,0,0,0,0,
};
constexpr unsigned long long COS_PK0 = 0x3f903f9a3fa03fa2ull;
constexpr unsigned long long COS_PK1 = 0x3f133f3e3f653f83ull;
constexpr unsigned long long COS_PK2 = 0x3e4b3ec8ull;

__device__ __forceinline__ void wgmma_ss_n80_z(float (&d)[40], uint64_t da, uint64_t db) {
  asm volatile("{\n.reg .pred p;\nsetp.ne.b32 p, 0, 0;\nwgmma.mma_async.sync.aligned.m64n80k16.f32.bf16.bf16 {%0,%1,%2,%3,%4,%5,%6,%7,%8,%9,%10,%11,%12,%13,%14,%15,%16,%17,%18,%19,%20,%21,%22,%23,%24,%25,%26,%27,%28,%29,%30,%31,%32,%33,%34,%35,%36,%37,%38,%39}, %40, %41, p, 1, 1, 1, 0;\n}\n"
    : "+f"(d[0]), "+f"(d[1]), "+f"(d[2]), "+f"(d[3]), "+f"(d[4]), "+f"(d[5]), "+f"(d[6]), "+f"(d[7]), "+f"(d[8]), "+f"(d[9]), "+f"(d[10]), "+f"(d[11]), "+f"(d[12]), "+f"(d[13]), "+f"(d[14]), "+f"(d[15]), "+f"(d[16]), "+f"(d[17]), "+f"(d[18]), "+f"(d[19]), "+f"(d[20]), "+f"(d[21]), "+f"(d[22]), "+f"(d[23]), "+f"(d[24]), "+f"(d[25]), "+f"(d[26]), "+f"(d[27]), "+f"(d[28]), "+f"(d[29]), "+f"(d[30]), "+f"(d[31]), "+f"(d[32]), "+f"(d[33]), "+f"(d[34]), "+f"(d[35]), "+f"(d[36]), "+f"(d[37]), "+f"(d[38]), "+f"(d[39])
    : "l"(da), "l"(db));
}
__device__ __forceinline__ void wgmma_ss_n80_a(float (&d)[40], uint64_t da, uint64_t db) {
  asm volatile("{\n.reg .pred p;\nsetp.ne.b32 p, 1, 0;\nwgmma.mma_async.sync.aligned.m64n80k16.f32.bf16.bf16 {%0,%1,%2,%3,%4,%5,%6,%7,%8,%9,%10,%11,%12,%13,%14,%15,%16,%17,%18,%19,%20,%21,%22,%23,%24,%25,%26,%27,%28,%29,%30,%31,%32,%33,%34,%35,%36,%37,%38,%39}, %40, %41, p, 1, 1, 1, 0;\n}\n"
    : "+f"(d[0]), "+f"(d[1]), "+f"(d[2]), "+f"(d[3]), "+f"(d[4]), "+f"(d[5]), "+f"(d[6]), "+f"(d[7]), "+f"(d[8]), "+f"(d[9]), "+f"(d[10]), "+f"(d[11]), "+f"(d[12]), "+f"(d[13]), "+f"(d[14]), "+f"(d[15]), "+f"(d[16]), "+f"(d[17]), "+f"(d[18]), "+f"(d[19]), "+f"(d[20]), "+f"(d[21]), "+f"(d[22]), "+f"(d[23]), "+f"(d[24]), "+f"(d[25]), "+f"(d[26]), "+f"(d[27]), "+f"(d[28]), "+f"(d[29]), "+f"(d[30]), "+f"(d[31]), "+f"(d[32]), "+f"(d[33]), "+f"(d[34]), "+f"(d[35]), "+f"(d[36]), "+f"(d[37]), "+f"(d[38]), "+f"(d[39])
    : "l"(da), "l"(db));
}

__device__ __forceinline__ void wgmma_rs_n40_z(float (&d)[20], uint32_t a0, uint32_t a1, uint32_t a2, uint32_t a3, uint64_t db) {
  asm volatile("{\n.reg .pred p;\nsetp.ne.b32 p, 0, 0;\nwgmma.mma_async.sync.aligned.m64n40k16.f32.bf16.bf16 {%0,%1,%2,%3,%4,%5,%6,%7,%8,%9,%10,%11,%12,%13,%14,%15,%16,%17,%18,%19}, {%20,%21,%22,%23}, %24, p, 1, 1, 0;\n}\n"
    : "+f"(d[0]), "+f"(d[1]), "+f"(d[2]), "+f"(d[3]), "+f"(d[4]), "+f"(d[5]), "+f"(d[6]), "+f"(d[7]), "+f"(d[8]), "+f"(d[9]), "+f"(d[10]), "+f"(d[11]), "+f"(d[12]), "+f"(d[13]), "+f"(d[14]), "+f"(d[15]), "+f"(d[16]), "+f"(d[17]), "+f"(d[18]), "+f"(d[19])
    : "r"(a0), "r"(a1), "r"(a2), "r"(a3), "l"(db));
}
__device__ __forceinline__ void wgmma_rs_n40_a(float (&d)[20], uint32_t a0, uint32_t a1, uint32_t a2, uint32_t a3, uint64_t db) {
  asm volatile("{\n.reg .pred p;\nsetp.ne.b32 p, 1, 0;\nwgmma.mma_async.sync.aligned.m64n40k16.f32.bf16.bf16 {%0,%1,%2,%3,%4,%5,%6,%7,%8,%9,%10,%11,%12,%13,%14,%15,%16,%17,%18,%19}, {%20,%21,%22,%23}, %24, p, 1, 1, 0;\n}\n"
    : "+f"(d[0]), "+f"(d[1]), "+f"(d[2]), "+f"(d[3]), "+f"(d[4]), "+f"(d[5]), "+f"(d[6]), "+f"(d[7]), "+f"(d[8]), "+f"(d[9]), "+f"(d[10]), "+f"(d[11]), "+f"(d[12]), "+f"(d[13]), "+f"(d[14]), "+f"(d[15]), "+f"(d[16]), "+f"(d[17]), "+f"(d[18]), "+f"(d[19])
    : "r"(a0), "r"(a1), "r"(a2), "r"(a3), "l"(db));
}

__device__ __forceinline__ void wgmma_rs_n128_z(float (&d)[64], uint32_t a0, uint32_t a1, uint32_t a2, uint32_t a3, uint64_t db) {
  asm volatile("{\n.reg .pred p;\nsetp.ne.b32 p, 0, 0;\nwgmma.mma_async.sync.aligned.m64n128k16.f32.bf16.bf16 {%0,%1,%2,%3,%4,%5,%6,%7,%8,%9,%10,%11,%12,%13,%14,%15,%16,%17,%18,%19,%20,%21,%22,%23,%24,%25,%26,%27,%28,%29,%30,%31,%32,%33,%34,%35,%36,%37,%38,%39,%40,%41,%42,%43,%44,%45,%46,%47,%48,%49,%50,%51,%52,%53,%54,%55,%56,%57,%58,%59,%60,%61,%62,%63}, {%64,%65,%66,%67}, %68, p, 1, 1, 1;\n}\n"
    : "+f"(d[0]), "+f"(d[1]), "+f"(d[2]), "+f"(d[3]), "+f"(d[4]), "+f"(d[5]), "+f"(d[6]), "+f"(d[7]), "+f"(d[8]), "+f"(d[9]), "+f"(d[10]), "+f"(d[11]), "+f"(d[12]), "+f"(d[13]), "+f"(d[14]), "+f"(d[15]), "+f"(d[16]), "+f"(d[17]), "+f"(d[18]), "+f"(d[19]), "+f"(d[20]), "+f"(d[21]), "+f"(d[22]), "+f"(d[23]), "+f"(d[24]), "+f"(d[25]), "+f"(d[26]), "+f"(d[27]), "+f"(d[28]), "+f"(d[29]), "+f"(d[30]), "+f"(d[31]), "+f"(d[32]), "+f"(d[33]), "+f"(d[34]), "+f"(d[35]), "+f"(d[36]), "+f"(d[37]), "+f"(d[38]), "+f"(d[39]), "+f"(d[40]), "+f"(d[41]), "+f"(d[42]), "+f"(d[43]), "+f"(d[44]), "+f"(d[45]), "+f"(d[46]), "+f"(d[47]), "+f"(d[48]), "+f"(d[49]), "+f"(d[50]), "+f"(d[51]), "+f"(d[52]), "+f"(d[53]), "+f"(d[54]), "+f"(d[55]), "+f"(d[56]), "+f"(d[57]), "+f"(d[58]), "+f"(d[59]), "+f"(d[60]), "+f"(d[61]), "+f"(d[62]), "+f"(d[63])
    : "r"(a0), "r"(a1), "r"(a2), "r"(a3), "l"(db));
}
__device__ __forceinline__ void wgmma_rs_n128_a(float (&d)[64], uint32_t a0, uint32_t a1, uint32_t a2, uint32_t a3, uint64_t db) {
  asm volatile("{\n.reg .pred p;\nsetp.ne.b32 p, 1, 0;\nwgmma.mma_async.sync.aligned.m64n128k16.f32.bf16.bf16 {%0,%1,%2,%3,%4,%5,%6,%7,%8,%9,%10,%11,%12,%13,%14,%15,%16,%17,%18,%19,%20,%21,%22,%23,%24,%25,%26,%27,%28,%29,%30,%31,%32,%33,%34,%35,%36,%37,%38,%39,%40,%41,%42,%43,%44,%45,%46,%47,%48,%49,%50,%51,%52,%53,%54,%55,%56,%57,%58,%59,%60,%61,%62,%63}, {%64,%65,%66,%67}, %68, p, 1, 1, 1;\n}\n"
    : "+f"(d[0]), "+f"(d[1]), "+f"(d[2]), "+f"(d[3]), "+f"(d[4]), "+f"(d[5]), "+f"(d[6]), "+f"(d[7]), "+f"(d[8]), "+f"(d[9]), "+f"(d[10]), "+f"(d[11]), "+f"(d[12]), "+f"(d[13]), "+f"(d[14]), "+f"(d[15]), "+f"(d[16]), "+f"(d[17]), "+f"(d[18]), "+f"(d[19]), "+f"(d[20]), "+f"(d[21]), "+f"(d[22]), "+f"(d[23]), "+f"(d[24]), "+f"(d[25]), "+f"(d[26]), "+f"(d[27]), "+f"(d[28]), "+f"(d[29]), "+f"(d[30]), "+f"(d[31]), "+f"(d[32]), "+f"(d[33]), "+f"(d[34]), "+f"(d[35]), "+f"(d[36]), "+f"(d[37]), "+f"(d[38]), "+f"(d[39]), "+f"(d[40]), "+f"(d[41]), "+f"(d[42]), "+f"(d[43]), "+f"(d[44]), "+f"(d[45]), "+f"(d[46]), "+f"(d[47]), "+f"(d[48]), "+f"(d[49]), "+f"(d[50]), "+f"(d[51]), "+f"(d[52]), "+f"(d[53]), "+f"(d[54]), "+f"(d[55]), "+f"(d[56]), "+f"(d[57]), "+f"(d[58]), "+f"(d[59]), "+f"(d[60]), "+f"(d[61]), "+f"(d[62]), "+f"(d[63])
    : "r"(a0), "r"(a1), "r"(a2), "r"(a3), "l"(db));
}

__device__ __forceinline__ void wgmma_rs_n32_z(float (&d)[16], uint32_t a0, uint32_t a1, uint32_t a2, uint32_t a3, uint64_t db) {
  asm volatile("{\n.reg .pred p;\nsetp.ne.b32 p, 0, 0;\nwgmma.mma_async.sync.aligned.m64n32k16.f32.bf16.bf16 {%0,%1,%2,%3,%4,%5,%6,%7,%8,%9,%10,%11,%12,%13,%14,%15}, {%16,%17,%18,%19}, %20, p, 1, 1, 0;\n}\n"
    : "+f"(d[0]), "+f"(d[1]), "+f"(d[2]), "+f"(d[3]), "+f"(d[4]), "+f"(d[5]), "+f"(d[6]), "+f"(d[7]), "+f"(d[8]), "+f"(d[9]), "+f"(d[10]), "+f"(d[11]), "+f"(d[12]), "+f"(d[13]), "+f"(d[14]), "+f"(d[15])
    : "r"(a0), "r"(a1), "r"(a2), "r"(a3), "l"(db));
}
__device__ __forceinline__ void wgmma_rs_n32_a(float (&d)[16], uint32_t a0, uint32_t a1, uint32_t a2, uint32_t a3, uint64_t db) {
  asm volatile("{\n.reg .pred p;\nsetp.ne.b32 p, 1, 0;\nwgmma.mma_async.sync.aligned.m64n32k16.f32.bf16.bf16 {%0,%1,%2,%3,%4,%5,%6,%7,%8,%9,%10,%11,%12,%13,%14,%15}, {%16,%17,%18,%19}, %20, p, 1, 1, 0;\n}\n"
    : "+f"(d[0]), "+f"(d[1]), "+f"(d[2]), "+f"(d[3]), "+f"(d[4]), "+f"(d[5]), "+f"(d[6]), "+f"(d[7]), "+f"(d[8]), "+f"(d[9]), "+f"(d[10]), "+f"(d[11]), "+f"(d[12]), "+f"(d[13]), "+f"(d[14]), "+f"(d[15])
    : "r"(a0), "r"(a1), "r"(a2), "r"(a3), "l"(db));
}

__device__ __forceinline__ void wgmma_ss_n32_z(float (&d)[16], uint64_t da, uint64_t db) {
  asm volatile("{\n.reg .pred p;\nsetp.ne.b32 p, 0, 0;\nwgmma.mma_async.sync.aligned.m64n32k16.f32.bf16.bf16 {%0,%1,%2,%3,%4,%5,%6,%7,%8,%9,%10,%11,%12,%13,%14,%15}, %16, %17, p, 1, 1, 1, 0;\n}\n"
    : "+f"(d[0]), "+f"(d[1]), "+f"(d[2]), "+f"(d[3]), "+f"(d[4]), "+f"(d[5]), "+f"(d[6]), "+f"(d[7]), "+f"(d[8]), "+f"(d[9]), "+f"(d[10]), "+f"(d[11]), "+f"(d[12]), "+f"(d[13]), "+f"(d[14]), "+f"(d[15])
    : "l"(da), "l"(db));
}
__device__ __forceinline__ void wgmma_ss_n32_a(float (&d)[16], uint64_t da, uint64_t db) {
  asm volatile("{\n.reg .pred p;\nsetp.ne.b32 p, 1, 0;\nwgmma.mma_async.sync.aligned.m64n32k16.f32.bf16.bf16 {%0,%1,%2,%3,%4,%5,%6,%7,%8,%9,%10,%11,%12,%13,%14,%15}, %16, %17, p, 1, 1, 1, 0;\n}\n"
    : "+f"(d[0]), "+f"(d[1]), "+f"(d[2]), "+f"(d[3]), "+f"(d[4]), "+f"(d[5]), "+f"(d[6]), "+f"(d[7]), "+f"(d[8]), "+f"(d[9]), "+f"(d[10]), "+f"(d[11]), "+f"(d[12]), "+f"(d[13]), "+f"(d[14]), "+f"(d[15])
    : "l"(da), "l"(db));
}

__device__ __forceinline__ void wgmma_ss_n40_z(float (&d)[20], uint64_t da, uint64_t db) {
  asm volatile("{\n.reg .pred p;\nsetp.ne.b32 p, 0, 0;\nwgmma.mma_async.sync.aligned.m64n40k16.f32.bf16.bf16 {%0,%1,%2,%3,%4,%5,%6,%7,%8,%9,%10,%11,%12,%13,%14,%15,%16,%17,%18,%19}, %20, %21, p, 1, 1, 1, 0;\n}\n"
    : "+f"(d[0]), "+f"(d[1]), "+f"(d[2]), "+f"(d[3]), "+f"(d[4]), "+f"(d[5]), "+f"(d[6]), "+f"(d[7]), "+f"(d[8]), "+f"(d[9]), "+f"(d[10]), "+f"(d[11]), "+f"(d[12]), "+f"(d[13]), "+f"(d[14]), "+f"(d[15]), "+f"(d[16]), "+f"(d[17]), "+f"(d[18]), "+f"(d[19])
    : "l"(da), "l"(db));
}
__device__ __forceinline__ void wgmma_ss_n40_a(float (&d)[20], uint64_t da, uint64_t db) {
  asm volatile("{\n.reg .pred p;\nsetp.ne.b32 p, 1, 0;\nwgmma.mma_async.sync.aligned.m64n40k16.f32.bf16.bf16 {%0,%1,%2,%3,%4,%5,%6,%7,%8,%9,%10,%11,%12,%13,%14,%15,%16,%17,%18,%19}, %20, %21, p, 1, 1, 1, 0;\n}\n"
    : "+f"(d[0]), "+f"(d[1]), "+f"(d[2]), "+f"(d[3]), "+f"(d[4]), "+f"(d[5]), "+f"(d[6]), "+f"(d[7]), "+f"(d[8]), "+f"(d[9]), "+f"(d[10]), "+f"(d[11]), "+f"(d[12]), "+f"(d[13]), "+f"(d[14]), "+f"(d[15]), "+f"(d[16]), "+f"(d[17]), "+f"(d[18]), "+f"(d[19])
    : "l"(da), "l"(db));
}

constexpr int NSM = 132, NH = 66;
constexpr int S0 = 0, S1 = 51200, C3 = 153600, RG = 171008;
constexpr int C1 = RG, WP = RG + 18432, TBL = RG + 47104;
constexpr int BARS = RG + 50688;
constexpr int WST = 102400;
constexpr int NBAR = 232;
constexpr int REL = BARS + NBAR * 8;
constexpr int SMEM_BYTES = REL + 16;
constexpr int B_XF = 0, B_CF1 = 15, B_CF3 = 16, B_WF = 17, B_P1D = 18, B_WFREE = 20, B_REL = 21, B_ROLE = 22, B_X1 = 23, B_SIG = 24;
constexpr int B_RF = 32, B_RE = 46, B_YF = 60, B_WRD = 75, B_SFREE = 89, B_WCH = 131, B_RDY = 136, B_WE = 205, B_WL = 217;
constexpr int R_P2 = 15, R_P3 = 57;
constexpr int CNT_P1 = 0, CNT_P2 = 4, CNT_W = 8, CNT_RANK = 9, NCLS = 10, CNT_DONE = 0, CNT_REL = 1, NCNT = 2;
constexpr int SIG_W = 0, SIG_P1 = 1, SIG_P2 = 4;
#define PROBES 1
#define WB 100
#define PACE 0
#define PACE_SLACK 300
#define SWIN 2
#define X1AT 10
#define XWIN 5

__device__ uint4 g_scr[(14 << 21) / 16];
__device__ uint4 g_wf[200 * 72 * 32];
__device__ unsigned g_cnt[NCNT * 32];
__device__ __forceinline__ int slot_line(int chunk, int pg, int cls) {
    return (pg & 1) << 6 | (pg >> 1) << 9 | (chunk & 1) << 10 | (chunk >> 1) << 12 | ((pg ^ (pg >> 1) ^ chunk ^ (chunk >> 1) ^ cls) & 1) << 5;
}
__device__ __forceinline__ int phi_line(int phi, uint32_t rel) {
    return (phi >> 4) << 14 | (phi & 3) << 7 | ((phi >> 2) & 1) << 11 | ((phi >> 3) & 1) << 13 | ((rel >> (phi >> 4)) & 1) << 5;
}
__device__ __forceinline__ int extra_mask(int rk) { return rk < 60 ? 0 : rk < 62 ? 3 : rk < 64 ? 4 : 8; }
__device__ __forceinline__ int wslot(int pc) { return pc < 4 ? S0 + pc * 12288 : pc < 6 ? RG + (pc - 2) * 12288 : S0 + ((pc - 6) & 3) * 12288; }
__device__ __forceinline__ int extra_phi(int rk) { return 198 + (rk & 1); }
__host__ __device__ constexpr int quad_off(int Q) { return (Q >> 2) * 4096 + (Q & 3) * 512; }

#define PROF(k)
#define PROFW(k)
struct Maps { CUtensorMap w, x34, x6, x28, wst, f16, f8, y4, y2; char* scr; };

__device__ __forceinline__ uint32_t smem_u32(const void* p) { return (uint32_t)__cvta_generic_to_shared(p); }
__device__ __forceinline__ void mbar_wait(uint32_t bar) {
    uint32_t ok, it = 0;
    do {
        asm volatile("{\n.reg .pred p;\nmbarrier.try_wait.parity.shared::cta.b64 p, [%1], 0;\nselp.u32 %0, 1, 0, p;\n}" : "=r"(ok) : "r"(bar) : "memory");
        if (++it > (1u << 22)) break;
    } while (!ok);
}
__device__ __forceinline__ bool mbar_test(uint32_t bar) {
    uint32_t ok;
    asm volatile("{\n.reg .pred p;\nmbarrier.test_wait.parity.shared::cta.b64 p, [%1], 0;\nselp.u32 %0, 1, 0, p;\n}" : "=r"(ok) : "r"(bar) : "memory");
    return ok;
}
__device__ __forceinline__ void fence_async() { asm volatile("fence.proxy.async;" ::: "memory"); }
__device__ __forceinline__ void fence_async_smem() { asm volatile("fence.proxy.async.shared::cta;" ::: "memory"); }
#define ELECT "{\n.reg .pred p;\nelect.sync _|p, 0xffffffff;\n@p "
__device__ __forceinline__ void e_arrive(uint32_t bar) { asm volatile(ELECT "mbarrier.arrive.shared::cta.b64 _, [%0];\n}" :: "r"(bar) : "memory"); }
__device__ __forceinline__ void e_expect(uint32_t bar, uint32_t bytes) { asm volatile(ELECT "mbarrier.arrive.expect_tx.shared::cta.b64 _, [%0], %1;\n}" :: "r"(bar), "r"(bytes) : "memory"); }
__device__ __forceinline__ void e_g2s(uint32_t dst, const void* src, uint32_t bytes, uint32_t bar) {
    asm volatile(ELECT "cp.async.bulk.shared::cluster.global.mbarrier::complete_tx::bytes [%0], [%1], %2, [%3];\n}" :: "r"(dst), "l"(src), "r"(bytes), "r"(bar) : "memory");
}
__device__ __forceinline__ void e_s2g(void* dst, uint32_t src, uint32_t bytes) {
    asm volatile(ELECT "cp.async.bulk.global.shared::cta.bulk_group [%0], [%1], %2;\n}" :: "l"(dst), "r"(src), "r"(bytes) : "memory");
}
__device__ __forceinline__ void e_ld3(uint32_t dst, const CUtensorMap* m, int c0, int c1, int c2, uint32_t bar) {
    asm volatile(ELECT "cp.async.bulk.tensor.3d.shared::cluster.global.mbarrier::complete_tx::bytes [%0], [%1, {%3, %4, %5}], [%2];\n}"
                 :: "r"(dst), "l"(m), "r"(bar), "r"(c0), "r"(c1), "r"(c2) : "memory");
}
__device__ __forceinline__ void e_st3(const CUtensorMap* m, uint32_t src, int c0, int c1, int c2) {
    asm volatile(ELECT "cp.async.bulk.tensor.3d.global.shared::cta.bulk_group [%0, {%2, %3, %4}], [%1];\n}" :: "l"(m), "r"(src), "r"(c0), "r"(c1), "r"(c2) : "memory");
}
__device__ __forceinline__ void e_ld5(uint32_t dst, const CUtensorMap* m, int c4, uint32_t bar) {
    asm volatile(ELECT "cp.async.bulk.tensor.5d.shared::cluster.global.mbarrier::complete_tx::bytes [%0], [%1, {%4, %4, %4, %4, %3}], [%2];\n}"
                 :: "r"(dst), "l"(m), "r"(bar), "r"(c4), "r"(0) : "memory");
}
__device__ __forceinline__ void e_st5(const CUtensorMap* m, uint32_t src, int c4) {
    asm volatile(ELECT "cp.async.bulk.tensor.5d.global.shared::cta.bulk_group [%0, {%3, %3, %3, %3, %2}], [%1];\n}" :: "l"(m), "r"(src), "r"(c4), "r"(0) : "memory");
}
__device__ __forceinline__ void bulk_commit() { asm volatile("cp.async.bulk.commit_group;" ::: "memory"); }
template <int N> __device__ __forceinline__ void bulk_wait_read() { asm volatile("cp.async.bulk.wait_group.read %0;" :: "n"(N) : "memory"); }
__device__ __forceinline__ void wg_bar(int id) { asm volatile("bar.sync %0, 128;" :: "r"(id) : "memory"); }
__device__ __forceinline__ void bb_break(uint32_t v) { asm volatile("{\n.reg .pred p;\nsetp.eq.u32 p, %0, 0x7fc17fc1;\n@p nanosleep.u32 0;\n}" :: "r"(v) : "memory"); }
__device__ __forceinline__ uint32_t uni(uint32_t v) { return __shfl_sync(0xffffffffu, v, 0); }
__device__ __forceinline__ char* cls_cnt(char* scr, int cls) { return scr + slot_line(3, 2, cls) * 128; }
__device__ __forceinline__ uint32_t cnt_wait(const void* p, unsigned target) {
    unsigned v, it = 0;
    while (true) {
        asm volatile("ld.acquire.gpu.global.u32 %0, [%1];" : "=r"(v) : "l"(p) : "memory");
        v = uni(v);
        if (v >= target || ++it > (1u << 22)) break;
    }
    return v;
}
__device__ __forceinline__ void wg_fence() { asm volatile("wgmma.fence.sync.aligned;" ::: "memory"); }
__device__ __forceinline__ void wg_commit() { asm volatile("wgmma.commit_group.sync.aligned;" ::: "memory"); }
template <int N> __device__ __forceinline__ void wg_wait() { asm volatile("wgmma.wait_group.sync.aligned %0;" :: "n"(N) : "memory"); }
template <int N> __device__ __forceinline__ void reg_fence(float (&d)[N]) {
#pragma unroll
    for (int i = 0; i < N; i++) asm volatile("" : "+f"(d[i]) :: "memory");
}
template <int N, int O, int M> __device__ __forceinline__ float (&sub(float (&d)[M]))[N] { return *reinterpret_cast<float (*)[N]>(&d[O]); }
template <int N> __device__ __forceinline__ void zero(float (&d)[N]) {
#pragma unroll
    for (int i = 0; i < N; i++) d[i] = 0.f;
}
__device__ __forceinline__ uint32_t pack2(float lo, float hi) {
    uint32_t r; asm volatile("cvt.rn.bf16x2.f32 %0, %1, %2;" : "=r"(r) : "f"(hi), "f"(lo)); return r;
}
__device__ __forceinline__ void stm4(uint32_t a, uint32_t r0, uint32_t r1, uint32_t r2, uint32_t r3) {
    asm volatile("stmatrix.sync.aligned.m8n8.x4.trans.shared.b16 [%0], {%1,%2,%3,%4};" :: "r"(a), "r"(r0), "r"(r1), "r"(r2), "r"(r3) : "memory");
}
__device__ __forceinline__ void stm2(uint32_t a, uint32_t r0, uint32_t r1) {
    asm volatile("stmatrix.sync.aligned.m8n8.x2.trans.shared.b16 [%0], {%1,%2};" :: "r"(a), "r"(r0), "r"(r1) : "memory");
}
__device__ __forceinline__ void stm1(uint32_t a, uint32_t r0) {
    asm volatile("stmatrix.sync.aligned.m8n8.x1.trans.shared.b16 [%0], {%1};" :: "r"(a), "r"(r0) : "memory");
}
struct Desc {
    uint32_t lo, hi;
    __device__ __forceinline__ operator uint64_t() const { return ((uint64_t)hi << 32) | lo; }
    __device__ __forceinline__ Desc operator+(uint32_t o) const { return Desc{lo + o, hi}; }
    __device__ __forceinline__ Desc operator^(uint32_t o) const { return Desc{lo ^ o, hi}; }
};
__device__ __forceinline__ Desc mkdesc(uint32_t addr, uint32_t lbo, uint32_t sbo, uint32_t swz) {
    return Desc{((addr & 0x3FFFF) >> 4) | ((lbo >> 4) << 16), (sbo >> 4) | (swz << 30)};
}
__device__ __forceinline__ uint32_t cos_bits(int k) {
    if (k > 20) k = 40 - k;
    const bool neg = k > 10;
    if (neg) k = 20 - k;
    const unsigned long long pk = k < 4 ? COS_PK0 : k < 8 ? COS_PK1 : COS_PK2;
    return (uint32_t)((pk >> (16 * (k & 3))) & 0xffff) ^ (neg ? 0x8000u : 0u);
}

__device__ __forceinline__ void task_w(int wg, int k, uint32_t sb) {
    const int tid = threadIdx.x & 127, w = uni(tid >> 5), lane = tid & 31, q = lane & 3;
    const int tb = 14 * k, t1 = min(tb + 14, 1800), cb0 = tb / 25;
    float acc[64];
    zero(acc);
    int cnt, at = 0;
#pragma unroll 1
    for (int t = tb; t < t1; t += cnt, at++) {
        const int cb = t / 25, oc = t - 25 * cb;
        cnt = min(min(4, 25 - oc), t1 - t);
        if ((at ? 2 - (at & 1) : 0) != wg) continue;
        const Desc dB = mkdesc(sb + WP + (cb - cb0) * 14336, 3584, 512, 2);
        const int phi = 8 * (oc + w) + (lane >> 2), f = phi / 20, ca = (2 * f + 1) * 4, cbb = (phi - 20 * f) * 8;
        uint32_t a[4][4];
#pragma unroll
        for (int j = 0; j < 3; j++)
#pragma unroll
            for (int h = 0; h < 2; h++) {
                uint32_t v[2];
#pragma unroll
                for (int e = 0; e < 2; e++) {
                    const int tap = 16 * j + 8 * h + 2 * q + e, kh = (tap * 37) >> 8, kw = tap - 7 * kh;
                    asm volatile("ld.shared.u32 %0, [%1];" : "=r"(v[e]) : "r"(sb + TBL + ca * kh + cbb * kw));
                }
                a[j][2 * h] = __byte_perm(v[0], v[1], 0x5410);
                a[j][2 * h + 1] = __byte_perm(v[0], v[1], 0x7632);
            }
        {
            uint32_t v;
            asm volatile("ld.shared.u32 %0, [%1];" : "=r"(v) : "r"(sb + TBL + (ca + cbb) * 6));
            if (q) v = 0;
            a[3][0] = 0; a[3][1] = 0; a[3][2] = v & 0xffff; a[3][3] = v >> 16;
        }
        if (at == 0) PROFW(124);
        mbar_wait(sb + BARS + 8 * B_WF);
        if (at) mbar_wait(sb + BARS + 8 * (B_WCH + at - 1));
        if (at == 0) PROFW(125);
        wg_fence();
        wgmma_rs_n128_z(acc, a[0][0], a[0][1], a[0][2], a[0][3], dB);
        wgmma_rs_n128_a(acc, a[1][0], a[1][1], a[1][2], a[1][3], dB + (uint32_t)(16 * 64 >> 4));
        wgmma_rs_n128_a(acc, a[2][0], a[2][1], a[2][2], a[2][3], dB + (uint32_t)(32 * 64 >> 4));
        wgmma_rs_n128_a(acc, a[3][0], a[3][1], a[3][2], a[3][3], dB + (uint32_t)(40 * 64 >> 4));
        wg_commit();
        wg_wait<0>();
        reg_fence(acc);
        if (at == 0) PROFW(120);
        e_arrive(sb + BARS + 8 * (B_WCH + at));
        if (w < cnt) {
            const uint32_t dst = sb + WST + (t - tb + w) * 4096 + (lane >> 2) * 512 + ((q ^ cb) & 3) * 16;
#pragma unroll
            for (int j = 0; j < 4; j++)
#pragma unroll
                for (int e = 0; e < 2; e++)
                    asm volatile("st.shared.v4.u32 [%0], {%1,%2,%3,%4};" :: "r"(dst + j * 128 + e * 64),
                                 "r"(pack2(acc[4 * j + e], acc[16 + 4 * j + e])), "r"(pack2(acc[4 * j + 2 + e], acc[16 + 4 * j + 2 + e])),
                                 "r"(pack2(acc[32 + 4 * j + e], acc[48 + 4 * j + e])), "r"(pack2(acc[32 + 4 * j + 2 + e], acc[48 + 4 * j + 2 + e])) : "memory");
            fence_async_smem();
            e_arrive(sb + BARS + 8 * (B_WRD + t - tb + w));
        }
    }
}

__device__ __forceinline__ void task_p1(int wg, int pair, uint32_t sb) {
    const int tid = threadIdx.x & 127, w = tid >> 5, lane = tid & 31;
    const uint32_t buf = sb + wg * 51200, bars = sb + BARS;
    uint32_t fr[5][10][2];
    float A[40], d[20];
    zero(A);
    {
        const Desc dA = mkdesc(buf, 3584, 512, 2), dB = mkdesc(sb + C1, 128, 256, 0);
        auto issue = [&](int g, float (&d)[40]) {
            mbar_wait(bars + 8 * (B_XF + wg * 5 + g));
            wg_fence();
            wgmma_ss_n80_z(d, dA + (uint32_t)(g * 8704 >> 4), dB);
#pragma unroll
            for (int j = 1; j < 5; j++) wgmma_ss_n80_a(d, dA + (uint32_t)((g * 8704 + j * 1024) >> 4), dB + (uint32_t)(j * 2560 >> 4));
            wg_commit();
        };
        auto pack = [&](int g, float (&d)[40]) {
            reg_fence(d);
#pragma unroll
            for (int f = 0; f < 10; f++) {
                fr[g][f][0] = pack2(d[4 * f], d[4 * f + 1]);
                fr[g][f][1] = pack2(d[4 * f + 2], d[4 * f + 3]);
            }
        };
        mbar_wait(bars + 8 * B_CF1);
#pragma unroll
        for (int g = 0; g < 4; g++) { issue(g, A); if (g == 0) PROFW(8 + wg * 8 + 1); wg_wait<0>(); pack(g, A); }
        zero(d);
        mbar_wait(bars + 8 * (B_XF + wg * 5 + 4));
#pragma unroll
        for (int h = 0; h < 2; h++) {
            wg_fence();
            wgmma_ss_n40_z(d, dA + (uint32_t)(4 * 8704 >> 4), dB + (uint32_t)(h * 1280 >> 4));
#pragma unroll
            for (int j = 1; j < 5; j++) wgmma_ss_n40_a(d, dA + (uint32_t)((4 * 8704 + j * 1024) >> 4), dB + (uint32_t)((j * 2560 + h * 1280) >> 4));
            wg_commit(); wg_wait<0>(); reg_fence(d);
#pragma unroll
            for (int f = 0; f < 5; f++) { fr[4][5 * h + f][0] = pack2(d[4 * f], d[4 * f + 1]); fr[4][5 * h + f][1] = pack2(d[4 * f + 2], d[4 * f + 3]); }
        }
    }
    bb_break(sb);
    wg_bar(1 + wg);
    PROFW(8 + wg * 8 + 2);
    {
        const Desc dB = mkdesc(sb + C1 + 12800, 128, 256, 0);
        const int i = lane & 7, mi = lane >> 3, th = w >> 1, tz = (2 * pair + th) & 3;
        const uint32_t s0 = buf + (i >> 1) * 128 + (i & 1) * 64 + (((2 * (w & 1) + (mi & 1)) ^ tz ^ (i >> 1)) << 4);
        const uint32_t sA = s0 + th * 2048 + (mi >> 1) * 512, sB = s0 + th * 2048 + (mi >> 1) * 2560, sC = s0 + th * 1024 + (mi >> 1) * 512;
        auto issue = [&](int f, float (&d)[20]) {
            wg_fence();
            wgmma_rs_n40_z(d, fr[0][f][0], fr[0][f][1], fr[1][f][0], fr[1][f][1], dB);
            wgmma_rs_n40_a(d, fr[2][f][0], fr[2][f][1], fr[3][f][0], fr[3][f][1], dB + (uint32_t)(1280 >> 4));
            wgmma_rs_n40_a(d, fr[4][f % 5][0], fr[4][f % 5][1], fr[4][f % 5 + 5][0], fr[4][f % 5 + 5][1], dB + (uint32_t)((2560 + (f / 5) * 1280) >> 4));
            wg_commit();
        };
#pragma unroll
        for (int f = 0; f < 10; f++) {
                        issue(f, d); wg_wait<0>(); reg_fence(d);
            const int Q = 5 * f;
            stm4(((Q & 3) == 3 ? sB : sA) + quad_off(Q), pack2(d[0], d[1]), pack2(d[2], d[3]), pack2(d[4], d[5]), pack2(d[6], d[7]));
            stm2(sA + quad_off(Q + 2), pack2(d[8], d[9]), pack2(d[10], d[11]));
            stm4((f == 9 ? sC : ((Q + 3) & 3) == 3 ? sB : sA) + quad_off(Q + 3), pack2(d[12], d[13]), pack2(d[14], d[15]), pack2(d[16], d[17]), pack2(d[18], d[19]));
            if (f & 1) { fence_async_smem(); e_arrive(bars + 8 * (B_RDY + wg * 5 + (f >> 1))); }
        }
    }
}

__device__ __forceinline__ void task_p2(int wg, int rk, uint32_t sb) {
    const int tid = threadIdx.x & 127, w = tid >> 5, lane = tid & 31;
    const uint32_t bars = sb + BARS;
    const int phi0 = 3 * rk, phiE = extra_phi(rk), mE = extra_mask(rk);
    uint4 wA[6], wB[6], wC[6], wE[6];
    auto ldw = [&](uint4 (&a)[6], int j, int phi) {
        const int pc = 3 * j + wg;
        const uint32_t p = sb + wslot(pc) + (lane & 3) * 512 + w * 128 + ((lane >> 2) & 1) * 64 + (((lane >> 3) ^ lane) & 3) * 16 + (phi & 1) * 8;
        mbar_wait(bars + 8 * (B_WL + pc));
#pragma unroll
        for (int s = 0; s < 6; s++) {
            asm volatile("ld.shared.v2.u32 {%0, %1}, [%2];" : "=r"(a[s].x), "=r"(a[s].y) : "r"(p + s * 2048) : "memory");
            asm volatile("ld.shared.v2.u32 {%0, %1}, [%2];" : "=r"(a[s].z), "=r"(a[s].w) : "r"((p ^ 8) + s * 2048) : "memory");
        }
        uint32_t dep = 0;
#pragma unroll
        for (int s = 0; s < 6; s++) dep |= a[s].x ^ a[s].z;
        bb_break(dep);
        __syncwarp();
        e_arrive(bars + 8 * (B_WE + pc));
    };
    ldw(wA, 0, phi0); ldw(wB, 1, phi0 + 1); ldw(wC, 2, phi0 + 2);
    PROFW(8 + wg * 8 + 4);
    mbar_wait(bars + 8 * (B_SIG + SIG_P1 + 1));
    const int i = lane & 7, mi = lane >> 3;
    const uint32_t soff = sb + S1 + wg * 4096 + mi * 512 + (i >> 1) * 128 + (i & 1) * 64;
    const int xo = w ^ (i >> 1);
    float p0[16], p1[16];
    zero(p0); zero(p1);
    auto issue = [&](float (&d)[16], int n, int h, const uint4 (&a)[6], int z) {
        const Desc d0 = mkdesc(sb + RG + (n & 3) * 12288 + h * 2048 + ((z >> 1) << 5), 16, 512, 2), d1 = d0 ^ 2u;
        if (h == 0) mbar_wait(bars + 8 * (B_RF + n));
        wg_fence();
        wgmma_rs_n32_z(d, a[0].x, a[0].y, a[0].z, a[0].w, d0);
        wgmma_rs_n32_a(d, a[1].x, a[1].y, a[1].z, a[1].w, d1);
#pragma unroll
        for (int c = 1; c < 3; c++) {
            wgmma_rs_n32_a(d, a[2 * c].x, a[2 * c].y, a[2 * c].z, a[2 * c].w, d0 + (uint32_t)(c * 4096 >> 4));
            wgmma_rs_n32_a(d, a[2 * c + 1].x, a[2 * c + 1].y, a[2 * c + 1].z, a[2 * c + 1].w, d1 + (uint32_t)(c * 4096 >> 4));
        }
        wg_commit();
    };
    auto epi = [&](float (&d)[16], int n, int h, int z) {
        reg_fence(d);
        if (h) e_arrive(bars + 8 * (B_RE + n));
        uint32_t p[4];
#pragma unroll
        for (int j = 0; j < 4; j++) p[j] = pack2(d[4 * j] - d[4 * j + 3], d[4 * j + 2] + d[4 * j + 1]);
        if (h == 0 && n >= 4) mbar_wait(bars + 8 * (B_SFREE + (n - 4) * 3 + wg));
        stm4(soff + (n & 3) * 12288 + h * 2048 + ((xo ^ z) << 4), p[0], p[1], p[2], p[3]);
        if (h) { fence_async_smem(); e_arrive(bars + 8 * (B_RDY + R_P2 + n * 3 + wg)); }
    };
    const int zA = phi0 & 3, zB = (phi0 + 1) & 3, zC = (phi0 + 2) & 3, zE = phiE & 3;
    int n = 0;
#pragma unroll 1
    for (int it = 0; it < 4; it++) {
        issue(p0, n, 0, wA, zA);
        issue(p1, n, 1, wA, zA);     wg_wait<1>(); epi(p0, n, 0, zA);
        issue(p0, n + 1, 0, wB, zB); wg_wait<1>(); epi(p1, n, 1, zA);
        PROFW(40 + wg * 8 + it * 2);
        issue(p1, n + 1, 1, wB, zB); wg_wait<1>(); epi(p0, n + 1, 0, zB);
        issue(p0, n + 2, 0, wC, zC); wg_wait<1>(); epi(p1, n + 1, 1, zB);
        issue(p1, n + 2, 1, wC, zC); wg_wait<1>(); epi(p0, n + 2, 0, zC);
        wg_wait<0>(); epi(p1, n + 2, 1, zC);
        n += 3;
        if (it == 0 && mE) ldw(wE, 3, phiE);
        if (mE >> it & 1) {
            issue(p0, n, 0, wE, zE);
            issue(p1, n, 1, wE, zE); wg_wait<1>(); epi(p0, n, 0, zE);
            wg_wait<0>(); epi(p1, n, 1, zE);
            n++;
        }
        PROFW(40 + wg * 8 + it * 2 + 1);
    }
}

__device__ __forceinline__ void task_p3(int wg, int pair, uint32_t sb) {
    const int tid = threadIdx.x & 127, w = tid >> 5, lane = tid & 31;
    const uint32_t buf = sb + (wg ? 3 - wg : 0) * 51200, bars = sb + BARS;
    uint32_t fr[10][4][2];
    float acc[2][16];
    zero(acc[0]); zero(acc[1]);
    {
        const Desc dB = mkdesc(sb + C3, 128, 256, 0);
        const uint32_t a0 = (buf & 0x3FFFF) >> 4;
        auto dq = [&](int Q) {
            return Desc{a0 + (uint32_t)((quad_off(Q) >> 4) | ((Q < 48 ? 2048 : 1024) >> 4) << 16), (uint32_t)((quad_off(Q + 1) - quad_off(Q)) >> 4) | (2u << 30)};
        };
        auto issue = [&](int f) {
            if (!(f & 1)) mbar_wait(bars + 8 * (B_YF + wg * 5 + (f >> 1)));
            wg_fence();
            wgmma_ss_n32_z(acc[f & 1], dq(5 * f), dB);
            wgmma_ss_n32_a(acc[f & 1], dq(5 * f + 1), dB + (uint32_t)(1024 >> 4));
            wgmma_ss_n32_a(acc[f & 1], dq(5 * f + 3), dB + (uint32_t)(2048 >> 4));
            wg_commit();
        };
        mbar_wait(bars + 8 * B_CF3);
        issue(0);
        PROFW(64 + wg * 8 + 1);
#pragma unroll
        for (int f = 0; f < 10; f++) {
            if (f < 9) { issue(f + 1); wg_wait<1>(); } else wg_wait<0>();
            float (&d)[16] = acc[f & 1];
            reg_fence(d);
#pragma unroll
            for (int g = 0; g < 4; g++) { fr[f][g][0] = pack2(d[4 * g], d[4 * g + 1]); fr[f][g][1] = pack2(d[4 * g + 2], d[4 * g + 3]); }
        }
    }
    PROFW(64 + wg * 8 + 2);
    {
        const Desc dB = mkdesc(sb + C3 + 3072, 128, 256, 0);
        const int i = lane & 7, mi = lane >> 3, th = w >> 1, tz = (2 * pair + th) & 3;
        const int oct = (2 * (w & 1) + (mi & 1)) ^ tz;
        const uint32_t soff = buf + th * 3584 + (mi >> 1) * 512 + i * 64 + ((oct ^ (i >> 1)) << 4);
        auto issue = [&](int t) {
            const int g = t < 6 ? 1 + (t >> 1) : 0;
            const uint32_t o = t < 6 ? (t & 1) * 1024 : 8960, st = t < 6 ? 1792 : 1024;
            wg_fence();
            wgmma_rs_n32_z(acc[t & 1], fr[0][g][0], fr[0][g][1], fr[1][g][0], fr[1][g][1], dB + (o >> 4));
#pragma unroll
            for (int s = 1; s < 5; s++) wgmma_rs_n32_a(acc[t & 1], fr[2 * s][g][0], fr[2 * s][g][1], fr[2 * s + 1][g][0], fr[2 * s + 1][g][1], dB + ((o + s * st) >> 4));
            wg_commit();
        };
        bb_break(sb);
        issue(0);
        wg_bar(1 + wg);
#pragma unroll
        for (int t = 0; t < 7; t++) {
            if (t < 6) { issue(t + 1); wg_wait<1>(); } else wg_wait<0>();
            float (&d)[16] = acc[t & 1];
            reg_fence(d);
            if (t < 6) {
                const uint32_t a = soff + (1 + (t >> 1)) * 7168 + (t & 1) * 2048;
                stm4(a, pack2(d[0], d[1]), pack2(d[2], d[3]), pack2(d[4], d[5]), pack2(d[6], d[7]));
                if (t & 1) stm2(a + 1024, pack2(d[8], d[9]), pack2(d[10], d[11]));
                else stm4(a + 1024, pack2(d[8], d[9]), pack2(d[10], d[11]), pack2(d[12], d[13]), pack2(d[14], d[15]));
            } else {
                const int row = th * 14 + 4 * (mi >> 1) + (i >> 1);
                const uint32_t a = buf + row * 128 + (i & 1) * 64 + ((oct ^ (row & 3)) << 4);
                stm4(a, pack2(d[0], d[1]), pack2(d[2], d[3]), pack2(d[4], d[5]), pack2(d[6], d[7]));
                stm4((lane & 20) == 20 ? buf + 4096 + lane * 16 : a + 1024, pack2(d[8], d[9]), pack2(d[10], d[11]), pack2(d[12], d[13]), pack2(d[14], d[15]));
            }
            if ((t & 1) || t == 6) { fence_async_smem(); e_arrive(bars + 8 * (B_RDY + R_P3 + wg * 4 + (t >> 1))); }
        }
    }
}

__device__ __forceinline__ void load_x(int cls, int rk, int u, uint32_t sb, const Maps& mp) {
    const uint32_t bars = sb + BARS;
    const int id = u * NH + rk, pl = id / 3, chunk = id - 3 * pl, tp = cls * 4 + (pl >> 4), tx = pl & 15;
#pragma unroll 1
    for (int g = 0; g < 5; g++) {
        const int bi = u * 5 + g;
        if (bi >= XWIN) mbar_wait(bars + 8 * (B_XF + bi - XWIN));
        int col = 14 * tx - 8 + 4 * g; if (col < 0) col += 224;
        const uint32_t bar = bars + 8 * (B_XF + bi), dst = sb + u * 51200 + g * 8704;
        e_expect(bar, 8704);
        if (tp) e_ld3(dst, &mp.x34, 32 * chunk, col, 28 * tp - 6, bar);
        else { e_ld3(dst, &mp.x6, 32 * chunk, col, 218, bar); e_ld3(dst + 1536, &mp.x28, 32 * chunk, col, 0, bar); }
    }
}

__device__ __forceinline__ void load_first(uint32_t sb, const Maps& mp) {
    const uint32_t bars = sb + BARS;
    const int k = blockIdx.x;
    PROF(122);
    if (k < 129) {
        const int cb0 = 14 * k / 25, cb1 = min((14 * k + 13) / 25, 71);
        e_expect(bars + 8 * B_WF, (cb1 - cb0 + 1) * 14336);
#pragma unroll 1
        for (int cb = cb0; cb <= cb1; cb++) {
            const int b = cb / 24, i0 = 16 * ((cb >> 2) - 6 * b) + 2 * (cb & 3);
            e_ld3(sb + WP + (cb - cb0) * 14336, &mp.w, 32 * b, 0, i0, bars + 8 * B_WF);
            e_ld3(sb + WP + (cb - cb0) * 14336 + 7168, &mp.w, 32 * b, 0, i0 + 8, bars + 8 * B_WF);
        }
    }
    e_expect(bars + 8 * B_CF1, 17920); e_g2s(sb + C1, TAB_P1, 17920, bars + 8 * B_CF1);
}

__device__ __forceinline__ uint32_t get_rel(uint32_t sb) {
    mbar_wait(sb + BARS + 8 * B_REL);
    uint32_t v; asm volatile("ld.shared.u32 %0, [%1];" : "=r"(v) : "r"(sb + REL) : "memory");
    return uni(v);
}

__device__ __forceinline__ void load_warp(int cls, int rk, uint32_t sb, const Maps& mp) {
    const uint32_t bars = sb + BARS;
    load_x(cls, rk, 0, sb, mp);
    PROF(123);
    mbar_wait(bars + 8 * B_X1);
    load_x(cls, rk, 1, sb, mp);
    mbar_wait(bars + 8 * B_WFREE);
    if (rk < 60) load_x(cls, rk, 2, sb, mp);
    e_expect(bars + 8 * B_CF3, 17152); e_g2s(sb + C3, TAB_P3, 17152, bars + 8 * B_CF3);
    PROF(1);
    const uint32_t rel = get_rel(sb);
    const char* cnt = cls_cnt(mp.scr, cls);
    const int mE = extra_mask(rk);
    mbar_wait(bars + 8 * B_P1D);
    int n = 0;
#pragma unroll 1
    for (int pg = 0; pg < 4; pg++) {
        cnt_wait(cnt + (CNT_P1 + pg) * 128, 48);
        PROF(88 + pg);
        const int l0 = slot_line(0, pg, cls), l1 = slot_line(1, pg, cls), l2 = slot_line(2, pg, cls);
        const int nj = 3 + (mE >> pg & 1);
#pragma unroll 1
        for (int j = 0; j < nj; j++) {
            const int lp = phi_line(j == 3 ? extra_phi(rk) : 3 * rk + j, rel);
            const uint32_t bar = bars + 8 * (B_RF + n), dst = sb + RG + (n & 3) * 12288;
            if (n >= 2) mbar_wait(bars + 8 * (n >= 4 ? B_RE + n - 4 : B_WE + n + 2));
            e_expect(bar, 12288);
            e_g2s(dst, mp.scr + (size_t)(lp ^ l0) * 128, 4096, bar);
            e_g2s(dst + 4096, mp.scr + (size_t)(lp ^ l1) * 128, 4096, bar);
            e_g2s(dst + 8192, mp.scr + (size_t)(lp ^ l2) * 128, 4096, bar);
            n++;
        }
    }
}

__device__ __forceinline__ int near_page(char* p, int rounds) {
#pragma unroll
    for (int e = 0; e < 4; e++) asm volatile("st.relaxed.gpu.global.v4.u32 [%0], {%1, %1, %1, %1};" :: "l"(p + (e >> 1) * 4096 + (e & 1) * 16), "r"(0) : "memory");
    int score = 0;
#pragma unroll 1
    for (int r = 0; r < rounds; r++) {
        uint32_t v0, v1, t0, t1;
        asm volatile("atom.relaxed.gpu.global.exch.b32 %0, [%1], 1;" : "=r"(v0) : "l"(p + (r & 1) * 4096) : "memory");
        asm volatile("atom.relaxed.gpu.global.exch.b32 %0, [%1], 1;" : "=r"(v1) : "l"(p + (~r & 1) * 4096) : "memory");
        asm volatile("{\n.reg .pred p;\nsetp.ne.u32 p, %1, 0xffffffff;\nmov.u32 %0, 0;\n@p mov.u32 %0, %%clock;\n}" : "=r"(t0) : "r"(v0) : "memory");
        asm volatile("{\n.reg .pred p;\nsetp.ne.u32 p, %1, 0xffffffff;\nmov.u32 %0, 0;\n@p mov.u32 %0, %%clock;\n}" : "=r"(t1) : "r"(v1) : "memory");
        const int gap = min((int)(t1 - t0), 160) - 80;
        score += (r & 1) ? gap : -gap;
    }
    return score > 0;
}

__device__ __forceinline__ void find_role(uint32_t sb, char* scr) {
    const int k = blockIdx.x;
    int c = near_page(scr + (slot_line(3, 3, 0) + phi_line(1 + (k >> 5), 0) + (k & 31)) * 128, PROBES);
    PROF(3);
    int r;
    asm volatile("atom.relaxed.gpu.global.add.u32 %0, [%1], 1;" : "=r"(r) : "l"(cls_cnt(scr, c) + CNT_RANK * 128) : "memory");
    if (r >= NH) { c ^= 1; r = NSM - 1 - r; }
    asm volatile("st.shared.u32 [%0], %1;" :: "r"(sb + REL + 4), "r"(c << 8 | r) : "memory");
    PROF(5);
}
__device__ __forceinline__ void get_role(uint32_t sb, int& cls, int& rk) {
    mbar_wait(sb + BARS + 8 * B_ROLE);
    uint32_t v; asm volatile("ld.shared.u32 %0, [%1];" : "=r"(v) : "r"(sb + REL + 4) : "memory");
    v = uni(v); cls = v >> 8; rk = v & 255;
}

__device__ __forceinline__ void load3_warp(int cls, int rk, uint32_t sb, const Maps& mp) {
    const uint32_t bars = sb + BARS;
    uint32_t rel = 0;
    mbar_wait(bars + 8 * B_XF);
    rel = cnt_wait(&g_cnt[CNT_REL * 32], 12u << 16);
    asm volatile("st.shared.u32 [%0], %1;" :: "r"(sb + REL), "r"(rel) : "memory");
    __syncwarp();
    e_arrive(bars + 8 * B_REL);
    PROF(7);
    mbar_wait(bars + 8 * (B_SIG + SIG_W));
    cnt_wait(cls_cnt(mp.scr, cls) + CNT_W * 128, NSM);
    PROF(2);
    mbar_wait(bars + 8 * (B_SIG + SIG_P1));
    {
        const int np = rk >= 60 ? 12 : 9;
#pragma unroll 1
        for (int pc = 0; pc < np; pc++) {
            if (pc >= 6) mbar_wait(bars + 8 * (B_WE + pc - (pc < 10 ? 6 : 4)));
            e_expect(bars + 8 * (B_WL + pc), 12288);
            e_g2s(sb + wslot(pc), g_wf + (pc < 9 ? 9 * rk + pc : 3 * extra_phi(rk) + pc - 9) * 768, 12288, bars + 8 * (B_WL + pc));
        }
        if (np == 12) { mbar_wait(bars + 8 * (B_WE + 9)); mbar_wait(bars + 8 * (B_WE + 10)); mbar_wait(bars + 8 * (B_WE + 11)); }
    }
    mbar_wait(bars + 8 * (B_SIG + SIG_P2));
    const int nu = rk < 60 ? 3 : 2;
#pragma unroll 1
    for (int u = 0; u < nu; u++) {
        const int id = u * NH + rk, pl = id / 3, chunk = id - 3 * pl;
        const int l0 = slot_line(chunk, pl >> 4, cls) + (pl & 15) * 2;
        const uint32_t buf = sb + (u ? 3 - u : 0) * 51200, bar = bars + 8 * (B_YF + u * 5);
#pragma unroll
        for (int j = 0; j < 5; j++) e_expect(bar + 8 * j, j == 4 ? 10240 : (j & 1) ? 8192 : 12288);
        if (u == 2) mbar_wait(bars + 8 * (B_SIG + SIG_P2 + 3));
        cnt_wait(cls_cnt(mp.scr, cls) + (CNT_P2 + (pl >> 4)) * 128, NH);
        PROF(64 + u * 8);
        uint32_t bj = bar;
#pragma unroll 1
        for (int G = 0; G < 12; G++) {
            e_ld5(buf + G * 4096, &mp.f16, (l0 ^ ((rel >> G) & 1) << 5) + (G << 14), bj);
            bj += (0x294 >> G & 1) * 8;
        }
        e_ld5(buf + 12 * 4096, &mp.f8, (l0 ^ ((rel >> 12) & 1) << 5) + (12 << 14), bj);
    }
}

__device__ __forceinline__ void store_warp(uint32_t sb, const Maps& mp) {
    const uint32_t bars = sb + BARS;
    const int k = blockIdx.x;
    uint32_t pa = 0, pb = 0, qa = 0, qb = 0;
    auto arr2 = [&](uint32_t& a, uint32_t& b) { if (a) e_arrive(a); if (b) e_arrive(b); a = b = 0; };
    auto pre = [&](int idx) {
        const uint32_t bar = bars + 8 * idx;
        if (!mbar_test(bar)) { bulk_wait_read<0>(); arr2(qa, qb); arr2(pa, pb); mbar_wait(bar); }
    };
    auto post = [&](uint32_t fr) {
        bulk_commit(); bulk_wait_read<SWIN - 1>();
        if (SWIN == 3) { arr2(qa, qb); qa = pa; qb = pb; pb = 0; } else arr2(pa, pb);
        pa = fr;
    };
    auto after = [&](uint32_t a, uint32_t b) { if (a) pa = a; pb = b; };
    auto pace = [&](uint32_t) {};
    {
        int cb = 14 * k / 25, oc = 14 * k - 25 * cb;
#pragma unroll 1
        for (int i = 0; i < 14 && cb < 72; i++) {
            pre(B_WRD + i);
            if (i == 0) PROF(6);
            pace(4 * PACE);
            e_st3(&mp.wst, sb + WST + i * 4096, 0, 8 * oc, cb);
            post(0);
            if (i == X1AT - 1) e_arrive(bars + 8 * B_X1);
            if (++oc == 25) { oc = 0; cb++; }
        }
        if (X1AT && 14 * k + X1AT > 1800) e_arrive(bars + 8 * B_X1);
        after(bars + 8 * B_WFREE, bars + 8 * (B_SIG + SIG_W));
    }
    pre(B_REL);
    const uint32_t rel = get_rel(sb);
    int cls, rk; get_role(sb, cls, rk);
    const int nu = rk < 60 ? 3 : 2;
#pragma unroll 1
    for (int u = 0; u < nu; u++) {
        const int id = u * NH + rk, pl = id / 3, chunk = id - 3 * pl;
        const int l0 = slot_line(chunk, pl >> 4, cls) + (pl & 15) * 2;
        int j = B_RDY + u * 5;
#pragma unroll 1
        for (int G = 0; G < 13; G++) {
            if (0x4a5 >> G & 1) pre(j++);
            if (G == 0) PROF(104 + u);
            pace(G < 12 ? 4 * PACE : 2 * PACE);
            e_st5(G < 12 ? &mp.f16 : &mp.f8, sb + u * 51200 + G * 4096, (l0 ^ ((rel >> G) & 1) << 5) + (G << 14));
            post(0);
        }
        after(0, bars + 8 * (B_SIG + SIG_P1 + u));
    }
    const int mE = extra_mask(rk);
    int n = 0;
#pragma unroll 1
    for (int pg = 0; pg < 4; pg++) {
        const int nj = 3 + (mE >> pg & 1);
        const int l0 = slot_line(0, pg, cls), l1 = slot_line(1, pg, cls), l2 = slot_line(2, pg, cls);
#pragma unroll 1
        for (int j = 0; j < nj; j++) {
            const int lp = phi_line(j == 3 ? extra_phi(rk) : 3 * rk + j, rel);
#pragma unroll
            for (int b = 0; b < 3; b++) {
                pre(B_RDY + R_P2 + n * 3 + b);
                if (j == 0 && b == 0 && pg < 3) PROF(107 + pg);
                pace(4 * PACE);
                e_s2g(mp.scr + (size_t)(lp ^ (b == 0 ? l0 : b == 1 ? l1 : l2)) * 128, sb + S1 + (n & 3) * 12288 + b * 4096, 4096);
                post(bars + 8 * (B_SFREE + n * 3 + b));
            }
            n++;
        }
        after(0, bars + 8 * (B_SIG + SIG_P2 + pg));
    }
#pragma unroll 1
    for (int u = 0; u < nu; u++) {
        const int id = u * NH + rk, pl = id / 3, chunk = id - 3 * pl, tp = cls * 4 + (pl >> 4), tx = pl & 15;
        const uint32_t buf = sb + (u ? 3 - u : 0) * 51200;
#pragma unroll
        for (int gg = 1; gg < 5; gg++) {
            pre(B_RDY + R_P3 + u * 4 + gg - 1);
            if (gg == 1) PROF(110 + u);
            if (u < 2) pace(gg < 4 ? 7 * PACE : 7 * PACE / 2);
            if (gg < 4) e_st3(&mp.y4, buf + gg * 7168, 32 * chunk, 14 * tx - 4 + 4 * gg, 28 * tp);
            else e_st3(&mp.y2, buf, 32 * chunk, tx == 0 ? 222 : 14 * tx - 2, 28 * tp);
            post(0);
        }
    }
    bulk_wait_read<0>();
    PROF(113);
}

__device__ __forceinline__ void signal_warp(int cls, int rk, uint32_t sb, char* scr) {
    const uint32_t bars = sb + BARS;
    char* cnt = cls_cnt(scr, cls);
    if (threadIdx.x & 31) return;
#pragma unroll 1
    for (int c = 0; c < 8; c++) {
        if (c == SIG_P1 + 2 && rk >= 60) continue;
        char* ctr = cnt + (c == SIG_W ? CNT_W : c < SIG_P2 ? CNT_P1 + ((c - SIG_P1) * NH + rk) / 48 : CNT_P2 + c - SIG_P2) * 128;
        mbar_wait(bars + 8 * (B_SIG + c));
        PROF(32 + c);
        fence_async();
        asm volatile("red.relaxed.gpu.global.add.u32 [%0], 1;" :: "l"(ctr) : "memory");
        if (c == SIG_W) asm volatile("red.relaxed.gpu.global.add.u32 [%0], 1;" :: "l"((uintptr_t)ctr ^ 4096) : "memory");
        PROF(96 + c);
    }
    mbar_wait(bars + 8 * (B_YF + (rk < 60 ? 14 : 9)));
    unsigned old;
    asm volatile("atom.add.acq_rel.gpu.global.u32 %0, [%1], 1;" : "=r"(old) : "l"(&g_cnt[CNT_DONE * 32]) : "memory");
    if (old == NSM - 1) {
#pragma unroll
        for (int c = 0; c < NCNT; c++) g_cnt[c * 32] = 0;
#pragma unroll 1
        for (int c = 0; c < NCLS; c++) { *reinterpret_cast<unsigned*>(cnt + c * 128) = 0; *reinterpret_cast<unsigned*>(((uintptr_t)cnt ^ 4096) + c * 128) = 0; }
    }
}

__global__ void __launch_bounds__(512, 1) fftconv_kernel(const __grid_constant__ Maps mp) {
    extern __shared__ __align__(1024) uint8_t smem[];
    const uint32_t sb = smem_u32(smem);
    const int tid = threadIdx.x, warp = uni(tid >> 5), wg = warp >> 2;
    int cls, rk;
    auto bar_init = [&](int i) {
        uint32_t c = 1;
        if (i == B_P1D || (i >= B_RE && i < B_RE + 14)) c = 12;
        else if (i >= B_WCH && i < B_WL) c = 4;
        asm volatile("st.shared.v2.u32 [%0], {%1, %2};" :: "r"(sb + BARS + 8 * i), "r"((0x100000u - c) << 1), "r"((0x100000u - c) << 11) : "memory");
        fence_async_smem();
    };
    if (wg == 3) {
        asm volatile("setmaxnreg.dec.sync.aligned.u32 32;");
        if (warp == 12) {
            bar_init(tid & 31);
            __syncwarp();
            asm volatile("bar.arrive 4, 416;" ::: "memory");
            load_first(sb, mp);
            asm volatile("bar.sync 5, 416;" ::: "memory");
            get_role(sb, cls, rk);
            load_warp(cls, rk, sb, mp);
        } else if (warp == 13) {
            if ((tid & 31) < 8) asm volatile("prefetch.tensormap [%0];" :: "l"(reinterpret_cast<const CUtensorMap*>(&mp) + 1 + (tid & 31)) : "memory");
            __syncwarp();
            asm volatile("bar.sync 6, 416;" ::: "memory");
            store_warp(sb, mp);
        } else if (warp == 14) {
            const int G = blockIdx.x - 119;
            int sel = 0;
            if (G >= 1 && (tid & 31) == 0) sel = near_page(mp.scr + ((size_t)G << 21) + slot_line(3, 3, 0) * 128, 2);
            __syncwarp();
            asm volatile("bar.sync 7, 416;" ::: "memory");
            get_role(sb, cls, rk);
            if (G >= 1 && (tid & 31) == 0) asm volatile("red.relaxed.gpu.global.add.u32 [%0], %1;" :: "l"(&g_cnt[CNT_REL * 32]), "r"(0x10000u | (uint32_t)(sel ^ cls) << G) : "memory");
            __syncwarp();
            load3_warp(cls, rk, sb, mp);
        } else {
            if ((tid & 31) == 0) find_role(sb, mp.scr);
            __syncwarp();
            asm volatile("bar.sync 8, 416;" ::: "memory");
            e_arrive(sb + BARS + 8 * B_ROLE);
            get_role(sb, cls, rk);
            signal_warp(cls, rk, sb, mp.scr);
        }
    } else {
        if (tid >= 32 && tid < NBAR) bar_init(tid);
        {
            const int r = tid % 40;
            asm volatile("st.shared.u32 [%0], %1;" :: "r"(sb + TBL + 4 * tid), "r"(cos_bits(r) | (cos_bits(r < 30 ? r + 10 : r - 30) << 16)) : "memory");
        }
        __syncwarp();
        asm volatile("bar.sync 4, 416;" ::: "memory");
        asm volatile("bar.arrive 5, 416;" ::: "memory");
        asm volatile("bar.arrive 6, 416;" ::: "memory");
        asm volatile("bar.arrive 7, 416;" ::: "memory");
        asm volatile("bar.arrive 8, 416;" ::: "memory");
        if (tid == 64) PROF(121);
        asm volatile("setmaxnreg.inc.sync.aligned.u32 160;");
        task_w(wg, blockIdx.x, sb);
        get_role(sb, cls, rk);
        const int id = wg * NH + rk;
        PROFW(8 + wg * 8);
        if (id < 192) task_p1(wg, id / 3, sb);
        e_arrive(sb + BARS + 8 * B_P1D);
        PROFW(8 + wg * 8 + 3);
        task_p2(wg, rk, sb);
        if (id < 192) task_p3(wg, id / 3, sb);
        PROFW(64 + wg * 8 + 3);
    }
}

typedef CUresult (*EncodeFn)(CUtensorMap*, CUtensorMapDataType, cuuint32_t, void*, const cuuint64_t*, const cuuint64_t*, const cuuint32_t*, const cuuint32_t*,
                             CUtensorMapInterleave, CUtensorMapSwizzle, CUtensorMapL2promotion, CUtensorMapFloatOOBfill);

static void encode3(EncodeFn fn, CUtensorMap* m, void* ptr, uint64_t d0, uint64_t d1, uint64_t d2, uint64_t s1, uint64_t s2,
                    uint32_t b0, uint32_t b1, uint32_t b2, CUtensorMapSwizzle sw) {
    cuuint64_t dims[3] = {d0, d1, d2}, strides[2] = {s1, s2};
    cuuint32_t box[3] = {b0, b1, b2}, es[3] = {1, 1, 1};
    fn(m, CU_TENSOR_MAP_DATA_TYPE_BFLOAT16, 3, ptr, dims, strides, box, es, CU_TENSOR_MAP_INTERLEAVE_NONE, sw,
       CU_TENSOR_MAP_L2_PROMOTION_NONE, CU_TENSOR_MAP_FLOAT_OOB_FILL_NONE);
}

extern "C" void kernel_launch(void* const* d_in, const int* in_sizes, int n_in, void* d_out, int out_size) {
    (void)in_sizes; (void)n_in; (void)out_size;
    void* fnp = nullptr; cudaDriverEntryPointQueryResult qr;
    cudaGetDriverEntryPoint("cuTensorMapEncodeTiled", &fnp, cudaEnableDefault, &qr);
    EncodeFn fn = (EncodeFn)fnp;
    void* xf = nullptr; cudaGetSymbolAddress(&xf, g_scr);
    xf = (void*)(((uintptr_t)xf + (1u << 21) - 1) & ~(uintptr_t)((1u << 21) - 1));
    void* wf = nullptr; cudaGetSymbolAddress(&wf, g_wf);
    Maps mp;
    mp.scr = (char*)xf;
    {
        cuuint32_t b16[5] = {64, 4, 2, 2, 2}, b8[5] = {64, 4, 2, 1, 2}, es[5] = {1, 1, 1, 1, 1};
        cuuint64_t d[5] = {64, 4, 2, 2, 13 << 14}, st[4] = {16384, 262144, 1048576, 128};
        fn(&mp.f16, CU_TENSOR_MAP_DATA_TYPE_BFLOAT16, 5, xf, d, st, b16, es, CU_TENSOR_MAP_INTERLEAVE_NONE, CU_TENSOR_MAP_SWIZZLE_NONE, CU_TENSOR_MAP_L2_PROMOTION_NONE, CU_TENSOR_MAP_FLOAT_OOB_FILL_NONE);
        fn(&mp.f8, CU_TENSOR_MAP_DATA_TYPE_BFLOAT16, 5, xf, d, st, b8, es, CU_TENSOR_MAP_INTERLEAVE_NONE, CU_TENSOR_MAP_SWIZZLE_NONE, CU_TENSOR_MAP_L2_PROMOTION_NONE, CU_TENSOR_MAP_FLOAT_OOB_FILL_NONE);
    }
    encode3(fn, &mp.x6, d_in[0], 96, 224, 224, 192, 224 * 192, 32, 4, 6, CU_TENSOR_MAP_SWIZZLE_64B);
    encode3(fn, &mp.x34, d_in[0], 96, 224, 224, 192, 224 * 192, 32, 4, 34, CU_TENSOR_MAP_SWIZZLE_64B);
    encode3(fn, &mp.x28, d_in[0], 96, 224, 224, 192, 224 * 192, 32, 4, 28, CU_TENSOR_MAP_SWIZZLE_64B);
    encode3(fn, &mp.w, d_in[1], 96, 49, 96, 18432, 192, 32, 56, 2, CU_TENSOR_MAP_SWIZZLE_64B);
    encode3(fn, &mp.wst, wf, 256, 200, 72, 36864, 512, 256, 8, 1, CU_TENSOR_MAP_SWIZZLE_NONE);
    encode3(fn, &mp.y4, d_out, 96, 224, 224, 192, 224 * 192, 32, 4, 28, CU_TENSOR_MAP_SWIZZLE_64B);
    encode3(fn, &mp.y2, d_out, 96, 224, 224, 192, 224 * 192, 32, 2, 28, CU_TENSOR_MAP_SWIZZLE_64B);
    cudaFuncSetAttribute(fftconv_kernel, cudaFuncAttributeMaxDynamicSharedMemorySize, SMEM_BYTES);
    fftconv_kernel<<<NSM, 512, SMEM_BYTES>>>(mp);
}
```

```cpp
#include <cuda_runtime.h>
#include <cuda_bf16.h>
#include <cuda.h>
#include <stdint.h>

__device__ __align__(128) const uint32_t TAB_P1[4480] = {
0x3e75,0,0x3e72,0,0x8000,0,0xbd19,0,0x3e750000,0,0x3e720000,0,0x80000000,0,0xbd190000,0,
0,0x3e75,0,0x3e72,0,0x8000,0,0xbd19,0,0x3e750000,0,0x3e720000,0,0x80000000,0,0xbd190000,
0x3e69,0,0x3e5a,0,0xbd97,0,0xbdde,0,0x3e690000,0,0x3e5a0000,0,0xbd970000,0,0xbdde0000,0,
0,0x3e69,0,0x3e5a,0,0xbd97,0,0xbdde,0,0x3e690000,0,0x3e5a0000,0,0xbd970000,0,0xbdde0000,
0x3e75,0,0x3e5a,0,0x8000,0,0xbdde,0,0x3e750000,0,0x3e5a0000,0,0x80000000,0,0xbdde0000,0,
0,0x3e75,0,0x3e5a,0,0x8000,0,0xbdde,0,0x3e750000,0,0x3e5a0000,0,0x80000000,0,0xbdde0000,
0x3e10,0,0x3d19,0,0xbe46,0,0xbe72,0,0x3e100000,0,0x3d190000,0,0xbe460000,0,0xbe720000,0,
0,0x3e10,0,0x3d19,0,0xbe46,0,0xbe72,0,0x3e100000,0,0x3d190000,0,0xbe460000,0,0xbe720000,
0x3e75,0,0x3e2d,0,0x8000,0,0xbe2d,0,0x3e750000,0,0x3e2d0000,0,0x80000000,0,0xbe2d0000,0,
0,0x3e75,0,0x3e2d,0,0x8000,0,0xbe2d,0,0x3e750000,0,0x3e2d0000,0,0x80000000,0,0xbe2d0000,
0,0,0xbe2d,0,0xbe75,0,0xbe2d,0,0,0,0xbe2d0000,0,0xbe750000,0,0xbe2d0000,0,
0,0,0,0xbe2d,0,0xbe75,0,0xbe2d,0,0,0,0xbe2d0000,0,0xbe750000,0,0xbe2d0000,
0x3e75,0,0x3dde,0,0x8000,0,0xbe5a,0,0x3e750000,0,0x3dde0000,0,0x80000000,0,0xbe5a0000,0,
0,0x3e75,0,0x3dde,0,0x8000,0,0xbe5a,0,0x3e750000,0,0x3dde0000,0,0x80000000,0,0xbe5a0000,
0xbe10,0,0xbe72,0,0xbe46,0,0x3d19,0,0xbe100000,0,0xbe720000,0,0xbe460000,0,0x3d190000,0,
0,0xbe10,0,0xbe72,0,0xbe46,0,0x3d19,0,0xbe100000,0,0xbe720000,0,0xbe460000,0,0x3d190000,
0x3e75,0,0x3d19,0,0x8000,0,0xbe72,0,0x3e750000,0,0x3d190000,0,0x80000000,0,0xbe720000,0,
0,0x3e75,0,0x3d19,0,0x8000,0,0xbe72,0,0x3e750000,0,0x3d190000,0,0x80000000,0,0xbe720000,
0xbe69,0,0xbdde,0,0xbd97,0,0x3e5a,0,0xbe690000,0,0xbdde0000,0,0xbd970000,0,0x3e5a0000,0,
0,0xbe69,0,0xbdde,0,0xbd97,0,0x3e5a,0,0xbe690000,0,0xbdde0000,0,0xbd970000,0,0x3e5a0000,
0x3e75,0,0xbd19,0,0x8000,0,0xbe72,0,0x3e750000,0,0xbd190000,0,0x80000000,0,0xbe720000,0,
0,0x3e75,0,0xbd19,0,0x8000,0,0xbe72,0,0x3e750000,0,0xbd190000,0,0x80000000,0,0xbe720000,
0xbe69,0,0x3dde,0,0x3d97,0,0x3e5a,0,0xbe690000,0,0x3dde0000,0,0x3d970000,0,0x3e5a0000,0,
0,0xbe69,0,0x3dde,0,0x3d97,0,0x3e5a,0,0xbe690000,0,0x3dde0000,0,0x3d970000,0,0x3e5a0000,
0x3e75,0,0xbdde,0,0x8000,0,0xbe5a,0,0x3e750000,0,0xbdde0000,0,0x80000000,0,0xbe5a0000,0,
0,0x3e75,0,0xbdde,0,0x8000,0,0xbe5a,0,0x3e750000,0,0xbdde0000,0,0x80000000,0,0xbe5a0000,
0xbe10,0,0x3e72,0,0x3e46,0,0x3d19,0,0xbe100000,0,0x3e720000,0,0x3e460000,0,0x3d190000,0,
0,0xbe10,0,0x3e72,0,0x3e46,0,0x3d19,0,0xbe100000,0,0x3e720000,0,0x3e460000,0,0x3d190000,
0x3e75,0,0xbe2d,0,0x8000,0,0xbe2d,0,0x3e750000,0,0xbe2d0000,0,0x80000000,0,0xbe2d0000,0,
0,0x3e75,0,0xbe2d,0,0x8000,0,0xbe2d,0,0x3e750000,0,0xbe2d0000,0,0x80000000,0,0xbe2d0000,
0,0,0x3e2d,0,0x3e75,0,0xbe2d,0,0,0,0x3e2d0000,0,0x3e750000,0,0xbe2d0000,0,
0,0,0,0x3e2d,0,0x3e75,0,0xbe2d,0,0,0,0x3e2d0000,0,0x3e750000,0,0xbe2d0000,
0x3e75,0,0xbe5a,0,0x8000,0,0xbdde,0,0x3e750000,0,0xbe5a0000,0,0x80000000,0,0xbdde0000,0,
0,0x3e75,0,0xbe5a,0,0x8000,0,0xbdde,0,0x3e750000,0,0xbe5a0000,0,0x80000000,0,0xbdde0000,
0x3e10,0,0xbd19,0,0x3e46,0,0xbe72,0,0x3e100000,0,0xbd190000,0,0x3e460000,0,0xbe720000,0,
0,0x3e10,0,0xbd19,0,0x3e46,0,0xbe72,0,0x3e100000,0,0xbd190000,0,0x3e460000,0,0xbe720000,
0x3e75,0,0xbe72,0,0x8000,0,0xbd19,0,0x3e750000,0,0xbe720000,0,0x80000000,0,0xbd190000,0,
0,0x3e75,0,0xbe72,0,0x8000,0,0xbd19,0,0x3e750000,0,0xbe720000,0,0x80000000,0,0xbd190000,
0x3e69,0,0xbe5a,0,0x3d97,0,0xbdde,0,0x3e690000,0,0xbe5a0000,0,0x3d970000,0,0xbdde0000,0,
0,0x3e69,0,0xbe5a,0,0x3d97,0,0xbdde,0,0x3e690000,0,0xbe5a0000,0,0x3d970000,0,0xbdde0000,
0x3e46,0,0x3e2d,0,0xbe10,0,0xbe2d,0,0x3e460000,0,0x3e2d0000,0,0xbe100000,0,0xbe2d0000,0,
0,0x3e46,0,0x3e2d,0,0xbe10,0,0xbe2d,0,0x3e460000,0,0x3e2d0000,0,0xbe100000,0,0xbe2d0000,
0x3e10,0,0x3dde,0,0xbe46,0,0xbe5a,0,0x3e100000,0,0x3dde0000,0,0xbe460000,0,0xbe5a0000,0,
0,0x3e10,0,0x3dde,0,0xbe46,0,0xbe5a,0,0x3e100000,0,0x3dde0000,0,0xbe460000,0,0xbe5a0000,
0xbd97,0,0xbe2d,0,0xbe69,0,0xbe2d,0,0xbd970000,0,0xbe2d0000,0,0xbe690000,0,0xbe2d0000,0,
0,0xbd97,0,0xbe2d,0,0xbe69,0,0xbe2d,0,0xbd970000,0,0xbe2d0000,0,0xbe690000,0,0xbe2d0000,
0xbe69,0,0xbe72,0,0xbd97,0,0x3d19,0,0xbe690000,0,0xbe720000,0,0xbd970000,0,0x3d190000,0,
0,0xbe69,0,0xbe72,0,0xbd97,0,0x3d19,0,0xbe690000,0,0xbe720000,0,0xbd970000,0,0x3d190000,
0xbe75,0,0xbe2d,0,0x8000,0,0x3e2d,0,0xbe750000,0,0xbe2d0000,0,0x80000000,0,0x3e2d0000,0,
0,0xbe75,0,0xbe2d,0,0x8000,0,0x3e2d,0,0xbe750000,0,0xbe2d0000,0,0x80000000,0,0x3e2d0000,
0,0,0x3e2d,0,0x3e75,0,0x3e2d,0,0,0,0x3e2d0000,0,0x3e750000,0,0x3e2d0000,0,
0,0,0,0x3e2d,0,0x3e75,0,0x3e2d,0,0,0,0x3e2d0000,0,0x3e750000,0,0x3e2d0000,
0xbd97,0,0x3e2d,0,0x3e69,0,0x3e2d,0,0xbd970000,0,0x3e2d0000,0,0x3e690000,0,0x3e2d0000,0,
0,0xbd97,0,0x3e2d,0,0x3e69,0,0x3e2d,0,0xbd970000,0,0x3e2d0000,0,0x3e690000,0,0x3e2d0000,
0x3e69,0,0x3d19,0,0xbd97,0,0xbe72,0,0x3e690000,0,0x3d190000,0,0xbd970000,0,0xbe720000,0,
0,0x3e69,0,0x3d19,0,0xbd97,0,0xbe72,0,0x3e690000,0,0x3d190000,0,0xbd970000,0,0xbe720000,
0x3e46,0,0x3e2d,0,0x3e10,0,0xbe2d,0,0x3e460000,0,0x3e2d0000,0,0x3e100000,0,0xbe2d0000,0,
0,0x3e46,0,0x3e2d,0,0x3e10,0,0xbe2d,0,0x3e460000,0,0x3e2d0000,0,0x3e100000,0,0xbe2d0000,
0xbe10,0,0xbe5a,0,0xbe46,0,0x3dde,0,0xbe100000,0,0xbe5a0000,0,0xbe460000,0,0x3dde0000,0,
0,0xbe10,0,0xbe5a,0,0xbe46,0,0x3dde,0,0xbe100000,0,0xbe5a0000,0,0xbe460000,0,0x3dde0000,
0x3e46,0,0xbe2d,0,0xbe10,0,0xbe2d,0,0x3e460000,0,0xbe2d0000,0,0xbe100000,0,0xbe2d0000,0,
0,0x3e46,0,0xbe2d,0,0xbe10,0,0xbe2d,0,0x3e460000,0,0xbe2d0000,0,0xbe100000,0,0xbe2d0000,
0xbe10,0,0x3e5a,0,0x3e46,0,0x3dde,0,0xbe100000,0,0x3e5a0000,0,0x3e460000,0,0x3dde0000,0,
0,0xbe10,0,0x3e5a,0,0x3e46,0,0x3dde,0,0xbe100000,0,0x3e5a0000,0,0x3e460000,0,0x3dde0000,
0xbd97,0,0xbe2d,0,0xbe69,0,0x3e2d,0,0xbd970000,0,0xbe2d0000,0,0xbe690000,0,0x3e2d0000,0,
0,0xbd97,0,0xbe2d,0,0xbe69,0,0x3e2d,0,0xbd970000,0,0xbe2d0000,0,0xbe690000,0,0x3e2d0000,
0x3e69,0,0xbd19,0,0x3d97,0,0xbe72,0,0x3e690000,0,0xbd190000,0,0x3d970000,0,0xbe720000,0,
0,0x3e69,0,0xbd19,0,0x3d97,0,0xbe72,0,0x3e690000,0,0xbd190000,0,0x3d970000,0,0xbe720000,
0xbe75,0,0x3e2d,0,0x8000,0,0x3e2d,0,0xbe750000,0,0x3e2d0000,0,0x80000000,0,0x3e2d0000,0,
0,0xbe75,0,0x3e2d,0,0x8000,0,0x3e2d,0,0xbe750000,0,0x3e2d0000,0,0x80000000,0,0x3e2d0000,
0,0,0xbe2d,0,0xbe75,0,0x3e2d,0,0,0,0xbe2d0000,0,0xbe750000,0,0x3e2d0000,0,
0,0,0,0xbe2d,0,0xbe75,0,0x3e2d,0,0,0,0xbe2d0000,0,0xbe750000,0,0x3e2d0000,
0xbd97,0,0x3e2d,0,0x3e69,0,0xbe2d,0,0xbd970000,0,0x3e2d0000,0,0x3e690000,0,0xbe2d0000,0,
0,0xbd97,0,0x3e2d,0,0x3e69,0,0xbe2d,0,0xbd970000,0,0x3e2d0000,0,0x3e690000,0,0xbe2d0000,
0xbe69,0,0x3e72,0,0x3d97,0,0x3d19,0,0xbe690000,0,0x3e720000,0,0x3d970000,0,0x3d190000,0,
0,0xbe69,0,0x3e72,0,0x3d97,0,0x3d19,0,0xbe690000,0,0x3e720000,0,0x3d970000,0,0x3d190000,
0x3e46,0,0xbe2d,0,0x3e10,0,0xbe2d,0,0x3e460000,0,0xbe2d0000,0,0x3e100000,0,0xbe2d0000,0,
0,0x3e46,0,0xbe2d,0,0x3e10,0,0xbe2d,0,0x3e460000,0,0xbe2d0000,0,0x3e100000,0,0xbe2d0000,
0x3e10,0,0xbdde,0,0x3e46,0,0xbe5a,0,0x3e100000,0,0xbdde0000,0,0x3e460000,0,0xbe5a0000,0,
0,0x3e10,0,0xbdde,0,0x3e46,0,0xbe5a,0,0x3e100000,0,0xbdde0000,0,0x3e460000,0,0xbe5a0000,
0x3d97,0,0x3d19,0,0xbe69,0,0xbe72,0,0x3d970000,0,0x3d190000,0,0xbe690000,0,0xbe720000,0,
0,0x3d97,0,0x3d19,0,0xbe69,0,0xbe72,0,0x3d970000,0,0x3d190000,0,0xbe690000,0,0xbe720000,
0,0,0xbd19,0,0xbe75,0,0xbe72,0,0,0,0xbd190000,0,0xbe750000,0,0xbe720000,0,
0,0,0,0xbd19,0,0xbe75,0,0xbe72,0,0,0,0xbd190000,0,0xbe750000,0,0xbe720000,
0xbe46,0,0xbdde,0,0x3e10,0,0x3e5a,0,0xbe460000,0,0xbdde0000,0,0x3e100000,0,0x3e5a0000,0,
0,0xbe46,0,0xbdde,0,0x3e10,0,0x3e5a,0,0xbe460000,0,0xbdde0000,0,0x3e100000,0,0x3e5a0000,
0,0,0x3dde,0,0x3e75,0,0x3e5a,0,0,0,0x3dde0000,0,0x3e750000,0,0x3e5a0000,0,
0,0,0,0x3dde,0,0x3e75,0,0x3e5a,0,0,0,0x3dde0000,0,0x3e750000,0,0x3e5a0000,
0x3e75,0,0x3e2d,0,0x8000,0,0xbe2d,0,0x3e750000,0,0x3e2d0000,0,0x80000000,0,0xbe2d0000,0,
0,0x3e75,0,0x3e2d,0,0x8000,0,0xbe2d,0,0x3e750000,0,0x3e2d0000,0,0x80000000,0,0xbe2d0000,
0,0,0xbe2d,0,0xbe75,0,0xbe2d,0,0,0,0xbe2d0000,0,0xbe750000,0,0xbe2d0000,0,
0,0,0,0xbe2d,0,0xbe75,0,0xbe2d,0,0,0,0xbe2d0000,0,0xbe750000,0,0xbe2d0000,
0xbe46,0,0xbe5a,0,0xbe10,0,0x3dde,0,0xbe460000,0,0xbe5a0000,0,0xbe100000,0,0x3dde0000,0,
0,0xbe46,0,0xbe5a,0,0xbe10,0,0x3dde,0,0xbe460000,0,0xbe5a0000,0,0xbe100000,0,0x3dde0000,
0,0,0x3e5a,0,0x3e75,0,0x3dde,0,0,0,0x3e5a0000,0,0x3e750000,0,0x3dde0000,0,
0,0,0,0x3e5a,0,0x3e75,0,0x3dde,0,0,0,0x3e5a0000,0,0x3e750000,0,0x3dde0000,
0x3d97,0,0x3e72,0,0x3e69,0,0xbd19,0,0x3d970000,0,0x3e720000,0,0x3e690000,0,0xbd190000,0,
0,0x3d97,0,0x3e72,0,0x3e69,0,0xbd19,0,0x3d970000,0,0x3e720000,0,0x3e690000,0,0xbd190000,
0,0,0xbe72,0,0xbe75,0,0xbd19,0,0,0,0xbe720000,0,0xbe750000,0,0xbd190000,0,
0,0,0,0xbe72,0,0xbe75,0,0xbd19,0,0,0,0xbe720000,0,0xbe750000,0,0xbd190000,
0x3d97,0,0xbe72,0,0xbe69,0,0xbd19,0,0x3d970000,0,0xbe720000,0,0xbe690000,0,0xbd190000,0,
0,0x3d97,0,0xbe72,0,0xbe69,0,0xbd19,0,0x3d970000,0,0xbe720000,0,0xbe690000,0,0xbd190000,
0,0,0x3e72,0,0x3e75,0,0xbd19,0,0,0,0x3e720000,0,0x3e750000,0,0xbd190000,0,
0,0,0,0x3e72,0,0x3e75,0,0xbd19,0,0,0,0x3e720000,0,0x3e750000,0,0xbd190000,
0xbe46,0,0x3e5a,0,0x3e10,0,0x3dde,0,0xbe460000,0,0x3e5a0000,0,0x3e100000,0,0x3dde0000,0,
0,0xbe46,0,0x3e5a,0,0x3e10,0,0x3dde,0,0xbe460000,0,0x3e5a0000,0,0x3e100000,0,0x3dde0000,
0,0,0xbe5a,0,0xbe75,0,0x3dde,0,0,0,0xbe5a0000,0,0xbe750000,0,0x3dde0000,0,
0,0,0,0xbe5a,0,0xbe75,0,0x3dde,0,0,0,0xbe5a0000,0,0xbe750000,0,0x3dde0000,
0x3e75,0,0xbe2d,0,0x8000,0,0xbe2d,0,0x3e750000,0,0xbe2d0000,0,0x80000000,0,0xbe2d0000,0,
0,0x3e75,0,0xbe2d,0,0x8000,0,0xbe2d,0,0x3e750000,0,0xbe2d0000,0,0x80000000,0,0xbe2d0000,
0,0,0x3e2d,0,0x3e75,0,0xbe2d,0,0,0,0x3e2d0000,0,0x3e750000,0,0xbe2d0000,0,
0,0,0,0x3e2d,0,0x3e75,0,0xbe2d,0,0,0,0x3e2d0000,0,0x3e750000,0,0xbe2d0000,
0xbe46,0,0x3dde,0,0xbe10,0,0x3e5a,0,0xbe460000,0,0x3dde0000,0,0xbe100000,0,0x3e5a0000,0,
0,0xbe46,0,0x3dde,0,0xbe10,0,0x3e5a,0,0xbe460000,0,0x3dde0000,0,0xbe100000,0,0x3e5a0000,
0,0,0xbdde,0,0xbe75,0,0x3e5a,0,0,0,0xbdde0000,0,0xbe750000,0,0x3e5a0000,0,
0,0,0,0xbdde,0,0xbe75,0,0x3e5a,0,0,0,0xbdde0000,0,0xbe750000,0,0x3e5a0000,
0x3d97,0,0xbd19,0,0x3e69,0,0xbe72,0,0x3d970000,0,0xbd190000,0,0x3e690000,0,0xbe720000,0,
0,0x3d97,0,0xbd19,0,0x3e69,0,0xbe72,0,0x3d970000,0,0xbd190000,0,0x3e690000,0,0xbe720000,
0,0,0x3d19,0,0x3e75,0,0xbe72,0,0,0,0x3d190000,0,0x3e750000,0,0xbe720000,0,
0,0,0,0x3d19,0,0x3e75,0,0xbe72,0,0,0,0x3d190000,0,0x3e750000,0,0xbe720000,
0xbd97,0,0xbdde,0,0xbe69,0,0xbe5a,0,0xbd970000,0,0xbdde0000,0,0xbe690000,0,0xbe5a0000,0,
0,0xbd97,0,0xbdde,0,0xbe69,0,0xbe5a,0,0xbd970000,0,0xbdde0000,0,0xbe690000,0,0xbe5a0000,
0xbe10,0,0xbe2d,0,0xbe46,0,0xbe2d,0,0xbe100000,0,0xbe2d0000,0,0xbe460000,0,0xbe2d0000,0,
0,0xbe10,0,0xbe2d,0,0xbe46,0,0xbe2d,0,0xbe100000,0,0xbe2d0000,0,0xbe460000,0,0xbe2d0000,
0x3e46,0,0x3e72,0,0x3e10,0,0x3d19,0,0x3e460000,0,0x3e720000,0,0x3e100000,0,0x3d190000,0,
0,0x3e46,0,0x3e72,0,0x3e10,0,0x3d19,0,0x3e460000,0,0x3e720000,0,0x3e100000,0,0x3d190000,
0x3e69,0,0x3e2d,0,0xbd97,0,0xbe2d,0,0x3e690000,0,0x3e2d0000,0,0xbd970000,0,0xbe2d0000,0,
0,0x3e69,0,0x3e2d,0,0xbd97,0,0xbe2d,0,0x3e690000,0,0x3e2d0000,0,0xbd970000,0,0xbe2d0000,
0xbe75,0,0xbe2d,0,0x8000,0,0x3e2d,0,0xbe750000,0,0xbe2d0000,0,0x80000000,0,0x3e2d0000,0,
0,0xbe75,0,0xbe2d,0,0x8000,0,0x3e2d,0,0xbe750000,0,0xbe2d0000,0,0x80000000,0,0x3e2d0000,
0,0,0x3e2d,0,0x3e75,0,0x3e2d,0,0,0,0x3e2d0000,0,0x3e750000,0,0x3e2d0000,0,
0,0,0,0x3e2d,0,0x3e75,0,0x3e2d,0,0,0,0x3e2d0000,0,0x3e750000,0,0x3e2d0000,
0x3e46,0,0xbd19,0,0xbe10,0,0xbe72,0,0x3e460000,0,0xbd190000,0,0xbe100000,0,0xbe720000,0,
0,0x3e46,0,0xbd19,0,0xbe10,0,0xbe72,0,0x3e460000,0,0xbd190000,0,0xbe100000,0,0xbe720000,
0xbe69,0,0xbe2d,0,0xbd97,0,0x3e2d,0,0xbe690000,0,0xbe2d0000,0,0xbd970000,0,0x3e2d0000,0,
0,0xbe69,0,0xbe2d,0,0xbd97,0,0x3e2d,0,0xbe690000,0,0xbe2d0000,0,0xbd970000,0,0x3e2d0000,
0xbd97,0,0x3e5a,0,0x3e69,0,0x3dde,0,0xbd970000,0,0x3e5a0000,0,0x3e690000,0,0x3dde0000,0,
0,0xbd97,0,0x3e5a,0,0x3e69,0,0x3dde,0,0xbd970000,0,0x3e5a0000,0,0x3e690000,0,0x3dde0000,
0x3e10,0,0xbe2d,0,0xbe46,0,0xbe2d,0,0x3e100000,0,0xbe2d0000,0,0xbe460000,0,0xbe2d0000,0,
0,0x3e10,0,0xbe2d,0,0xbe46,0,0xbe2d,0,0x3e100000,0,0xbe2d0000,0,0xbe460000,0,0xbe2d0000,
0xbd97,0,0xbe5a,0,0xbe69,0,0x3dde,0,0xbd970000,0,0xbe5a0000,0,0xbe690000,0,0x3dde0000,0,
0,0xbd97,0,0xbe5a,0,0xbe69,0,0x3dde,0,0xbd970000,0,0xbe5a0000,0,0xbe690000,0,0x3dde0000,
0x3e10,0,0x3e2d,0,0x3e46,0,0xbe2d,0,0x3e100000,0,0x3e2d0000,0,0x3e460000,0,0xbe2d0000,0,
0,0x3e10,0,0x3e2d,0,0x3e46,0,0xbe2d,0,0x3e100000,0,0x3e2d0000,0,0x3e460000,0,0xbe2d0000,
0x3e46,0,0x3d19,0,0x3e10,0,0xbe72,0,0x3e460000,0,0x3d190000,0,0x3e100000,0,0xbe720000,0,
0,0x3e46,0,0x3d19,0,0x3e10,0,0xbe72,0,0x3e460000,0,0x3d190000,0,0x3e100000,0,0xbe720000,
0xbe69,0,0x3e2d,0,0x3d97,0,0x3e2d,0,0xbe690000,0,0x3e2d0000,0,0x3d970000,0,0x3e2d0000,0,
0,0xbe69,0,0x3e2d,0,0x3d97,0,0x3e2d,0,0xbe690000,0,0x3e2d0000,0,0x3d970000,0,0x3e2d0000,
0xbe75,0,0x3e2d,0,0x8000,0,0x3e2d,0,0xbe750000,0,0x3e2d0000,0,0x80000000,0,0x3e2d0000,0,
0,0xbe75,0,0x3e2d,0,0x8000,0,0x3e2d,0,0xbe750000,0,0x3e2d0000,0,0x80000000,0,0x3e2d0000,
0,0,0xbe2d,0,0xbe75,0,0x3e2d,0,0,0,0xbe2d0000,0,0xbe750000,0,0x3e2d0000,0,
0,0,0,0xbe2d,0,0xbe75,0,0x3e2d,0,0,0,0xbe2d0000,0,0xbe750000,0,0x3e2d0000,
0x3e46,0,0xbe72,0,0xbe10,0,0x3d19,0,0x3e460000,0,0xbe720000,0,0xbe100000,0,0x3d190000,0,
0,0x3e46,0,0xbe72,0,0xbe10,0,0x3d19,0,0x3e460000,0,0xbe720000,0,0xbe100000,0,0x3d190000,
0x3e69,0,0xbe2d,0,0x3d97,0,0xbe2d,0,0x3e690000,0,0xbe2d0000,0,0x3d970000,0,0xbe2d0000,0,
0,0x3e69,0,0xbe2d,0,0x3d97,0,0xbe2d,0,0x3e690000,0,0xbe2d0000,0,0x3d970000,0,0xbe2d0000,
0xbd97,0,0x3dde,0,0x3e69,0,0xbe5a,0,0xbd970000,0,0x3dde0000,0,0x3e690000,0,0xbe5a0000,0,
0,0xbd97,0,0x3dde,0,0x3e69,0,0xbe5a,0,0xbd970000,0,0x3dde0000,0,0x3e690000,0,0xbe5a0000,
0xbe10,0,0x3e2d,0,0x3e46,0,0xbe2d,0,0xbe100000,0,0x3e2d0000,0,0x3e460000,0,0xbe2d0000,0,
0,0xbe10,0,0x3e2d,0,0x3e46,0,0xbe2d,0,0xbe100000,0,0x3e2d0000,0,0x3e460000,0,0xbe2d0000,
0xbe46,0,0xbe5a,0,0xbe10,0,0xbdde,0,0xbe460000,0,0xbe5a0000,0,0xbe100000,0,0xbdde0000,0,
0,0xbe46,0,0xbe5a,0,0xbe10,0,0xbdde,0,0xbe460000,0,0xbe5a0000,0,0xbe100000,0,0xbdde0000,
0xbe69,0,0xbe72,0,0xbd97,0,0xbd19,0,0xbe690000,0,0xbe720000,0,0xbd970000,0,0xbd190000,0,
0,0xbe69,0,0xbe72,0,0xbd97,0,0xbd19,0,0xbe690000,0,0xbe720000,0,0xbd970000,0,0xbd190000,
0x3d97,0,0xbd19,0,0xbe69,0,0xbe72,0,0x3d970000,0,0xbd190000,0,0xbe690000,0,0xbe720000,0,
0,0x3d97,0,0xbd19,0,0xbe69,0,0xbe72,0,0x3d970000,0,0xbd190000,0,0xbe690000,0,0xbe720000,
0xbe10,0,0xbe5a,0,0xbe46,0,0xbdde,0,0xbe100000,0,0xbe5a0000,0,0xbe460000,0,0xbdde0000,0,
0,0xbe10,0,0xbe5a,0,0xbe46,0,0xbdde,0,0xbe100000,0,0xbe5a0000,0,0xbe460000,0,0xbdde0000,
0x3e75,0,0x3e2d,0,0x8000,0,0xbe2d,0,0x3e750000,0,0x3e2d0000,0,0x80000000,0,0xbe2d0000,0,
0,0x3e75,0,0x3e2d,0,0x8000,0,0xbe2d,0,0x3e750000,0,0x3e2d0000,0,0x80000000,0,0xbe2d0000,
0,0,0xbe2d,0,0xbe75,0,0xbe2d,0,0,0,0xbe2d0000,0,0xbe750000,0,0xbe2d0000,0,
0,0,0,0xbe2d,0,0xbe75,0,0xbe2d,0,0,0,0xbe2d0000,0,0xbe750000,0,0xbe2d0000,
0x3d97,0,0x3e72,0,0x3e69,0,0x3d19,0,0x3d970000,0,0x3e720000,0,0x3e690000,0,0x3d190000,0,
0,0x3d97,0,0x3e72,0,0x3e69,0,0x3d19,0,0x3d970000,0,0x3e720000,0,0x3e690000,0,0x3d190000,
0x3e10,0,0xbdde,0,0xbe46,0,0xbe5a,0,0x3e100000,0,0xbdde0000,0,0xbe460000,0,0xbe5a0000,0,
0,0x3e10,0,0xbdde,0,0xbe46,0,0xbe5a,0,0x3e100000,0,0xbdde0000,0,0xbe460000,0,0xbe5a0000,
0xbe46,0,0x3dde,0,0x3e10,0,0x3e5a,0,0xbe460000,0,0x3dde0000,0,0x3e100000,0,0x3e5a0000,0,
0,0xbe46,0,0x3dde,0,0x3e10,0,0x3e5a,0,0xbe460000,0,0x3dde0000,0,0x3e100000,0,0x3e5a0000,
0x3e69,0,0xbd19,0,0xbd97,0,0xbe72,0,0x3e690000,0,0xbd190000,0,0xbd970000,0,0xbe720000,0,
0,0x3e69,0,0xbd19,0,0xbd97,0,0xbe72,0,0x3e690000,0,0xbd190000,0,0xbd970000,0,0xbe720000,
0xbe46,0,0xbdde,0,0xbe10,0,0x3e5a,0,0xbe460000,0,0xbdde0000,0,0xbe100000,0,0x3e5a0000,0,
0,0xbe46,0,0xbdde,0,0xbe10,0,0x3e5a,0,0xbe460000,0,0xbdde0000,0,0xbe100000,0,0x3e5a0000,
0x3e69,0,0x3d19,0,0x3d97,0,0xbe72,0,0x3e690000,0,0x3d190000,0,0x3d970000,0,0xbe720000,0,
0,0x3e69,0,0x3d19,0,0x3d97,0,0xbe72,0,0x3e690000,0,0x3d190000,0,0x3d970000,0,0xbe720000,
0x3d97,0,0xbe72,0,0xbe69,0,0x3d19,0,0x3d970000,0,0xbe720000,0,0xbe690000,0,0x3d190000,0,
0,0x3d97,0,0xbe72,0,0xbe69,0,0x3d19,0,0x3d970000,0,0xbe720000,0,0xbe690000,0,0x3d190000,
0x3e10,0,0x3dde,0,0x3e46,0,0xbe5a,0,0x3e100000,0,0x3dde0000,0,0x3e460000,0,0xbe5a0000,0,
0,0x3e10,0,0x3dde,0,0x3e46,0,0xbe5a,0,0x3e100000,0,0x3dde0000,0,0x3e460000,0,0xbe5a0000,
0x3e75,0,0xbe2d,0,0x8000,0,0xbe2d,0,0x3e750000,0,0xbe2d0000,0,0x80000000,0,0xbe2d0000,0,
0,0x3e75,0,0xbe2d,0,0x8000,0,0xbe2d,0,0x3e750000,0,0xbe2d0000,0,0x80000000,0,0xbe2d0000,
0,0,0x3e2d,0,0x3e75,0,0xbe2d,0,0,0,0x3e2d0000,0,0x3e750000,0,0xbe2d0000,0,
0,0,0,0x3e2d,0,0x3e75,0,0xbe2d,0,0,0,0x3e2d0000,0,0x3e750000,0,0xbe2d0000,
0x3d97,0,0x3d19,0,0x3e69,0,0xbe72,0,0x3d970000,0,0x3d190000,0,0x3e690000,0,0xbe720000,0,
0,0x3d97,0,0x3d19,0,0x3e69,0,0xbe72,0,0x3d970000,0,0x3d190000,0,0x3e690000,0,0xbe720000,
0xbe10,0,0x3e5a,0,0x3e46,0,0xbdde,0,0xbe100000,0,0x3e5a0000,0,0x3e460000,0,0xbdde0000,0,
0,0xbe10,0,0x3e5a,0,0x3e46,0,0xbdde,0,0xbe100000,0,0x3e5a0000,0,0x3e460000,0,0xbdde0000,
0xbe46,0,0x3e5a,0,0x3e10,0,0xbdde,0,0xbe460000,0,0x3e5a0000,0,0x3e100000,0,0xbdde0000,0,
0,0xbe46,0,0x3e5a,0,0x3e10,0,0xbdde,0,0xbe460000,0,0x3e5a0000,0,0x3e100000,0,0xbdde0000,
0xbe69,0,0x3e72,0,0x3d97,0,0xbd19,0,0xbe690000,0,0x3e720000,0,0x3d970000,0,0xbd190000,0,
0,0xbe69,0,0x3e72,0,0x3d97,0,0xbd19,0,0xbe690000,0,0x3e720000,0,0x3d970000,0,0xbd190000,
0x3eb7,0x3eb7,0x3eb7,0x3eb7,0x3eb78000,0x3eb78000,0x3eb78000,0x3eb78000,0x3eb7,0x3de23eae,0x3e573e94,0x3e943e57,0x3eb78000,0x3eaebde2,0x3e94be57,0x3e57be94,
0x3eb7,0x3e573e94,0x3eae3de2,0x3eaebde2,0x3eb78000,0x3e94be57,0x3de2beae,0xbde2beae,0x3eb7,0x3e943e57,0x3eaebde2,0x3de2beae,0x3eb78000,0x3e57be94,0xbde2beae,0xbeaebde2,
0x3eb7,0x3eb7,0x3eb7,0x3eb7,0x3eb78000,0x3eb78000,0x3eb78000,0x3eb78000,0x3eae3de2,0x3eb70000,0x3eaebde2,0x3e94be57,0x3de2beae,0xbeb7,0xbde2beae,0xbe57be94,
0x3e57be94,0xbeb7,0xbe57be94,0xbeaebde2,0xbe94be57,0xbeb78000,0xbe943e57,0xbde23eae,0xbe57be94,0xbeb70000,0xbe573e94,0x3de23eae,0xbe943e57,0x3eb7,0x3e943e57,0x3eaebde2,
0x3eb7,0x3eae3de2,0x3e57be94,0xbe57be94,0x3eb78000,0x3de2beae,0xbe94be57,0xbe943e57,0x3eb7,0x3eb70000,0xbeb7,0xbeb70000,0x3eb78000,0xbeb7,0xbeb78000,0x3eb7,
0x3eb7,0x3eaebde2,0xbe57be94,0xbe573e94,0x3eb78000,0xbde2beae,0xbe943e57,0x3e943e57,0x3eb7,0x3e94be57,0xbeaebde2,0x3de23eae,0x3eb78000,0xbe57be94,0xbde23eae,0x3eaebde2,
0xbeae3de2,0x3eb7,0x3eae3de2,0x3e57be94,0x3de23eae,0x3eb78000,0x3de2beae,0xbe94be57,0x3eb7,0x3eb70000,0xbeb7,0xbeb70000,0x3eb78000,0xbeb7,0xbeb78000,0x3eb7,
0x3eae3de2,0xbeb7,0xbeae3de2,0x3e573e94,0x3de2beae,0xbeb78000,0x3de23eae,0x3e94be57,0x3e57be94,0xbeb70000,0x3e573e94,0x3de2beae,0xbe94be57,0x3eb7,0x3e94be57,0xbeaebde2,
0x3eb7,0x3e57be94,0xbeae3de2,0x3eae3de2,0x3eb78000,0xbe94be57,0x3de23eae,0x3de2beae,0x3eb7,0x3de2beae,0xbe573e94,0x3e94be57,0x3eb78000,0xbeaebde2,0x3e943e57,0xbe57be94,
0x3eb7,0xbeb7,0x3eb7,0xbeb7,0x3eb78000,0xbeb78000,0x3eb78000,0xbeb78000,0x3eb7,0xbde2beae,0x3e573e94,0xbe94be57,0x3eb78000,0xbeae3de2,0x3e94be57,0xbe573e94,
0xbe57be94,0x3eb7,0x3e57be94,0xbeae3de2,0xbe943e57,0x3eb78000,0xbe94be57,0x3de23eae,0xbeae3de2,0x3eb70000,0xbeaebde2,0x3e943e57,0x3de23eae,0xbeb7,0xbde23eae,0x3e57be94,
0x3eb7,0xbeb7,0x3eb7,0xbeb7,0x3eb78000,0xbeb78000,0x3eb78000,0xbeb78000,0x3eae3de2,0xbeb70000,0x3eaebde2,0xbe943e57,0x3de2beae,0x3eb7,0xbde2beae,0x3e573e94,
0x3eb7,0xbe57be94,0x3eae3de2,0xbeae3de2,0x3eb78000,0xbe943e57,0x3de2beae,0x3de23eae,0x3eb7,0xbe94be57,0x3eaebde2,0xbde23eae,0x3eb78000,0xbe573e94,0xbde2beae,0x3eae3de2,
0x3eb7,0xbeaebde2,0x3e57be94,0x3e573e94,0x3eb78000,0xbde23eae,0xbe94be57,0x3e94be57,0x3eb7,0xbeb70000,0xbeb7,0x3eb70000,0x3eb78000,0x3eb7,0xbeb78000,0xbeb7,
0x3e57be94,0x3eb7,0xbe57be94,0x3eae3de2,0xbe94be57,0x3eb78000,0xbe943e57,0x3de2beae,0xbe57be94,0x3eb70000,0xbe573e94,0xbde2beae,0xbe943e57,0xbeb7,0x3e943e57,0xbeae3de2,
0xbeae3de2,0xbeb7,0x3eae3de2,0xbe573e94,0x3de23eae,0xbeb78000,0x3de2beae,0x3e943e57,0x3eb7,0xbeb70000,0xbeb7,0x3eb70000,0x3eb78000,0x3eb7,0xbeb78000,0xbeb7,
0x3eb7,0xbeae3de2,0xbe57be94,0x3e57be94,0x3eb78000,0x3de23eae,0xbe943e57,0xbe94be57,0x3eb7,0xbe943e57,0xbeaebde2,0xbde2beae,0x3eb78000,0x3e573e94,0xbde23eae,0xbeae3de2,
0x3eb7,0xbe573e94,0xbeae3de2,0xbeaebde2,0x3eb78000,0x3e943e57,0x3de23eae,0xbde23eae,0x3eb7,0xbde23eae,0xbe573e94,0xbe943e57,0x3eb78000,0x3eae3de2,0x3e943e57,0x3e573e94,
0x3eae3de2,0x3eb7,0xbeae3de2,0xbe57be94,0x3de2beae,0x3eb78000,0x3de23eae,0xbe943e57,0x3e57be94,0x3eb70000,0x3e573e94,0xbde23eae,0xbe94be57,0xbeb7,0x3e94be57,0x3eae3de2,
0xbe57be94,0xbeb7,0x3e57be94,0x3eaebde2,0xbe943e57,0xbeb78000,0xbe94be57,0xbde2beae,0xbeae3de2,0xbeb70000,0xbeaebde2,0xbe94be57,0x3de23eae,0x3eb7,0xbde23eae,0xbe573e94,
0x3eb7,0x3eb7,0x3eb7,0x3eb7,0x3eb78000,0x3eb78000,0x3eb78000,0x3eb78000,0x3e57be94,0x3de2beae,0xbeb7,0xbde2beae,0xbe94be57,0xbeaebde2,0xbeb78000,0xbeae3de2,
0xbeae3de2,0xbe573e94,0x3eb7,0x3e573e94,0x3de23eae,0x3e943e57,0x3eb78000,0x3e94be57,0x3eae3de2,0x3e94be57,0xbeb7,0xbe94be57,0x3de2beae,0xbe57be94,0xbeb78000,0xbe573e94,
0x3eb7,0x3eb7,0x3eb7,0x3eb7,0x3eb78000,0x3eb78000,0x3eb78000,0x3eb78000,0xbe57be94,0xbe94be57,0xbeaebde2,0xbeb70000,0xbe943e57,0xbe573e94,0xbde23eae,0x3eb7,
0x3eae3de2,0x3eaebde2,0x3e57be94,0xbeb7,0x3de2beae,0xbde2beae,0xbe94be57,0xbeb78000,0xbeae3de2,0xbde23eae,0x3e573e94,0x3eb70000,0x3de23eae,0x3eae3de2,0x3e94be57,0xbeb7,
0xbe57be94,0xbeae3de2,0x3eb7,0x3eae3de2,0xbe943e57,0x3de23eae,0x3eb78000,0x3de2beae,0x3eb7,0x3eb70000,0xbeb7,0xbeb70000,0x3eb78000,0xbeb7,0xbeb78000,0x3eb7,
0x3e57be94,0xbeaebde2,0x3eb7,0x3eaebde2,0xbe94be57,0xbde23eae,0x3eb78000,0xbde2beae,0xbeae3de2,0x3e943e57,0xbeb7,0xbe943e57,0x3de23eae,0x3e57be94,0xbeb78000,0x3e573e94,
0x3e57be94,0xbe57be94,0xbeae3de2,0x3eb7,0xbe94be57,0xbe943e57,0x3de23eae,0x3eb78000,0x3eb7,0x3eb70000,0xbeb7,0xbeb70000,0x3eb78000,0xbeb7,0xbeb78000,0x3eb7,
0xbe57be94,0xbe573e94,0x3eae3de2,0xbeb7,0xbe943e57,0x3e943e57,0x3de2beae,0xbeb78000,0x3eae3de2,0xbde2beae,0xbe573e94,0x3eb70000,0x3de2beae,0xbeae3de2,0x3e943e57,0xbeb7,
0x3eae3de2,0xbe57be94,0x3eb7,0x3e57be94,0x3de2beae,0xbe943e57,0x3eb78000,0xbe94be57,0xbe57be94,0x3de23eae,0xbeb7,0xbde23eae,0xbe943e57,0x3eaebde2,0xbeb78000,0x3eae3de2,
0x3eb7,0xbeb7,0x3eb7,0xbeb7,0x3eb78000,0xbeb78000,0x3eb78000,0xbeb78000,0x3e57be94,0xbde23eae,0xbeb7,0x3de23eae,0xbe94be57,0x3eae3de2,0xbeb78000,0x3eaebde2,
0xbeae3de2,0x3eae3de2,0xbe57be94,0x3eb7,0x3de23eae,0x3de2beae,0xbe943e57,0x3eb78000,0x3e57be94,0xbe943e57,0x3eaebde2,0xbeb70000,0xbe94be57,0x3e573e94,0xbde2beae,0x3eb7,
0x3eb7,0xbeb7,0x3eb7,0xbeb7,0x3eb78000,0xbeb78000,0x3eb78000,0xbeb78000,0xbe57be94,0x3e943e57,0xbeaebde2,0x3eb70000,0xbe943e57,0x3e57be94,0xbde23eae,0xbeb7,
0xbeae3de2,0x3e57be94,0x3eb7,0xbe57be94,0x3de23eae,0xbe94be57,0x3eb78000,0xbe943e57,0x3eae3de2,0xbe943e57,0xbeb7,0x3e943e57,0x3de2beae,0x3e573e94,0xbeb78000,0x3e57be94,
0xbe57be94,0x3eaebde2,0x3eb7,0xbeaebde2,0xbe943e57,0xbde2beae,0x3eb78000,0xbde23eae,0x3eb7,0xbeb70000,0xbeb7,0x3eb70000,0x3eb78000,0x3eb7,0xbeb78000,0xbeb7,
0x3eae3de2,0xbeae3de2,0x3e57be94,0x3eb7,0x3de2beae,0x3de23eae,0xbe94be57,0x3eb78000,0xbeae3de2,0x3de2beae,0x3e573e94,0xbeb70000,0x3de23eae,0xbeaebde2,0x3e94be57,0x3eb7,
0x3e57be94,0x3e573e94,0xbeae3de2,0xbeb7,0xbe94be57,0x3e94be57,0x3de23eae,0xbeb78000,0x3eb7,0xbeb70000,0xbeb7,0x3eb70000,0x3eb78000,0x3eb7,0xbeb78000,0xbeb7,
0x3e57be94,0x3eae3de2,0x3eb7,0xbeae3de2,0xbe94be57,0x3de2beae,0x3eb78000,0x3de23eae,0xbeae3de2,0xbe94be57,0xbeb7,0x3e94be57,0x3de23eae,0xbe573e94,0xbeb78000,0xbe57be94,
0x3eae3de2,0x3e573e94,0x3eb7,0xbe573e94,0x3de2beae,0x3e94be57,0x3eb78000,0x3e943e57,0xbe57be94,0xbde2beae,0xbeb7,0x3de2beae,0xbe943e57,0xbeae3de2,0xbeb78000,0xbeaebde2,
0xbe57be94,0x3e57be94,0x3eae3de2,0x3eb7,0xbe943e57,0xbe94be57,0x3de2beae,0x3eb78000,0x3eae3de2,0x3de23eae,0xbe573e94,0xbeb70000,0x3de2beae,0x3eaebde2,0x3e943e57,0x3eb7,
0xbeae3de2,0xbeaebde2,0xbe57be94,0xbeb7,0x3de23eae,0xbde23eae,0xbe943e57,0xbeb78000,0x3e57be94,0x3e94be57,0x3eaebde2,0x3eb70000,0xbe94be57,0xbe57be94,0xbde2beae,0xbeb7,
0x3eb7,0x3eb7,0x3eb7,0x3eb7,0x3eb78000,0x3eb78000,0x3eb78000,0x3eb78000,0xbeae3de2,0xbe943e57,0xbe573e94,0xbde23eae,0x3de23eae,0x3e573e94,0x3e943e57,0x3eae3de2,
0xbe57be94,0xbeaebde2,0xbeae3de2,0xbe573e94,0xbe943e57,0xbde23eae,0x3de23eae,0x3e943e57,0x3e57be94,0xbde2beae,0xbeaebde2,0xbe943e57,0xbe94be57,0xbeae3de2,0xbde23eae,0x3e573e94,
0,0,0,0,0,0,0,0,0,0,0,0,0,0,0,0,
0,0,0,0,0,0,0,0,0,0,0,0,0,0,0,0,
0x3eae3de2,0x3e57be94,0xbe57be94,0xbeae3de2,0x3de2beae,0xbe94be57,0xbe943e57,0x3de23eae,0x3eb7,0x3eb70000,0xbeb7,0xbeb70000,0x3eb78000,0xbeb7,0xbeb78000,0x3eb7,
0xbeae3de2,0x3e573e94,0x3e57be94,0xbeaebde2,0x3de23eae,0x3e94be57,0xbe94be57,0xbde23eae,0xbe57be94,0xbde23eae,0x3eaebde2,0xbe94be57,0xbe943e57,0x3eae3de2,0xbde2beae,0xbe573e94,
0,0,0,0,0,0,0,0,0,0,0,0,0,0,0,0,
0,0,0,0,0,0,0,0,0,0,0,0,0,0,0,0,
0x3e57be94,0xbeae3de2,0x3eae3de2,0xbe57be94,0xbe94be57,0x3de23eae,0x3de2beae,0xbe943e57,0x3eae3de2,0xbe94be57,0x3e573e94,0xbde2beae,0x3de2beae,0xbe573e94,0x3e94be57,0xbeae3de2,
0x3eb7,0xbeb7,0x3eb7,0xbeb7,0x3eb78000,0xbeb78000,0x3eb78000,0xbeb78000,0xbeae3de2,0x3e94be57,0xbe573e94,0x3de2beae,0x3de23eae,0xbe57be94,0x3e943e57,0xbeaebde2,
0,0,0,0,0,0,0,0,0,0,0,0,0,0,0,0,
0,0,0,0,0,0,0,0,0,0,0,0,0,0,0,0,
0xbe57be94,0x3eae3de2,0xbeae3de2,0x3e57be94,0xbe943e57,0x3de2beae,0x3de23eae,0xbe94be57,0x3e57be94,0x3de23eae,0xbeaebde2,0x3e94be57,0xbe94be57,0x3eaebde2,0xbde23eae,0xbe57be94,
0x3eae3de2,0xbe573e94,0xbe57be94,0x3eaebde2,0x3de2beae,0x3e943e57,0xbe943e57,0xbde2beae,0x3eb7,0xbeb70000,0xbeb7,0x3eb70000,0x3eb78000,0x3eb7,0xbeb78000,0xbeb7,
0,0,0,0,0,0,0,0,0,0,0,0,0,0,0,0,
0,0,0,0,0,0,0,0,0,0,0,0,0,0,0,0,
0xbeae3de2,0xbe57be94,0x3e57be94,0x3eae3de2,0x3de23eae,0xbe943e57,0xbe94be57,0x3de2beae,0xbe57be94,0x3de2beae,0x3eaebde2,0x3e943e57,0xbe943e57,0xbeaebde2,0xbde2beae,0x3e57be94,
0x3e57be94,0x3eaebde2,0x3eae3de2,0x3e573e94,0xbe94be57,0xbde2beae,0x3de2beae,0x3e94be57,0x3eae3de2,0x3e943e57,0x3e573e94,0x3de23eae,0x3de2beae,0x3e57be94,0x3e94be57,0x3eaebde2,
0,0,0,0,0,0,0,0,0,0,0,0,0,0,0,0,
0,0,0,0,0,0,0,0,0,0,0,0,0,0,0,0,
0,0,0,0,0,0,0,0,0,0,0,0,0,0,0,0,
0,0,0,0,0,0,0,0,0,0,0,0,0,0,0,0,
0x3eb7,0x3eb7,0x3eb7,0x3eb7,0x3eb78000,0x3eb78000,0x3eb78000,0x3eb78000,0xbeae3de2,0xbe943e57,0xbe573e94,0xbde23eae,0x3de23eae,0x3e573e94,0x3e943e57,0x3eae3de2,
0xbe57be94,0xbeaebde2,0xbeae3de2,0xbe573e94,0xbe943e57,0xbde23eae,0x3de23eae,0x3e943e57,0x3e57be94,0xbde2beae,0xbeaebde2,0xbe943e57,0xbe94be57,0xbeae3de2,0xbde23eae,0x3e573e94,
0,0,0,0,0,0,0,0,0,0,0,0,0,0,0,0,
0,0,0,0,0,0,0,0,0,0,0,0,0,0,0,0,
0x3eae3de2,0x3e57be94,0xbe57be94,0xbeae3de2,0x3de2beae,0xbe94be57,0xbe943e57,0x3de23eae,0x3eb7,0x3eb70000,0xbeb7,0xbeb70000,0x3eb78000,0xbeb7,0xbeb78000,0x3eb7,
0xbeae3de2,0x3e573e94,0x3e57be94,0xbeaebde2,0x3de23eae,0x3e94be57,0xbe94be57,0xbde23eae,0xbe57be94,0xbde23eae,0x3eaebde2,0xbe94be57,0xbe943e57,0x3eae3de2,0xbde2beae,0xbe573e94,
0,0,0,0,0,0,0,0,0,0,0,0,0,0,0,0,
0,0,0,0,0,0,0,0,0,0,0,0,0,0,0,0,
0x3e57be94,0xbeae3de2,0x3eae3de2,0xbe57be94,0xbe94be57,0x3de23eae,0x3de2beae,0xbe943e57,0x3eae3de2,0xbe94be57,0x3e573e94,0xbde2beae,0x3de2beae,0xbe573e94,0x3e94be57,0xbeae3de2,
0x3eb7,0xbeb7,0x3eb7,0xbeb7,0x3eb78000,0xbeb78000,0x3eb78000,0xbeb78000,0xbeae3de2,0x3e94be57,0xbe573e94,0x3de2beae,0x3de23eae,0xbe57be94,0x3e943e57,0xbeaebde2,
0,0,0,0,0,0,0,0,0,0,0,0,0,0,0,0,
0,0,0,0,0,0,0,0,0,0,0,0,0,0,0,0,
0xbe57be94,0x3eae3de2,0xbeae3de2,0x3e57be94,0xbe943e57,0x3de2beae,0x3de23eae,0xbe94be57,0x3e57be94,0x3de23eae,0xbeaebde2,0x3e94be57,0xbe94be57,0x3eaebde2,0xbde23eae,0xbe57be94,
0x3eae3de2,0xbe573e94,0xbe57be94,0x3eaebde2,0x3de2beae,0x3e943e57,0xbe943e57,0xbde2beae,0x3eb7,0xbeb70000,0xbeb7,0x3eb70000,0x3eb78000,0x3eb7,0xbeb78000,0xbeb7,
0,0,0,0,0,0,0,0,0,0,0,0,0,0,0,0,
0,0,0,0,0,0,0,0,0,0,0,0,0,0,0,0,
0xbeae3de2,0xbe57be94,0x3e57be94,0x3eae3de2,0x3de23eae,0xbe943e57,0xbe94be57,0x3de2beae,0xbe57be94,0x3de2beae,0x3eaebde2,0x3e943e57,0xbe943e57,0xbeaebde2,0xbde2beae,0x3e57be94,
0x3e57be94,0x3eaebde2,0x3eae3de2,0x3e573e94,0xbe94be57,0xbde2beae,0x3de2beae,0x3e94be57,0x3eae3de2,0x3e943e57,0x3e573e94,0x3de23eae,0x3de2beae,0x3e57be94,0x3e94be57,0x3eaebde2,
};
__device__ __align__(128) const uint32_t TAB_P3[4288] = {
0,0,0,0,0,0,0,0,0,0,0,0,0,0,0,0,
0x80003e83,0xbe79bda2,0x3e1abe54,0x3e1a3e54,0x3e830000,0xbda23e79,0xbe54be1a,0x3e54be1a,0x80003e83,0xbe54be1a,0x3e79bda2,0xbda23e79,0x3e830000,0xbe1a3e54,0xbda2be79,0x3e793da2,
0,0,0,0,0,0,0,0,0,0,0,0,0,0,0,0,
0xbe793da2,0x8000be83,0x3e793da2,0xbe1a3e54,0x3da23e79,0xbe830000,0x3da2be79,0x3e543e1a,0xbe1abe54,0x3e830000,0xbe1a3e54,0xbda2be79,0xbe543e1a,0xbe83,0x3e543e1a,0xbe793da2,
0x80003e83,0xbe1abe54,0x3e793da2,0xbe793da2,0x3e830000,0xbe543e1a,0x3da2be79,0x3da23e79,0x80003e83,0xbda2be79,0x3e1a3e54,0xbe54be1a,0x3e830000,0xbe793da2,0x3e54be1a,0xbe1a3e54,
0x80003e83,0x8000be83,0x80003e83,0x8000be83,0x3e830000,0xbe830000,0x3e830000,0xbe830000,0x80003e83,0x3da2be79,0xbe1a3e54,0x3e54be1a,0x3e830000,0xbe79bda2,0x3e543e1a,0xbe1abe54,
0x3e1abe54,0x80003e83,0xbe1abe54,0x3e793da2,0xbe54be1a,0x3e830000,0xbe543e1a,0x3da2be79,0x3e793da2,0xbe830000,0x3e79bda2,0xbe543e1a,0x3da2be79,0x3e83,0xbda2be79,0x3e1a3e54,
0x80003e83,0x8000be83,0x80003e83,0x8000be83,0x3e830000,0xbe830000,0x3e830000,0xbe830000,0xbe793da2,0x3e830000,0xbe79bda2,0x3e543e1a,0x3da23e79,0xbe83,0xbda23e79,0x3e1abe54,
0x80003e83,0x3e1abe54,0xbe793da2,0x3e793da2,0x3e830000,0xbe54be1a,0x3da23e79,0x3da2be79,0x80003e83,0x3e54be1a,0xbe79bda2,0x3da23e79,0x3e830000,0xbe1abe54,0xbda23e79,0x3e79bda2,
0x80003e83,0x3e79bda2,0xbe1abe54,0xbe1a3e54,0x3e830000,0xbda2be79,0xbe543e1a,0x3e543e1a,0x80003e83,0x3e830000,0x8000be83,0xbe830000,0x3e830000,0xbe83,0xbe830000,0x3e83,
0xbe1abe54,0x80003e83,0x3e1abe54,0xbe793da2,0xbe543e1a,0x3e830000,0xbe54be1a,0x3da23e79,0x3e1abe54,0xbe830000,0x3e1a3e54,0x3da2be79,0xbe54be1a,0x3e83,0x3e54be1a,0xbe79bda2,
0x3e793da2,0x8000be83,0xbe793da2,0x3e1a3e54,0x3da2be79,0xbe830000,0x3da23e79,0x3e54be1a,0x80003e83,0x3e830000,0x8000be83,0xbe830000,0x3e830000,0xbe83,0xbe830000,0x3e83,
0x80003e83,0x3e793da2,0x3e1abe54,0xbe1abe54,0x3e830000,0x3da2be79,0xbe54be1a,0xbe543e1a,0x80003e83,0x3e543e1a,0x3e79bda2,0x3da2be79,0x3e830000,0x3e1abe54,0xbda2be79,0xbe79bda2,
0x80003e83,0x3e1a3e54,0x3e793da2,0x3e79bda2,0x3e830000,0x3e54be1a,0x3da2be79,0xbda2be79,0x80003e83,0x3da23e79,0x3e1a3e54,0x3e543e1a,0x3e830000,0x3e79bda2,0x3e54be1a,0x3e1abe54,
0xbe793da2,0x80003e83,0x3e793da2,0x3e1abe54,0x3da23e79,0x3e830000,0x3da2be79,0xbe54be1a,0xbe1abe54,0xbe830000,0xbe1a3e54,0x3da23e79,0xbe543e1a,0x3e83,0x3e543e1a,0x3e79bda2,
0x3e1abe54,0x8000be83,0xbe1abe54,0xbe79bda2,0xbe54be1a,0xbe830000,0xbe543e1a,0xbda23e79,0x3e793da2,0x3e830000,0x3e79bda2,0x3e54be1a,0x3da2be79,0xbe83,0xbda2be79,0xbe1abe54,
0,0,0,0,0,0,0,0,0,0,0,0,0,0,0,0,
0,0,0,0,0,0,0,0,0,0,0,0,0,0,0,0,
0,0,0,0,0,0,0,0,0,0,0,0,0,0,0,0,
0xbe1abe54,0x3e79bda2,0x80003e83,0xbe79bda2,0xbe543e1a,0xbda2be79,0x3e830000,0xbda23e79,0x3e793da2,0xbe543e1a,0x8000be83,0x3e543e1a,0x3da2be79,0x3e1a3e54,0xbe830000,0x3e1abe54,
0,0,0,0,0,0,0,0,0,0,0,0,0,0,0,0,
0,0,0,0,0,0,0,0,0,0,0,0,0,0,0,0,
0xbe793da2,0x3e1abe54,0x80003e83,0xbe1abe54,0x3da23e79,0xbe54be1a,0x3e830000,0xbe543e1a,0x3e1abe54,0xbda23e79,0x8000be83,0x3da23e79,0xbe54be1a,0x3e793da2,0xbe830000,0x3e79bda2,
0x80003e83,0x8000be83,0x80003e83,0x8000be83,0x3e830000,0xbe830000,0x3e830000,0xbe830000,0xbe1abe54,0x3da23e79,0x8000be83,0xbda23e79,0xbe543e1a,0x3e79bda2,0xbe830000,0x3e793da2,
0,0,0,0,0,0,0,0,0,0,0,0,0,0,0,0,
0,0,0,0,0,0,0,0,0,0,0,0,0,0,0,0,
0x3e793da2,0xbe1abe54,0x80003e83,0x3e1abe54,0x3da2be79,0xbe543e1a,0x3e830000,0xbe54be1a,0xbe793da2,0x3e543e1a,0x8000be83,0xbe543e1a,0x3da23e79,0x3e1abe54,0xbe830000,0x3e1a3e54,
0x3e1abe54,0xbe79bda2,0x80003e83,0x3e79bda2,0xbe54be1a,0xbda23e79,0x3e830000,0xbda2be79,0x80003e83,0x3e830000,0x8000be83,0xbe830000,0x3e830000,0xbe83,0xbe830000,0x3e83,
0,0,0,0,0,0,0,0,0,0,0,0,0,0,0,0,
0,0,0,0,0,0,0,0,0,0,0,0,0,0,0,0,
0xbe1abe54,0xbe793da2,0x80003e83,0x3e793da2,0xbe543e1a,0x3da23e79,0x3e830000,0x3da2be79,0x3e793da2,0x3e54be1a,0x8000be83,0xbe54be1a,0x3da2be79,0xbe1abe54,0xbe830000,0xbe1a3e54,
0xbe793da2,0xbe1a3e54,0x80003e83,0x3e1a3e54,0x3da23e79,0x3e543e1a,0x3e830000,0x3e54be1a,0x3e1abe54,0x3da2be79,0x8000be83,0xbda2be79,0xbe54be1a,0xbe79bda2,0xbe830000,0xbe793da2,
0,0,0,0,0,0,0,0,0,0,0,0,0,0,0,0,
0x3e1abe54,0x3e1a3e54,0xbe793da2,0x8000be83,0xbe54be1a,0x3e54be1a,0x3da23e79,0xbe830000,0xbe793da2,0x3da2be79,0x3e1a3e54,0xbe830000,0x3da23e79,0xbe79bda2,0x3e54be1a,0x3e83,
0,0,0,0,0,0,0,0,0,0,0,0,0,0,0,0,
0x3e793da2,0xbe1a3e54,0xbe1abe54,0x3e79bda2,0x3da2be79,0x3e543e1a,0xbe543e1a,0xbda2be79,0x3e1abe54,0x3da23e79,0xbe79bda2,0x3e54be1a,0xbe54be1a,0x3e79bda2,0xbda23e79,0xbe1abe54,
0x3e793da2,0xbe793da2,0x3e1abe54,0x80003e83,0x3da2be79,0x3da23e79,0xbe54be1a,0x3e830000,0xbe1abe54,0x3e543e1a,0xbe79bda2,0x3e830000,0xbe543e1a,0x3e1abe54,0xbda23e79,0xbe83,
0x80003e83,0x8000be83,0x80003e83,0x8000be83,0x3e830000,0xbe830000,0x3e830000,0xbe830000,0x3e1abe54,0xbe543e1a,0x3e79bda2,0xbe830000,0xbe54be1a,0x3e1a3e54,0xbda2be79,0x3e83,
0xbe1abe54,0x3e793da2,0xbe793da2,0x3e1abe54,0xbe543e1a,0x3da2be79,0x3da23e79,0xbe54be1a,0xbe793da2,0x3e54be1a,0xbe1a3e54,0x3da2be79,0x3da23e79,0xbe1abe54,0x3e543e1a,0xbe79bda2,
0x80003e83,0x8000be83,0x80003e83,0x8000be83,0x3e830000,0xbe830000,0x3e830000,0xbe830000,0x3e793da2,0xbe54be1a,0x3e1a3e54,0xbda2be79,0x3da2be79,0xbe1a3e54,0x3e54be1a,0xbe793da2,
0xbe793da2,0x3e793da2,0xbe1abe54,0x80003e83,0x3da23e79,0x3da2be79,0xbe543e1a,0x3e830000,0x3e793da2,0xbda2be79,0xbe1a3e54,0x3e830000,0x3da2be79,0xbe793da2,0x3e543e1a,0xbe83,
0xbe1abe54,0xbe1a3e54,0x3e793da2,0x8000be83,0xbe543e1a,0x3e543e1a,0x3da2be79,0xbe830000,0x80003e83,0x3e830000,0x8000be83,0xbe830000,0x3e830000,0xbe83,0xbe830000,0x3e83,
0x3e1abe54,0xbe793da2,0x3e793da2,0xbe1abe54,0xbe54be1a,0x3da23e79,0x3da2be79,0xbe543e1a,0xbe1abe54,0xbda23e79,0x3e79bda2,0xbe54be1a,0xbe543e1a,0x3e793da2,0xbda2be79,0xbe1a3e54,
0xbe793da2,0x3e1a3e54,0x3e1abe54,0xbe79bda2,0x3da23e79,0x3e54be1a,0xbe54be1a,0xbda23e79,0x80003e83,0x3e830000,0x8000be83,0xbe830000,0x3e830000,0xbe83,0xbe830000,0x3e83,
0x3e1abe54,0xbe1abe54,0xbe793da2,0x80003e83,0xbe54be1a,0xbe543e1a,0x3da23e79,0x3e830000,0xbe793da2,0xbda23e79,0x3e1a3e54,0x3e830000,0x3da23e79,0x3e793da2,0x3e54be1a,0xbe83,
0x3e793da2,0x3e79bda2,0x3e1abe54,0x8000be83,0x3da2be79,0xbda2be79,0xbe54be1a,0xbe830000,0xbe1abe54,0xbe54be1a,0xbe79bda2,0xbe830000,0xbe543e1a,0xbe1a3e54,0xbda23e79,0x3e83,
0x3e793da2,0x3e1abe54,0xbe1abe54,0xbe793da2,0x3da2be79,0xbe54be1a,0xbe543e1a,0x3da23e79,0x3e1abe54,0xbda2be79,0xbe79bda2,0xbe543e1a,0xbe54be1a,0xbe793da2,0xbda23e79,0x3e1a3e54,
0xbe1abe54,0xbe79bda2,0xbe793da2,0xbe1a3e54,0xbe543e1a,0xbda23e79,0x3da23e79,0x3e543e1a,0xbe793da2,0xbe543e1a,0xbe1a3e54,0xbda23e79,0x3da23e79,0x3e1a3e54,0x3e543e1a,0x3e793da2,
0xbe163dda,0,0,0,0,0xbe163dda,0,0,0,0,0xbe163dda,0,0,0,0,0xbe163dda,
0xbe253da8,0,0,0,0,0xbe253da8,0,0,0,0,0xbe253da8,0,0,0,0,0xbe253da8,
0xbd65be30,0,0,0,0,0xbd65be30,0,0,0,0,0xbd65be30,0,0,0,0,0xbd65be30,
0x3ce8be37,0,0,0,0,0x3ce8be37,0,0,0,0,0x3ce8be37,0,0,0,0,0x3ce8be37,
0xbe303d65,0,0,0,0,0xbe303d65,0,0,0,0,0xbe303d65,0,0,0,0,0xbe303d65,
0xbe373ce8,0,0,0,0,0xbe373ce8,0,0,0,0,0xbe373ce8,0,0,0,0,0xbe373ce8,
0x3ddabe16,0,0,0,0,0x3ddabe16,0,0,0,0,0x3ddabe16,0,0,0,0,0x3ddabe16,
0x3e25bda8,0,0,0,0,0x3e25bda8,0,0,0,0,0x3e25bda8,0,0,0,0,0x3e25bda8,
0xbe390000,0,0,0,0,0xbe390000,0,0,0,0,0xbe390000,0,0,0,0,0xbe390000,
0xbe37bce8,0,0,0,0,0xbe37bce8,0,0,0,0,0xbe37bce8,0,0,0,0,0xbe37bce8,
0x3e390000,0,0,0,0,0x3e390000,0,0,0,0,0x3e390000,0,0,0,0,0x3e390000,
0x3e253da8,0,0,0,0,0x3e253da8,0,0,0,0,0x3e253da8,0,0,0,0,0x3e253da8,
0xbe30bd65,0,0,0,0,0xbe30bd65,0,0,0,0,0xbe30bd65,0,0,0,0,0xbe30bd65,
0xbe25bda8,0,0,0,0,0xbe25bda8,0,0,0,0,0xbe25bda8,0,0,0,0,0xbe25bda8,
0x3dda3e16,0,0,0,0,0x3dda3e16,0,0,0,0,0x3dda3e16,0,0,0,0,0x3dda3e16,
0x3ce83e37,0,0,0,0,0x3ce83e37,0,0,0,0,0x3ce83e37,0,0,0,0,0x3ce83e37,
0xbe16bdda,0,0,0,0,0xbe16bdda,0,0,0,0,0xbe16bdda,0,0,0,0,0xbe16bdda,
0xbe03be03,0,0,0,0,0xbe03be03,0,0,0,0,0xbe03be03,0,0,0,0,0xbe03be03,
0xbd653e30,0,0,0,0,0xbd653e30,0,0,0,0,0xbd653e30,0,0,0,0,0xbd653e30,
0xbe033e03,0,0,0,0,0xbe033e03,0,0,0,0,0xbe033e03,0,0,0,0,0xbe033e03,
0xbddabe16,0,0,0,0,0xbddabe16,0,0,0,0,0xbddabe16,0,0,0,0,0xbddabe16,
0xbda8be25,0,0,0,0,0xbda8be25,0,0,0,0,0xbda8be25,0,0,0,0,0xbda8be25,
0xbe303d65,0,0,0,0,0xbe303d65,0,0,0,0,0xbe303d65,0,0,0,0,0xbe303d65,
0xbe37bce8,0,0,0,0,0xbe37bce8,0,0,0,0,0xbe37bce8,0,0,0,0,0xbe37bce8,
0xbd65be30,0,0,0,0,0xbd65be30,0,0,0,0,0xbd65be30,0,0,0,0,0xbd65be30,
0xbce8be37,0,0,0,0,0xbce8be37,0,0,0,0,0xbce8be37,0,0,0,0,0xbce8be37,
0xbe16bdda,0,0,0,0,0xbe16bdda,0,0,0,0,0xbe16bdda,0,0,0,0,0xbe16bdda,
0xbda8be25,0,0,0,0,0xbda8be25,0,0,0,0,0xbda8be25,0,0,0,0,0xbda8be25,
0x3e390000,0,0,0,0,0x3e390000,0,0,0,0,0x3e390000,0,0,0,0,0x3e390000,
0x3e033e03,0,0,0,0,0x3e033e03,0,0,0,0,0x3e033e03,0,0,0,0,0x3e033e03,
0xbd653e30,0,0,0,0,0xbd653e30,0,0,0,0,0xbd653e30,0,0,0,0,0xbd653e30,
0xbe373ce8,0,0,0,0,0xbe373ce8,0,0,0,0,0xbe373ce8,0,0,0,0,0xbe373ce8,
0x80003e39,0,0,0,0,0x80003e39,0,0,0,0,0x80003e39,0,0,0,0,0x80003e39,
0xbe033e03,0,0,0,0,0xbe033e03,0,0,0,0,0xbe033e03,0,0,0,0,0xbe033e03,
0xbddabe16,0,0,0,0,0xbddabe16,0,0,0,0,0xbddabe16,0,0,0,0,0xbddabe16,
0x3da8be25,0,0,0,0,0x3da8be25,0,0,0,0,0x3da8be25,0,0,0,0,0x3da8be25,
0xbe390000,0,0,0,0,0xbe390000,0,0,0,0,0xbe390000,0,0,0,0,0xbe390000,
0xbe03be03,0,0,0,0,0xbe03be03,0,0,0,0,0xbe03be03,0,0,0,0,0xbe03be03,
0x3e390000,0,0,0,0,0x3e390000,0,0,0,0,0x3e390000,0,0,0,0,0x3e390000,
0x3da83e25,0,0,0,0,0x3da83e25,0,0,0,0,0x3da83e25,0,0,0,0,0x3da83e25,
0x8000be39,0,0,0,0,0x8000be39,0,0,0,0,0x8000be39,0,0,0,0,0x8000be39,
0x3e03be03,0,0,0,0,0x3e03be03,0,0,0,0,0x3e03be03,0,0,0,0,0x3e03be03,
0xbdda3e16,0,0,0,0,0xbdda3e16,0,0,0,0,0xbdda3e16,0,0,0,0,0xbdda3e16,
0xbe37bce8,0,0,0,0,0xbe37bce8,0,0,0,0,0xbe37bce8,0,0,0,0,0xbe37bce8,
0x3e390000,0,0,0,0,0x3e390000,0,0,0,0,0x3e390000,0,0,0,0,0x3e390000,
0x3e033e03,0,0,0,0,0x3e033e03,0,0,0,0,0x3e033e03,0,0,0,0,0x3e033e03,
0xbd65be30,0,0,0,0,0xbd65be30,0,0,0,0,0xbd65be30,0,0,0,0,0xbd65be30,
0x3e03be03,0,0,0,0,0x3e03be03,0,0,0,0,0x3e03be03,0,0,0,0,0x3e03be03,
0x80003e39,0,0,0,0,0x80003e39,0,0,0,0,0x80003e39,0,0,0,0,0x80003e39,
0xbe033e03,0,0,0,0,0xbe033e03,0,0,0,0,0xbe033e03,0,0,0,0,0xbe033e03,
0x3e303d65,0,0,0,0,0x3e303d65,0,0,0,0,0x3e303d65,0,0,0,0,0x3e303d65,
0x3ce83e37,0,0,0,0,0x3ce83e37,0,0,0,0,0x3ce83e37,0,0,0,0,0x3ce83e37,
0xbe390000,0,0,0,0,0xbe390000,0,0,0,0,0xbe390000,0,0,0,0,0xbe390000,
0xbe03be03,0,0,0,0,0xbe03be03,0,0,0,0,0xbe03be03,0,0,0,0,0xbe03be03,
0xbe163dda,0,0,0,0,0xbe163dda,0,0,0,0,0xbe163dda,0,0,0,0,0xbe163dda,
0xbe25bda8,0,0,0,0,0xbe25bda8,0,0,0,0,0xbe25bda8,0,0,0,0,0xbe25bda8,
0xbe16bdda,0,0,0,0,0xbe16bdda,0,0,0,0,0xbe16bdda,0,0,0,0,0xbe16bdda,
0x3da8be25,0,0,0,0,0x3da8be25,0,0,0,0,0x3da8be25,0,0,0,0,0x3da8be25,
0x3e16bdda,0,0,0,0,0x3e16bdda,0,0,0,0,0x3e16bdda,0,0,0,0,0x3e16bdda,
0x3da83e25,0,0,0,0,0x3da83e25,0,0,0,0,0x3da83e25,0,0,0,0,0x3da83e25,
0x3e303d65,0,0,0,0,0x3e303d65,0,0,0,0,0x3e303d65,0,0,0,0,0x3e303d65,
0xbce83e37,0,0,0,0,0xbce83e37,0,0,0,0,0xbce83e37,0,0,0,0,0xbce83e37,
0xbe303d65,0,0,0,0,0xbe303d65,0,0,0,0,0xbe303d65,0,0,0,0,0xbe303d65,
0xbce8be37,0,0,0,0,0xbce8be37,0,0,0,0,0xbce8be37,0,0,0,0,0xbce8be37,
0xbe390000,0,0,0,0,0xbe390000,0,0,0,0,0xbe390000,0,0,0,0,0xbe390000,
0xbce8be37,0,0,0,0,0xbce8be37,0,0,0,0,0xbce8be37,0,0,0,0,0xbce8be37,
0x3e390000,0,0,0,0,0x3e390000,0,0,0,0,0x3e390000,0,0,0,0,0x3e390000,
0xbce83e37,0,0,0,0,0xbce83e37,0,0,0,0,0xbce83e37,0,0,0,0,0xbce83e37,
0x3e30bd65,0,0,0,0,0x3e30bd65,0,0,0,0,0x3e30bd65,0,0,0,0,0x3e30bd65,
0x3da83e25,0,0,0,0,0x3da83e25,0,0,0,0,0x3da83e25,0,0,0,0,0x3da83e25,
0xbe30bd65,0,0,0,0,0xbe30bd65,0,0,0,0,0xbe30bd65,0,0,0,0,0xbe30bd65,
0x3da8be25,0,0,0,0,0x3da8be25,0,0,0,0,0x3da8be25,0,0,0,0,0x3da8be25,
0xbe163dda,0,0,0,0,0xbe163dda,0,0,0,0,0xbe163dda,0,0,0,0,0xbe163dda,
0xbe03be03,0,0,0,0,0xbe03be03,0,0,0,0,0xbe03be03,0,0,0,0,0xbe03be03,
0x3e163dda,0,0,0,0,0x3e163dda,0,0,0,0,0x3e163dda,0,0,0,0,0x3e163dda,
0xbe033e03,0,0,0,0,0xbe033e03,0,0,0,0,0xbe033e03,0,0,0,0,0xbe033e03,
0x3ddabe16,0,0,0,0,0x3ddabe16,0,0,0,0,0x3ddabe16,0,0,0,0,0x3ddabe16,
0x3e253da8,0,0,0,0,0x3e253da8,0,0,0,0,0x3e253da8,0,0,0,0,0x3e253da8,
0xbddabe16,0,0,0,0,0xbddabe16,0,0,0,0,0xbddabe16,0,0,0,0,0xbddabe16,
0x3e25bda8,0,0,0,0,0x3e25bda8,0,0,0,0,0x3e25bda8,0,0,0,0,0x3e25bda8,
0xbd653e30,0,0,0,0,0xbd653e30,0,0,0,0,0xbd653e30,0,0,0,0,0xbd653e30,
0xbe37bce8,0,0,0,0,0xbe37bce8,0,0,0,0,0xbe37bce8,0,0,0,0,0xbe37bce8,
0x3d653e30,0,0,0,0,0x3d653e30,0,0,0,0,0x3d653e30,0,0,0,0,0x3d653e30,
0xbe373ce8,0,0,0,0,0xbe373ce8,0,0,0,0,0xbe373ce8,0,0,0,0,0xbe373ce8,
0x3d653e30,0,0,0,0,0x3d653e30,0,0,0,0,0x3d653e30,0,0,0,0,0x3d653e30,
0xbe37bce8,0,0,0,0,0xbe37bce8,0,0,0,0,0xbe37bce8,0,0,0,0,0xbe37bce8,
0xbe390000,0,0,0,0,0xbe390000,0,0,0,0,0xbe390000,0,0,0,0,0xbe390000,
0x3e03be03,0,0,0,0,0x3e03be03,0,0,0,0,0x3e03be03,0,0,0,0,0x3e03be03,
0x3ddabe16,0,0,0,0,0x3ddabe16,0,0,0,0,0x3ddabe16,0,0,0,0,0x3ddabe16,
0x3da83e25,0,0,0,0,0x3da83e25,0,0,0,0,0x3da83e25,0,0,0,0,0x3da83e25,
0x80003e39,0,0,0,0,0x80003e39,0,0,0,0,0x80003e39,0,0,0,0,0x80003e39,
0xbe03be03,0,0,0,0,0xbe03be03,0,0,0,0,0xbe03be03,0,0,0,0,0xbe03be03,
0xbe390000,0,0,0,0,0xbe390000,0,0,0,0,0xbe390000,0,0,0,0,0xbe390000,
0x3da8be25,0,0,0,0,0x3da8be25,0,0,0,0,0x3da8be25,0,0,0,0,0x3da8be25,
0x3e390000,0,0,0,0,0x3e390000,0,0,0,0,0x3e390000,0,0,0,0,0x3e390000,
0xbe033e03,0,0,0,0,0xbe033e03,0,0,0,0,0xbe033e03,0,0,0,0,0xbe033e03,
0x3dda3e16,0,0,0,0,0x3dda3e16,0,0,0,0,0x3dda3e16,0,0,0,0,0x3dda3e16,
0xbe373ce8,0,0,0,0,0xbe373ce8,0,0,0,0,0xbe373ce8,0,0,0,0,0xbe373ce8,
0x8000be39,0,0,0,0,0x8000be39,0,0,0,0,0x8000be39,0,0,0,0,0x8000be39,
0x3e033e03,0,0,0,0,0x3e033e03,0,0,0,0,0x3e033e03,0,0,0,0,0x3e033e03,
0x3d65be30,0,0,0,0,0x3d65be30,0,0,0,0,0x3d65be30,0,0,0,0,0x3d65be30,
0x3e033e03,0,0,0,0,0x3e033e03,0,0,0,0,0x3e033e03,0,0,0,0,0x3e033e03,
0xbe390000,0,0,0,0,0xbe390000,0,0,0,0,0xbe390000,0,0,0,0,0xbe390000,
0x3e03be03,0,0,0,0,0x3e03be03,0,0,0,0,0x3e03be03,0,0,0,0,0x3e03be03,
0xbe303d65,0,0,0,0,0xbe303d65,0,0,0,0,0xbe303d65,0,0,0,0,0xbe303d65,
0x3ce8be37,0,0,0,0,0x3ce8be37,0,0,0,0,0x3ce8be37,0,0,0,0,0x3ce8be37,
0x80003e39,0,0,0,0,0x80003e39,0,0,0,0,0x80003e39,0,0,0,0,0x80003e39,
0xbe03be03,0,0,0,0,0xbe03be03,0,0,0,0,0xbe03be03,0,0,0,0,0xbe03be03,
0x3e163dda,0,0,0,0,0x3e163dda,0,0,0,0,0x3e163dda,0,0,0,0,0x3e163dda,
0xbe253da8,0,0,0,0,0xbe253da8,0,0,0,0,0xbe253da8,0,0,0,0,0xbe253da8,
0x3e390000,0,0,0,0,0x3e390000,0,0,0,0,0x3e390000,0,0,0,0,0x3e390000,
0xbe033e03,0,0,0,0,0xbe033e03,0,0,0,0,0xbe033e03,0,0,0,0,0xbe033e03,
0x3d65be30,0,0,0,0,0x3d65be30,0,0,0,0,0x3d65be30,0,0,0,0,0x3d65be30,
0x3ce83e37,0,0,0,0,0x3ce83e37,0,0,0,0,0x3ce83e37,0,0,0,0,0x3ce83e37,
0x3e163dda,0,0,0,0,0x3e163dda,0,0,0,0,0x3e163dda,0,0,0,0,0x3e163dda,
0xbe25bda8,0,0,0,0,0xbe25bda8,0,0,0,0,0xbe25bda8,0,0,0,0,0xbe25bda8,
0xbddabe16,0,0,0,0,0xbddabe16,0,0,0,0,0xbddabe16,0,0,0,0,0xbddabe16,
0x3e253da8,0,0,0,0,0x3e253da8,0,0,0,0,0x3e253da8,0,0,0,0,0x3e253da8,
0x3e303d65,0,0,0,0,0x3e303d65,0,0,0,0,0x3e303d65,0,0,0,0,0x3e303d65,
0xbe37bce8,0,0,0,0,0xbe37bce8,0,0,0,0,0xbe37bce8,0,0,0,0,0xbe37bce8,
0xbe390000,0,0,0,0,0xbe390000,0,0,0,0,0xbe390000,0,0,0,0,0xbe390000,
0x3e25bda8,0,0,0,0,0x3e25bda8,0,0,0,0,0x3e25bda8,0,0,0,0,0x3e25bda8,
0x3e390000,0,0,0,0,0x3e390000,0,0,0,0,0x3e390000,0,0,0,0,0x3e390000,
0xbe373ce8,0,0,0,0,0xbe373ce8,0,0,0,0,0xbe373ce8,0,0,0,0,0xbe373ce8,
0xbdda3e16,0,0,0,0,0xbdda3e16,0,0,0,0,0xbdda3e16,0,0,0,0,0xbdda3e16,
0x3ce8be37,0,0,0,0,0x3ce8be37,0,0,0,0,0x3ce8be37,0,0,0,0,0x3ce8be37,
0x3e30bd65,0,0,0,0,0x3e30bd65,0,0,0,0,0x3e30bd65,0,0,0,0,0x3e30bd65,
0xbe253da8,0,0,0,0,0xbe253da8,0,0,0,0,0xbe253da8,0,0,0,0,0xbe253da8,
0x3d653e30,0,0,0,0,0x3d653e30,0,0,0,0,0x3d653e30,0,0,0,0,0x3d653e30,
0xbe03be03,0,0,0,0,0xbe03be03,0,0,0,0,0xbe03be03,0,0,0,0,0xbe03be03,
0x3e16bdda,0,0,0,0,0x3e16bdda,0,0,0,0,0x3e16bdda,0,0,0,0,0x3e16bdda,
0xbe033e03,0,0,0,0,0xbe033e03,0,0,0,0,0xbe033e03,0,0,0,0,0xbe033e03,
0x3e303d65,0,0,0,0,0x3e303d65,0,0,0,0,0x3e303d65,0,0,0,0,0x3e303d65,
0xbe373ce8,0,0,0,0,0xbe373ce8,0,0,0,0,0xbe373ce8,0,0,0,0,0xbe373ce8,
0x3ddabe16,0,0,0,0,0x3ddabe16,0,0,0,0,0x3ddabe16,0,0,0,0,0x3ddabe16,
0xbda83e25,0,0,0,0,0xbda83e25,0,0,0,0,0xbda83e25,0,0,0,0,0xbda83e25,
0x3e16bdda,0,0,0,0,0x3e16bdda,0,0,0,0,0x3e16bdda,0,0,0,0,0x3e16bdda,
0xbda83e25,0,0,0,0,0xbda83e25,0,0,0,0,0xbda83e25,0,0,0,0,0xbda83e25,
0x3d65be30,0,0,0,0,0x3d65be30,0,0,0,0,0x3d65be30,0,0,0,0,0x3d65be30,
0xbce83e37,0,0,0,0,0xbce83e37,0,0,0,0,0xbce83e37,0,0,0,0,0xbce83e37,
0,0,0xbe163dda,0,0,0,0,0xbe163dda,0,0,0xbe253da8,0,0,0,0,0xbe253da8,
0,0,0xbe303d65,0,0,0,0,0xbe303d65,0,0,0xbe373ce8,0,0,0,0,0xbe373ce8,
0,0,0xbd65be30,0,0,0,0,0xbd65be30,0,0,0x3ce8be37,0,0,0,0,0x3ce8be37,
0,0,0x3ddabe16,0,0,0,0,0x3ddabe16,0,0,0x3e25bda8,0,0,0,0,0x3e25bda8,
0,0,0xbe390000,0,0,0,0,0xbe390000,0,0,0xbe37bce8,0,0,0,0,0xbe37bce8,
0,0,0xbe30bd65,0,0,0,0,0xbe30bd65,0,0,0xbe25bda8,0,0,0,0,0xbe25bda8,
0,0,0x3e390000,0,0,0,0,0x3e390000,0,0,0x3e253da8,0,0,0,0,0x3e253da8,
0,0,0x3dda3e16,0,0,0,0,0x3dda3e16,0,0,0x3ce83e37,0,0,0,0,0x3ce83e37,
0,0,0xbe16bdda,0,0,0,0,0xbe16bdda,0,0,0xbe03be03,0,0,0,0,0xbe03be03,
0,0,0xbddabe16,0,0,0,0,0xbddabe16,0,0,0xbda8be25,0,0,0,0,0xbda8be25,
0,0,0xbd653e30,0,0,0,0,0xbd653e30,0,0,0xbe033e03,0,0,0,0,0xbe033e03,
0,0,0xbe303d65,0,0,0,0,0xbe303d65,0,0,0xbe37bce8,0,0,0,0,0xbe37bce8,
0,0,0xbd65be30,0,0,0,0,0xbd65be30,0,0,0xbce8be37,0,0,0,0,0xbce8be37,
0,0,0,0,0,0,0,0,0,0,0,0,0,0,0,0,
0,0,0xbe16bdda,0,0,0,0,0xbe16bdda,0,0,0xbda8be25,0,0,0,0,0xbda8be25,
0,0,0,0,0,0,0,0,0,0,0,0,0,0,0,0,
0,0,0x3e390000,0,0,0,0,0x3e390000,0,0,0x3e033e03,0,0,0,0,0x3e033e03,
0,0,0x80003e39,0,0,0,0,0x80003e39,0,0,0xbe033e03,0,0,0,0,0xbe033e03,
0,0,0xbd653e30,0,0,0,0,0xbd653e30,0,0,0xbe373ce8,0,0,0,0,0xbe373ce8,
0,0,0xbddabe16,0,0,0,0,0xbddabe16,0,0,0x3da8be25,0,0,0,0,0x3da8be25,
0,0,0xbe390000,0,0,0,0,0xbe390000,0,0,0xbe03be03,0,0,0,0,0xbe03be03,
0,0,0x8000be39,0,0,0,0,0x8000be39,0,0,0x3e03be03,0,0,0,0,0x3e03be03,
0,0,0x3e390000,0,0,0,0,0x3e390000,0,0,0x3da83e25,0,0,0,0,0x3da83e25,
0,0,0xbdda3e16,0,0,0,0,0xbdda3e16,0,0,0xbe37bce8,0,0,0,0,0xbe37bce8,
0,0,0x3e390000,0,0,0,0,0x3e390000,0,0,0x3e033e03,0,0,0,0,0x3e033e03,
0,0,0x80003e39,0,0,0,0,0x80003e39,0,0,0xbe033e03,0,0,0,0,0xbe033e03,
0,0,0xbd65be30,0,0,0,0,0xbd65be30,0,0,0x3e03be03,0,0,0,0,0x3e03be03,
0,0,0x3e303d65,0,0,0,0,0x3e303d65,0,0,0x3ce83e37,0,0,0,0,0x3ce83e37,
0,0,0xbe390000,0,0,0,0,0xbe390000,0,0,0xbe03be03,0,0,0,0,0xbe03be03,
0,0,0,0,0,0,0,0,0,0,0,0,0,0,0,0,
0,0,0xbe163dda,0,0,0,0,0xbe163dda,0,0,0xbe25bda8,0,0,0,0,0xbe25bda8,
0,0,0,0,0,0,0,0,0,0,0,0,0,0,0,0,
0,0,0xbe16bdda,0,0,0,0,0xbe16bdda,0,0,0x3da8be25,0,0,0,0,0x3da8be25,
0,0,0x3e303d65,0,0,0,0,0x3e303d65,0,0,0xbce83e37,0,0,0,0,0xbce83e37,
0,0,0x3e16bdda,0,0,0,0,0x3e16bdda,0,0,0x3da83e25,0,0,0,0,0x3da83e25,
0,0,0xbe303d65,0,0,0,0,0xbe303d65,0,0,0xbce8be37,0,0,0,0,0xbce8be37,
0,0,0xbe390000,0,0,0,0,0xbe390000,0,0,0xbce8be37,0,0,0,0,0xbce8be37,
0,0,0x3e30bd65,0,0,0,0,0x3e30bd65,0,0,0x3da83e25,0,0,0,0,0x3da83e25,
0,0,0x3e390000,0,0,0,0,0x3e390000,0,0,0xbce83e37,0,0,0,0,0xbce83e37,
0,0,0xbe30bd65,0,0,0,0,0xbe30bd65,0,0,0x3da8be25,0,0,0,0,0x3da8be25,
0,0,0xbe163dda,0,0,0,0,0xbe163dda,0,0,0xbe03be03,0,0,0,0,0xbe03be03,
0,0,0x3ddabe16,0,0,0,0,0x3ddabe16,0,0,0x3e253da8,0,0,0,0,0x3e253da8,
0,0,0x3e163dda,0,0,0,0,0x3e163dda,0,0,0xbe033e03,0,0,0,0,0xbe033e03,
0,0,0xbddabe16,0,0,0,0,0xbddabe16,0,0,0x3e25bda8,0,0,0,0,0x3e25bda8,
0,0,0xbd653e30,0,0,0,0,0xbd653e30,0,0,0xbe37bce8,0,0,0,0,0xbe37bce8,
0,0,0,0,0,0,0,0,0,0,0,0,0,0,0,0,
0,0,0x3d653e30,0,0,0,0,0x3d653e30,0,0,0xbe373ce8,0,0,0,0,0xbe373ce8,
0,0,0,0,0,0,0,0,0,0,0,0,0,0,0,0,
0,0,0x3d653e30,0,0,0,0,0x3d653e30,0,0,0xbe37bce8,0,0,0,0,0xbe37bce8,
0,0,0x3ddabe16,0,0,0,0,0x3ddabe16,0,0,0x3da83e25,0,0,0,0,0x3da83e25,
0,0,0xbe390000,0,0,0,0,0xbe390000,0,0,0x3e03be03,0,0,0,0,0x3e03be03,
0,0,0x80003e39,0,0,0,0,0x80003e39,0,0,0xbe03be03,0,0,0,0,0xbe03be03,
0,0,0xbe390000,0,0,0,0,0xbe390000,0,0,0x3da8be25,0,0,0,0,0x3da8be25,
0,0,0x3dda3e16,0,0,0,0,0x3dda3e16,0,0,0xbe373ce8,0,0,0,0,0xbe373ce8,
0,0,0x3e390000,0,0,0,0,0x3e390000,0,0,0xbe033e03,0,0,0,0,0xbe033e03,
0,0,0x8000be39,0,0,0,0,0x8000be39,0,0,0x3e033e03,0,0,0,0,0x3e033e03,
0,0,0x3d65be30,0,0,0,0,0x3d65be30,0,0,0x3e033e03,0,0,0,0,0x3e033e03,
0,0,0xbe303d65,0,0,0,0,0xbe303d65,0,0,0x3ce8be37,0,0,0,0,0x3ce8be37,
0,0,0xbe390000,0,0,0,0,0xbe390000,0,0,0x3e03be03,0,0,0,0,0x3e03be03,
0,0,0x80003e39,0,0,0,0,0x80003e39,0,0,0xbe03be03,0,0,0,0,0xbe03be03,
0,0,0x3e163dda,0,0,0,0,0x3e163dda,0,0,0xbe253da8,0,0,0,0,0xbe253da8,
0,0,0,0,0,0,0,0,0,0,0,0,0,0,0,0,
0,0,0x3e390000,0,0,0,0,0x3e390000,0,0,0xbe033e03,0,0,0,0,0xbe033e03,
0,0,0,0,0,0,0,0,0,0,0,0,0,0,0,0,
0,0,0x3d65be30,0,0,0,0,0x3d65be30,0,0,0x3ce83e37,0,0,0,0,0x3ce83e37,
0,0,0xbddabe16,0,0,0,0,0xbddabe16,0,0,0x3e253da8,0,0,0,0,0x3e253da8,
0,0,0x3e163dda,0,0,0,0,0x3e163dda,0,0,0xbe25bda8,0,0,0,0,0xbe25bda8,
0,0,0x3e303d65,0,0,0,0,0x3e303d65,0,0,0xbe37bce8,0,0,0,0,0xbe37bce8,
0,0,0xbe390000,0,0,0,0,0xbe390000,0,0,0x3e25bda8,0,0,0,0,0x3e25bda8,
0,0,0xbdda3e16,0,0,0,0,0xbdda3e16,0,0,0x3ce8be37,0,0,0,0,0x3ce8be37,
0,0,0x3e390000,0,0,0,0,0x3e390000,0,0,0xbe373ce8,0,0,0,0,0xbe373ce8,
0,0,0x3e30bd65,0,0,0,0,0x3e30bd65,0,0,0xbe253da8,0,0,0,0,0xbe253da8,
0,0,0x3d653e30,0,0,0,0,0x3d653e30,0,0,0xbe03be03,0,0,0,0,0xbe03be03,
0,0,0x3e303d65,0,0,0,0,0x3e303d65,0,0,0xbe373ce8,0,0,0,0,0xbe373ce8,
0,0,0x3e16bdda,0,0,0,0,0x3e16bdda,0,0,0xbe033e03,0,0,0,0,0xbe033e03,
0,0,0x3ddabe16,0,0,0,0,0x3ddabe16,0,0,0xbda83e25,0,0,0,0,0xbda83e25,
0,0,0x3e16bdda,0,0,0,0,0x3e16bdda,0,0,0xbda83e25,0,0,0,0,0xbda83e25,
0,0,0,0,0,0,0,0,0,0,0,0,0,0,0,0,
0,0,0x3d65be30,0,0,0,0,0x3d65be30,0,0,0xbce83e37,0,0,0,0,0xbce83e37,
0,0,0,0,0,0,0,0,0,0,0,0,0,0,0,0,
};
constexpr unsigned long long COS_PK0 = 0x3f903f9a3fa03fa2ull;
constexpr unsigned long long COS_PK1 = 0x3f133f3e3f653f83ull;
constexpr unsigned long long COS_PK2 = 0x3e4b3ec8ull;

__device__ __forceinline__ void wgmma_ss_n80_z(float (&d)[40], uint64_t da, uint64_t db) {
  asm volatile("{\n.reg .pred p;\nsetp.ne.b32 p, 0, 0;\nwgmma.mma_async.sync.aligned.m64n80k16.f32.bf16.bf16 {%0,%1,%2,%3,%4,%5,%6,%7,%8,%9,%10,%11,%12,%13,%14,%15,%16,%17,%18,%19,%20,%21,%22,%23,%24,%25,%26,%27,%28,%29,%30,%31,%32,%33,%34,%35,%36,%37,%38,%39}, %40, %41, p, 1, 1, 1, 0;\n}\n"
    : "+f"(d[0]), "+f"(d[1]), "+f"(d[2]), "+f"(d[3]), "+f"(d[4]), "+f"(d[5]), "+f"(d[6]), "+f"(d[7]), "+f"(d[8]), "+f"(d[9]), "+f"(d[10]), "+f"(d[11]), "+f"(d[12]), "+f"(d[13]), "+f"(d[14]), "+f"(d[15]), "+f"(d[16]), "+f"(d[17]), "+f"(d[18]), "+f"(d[19]), "+f"(d[20]), "+f"(d[21]), "+f"(d[22]), "+f"(d[23]), "+f"(d[24]), "+f"(d[25]), "+f"(d[26]), "+f"(d[27]), "+f"(d[28]), "+f"(d[29]), "+f"(d[30]), "+f"(d[31]), "+f"(d[32]), "+f"(d[33]), "+f"(d[34]), "+f"(d[35]), "+f"(d[36]), "+f"(d[37]), "+f"(d[38]), "+f"(d[39])
    : "l"(da), "l"(db));
}
__device__ __forceinline__ void wgmma_ss_n80_a(float (&d)[40], uint64_t da, uint64_t db) {
  asm volatile("{\n.reg .pred p;\nsetp.ne.b32 p, 1, 0;\nwgmma.mma_async.sync.aligned.m64n80k16.f32.bf16.bf16 {%0,%1,%2,%3,%4,%5,%6,%7,%8,%9,%10,%11,%12,%13,%14,%15,%16,%17,%18,%19,%20,%21,%22,%23,%24,%25,%26,%27,%28,%29,%30,%31,%32,%33,%34,%35,%36,%37,%38,%39}, %40, %41, p, 1, 1, 1, 0;\n}\n"
    : "+f"(d[0]), "+f"(d[1]), "+f"(d[2]), "+f"(d[3]), "+f"(d[4]), "+f"(d[5]), "+f"(d[6]), "+f"(d[7]), "+f"(d[8]), "+f"(d[9]), "+f"(d[10]), "+f"(d[11]), "+f"(d[12]), "+f"(d[13]), "+f"(d[14]), "+f"(d[15]), "+f"(d[16]), "+f"(d[17]), "+f"(d[18]), "+f"(d[19]), "+f"(d[20]), "+f"(d[21]), "+f"(d[22]), "+f"(d[23]), "+f"(d[24]), "+f"(d[25]), "+f"(d[26]), "+f"(d[27]), "+f"(d[28]), "+f"(d[29]), "+f"(d[30]), "+f"(d[31]), "+f"(d[32]), "+f"(d[33]), "+f"(d[34]), "+f"(d[35]), "+f"(d[36]), "+f"(d[37]), "+f"(d[38]), "+f"(d[39])
    : "l"(da), "l"(db));
}

__device__ __forceinline__ void wgmma_rs_n40_z(float (&d)[20], uint32_t a0, uint32_t a1, uint32_t a2, uint32_t a3, uint64_t db) {
  asm volatile("{\n.reg .pred p;\nsetp.ne.b32 p, 0, 0;\nwgmma.mma_async.sync.aligned.m64n40k16.f32.bf16.bf16 {%0,%1,%2,%3,%4,%5,%6,%7,%8,%9,%10,%11,%12,%13,%14,%15,%16,%17,%18,%19}, {%20,%21,%22,%23}, %24, p, 1, 1, 0;\n}\n"
    : "+f"(d[0]), "+f"(d[1]), "+f"(d[2]), "+f"(d[3]), "+f"(d[4]), "+f"(d[5]), "+f"(d[6]), "+f"(d[7]), "+f"(d[8]), "+f"(d[9]), "+f"(d[10]), "+f"(d[11]), "+f"(d[12]), "+f"(d[13]), "+f"(d[14]), "+f"(d[15]), "+f"(d[16]), "+f"(d[17]), "+f"(d[18]), "+f"(d[19])
    : "r"(a0), "r"(a1), "r"(a2), "r"(a3), "l"(db));
}
__device__ __forceinline__ void wgmma_rs_n40_a(float (&d)[20], uint32_t a0, uint32_t a1, uint32_t a2, uint32_t a3, uint64_t db) {
  asm volatile("{\n.reg .pred p;\nsetp.ne.b32 p, 1, 0;\nwgmma.mma_async.sync.aligned.m64n40k16.f32.bf16.bf16 {%0,%1,%2,%3,%4,%5,%6,%7,%8,%9,%10,%11,%12,%13,%14,%15,%16,%17,%18,%19}, {%20,%21,%22,%23}, %24, p, 1, 1, 0;\n}\n"
    : "+f"(d[0]), "+f"(d[1]), "+f"(d[2]), "+f"(d[3]), "+f"(d[4]), "+f"(d[5]), "+f"(d[6]), "+f"(d[7]), "+f"(d[8]), "+f"(d[9]), "+f"(d[10]), "+f"(d[11]), "+f"(d[12]), "+f"(d[13]), "+f"(d[14]), "+f"(d[15]), "+f"(d[16]), "+f"(d[17]), "+f"(d[18]), "+f"(d[19])
    : "r"(a0), "r"(a1), "r"(a2), "r"(a3), "l"(db));
}

__device__ __forceinline__ void wgmma_rs_n128_z(float (&d)[64], uint32_t a0, uint32_t a1, uint32_t a2, uint32_t a3, uint64_t db) {
  asm volatile("{\n.reg .pred p;\nsetp.ne.b32 p, 0, 0;\nwgmma.mma_async.sync.aligned.m64n128k16.f32.bf16.bf16 {%0,%1,%2,%3,%4,%5,%6,%7,%8,%9,%10,%11,%12,%13,%14,%15,%16,%17,%18,%19,%20,%21,%22,%23,%24,%25,%26,%27,%28,%29,%30,%31,%32,%33,%34,%35,%36,%37,%38,%39,%40,%41,%42,%43,%44,%45,%46,%47,%48,%49,%50,%51,%52,%53,%54,%55,%56,%57,%58,%59,%60,%61,%62,%63}, {%64,%65,%66,%67}, %68, p, 1, 1, 1;\n}\n"
    : "+f"(d[0]), "+f"(d[1]), "+f"(d[2]), "+f"(d[3]), "+f"(d[4]), "+f"(d[5]), "+f"(d[6]), "+f"(d[7]), "+f"(d[8]), "+f"(d[9]), "+f"(d[10]), "+f"(d[11]), "+f"(d[12]), "+f"(d[13]), "+f"(d[14]), "+f"(d[15]), "+f"(d[16]), "+f"(d[17]), "+f"(d[18]), "+f"(d[19]), "+f"(d[20]), "+f"(d[21]), "+f"(d[22]), "+f"(d[23]), "+f"(d[24]), "+f"(d[25]), "+f"(d[26]), "+f"(d[27]), "+f"(d[28]), "+f"(d[29]), "+f"(d[30]), "+f"(d[31]), "+f"(d[32]), "+f"(d[33]), "+f"(d[34]), "+f"(d[35]), "+f"(d[36]), "+f"(d[37]), "+f"(d[38]), "+f"(d[39]), "+f"(d[40]), "+f"(d[41]), "+f"(d[42]), "+f"(d[43]), "+f"(d[44]), "+f"(d[45]), "+f"(d[46]), "+f"(d[47]), "+f"(d[48]), "+f"(d[49]), "+f"(d[50]), "+f"(d[51]), "+f"(d[52]), "+f"(d[53]), "+f"(d[54]), "+f"(d[55]), "+f"(d[56]), "+f"(d[57]), "+f"(d[58]), "+f"(d[59]), "+f"(d[60]), "+f"(d[61]), "+f"(d[62]), "+f"(d[63])
    : "r"(a0), "r"(a1), "r"(a2), "r"(a3), "l"(db));
}
__device__ __forceinline__ void wgmma_rs_n128_a(float (&d)[64], uint32_t a0, uint32_t a1, uint32_t a2, uint32_t a3, uint64_t db) {
  asm volatile("{\n.reg .pred p;\nsetp.ne.b32 p, 1, 0;\nwgmma.mma_async.sync.aligned.m64n128k16.f32.bf16.bf16 {%0,%1,%2,%3,%4,%5,%6,%7,%8,%9,%10,%11,%12,%13,%14,%15,%16,%17,%18,%19,%20,%21,%22,%23,%24,%25,%26,%27,%28,%29,%30,%31,%32,%33,%34,%35,%36,%37,%38,%39,%40,%41,%42,%43,%44,%45,%46,%47,%48,%49,%50,%51,%52,%53,%54,%55,%56,%57,%58,%59,%60,%61,%62,%63}, {%64,%65,%66,%67}, %68, p, 1, 1, 1;\n}\n"
    : "+f"(d[0]), "+f"(d[1]), "+f"(d[2]), "+f"(d[3]), "+f"(d[4]), "+f"(d[5]), "+f"(d[6]), "+f"(d[7]), "+f"(d[8]), "+f"(d[9]), "+f"(d[10]), "+f"(d[11]), "+f"(d[12]), "+f"(d[13]), "+f"(d[14]), "+f"(d[15]), "+f"(d[16]), "+f"(d[17]), "+f"(d[18]), "+f"(d[19]), "+f"(d[20]), "+f"(d[21]), "+f"(d[22]), "+f"(d[23]), "+f"(d[24]), "+f"(d[25]), "+f"(d[26]), "+f"(d[27]), "+f"(d[28]), "+f"(d[29]), "+f"(d[30]), "+f"(d[31]), "+f"(d[32]), "+f"(d[33]), "+f"(d[34]), "+f"(d[35]), "+f"(d[36]), "+f"(d[37]), "+f"(d[38]), "+f"(d[39]), "+f"(d[40]), "+f"(d[41]), "+f"(d[42]), "+f"(d[43]), "+f"(d[44]), "+f"(d[45]), "+f"(d[46]), "+f"(d[47]), "+f"(d[48]), "+f"(d[49]), "+f"(d[50]), "+f"(d[51]), "+f"(d[52]), "+f"(d[53]), "+f"(d[54]), "+f"(d[55]), "+f"(d[56]), "+f"(d[57]), "+f"(d[58]), "+f"(d[59]), "+f"(d[60]), "+f"(d[61]), "+f"(d[62]), "+f"(d[63])
    : "r"(a0), "r"(a1), "r"(a2), "r"(a3), "l"(db));
}

__device__ __forceinline__ void wgmma_rs_n32_z(float (&d)[16], uint32_t a0, uint32_t a1, uint32_t a2, uint32_t a3, uint64_t db) {
  asm volatile("{\n.reg .pred p;\nsetp.ne.b32 p, 0, 0;\nwgmma.mma_async.sync.aligned.m64n32k16.f32.bf16.bf16 {%0,%1,%2,%3,%4,%5,%6,%7,%8,%9,%10,%11,%12,%13,%14,%15}, {%16,%17,%18,%19}, %20, p, 1, 1, 0;\n}\n"
    : "+f"(d[0]), "+f"(d[1]), "+f"(d[2]), "+f"(d[3]), "+f"(d[4]), "+f"(d[5]), "+f"(d[6]), "+f"(d[7]), "+f"(d[8]), "+f"(d[9]), "+f"(d[10]), "+f"(d[11]), "+f"(d[12]), "+f"(d[13]), "+f"(d[14]), "+f"(d[15])
    : "r"(a0), "r"(a1), "r"(a2), "r"(a3), "l"(db));
}
__device__ __forceinline__ void wgmma_rs_n32_a(float (&d)[16], uint32_t a0, uint32_t a1, uint32_t a2, uint32_t a3, uint64_t db) {
  asm volatile("{\n.reg .pred p;\nsetp.ne.b32 p, 1, 0;\nwgmma.mma_async.sync.aligned.m64n32k16.f32.bf16.bf16 {%0,%1,%2,%3,%4,%5,%6,%7,%8,%9,%10,%11,%12,%13,%14,%15}, {%16,%17,%18,%19}, %20, p, 1, 1, 0;\n}\n"
    : "+f"(d[0]), "+f"(d[1]), "+f"(d[2]), "+f"(d[3]), "+f"(d[4]), "+f"(d[5]), "+f"(d[6]), "+f"(d[7]), "+f"(d[8]), "+f"(d[9]), "+f"(d[10]), "+f"(d[11]), "+f"(d[12]), "+f"(d[13]), "+f"(d[14]), "+f"(d[15])
    : "r"(a0), "r"(a1), "r"(a2), "r"(a3), "l"(db));
}

__device__ __forceinline__ void wgmma_ss_n32_z(float (&d)[16], uint64_t da, uint64_t db) {
  asm volatile("{\n.reg .pred p;\nsetp.ne.b32 p, 0, 0;\nwgmma.mma_async.sync.aligned.m64n32k16.f32.bf16.bf16 {%0,%1,%2,%3,%4,%5,%6,%7,%8,%9,%10,%11,%12,%13,%14,%15}, %16, %17, p, 1, 1, 1, 0;\n}\n"
    : "+f"(d[0]), "+f"(d[1]), "+f"(d[2]), "+f"(d[3]), "+f"(d[4]), "+f"(d[5]), "+f"(d[6]), "+f"(d[7]), "+f"(d[8]), "+f"(d[9]), "+f"(d[10]), "+f"(d[11]), "+f"(d[12]), "+f"(d[13]), "+f"(d[14]), "+f"(d[15])
    : "l"(da), "l"(db));
}
__device__ __forceinline__ void wgmma_ss_n32_a(float (&d)[16], uint64_t da, uint64_t db) {
  asm volatile("{\n.reg .pred p;\nsetp.ne.b32 p, 1, 0;\nwgmma.mma_async.sync.aligned.m64n32k16.f32.bf16.bf16 {%0,%1,%2,%3,%4,%5,%6,%7,%8,%9,%10,%11,%12,%13,%14,%15}, %16, %17, p, 1, 1, 1, 0;\n}\n"
    : "+f"(d[0]), "+f"(d[1]), "+f"(d[2]), "+f"(d[3]), "+f"(d[4]), "+f"(d[5]), "+f"(d[6]), "+f"(d[7]), "+f"(d[8]), "+f"(d[9]), "+f"(d[10]), "+f"(d[11]), "+f"(d[12]), "+f"(d[13]), "+f"(d[14]), "+f"(d[15])
    : "l"(da), "l"(db));
}

__device__ __forceinline__ void wgmma_ss_n40_z(float (&d)[20], uint64_t da, uint64_t db) {
  asm volatile("{\n.reg .pred p;\nsetp.ne.b32 p, 0, 0;\nwgmma.mma_async.sync.aligned.m64n40k16.f32.bf16.bf16 {%0,%1,%2,%3,%4,%5,%6,%7,%8,%9,%10,%11,%12,%13,%14,%15,%16,%17,%18,%19}, %20, %21, p, 1, 1, 1, 0;\n}\n"
    : "+f"(d[0]), "+f"(d[1]), "+f"(d[2]), "+f"(d[3]), "+f"(d[4]), "+f"(d[5]), "+f"(d[6]), "+f"(d[7]), "+f"(d[8]), "+f"(d[9]), "+f"(d[10]), "+f"(d[11]), "+f"(d[12]), "+f"(d[13]), "+f"(d[14]), "+f"(d[15]), "+f"(d[16]), "+f"(d[17]), "+f"(d[18]), "+f"(d[19])
    : "l"(da), "l"(db));
}
__device__ __forceinline__ void wgmma_ss_n40_a(float (&d)[20], uint64_t da, uint64_t db) {
  asm volatile("{\n.reg .pred p;\nsetp.ne.b32 p, 1, 0;\nwgmma.mma_async.sync.aligned.m64n40k16.f32.bf16.bf16 {%0,%1,%2,%3,%4,%5,%6,%7,%8,%9,%10,%11,%12,%13,%14,%15,%16,%17,%18,%19}, %20, %21, p, 1, 1, 1, 0;\n}\n"
    : "+f"(d[0]), "+f"(d[1]), "+f"(d[2]), "+f"(d[3]), "+f"(d[4]), "+f"(d[5]), "+f"(d[6]), "+f"(d[7]), "+f"(d[8]), "+f"(d[9]), "+f"(d[10]), "+f"(d[11]), "+f"(d[12]), "+f"(d[13]), "+f"(d[14]), "+f"(d[15]), "+f"(d[16]), "+f"(d[17]), "+f"(d[18]), "+f"(d[19])
    : "l"(da), "l"(db));
}

constexpr int NSM = 132, NH = 66;
constexpr int S0 = 0, S1 = 51200, S2 = 102400;
constexpr int C1 = 153600, C3 = C1, RG = C1 + 18432;
constexpr int WP = RG, TBL = RG + 28672, WS2 = RG + 30720;
constexpr int BARS = RG + 49152;
__host__ __device__ constexpr int wst_off(int i) { return i < 12 ? S2 + i * 4096 : WS2 + (i - 12) * 4096; }
constexpr int NBAR = 232;
constexpr int REL = BARS + NBAR * 8;
constexpr int SMEM_BYTES = REL + 16;
constexpr int B_XF = 0, B_CF1 = 15, B_CF3 = 16, B_WF = 17  , B_P1D = 18, B_WFREE = 20, B_REL = 21, B_ROLE = 22, B_X1 = 23, B_SIG = 24;
constexpr int B_RF = 32, B_RE = 46, B_YF = 60, B_WRD = 75, B_SFREE = 89, B_WCH = 131, B_RDY = 136, B_WE = 205, B_WL = 217, B_FIN = 229;
constexpr int R_P2 = 15, R_P3 = 57;
constexpr int CNT_P1 = 0, CNT_P2 = 4, CNT_W = 8, CNT_RANK = 9, NCLS = 10, CNT_DONE = 0, CNT_REL = 1, NCNT = 2;
constexpr int SIG_W = 0, SIG_P1 = 1, SIG_P2 = 4;
#define PROBES 1
#define WB 100
#define PACE 0
#define PACE_SLACK 300
#define SWIN 2
#define X1AT 10
#define WARMUP 0
#define YPACE 0
#define POLL3 0
#define XPF 0
#define PSLEEP 0
#define TRICKLE
#define T1MASK 0x3e00
#define T2MASK 0x1f00
#define X1BOX 0
#define X2BOX 5

__device__ uint4 g_scr[(14 << 21) / 16];
__device__ uint4 g_wf[200 * 72 * 32];
__device__ unsigned g_cnt[NCNT * 32];
__device__ __forceinline__ int slot_line(int chunk, int pg, int cls) {
    return (pg & 1) << 6 | (pg >> 1) << 9 | (chunk & 1) << 10 | (chunk >> 1) << 12 | ((pg ^ (pg >> 1) ^ chunk ^ (chunk >> 1) ^ cls) & 1) << 5;
}
__device__ __forceinline__ int phi_line(int phi, uint32_t rel) {
    return (phi >> 4) << 14 | (phi & 3) << 7 | ((phi >> 2) & 1) << 11 | ((phi >> 3) & 1) << 13 | ((rel >> (phi >> 4)) & 1) << 5;
}
__device__ __forceinline__ int extra_mask(int rk) { return rk < 60 ? 0 : rk < 62 ? 3 : rk < 64 ? 4 : 8; }
__device__ __forceinline__ int wslot(int pc) {
    return pc >= 9 ? S2 + (pc - 9) * 12288 : (int)((0x702651430ull >> (4 * pc)) & 3) * 12288 + (((0x702651430ull >> (4 * pc)) & 4) ? S0 : RG);
}
__device__ __forceinline__ int extra_phi(int rk) { return 198 + (rk & 1); }
__host__ __device__ constexpr int quad_off(int Q) { return (Q >> 2) * 4096 + (Q & 3) * 512; }

#define PROF(k)
#define PROFW(k)
#define prof_dump()
struct Maps { CUtensorMap w, x34, x6, x28, wst, f16, f8, y4, y2; };
struct Ptrs { char* scr; const char* wf; const void* tab1; const void* tab3; unsigned* cnt; };

__device__ __forceinline__ uint32_t smem_u32(const void* p) { return (uint32_t)__cvta_generic_to_shared(p); }
__device__ __forceinline__ void mbar_wait(uint32_t bar) {
    uint32_t ok, it = 0;
    do {
        asm volatile("{\n.reg .pred p;\nmbarrier.try_wait.parity.shared::cta.b64 p, [%1], 0;\nselp.u32 %0, 1, 0, p;\n}" : "=r"(ok) : "r"(bar) : "memory");
        if (++it > (1u << 22)) break;
    } while (!ok);
}
__device__ __forceinline__ bool mbar_test(uint32_t bar) {
    uint32_t ok;
    asm volatile("{\n.reg .pred p;\nmbarrier.test_wait.parity.shared::cta.b64 p, [%1], 0;\nselp.u32 %0, 1, 0, p;\n}" : "=r"(ok) : "r"(bar) : "memory");
    return ok;
}
__device__ __forceinline__ void fence_async() { asm volatile("fence.proxy.async;" ::: "memory"); }
__device__ __forceinline__ void fence_async_smem() { asm volatile("fence.proxy.async.shared::cta;" ::: "memory"); }
#define ELECT "{\n.reg .pred p;\nelect.sync _|p, 0xffffffff;\n@p "
__device__ __forceinline__ void e_arrive(uint32_t bar) { asm volatile(ELECT "mbarrier.arrive.shared::cta.b64 _, [%0];\n}" :: "r"(bar) : "memory"); }
__device__ __forceinline__ void e_expect(uint32_t bar, uint32_t bytes) { asm volatile(ELECT "mbarrier.arrive.expect_tx.shared::cta.b64 _, [%0], %1;\n}" :: "r"(bar), "r"(bytes) : "memory"); }
__device__ __forceinline__ void e_g2s(uint32_t dst, const void* src, uint32_t bytes, uint32_t bar) {
    asm volatile(ELECT "cp.async.bulk.shared::cluster.global.mbarrier::complete_tx::bytes [%0], [%1], %2, [%3];\n}" :: "r"(dst), "l"(src), "r"(bytes), "r"(bar) : "memory");
}
__device__ __forceinline__ void e_s2g(void* dst, uint32_t src, uint32_t bytes) {
    asm volatile(ELECT "cp.async.bulk.global.shared::cta.bulk_group [%0], [%1], %2;\n}" :: "l"(dst), "r"(src), "r"(bytes) : "memory");
}
__device__ __forceinline__ void e_ld3(uint32_t dst, const CUtensorMap* m, int c0, int c1, int c2, uint32_t bar) {
    asm volatile(ELECT "cp.async.bulk.tensor.3d.shared::cluster.global.mbarrier::complete_tx::bytes [%0], [%1, {%3, %4, %5}], [%2];\n}"
                 :: "r"(dst), "l"(m), "r"(bar), "r"(c0), "r"(c1), "r"(c2) : "memory");
}
__device__ __forceinline__ void e_ld4(uint32_t dst, const CUtensorMap* m, int c0, int c3, uint32_t bar) {
    asm volatile(ELECT "cp.async.bulk.tensor.4d.shared::cluster.global.mbarrier::complete_tx::bytes [%0], [%1, {%3, %5, %5, %4}], [%2];\n}"
                 :: "r"(dst), "l"(m), "r"(bar), "r"(c0), "r"(c3), "r"(0) : "memory");
}
__device__ __forceinline__ void e_st3(const CUtensorMap* m, uint32_t src, int c0, int c1, int c2) {
    asm volatile(ELECT "cp.async.bulk.tensor.3d.global.shared::cta.bulk_group [%0, {%2, %3, %4}], [%1];\n}" :: "l"(m), "r"(src), "r"(c0), "r"(c1), "r"(c2) : "memory");
}
__device__ __forceinline__ void e_ld5(uint32_t dst, const CUtensorMap* m, int c4, uint32_t bar) {
    asm volatile(ELECT "cp.async.bulk.tensor.5d.shared::cluster.global.mbarrier::complete_tx::bytes [%0], [%1, {%4, %4, %4, %4, %3}], [%2];\n}"
                 :: "r"(dst), "l"(m), "r"(bar), "r"(c4), "r"(0) : "memory");
}
__device__ __forceinline__ void e_st5(const CUtensorMap* m, uint32_t src, int c4) {
    asm volatile(ELECT "cp.async.bulk.tensor.5d.global.shared::cta.bulk_group [%0, {%3, %3, %3, %3, %2}], [%1];\n}" :: "l"(m), "r"(src), "r"(c4), "r"(0) : "memory");
}
__device__ __forceinline__ void bulk_commit() { asm volatile("cp.async.bulk.commit_group;" ::: "memory"); }
template <int N> __device__ __forceinline__ void bulk_wait_read() { asm volatile("cp.async.bulk.wait_group.read %0;" :: "n"(N) : "memory"); }
__device__ __forceinline__ void wg_bar(int id) { asm volatile("bar.sync %0, 128;" :: "r"(id) : "memory"); }
__device__ __forceinline__ void bb_break(uint32_t v) { asm volatile("{\n.reg .pred p;\nsetp.eq.u32 p, %0, 0x7fc17fc1;\n@p nanosleep.u32 0;\n}" :: "r"(v) : "memory"); }
__device__ __forceinline__ uint32_t uni(uint32_t v) { return __shfl_sync(0xffffffffu, v, 0); }
__device__ __forceinline__ char* cls_cnt(char* scr, int cls) { return scr + slot_line(3, 2, cls) * 128; }
__device__ __forceinline__ uint32_t cnt_wait(const void* p, unsigned target) {
    auto ld = [&]() { unsigned v; asm volatile("ld.relaxed.gpu.global.u32 %0, [%1];" : "=r"(v) : "l"(p) : "memory"); return v; };
    unsigned v0 = ld(), v;
#pragma unroll 1
    for (unsigned it = 0; it < (1u << 22); it++) { if ((v = uni(v0)) >= target) break; if (PSLEEP) __nanosleep(PSLEEP); v0 = ld(); }
    return v;
}
__device__ __forceinline__ void wg_fence() { asm volatile("wgmma.fence.sync.aligned;" ::: "memory"); }
__device__ __forceinline__ void wg_commit() { asm volatile("wgmma.commit_group.sync.aligned;" ::: "memory"); }
template <int N> __device__ __forceinline__ void wg_wait() { asm volatile("wgmma.wait_group.sync.aligned %0;" :: "n"(N) : "memory"); }
template <int N> __device__ __forceinline__ void reg_fence(float (&d)[N]) {
#pragma unroll
    for (int i = 0; i < N; i++) asm volatile("" : "+f"(d[i]) :: "memory");
}
template <int N, int O, int M> __device__ __forceinline__ float (&sub(float (&d)[M]))[N] { return *reinterpret_cast<float (*)[N]>(&d[O]); }
template <int N> __device__ __forceinline__ void zero(float (&d)[N]) {
#pragma unroll
    for (int i = 0; i < N; i++) d[i] = 0.f;
}
__device__ __forceinline__ uint32_t pack2(float lo, float hi) {
    uint32_t r; asm volatile("cvt.rn.bf16x2.f32 %0, %1, %2;" : "=r"(r) : "f"(hi), "f"(lo)); return r;
}
__device__ __forceinline__ void stm4(uint32_t a, uint32_t r0, uint32_t r1, uint32_t r2, uint32_t r3) {
    asm volatile("stmatrix.sync.aligned.m8n8.x4.trans.shared.b16 [%0], {%1,%2,%3,%4};" :: "r"(a), "r"(r0), "r"(r1), "r"(r2), "r"(r3) : "memory");
}
__device__ __forceinline__ void stm2(uint32_t a, uint32_t r0, uint32_t r1) {
    asm volatile("stmatrix.sync.aligned.m8n8.x2.trans.shared.b16 [%0], {%1,%2};" :: "r"(a), "r"(r0), "r"(r1) : "memory");
}
__device__ __forceinline__ void stm1(uint32_t a, uint32_t r0) {
    asm volatile("stmatrix.sync.aligned.m8n8.x1.trans.shared.b16 [%0], {%1};" :: "r"(a), "r"(r0) : "memory");
}
struct Desc {
    uint32_t lo, hi;
    __device__ __forceinline__ operator uint64_t() const { return ((uint64_t)hi << 32) | lo; }
    __device__ __forceinline__ Desc operator+(uint32_t o) const { return Desc{lo + o, hi}; }
    __device__ __forceinline__ Desc operator^(uint32_t o) const { return Desc{lo ^ o, hi}; }
};
__device__ __forceinline__ Desc mkdesc(uint32_t addr, uint32_t lbo, uint32_t sbo, uint32_t swz) {
    return Desc{((addr & 0x3FFFF) >> 4) | ((lbo >> 4) << 16), (sbo >> 4) | (swz << 30)};
}
__device__ __forceinline__ uint32_t cos_bits(int k) {
    if (k > 20) k = 40 - k;
    const bool neg = k > 10;
    if (neg) k = 20 - k;
    const unsigned long long pk = k < 4 ? COS_PK0 : k < 8 ? COS_PK1 : COS_PK2;
    return (uint32_t)((pk >> (16 * (k & 3))) & 0xffff) ^ (neg ? 0x8000u : 0u);
}

__device__ __forceinline__ void task_w(int wg, int k, uint32_t sb) {
    const int tid = threadIdx.x & 127, w = uni(tid >> 5), lane = tid & 31, q = lane & 3;
    const int tb = 14 * k, t1 = min(tb + 14, 1800), cb0 = tb / 25;
    float acc[64];
    zero(acc);
    const int oc0 = tb - 25 * cb0, Lt = t1 - tb, L0 = min(Lt, 25 - oc0), n0 = (L0 + 3) >> 2;
    uint32_t a[2][4][4];
    auto gen = [&](uint32_t (&a)[4][4], int at) {
        const int phi = 8 * ((at < n0 ? oc0 + 4 * at : 4 * (at - n0)) + w) + (lane >> 2), f = (phi * 205) >> 12;
        const uint32_t ca = 8 * f + 4, cw = (phi - 20 * f) * 8, p0 = sb + TBL + cw * 2 * q;
#pragma unroll
        for (int kh = 0; kh < 7; kh++) {
            uint32_t v0, v1;
            asm volatile("ld.shared.u32 %0, [%1];" : "=r"(v0) : "r"(p0 + ca * kh));
            asm volatile("ld.shared.u32 %0, [%1];" : "=r"(v1) : "r"(p0 + cw + ca * kh));
            const int h = kh == 6 ? 1 : kh & 1;
            a[kh >> 1][2 * h] = __byte_perm(v0, v1, 0x5410);
            a[kh >> 1][2 * h + 1] = __byte_perm(v0, v1, 0x7632);
        }
        a[3][0] = 0; a[3][1] = 0;
    };
    gen(a[0], wg);
    if (wg) gen(a[1], wg + 2);
    PROFW(wg == 0 ? 124 : 127);
#pragma unroll 1
    for (int n = 0; n < 2; n++) {
        const int at = wg + 2 * n, i0 = at < n0 ? 4 * at : L0 + 4 * (at - n0), cnt = (at < n0 ? L0 : Lt) - i0, cb = cb0 + (at >= n0);
        if (cnt <= 0 || (n && !wg)) break;
        if (n) {
#pragma unroll
            for (int j = 0; j < 16; j++) a[0][j >> 2][j & 3] = a[1][j >> 2][j & 3];
        }
        const Desc dB = mkdesc(sb + WP + (cb - cb0) * 14336, 3584, 512, 2);
        if (at) mbar_wait(sb + BARS + 8 * (B_WCH + at - 1));
        mbar_wait(sb + BARS + 8 * (B_WF + 2 * (cb - cb0)));
        PROFW(at == 0 ? 125 : 127);
        wg_fence();
        wgmma_rs_n128_z(acc, a[0][0][0], a[0][0][1], a[0][0][2], a[0][0][3], dB);
        wgmma_rs_n128_a(acc, a[0][1][0], a[0][1][1], a[0][1][2], a[0][1][3], dB + (uint32_t)(16 * 64 >> 4));
        wgmma_rs_n128_a(acc, a[0][2][0], a[0][2][1], a[0][2][2], a[0][2][3], dB + (uint32_t)(32 * 64 >> 4));
        wgmma_rs_n128_a(acc, a[0][3][0], a[0][3][1], a[0][3][2], a[0][3][3], dB + (uint32_t)(40 * 64 >> 4));
        wg_commit();
        wg_wait<0>();
        reg_fence(acc);
        PROFW(at == 0 ? 120 : 127);
        e_arrive(sb + BARS + 8 * (B_WCH + at));
        if (w < cnt) {
            const uint32_t dst = sb + wst_off(i0 + w) + (lane >> 2) * 512 + (lane & 4) * 16 + ((q ^ cb) & 3) * 16;
#pragma unroll
            for (int j = 0; j < 4; j++)
#pragma unroll
                for (int e = 0; e < 2; e++)
                    asm volatile("st.shared.v4.u32 [%0], {%1,%2,%3,%4};" :: "r"((dst ^ (e * 64)) + j * 128),
                                 "r"(pack2(acc[4 * j + e], acc[16 + 4 * j + e])), "r"(pack2(acc[4 * j + 2 + e], acc[16 + 4 * j + 2 + e])),
                                 "r"(pack2(acc[32 + 4 * j + e], acc[48 + 4 * j + e])), "r"(pack2(acc[32 + 4 * j + 2 + e], acc[48 + 4 * j + 2 + e])) : "memory");
            fence_async_smem();
            e_arrive(sb + BARS + 8 * (B_WRD + i0 + w));
        }
    }
}

__device__ __forceinline__ void task_p1(int wg, int pair, uint32_t sb) {
    const int tid = threadIdx.x & 127, w = tid >> 5, lane = tid & 31;
    const uint32_t buf = sb + wg * 51200, bars = sb + BARS;
    uint32_t fr[5][10][2];
    float A[40], d[20];
    zero(A);
    {
        const Desc dA = mkdesc(buf, 3584, 512, 2), dB = mkdesc(sb + C1, 128, 256, 0);
        auto issue = [&](int g, float (&d)[40]) {
            mbar_wait(bars + 8 * (B_XF + wg * 5 + g));
            wg_fence();
            wgmma_ss_n80_z(d, dA + (uint32_t)(g * 8704 >> 4), dB);
#pragma unroll
            for (int j = 1; j < 5; j++) wgmma_ss_n80_a(d, dA + (uint32_t)((g * 8704 + j * 1024) >> 4), dB + (uint32_t)(j * 2560 >> 4));
            wg_commit();
        };
        auto pack = [&](int g, float (&d)[40]) {
            reg_fence(d);
#pragma unroll
            for (int f = 0; f < 10; f++) {
                fr[g][f][0] = pack2(d[4 * f], d[4 * f + 1]);
                fr[g][f][1] = pack2(d[4 * f + 2], d[4 * f + 3]);
            }
        };
        mbar_wait(bars + 8 * B_CF1);
#pragma unroll
        for (int g = 0; g < 4; g++) { issue(g, A); if (g == 0) PROFW(8 + wg * 8 + 1); wg_wait<0>(); pack(g, A); }
        zero(d);
        mbar_wait(bars + 8 * (B_XF + wg * 5 + 4));
#pragma unroll
        for (int h = 0; h < 2; h++) {
            wg_fence();
            wgmma_ss_n40_z(d, dA + (uint32_t)(4 * 8704 >> 4), dB + (uint32_t)(h * 1280 >> 4));
#pragma unroll
            for (int j = 1; j < 5; j++) wgmma_ss_n40_a(d, dA + (uint32_t)((4 * 8704 + j * 1024) >> 4), dB + (uint32_t)((j * 2560 + h * 1280) >> 4));
            wg_commit(); wg_wait<0>(); reg_fence(d);
#pragma unroll
            for (int f = 0; f < 5; f++) { fr[4][5 * h + f][0] = pack2(d[4 * f], d[4 * f + 1]); fr[4][5 * h + f][1] = pack2(d[4 * f + 2], d[4 * f + 3]); }
        }
    }
    bb_break(sb);
    wg_bar(1 + wg);
    PROFW(8 + wg * 8 + 2);
    {
        const Desc dB = mkdesc(sb + C1 + 12800, 128, 256, 0);
        const int i = lane & 7, mi = lane >> 3, th = w >> 1, tz = (2 * pair + th) & 3;
        const uint32_t s0 = buf + (i >> 1) * 128 + (i & 1) * 64 + (((2 * (w & 1) + (mi & 1)) ^ tz ^ (i >> 1)) << 4);
        const uint32_t sA = s0 + th * 2048 + (mi >> 1) * 512, sB = s0 + th * 2048 + (mi >> 1) * 2560, sC = s0 + th * 1024 + (mi >> 1) * 512;
        auto issue = [&](int f, float (&d)[20]) {
            wg_fence();
            wgmma_rs_n40_z(d, fr[0][f][0], fr[0][f][1], fr[1][f][0], fr[1][f][1], dB);
            wgmma_rs_n40_a(d, fr[2][f][0], fr[2][f][1], fr[3][f][0], fr[3][f][1], dB + (uint32_t)(1280 >> 4));
            wgmma_rs_n40_a(d, fr[4][f % 5][0], fr[4][f % 5][1], fr[4][f % 5 + 5][0], fr[4][f % 5 + 5][1], dB + (uint32_t)((2560 + (f / 5) * 1280) >> 4));
            wg_commit();
        };
#pragma unroll
        for (int f = 0; f < 10; f++) {
                        issue(f, d); wg_wait<0>(); reg_fence(d);
            const int Q = 5 * f;
            stm4(((Q & 3) == 3 ? sB : sA) + quad_off(Q), pack2(d[0], d[1]), pack2(d[2], d[3]), pack2(d[4], d[5]), pack2(d[6], d[7]));
            stm2(sA + quad_off(Q + 2), pack2(d[8], d[9]), pack2(d[10], d[11]));
            stm4((f == 9 ? sC : ((Q + 3) & 3) == 3 ? sB : sA) + quad_off(Q + 3), pack2(d[12], d[13]), pack2(d[14], d[15]), pack2(d[16], d[17]), pack2(d[18], d[19]));
            if (f & 1) { fence_async_smem(); e_arrive(bars + 8 * (B_RDY + wg * 5 + (f >> 1))); }
        }
    }
}

__device__ __forceinline__ void task_p2(int wg, int rk, uint32_t sb) {
    const int tid = threadIdx.x & 127, w = tid >> 5, lane = tid & 31;
    const uint32_t bars = sb + BARS;
    const int phi0 = 3 * rk, phiE = extra_phi(rk), mE = extra_mask(rk);
    uint4 wA[6], wB[6], wC[6], wE[6];
    auto ldw = [&](uint4 (&a)[6], int j, int phi) {
        const int pc = 3 * j + wg;
        const uint32_t p = sb + wslot(pc) + (lane & 3) * 512 + w * 128 + (((lane >> 2) ^ phi) & 1) * 64 + (((lane >> 3) ^ lane) & 3) * 16 + (phi & 1) * 8;
        mbar_wait(bars + 8 * (B_WL + pc));
#pragma unroll
        for (int s = 0; s < 6; s++) {
            asm volatile("ld.shared.v2.u32 {%0, %1}, [%2];" : "=r"(a[s].x), "=r"(a[s].y) : "r"(p + s * 2048) : "memory");
            asm volatile("ld.shared.v2.u32 {%0, %1}, [%2];" : "=r"(a[s].z), "=r"(a[s].w) : "r"((p ^ 8) + s * 2048) : "memory");
        }
        uint32_t dep = 0;
#pragma unroll
        for (int s = 0; s < 6; s++) dep |= a[s].x ^ a[s].z;
        if (__any_sync(0xffffffffu, dep == 0x7fc17fc1u)) __nanosleep(0);
        e_arrive(bars + 8 * (B_WE + pc));
    };
    ldw(wA, 0, phi0); ldw(wB, 1, phi0 + 1);
    ldw(wC, 2, phi0 + 2);
    PROFW(8 + wg * 8 + 4);
    mbar_wait(bars + 8 * (B_SIG + SIG_P1 + 1));
    const int i = lane & 7, mi = lane >> 3;
    const uint32_t soff = sb + S1 + wg * 4096 + mi * 512 + (i >> 1) * 128 + (i & 1) * 64;
    const int xo = w ^ (i >> 1);
    float p0[16], p1[16];
    zero(p0); zero(p1);
    auto issue = [&](float (&d)[16], int n, int h, const uint4 (&a)[6], int z) {
        const Desc d0 = mkdesc(sb + RG + ((n + 1) & 3) * 12288 + h * 2048 + ((z >> 1) << 5), 16, 512, 2), d1 = d0 ^ 2u;
        if (h == 0) mbar_wait(bars + 8 * (B_RF + n));
        wg_fence();
        wgmma_rs_n32_z(d, a[0].x, a[0].y, a[0].z, a[0].w, d0);
        wgmma_rs_n32_a(d, a[1].x, a[1].y, a[1].z, a[1].w, d1);
#pragma unroll
        for (int c = 1; c < 3; c++) {
            wgmma_rs_n32_a(d, a[2 * c].x, a[2 * c].y, a[2 * c].z, a[2 * c].w, d0 + (uint32_t)(c * 4096 >> 4));
            wgmma_rs_n32_a(d, a[2 * c + 1].x, a[2 * c + 1].y, a[2 * c + 1].z, a[2 * c + 1].w, d1 + (uint32_t)(c * 4096 >> 4));
        }
        wg_commit();
    };
    auto epi = [&](float (&d)[16], int n, int h, int z) {
        reg_fence(d);
        if (h) e_arrive(bars + 8 * (B_RE + n));
        uint32_t p[4];
#pragma unroll
        for (int j = 0; j < 4; j++) p[j] = pack2(d[4 * j] - d[4 * j + 3], d[4 * j + 2] + d[4 * j + 1]);
        if (h == 0 && n >= 4) mbar_wait(bars + 8 * (B_SFREE + (n - 4) * 3 + wg));
        stm4(soff + (n & 3) * 12288 + h * 2048 + ((xo ^ z) << 4), p[0], p[1], p[2], p[3]);
        if (h) { fence_async_smem(); e_arrive(bars + 8 * (B_RDY + R_P2 + n * 3 + wg)); }
    };
    const int zA = phi0 & 3, zB = (phi0 + 1) & 3, zC = (phi0 + 2) & 3, zE = phiE & 3;
    int n = 0;
#pragma unroll 1
    for (int it = 0; it < 4; it++) {
        issue(p0, n, 0, wA, zA);
        issue(p1, n, 1, wA, zA);     wg_wait<1>(); epi(p0, n, 0, zA);
        issue(p0, n + 1, 0, wB, zB); wg_wait<1>(); epi(p1, n, 1, zA);
        PROFW(40 + wg * 8 + it * 2);
        issue(p1, n + 1, 1, wB, zB); wg_wait<1>(); epi(p0, n + 1, 0, zB);
        issue(p0, n + 2, 0, wC, zC); wg_wait<1>(); epi(p1, n + 1, 1, zB);
        issue(p1, n + 2, 1, wC, zC); wg_wait<1>(); epi(p0, n + 2, 0, zC);
        wg_wait<0>(); epi(p1, n + 2, 1, zC);
        n += 3;
        if (it == 0 && mE) ldw(wE, 3, phiE);
        if (mE >> it & 1) {
            issue(p0, n, 0, wE, zE);
            issue(p1, n, 1, wE, zE); wg_wait<1>(); epi(p0, n, 0, zE);
            wg_wait<0>(); epi(p1, n, 1, zE);
            n++;
        }
        PROFW(40 + wg * 8 + it * 2 + 1);
    }
}

__device__ __forceinline__ void task_p3(int wg, int pair, uint32_t sb) {
    const int tid = threadIdx.x & 127, w = tid >> 5, lane = tid & 31;
    const uint32_t buf = sb + (wg ? 3 - wg : 0) * 51200, bars = sb + BARS;
    uint32_t fr[10][4][2];
    float acc[2][16];
    zero(acc[0]); zero(acc[1]);
    {
        const Desc dB = mkdesc(sb + C3, 128, 256, 0);
        const uint32_t a0 = (buf & 0x3FFFF) >> 4;
        auto dq = [&](int Q) {
            return Desc{a0 + (uint32_t)((quad_off(Q) >> 4) | ((Q < 48 ? 2048 : 1024) >> 4) << 16), (uint32_t)((quad_off(Q + 1) - quad_off(Q)) >> 4) | (2u << 30)};
        };
        auto issue = [&](int f) {
            if (!(f & 1)) mbar_wait(bars + 8 * (B_YF + wg * 5 + (f >> 1)));
            wg_fence();
            wgmma_ss_n32_z(acc[f & 1], dq(5 * f), dB);
            wgmma_ss_n32_a(acc[f & 1], dq(5 * f + 1), dB + (uint32_t)(1024 >> 4));
            wgmma_ss_n32_a(acc[f & 1], dq(5 * f + 3), dB + (uint32_t)(2048 >> 4));
            wg_commit();
        };
        mbar_wait(bars + 8 * B_CF3);
        issue(0);
        PROFW(64 + wg * 8 + 1);
#pragma unroll
        for (int f = 0; f < 10; f++) {
            if (f < 9) { issue(f + 1); wg_wait<1>(); } else wg_wait<0>();
            float (&d)[16] = acc[f & 1];
            reg_fence(d);
#pragma unroll
            for (int g = 0; g < 4; g++) { fr[f][g][0] = pack2(d[4 * g], d[4 * g + 1]); fr[f][g][1] = pack2(d[4 * g + 2], d[4 * g + 3]); }
        }
    }
    PROFW(64 + wg * 8 + 2);
    {
        const Desc dB = mkdesc(sb + C3 + 3072, 128, 256, 0);
        const int i = lane & 7, mi = lane >> 3, th = w >> 1, tz = (2 * pair + th) & 3;
        const int oct = (2 * (w & 1) + (mi & 1)) ^ tz;
        const uint32_t soff = buf + th * 3584 + (mi >> 1) * 512 + i * 64 + ((oct ^ (i >> 1)) << 4);
        auto issue = [&](int t) {
            const int g = t < 6 ? 1 + (t >> 1) : 0;
            const uint32_t o = t < 6 ? (t & 1) * 1024 : 8960, st = t < 6 ? 1792 : 1024;
            wg_fence();
            wgmma_rs_n32_z(acc[t & 1], fr[0][g][0], fr[0][g][1], fr[1][g][0], fr[1][g][1], dB + (o >> 4));
#pragma unroll
            for (int s = 1; s < 5; s++) wgmma_rs_n32_a(acc[t & 1], fr[2 * s][g][0], fr[2 * s][g][1], fr[2 * s + 1][g][0], fr[2 * s + 1][g][1], dB + ((o + s * st) >> 4));
            wg_commit();
        };
        bb_break(sb);
        issue(0);
        wg_bar(1 + wg);
#pragma unroll
        for (int t = 0; t < 7; t++) {
            if (t < 6) { issue(t + 1); wg_wait<1>(); } else wg_wait<0>();
            float (&d)[16] = acc[t & 1];
            reg_fence(d);
            if (t < 6) {
                const uint32_t a = soff + (1 + (t >> 1)) * 7168 + (t & 1) * 2048;
                stm4(a, pack2(d[0], d[1]), pack2(d[2], d[3]), pack2(d[4], d[5]), pack2(d[6], d[7]));
                if (t & 1) stm2(a + 1024, pack2(d[8], d[9]), pack2(d[10], d[11]));
                else stm4(a + 1024, pack2(d[8], d[9]), pack2(d[10], d[11]), pack2(d[12], d[13]), pack2(d[14], d[15]));
            } else {
                const int row = th * 14 + 4 * (mi >> 1) + (i >> 1);
                const uint32_t a = buf + row * 128 + (i & 1) * 64 + ((oct ^ (row & 3)) << 4);
                stm4(a, pack2(d[0], d[1]), pack2(d[2], d[3]), pack2(d[4], d[5]), pack2(d[6], d[7]));
                stm4((lane & 20) == 20 ? buf + 4096 + lane * 16 : a + 1024, pack2(d[8], d[9]), pack2(d[10], d[11]), pack2(d[12], d[13]), pack2(d[14], d[15]));
            }
            if ((t & 1) || t == 6) { fence_async_smem(); e_arrive(bars + 8 * (B_RDY + R_P3 + wg * 4 + (t >> 1))); }
        }
    }
}

__device__ __forceinline__ void load_x(int cls, int rk, int u, uint32_t sb, const Maps& mp) {
    const int id = u * NH + rk, pl = id / 3, c0 = 32 * (id - 3 * pl), tp = cls * 4 + (pl >> 4), col = 14 * (pl & 15) - 8;
    const uint32_t bar = sb + BARS + 8 * (B_XF + u * 5), dst = sb + u * 51200;
    const int wrap = col < 0 ? 224 : 0;
    if (tp) {
#pragma unroll
        for (int g = 0; g < 5; g++) e_ld3(dst + g * 8704, &mp.x34, c0, col + 4 * g + (g < 2 ? wrap : 0), 28 * tp - 6, bar + 8 * g);
    } else {
#pragma unroll
        for (int g = 0; g < 5; g++) {
            e_ld3(dst + g * 8704, &mp.x6, c0, col + 4 * g + (g < 2 ? wrap : 0), 218, bar + 8 * g);
            e_ld3(dst + g * 8704 + 1536, &mp.x28, c0, col + 4 * g + (g < 2 ? wrap : 0), 0, bar + 8 * g);
        }
    }
}

__device__ __forceinline__ void load_x_box(int cls, int rk, int u, int g, uint32_t sb, const Maps& mp) {
    const int id = u * NH + rk, pl = id / 3, c0 = 32 * (id - 3 * pl), tp = cls * 4 + (pl >> 4), col = 14 * (pl & 15) - 8 + 4 * g;
    e_ld3(sb + u * 51200 + g * 8704, &mp.x34, c0, col < 0 ? col + 224 : col, 28 * tp - 6, sb + BARS + 8 * (B_XF + u * 5 + g));
}

__device__ __forceinline__ void load_first(uint32_t sb, const Maps& mp, const Ptrs& pt) {
    const uint32_t bars = sb + BARS;
    const int k = blockIdx.x;
    PROF(122);
    if (k < 129) {
        const int cb0 = 14 * k / 25, cb1 = min((14 * k + 13) / 25, 71);
#pragma unroll 1
        for (int cb = cb0; cb <= cb1; cb++) {
            const int b = cb / 24, i0 = 16 * ((cb >> 2) - 6 * b) + 2 * (cb & 3);
            const uint32_t bar = bars + 8 * (B_WF + 2 * (cb - cb0));
            e_expect(bar, 14336);
            e_ld4(sb + WP + (cb - cb0) * 14336, &mp.w, 32 * b, i0, bar);
            e_ld4(sb + WP + (cb - cb0) * 14336 + 7168, &mp.w, 32 * b, i0 + 8, bar);
        }
    }
    e_expect(bars + 8 * B_CF1, 17920); e_g2s(sb + C1, pt.tab1, 17920, bars + 8 * B_CF1);
    if ((threadIdx.x & 31) < 15) asm volatile("mbarrier.arrive.expect_tx.shared::cta.b64 _, [%0], 8704;" :: "r"(bars + 8 * (B_XF + (threadIdx.x & 31))) : "memory");
    __syncwarp();
}

__device__ __forceinline__ uint32_t get_rel(uint32_t sb) {
    mbar_wait(sb + BARS + 8 * B_REL);
    uint32_t v; asm volatile("ld.shared.u32 %0, [%1];" : "=r"(v) : "r"(sb + REL) : "memory");
    return uni(v);
}

__device__ __forceinline__ void load_warp(int cls, int rk, uint32_t sb, const Maps& mp, const Ptrs& pt) {
    const uint32_t bars = sb + BARS;
    mbar_wait(bars + 8 * (B_SIG + SIG_P1));
    PROF(1);
    const uint32_t rel = get_rel(sb);
    const char* cnt = cls_cnt(pt.scr, cls);
    const int mE = extra_mask(rk);
    const int lpA = phi_line(3 * rk, rel), lpB = phi_line(3 * rk + 1, rel), lpC = phi_line(3 * rk + 2, rel), lpE = phi_line(extra_phi(rk), rel);
    if ((threadIdx.x & 31) < 14) asm volatile("mbarrier.arrive.expect_tx.shared::cta.b64 _, [%0], 12288;" :: "r"(bars + 8 * (B_RF + (threadIdx.x & 31))) : "memory");
    __syncwarp();
    int n = 0;
#pragma unroll 1
    for (int pg = 0; pg < 4; pg++) {
        const int l0 = slot_line(0, pg, cls), l1 = slot_line(1, pg, cls), l2 = slot_line(2, pg, cls);
        auto unit = [&](int lp) {
            const uint32_t bar = bars + 8 * (B_RF + n), dst = sb + RG + ((n + 1) & 3) * 12288;
            mbar_wait(bars + 8 * (n >= 4 ? B_RE + n - 4 : B_WE + ((0x7163 >> (4 * n)) & 15)));
            e_g2s(dst, pt.scr + (size_t)(lp ^ l0) * 128, 4096, bar);
            e_g2s(dst + 4096, pt.scr + (size_t)(lp ^ l1) * 128, 4096, bar);
            e_g2s(dst + 8192, pt.scr + (size_t)(lp ^ l2) * 128, 4096, bar);
            n++;
        };
        cnt_wait(cnt + (CNT_P1 + pg) * 128, 48);
        PROF(88 + pg);
        unit(lpA); unit(lpB); unit(lpC);
        if (mE >> pg & 1) unit(lpE);
        if (pg == 1) { mbar_wait(bars + 8 * B_P1D); e_expect(bars + 8 * B_CF3, 17152); e_g2s(sb + C3, pt.tab3, 17152, bars + 8 * B_CF3); }
    }
}

__device__ __forceinline__ int near_page(char* p, int rounds) {
#pragma unroll
    for (int e = 0; e < 4; e++) asm volatile("st.relaxed.gpu.global.v4.u32 [%0], {%1, %1, %1, %1};" :: "l"(p + (e >> 1) * 4096 + (e & 1) * 16), "r"(0) : "memory");
    int score = 0;
#pragma unroll 1
    for (int r = 0; r < rounds; r++) {
        uint32_t v0, v1, t0, t1;
        asm volatile("atom.relaxed.gpu.global.exch.b32 %0, [%1], 1;" : "=r"(v0) : "l"(p + (r & 1) * 4096) : "memory");
        asm volatile("atom.relaxed.gpu.global.exch.b32 %0, [%1], 1;" : "=r"(v1) : "l"(p + (~r & 1) * 4096) : "memory");
        asm volatile("{\n.reg .pred p;\nsetp.ne.u32 p, %1, 0xffffffff;\nmov.u32 %0, 0;\n@p mov.u32 %0, %%clock;\n}" : "=r"(t0) : "r"(v0) : "memory");
        asm volatile("{\n.reg .pred p;\nsetp.ne.u32 p, %1, 0xffffffff;\nmov.u32 %0, 0;\n@p mov.u32 %0, %%clock;\n}" : "=r"(t1) : "r"(v1) : "memory");
        const int gap = min((int)(t1 - t0), 160) - 80;
        score += (r & 1) ? gap : -gap;

    }
    return score > 0;
}

__device__ __forceinline__ uint32_t find_role(uint32_t sb, char* scr) {
    const int k = blockIdx.x;
    int c = near_page(scr + (slot_line(3, 3, 0) + phi_line(1 + (k >> 5), 0) + (k & 31)) * 128, PROBES);
    PROF(3);
    int r;
    asm volatile("atom.relaxed.gpu.global.add.u32 %0, [%1], 1;" : "=r"(r) : "l"(cls_cnt(scr, c) + CNT_RANK * 128) : "memory");
    if (r >= NH) { c ^= 1; r = NSM - 1 - r; }
    asm volatile("st.shared.u32 [%0], %1;" :: "r"(sb + REL + 4), "r"(c << 8 | r) : "memory");
    PROF(5);
    return c << 8 | r;
}
__device__ __forceinline__ void get_role(uint32_t sb, int& cls, int& rk) {
    mbar_wait(sb + BARS + 8 * B_ROLE);
    uint32_t v; asm volatile("ld.shared.u32 %0, [%1];" : "=r"(v) : "r"(sb + REL + 4) : "memory");
    v = uni(v); cls = v >> 8; rk = v & 255;
}

__device__ __forceinline__ void load3_warp(int cls, int rk, uint32_t sb, const Maps& mp, const Ptrs& pt) {
    const uint32_t bars = sb + BARS;
    uint32_t rel = 0;
    mbar_wait(bars + 8 * B_XF);
    PROF(107);
    rel = cnt_wait(pt.cnt + CNT_REL * 32, 12u << 16);
    asm volatile("st.shared.u32 [%0], %1;" :: "r"(sb + REL), "r"(rel) : "memory");
    __syncwarp();
    e_arrive(bars + 8 * B_REL);
    PROF(7);
    mbar_wait(bars + 8 * (B_SIG + SIG_W));
    cnt_wait(cls_cnt(pt.scr, cls) + CNT_W * 128, NSM);
    PROF(2);
    {
        const int np = rk >= 60 ? 12 : 9;
#pragma unroll 1
        for (int o = 0; o < np; o++) {
            const int pc = (0xba9785421630ull >> (4 * o)) & 15;
            if (o == 4) mbar_wait(bars + 8 * (B_SIG + SIG_P1));
            if (o == 8) mbar_wait(bars + 8 * (B_WE + 0));
            e_expect(bars + 8 * (B_WL + pc), 12288);
            e_g2s(sb + wslot(pc), pt.wf + (pc < 9 ? 9 * rk + pc : 3 * extra_phi(rk) + pc - 9) * 12288, 12288, bars + 8 * (B_WL + pc));
        }
        if (np == 12) { mbar_wait(bars + 8 * (B_WE + 9)); mbar_wait(bars + 8 * (B_WE + 10)); mbar_wait(bars + 8 * (B_WE + 11)); }
    }
    mbar_wait(bars + 8 * (B_SIG + SIG_P2));
    const int nu = rk < 60 ? 3 : 2;
#pragma unroll 1
    for (int u = 0; u < nu; u++) {
        const int id = u * NH + rk, pl = id / 3, chunk = id - 3 * pl;
        const int l0 = slot_line(chunk, pl >> 4, cls) + (pl & 15) * 2;
        const uint32_t buf = sb + (u ? 3 - u : 0) * 51200, bar = bars + 8 * (B_YF + u * 5);
#pragma unroll
        for (int j = 0; j < 5; j++) e_expect(bar + 8 * j, j == 4 ? 10240 : (j & 1) ? 8192 : 12288);
        if (u == 2) mbar_wait(bars + 8 * (B_SIG + SIG_P2 + 3));
        cnt_wait(cls_cnt(pt.scr, cls) + (CNT_P2 + (pl >> 4)) * 128, NH);
        PROF(64 + u * 8);
        if (u == nu - 1) e_arrive(bars + 8 * B_FIN);
        const uint32_t r2 = uni(rel) << 5;
#pragma unroll
        for (int G = 0; G < 13; G++)
            e_ld5(buf + G * 4096, G < 12 ? &mp.f16 : &mp.f8, (l0 ^ ((r2 >> G) & 32)) + (G << 14), bar + 8 * ((2 * G) / 5));
    }
}

__device__ __forceinline__ void store_warp(uint32_t sb, const Maps& mp, const Ptrs& pt) {
    const uint32_t bars = sb + BARS;
    const int k = blockIdx.x;
    uint32_t pa = 0, pb = 0, qa = 0, qb = 0;
    auto arr2 = [&](uint32_t& a, uint32_t& b) { if (a) e_arrive(a); if (b) e_arrive(b); a = b = 0; };
    auto pre = [&](int idx) {
        const uint32_t bar = bars + 8 * idx;
        if (!mbar_test(bar)) { bulk_wait_read<0>(); arr2(qa, qb); arr2(pa, pb); mbar_wait(bar); }
    };
    auto post = [&](uint32_t fr) {
        bulk_commit(); bulk_wait_read<SWIN - 1>();
        if (SWIN == 3) { arr2(qa, qb); qa = pa; qb = pb; pb = 0; } else arr2(pa, pb);
        pa = fr;
    };
    auto after = [&](uint32_t a, uint32_t b) { if (a) pa = a; pb = b; };
    auto pace = [&](uint32_t) {};
    int cls, rk; get_role(sb, cls, rk);
    {
        int cb = 14 * k / 25, oc = 14 * k - 25 * cb;
        int g1 = 0;
#pragma unroll 1
        for (int i = 0; i < 14 && cb < 72; i++) {
            pre(B_WRD + i);
            if (PACE) pace(4 * PACE);
            e_st3(&mp.wst, sb + wst_off(i), 0, 8 * oc, cb);
            post(0);
            if (T1MASK >> i & 1) load_x_box(cls, rk, 1, g1++, sb, mp);
            if (++oc == 25) { oc = 0; cb++; }
        }
#pragma unroll 1
        for (; g1 < 5; g1++) load_x_box(cls, rk, 1, g1, sb, mp);
        if (X1AT && 14 * k + X1AT > 1800) e_arrive(bars + 8 * B_X1);
        after(bars + 8 * B_WFREE, bars + 8 * (B_SIG + SIG_W));
    }
    pre(B_REL);
    const uint32_t rel = get_rel(sb);
    const int nu = rk < 60 ? 3 : 2;
#pragma unroll 1
    for (int u = 0; u < nu; u++) {
        const int id = u * NH + rk, pl = id / 3, chunk = id - 3 * pl;
        const int l0 = slot_line(chunk, pl >> 4, cls) + (pl & 15) * 2;
        int j = B_RDY + u * 5;
        int g2 = 0;
        const int m2 = (u == 0 && nu == 3) ? T2MASK : 0;
#pragma unroll 1
        for (int G = 0; G < 13; G++) {
            if (0x4a5 >> G & 1) pre(j++);
            if (PACE) pace(G < 12 ? 4 * PACE : 2 * PACE);
            e_st5(G < 12 ? &mp.f16 : &mp.f8, sb + u * 51200 + G * 4096, (l0 ^ ((rel >> G) & 1) << 5) + (G << 14));
            post(0);
            if (m2 >> G & 1) load_x_box(cls, rk, 2, g2++, sb, mp);
        }
        after(0, bars + 8 * (B_SIG + SIG_P1 + u));
    }
    const int mE = extra_mask(rk);
    int n = 0;
#pragma unroll 1
    for (int pg = 0; pg < 4; pg++) {
        const int nj = 3 + (mE >> pg & 1);
        const int l0 = slot_line(0, pg, cls), l1 = slot_line(1, pg, cls), l2 = slot_line(2, pg, cls);
#pragma unroll 1
        for (int j = 0; j < nj; j++) {
            const int lp = phi_line(j == 3 ? extra_phi(rk) : 3 * rk + j, rel);
#pragma unroll
            for (int b = 0; b < 3; b++) {
                pre(B_RDY + R_P2 + n * 3 + b);
                if (PACE) pace(4 * PACE);
                e_s2g(pt.scr + (size_t)(lp ^ (b == 0 ? l0 : b == 1 ? l1 : l2)) * 128, sb + S1 + (n & 3) * 12288 + b * 4096, 4096);
                post(bars + 8 * (B_SFREE + n * 3 + b));
            }
            n++;
        }
        after(0, bars + 8 * (B_SIG + SIG_P2 + pg));
    }
#pragma unroll 1
    for (int u = 0; u < nu; u++) {
        const int id = u * NH + rk, pl = id / 3, chunk = id - 3 * pl, tp = cls * 4 + (pl >> 4), tx = pl & 15;
        const uint32_t buf = sb + (u ? 3 - u : 0) * 51200;
#pragma unroll
        for (int gg = 1; gg < 5; gg++) {
            pre(B_RDY + R_P3 + u * 4 + gg - 1);
            if (u < 2) pace(gg < 4 ? 7 * YPACE : 7 * YPACE / 2);
            if (gg < 4) e_st3(&mp.y4, buf + gg * 7168, 32 * chunk, 14 * tx - 4 + 4 * gg, 28 * tp);
            else e_st3(&mp.y2, buf, 32 * chunk, tx == 0 ? 222 : 14 * tx - 2, 28 * tp);
            post(0);
        }
    }
    bulk_wait_read<0>();
    PROF(113);
    prof_dump();
}

__device__ __forceinline__ void signal_warp(int cls, int rk, uint32_t sb, const Ptrs& pt) {
    const uint32_t bars = sb + BARS;
    char* cnt = cls_cnt(pt.scr, cls);
    if (threadIdx.x & 31) return;
#pragma unroll 1
    for (int c = 0; c < 8; c++) {
        if (c == SIG_P1 + 2 && rk >= 60) continue;
        char* ctr = cnt + (c == SIG_W ? CNT_W : c < SIG_P2 ? CNT_P1 + ((c - SIG_P1) * NH + rk) / 48 : CNT_P2 + c - SIG_P2) * 128;
        mbar_wait(bars + 8 * (B_SIG + c));
        PROF(32 + c);
        fence_async();
        asm volatile("red.relaxed.gpu.global.add.u32 [%0], 1;" :: "l"(ctr) : "memory");
        if (c == SIG_W) asm volatile("red.relaxed.gpu.global.add.u32 [%0], 1;" :: "l"((uintptr_t)ctr ^ 4096) : "memory");
        PROF(96 + c);
    }
    mbar_wait(bars + 8 * B_FIN);
    unsigned old;
    asm volatile("atom.add.relaxed.gpu.global.u32 %0, [%1], 1;" : "=r"(old) : "l"(pt.cnt + CNT_DONE * 32) : "memory");
    if (old == NSM - 1) {
#pragma unroll
        for (int c = 0; c < NCNT; c++) pt.cnt[c * 32] = 0;
#pragma unroll 1
        for (int c = 0; c < NCLS; c++) { *reinterpret_cast<unsigned*>(cnt + c * 128) = 0; *reinterpret_cast<unsigned*>(((uintptr_t)cnt ^ 4096) + c * 128) = 0; }
    }
}

__global__ void __launch_bounds__(512, 1) fftconv_kernel(const Ptrs pt, const __grid_constant__ Maps mp) {
    extern __shared__ __align__(1024) uint8_t smem[];
    const uint32_t sb = smem_u32(smem);
    const int tid = threadIdx.x, warp = uni(tid >> 5), wg = warp >> 2;
    int cls, rk;
    auto bar_init = [&](int i) {
        uint32_t c = 1;
        if (i == B_P1D || (i >= B_RE && i < B_RE + 14)) c = 12;
        else if (i >= B_WCH && i < B_WL) c = 4;
        asm volatile("st.shared.v2.u32 [%0], {%1, %2};" :: "r"(sb + BARS + 8 * i), "r"((0x100000u - c) << 1), "r"((0x100000u - c) << 11) : "memory");
        fence_async_smem();
    };
    if (wg == 3) {
        asm volatile("setmaxnreg.dec.sync.aligned.u32 32;");
        if (warp == 12) {
            bar_init(tid & 31);
            __syncwarp();
            asm volatile("bar.arrive 4, 416;" ::: "memory");
            load_first(sb, mp, pt);
            PROF(106);
            asm volatile("bar.sync 5, 416;" ::: "memory");
            get_role(sb, cls, rk);
            load_warp(cls, rk, sb, mp, pt);
        } else if (warp == 13) {
            if ((tid & 31) < 8) asm volatile("prefetch.tensormap [%0];" :: "l"(reinterpret_cast<const CUtensorMap*>(&mp) + 1 + (tid & 31)) : "memory");
            __syncwarp();
            asm volatile("bar.sync 6, 416;" ::: "memory");
            store_warp(sb, mp, pt);
        } else if (warp == 14) {
            const int G = blockIdx.x - 119;
            int sel = 0;
            if (G >= 1 && (tid & 31) == 0) sel = near_page(pt.scr + ((size_t)G << 21) + slot_line(3, 3, 0) * 128, 2);
            __syncwarp();
            asm volatile("bar.sync 7, 416;" ::: "memory");
            get_role(sb, cls, rk);
            if (G >= 1 && (tid & 31) == 0) asm volatile("red.relaxed.gpu.global.add.u32 [%0], %1;" :: "l"(pt.cnt + CNT_REL * 32), "r"(0x10000u | (uint32_t)(sel ^ cls) << G) : "memory");
            __syncwarp();
            load3_warp(cls, rk, sb, mp, pt);
        } else {
            uint32_t role = 0;
            if ((tid & 31) == 0) role = find_role(sb, pt.scr);
            role = uni(role); cls = role >> 8; rk = role & 255;
            asm volatile("bar.sync 8, 416;" ::: "memory");
            load_x(cls, rk, 0, sb, mp);
            PROF(123);
            e_arrive(sb + BARS + 8 * B_ROLE);
            signal_warp(cls, rk, sb, pt);
        }
    } else {
        if (tid >= 32 && tid < NBAR) bar_init(tid);
        {
            const int r = tid % 40;
            asm volatile("st.shared.u32 [%0], %1;" :: "r"(sb + TBL + 4 * tid), "r"(cos_bits(r) | (cos_bits(r < 30 ? r + 10 : r - 30) << 16)) : "memory");
        }
        __syncwarp();
        asm volatile("bar.sync 4, 416;" ::: "memory");
        asm volatile("bar.arrive 5, 416;" ::: "memory");
        asm volatile("bar.arrive 6, 416;" ::: "memory");
        asm volatile("bar.arrive 7, 416;" ::: "memory");
        asm volatile("bar.arrive 8, 416;" ::: "memory");
        PROF(121);
        task_w(wg, blockIdx.x, sb);
        asm volatile("setmaxnreg.inc.sync.aligned.u32 160;");
        get_role(sb, cls, rk);
        const int id = wg * NH + rk;
        PROFW(8 + wg * 8);
        if (id < 192) task_p1(wg, id / 3, sb);
        e_arrive(sb + BARS + 8 * B_P1D);
        PROFW(8 + wg * 8 + 3);
        task_p2(wg, rk, sb);
        if (id < 192) task_p3(wg, id / 3, sb);
        PROFW(64 + wg * 8 + 3);
        prof_dump();
    }
}

typedef CUresult (*EncodeFn)(CUtensorMap*, CUtensorMapDataType, cuuint32_t, void*, const cuuint64_t*, const cuuint64_t*, const cuuint32_t*, const cuuint32_t*,
                             CUtensorMapInterleave, CUtensorMapSwizzle, CUtensorMapL2promotion, CUtensorMapFloatOOBfill);

static void encode3(EncodeFn fn, CUtensorMap* m, void* ptr, uint64_t d0, uint64_t d1, uint64_t d2, uint64_t s1, uint64_t s2,
                    uint32_t b0, uint32_t b1, uint32_t b2, CUtensorMapSwizzle sw) {
    cuuint64_t dims[3] = {d0, d1, d2}, strides[2] = {s1, s2};
    cuuint32_t box[3] = {b0, b1, b2}, es[3] = {1, 1, 1};
    fn(m, CU_TENSOR_MAP_DATA_TYPE_BFLOAT16, 3, ptr, dims, strides, box, es, CU_TENSOR_MAP_INTERLEAVE_NONE, sw,
       CU_TENSOR_MAP_L2_PROMOTION_NONE, CU_TENSOR_MAP_FLOAT_OOB_FILL_NONE);
}

extern "C" void kernel_launch(void* const* d_in, const int* in_sizes, int n_in, void* d_out, int out_size) {
    (void)in_sizes; (void)n_in; (void)out_size;
    void* fnp = nullptr; cudaDriverEntryPointQueryResult qr;
    cudaGetDriverEntryPoint("cuTensorMapEncodeTiled", &fnp, cudaEnableDefault, &qr);
    EncodeFn fn = (EncodeFn)fnp;
    void* xf = nullptr; cudaGetSymbolAddress(&xf, g_scr);
    xf = (void*)(((uintptr_t)xf + (1u << 21) - 1) & ~(uintptr_t)((1u << 21) - 1));
    void* wf = nullptr; cudaGetSymbolAddress(&wf, g_wf);
    Maps mp;
    Ptrs pt;
    pt.scr = (char*)xf; pt.wf = (const char*)wf;
    void* p = nullptr;
    cudaGetSymbolAddress(&p, TAB_P1); pt.tab1 = p;
    cudaGetSymbolAddress(&p, TAB_P3); pt.tab3 = p;
    cudaGetSymbolAddress(&p, g_cnt); pt.cnt = (unsigned*)p;
    {
        cuuint32_t b16[5] = {64, 4, 2, 2, 2}, b8[5] = {64, 4, 2, 1, 2}, es[5] = {1, 1, 1, 1, 1};
        cuuint64_t d[5] = {64, 4, 2, 2, 13 << 14}, st[4] = {16384, 262144, 1048576, 128};
        fn(&mp.f16, CU_TENSOR_MAP_DATA_TYPE_BFLOAT16, 5, xf, d, st, b16, es, CU_TENSOR_MAP_INTERLEAVE_NONE, CU_TENSOR_MAP_SWIZZLE_NONE, CU_TENSOR_MAP_L2_PROMOTION_NONE, CU_TENSOR_MAP_FLOAT_OOB_FILL_NONE);
        fn(&mp.f8, CU_TENSOR_MAP_DATA_TYPE_BFLOAT16, 5, xf, d, st, b8, es, CU_TENSOR_MAP_INTERLEAVE_NONE, CU_TENSOR_MAP_SWIZZLE_NONE, CU_TENSOR_MAP_L2_PROMOTION_NONE, CU_TENSOR_MAP_FLOAT_OOB_FILL_NONE);
    }
    encode3(fn, &mp.x6, d_in[0], 96, 224, 224, 192, 224 * 192, 32, 4, 6, CU_TENSOR_MAP_SWIZZLE_64B);
    encode3(fn, &mp.x34, d_in[0], 96, 224, 224, 192, 224 * 192, 32, 4, 34, CU_TENSOR_MAP_SWIZZLE_64B);
    encode3(fn, &mp.x28, d_in[0], 96, 224, 224, 192, 224 * 192, 32, 4, 28, CU_TENSOR_MAP_SWIZZLE_64B);
    {
        cuuint32_t box[4] = {32, 8, 7, 2}, es[4] = {1, 1, 1, 1};
        cuuint64_t d[4] = {96, 7, 7, 96}, st[3] = {18432, 7 * 18432, 192};
        fn(&mp.w, CU_TENSOR_MAP_DATA_TYPE_BFLOAT16, 4, d_in[1], d, st, box, es, CU_TENSOR_MAP_INTERLEAVE_NONE, CU_TENSOR_MAP_SWIZZLE_64B, CU_TENSOR_MAP_L2_PROMOTION_NONE, CU_TENSOR_MAP_FLOAT_OOB_FILL_NONE);
    }
    encode3(fn, &mp.wst, wf, 256, 200, 72, 36864, 512, 256, 8, 1, CU_TENSOR_MAP_SWIZZLE_NONE);
    encode3(fn, &mp.y4, d_out, 96, 224, 224, 192, 224 * 192, 32, 4, 28, CU_TENSOR_MAP_SWIZZLE_64B);
    encode3(fn, &mp.y2, d_out, 96, 224, 224, 192, 224 * 192, 32, 2, 28, CU_TENSOR_MAP_SWIZZLE_64B);
    constexpr int SMEM_LAUNCH = SMEM_BYTES;
    cudaFuncSetAttribute(fftconv_kernel, cudaFuncAttributeMaxDynamicSharedMemorySize, SMEM_LAUNCH);
    fftconv_kernel<<<NSM, 512, SMEM_LAUNCH>>>(pt, mp);
}
```

```cpp
#include <cuda_runtime.h>
#include <cuda_bf16.h>
#include <cuda.h>
#include <stdint.h>

__device__ __align__(128) const uint32_t TAB_P1[4480] = {
0x3e75,0,0x3e72,0,0x8000,0,0xbd19,0,0x3e750000,0,0x3e720000,0,0x80000000,0,0xbd190000,0,
0,0x3e75,0,0x3e72,0,0x8000,0,0xbd19,0,0x3e750000,0,0x3e720000,0,0x80000000,0,0xbd190000,
0x3e69,0,0x3e5a,0,0xbd97,0,0xbdde,0,0x3e690000,0,0x3e5a0000,0,0xbd970000,0,0xbdde0000,0,
0,0x3e69,0,0x3e5a,0,0xbd97,0,0xbdde,0,0x3e690000,0,0x3e5a0000,0,0xbd970000,0,0xbdde0000,
0x3e75,0,0x3e5a,0,0x8000,0,0xbdde,0,0x3e750000,0,0x3e5a0000,0,0x80000000,0,0xbdde0000,0,
0,0x3e75,0,0x3e5a,0,0x8000,0,0xbdde,0,0x3e750000,0,0x3e5a0000,0,0x80000000,0,0xbdde0000,
0x3e10,0,0x3d19,0,0xbe46,0,0xbe72,0,0x3e100000,0,0x3d190000,0,0xbe460000,0,0xbe720000,0,
0,0x3e10,0,0x3d19,0,0xbe46,0,0xbe72,0,0x3e100000,0,0x3d190000,0,0xbe460000,0,0xbe720000,
0x3e75,0,0x3e2d,0,0x8000,0,0xbe2d,0,0x3e750000,0,0x3e2d0000,0,0x80000000,0,0xbe2d0000,0,
0,0x3e75,0,0x3e2d,0,0x8000,0,0xbe2d,0,0x3e750000,0,0x3e2d0000,0,0x80000000,0,0xbe2d0000,
0,0,0xbe2d,0,0xbe75,0,0xbe2d,0,0,0,0xbe2d0000,0,0xbe750000,0,0xbe2d0000,0,
0,0,0,0xbe2d,0,0xbe75,0,0xbe2d,0,0,0,0xbe2d0000,0,0xbe750000,0,0xbe2d0000,
0x3e75,0,0x3dde,0,0x8000,0,0xbe5a,0,0x3e750000,0,0x3dde0000,0,0x80000000,0,0xbe5a0000,0,
0,0x3e75,0,0x3dde,0,0x8000,0,0xbe5a,0,0x3e750000,0,0x3dde0000,0,0x80000000,0,0xbe5a0000,
0xbe10,0,0xbe72,0,0xbe46,0,0x3d19,0,0xbe100000,0,0xbe720000,0,0xbe460000,0,0x3d190000,0,
0,0xbe10,0,0xbe72,0,0xbe46,0,0x3d19,0,0xbe100000,0,0xbe720000,0,0xbe460000,0,0x3d190000,
0x3e75,0,0x3d19,0,0x8000,0,0xbe72,0,0x3e750000,0,0x3d190000,0,0x80000000,0,0xbe720000,0,
0,0x3e75,0,0x3d19,0,0x8000,0,0xbe72,0,0x3e750000,0,0x3d190000,0,0x80000000,0,0xbe720000,
0xbe69,0,0xbdde,0,0xbd97,0,0x3e5a,0,0xbe690000,0,0xbdde0000,0,0xbd970000,0,0x3e5a0000,0,
0,0xbe69,0,0xbdde,0,0xbd97,0,0x3e5a,0,0xbe690000,0,0xbdde0000,0,0xbd970000,0,0x3e5a0000,
0x3e75,0,0xbd19,0,0x8000,0,0xbe72,0,0x3e750000,0,0xbd190000,0,0x80000000,0,0xbe720000,0,
0,0x3e75,0,0xbd19,0,0x8000,0,0xbe72,0,0x3e750000,0,0xbd190000,0,0x80000000,0,0xbe720000,
0xbe69,0,0x3dde,0,0x3d97,0,0x3e5a,0,0xbe690000,0,0x3dde0000,0,0x3d970000,0,0x3e5a0000,0,
0,0xbe69,0,0x3dde,0,0x3d97,0,0x3e5a,0,0xbe690000,0,0x3dde0000,0,0x3d970000,0,0x3e5a0000,
0x3e75,0,0xbdde,0,0x8000,0,0xbe5a,0,0x3e750000,0,0xbdde0000,0,0x80000000,0,0xbe5a0000,0,
0,0x3e75,0,0xbdde,0,0x8000,0,0xbe5a,0,0x3e750000,0,0xbdde0000,0,0x80000000,0,0xbe5a0000,
0xbe10,0,0x3e72,0,0x3e46,0,0x3d19,0,0xbe100000,0,0x3e720000,0,0x3e460000,0,0x3d190000,0,
0,0xbe10,0,0x3e72,0,0x3e46,0,0x3d19,0,0xbe100000,0,0x3e720000,0,0x3e460000,0,0x3d190000,
0x3e75,0,0xbe2d,0,0x8000,0,0xbe2d,0,0x3e750000,0,0xbe2d0000,0,0x80000000,0,0xbe2d0000,0,
0,0x3e75,0,0xbe2d,0,0x8000,0,0xbe2d,0,0x3e750000,0,0xbe2d0000,0,0x80000000,0,0xbe2d0000,
0,0,0x3e2d,0,0x3e75,0,0xbe2d,0,0,0,0x3e2d0000,0,0x3e750000,0,0xbe2d0000,0,
0,0,0,0x3e2d,0,0x3e75,0,0xbe2d,0,0,0,0x3e2d0000,0,0x3e750000,0,0xbe2d0000,
0x3e75,0,0xbe5a,0,0x8000,0,0xbdde,0,0x3e750000,0,0xbe5a0000,0,0x80000000,0,0xbdde0000,0,
0,0x3e75,0,0xbe5a,0,0x8000,0,0xbdde,0,0x3e750000,0,0xbe5a0000,0,0x80000000,0,0xbdde0000,
0x3e10,0,0xbd19,0,0x3e46,0,0xbe72,0,0x3e100000,0,0xbd190000,0,0x3e460000,0,0xbe720000,0,
0,0x3e10,0,0xbd19,0,0x3e46,0,0xbe72,0,0x3e100000,0,0xbd190000,0,0x3e460000,0,0xbe720000,
0x3e75,0,0xbe72,0,0x8000,0,0xbd19,0,0x3e750000,0,0xbe720000,0,0x80000000,0,0xbd190000,0,
0,0x3e75,0,0xbe72,0,0x8000,0,0xbd19,0,0x3e750000,0,0xbe720000,0,0x80000000,0,0xbd190000,
0x3e69,0,0xbe5a,0,0x3d97,0,0xbdde,0,0x3e690000,0,0xbe5a0000,0,0x3d970000,0,0xbdde0000,0,
0,0x3e69,0,0xbe5a,0,0x3d97,0,0xbdde,0,0x3e690000,0,0xbe5a0000,0,0x3d970000,0,0xbdde0000,
0x3e46,0,0x3e2d,0,0xbe10,0,0xbe2d,0,0x3e460000,0,0x3e2d0000,0,0xbe100000,0,0xbe2d0000,0,
0,0x3e46,0,0x3e2d,0,0xbe10,0,0xbe2d,0,0x3e460000,0,0x3e2d0000,0,0xbe100000,0,0xbe2d0000,
0x3e10,0,0x3dde,0,0xbe46,0,0xbe5a,0,0x3e100000,0,0x3dde0000,0,0xbe460000,0,0xbe5a0000,0,
0,0x3e10,0,0x3dde,0,0xbe46,0,0xbe5a,0,0x3e100000,0,0x3dde0000,0,0xbe460000,0,0xbe5a0000,
0xbd97,0,0xbe2d,0,0xbe69,0,0xbe2d,0,0xbd970000,0,0xbe2d0000,0,0xbe690000,0,0xbe2d0000,0,
0,0xbd97,0,0xbe2d,0,0xbe69,0,0xbe2d,0,0xbd970000,0,0xbe2d0000,0,0xbe690000,0,0xbe2d0000,
0xbe69,0,0xbe72,0,0xbd97,0,0x3d19,0,0xbe690000,0,0xbe720000,0,0xbd970000,0,0x3d190000,0,
0,0xbe69,0,0xbe72,0,0xbd97,0,0x3d19,0,0xbe690000,0,0xbe720000,0,0xbd970000,0,0x3d190000,
0xbe75,0,0xbe2d,0,0x8000,0,0x3e2d,0,0xbe750000,0,0xbe2d0000,0,0x80000000,0,0x3e2d0000,0,
0,0xbe75,0,0xbe2d,0,0x8000,0,0x3e2d,0,0xbe750000,0,0xbe2d0000,0,0x80000000,0,0x3e2d0000,
0,0,0x3e2d,0,0x3e75,0,0x3e2d,0,0,0,0x3e2d0000,0,0x3e750000,0,0x3e2d0000,0,
0,0,0,0x3e2d,0,0x3e75,0,0x3e2d,0,0,0,0x3e2d0000,0,0x3e750000,0,0x3e2d0000,
0xbd97,0,0x3e2d,0,0x3e69,0,0x3e2d,0,0xbd970000,0,0x3e2d0000,0,0x3e690000,0,0x3e2d0000,0,
0,0xbd97,0,0x3e2d,0,0x3e69,0,0x3e2d,0,0xbd970000,0,0x3e2d0000,0,0x3e690000,0,0x3e2d0000,
0x3e69,0,0x3d19,0,0xbd97,0,0xbe72,0,0x3e690000,0,0x3d190000,0,0xbd970000,0,0xbe720000,0,
0,0x3e69,0,0x3d19,0,0xbd97,0,0xbe72,0,0x3e690000,0,0x3d190000,0,0xbd970000,0,0xbe720000,
0x3e46,0,0x3e2d,0,0x3e10,0,0xbe2d,0,0x3e460000,0,0x3e2d0000,0,0x3e100000,0,0xbe2d0000,0,
0,0x3e46,0,0x3e2d,0,0x3e10,0,0xbe2d,0,0x3e460000,0,0x3e2d0000,0,0x3e100000,0,0xbe2d0000,
0xbe10,0,0xbe5a,0,0xbe46,0,0x3dde,0,0xbe100000,0,0xbe5a0000,0,0xbe460000,0,0x3dde0000,0,
0,0xbe10,0,0xbe5a,0,0xbe46,0,0x3dde,0,0xbe100000,0,0xbe5a0000,0,0xbe460000,0,0x3dde0000,
0x3e46,0,0xbe2d,0,0xbe10,0,0xbe2d,0,0x3e460000,0,0xbe2d0000,0,0xbe100000,0,0xbe2d0000,0,
0,0x3e46,0,0xbe2d,0,0xbe10,0,0xbe2d,0,0x3e460000,0,0xbe2d0000,0,0xbe100000,0,0xbe2d0000,
0xbe10,0,0x3e5a,0,0x3e46,0,0x3dde,0,0xbe100000,0,0x3e5a0000,0,0x3e460000,0,0x3dde0000,0,
0,0xbe10,0,0x3e5a,0,0x3e46,0,0x3dde,0,0xbe100000,0,0x3e5a0000,0,0x3e460000,0,0x3dde0000,
0xbd97,0,0xbe2d,0,0xbe69,0,0x3e2d,0,0xbd970000,0,0xbe2d0000,0,0xbe690000,0,0x3e2d0000,0,
0,0xbd97,0,0xbe2d,0,0xbe69,0,0x3e2d,0,0xbd970000,0,0xbe2d0000,0,0xbe690000,0,0x3e2d0000,
0x3e69,0,0xbd19,0,0x3d97,0,0xbe72,0,0x3e690000,0,0xbd190000,0,0x3d970000,0,0xbe720000,0,
0,0x3e69,0,0xbd19,0,0x3d97,0,0xbe72,0,0x3e690000,0,0xbd190000,0,0x3d970000,0,0xbe720000,
0xbe75,0,0x3e2d,0,0x8000,0,0x3e2d,0,0xbe750000,0,0x3e2d0000,0,0x80000000,0,0x3e2d0000,0,
0,0xbe75,0,0x3e2d,0,0x8000,0,0x3e2d,0,0xbe750000,0,0x3e2d0000,0,0x80000000,0,0x3e2d0000,
0,0,0xbe2d,0,0xbe75,0,0x3e2d,0,0,0,0xbe2d0000,0,0xbe750000,0,0x3e2d0000,0,
0,0,0,0xbe2d,0,0xbe75,0,0x3e2d,0,0,0,0xbe2d0000,0,0xbe750000,0,0x3e2d0000,
0xbd97,0,0x3e2d,0,0x3e69,0,0xbe2d,0,0xbd970000,0,0x3e2d0000,0,0x3e690000,0,0xbe2d0000,0,
0,0xbd97,0,0x3e2d,0,0x3e69,0,0xbe2d,0,0xbd970000,0,0x3e2d0000,0,0x3e690000,0,0xbe2d0000,
0xbe69,0,0x3e72,0,0x3d97,0,0x3d19,0,0xbe690000,0,0x3e720000,0,0x3d970000,0,0x3d190000,0,
0,0xbe69,0,0x3e72,0,0x3d97,0,0x3d19,0,0xbe690000,0,0x3e720000,0,0x3d970000,0,0x3d190000,
0x3e46,0,0xbe2d,0,0x3e10,0,0xbe2d,0,0x3e460000,0,0xbe2d0000,0,0x3e100000,0,0xbe2d0000,0,
0,0x3e46,0,0xbe2d,0,0x3e10,0,0xbe2d,0,0x3e460000,0,0xbe2d0000,0,0x3e100000,0,0xbe2d0000,
0x3e10,0,0xbdde,0,0x3e46,0,0xbe5a,0,0x3e100000,0,0xbdde0000,0,0x3e460000,0,0xbe5a0000,0,
0,0x3e10,0,0xbdde,0,0x3e46,0,0xbe5a,0,0x3e100000,0,0xbdde0000,0,0x3e460000,0,0xbe5a0000,
0x3d97,0,0x3d19,0,0xbe69,0,0xbe72,0,0x3d970000,0,0x3d190000,0,0xbe690000,0,0xbe720000,0,
0,0x3d97,0,0x3d19,0,0xbe69,0,0xbe72,0,0x3d970000,0,0x3d190000,0,0xbe690000,0,0xbe720000,
0,0,0xbd19,0,0xbe75,0,0xbe72,0,0,0,0xbd190000,0,0xbe750000,0,0xbe720000,0,
0,0,0,0xbd19,0,0xbe75,0,0xbe72,0,0,0,0xbd190000,0,0xbe750000,0,0xbe720000,
0xbe46,0,0xbdde,0,0x3e10,0,0x3e5a,0,0xbe460000,0,0xbdde0000,0,0x3e100000,0,0x3e5a0000,0,
0,0xbe46,0,0xbdde,0,0x3e10,0,0x3e5a,0,0xbe460000,0,0xbdde0000,0,0x3e100000,0,0x3e5a0000,
0,0,0x3dde,0,0x3e75,0,0x3e5a,0,0,0,0x3dde0000,0,0x3e750000,0,0x3e5a0000,0,
0,0,0,0x3dde,0,0x3e75,0,0x3e5a,0,0,0,0x3dde0000,0,0x3e750000,0,0x3e5a0000,
0x3e75,0,0x3e2d,0,0x8000,0,0xbe2d,0,0x3e750000,0,0x3e2d0000,0,0x80000000,0,0xbe2d0000,0,
0,0x3e75,0,0x3e2d,0,0x8000,0,0xbe2d,0,0x3e750000,0,0x3e2d0000,0,0x80000000,0,0xbe2d0000,
0,0,0xbe2d,0,0xbe75,0,0xbe2d,0,0,0,0xbe2d0000,0,0xbe750000,0,0xbe2d0000,0,
0,0,0,0xbe2d,0,0xbe75,0,0xbe2d,0,0,0,0xbe2d0000,0,0xbe750000,0,0xbe2d0000,
0xbe46,0,0xbe5a,0,0xbe10,0,0x3dde,0,0xbe460000,0,0xbe5a0000,0,0xbe100000,0,0x3dde0000,0,
0,0xbe46,0,0xbe5a,0,0xbe10,0,0x3dde,0,0xbe460000,0,0xbe5a0000,0,0xbe100000,0,0x3dde0000,
0,0,0x3e5a,0,0x3e75,0,0x3dde,0,0,0,0x3e5a0000,0,0x3e750000,0,0x3dde0000,0,
0,0,0,0x3e5a,0,0x3e75,0,0x3dde,0,0,0,0x3e5a0000,0,0x3e750000,0,0x3dde0000,
0x3d97,0,0x3e72,0,0x3e69,0,0xbd19,0,0x3d970000,0,0x3e720000,0,0x3e690000,0,0xbd190000,0,
0,0x3d97,0,0x3e72,0,0x3e69,0,0xbd19,0,0x3d970000,0,0x3e720000,0,0x3e690000,0,0xbd190000,
0,0,0xbe72,0,0xbe75,0,0xbd19,0,0,0,0xbe720000,0,0xbe750000,0,0xbd190000,0,
0,0,0,0xbe72,0,0xbe75,0,0xbd19,0,0,0,0xbe720000,0,0xbe750000,0,0xbd190000,
0x3d97,0,0xbe72,0,0xbe69,0,0xbd19,0,0x3d970000,0,0xbe720000,0,0xbe690000,0,0xbd190000,0,
0,0x3d97,0,0xbe72,0,0xbe69,0,0xbd19,0,0x3d970000,0,0xbe720000,0,0xbe690000,0,0xbd190000,
0,0,0x3e72,0,0x3e75,0,0xbd19,0,0,0,0x3e720000,0,0x3e750000,0,0xbd190000,0,
0,0,0,0x3e72,0,0x3e75,0,0xbd19,0,0,0,0x3e720000,0,0x3e750000,0,0xbd190000,
0xbe46,0,0x3e5a,0,0x3e10,0,0x3dde,0,0xbe460000,0,0x3e5a0000,0,0x3e100000,0,0x3dde0000,0,
0,0xbe46,0,0x3e5a,0,0x3e10,0,0x3dde,0,0xbe460000,0,0x3e5a0000,0,0x3e100000,0,0x3dde0000,
0,0,0xbe5a,0,0xbe75,0,0x3dde,0,0,0,0xbe5a0000,0,0xbe750000,0,0x3dde0000,0,
0,0,0,0xbe5a,0,0xbe75,0,0x3dde,0,0,0,0xbe5a0000,0,0xbe750000,0,0x3dde0000,
0x3e75,0,0xbe2d,0,0x8000,0,0xbe2d,0,0x3e750000,0,0xbe2d0000,0,0x80000000,0,0xbe2d0000,0,
0,0x3e75,0,0xbe2d,0,0x8000,0,0xbe2d,0,0x3e750000,0,0xbe2d0000,0,0x80000000,0,0xbe2d0000,
0,0,0x3e2d,0,0x3e75,0,0xbe2d,0,0,0,0x3e2d0000,0,0x3e750000,0,0xbe2d0000,0,
0,0,0,0x3e2d,0,0x3e75,0,0xbe2d,0,0,0,0x3e2d0000,0,0x3e750000,0,0xbe2d0000,
0xbe46,0,0x3dde,0,0xbe10,0,0x3e5a,0,0xbe460000,0,0x3dde0000,0,0xbe100000,0,0x3e5a0000,0,
0,0xbe46,0,0x3dde,0,0xbe10,0,0x3e5a,0,0xbe460000,0,0x3dde0000,0,0xbe100000,0,0x3e5a0000,
0,0,0xbdde,0,0xbe75,0,0x3e5a,0,0,0,0xbdde0000,0,0xbe750000,0,0x3e5a0000,0,
0,0,0,0xbdde,0,0xbe75,0,0x3e5a,0,0,0,0xbdde0000,0,0xbe750000,0,0x3e5a0000,
0x3d97,0,0xbd19,0,0x3e69,0,0xbe72,0,0x3d970000,0,0xbd190000,0,0x3e690000,0,0xbe720000,0,
0,0x3d97,0,0xbd19,0,0x3e69,0,0xbe72,0,0x3d970000,0,0xbd190000,0,0x3e690000,0,0xbe720000,
0,0,0x3d19,0,0x3e75,0,0xbe72,0,0,0,0x3d190000,0,0x3e750000,0,0xbe720000,0,
0,0,0,0x3d19,0,0x3e75,0,0xbe72,0,0,0,0x3d190000,0,0x3e750000,0,0xbe720000,
0xbd97,0,0xbdde,0,0xbe69,0,0xbe5a,0,0xbd970000,0,0xbdde0000,0,0xbe690000,0,0xbe5a0000,0,
0,0xbd97,0,0xbdde,0,0xbe69,0,0xbe5a,0,0xbd970000,0,0xbdde0000,0,0xbe690000,0,0xbe5a0000,
0xbe10,0,0xbe2d,0,0xbe46,0,0xbe2d,0,0xbe100000,0,0xbe2d0000,0,0xbe460000,0,0xbe2d0000,0,
0,0xbe10,0,0xbe2d,0,0xbe46,0,0xbe2d,0,0xbe100000,0,0xbe2d0000,0,0xbe460000,0,0xbe2d0000,
0x3e46,0,0x3e72,0,0x3e10,0,0x3d19,0,0x3e460000,0,0x3e720000,0,0x3e100000,0,0x3d190000,0,
0,0x3e46,0,0x3e72,0,0x3e10,0,0x3d19,0,0x3e460000,0,0x3e720000,0,0x3e100000,0,0x3d190000,
0x3e69,0,0x3e2d,0,0xbd97,0,0xbe2d,0,0x3e690000,0,0x3e2d0000,0,0xbd970000,0,0xbe2d0000,0,
0,0x3e69,0,0x3e2d,0,0xbd97,0,0xbe2d,0,0x3e690000,0,0x3e2d0000,0,0xbd970000,0,0xbe2d0000,
0xbe75,0,0xbe2d,0,0x8000,0,0x3e2d,0,0xbe750000,0,0xbe2d0000,0,0x80000000,0,0x3e2d0000,0,
0,0xbe75,0,0xbe2d,0,0x8000,0,0x3e2d,0,0xbe750000,0,0xbe2d0000,0,0x80000000,0,0x3e2d0000,
0,0,0x3e2d,0,0x3e75,0,0x3e2d,0,0,0,0x3e2d0000,0,0x3e750000,0,0x3e2d0000,0,
0,0,0,0x3e2d,0,0x3e75,0,0x3e2d,0,0,0,0x3e2d0000,0,0x3e750000,0,0x3e2d0000,
0x3e46,0,0xbd19,0,0xbe10,0,0xbe72,0,0x3e460000,0,0xbd190000,0,0xbe100000,0,0xbe720000,0,
0,0x3e46,0,0xbd19,0,0xbe10,0,0xbe72,0,0x3e460000,0,0xbd190000,0,0xbe100000,0,0xbe720000,
0xbe69,0,0xbe2d,0,0xbd97,0,0x3e2d,0,0xbe690000,0,0xbe2d0000,0,0xbd970000,0,0x3e2d0000,0,
0,0xbe69,0,0xbe2d,0,0xbd97,0,0x3e2d,0,0xbe690000,0,0xbe2d0000,0,0xbd970000,0,0x3e2d0000,
0xbd97,0,0x3e5a,0,0x3e69,0,0x3dde,0,0xbd970000,0,0x3e5a0000,0,0x3e690000,0,0x3dde0000,0,
0,0xbd97,0,0x3e5a,0,0x3e69,0,0x3dde,0,0xbd970000,0,0x3e5a0000,0,0x3e690000,0,0x3dde0000,
0x3e10,0,0xbe2d,0,0xbe46,0,0xbe2d,0,0x3e100000,0,0xbe2d0000,0,0xbe460000,0,0xbe2d0000,0,
0,0x3e10,0,0xbe2d,0,0xbe46,0,0xbe2d,0,0x3e100000,0,0xbe2d0000,0,0xbe460000,0,0xbe2d0000,
0xbd97,0,0xbe5a,0,0xbe69,0,0x3dde,0,0xbd970000,0,0xbe5a0000,0,0xbe690000,0,0x3dde0000,0,
0,0xbd97,0,0xbe5a,0,0xbe69,0,0x3dde,0,0xbd970000,0,0xbe5a0000,0,0xbe690000,0,0x3dde0000,
0x3e10,0,0x3e2d,0,0x3e46,0,0xbe2d,0,0x3e100000,0,0x3e2d0000,0,0x3e460000,0,0xbe2d0000,0,
0,0x3e10,0,0x3e2d,0,0x3e46,0,0xbe2d,0,0x3e100000,0,0x3e2d0000,0,0x3e460000,0,0xbe2d0000,
0x3e46,0,0x3d19,0,0x3e10,0,0xbe72,0,0x3e460000,0,0x3d190000,0,0x3e100000,0,0xbe720000,0,
0,0x3e46,0,0x3d19,0,0x3e10,0,0xbe72,0,0x3e460000,0,0x3d190000,0,0x3e100000,0,0xbe720000,
0xbe69,0,0x3e2d,0,0x3d97,0,0x3e2d,0,0xbe690000,0,0x3e2d0000,0,0x3d970000,0,0x3e2d0000,0,
0,0xbe69,0,0x3e2d,0,0x3d97,0,0x3e2d,0,0xbe690000,0,0x3e2d0000,0,0x3d970000,0,0x3e2d0000,
0xbe75,0,0x3e2d,0,0x8000,0,0x3e2d,0,0xbe750000,0,0x3e2d0000,0,0x80000000,0,0x3e2d0000,0,
0,0xbe75,0,0x3e2d,0,0x8000,0,0x3e2d,0,0xbe750000,0,0x3e2d0000,0,0x80000000,0,0x3e2d0000,
0,0,0xbe2d,0,0xbe75,0,0x3e2d,0,0,0,0xbe2d0000,0,0xbe750000,0,0x3e2d0000,0,
0,0,0,0xbe2d,0,0xbe75,0,0x3e2d,0,0,0,0xbe2d0000,0,0xbe750000,0,0x3e2d0000,
0x3e46,0,0xbe72,0,0xbe10,0,0x3d19,0,0x3e460000,0,0xbe720000,0,0xbe100000,0,0x3d190000,0,
0,0x3e46,0,0xbe72,0,0xbe10,0,0x3d19,0,0x3e460000,0,0xbe720000,0,0xbe100000,0,0x3d190000,
0x3e69,0,0xbe2d,0,0x3d97,0,0xbe2d,0,0x3e690000,0,0xbe2d0000,0,0x3d970000,0,0xbe2d0000,0,
0,0x3e69,0,0xbe2d,0,0x3d97,0,0xbe2d,0,0x3e690000,0,0xbe2d0000,0,0x3d970000,0,0xbe2d0000,
0xbd97,0,0x3dde,0,0x3e69,0,0xbe5a,0,0xbd970000,0,0x3dde0000,0,0x3e690000,0,0xbe5a0000,0,
0,0xbd97,0,0x3dde,0,0x3e69,0,0xbe5a,0,0xbd970000,0,0x3dde0000,0,0x3e690000,0,0xbe5a0000,
0xbe10,0,0x3e2d,0,0x3e46,0,0xbe2d,0,0xbe100000,0,0x3e2d0000,0,0x3e460000,0,0xbe2d0000,0,
0,0xbe10,0,0x3e2d,0,0x3e46,0,0xbe2d,0,0xbe100000,0,0x3e2d0000,0,0x3e460000,0,0xbe2d0000,
0xbe46,0,0xbe5a,0,0xbe10,0,0xbdde,0,0xbe460000,0,0xbe5a0000,0,0xbe100000,0,0xbdde0000,0,
0,0xbe46,0,0xbe5a,0,0xbe10,0,0xbdde,0,0xbe460000,0,0xbe5a0000,0,0xbe100000,0,0xbdde0000,
0xbe69,0,0xbe72,0,0xbd97,0,0xbd19,0,0xbe690000,0,0xbe720000,0,0xbd970000,0,0xbd190000,0,
0,0xbe69,0,0xbe72,0,0xbd97,0,0xbd19,0,0xbe690000,0,0xbe720000,0,0xbd970000,0,0xbd190000,
0x3d97,0,0xbd19,0,0xbe69,0,0xbe72,0,0x3d970000,0,0xbd190000,0,0xbe690000,0,0xbe720000,0,
0,0x3d97,0,0xbd19,0,0xbe69,0,0xbe72,0,0x3d970000,0,0xbd190000,0,0xbe690000,0,0xbe720000,
0xbe10,0,0xbe5a,0,0xbe46,0,0xbdde,0,0xbe100000,0,0xbe5a0000,0,0xbe460000,0,0xbdde0000,0,
0,0xbe10,0,0xbe5a,0,0xbe46,0,0xbdde,0,0xbe100000,0,0xbe5a0000,0,0xbe460000,0,0xbdde0000,
0x3e75,0,0x3e2d,0,0x8000,0,0xbe2d,0,0x3e750000,0,0x3e2d0000,0,0x80000000,0,0xbe2d0000,0,
0,0x3e75,0,0x3e2d,0,0x8000,0,0xbe2d,0,0x3e750000,0,0x3e2d0000,0,0x80000000,0,0xbe2d0000,
0,0,0xbe2d,0,0xbe75,0,0xbe2d,0,0,0,0xbe2d0000,0,0xbe750000,0,0xbe2d0000,0,
0,0,0,0xbe2d,0,0xbe75,0,0xbe2d,0,0,0,0xbe2d0000,0,0xbe750000,0,0xbe2d0000,
0x3d97,0,0x3e72,0,0x3e69,0,0x3d19,0,0x3d970000,0,0x3e720000,0,0x3e690000,0,0x3d190000,0,
0,0x3d97,0,0x3e72,0,0x3e69,0,0x3d19,0,0x3d970000,0,0x3e720000,0,0x3e690000,0,0x3d190000,
0x3e10,0,0xbdde,0,0xbe46,0,0xbe5a,0,0x3e100000,0,0xbdde0000,0,0xbe460000,0,0xbe5a0000,0,
0,0x3e10,0,0xbdde,0,0xbe46,0,0xbe5a,0,0x3e100000,0,0xbdde0000,0,0xbe460000,0,0xbe5a0000,
0xbe46,0,0x3dde,0,0x3e10,0,0x3e5a,0,0xbe460000,0,0x3dde0000,0,0x3e100000,0,0x3e5a0000,0,
0,0xbe46,0,0x3dde,0,0x3e10,0,0x3e5a,0,0xbe460000,0,0x3dde0000,0,0x3e100000,0,0x3e5a0000,
0x3e69,0,0xbd19,0,0xbd97,0,0xbe72,0,0x3e690000,0,0xbd190000,0,0xbd970000,0,0xbe720000,0,
0,0x3e69,0,0xbd19,0,0xbd97,0,0xbe72,0,0x3e690000,0,0xbd190000,0,0xbd970000,0,0xbe720000,
0xbe46,0,0xbdde,0,0xbe10,0,0x3e5a,0,0xbe460000,0,0xbdde0000,0,0xbe100000,0,0x3e5a0000,0,
0,0xbe46,0,0xbdde,0,0xbe10,0,0x3e5a,0,0xbe460000,0,0xbdde0000,0,0xbe100000,0,0x3e5a0000,
0x3e69,0,0x3d19,0,0x3d97,0,0xbe72,0,0x3e690000,0,0x3d190000,0,0x3d970000,0,0xbe720000,0,
0,0x3e69,0,0x3d19,0,0x3d97,0,0xbe72,0,0x3e690000,0,0x3d190000,0,0x3d970000,0,0xbe720000,
0x3d97,0,0xbe72,0,0xbe69,0,0x3d19,0,0x3d970000,0,0xbe720000,0,0xbe690000,0,0x3d190000,0,
0,0x3d97,0,0xbe72,0,0xbe69,0,0x3d19,0,0x3d970000,0,0xbe720000,0,0xbe690000,0,0x3d190000,
0x3e10,0,0x3dde,0,0x3e46,0,0xbe5a,0,0x3e100000,0,0x3dde0000,0,0x3e460000,0,0xbe5a0000,0,
0,0x3e10,0,0x3dde,0,0x3e46,0,0xbe5a,0,0x3e100000,0,0x3dde0000,0,0x3e460000,0,0xbe5a0000,
0x3e75,0,0xbe2d,0,0x8000,0,0xbe2d,0,0x3e750000,0,0xbe2d0000,0,0x80000000,0,0xbe2d0000,0,
0,0x3e75,0,0xbe2d,0,0x8000,0,0xbe2d,0,0x3e750000,0,0xbe2d0000,0,0x80000000,0,0xbe2d0000,
0,0,0x3e2d,0,0x3e75,0,0xbe2d,0,0,0,0x3e2d0000,0,0x3e750000,0,0xbe2d0000,0,
0,0,0,0x3e2d,0,0x3e75,0,0xbe2d,0,0,0,0x3e2d0000,0,0x3e750000,0,0xbe2d0000,
0x3d97,0,0x3d19,0,0x3e69,0,0xbe72,0,0x3d970000,0,0x3d190000,0,0x3e690000,0,0xbe720000,0,
0,0x3d97,0,0x3d19,0,0x3e69,0,0xbe72,0,0x3d970000,0,0x3d190000,0,0x3e690000,0,0xbe720000,
0xbe10,0,0x3e5a,0,0x3e46,0,0xbdde,0,0xbe100000,0,0x3e5a0000,0,0x3e460000,0,0xbdde0000,0,
0,0xbe10,0,0x3e5a,0,0x3e46,0,0xbdde,0,0xbe100000,0,0x3e5a0000,0,0x3e460000,0,0xbdde0000,
0xbe46,0,0x3e5a,0,0x3e10,0,0xbdde,0,0xbe460000,0,0x3e5a0000,0,0x3e100000,0,0xbdde0000,0,
0,0xbe46,0,0x3e5a,0,0x3e10,0,0xbdde,0,0xbe460000,0,0x3e5a0000,0,0x3e100000,0,0xbdde0000,
0xbe69,0,0x3e72,0,0x3d97,0,0xbd19,0,0xbe690000,0,0x3e720000,0,0x3d970000,0,0xbd190000,0,
0,0xbe69,0,0x3e72,0,0x3d97,0,0xbd19,0,0xbe690000,0,0x3e720000,0,0x3d970000,0,0xbd190000,
0x3eb7,0x3eb7,0x3eb7,0x3eb7,0x3eb78000,0x3eb78000,0x3eb78000,0x3eb78000,0x3eb7,0x3de23eae,0x3e573e94,0x3e943e57,0x3eb78000,0x3eaebde2,0x3e94be57,0x3e57be94,
0x3eb7,0x3e573e94,0x3eae3de2,0x3eaebde2,0x3eb78000,0x3e94be57,0x3de2beae,0xbde2beae,0x3eb7,0x3e943e57,0x3eaebde2,0x3de2beae,0x3eb78000,0x3e57be94,0xbde2beae,0xbeaebde2,
0x3eb7,0x3eb7,0x3eb7,0x3eb7,0x3eb78000,0x3eb78000,0x3eb78000,0x3eb78000,0x3eae3de2,0x3eb70000,0x3eaebde2,0x3e94be57,0x3de2beae,0xbeb7,0xbde2beae,0xbe57be94,
0x3e57be94,0xbeb7,0xbe57be94,0xbeaebde2,0xbe94be57,0xbeb78000,0xbe943e57,0xbde23eae,0xbe57be94,0xbeb70000,0xbe573e94,0x3de23eae,0xbe943e57,0x3eb7,0x3e943e57,0x3eaebde2,
0x3eb7,0x3eae3de2,0x3e57be94,0xbe57be94,0x3eb78000,0x3de2beae,0xbe94be57,0xbe943e57,0x3eb7,0x3eb70000,0xbeb7,0xbeb70000,0x3eb78000,0xbeb7,0xbeb78000,0x3eb7,
0x3eb7,0x3eaebde2,0xbe57be94,0xbe573e94,0x3eb78000,0xbde2beae,0xbe943e57,0x3e943e57,0x3eb7,0x3e94be57,0xbeaebde2,0x3de23eae,0x3eb78000,0xbe57be94,0xbde23eae,0x3eaebde2,
0xbeae3de2,0x3eb7,0x3eae3de2,0x3e57be94,0x3de23eae,0x3eb78000,0x3de2beae,0xbe94be57,0x3eb7,0x3eb70000,0xbeb7,0xbeb70000,0x3eb78000,0xbeb7,0xbeb78000,0x3eb7,
0x3eae3de2,0xbeb7,0xbeae3de2,0x3e573e94,0x3de2beae,0xbeb78000,0x3de23eae,0x3e94be57,0x3e57be94,0xbeb70000,0x3e573e94,0x3de2beae,0xbe94be57,0x3eb7,0x3e94be57,0xbeaebde2,
0x3eb7,0x3e57be94,0xbeae3de2,0x3eae3de2,0x3eb78000,0xbe94be57,0x3de23eae,0x3de2beae,0x3eb7,0x3de2beae,0xbe573e94,0x3e94be57,0x3eb78000,0xbeaebde2,0x3e943e57,0xbe57be94,
0x3eb7,0xbeb7,0x3eb7,0xbeb7,0x3eb78000,0xbeb78000,0x3eb78000,0xbeb78000,0x3eb7,0xbde2beae,0x3e573e94,0xbe94be57,0x3eb78000,0xbeae3de2,0x3e94be57,0xbe573e94,
0xbe57be94,0x3eb7,0x3e57be94,0xbeae3de2,0xbe943e57,0x3eb78000,0xbe94be57,0x3de23eae,0xbeae3de2,0x3eb70000,0xbeaebde2,0x3e943e57,0x3de23eae,0xbeb7,0xbde23eae,0x3e57be94,
0x3eb7,0xbeb7,0x3eb7,0xbeb7,0x3eb78000,0xbeb78000,0x3eb78000,0xbeb78000,0x3eae3de2,0xbeb70000,0x3eaebde2,0xbe943e57,0x3de2beae,0x3eb7,0xbde2beae,0x3e573e94,
0x3eb7,0xbe57be94,0x3eae3de2,0xbeae3de2,0x3eb78000,0xbe943e57,0x3de2beae,0x3de23eae,0x3eb7,0xbe94be57,0x3eaebde2,0xbde23eae,0x3eb78000,0xbe573e94,0xbde2beae,0x3eae3de2,
0x3eb7,0xbeaebde2,0x3e57be94,0x3e573e94,0x3eb78000,0xbde23eae,0xbe94be57,0x3e94be57,0x3eb7,0xbeb70000,0xbeb7,0x3eb70000,0x3eb78000,0x3eb7,0xbeb78000,0xbeb7,
0x3e57be94,0x3eb7,0xbe57be94,0x3eae3de2,0xbe94be57,0x3eb78000,0xbe943e57,0x3de2beae,0xbe57be94,0x3eb70000,0xbe573e94,0xbde2beae,0xbe943e57,0xbeb7,0x3e943e57,0xbeae3de2,
0xbeae3de2,0xbeb7,0x3eae3de2,0xbe573e94,0x3de23eae,0xbeb78000,0x3de2beae,0x3e943e57,0x3eb7,0xbeb70000,0xbeb7,0x3eb70000,0x3eb78000,0x3eb7,0xbeb78000,0xbeb7,
0x3eb7,0xbeae3de2,0xbe57be94,0x3e57be94,0x3eb78000,0x3de23eae,0xbe943e57,0xbe94be57,0x3eb7,0xbe943e57,0xbeaebde2,0xbde2beae,0x3eb78000,0x3e573e94,0xbde23eae,0xbeae3de2,
0x3eb7,0xbe573e94,0xbeae3de2,0xbeaebde2,0x3eb78000,0x3e943e57,0x3de23eae,0xbde23eae,0x3eb7,0xbde23eae,0xbe573e94,0xbe943e57,0x3eb78000,0x3eae3de2,0x3e943e57,0x3e573e94,
0x3eae3de2,0x3eb7,0xbeae3de2,0xbe57be94,0x3de2beae,0x3eb78000,0x3de23eae,0xbe943e57,0x3e57be94,0x3eb70000,0x3e573e94,0xbde23eae,0xbe94be57,0xbeb7,0x3e94be57,0x3eae3de2,
0xbe57be94,0xbeb7,0x3e57be94,0x3eaebde2,0xbe943e57,0xbeb78000,0xbe94be57,0xbde2beae,0xbeae3de2,0xbeb70000,0xbeaebde2,0xbe94be57,0x3de23eae,0x3eb7,0xbde23eae,0xbe573e94,
0x3eb7,0x3eb7,0x3eb7,0x3eb7,0x3eb78000,0x3eb78000,0x3eb78000,0x3eb78000,0x3e57be94,0x3de2beae,0xbeb7,0xbde2beae,0xbe94be57,0xbeaebde2,0xbeb78000,0xbeae3de2,
0xbeae3de2,0xbe573e94,0x3eb7,0x3e573e94,0x3de23eae,0x3e943e57,0x3eb78000,0x3e94be57,0x3eae3de2,0x3e94be57,0xbeb7,0xbe94be57,0x3de2beae,0xbe57be94,0xbeb78000,0xbe573e94,
0x3eb7,0x3eb7,0x3eb7,0x3eb7,0x3eb78000,0x3eb78000,0x3eb78000,0x3eb78000,0xbe57be94,0xbe94be57,0xbeaebde2,0xbeb70000,0xbe943e57,0xbe573e94,0xbde23eae,0x3eb7,
0x3eae3de2,0x3eaebde2,0x3e57be94,0xbeb7,0x3de2beae,0xbde2beae,0xbe94be57,0xbeb78000,0xbeae3de2,0xbde23eae,0x3e573e94,0x3eb70000,0x3de23eae,0x3eae3de2,0x3e94be57,0xbeb7,
0xbe57be94,0xbeae3de2,0x3eb7,0x3eae3de2,0xbe943e57,0x3de23eae,0x3eb78000,0x3de2beae,0x3eb7,0x3eb70000,0xbeb7,0xbeb70000,0x3eb78000,0xbeb7,0xbeb78000,0x3eb7,
0x3e57be94,0xbeaebde2,0x3eb7,0x3eaebde2,0xbe94be57,0xbde23eae,0x3eb78000,0xbde2beae,0xbeae3de2,0x3e943e57,0xbeb7,0xbe943e57,0x3de23eae,0x3e57be94,0xbeb78000,0x3e573e94,
0x3e57be94,0xbe57be94,0xbeae3de2,0x3eb7,0xbe94be57,0xbe943e57,0x3de23eae,0x3eb78000,0x3eb7,0x3eb70000,0xbeb7,0xbeb70000,0x3eb78000,0xbeb7,0xbeb78000,0x3eb7,
0xbe57be94,0xbe573e94,0x3eae3de2,0xbeb7,0xbe943e57,0x3e943e57,0x3de2beae,0xbeb78000,0x3eae3de2,0xbde2beae,0xbe573e94,0x3eb70000,0x3de2beae,0xbeae3de2,0x3e943e57,0xbeb7,
0x3eae3de2,0xbe57be94,0x3eb7,0x3e57be94,0x3de2beae,0xbe943e57,0x3eb78000,0xbe94be57,0xbe57be94,0x3de23eae,0xbeb7,0xbde23eae,0xbe943e57,0x3eaebde2,0xbeb78000,0x3eae3de2,
0x3eb7,0xbeb7,0x3eb7,0xbeb7,0x3eb78000,0xbeb78000,0x3eb78000,0xbeb78000,0x3e57be94,0xbde23eae,0xbeb7,0x3de23eae,0xbe94be57,0x3eae3de2,0xbeb78000,0x3eaebde2,
0xbeae3de2,0x3eae3de2,0xbe57be94,0x3eb7,0x3de23eae,0x3de2beae,0xbe943e57,0x3eb78000,0x3e57be94,0xbe943e57,0x3eaebde2,0xbeb70000,0xbe94be57,0x3e573e94,0xbde2beae,0x3eb7,
0x3eb7,0xbeb7,0x3eb7,0xbeb7,0x3eb78000,0xbeb78000,0x3eb78000,0xbeb78000,0xbe57be94,0x3e943e57,0xbeaebde2,0x3eb70000,0xbe943e57,0x3e57be94,0xbde23eae,0xbeb7,
0xbeae3de2,0x3e57be94,0x3eb7,0xbe57be94,0x3de23eae,0xbe94be57,0x3eb78000,0xbe943e57,0x3eae3de2,0xbe943e57,0xbeb7,0x3e943e57,0x3de2beae,0x3e573e94,0xbeb78000,0x3e57be94,
0xbe57be94,0x3eaebde2,0x3eb7,0xbeaebde2,0xbe943e57,0xbde2beae,0x3eb78000,0xbde23eae,0x3eb7,0xbeb70000,0xbeb7,0x3eb70000,0x3eb78000,0x3eb7,0xbeb78000,0xbeb7,
0x3eae3de2,0xbeae3de2,0x3e57be94,0x3eb7,0x3de2beae,0x3de23eae,0xbe94be57,0x3eb78000,0xbeae3de2,0x3de2beae,0x3e573e94,0xbeb70000,0x3de23eae,0xbeaebde2,0x3e94be57,0x3eb7,
0x3e57be94,0x3e573e94,0xbeae3de2,0xbeb7,0xbe94be57,0x3e94be57,0x3de23eae,0xbeb78000,0x3eb7,0xbeb70000,0xbeb7,0x3eb70000,0x3eb78000,0x3eb7,0xbeb78000,0xbeb7,
0x3e57be94,0x3eae3de2,0x3eb7,0xbeae3de2,0xbe94be57,0x3de2beae,0x3eb78000,0x3de23eae,0xbeae3de2,0xbe94be57,0xbeb7,0x3e94be57,0x3de23eae,0xbe573e94,0xbeb78000,0xbe57be94,
0x3eae3de2,0x3e573e94,0x3eb7,0xbe573e94,0x3de2beae,0x3e94be57,0x3eb78000,0x3e943e57,0xbe57be94,0xbde2beae,0xbeb7,0x3de2beae,0xbe943e57,0xbeae3de2,0xbeb78000,0xbeaebde2,
0xbe57be94,0x3e57be94,0x3eae3de2,0x3eb7,0xbe943e57,0xbe94be57,0x3de2beae,0x3eb78000,0x3eae3de2,0x3de23eae,0xbe573e94,0xbeb70000,0x3de2beae,0x3eaebde2,0x3e943e57,0x3eb7,
0xbeae3de2,0xbeaebde2,0xbe57be94,0xbeb7,0x3de23eae,0xbde23eae,0xbe943e57,0xbeb78000,0x3e57be94,0x3e94be57,0x3eaebde2,0x3eb70000,0xbe94be57,0xbe57be94,0xbde2beae,0xbeb7,
0x3eb7,0x3eb7,0x3eb7,0x3eb7,0x3eb78000,0x3eb78000,0x3eb78000,0x3eb78000,0xbeae3de2,0xbe943e57,0xbe573e94,0xbde23eae,0x3de23eae,0x3e573e94,0x3e943e57,0x3eae3de2,
0xbe57be94,0xbeaebde2,0xbeae3de2,0xbe573e94,0xbe943e57,0xbde23eae,0x3de23eae,0x3e943e57,0x3e57be94,0xbde2beae,0xbeaebde2,0xbe943e57,0xbe94be57,0xbeae3de2,0xbde23eae,0x3e573e94,
0,0,0,0,0,0,0,0,0,0,0,0,0,0,0,0,
0,0,0,0,0,0,0,0,0,0,0,0,0,0,0,0,
0x3eae3de2,0x3e57be94,0xbe57be94,0xbeae3de2,0x3de2beae,0xbe94be57,0xbe943e57,0x3de23eae,0x3eb7,0x3eb70000,0xbeb7,0xbeb70000,0x3eb78000,0xbeb7,0xbeb78000,0x3eb7,
0xbeae3de2,0x3e573e94,0x3e57be94,0xbeaebde2,0x3de23eae,0x3e94be57,0xbe94be57,0xbde23eae,0xbe57be94,0xbde23eae,0x3eaebde2,0xbe94be57,0xbe943e57,0x3eae3de2,0xbde2beae,0xbe573e94,
0,0,0,0,0,0,0,0,0,0,0,0,0,0,0,0,
0,0,0,0,0,0,0,0,0,0,0,0,0,0,0,0,
0x3e57be94,0xbeae3de2,0x3eae3de2,0xbe57be94,0xbe94be57,0x3de23eae,0x3de2beae,0xbe943e57,0x3eae3de2,0xbe94be57,0x3e573e94,0xbde2beae,0x3de2beae,0xbe573e94,0x3e94be57,0xbeae3de2,
0x3eb7,0xbeb7,0x3eb7,0xbeb7,0x3eb78000,0xbeb78000,0x3eb78000,0xbeb78000,0xbeae3de2,0x3e94be57,0xbe573e94,0x3de2beae,0x3de23eae,0xbe57be94,0x3e943e57,0xbeaebde2,
0,0,0,0,0,0,0,0,0,0,0,0,0,0,0,0,
0,0,0,0,0,0,0,0,0,0,0,0,0,0,0,0,
0xbe57be94,0x3eae3de2,0xbeae3de2,0x3e57be94,0xbe943e57,0x3de2beae,0x3de23eae,0xbe94be57,0x3e57be94,0x3de23eae,0xbeaebde2,0x3e94be57,0xbe94be57,0x3eaebde2,0xbde23eae,0xbe57be94,
0x3eae3de2,0xbe573e94,0xbe57be94,0x3eaebde2,0x3de2beae,0x3e943e57,0xbe943e57,0xbde2beae,0x3eb7,0xbeb70000,0xbeb7,0x3eb70000,0x3eb78000,0x3eb7,0xbeb78000,0xbeb7,
0,0,0,0,0,0,0,0,0,0,0,0,0,0,0,0,
0,0,0,0,0,0,0,0,0,0,0,0,0,0,0,0,
0xbeae3de2,0xbe57be94,0x3e57be94,0x3eae3de2,0x3de23eae,0xbe943e57,0xbe94be57,0x3de2beae,0xbe57be94,0x3de2beae,0x3eaebde2,0x3e943e57,0xbe943e57,0xbeaebde2,0xbde2beae,0x3e57be94,
0x3e57be94,0x3eaebde2,0x3eae3de2,0x3e573e94,0xbe94be57,0xbde2beae,0x3de2beae,0x3e94be57,0x3eae3de2,0x3e943e57,0x3e573e94,0x3de23eae,0x3de2beae,0x3e57be94,0x3e94be57,0x3eaebde2,
0,0,0,0,0,0,0,0,0,0,0,0,0,0,0,0,
0,0,0,0,0,0,0,0,0,0,0,0,0,0,0,0,
0,0,0,0,0,0,0,0,0,0,0,0,0,0,0,0,
0,0,0,0,0,0,0,0,0,0,0,0,0,0,0,0,
0x3eb7,0x3eb7,0x3eb7,0x3eb7,0x3eb78000,0x3eb78000,0x3eb78000,0x3eb78000,0xbeae3de2,0xbe943e57,0xbe573e94,0xbde23eae,0x3de23eae,0x3e573e94,0x3e943e57,0x3eae3de2,
0xbe57be94,0xbeaebde2,0xbeae3de2,0xbe573e94,0xbe943e57,0xbde23eae,0x3de23eae,0x3e943e57,0x3e57be94,0xbde2beae,0xbeaebde2,0xbe943e57,0xbe94be57,0xbeae3de2,0xbde23eae,0x3e573e94,
0,0,0,0,0,0,0,0,0,0,0,0,0,0,0,0,
0,0,0,0,0,0,0,0,0,0,0,0,0,0,0,0,
0x3eae3de2,0x3e57be94,0xbe57be94,0xbeae3de2,0x3de2beae,0xbe94be57,0xbe943e57,0x3de23eae,0x3eb7,0x3eb70000,0xbeb7,0xbeb70000,0x3eb78000,0xbeb7,0xbeb78000,0x3eb7,
0xbeae3de2,0x3e573e94,0x3e57be94,0xbeaebde2,0x3de23eae,0x3e94be57,0xbe94be57,0xbde23eae,0xbe57be94,0xbde23eae,0x3eaebde2,0xbe94be57,0xbe943e57,0x3eae3de2,0xbde2beae,0xbe573e94,
0,0,0,0,0,0,0,0,0,0,0,0,0,0,0,0,
0,0,0,0,0,0,0,0,0,0,0,0,0,0,0,0,
0x3e57be94,0xbeae3de2,0x3eae3de2,0xbe57be94,0xbe94be57,0x3de23eae,0x3de2beae,0xbe943e57,0x3eae3de2,0xbe94be57,0x3e573e94,0xbde2beae,0x3de2beae,0xbe573e94,0x3e94be57,0xbeae3de2,
0x3eb7,0xbeb7,0x3eb7,0xbeb7,0x3eb78000,0xbeb78000,0x3eb78000,0xbeb78000,0xbeae3de2,0x3e94be57,0xbe573e94,0x3de2beae,0x3de23eae,0xbe57be94,0x3e943e57,0xbeaebde2,
0,0,0,0,0,0,0,0,0,0,0,0,0,0,0,0,
0,0,0,0,0,0,0,0,0,0,0,0,0,0,0,0,
0xbe57be94,0x3eae3de2,0xbeae3de2,0x3e57be94,0xbe943e57,0x3de2beae,0x3de23eae,0xbe94be57,0x3e57be94,0x3de23eae,0xbeaebde2,0x3e94be57,0xbe94be57,0x3eaebde2,0xbde23eae,0xbe57be94,
0x3eae3de2,0xbe573e94,0xbe57be94,0x3eaebde2,0x3de2beae,0x3e943e57,0xbe943e57,0xbde2beae,0x3eb7,0xbeb70000,0xbeb7,0x3eb70000,0x3eb78000,0x3eb7,0xbeb78000,0xbeb7,
0,0,0,0,0,0,0,0,0,0,0,0,0,0,0,0,
0,0,0,0,0,0,0,0,0,0,0,0,0,0,0,0,
0xbeae3de2,0xbe57be94,0x3e57be94,0x3eae3de2,0x3de23eae,0xbe943e57,0xbe94be57,0x3de2beae,0xbe57be94,0x3de2beae,0x3eaebde2,0x3e943e57,0xbe943e57,0xbeaebde2,0xbde2beae,0x3e57be94,
0x3e57be94,0x3eaebde2,0x3eae3de2,0x3e573e94,0xbe94be57,0xbde2beae,0x3de2beae,0x3e94be57,0x3eae3de2,0x3e943e57,0x3e573e94,0x3de23eae,0x3de2beae,0x3e57be94,0x3e94be57,0x3eaebde2,
};
__device__ __align__(128) const uint32_t TAB_P3[4288] = {
0,0,0,0,0,0,0,0,0,0,0,0,0,0,0,0,
0x80003e83,0xbe79bda2,0x3e1abe54,0x3e1a3e54,0x3e830000,0xbda23e79,0xbe54be1a,0x3e54be1a,0x80003e83,0xbe54be1a,0x3e79bda2,0xbda23e79,0x3e830000,0xbe1a3e54,0xbda2be79,0x3e793da2,
0,0,0,0,0,0,0,0,0,0,0,0,0,0,0,0,
0xbe793da2,0x8000be83,0x3e793da2,0xbe1a3e54,0x3da23e79,0xbe830000,0x3da2be79,0x3e543e1a,0xbe1abe54,0x3e830000,0xbe1a3e54,0xbda2be79,0xbe543e1a,0xbe83,0x3e543e1a,0xbe793da2,
0x80003e83,0xbe1abe54,0x3e793da2,0xbe793da2,0x3e830000,0xbe543e1a,0x3da2be79,0x3da23e79,0x80003e83,0xbda2be79,0x3e1a3e54,0xbe54be1a,0x3e830000,0xbe793da2,0x3e54be1a,0xbe1a3e54,
0x80003e83,0x8000be83,0x80003e83,0x8000be83,0x3e830000,0xbe830000,0x3e830000,0xbe830000,0x80003e83,0x3da2be79,0xbe1a3e54,0x3e54be1a,0x3e830000,0xbe79bda2,0x3e543e1a,0xbe1abe54,
0x3e1abe54,0x80003e83,0xbe1abe54,0x3e793da2,0xbe54be1a,0x3e830000,0xbe543e1a,0x3da2be79,0x3e793da2,0xbe830000,0x3e79bda2,0xbe543e1a,0x3da2be79,0x3e83,0xbda2be79,0x3e1a3e54,
0x80003e83,0x8000be83,0x80003e83,0x8000be83,0x3e830000,0xbe830000,0x3e830000,0xbe830000,0xbe793da2,0x3e830000,0xbe79bda2,0x3e543e1a,0x3da23e79,0xbe83,0xbda23e79,0x3e1abe54,
0x80003e83,0x3e1abe54,0xbe793da2,0x3e793da2,0x3e830000,0xbe54be1a,0x3da23e79,0x3da2be79,0x80003e83,0x3e54be1a,0xbe79bda2,0x3da23e79,0x3e830000,0xbe1abe54,0xbda23e79,0x3e79bda2,
0x80003e83,0x3e79bda2,0xbe1abe54,0xbe1a3e54,0x3e830000,0xbda2be79,0xbe543e1a,0x3e543e1a,0x80003e83,0x3e830000,0x8000be83,0xbe830000,0x3e830000,0xbe83,0xbe830000,0x3e83,
0xbe1abe54,0x80003e83,0x3e1abe54,0xbe793da2,0xbe543e1a,0x3e830000,0xbe54be1a,0x3da23e79,0x3e1abe54,0xbe830000,0x3e1a3e54,0x3da2be79,0xbe54be1a,0x3e83,0x3e54be1a,0xbe79bda2,
0x3e793da2,0x8000be83,0xbe793da2,0x3e1a3e54,0x3da2be79,0xbe830000,0x3da23e79,0x3e54be1a,0x80003e83,0x3e830000,0x8000be83,0xbe830000,0x3e830000,0xbe83,0xbe830000,0x3e83,
0x80003e83,0x3e793da2,0x3e1abe54,0xbe1abe54,0x3e830000,0x3da2be79,0xbe54be1a,0xbe543e1a,0x80003e83,0x3e543e1a,0x3e79bda2,0x3da2be79,0x3e830000,0x3e1abe54,0xbda2be79,0xbe79bda2,
0x80003e83,0x3e1a3e54,0x3e793da2,0x3e79bda2,0x3e830000,0x3e54be1a,0x3da2be79,0xbda2be79,0x80003e83,0x3da23e79,0x3e1a3e54,0x3e543e1a,0x3e830000,0x3e79bda2,0x3e54be1a,0x3e1abe54,
0xbe793da2,0x80003e83,0x3e793da2,0x3e1abe54,0x3da23e79,0x3e830000,0x3da2be79,0xbe54be1a,0xbe1abe54,0xbe830000,0xbe1a3e54,0x3da23e79,0xbe543e1a,0x3e83,0x3e543e1a,0x3e79bda2,
0x3e1abe54,0x8000be83,0xbe1abe54,0xbe79bda2,0xbe54be1a,0xbe830000,0xbe543e1a,0xbda23e79,0x3e793da2,0x3e830000,0x3e79bda2,0x3e54be1a,0x3da2be79,0xbe83,0xbda2be79,0xbe1abe54,
0,0,0,0,0,0,0,0,0,0,0,0,0,0,0,0,
0,0,0,0,0,0,0,0,0,0,0,0,0,0,0,0,
0,0,0,0,0,0,0,0,0,0,0,0,0,0,0,0,
0xbe1abe54,0x3e79bda2,0x80003e83,0xbe79bda2,0xbe543e1a,0xbda2be79,0x3e830000,0xbda23e79,0x3e793da2,0xbe543e1a,0x8000be83,0x3e543e1a,0x3da2be79,0x3e1a3e54,0xbe830000,0x3e1abe54,
0,0,0,0,0,0,0,0,0,0,0,0,0,0,0,0,
0,0,0,0,0,0,0,0,0,0,0,0,0,0,0,0,
0xbe793da2,0x3e1abe54,0x80003e83,0xbe1abe54,0x3da23e79,0xbe54be1a,0x3e830000,0xbe543e1a,0x3e1abe54,0xbda23e79,0x8000be83,0x3da23e79,0xbe54be1a,0x3e793da2,0xbe830000,0x3e79bda2,
0x80003e83,0x8000be83,0x80003e83,0x8000be83,0x3e830000,0xbe830000,0x3e830000,0xbe830000,0xbe1abe54,0x3da23e79,0x8000be83,0xbda23e79,0xbe543e1a,0x3e79bda2,0xbe830000,0x3e793da2,
0,0,0,0,0,0,0,0,0,0,0,0,0,0,0,0,
0,0,0,0,0,0,0,0,0,0,0,0,0,0,0,0,
0x3e793da2,0xbe1abe54,0x80003e83,0x3e1abe54,0x3da2be79,0xbe543e1a,0x3e830000,0xbe54be1a,0xbe793da2,0x3e543e1a,0x8000be83,0xbe543e1a,0x3da23e79,0x3e1abe54,0xbe830000,0x3e1a3e54,
0x3e1abe54,0xbe79bda2,0x80003e83,0x3e79bda2,0xbe54be1a,0xbda23e79,0x3e830000,0xbda2be79,0x80003e83,0x3e830000,0x8000be83,0xbe830000,0x3e830000,0xbe83,0xbe830000,0x3e83,
0,0,0,0,0,0,0,0,0,0,0,0,0,0,0,0,
0,0,0,0,0,0,0,0,0,0,0,0,0,0,0,0,
0xbe1abe54,0xbe793da2,0x80003e83,0x3e793da2,0xbe543e1a,0x3da23e79,0x3e830000,0x3da2be79,0x3e793da2,0x3e54be1a,0x8000be83,0xbe54be1a,0x3da2be79,0xbe1abe54,0xbe830000,0xbe1a3e54,
0xbe793da2,0xbe1a3e54,0x80003e83,0x3e1a3e54,0x3da23e79,0x3e543e1a,0x3e830000,0x3e54be1a,0x3e1abe54,0x3da2be79,0x8000be83,0xbda2be79,0xbe54be1a,0xbe79bda2,0xbe830000,0xbe793da2,
0,0,0,0,0,0,0,0,0,0,0,0,0,0,0,0,
0x3e1abe54,0x3e1a3e54,0xbe793da2,0x8000be83,0xbe54be1a,0x3e54be1a,0x3da23e79,0xbe830000,0xbe793da2,0x3da2be79,0x3e1a3e54,0xbe830000,0x3da23e79,0xbe79bda2,0x3e54be1a,0x3e83,
0,0,0,0,0,0,0,0,0,0,0,0,0,0,0,0,
0x3e793da2,0xbe1a3e54,0xbe1abe54,0x3e79bda2,0x3da2be79,0x3e543e1a,0xbe543e1a,0xbda2be79,0x3e1abe54,0x3da23e79,0xbe79bda2,0x3e54be1a,0xbe54be1a,0x3e79bda2,0xbda23e79,0xbe1abe54,
0x3e793da2,0xbe793da2,0x3e1abe54,0x80003e83,0x3da2be79,0x3da23e79,0xbe54be1a,0x3e830000,0xbe1abe54,0x3e543e1a,0xbe79bda2,0x3e830000,0xbe543e1a,0x3e1abe54,0xbda23e79,0xbe83,
0x80003e83,0x8000be83,0x80003e83,0x8000be83,0x3e830000,0xbe830000,0x3e830000,0xbe830000,0x3e1abe54,0xbe543e1a,0x3e79bda2,0xbe830000,0xbe54be1a,0x3e1a3e54,0xbda2be79,0x3e83,
0xbe1abe54,0x3e793da2,0xbe793da2,0x3e1abe54,0xbe543e1a,0x3da2be79,0x3da23e79,0xbe54be1a,0xbe793da2,0x3e54be1a,0xbe1a3e54,0x3da2be79,0x3da23e79,0xbe1abe54,0x3e543e1a,0xbe79bda2,
0x80003e83,0x8000be83,0x80003e83,0x8000be83,0x3e830000,0xbe830000,0x3e830000,0xbe830000,0x3e793da2,0xbe54be1a,0x3e1a3e54,0xbda2be79,0x3da2be79,0xbe1a3e54,0x3e54be1a,0xbe793da2,
0xbe793da2,0x3e793da2,0xbe1abe54,0x80003e83,0x3da23e79,0x3da2be79,0xbe543e1a,0x3e830000,0x3e793da2,0xbda2be79,0xbe1a3e54,0x3e830000,0x3da2be79,0xbe793da2,0x3e543e1a,0xbe83,
0xbe1abe54,0xbe1a3e54,0x3e793da2,0x8000be83,0xbe543e1a,0x3e543e1a,0x3da2be79,0xbe830000,0x80003e83,0x3e830000,0x8000be83,0xbe830000,0x3e830000,0xbe83,0xbe830000,0x3e83,
0x3e1abe54,0xbe793da2,0x3e793da2,0xbe1abe54,0xbe54be1a,0x3da23e79,0x3da2be79,0xbe543e1a,0xbe1abe54,0xbda23e79,0x3e79bda2,0xbe54be1a,0xbe543e1a,0x3e793da2,0xbda2be79,0xbe1a3e54,
0xbe793da2,0x3e1a3e54,0x3e1abe54,0xbe79bda2,0x3da23e79,0x3e54be1a,0xbe54be1a,0xbda23e79,0x80003e83,0x3e830000,0x8000be83,0xbe830000,0x3e830000,0xbe83,0xbe830000,0x3e83,
0x3e1abe54,0xbe1abe54,0xbe793da2,0x80003e83,0xbe54be1a,0xbe543e1a,0x3da23e79,0x3e830000,0xbe793da2,0xbda23e79,0x3e1a3e54,0x3e830000,0x3da23e79,0x3e793da2,0x3e54be1a,0xbe83,
0x3e793da2,0x3e79bda2,0x3e1abe54,0x8000be83,0x3da2be79,0xbda2be79,0xbe54be1a,0xbe830000,0xbe1abe54,0xbe54be1a,0xbe79bda2,0xbe830000,0xbe543e1a,0xbe1a3e54,0xbda23e79,0x3e83,
0x3e793da2,0x3e1abe54,0xbe1abe54,0xbe793da2,0x3da2be79,0xbe54be1a,0xbe543e1a,0x3da23e79,0x3e1abe54,0xbda2be79,0xbe79bda2,0xbe543e1a,0xbe54be1a,0xbe793da2,0xbda23e79,0x3e1a3e54,
0xbe1abe54,0xbe79bda2,0xbe793da2,0xbe1a3e54,0xbe543e1a,0xbda23e79,0x3da23e79,0x3e543e1a,0xbe793da2,0xbe543e1a,0xbe1a3e54,0xbda23e79,0x3da23e79,0x3e1a3e54,0x3e543e1a,0x3e793da2,
0xbe163dda,0,0,0,0,0xbe163dda,0,0,0,0,0xbe163dda,0,0,0,0,0xbe163dda,
0xbe253da8,0,0,0,0,0xbe253da8,0,0,0,0,0xbe253da8,0,0,0,0,0xbe253da8,
0xbd65be30,0,0,0,0,0xbd65be30,0,0,0,0,0xbd65be30,0,0,0,0,0xbd65be30,
0x3ce8be37,0,0,0,0,0x3ce8be37,0,0,0,0,0x3ce8be37,0,0,0,0,0x3ce8be37,
0xbe303d65,0,0,0,0,0xbe303d65,0,0,0,0,0xbe303d65,0,0,0,0,0xbe303d65,
0xbe373ce8,0,0,0,0,0xbe373ce8,0,0,0,0,0xbe373ce8,0,0,0,0,0xbe373ce8,
0x3ddabe16,0,0,0,0,0x3ddabe16,0,0,0,0,0x3ddabe16,0,0,0,0,0x3ddabe16,
0x3e25bda8,0,0,0,0,0x3e25bda8,0,0,0,0,0x3e25bda8,0,0,0,0,0x3e25bda8,
0xbe390000,0,0,0,0,0xbe390000,0,0,0,0,0xbe390000,0,0,0,0,0xbe390000,
0xbe37bce8,0,0,0,0,0xbe37bce8,0,0,0,0,0xbe37bce8,0,0,0,0,0xbe37bce8,
0x3e390000,0,0,0,0,0x3e390000,0,0,0,0,0x3e390000,0,0,0,0,0x3e390000,
0x3e253da8,0,0,0,0,0x3e253da8,0,0,0,0,0x3e253da8,0,0,0,0,0x3e253da8,
0xbe30bd65,0,0,0,0,0xbe30bd65,0,0,0,0,0xbe30bd65,0,0,0,0,0xbe30bd65,
0xbe25bda8,0,0,0,0,0xbe25bda8,0,0,0,0,0xbe25bda8,0,0,0,0,0xbe25bda8,
0x3dda3e16,0,0,0,0,0x3dda3e16,0,0,0,0,0x3dda3e16,0,0,0,0,0x3dda3e16,
0x3ce83e37,0,0,0,0,0x3ce83e37,0,0,0,0,0x3ce83e37,0,0,0,0,0x3ce83e37,
0xbe16bdda,0,0,0,0,0xbe16bdda,0,0,0,0,0xbe16bdda,0,0,0,0,0xbe16bdda,
0xbe03be03,0,0,0,0,0xbe03be03,0,0,0,0,0xbe03be03,0,0,0,0,0xbe03be03,
0xbd653e30,0,0,0,0,0xbd653e30,0,0,0,0,0xbd653e30,0,0,0,0,0xbd653e30,
0xbe033e03,0,0,0,0,0xbe033e03,0,0,0,0,0xbe033e03,0,0,0,0,0xbe033e03,
0xbddabe16,0,0,0,0,0xbddabe16,0,0,0,0,0xbddabe16,0,0,0,0,0xbddabe16,
0xbda8be25,0,0,0,0,0xbda8be25,0,0,0,0,0xbda8be25,0,0,0,0,0xbda8be25,
0xbe303d65,0,0,0,0,0xbe303d65,0,0,0,0,0xbe303d65,0,0,0,0,0xbe303d65,
0xbe37bce8,0,0,0,0,0xbe37bce8,0,0,0,0,0xbe37bce8,0,0,0,0,0xbe37bce8,
0xbd65be30,0,0,0,0,0xbd65be30,0,0,0,0,0xbd65be30,0,0,0,0,0xbd65be30,
0xbce8be37,0,0,0,0,0xbce8be37,0,0,0,0,0xbce8be37,0,0,0,0,0xbce8be37,
0xbe16bdda,0,0,0,0,0xbe16bdda,0,0,0,0,0xbe16bdda,0,0,0,0,0xbe16bdda,
0xbda8be25,0,0,0,0,0xbda8be25,0,0,0,0,0xbda8be25,0,0,0,0,0xbda8be25,
0x3e390000,0,0,0,0,0x3e390000,0,0,0,0,0x3e390000,0,0,0,0,0x3e390000,
0x3e033e03,0,0,0,0,0x3e033e03,0,0,0,0,0x3e033e03,0,0,0,0,0x3e033e03,
0xbd653e30,0,0,0,0,0xbd653e30,0,0,0,0,0xbd653e30,0,0,0,0,0xbd653e30,
0xbe373ce8,0,0,0,0,0xbe373ce8,0,0,0,0,0xbe373ce8,0,0,0,0,0xbe373ce8,
0x80003e39,0,0,0,0,0x80003e39,0,0,0,0,0x80003e39,0,0,0,0,0x80003e39,
0xbe033e03,0,0,0,0,0xbe033e03,0,0,0,0,0xbe033e03,0,0,0,0,0xbe033e03,
0xbddabe16,0,0,0,0,0xbddabe16,0,0,0,0,0xbddabe16,0,0,0,0,0xbddabe16,
0x3da8be25,0,0,0,0,0x3da8be25,0,0,0,0,0x3da8be25,0,0,0,0,0x3da8be25,
0xbe390000,0,0,0,0,0xbe390000,0,0,0,0,0xbe390000,0,0,0,0,0xbe390000,
0xbe03be03,0,0,0,0,0xbe03be03,0,0,0,0,0xbe03be03,0,0,0,0,0xbe03be03,
0x3e390000,0,0,0,0,0x3e390000,0,0,0,0,0x3e390000,0,0,0,0,0x3e390000,
0x3da83e25,0,0,0,0,0x3da83e25,0,0,0,0,0x3da83e25,0,0,0,0,0x3da83e25,
0x8000be39,0,0,0,0,0x8000be39,0,0,0,0,0x8000be39,0,0,0,0,0x8000be39,
0x3e03be03,0,0,0,0,0x3e03be03,0,0,0,0,0x3e03be03,0,0,0,0,0x3e03be03,
0xbdda3e16,0,0,0,0,0xbdda3e16,0,0,0,0,0xbdda3e16,0,0,0,0,0xbdda3e16,
0xbe37bce8,0,0,0,0,0xbe37bce8,0,0,0,0,0xbe37bce8,0,0,0,0,0xbe37bce8,
0x3e390000,0,0,0,0,0x3e390000,0,0,0,0,0x3e390000,0,0,0,0,0x3e390000,
0x3e033e03,0,0,0,0,0x3e033e03,0,0,0,0,0x3e033e03,0,0,0,0,0x3e033e03,
0xbd65be30,0,0,0,0,0xbd65be30,0,0,0,0,0xbd65be30,0,0,0,0,0xbd65be30,
0x3e03be03,0,0,0,0,0x3e03be03,0,0,0,0,0x3e03be03,0,0,0,0,0x3e03be03,
0x80003e39,0,0,0,0,0x80003e39,0,0,0,0,0x80003e39,0,0,0,0,0x80003e39,
0xbe033e03,0,0,0,0,0xbe033e03,0,0,0,0,0xbe033e03,0,0,0,0,0xbe033e03,
0x3e303d65,0,0,0,0,0x3e303d65,0,0,0,0,0x3e303d65,0,0,0,0,0x3e303d65,
0x3ce83e37,0,0,0,0,0x3ce83e37,0,0,0,0,0x3ce83e37,0,0,0,0,0x3ce83e37,
0xbe390000,0,0,0,0,0xbe390000,0,0,0,0,0xbe390000,0,0,0,0,0xbe390000,
0xbe03be03,0,0,0,0,0xbe03be03,0,0,0,0,0xbe03be03,0,0,0,0,0xbe03be03,
0xbe163dda,0,0,0,0,0xbe163dda,0,0,0,0,0xbe163dda,0,0,0,0,0xbe163dda,
0xbe25bda8,0,0,0,0,0xbe25bda8,0,0,0,0,0xbe25bda8,0,0,0,0,0xbe25bda8,
0xbe16bdda,0,0,0,0,0xbe16bdda,0,0,0,0,0xbe16bdda,0,0,0,0,0xbe16bdda,
0x3da8be25,0,0,0,0,0x3da8be25,0,0,0,0,0x3da8be25,0,0,0,0,0x3da8be25,
0x3e16bdda,0,0,0,0,0x3e16bdda,0,0,0,0,0x3e16bdda,0,0,0,0,0x3e16bdda,
0x3da83e25,0,0,0,0,0x3da83e25,0,0,0,0,0x3da83e25,0,0,0,0,0x3da83e25,
0x3e303d65,0,0,0,0,0x3e303d65,0,0,0,0,0x3e303d65,0,0,0,0,0x3e303d65,
0xbce83e37,0,0,0,0,0xbce83e37,0,0,0,0,0xbce83e37,0,0,0,0,0xbce83e37,
0xbe303d65,0,0,0,0,0xbe303d65,0,0,0,0,0xbe303d65,0,0,0,0,0xbe303d65,
0xbce8be37,0,0,0,0,0xbce8be37,0,0,0,0,0xbce8be37,0,0,0,0,0xbce8be37,
0xbe390000,0,0,0,0,0xbe390000,0,0,0,0,0xbe390000,0,0,0,0,0xbe390000,
0xbce8be37,0,0,0,0,0xbce8be37,0,0,0,0,0xbce8be37,0,0,0,0,0xbce8be37,
0x3e390000,0,0,0,0,0x3e390000,0,0,0,0,0x3e390000,0,0,0,0,0x3e390000,
0xbce83e37,0,0,0,0,0xbce83e37,0,0,0,0,0xbce83e37,0,0,0,0,0xbce83e37,
0x3e30bd65,0,0,0,0,0x3e30bd65,0,0,0,0,0x3e30bd65,0,0,0,0,0x3e30bd65,
0x3da83e25,0,0,0,0,0x3da83e25,0,0,0,0,0x3da83e25,0,0,0,0,0x3da83e25,
0xbe30bd65,0,0,0,0,0xbe30bd65,0,0,0,0,0xbe30bd65,0,0,0,0,0xbe30bd65,
0x3da8be25,0,0,0,0,0x3da8be25,0,0,0,0,0x3da8be25,0,0,0,0,0x3da8be25,
0xbe163dda,0,0,0,0,0xbe163dda,0,0,0,0,0xbe163dda,0,0,0,0,0xbe163dda,
0xbe03be03,0,0,0,0,0xbe03be03,0,0,0,0,0xbe03be03,0,0,0,0,0xbe03be03,
0x3e163dda,0,0,0,0,0x3e163dda,0,0,0,0,0x3e163dda,0,0,0,0,0x3e163dda,
0xbe033e03,0,0,0,0,0xbe033e03,0,0,0,0,0xbe033e03,0,0,0,0,0xbe033e03,
0x3ddabe16,0,0,0,0,0x3ddabe16,0,0,0,0,0x3ddabe16,0,0,0,0,0x3ddabe16,
0x3e253da8,0,0,0,0,0x3e253da8,0,0,0,0,0x3e253da8,0,0,0,0,0x3e253da8,
0xbddabe16,0,0,0,0,0xbddabe16,0,0,0,0,0xbddabe16,0,0,0,0,0xbddabe16,
0x3e25bda8,0,0,0,0,0x3e25bda8,0,0,0,0,0x3e25bda8,0,0,0,0,0x3e25bda8,
0xbd653e30,0,0,0,0,0xbd653e30,0,0,0,0,0xbd653e30,0,0,0,0,0xbd653e30,
0xbe37bce8,0,0,0,0,0xbe37bce8,0,0,0,0,0xbe37bce8,0,0,0,0,0xbe37bce8,
0x3d653e30,0,0,0,0,0x3d653e30,0,0,0,0,0x3d653e30,0,0,0,0,0x3d653e30,
0xbe373ce8,0,0,0,0,0xbe373ce8,0,0,0,0,0xbe373ce8,0,0,0,0,0xbe373ce8,
0x3d653e30,0,0,0,0,0x3d653e30,0,0,0,0,0x3d653e30,0,0,0,0,0x3d653e30,
0xbe37bce8,0,0,0,0,0xbe37bce8,0,0,0,0,0xbe37bce8,0,0,0,0,0xbe37bce8,
0xbe390000,0,0,0,0,0xbe390000,0,0,0,0,0xbe390000,0,0,0,0,0xbe390000,
0x3e03be03,0,0,0,0,0x3e03be03,0,0,0,0,0x3e03be03,0,0,0,0,0x3e03be03,
0x3ddabe16,0,0,0,0,0x3ddabe16,0,0,0,0,0x3ddabe16,0,0,0,0,0x3ddabe16,
0x3da83e25,0,0,0,0,0x3da83e25,0,0,0,0,0x3da83e25,0,0,0,0,0x3da83e25,
0x80003e39,0,0,0,0,0x80003e39,0,0,0,0,0x80003e39,0,0,0,0,0x80003e39,
0xbe03be03,0,0,0,0,0xbe03be03,0,0,0,0,0xbe03be03,0,0,0,0,0xbe03be03,
0xbe390000,0,0,0,0,0xbe390000,0,0,0,0,0xbe390000,0,0,0,0,0xbe390000,
0x3da8be25,0,0,0,0,0x3da8be25,0,0,0,0,0x3da8be25,0,0,0,0,0x3da8be25,
0x3e390000,0,0,0,0,0x3e390000,0,0,0,0,0x3e390000,0,0,0,0,0x3e390000,
0xbe033e03,0,0,0,0,0xbe033e03,0,0,0,0,0xbe033e03,0,0,0,0,0xbe033e03,
0x3dda3e16,0,0,0,0,0x3dda3e16,0,0,0,0,0x3dda3e16,0,0,0,0,0x3dda3e16,
0xbe373ce8,0,0,0,0,0xbe373ce8,0,0,0,0,0xbe373ce8,0,0,0,0,0xbe373ce8,
0x8000be39,0,0,0,0,0x8000be39,0,0,0,0,0x8000be39,0,0,0,0,0x8000be39,
0x3e033e03,0,0,0,0,0x3e033e03,0,0,0,0,0x3e033e03,0,0,0,0,0x3e033e03,
0x3d65be30,0,0,0,0,0x3d65be30,0,0,0,0,0x3d65be30,0,0,0,0,0x3d65be30,
0x3e033e03,0,0,0,0,0x3e033e03,0,0,0,0,0x3e033e03,0,0,0,0,0x3e033e03,
0xbe390000,0,0,0,0,0xbe390000,0,0,0,0,0xbe390000,0,0,0,0,0xbe390000,
0x3e03be03,0,0,0,0,0x3e03be03,0,0,0,0,0x3e03be03,0,0,0,0,0x3e03be03,
0xbe303d65,0,0,0,0,0xbe303d65,0,0,0,0,0xbe303d65,0,0,0,0,0xbe303d65,
0x3ce8be37,0,0,0,0,0x3ce8be37,0,0,0,0,0x3ce8be37,0,0,0,0,0x3ce8be37,
0x80003e39,0,0,0,0,0x80003e39,0,0,0,0,0x80003e39,0,0,0,0,0x80003e39,
0xbe03be03,0,0,0,0,0xbe03be03,0,0,0,0,0xbe03be03,0,0,0,0,0xbe03be03,
0x3e163dda,0,0,0,0,0x3e163dda,0,0,0,0,0x3e163dda,0,0,0,0,0x3e163dda,
0xbe253da8,0,0,0,0,0xbe253da8,0,0,0,0,0xbe253da8,0,0,0,0,0xbe253da8,
0x3e390000,0,0,0,0,0x3e390000,0,0,0,0,0x3e390000,0,0,0,0,0x3e390000,
0xbe033e03,0,0,0,0,0xbe033e03,0,0,0,0,0xbe033e03,0,0,0,0,0xbe033e03,
0x3d65be30,0,0,0,0,0x3d65be30,0,0,0,0,0x3d65be30,0,0,0,0,0x3d65be30,
0x3ce83e37,0,0,0,0,0x3ce83e37,0,0,0,0,0x3ce83e37,0,0,0,0,0x3ce83e37,
0x3e163dda,0,0,0,0,0x3e163dda,0,0,0,0,0x3e163dda,0,0,0,0,0x3e163dda,
0xbe25bda8,0,0,0,0,0xbe25bda8,0,0,0,0,0xbe25bda8,0,0,0,0,0xbe25bda8,
0xbddabe16,0,0,0,0,0xbddabe16,0,0,0,0,0xbddabe16,0,0,0,0,0xbddabe16,
0x3e253da8,0,0,0,0,0x3e253da8,0,0,0,0,0x3e253da8,0,0,0,0,0x3e253da8,
0x3e303d65,0,0,0,0,0x3e303d65,0,0,0,0,0x3e303d65,0,0,0,0,0x3e303d65,
0xbe37bce8,0,0,0,0,0xbe37bce8,0,0,0,0,0xbe37bce8,0,0,0,0,0xbe37bce8,
0xbe390000,0,0,0,0,0xbe390000,0,0,0,0,0xbe390000,0,0,0,0,0xbe390000,
0x3e25bda8,0,0,0,0,0x3e25bda8,0,0,0,0,0x3e25bda8,0,0,0,0,0x3e25bda8,
0x3e390000,0,0,0,0,0x3e390000,0,0,0,0,0x3e390000,0,0,0,0,0x3e390000,
0xbe373ce8,0,0,0,0,0xbe373ce8,0,0,0,0,0xbe373ce8,0,0,0,0,0xbe373ce8,
0xbdda3e16,0,0,0,0,0xbdda3e16,0,0,0,0,0xbdda3e16,0,0,0,0,0xbdda3e16,
0x3ce8be37,0,0,0,0,0x3ce8be37,0,0,0,0,0x3ce8be37,0,0,0,0,0x3ce8be37,
0x3e30bd65,0,0,0,0,0x3e30bd65,0,0,0,0,0x3e30bd65,0,0,0,0,0x3e30bd65,
0xbe253da8,0,0,0,0,0xbe253da8,0,0,0,0,0xbe253da8,0,0,0,0,0xbe253da8,
0x3d653e30,0,0,0,0,0x3d653e30,0,0,0,0,0x3d653e30,0,0,0,0,0x3d653e30,
0xbe03be03,0,0,0,0,0xbe03be03,0,0,0,0,0xbe03be03,0,0,0,0,0xbe03be03,
0x3e16bdda,0,0,0,0,0x3e16bdda,0,0,0,0,0x3e16bdda,0,0,0,0,0x3e16bdda,
0xbe033e03,0,0,0,0,0xbe033e03,0,0,0,0,0xbe033e03,0,0,0,0,0xbe033e03,
0x3e303d65,0,0,0,0,0x3e303d65,0,0,0,0,0x3e303d65,0,0,0,0,0x3e303d65,
0xbe373ce8,0,0,0,0,0xbe373ce8,0,0,0,0,0xbe373ce8,0,0,0,0,0xbe373ce8,
0x3ddabe16,0,0,0,0,0x3ddabe16,0,0,0,0,0x3ddabe16,0,0,0,0,0x3ddabe16,
0xbda83e25,0,0,0,0,0xbda83e25,0,0,0,0,0xbda83e25,0,0,0,0,0xbda83e25,
0x3e16bdda,0,0,0,0,0x3e16bdda,0,0,0,0,0x3e16bdda,0,0,0,0,0x3e16bdda,
0xbda83e25,0,0,0,0,0xbda83e25,0,0,0,0,0xbda83e25,0,0,0,0,0xbda83e25,
0x3d65be30,0,0,0,0,0x3d65be30,0,0,0,0,0x3d65be30,0,0,0,0,0x3d65be30,
0xbce83e37,0,0,0,0,0xbce83e37,0,0,0,0,0xbce83e37,0,0,0,0,0xbce83e37,
0,0,0xbe163dda,0,0,0,0,0xbe163dda,0,0,0xbe253da8,0,0,0,0,0xbe253da8,
0,0,0xbe303d65,0,0,0,0,0xbe303d65,0,0,0xbe373ce8,0,0,0,0,0xbe373ce8,
0,0,0xbd65be30,0,0,0,0,0xbd65be30,0,0,0x3ce8be37,0,0,0,0,0x3ce8be37,
0,0,0x3ddabe16,0,0,0,0,0x3ddabe16,0,0,0x3e25bda8,0,0,0,0,0x3e25bda8,
0,0,0xbe390000,0,0,0,0,0xbe390000,0,0,0xbe37bce8,0,0,0,0,0xbe37bce8,
0,0,0xbe30bd65,0,0,0,0,0xbe30bd65,0,0,0xbe25bda8,0,0,0,0,0xbe25bda8,
0,0,0x3e390000,0,0,0,0,0x3e390000,0,0,0x3e253da8,0,0,0,0,0x3e253da8,
0,0,0x3dda3e16,0,0,0,0,0x3dda3e16,0,0,0x3ce83e37,0,0,0,0,0x3ce83e37,
0,0,0xbe16bdda,0,0,0,0,0xbe16bdda,0,0,0xbe03be03,0,0,0,0,0xbe03be03,
0,0,0xbddabe16,0,0,0,0,0xbddabe16,0,0,0xbda8be25,0,0,0,0,0xbda8be25,
0,0,0xbd653e30,0,0,0,0,0xbd653e30,0,0,0xbe033e03,0,0,0,0,0xbe033e03,
0,0,0xbe303d65,0,0,0,0,0xbe303d65,0,0,0xbe37bce8,0,0,0,0,0xbe37bce8,
0,0,0xbd65be30,0,0,0,0,0xbd65be30,0,0,0xbce8be37,0,0,0,0,0xbce8be37,
0,0,0,0,0,0,0,0,0,0,0,0,0,0,0,0,
0,0,0xbe16bdda,0,0,0,0,0xbe16bdda,0,0,0xbda8be25,0,0,0,0,0xbda8be25,
0,0,0,0,0,0,0,0,0,0,0,0,0,0,0,0,
0,0,0x3e390000,0,0,0,0,0x3e390000,0,0,0x3e033e03,0,0,0,0,0x3e033e03,
0,0,0x80003e39,0,0,0,0,0x80003e39,0,0,0xbe033e03,0,0,0,0,0xbe033e03,
0,0,0xbd653e30,0,0,0,0,0xbd653e30,0,0,0xbe373ce8,0,0,0,0,0xbe373ce8,
0,0,0xbddabe16,0,0,0,0,0xbddabe16,0,0,0x3da8be25,0,0,0,0,0x3da8be25,
0,0,0xbe390000,0,0,0,0,0xbe390000,0,0,0xbe03be03,0,0,0,0,0xbe03be03,
0,0,0x8000be39,0,0,0,0,0x8000be39,0,0,0x3e03be03,0,0,0,0,0x3e03be03,
0,0,0x3e390000,0,0,0,0,0x3e390000,0,0,0x3da83e25,0,0,0,0,0x3da83e25,
0,0,0xbdda3e16,0,0,0,0,0xbdda3e16,0,0,0xbe37bce8,0,0,0,0,0xbe37bce8,
0,0,0x3e390000,0,0,0,0,0x3e390000,0,0,0x3e033e03,0,0,0,0,0x3e033e03,
0,0,0x80003e39,0,0,0,0,0x80003e39,0,0,0xbe033e03,0,0,0,0,0xbe033e03,
0,0,0xbd65be30,0,0,0,0,0xbd65be30,0,0,0x3e03be03,0,0,0,0,0x3e03be03,
0,0,0x3e303d65,0,0,0,0,0x3e303d65,0,0,0x3ce83e37,0,0,0,0,0x3ce83e37,
0,0,0xbe390000,0,0,0,0,0xbe390000,0,0,0xbe03be03,0,0,0,0,0xbe03be03,
0,0,0,0,0,0,0,0,0,0,0,0,0,0,0,0,
0,0,0xbe163dda,0,0,0,0,0xbe163dda,0,0,0xbe25bda8,0,0,0,0,0xbe25bda8,
0,0,0,0,0,0,0,0,0,0,0,0,0,0,0,0,
0,0,0xbe16bdda,0,0,0,0,0xbe16bdda,0,0,0x3da8be25,0,0,0,0,0x3da8be25,
0,0,0x3e303d65,0,0,0,0,0x3e303d65,0,0,0xbce83e37,0,0,0,0,0xbce83e37,
0,0,0x3e16bdda,0,0,0,0,0x3e16bdda,0,0,0x3da83e25,0,0,0,0,0x3da83e25,
0,0,0xbe303d65,0,0,0,0,0xbe303d65,0,0,0xbce8be37,0,0,0,0,0xbce8be37,
0,0,0xbe390000,0,0,0,0,0xbe390000,0,0,0xbce8be37,0,0,0,0,0xbce8be37,
0,0,0x3e30bd65,0,0,0,0,0x3e30bd65,0,0,0x3da83e25,0,0,0,0,0x3da83e25,
0,0,0x3e390000,0,0,0,0,0x3e390000,0,0,0xbce83e37,0,0,0,0,0xbce83e37,
0,0,0xbe30bd65,0,0,0,0,0xbe30bd65,0,0,0x3da8be25,0,0,0,0,0x3da8be25,
0,0,0xbe163dda,0,0,0,0,0xbe163dda,0,0,0xbe03be03,0,0,0,0,0xbe03be03,
0,0,0x3ddabe16,0,0,0,0,0x3ddabe16,0,0,0x3e253da8,0,0,0,0,0x3e253da8,
0,0,0x3e163dda,0,0,0,0,0x3e163dda,0,0,0xbe033e03,0,0,0,0,0xbe033e03,
0,0,0xbddabe16,0,0,0,0,0xbddabe16,0,0,0x3e25bda8,0,0,0,0,0x3e25bda8,
0,0,0xbd653e30,0,0,0,0,0xbd653e30,0,0,0xbe37bce8,0,0,0,0,0xbe37bce8,
0,0,0,0,0,0,0,0,0,0,0,0,0,0,0,0,
0,0,0x3d653e30,0,0,0,0,0x3d653e30,0,0,0xbe373ce8,0,0,0,0,0xbe373ce8,
0,0,0,0,0,0,0,0,0,0,0,0,0,0,0,0,
0,0,0x3d653e30,0,0,0,0,0x3d653e30,0,0,0xbe37bce8,0,0,0,0,0xbe37bce8,
0,0,0x3ddabe16,0,0,0,0,0x3ddabe16,0,0,0x3da83e25,0,0,0,0,0x3da83e25,
0,0,0xbe390000,0,0,0,0,0xbe390000,0,0,0x3e03be03,0,0,0,0,0x3e03be03,
0,0,0x80003e39,0,0,0,0,0x80003e39,0,0,0xbe03be03,0,0,0,0,0xbe03be03,
0,0,0xbe390000,0,0,0,0,0xbe390000,0,0,0x3da8be25,0,0,0,0,0x3da8be25,
0,0,0x3dda3e16,0,0,0,0,0x3dda3e16,0,0,0xbe373ce8,0,0,0,0,0xbe373ce8,
0,0,0x3e390000,0,0,0,0,0x3e390000,0,0,0xbe033e03,0,0,0,0,0xbe033e03,
0,0,0x8000be39,0,0,0,0,0x8000be39,0,0,0x3e033e03,0,0,0,0,0x3e033e03,
0,0,0x3d65be30,0,0,0,0,0x3d65be30,0,0,0x3e033e03,0,0,0,0,0x3e033e03,
0,0,0xbe303d65,0,0,0,0,0xbe303d65,0,0,0x3ce8be37,0,0,0,0,0x3ce8be37,
0,0,0xbe390000,0,0,0,0,0xbe390000,0,0,0x3e03be03,0,0,0,0,0x3e03be03,
0,0,0x80003e39,0,0,0,0,0x80003e39,0,0,0xbe03be03,0,0,0,0,0xbe03be03,
0,0,0x3e163dda,0,0,0,0,0x3e163dda,0,0,0xbe253da8,0,0,0,0,0xbe253da8,
0,0,0,0,0,0,0,0,0,0,0,0,0,0,0,0,
0,0,0x3e390000,0,0,0,0,0x3e390000,0,0,0xbe033e03,0,0,0,0,0xbe033e03,
0,0,0,0,0,0,0,0,0,0,0,0,0,0,0,0,
0,0,0x3d65be30,0,0,0,0,0x3d65be30,0,0,0x3ce83e37,0,0,0,0,0x3ce83e37,
0,0,0xbddabe16,0,0,0,0,0xbddabe16,0,0,0x3e253da8,0,0,0,0,0x3e253da8,
0,0,0x3e163dda,0,0,0,0,0x3e163dda,0,0,0xbe25bda8,0,0,0,0,0xbe25bda8,
0,0,0x3e303d65,0,0,0,0,0x3e303d65,0,0,0xbe37bce8,0,0,0,0,0xbe37bce8,
0,0,0xbe390000,0,0,0,0,0xbe390000,0,0,0x3e25bda8,0,0,0,0,0x3e25bda8,
0,0,0xbdda3e16,0,0,0,0,0xbdda3e16,0,0,0x3ce8be37,0,0,0,0,0x3ce8be37,
0,0,0x3e390000,0,0,0,0,0x3e390000,0,0,0xbe373ce8,0,0,0,0,0xbe373ce8,
0,0,0x3e30bd65,0,0,0,0,0x3e30bd65,0,0,0xbe253da8,0,0,0,0,0xbe253da8,
0,0,0x3d653e30,0,0,0,0,0x3d653e30,0,0,0xbe03be03,0,0,0,0,0xbe03be03,
0,0,0x3e303d65,0,0,0,0,0x3e303d65,0,0,0xbe373ce8,0,0,0,0,0xbe373ce8,
0,0,0x3e16bdda,0,0,0,0,0x3e16bdda,0,0,0xbe033e03,0,0,0,0,0xbe033e03,
0,0,0x3ddabe16,0,0,0,0,0x3ddabe16,0,0,0xbda83e25,0,0,0,0,0xbda83e25,
0,0,0x3e16bdda,0,0,0,0,0x3e16bdda,0,0,0xbda83e25,0,0,0,0,0xbda83e25,
0,0,0,0,0,0,0,0,0,0,0,0,0,0,0,0,
0,0,0x3d65be30,0,0,0,0,0x3d65be30,0,0,0xbce83e37,0,0,0,0,0xbce83e37,
0,0,0,0,0,0,0,0,0,0,0,0,0,0,0,0,
};
constexpr unsigned long long COS_PK0 = 0x3f903f9a3fa03fa2ull;
constexpr unsigned long long COS_PK1 = 0x3f133f3e3f653f83ull;
constexpr unsigned long long COS_PK2 = 0x3e4b3ec8ull;

__device__ __forceinline__ void wgmma_ss_n80_z(float (&d)[40], uint64_t da, uint64_t db) {
  asm volatile("{\n.reg .pred p;\nsetp.ne.b32 p, 0, 0;\nwgmma.mma_async.sync.aligned.m64n80k16.f32.bf16.bf16 {%0,%1,%2,%3,%4,%5,%6,%7,%8,%9,%10,%11,%12,%13,%14,%15,%16,%17,%18,%19,%20,%21,%22,%23,%24,%25,%26,%27,%28,%29,%30,%31,%32,%33,%34,%35,%36,%37,%38,%39}, %40, %41, p, 1, 1, 1, 0;\n}\n"
    : "+f"(d[0]), "+f"(d[1]), "+f"(d[2]), "+f"(d[3]), "+f"(d[4]), "+f"(d[5]), "+f"(d[6]), "+f"(d[7]), "+f"(d[8]), "+f"(d[9]), "+f"(d[10]), "+f"(d[11]), "+f"(d[12]), "+f"(d[13]), "+f"(d[14]), "+f"(d[15]), "+f"(d[16]), "+f"(d[17]), "+f"(d[18]), "+f"(d[19]), "+f"(d[20]), "+f"(d[21]), "+f"(d[22]), "+f"(d[23]), "+f"(d[24]), "+f"(d[25]), "+f"(d[26]), "+f"(d[27]), "+f"(d[28]), "+f"(d[29]), "+f"(d[30]), "+f"(d[31]), "+f"(d[32]), "+f"(d[33]), "+f"(d[34]), "+f"(d[35]), "+f"(d[36]), "+f"(d[37]), "+f"(d[38]), "+f"(d[39])
    : "l"(da), "l"(db));
}
__device__ __forceinline__ void wgmma_ss_n80_a(float (&d)[40], uint64_t da, uint64_t db) {
  asm volatile("{\n.reg .pred p;\nsetp.ne.b32 p, 1, 0;\nwgmma.mma_async.sync.aligned.m64n80k16.f32.bf16.bf16 {%0,%1,%2,%3,%4,%5,%6,%7,%8,%9,%10,%11,%12,%13,%14,%15,%16,%17,%18,%19,%20,%21,%22,%23,%24,%25,%26,%27,%28,%29,%30,%31,%32,%33,%34,%35,%36,%37,%38,%39}, %40, %41, p, 1, 1, 1, 0;\n}\n"
    : "+f"(d[0]), "+f"(d[1]), "+f"(d[2]), "+f"(d[3]), "+f"(d[4]), "+f"(d[5]), "+f"(d[6]), "+f"(d[7]), "+f"(d[8]), "+f"(d[9]), "+f"(d[10]), "+f"(d[11]), "+f"(d[12]), "+f"(d[13]), "+f"(d[14]), "+f"(d[15]), "+f"(d[16]), "+f"(d[17]), "+f"(d[18]), "+f"(d[19]), "+f"(d[20]), "+f"(d[21]), "+f"(d[22]), "+f"(d[23]), "+f"(d[24]), "+f"(d[25]), "+f"(d[26]), "+f"(d[27]), "+f"(d[28]), "+f"(d[29]), "+f"(d[30]), "+f"(d[31]), "+f"(d[32]), "+f"(d[33]), "+f"(d[34]), "+f"(d[35]), "+f"(d[36]), "+f"(d[37]), "+f"(d[38]), "+f"(d[39])
    : "l"(da), "l"(db));
}

__device__ __forceinline__ void wgmma_rs_n40_z(float (&d)[20], uint32_t a0, uint32_t a1, uint32_t a2, uint32_t a3, uint64_t db) {
  asm volatile("{\n.reg .pred p;\nsetp.ne.b32 p, 0, 0;\nwgmma.mma_async.sync.aligned.m64n40k16.f32.bf16.bf16 {%0,%1,%2,%3,%4,%5,%6,%7,%8,%9,%10,%11,%12,%13,%14,%15,%16,%17,%18,%19}, {%20,%21,%22,%23}, %24, p, 1, 1, 0;\n}\n"
    : "+f"(d[0]), "+f"(d[1]), "+f"(d[2]), "+f"(d[3]), "+f"(d[4]), "+f"(d[5]), "+f"(d[6]), "+f"(d[7]), "+f"(d[8]), "+f"(d[9]), "+f"(d[10]), "+f"(d[11]), "+f"(d[12]), "+f"(d[13]), "+f"(d[14]), "+f"(d[15]), "+f"(d[16]), "+f"(d[17]), "+f"(d[18]), "+f"(d[19])
    : "r"(a0), "r"(a1), "r"(a2), "r"(a3), "l"(db));
}
__device__ __forceinline__ void wgmma_rs_n40_a(float (&d)[20], uint32_t a0, uint32_t a1, uint32_t a2, uint32_t a3, uint64_t db) {
  asm volatile("{\n.reg .pred p;\nsetp.ne.b32 p, 1, 0;\nwgmma.mma_async.sync.aligned.m64n40k16.f32.bf16.bf16 {%0,%1,%2,%3,%4,%5,%6,%7,%8,%9,%10,%11,%12,%13,%14,%15,%16,%17,%18,%19}, {%20,%21,%22,%23}, %24, p, 1, 1, 0;\n}\n"
    : "+f"(d[0]), "+f"(d[1]), "+f"(d[2]), "+f"(d[3]), "+f"(d[4]), "+f"(d[5]), "+f"(d[6]), "+f"(d[7]), "+f"(d[8]), "+f"(d[9]), "+f"(d[10]), "+f"(d[11]), "+f"(d[12]), "+f"(d[13]), "+f"(d[14]), "+f"(d[15]), "+f"(d[16]), "+f"(d[17]), "+f"(d[18]), "+f"(d[19])
    : "r"(a0), "r"(a1), "r"(a2), "r"(a3), "l"(db));
}

__device__ __forceinline__ void wgmma_rs_n128_z(float (&d)[64], uint32_t a0, uint32_t a1, uint32_t a2, uint32_t a3, uint64_t db) {
  asm volatile("{\n.reg .pred p;\nsetp.ne.b32 p, 0, 0;\nwgmma.mma_async.sync.aligned.m64n128k16.f32.bf16.bf16 {%0,%1,%2,%3,%4,%5,%6,%7,%8,%9,%10,%11,%12,%13,%14,%15,%16,%17,%18,%19,%20,%21,%22,%23,%24,%25,%26,%27,%28,%29,%30,%31,%32,%33,%34,%35,%36,%37,%38,%39,%40,%41,%42,%43,%44,%45,%46,%47,%48,%49,%50,%51,%52,%53,%54,%55,%56,%57,%58,%59,%60,%61,%62,%63}, {%64,%65,%66,%67}, %68, p, 1, 1, 1;\n}\n"
    : "+f"(d[0]), "+f"(d[1]), "+f"(d[2]), "+f"(d[3]), "+f"(d[4]), "+f"(d[5]), "+f"(d[6]), "+f"(d[7]), "+f"(d[8]), "+f"(d[9]), "+f"(d[10]), "+f"(d[11]), "+f"(d[12]), "+f"(d[13]), "+f"(d[14]), "+f"(d[15]), "+f"(d[16]), "+f"(d[17]), "+f"(d[18]), "+f"(d[19]), "+f"(d[20]), "+f"(d[21]), "+f"(d[22]), "+f"(d[23]), "+f"(d[24]), "+f"(d[25]), "+f"(d[26]), "+f"(d[27]), "+f"(d[28]), "+f"(d[29]), "+f"(d[30]), "+f"(d[31]), "+f"(d[32]), "+f"(d[33]), "+f"(d[34]), "+f"(d[35]), "+f"(d[36]), "+f"(d[37]), "+f"(d[38]), "+f"(d[39]), "+f"(d[40]), "+f"(d[41]), "+f"(d[42]), "+f"(d[43]), "+f"(d[44]), "+f"(d[45]), "+f"(d[46]), "+f"(d[47]), "+f"(d[48]), "+f"(d[49]), "+f"(d[50]), "+f"(d[51]), "+f"(d[52]), "+f"(d[53]), "+f"(d[54]), "+f"(d[55]), "+f"(d[56]), "+f"(d[57]), "+f"(d[58]), "+f"(d[59]), "+f"(d[60]), "+f"(d[61]), "+f"(d[62]), "+f"(d[63])
    : "r"(a0), "r"(a1), "r"(a2), "r"(a3), "l"(db));
}
__device__ __forceinline__ void wgmma_rs_n128_a(float (&d)[64], uint32_t a0, uint32_t a1, uint32_t a2, uint32_t a3, uint64_t db) {
  asm volatile("{\n.reg .pred p;\nsetp.ne.b32 p, 1, 0;\nwgmma.mma_async.sync.aligned.m64n128k16.f32.bf16.bf16 {%0,%1,%2,%3,%4,%5,%6,%7,%8,%9,%10,%11,%12,%13,%14,%15,%16,%17,%18,%19,%20,%21,%22,%23,%24,%25,%26,%27,%28,%29,%30,%31,%32,%33,%34,%35,%36,%37,%38,%39,%40,%41,%42,%43,%44,%45,%46,%47,%48,%49,%50,%51,%52,%53,%54,%55,%56,%57,%58,%59,%60,%61,%62,%63}, {%64,%65,%66,%67}, %68, p, 1, 1, 1;\n}\n"
    : "+f"(d[0]), "+f"(d[1]), "+f"(d[2]), "+f"(d[3]), "+f"(d[4]), "+f"(d[5]), "+f"(d[6]), "+f"(d[7]), "+f"(d[8]), "+f"(d[9]), "+f"(d[10]), "+f"(d[11]), "+f"(d[12]), "+f"(d[13]), "+f"(d[14]), "+f"(d[15]), "+f"(d[16]), "+f"(d[17]), "+f"(d[18]), "+f"(d[19]), "+f"(d[20]), "+f"(d[21]), "+f"(d[22]), "+f"(d[23]), "+f"(d[24]), "+f"(d[25]), "+f"(d[26]), "+f"(d[27]), "+f"(d[28]), "+f"(d[29]), "+f"(d[30]), "+f"(d[31]), "+f"(d[32]), "+f"(d[33]), "+f"(d[34]), "+f"(d[35]), "+f"(d[36]), "+f"(d[37]), "+f"(d[38]), "+f"(d[39]), "+f"(d[40]), "+f"(d[41]), "+f"(d[42]), "+f"(d[43]), "+f"(d[44]), "+f"(d[45]), "+f"(d[46]), "+f"(d[47]), "+f"(d[48]), "+f"(d[49]), "+f"(d[50]), "+f"(d[51]), "+f"(d[52]), "+f"(d[53]), "+f"(d[54]), "+f"(d[55]), "+f"(d[56]), "+f"(d[57]), "+f"(d[58]), "+f"(d[59]), "+f"(d[60]), "+f"(d[61]), "+f"(d[62]), "+f"(d[63])
    : "r"(a0), "r"(a1), "r"(a2), "r"(a3), "l"(db));
}

__device__ __forceinline__ void wgmma_rs_n32_z(float (&d)[16], uint32_t a0, uint32_t a1, uint32_t a2, uint32_t a3, uint64_t db) {
  asm volatile("{\n.reg .pred p;\nsetp.ne.b32 p, 0, 0;\nwgmma.mma_async.sync.aligned.m64n32k16.f32.bf16.bf16 {%0,%1,%2,%3,%4,%5,%6,%7,%8,%9,%10,%11,%12,%13,%14,%15}, {%16,%17,%18,%19}, %20, p, 1, 1, 0;\n}\n"
    : "+f"(d[0]), "+f"(d[1]), "+f"(d[2]), "+f"(d[3]), "+f"(d[4]), "+f"(d[5]), "+f"(d[6]), "+f"(d[7]), "+f"(d[8]), "+f"(d[9]), "+f"(d[10]), "+f"(d[11]), "+f"(d[12]), "+f"(d[13]), "+f"(d[14]), "+f"(d[15])
    : "r"(a0), "r"(a1), "r"(a2), "r"(a3), "l"(db));
}
__device__ __forceinline__ void wgmma_rs_n32_a(float (&d)[16], uint32_t a0, uint32_t a1, uint32_t a2, uint32_t a3, uint64_t db) {
  asm volatile("{\n.reg .pred p;\nsetp.ne.b32 p, 1, 0;\nwgmma.mma_async.sync.aligned.m64n32k16.f32.bf16.bf16 {%0,%1,%2,%3,%4,%5,%6,%7,%8,%9,%10,%11,%12,%13,%14,%15}, {%16,%17,%18,%19}, %20, p, 1, 1, 0;\n}\n"
    : "+f"(d[0]), "+f"(d[1]), "+f"(d[2]), "+f"(d[3]), "+f"(d[4]), "+f"(d[5]), "+f"(d[6]), "+f"(d[7]), "+f"(d[8]), "+f"(d[9]), "+f"(d[10]), "+f"(d[11]), "+f"(d[12]), "+f"(d[13]), "+f"(d[14]), "+f"(d[15])
    : "r"(a0), "r"(a1), "r"(a2), "r"(a3), "l"(db));
}

__device__ __forceinline__ void wgmma_rs_n64_z(float (&d)[32], uint32_t a0, uint32_t a1, uint32_t a2, uint32_t a3, uint64_t db) {
  asm volatile("{\n.reg .pred p;\nsetp.ne.b32 p, 0, 0;\nwgmma.mma_async.sync.aligned.m64n64k16.f32.bf16.bf16 {%0,%1,%2,%3,%4,%5,%6,%7,%8,%9,%10,%11,%12,%13,%14,%15,%16,%17,%18,%19,%20,%21,%22,%23,%24,%25,%26,%27,%28,%29,%30,%31}, {%32,%33,%34,%35}, %36, p, 1, 1, 0;\n}\n"
    : "+f"(d[0]), "+f"(d[1]), "+f"(d[2]), "+f"(d[3]), "+f"(d[4]), "+f"(d[5]), "+f"(d[6]), "+f"(d[7]), "+f"(d[8]), "+f"(d[9]), "+f"(d[10]), "+f"(d[11]), "+f"(d[12]), "+f"(d[13]), "+f"(d[14]), "+f"(d[15]), "+f"(d[16]), "+f"(d[17]), "+f"(d[18]), "+f"(d[19]), "+f"(d[20]), "+f"(d[21]), "+f"(d[22]), "+f"(d[23]), "+f"(d[24]), "+f"(d[25]), "+f"(d[26]), "+f"(d[27]), "+f"(d[28]), "+f"(d[29]), "+f"(d[30]), "+f"(d[31])
    : "r"(a0), "r"(a1), "r"(a2), "r"(a3), "l"(db));
}
__device__ __forceinline__ void wgmma_rs_n64_a(float (&d)[32], uint32_t a0, uint32_t a1, uint32_t a2, uint32_t a3, uint64_t db) {
  asm volatile("{\n.reg .pred p;\nsetp.ne.b32 p, 1, 0;\nwgmma.mma_async.sync.aligned.m64n64k16.f32.bf16.bf16 {%0,%1,%2,%3,%4,%5,%6,%7,%8,%9,%10,%11,%12,%13,%14,%15,%16,%17,%18,%19,%20,%21,%22,%23,%24,%25,%26,%27,%28,%29,%30,%31}, {%32,%33,%34,%35}, %36, p, 1, 1, 0;\n}\n"
    : "+f"(d[0]), "+f"(d[1]), "+f"(d[2]), "+f"(d[3]), "+f"(d[4]), "+f"(d[5]), "+f"(d[6]), "+f"(d[7]), "+f"(d[8]), "+f"(d[9]), "+f"(d[10]), "+f"(d[11]), "+f"(d[12]), "+f"(d[13]), "+f"(d[14]), "+f"(d[15]), "+f"(d[16]), "+f"(d[17]), "+f"(d[18]), "+f"(d[19]), "+f"(d[20]), "+f"(d[21]), "+f"(d[22]), "+f"(d[23]), "+f"(d[24]), "+f"(d[25]), "+f"(d[26]), "+f"(d[27]), "+f"(d[28]), "+f"(d[29]), "+f"(d[30]), "+f"(d[31])
    : "r"(a0), "r"(a1), "r"(a2), "r"(a3), "l"(db));
}

__device__ __forceinline__ void wgmma_ss_n32_z(float (&d)[16], uint64_t da, uint64_t db) {
  asm volatile("{\n.reg .pred p;\nsetp.ne.b32 p, 0, 0;\nwgmma.mma_async.sync.aligned.m64n32k16.f32.bf16.bf16 {%0,%1,%2,%3,%4,%5,%6,%7,%8,%9,%10,%11,%12,%13,%14,%15}, %16, %17, p, 1, 1, 1, 0;\n}\n"
    : "+f"(d[0]), "+f"(d[1]), "+f"(d[2]), "+f"(d[3]), "+f"(d[4]), "+f"(d[5]), "+f"(d[6]), "+f"(d[7]), "+f"(d[8]), "+f"(d[9]), "+f"(d[10]), "+f"(d[11]), "+f"(d[12]), "+f"(d[13]), "+f"(d[14]), "+f"(d[15])
    : "l"(da), "l"(db));
}
__device__ __forceinline__ void wgmma_ss_n32_a(float (&d)[16], uint64_t da, uint64_t db) {
  asm volatile("{\n.reg .pred p;\nsetp.ne.b32 p, 1, 0;\nwgmma.mma_async.sync.aligned.m64n32k16.f32.bf16.bf16 {%0,%1,%2,%3,%4,%5,%6,%7,%8,%9,%10,%11,%12,%13,%14,%15}, %16, %17, p, 1, 1, 1, 0;\n}\n"
    : "+f"(d[0]), "+f"(d[1]), "+f"(d[2]), "+f"(d[3]), "+f"(d[4]), "+f"(d[5]), "+f"(d[6]), "+f"(d[7]), "+f"(d[8]), "+f"(d[9]), "+f"(d[10]), "+f"(d[11]), "+f"(d[12]), "+f"(d[13]), "+f"(d[14]), "+f"(d[15])
    : "l"(da), "l"(db));
}

__device__ __forceinline__ void wgmma_ss_n40_z(float (&d)[20], uint64_t da, uint64_t db) {
  asm volatile("{\n.reg .pred p;\nsetp.ne.b32 p, 0, 0;\nwgmma.mma_async.sync.aligned.m64n40k16.f32.bf16.bf16 {%0,%1,%2,%3,%4,%5,%6,%7,%8,%9,%10,%11,%12,%13,%14,%15,%16,%17,%18,%19}, %20, %21, p, 1, 1, 1, 0;\n}\n"
    : "+f"(d[0]), "+f"(d[1]), "+f"(d[2]), "+f"(d[3]), "+f"(d[4]), "+f"(d[5]), "+f"(d[6]), "+f"(d[7]), "+f"(d[8]), "+f"(d[9]), "+f"(d[10]), "+f"(d[11]), "+f"(d[12]), "+f"(d[13]), "+f"(d[14]), "+f"(d[15]), "+f"(d[16]), "+f"(d[17]), "+f"(d[18]), "+f"(d[19])
    : "l"(da), "l"(db));
}
__device__ __forceinline__ void wgmma_ss_n40_a(float (&d)[20], uint64_t da, uint64_t db) {
  asm volatile("{\n.reg .pred p;\nsetp.ne.b32 p, 1, 0;\nwgmma.mma_async.sync.aligned.m64n40k16.f32.bf16.bf16 {%0,%1,%2,%3,%4,%5,%6,%7,%8,%9,%10,%11,%12,%13,%14,%15,%16,%17,%18,%19}, %20, %21, p, 1, 1, 1, 0;\n}\n"
    : "+f"(d[0]), "+f"(d[1]), "+f"(d[2]), "+f"(d[3]), "+f"(d[4]), "+f"(d[5]), "+f"(d[6]), "+f"(d[7]), "+f"(d[8]), "+f"(d[9]), "+f"(d[10]), "+f"(d[11]), "+f"(d[12]), "+f"(d[13]), "+f"(d[14]), "+f"(d[15]), "+f"(d[16]), "+f"(d[17]), "+f"(d[18]), "+f"(d[19])
    : "l"(da), "l"(db));
}

constexpr int NSM = 132, NH = 66;
constexpr int S0 = 0, S1 = 51200, S2 = 102400;
constexpr int C1 = 153600, C3 = C1, RG = C1 + 18432;
constexpr int WP = RG, TBL = RG + 28672, WS2 = RG + 30720;
constexpr int BARS = RG + 49152;
__host__ __device__ constexpr int wst_off(int i) { return i < 12 ? S2 + i * 4096 : WS2 + (i - 12) * 4096; }
constexpr int NBAR = 280;
constexpr int REL = BARS + NBAR * 8;
constexpr int SMEM_BYTES = REL + 16;
constexpr int B_XF = 0, B_CF1 = 15, B_CF3 = 16, B_WF = 17  , B_P1D = 18, B_WFREE = 20, B_REL = 21, B_ROLE = 22, B_X1 = 23, B_SIG = 24;
constexpr int B_RF = 32, B_RE = 46, B_YF = 60, B_WRD = 75, B_SFREE = 89, B_WCH = 131, B_RDY = 136, B_WE = 205, B_WL = 217, B_FIN = 229, B_TOK = 232;
constexpr int R_P2 = 15, R_P3 = 57;
constexpr int CNT_P1 = 0, CNT_P2 = 4, CNT_W = 8, CNT_RANK = 9, NCLS = 10, CNT_DONE = 0, CNT_REL = 1, NCNT = 2;
constexpr int SIG_W = 0, SIG_P1 = 1, SIG_P2 = 4;
#define PROBES 1
#define WB 100
#define PACE 0
#define PACE_SLACK 300
#define SWIN 2
#define X1AT 10
#define WARMUP 0
#define YPACE 0
#define POLL3 0
#define XPF 0
#define PSLEEP 0
#define TRICKLE
#define T1MASK 0x3e00
#define T2MASK 0x1f00
#define Y0AT 1
#define Y3FROM 1
#define EM58 2
#define TOKD 1
#define TOKM 6
#define X1BOX 0
#define X2BOX 5

__device__ uint4 g_scr[(14 << 21) / 16];
__device__ uint4 g_wf[200 * 72 * 32];
__device__ unsigned g_cnt[NCNT * 32];
__device__ __forceinline__ int slot_line(int chunk, int pg, int cls) {
    return (pg & 1) << 6 | (pg >> 1) << 9 | (chunk & 1) << 10 | (chunk >> 1) << 12 | ((pg ^ (pg >> 1) ^ chunk ^ (chunk >> 1) ^ cls) & 1) << 5;
}
__device__ __forceinline__ int phi_line(int phi, uint32_t rel) {
    return (phi >> 4) << 14 | (phi & 3) << 7 | ((phi >> 2) & 1) << 11 | ((phi >> 3) & 1) << 13 | ((rel >> (phi >> 4)) & 1) << 5;
}
__device__ __forceinline__ int extra_mask(int rk) { return rk < 58 ? 0 : rk < 60 ? EM58 : rk < 62 ? 1 : rk < 64 ? (EM58 == 2 ? 4 : 2) : (EM58 == 8 ? 4 : 8); }
__device__ __forceinline__ int wslot(int pc) {
    return (int)((0x645702651430ull >> (4 * pc)) & 3) * 12288 + (((0x645702651430ull >> (4 * pc)) & 4) ? S0 : RG);
}
__device__ __forceinline__ int xslot(int n) { return ((n & 4) ? S2 : RG) + ((n + 1) & 3) * 12288; }
__device__ __forceinline__ int extra_phi(int rk) { return 198 + (rk & 1); }
__host__ __device__ constexpr int quad_off(int Q) { return (Q >> 2) * 4096 + (Q & 3) * 512; }

#define PROF(k)
#define PROFW(k)
#define prof_dump()
struct Maps { CUtensorMap w, x34, x6, x28, wst, f16, f8, y4, y2; };
struct Ptrs { char* scr; const char* wf; const void* tab1; const void* tab3; unsigned* cnt; };

__device__ __forceinline__ uint32_t smem_u32(const void* p) { return (uint32_t)__cvta_generic_to_shared(p); }
__device__ __forceinline__ void mbar_wait(uint32_t bar) {
    uint32_t ok, it = 0;
    do {
        asm volatile("{\n.reg .pred p;\nmbarrier.try_wait.parity.shared::cta.b64 p, [%1], 0;\nselp.u32 %0, 1, 0, p;\n}" : "=r"(ok) : "r"(bar) : "memory");
        if (++it > (1u << 22)) break;
    } while (!ok);
}
__device__ __forceinline__ bool mbar_test(uint32_t bar) {
    uint32_t ok;
    asm volatile("{\n.reg .pred p;\nmbarrier.test_wait.parity.shared::cta.b64 p, [%1], 0;\nselp.u32 %0, 1, 0, p;\n}" : "=r"(ok) : "r"(bar) : "memory");
    return ok;
}
__device__ __forceinline__ void fence_async() { asm volatile("fence.proxy.async;" ::: "memory"); }
__device__ __forceinline__ void fence_async_smem() { asm volatile("fence.proxy.async.shared::cta;" ::: "memory"); }
#define ELECT "{\n.reg .pred p;\nelect.sync _|p, 0xffffffff;\n@p "
__device__ __forceinline__ void e_arrive(uint32_t bar) { asm volatile(ELECT "mbarrier.arrive.shared::cta.b64 _, [%0];\n}" :: "r"(bar) : "memory"); }
__device__ __forceinline__ void e_expect(uint32_t bar, uint32_t bytes) { asm volatile(ELECT "mbarrier.arrive.expect_tx.shared::cta.b64 _, [%0], %1;\n}" :: "r"(bar), "r"(bytes) : "memory"); }
__device__ __forceinline__ void e_g2s(uint32_t dst, const void* src, uint32_t bytes, uint32_t bar) {
    asm volatile(ELECT "cp.async.bulk.shared::cluster.global.mbarrier::complete_tx::bytes [%0], [%1], %2, [%3];\n}" :: "r"(dst), "l"(src), "r"(bytes), "r"(bar) : "memory");
}
__device__ __forceinline__ void e_s2g(void* dst, uint32_t src, uint32_t bytes) {
    asm volatile(ELECT "cp.async.bulk.global.shared::cta.bulk_group [%0], [%1], %2;\n}" :: "l"(dst), "r"(src), "r"(bytes) : "memory");
}
__device__ __forceinline__ void e_ld3(uint32_t dst, const CUtensorMap* m, int c0, int c1, int c2, uint32_t bar) {
    asm volatile(ELECT "cp.async.bulk.tensor.3d.shared::cluster.global.mbarrier::complete_tx::bytes [%0], [%1, {%3, %4, %5}], [%2];\n}"
                 :: "r"(dst), "l"(m), "r"(bar), "r"(c0), "r"(c1), "r"(c2) : "memory");
}
__device__ __forceinline__ void e_ld4(uint32_t dst, const CUtensorMap* m, int c0, int c3, uint32_t bar) {
    asm volatile(ELECT "cp.async.bulk.tensor.4d.shared::cluster.global.mbarrier::complete_tx::bytes [%0], [%1, {%3, %5, %5, %4}], [%2];\n}"
                 :: "r"(dst), "l"(m), "r"(bar), "r"(c0), "r"(c3), "r"(0) : "memory");
}
__device__ __forceinline__ void e_st3(const CUtensorMap* m, uint32_t src, int c0, int c1, int c2) {
    asm volatile(ELECT "cp.async.bulk.tensor.3d.global.shared::cta.bulk_group [%0, {%2, %3, %4}], [%1];\n}" :: "l"(m), "r"(src), "r"(c0), "r"(c1), "r"(c2) : "memory");
}
__device__ __forceinline__ void e_ld5(uint32_t dst, const CUtensorMap* m, int c4, uint32_t bar) {
    asm volatile(ELECT "cp.async.bulk.tensor.5d.shared::cluster.global.mbarrier::complete_tx::bytes [%0], [%1, {%4, %4, %4, %4, %3}], [%2];\n}"
                 :: "r"(dst), "l"(m), "r"(bar), "r"(c4), "r"(0) : "memory");
}
__device__ __forceinline__ void e_st5(const CUtensorMap* m, uint32_t src, int c4) {
    asm volatile(ELECT "cp.async.bulk.tensor.5d.global.shared::cta.bulk_group [%0, {%3, %3, %3, %3, %2}], [%1];\n}" :: "l"(m), "r"(src), "r"(c4), "r"(0) : "memory");
}
__device__ __forceinline__ void bulk_commit() { asm volatile("cp.async.bulk.commit_group;" ::: "memory"); }
template <int N> __device__ __forceinline__ void bulk_wait_read() { asm volatile("cp.async.bulk.wait_group.read %0;" :: "n"(N) : "memory"); }
__device__ __forceinline__ void wg_bar(int id) { asm volatile("bar.sync %0, 128;" :: "r"(id) : "memory"); }
__device__ __forceinline__ void bb_break(uint32_t v) { asm volatile("{\n.reg .pred p;\nsetp.eq.u32 p, %0, 0x7fc17fc1;\n@p nanosleep.u32 0;\n}" :: "r"(v) : "memory"); }
__device__ __forceinline__ uint32_t uni(uint32_t v) { return __shfl_sync(0xffffffffu, v, 0); }
__device__ __forceinline__ char* cls_cnt(char* scr, int cls) { return scr + slot_line(3, 2, cls) * 128; }
__device__ __forceinline__ uint32_t cnt_wait(const void* p, unsigned target) {
    auto ld = [&]() { unsigned v; asm volatile("ld.relaxed.gpu.global.u32 %0, [%1];" : "=r"(v) : "l"(p) : "memory"); return v; };
    unsigned v0 = ld(), v;
#pragma unroll 1
    for (unsigned it = 0; it < (1u << 22); it++) { if ((v = uni(v0)) >= target) break; if (PSLEEP) __nanosleep(PSLEEP); v0 = ld(); }
    return v;
}
__device__ __forceinline__ void wg_fence() { asm volatile("wgmma.fence.sync.aligned;" ::: "memory"); }
__device__ __forceinline__ void wg_commit() { asm volatile("wgmma.commit_group.sync.aligned;" ::: "memory"); }
template <int N> __device__ __forceinline__ void wg_wait() { asm volatile("wgmma.wait_group.sync.aligned %0;" :: "n"(N) : "memory"); }
template <int N> __device__ __forceinline__ void reg_fence(float (&d)[N]) {
#pragma unroll
    for (int i = 0; i < N; i++) asm volatile("" : "+f"(d[i]) :: "memory");
}
template <int N, int O, int M> __device__ __forceinline__ float (&sub(float (&d)[M]))[N] { return *reinterpret_cast<float (*)[N]>(&d[O]); }
template <int N> __device__ __forceinline__ void zero(float (&d)[N]) {
#pragma unroll
    for (int i = 0; i < N; i++) d[i] = 0.f;
}
__device__ __forceinline__ uint32_t pack2(float lo, float hi) {
    uint32_t r; asm volatile("cvt.rn.bf16x2.f32 %0, %1, %2;" : "=r"(r) : "f"(hi), "f"(lo)); return r;
}
__device__ __forceinline__ void stm4(uint32_t a, uint32_t r0, uint32_t r1, uint32_t r2, uint32_t r3) {
    asm volatile("stmatrix.sync.aligned.m8n8.x4.trans.shared.b16 [%0], {%1,%2,%3,%4};" :: "r"(a), "r"(r0), "r"(r1), "r"(r2), "r"(r3) : "memory");
}
__device__ __forceinline__ void stm2(uint32_t a, uint32_t r0, uint32_t r1) {
    asm volatile("stmatrix.sync.aligned.m8n8.x2.trans.shared.b16 [%0], {%1,%2};" :: "r"(a), "r"(r0), "r"(r1) : "memory");
}
__device__ __forceinline__ void stm1(uint32_t a, uint32_t r0) {
    asm volatile("stmatrix.sync.aligned.m8n8.x1.trans.shared.b16 [%0], {%1};" :: "r"(a), "r"(r0) : "memory");
}
struct Desc {
    uint32_t lo, hi;
    __device__ __forceinline__ operator uint64_t() const { return ((uint64_t)hi << 32) | lo; }
    __device__ __forceinline__ Desc operator+(uint32_t o) const { return Desc{lo + o, hi}; }
    __device__ __forceinline__ Desc operator^(uint32_t o) const { return Desc{lo ^ o, hi}; }
};
__device__ __forceinline__ Desc mkdesc(uint32_t addr, uint32_t lbo, uint32_t sbo, uint32_t swz) {
    return Desc{((addr & 0x3FFFF) >> 4) | ((lbo >> 4) << 16), (sbo >> 4) | (swz << 30)};
}
__device__ __forceinline__ uint32_t cos_bits(int k) {
    if (k > 20) k = 40 - k;
    const bool neg = k > 10;
    if (neg) k = 20 - k;
    const unsigned long long pk = k < 4 ? COS_PK0 : k < 8 ? COS_PK1 : COS_PK2;
    return (uint32_t)((pk >> (16 * (k & 3))) & 0xffff) ^ (neg ? 0x8000u : 0u);
}

__device__ __forceinline__ void task_w(int wg, int k, uint32_t sb) {
    const int tid = threadIdx.x & 127, w = uni(tid >> 5), lane = tid & 31, q = lane & 3;
    const int tb = 14 * k, t1 = min(tb + 14, 1800), cb0 = tb / 25;
    float acc[64];
    zero(acc);
    const int oc0 = tb - 25 * cb0, Lt = t1 - tb, L0 = min(Lt, 25 - oc0), n0 = (L0 + 3) >> 2;
    uint32_t a[2][4][4];
    auto gen = [&](uint32_t (&a)[4][4], int at) {
        const int phi = 8 * ((at < n0 ? oc0 + 4 * at : 4 * (at - n0)) + w) + (lane >> 2), f = (phi * 205) >> 12;
        const uint32_t ca = 8 * f + 4, cw = (phi - 20 * f) * 8, p0 = sb + TBL + cw * 2 * q;
#pragma unroll
        for (int kh = 0; kh < 7; kh++) {
            uint32_t v0, v1;
            asm volatile("ld.shared.u32 %0, [%1];" : "=r"(v0) : "r"(p0 + ca * kh));
            asm volatile("ld.shared.u32 %0, [%1];" : "=r"(v1) : "r"(p0 + cw + ca * kh));
            const int h = kh == 6 ? 1 : kh & 1;
            a[kh >> 1][2 * h] = __byte_perm(v0, v1, 0x5410);
            a[kh >> 1][2 * h + 1] = __byte_perm(v0, v1, 0x7632);
        }
        a[3][0] = 0; a[3][1] = 0;
    };
    gen(a[0], wg);
    if (wg) gen(a[1], wg + 2);
    PROFW(wg == 0 ? 124 : 127);
#pragma unroll 1
    for (int n = 0; n < 2; n++) {
        const int at = wg + 2 * n, i0 = at < n0 ? 4 * at : L0 + 4 * (at - n0), cnt = (at < n0 ? L0 : Lt) - i0, cb = cb0 + (at >= n0);
        if (cnt <= 0 || (n && !wg)) break;
        if (n) {
#pragma unroll
            for (int j = 0; j < 16; j++) a[0][j >> 2][j & 3] = a[1][j >> 2][j & 3];
        }
        const Desc dB = mkdesc(sb + WP + (cb - cb0) * 14336, 3584, 512, 2);
        if (at) mbar_wait(sb + BARS + 8 * (B_WCH + at - 1));
        mbar_wait(sb + BARS + 8 * (B_WF + 2 * (cb - cb0)));
        PROFW(at == 0 ? 125 : 127);
        wg_fence();
        wgmma_rs_n128_z(acc, a[0][0][0], a[0][0][1], a[0][0][2], a[0][0][3], dB);
        wgmma_rs_n128_a(acc, a[0][1][0], a[0][1][1], a[0][1][2], a[0][1][3], dB + (uint32_t)(16 * 64 >> 4));
        wgmma_rs_n128_a(acc, a[0][2][0], a[0][2][1], a[0][2][2], a[0][2][3], dB + (uint32_t)(32 * 64 >> 4));
        wgmma_rs_n128_a(acc, a[0][3][0], a[0][3][1], a[0][3][2], a[0][3][3], dB + (uint32_t)(40 * 64 >> 4));
        wg_commit();
        wg_wait<0>();
        reg_fence(acc);
        PROFW(at == 0 ? 120 : 127);
        e_arrive(sb + BARS + 8 * (B_WCH + at));
        if (w < cnt) {
            const uint32_t dst = sb + wst_off(i0 + w) + (lane >> 2) * 512 + (lane & 4) * 16 + ((q ^ cb) & 3) * 16;
#pragma unroll
            for (int j = 0; j < 4; j++)
#pragma unroll
                for (int e = 0; e < 2; e++)
                    asm volatile("st.shared.v4.u32 [%0], {%1,%2,%3,%4};" :: "r"((dst ^ (e * 64)) + j * 128),
                                 "r"(pack2(acc[4 * j + e], acc[16 + 4 * j + e])), "r"(pack2(acc[4 * j + 2 + e], acc[16 + 4 * j + 2 + e])),
                                 "r"(pack2(acc[32 + 4 * j + e], acc[48 + 4 * j + e])), "r"(pack2(acc[32 + 4 * j + 2 + e], acc[48 + 4 * j + 2 + e])) : "memory");
            fence_async_smem();
            e_arrive(sb + BARS + 8 * (B_WRD + i0 + w));
        }
    }
}

__device__ __forceinline__ void task_p1(int wg, int pair, uint32_t sb) {
    const int tid = threadIdx.x & 127, w = tid >> 5, lane = tid & 31;
    const uint32_t buf = sb + wg * 51200, bars = sb + BARS;
    uint32_t fr[5][10][2];
    float A[40], d[20];
    zero(A);
    {
        const Desc dA = mkdesc(buf, 3584, 512, 2), dB = mkdesc(sb + C1, 128, 256, 0);
        auto issue = [&](int g, float (&d)[40]) {
            mbar_wait(bars + 8 * (B_XF + wg * 5 + g));
            wg_fence();
            wgmma_ss_n80_z(d, dA + (uint32_t)(g * 8704 >> 4), dB);
#pragma unroll
            for (int j = 1; j < 5; j++) wgmma_ss_n80_a(d, dA + (uint32_t)((g * 8704 + j * 1024) >> 4), dB + (uint32_t)(j * 2560 >> 4));
            wg_commit();
        };
        auto pack = [&](int g, float (&d)[40]) {
            reg_fence(d);
#pragma unroll
            for (int f = 0; f < 10; f++) {
                fr[g][f][0] = pack2(d[4 * f], d[4 * f + 1]);
                fr[g][f][1] = pack2(d[4 * f + 2], d[4 * f + 3]);
            }
        };
        mbar_wait(bars + 8 * B_CF1);
#pragma unroll
        for (int g = 0; g < 4; g++) { issue(g, A); if (g == 0) PROFW(8 + wg * 8 + 1); wg_wait<0>(); pack(g, A); }
        zero(d);
        mbar_wait(bars + 8 * (B_XF + wg * 5 + 4));
#pragma unroll
        for (int h = 0; h < 2; h++) {
            wg_fence();
            wgmma_ss_n40_z(d, dA + (uint32_t)(4 * 8704 >> 4), dB + (uint32_t)(h * 1280 >> 4));
#pragma unroll
            for (int j = 1; j < 5; j++) wgmma_ss_n40_a(d, dA + (uint32_t)((4 * 8704 + j * 1024) >> 4), dB + (uint32_t)((j * 2560 + h * 1280) >> 4));
            wg_commit(); wg_wait<0>(); reg_fence(d);
#pragma unroll
            for (int f = 0; f < 5; f++) { fr[4][5 * h + f][0] = pack2(d[4 * f], d[4 * f + 1]); fr[4][5 * h + f][1] = pack2(d[4 * f + 2], d[4 * f + 3]); }
        }
    }
    bb_break(sb);
    wg_bar(1 + wg);
    PROFW(8 + wg * 8 + 2);
    {
        const Desc dB = mkdesc(sb + C1 + 12800, 128, 256, 0);
        const int i = lane & 7, mi = lane >> 3, th = w >> 1, tz = (2 * pair + th) & 3;
        const uint32_t s0 = buf + (i >> 1) * 128 + (i & 1) * 64 + (((2 * (w & 1) + (mi & 1)) ^ tz ^ (i >> 1)) << 4);
        const uint32_t sA = s0 + th * 2048 + (mi >> 1) * 512, sB = s0 + th * 2048 + (mi >> 1) * 2560, sC = s0 + th * 1024 + (mi >> 1) * 512;
        auto issue = [&](int f, float (&d)[20]) {
            wg_fence();
            wgmma_rs_n40_z(d, fr[0][f][0], fr[0][f][1], fr[1][f][0], fr[1][f][1], dB);
            wgmma_rs_n40_a(d, fr[2][f][0], fr[2][f][1], fr[3][f][0], fr[3][f][1], dB + (uint32_t)(1280 >> 4));
            wgmma_rs_n40_a(d, fr[4][f % 5][0], fr[4][f % 5][1], fr[4][f % 5 + 5][0], fr[4][f % 5 + 5][1], dB + (uint32_t)((2560 + (f / 5) * 1280) >> 4));
            wg_commit();
        };
#pragma unroll
        for (int f = 0; f < 10; f++) {
                        issue(f, d); wg_wait<0>(); reg_fence(d);
            const int Q = 5 * f;
            stm4(((Q & 3) == 3 ? sB : sA) + quad_off(Q), pack2(d[0], d[1]), pack2(d[2], d[3]), pack2(d[4], d[5]), pack2(d[6], d[7]));
            stm2(sA + quad_off(Q + 2), pack2(d[8], d[9]), pack2(d[10], d[11]));
            stm4((f == 9 ? sC : ((Q + 3) & 3) == 3 ? sB : sA) + quad_off(Q + 3), pack2(d[12], d[13]), pack2(d[14], d[15]), pack2(d[16], d[17]), pack2(d[18], d[19]));
            if (f & 1) { fence_async_smem(); e_arrive(bars + 8 * (B_RDY + wg * 5 + (f >> 1))); }
        }
    }
}

__device__ __forceinline__ void task_p2(int wg, int rk, uint32_t sb) {
    const int tid = threadIdx.x & 127, w = tid >> 5, lane = tid & 31;
    const uint32_t bars = sb + BARS;
    const int phi0 = 3 * rk, phiE = extra_phi(rk), mE = extra_mask(rk);
    uint4 wA[6], wB[6], wC[6], wE[6];
    auto ldw = [&](uint4 (&a)[6], int j, int phi) {
        const int pc = 3 * j + wg;
        const uint32_t p = sb + wslot(pc) + (lane & 3) * 512 + w * 128 + (((lane >> 2) ^ phi) & 1) * 64 + (((lane >> 3) ^ lane) & 3) * 16 + (phi & 1) * 8;
        mbar_wait(bars + 8 * (B_WL + pc));
#pragma unroll
        for (int s = 0; s < 6; s++) {
            asm volatile("ld.shared.v2.u32 {%0, %1}, [%2];" : "=r"(a[s].x), "=r"(a[s].y) : "r"(p + s * 2048) : "memory");
            asm volatile("ld.shared.v2.u32 {%0, %1}, [%2];" : "=r"(a[s].z), "=r"(a[s].w) : "r"((p ^ 8) + s * 2048) : "memory");
        }
        uint32_t dep = 0;
#pragma unroll
        for (int s = 0; s < 6; s++) dep |= a[s].x ^ a[s].z;
        if (__any_sync(0xffffffffu, dep == 0x7fc17fc1u)) __nanosleep(0);
        e_arrive(bars + 8 * (B_WE + pc));
    };
    ldw(wA, 0, phi0); ldw(wB, 1, phi0 + 1);
    ldw(wC, 2, phi0 + 2);
    PROFW(8 + wg * 8 + 4);
    mbar_wait(bars + 8 * (B_SIG + SIG_P1 + 1));
    const int i = lane & 7, mi = lane >> 3;
    const uint32_t soff = sb + S1 + wg * 4096 + mi * 512 + (i >> 1) * 128 + (i & 1) * 64;
    const int xo = w ^ (i >> 1);
    float d[32];
    zero(d);
    int n = 0;
    auto unit = [&](const uint4 (&a)[6], int z) {
        const Desc d0 = mkdesc(sb + xslot(n) + ((z >> 1) << 5), 16, 512, 2), d1 = d0 ^ 2u;
        const int m = 3 * n + wg;
        mbar_wait(bars + 8 * (B_RF + n));
        if (m >= TOKD) mbar_wait(bars + 8 * (B_TOK + m - TOKD));
        if (TOKM == 4) e_arrive(bars + 8 * (B_TOK + m));
        wg_fence();
        wgmma_rs_n64_z(d, a[0].x, a[0].y, a[0].z, a[0].w, d0);
        if (TOKM == 1) wg_commit();
        wgmma_rs_n64_a(d, a[1].x, a[1].y, a[1].z, a[1].w, d1);
        if (TOKM == 2) wg_commit();
        if (TOKM == 5) e_arrive(bars + 8 * (B_TOK + m));
#pragma unroll
        for (int c = 1; c < 3; c++) {
            wgmma_rs_n64_a(d, a[2 * c].x, a[2 * c].y, a[2 * c].z, a[2 * c].w, d0 + (uint32_t)(c * 4096 >> 4));
            wgmma_rs_n64_a(d, a[2 * c + 1].x, a[2 * c + 1].y, a[2 * c + 1].z, a[2 * c + 1].w, d1 + (uint32_t)(c * 4096 >> 4));
            if (TOKM == 6 && c == 1) e_arrive(bars + 8 * (B_TOK + m));
        }
        wg_commit();
        if (TOKM == 1 || TOKM == 2) wg_wait<1>();
        if (TOKM && TOKM < 4) e_arrive(bars + 8 * (B_TOK + m));
        if (n >= 4) mbar_wait(bars + 8 * (B_SFREE + m - 12));
        wg_wait<0>();
        reg_fence(d);
        if (!TOKM) e_arrive(bars + 8 * (B_TOK + m));
        if (n < 6) e_arrive(bars + 8 * (B_RE + n));
        uint32_t p[8];
#pragma unroll
        for (int j = 0; j < 8; j++) p[j] = pack2(d[4 * j] - d[4 * j + 3], d[4 * j + 2] + d[4 * j + 1]);
        const uint32_t a0 = soff + (n & 3) * 12288 + ((xo ^ z) << 4);
        stm4(a0, p[0], p[1], p[2], p[3]);
        stm4(a0 + 2048, p[4], p[5], p[6], p[7]);
        fence_async_smem();
        e_arrive(bars + 8 * (B_RDY + R_P2 + m));
        n++;
    };
    const int zA = phi0 & 3, zB = (phi0 + 1) & 3, zC = (phi0 + 2) & 3, zE = phiE & 3;
#pragma unroll 1
    for (int it = 0; it < 4; it++) {
        unit(wA, zA);
        PROFW(40 + wg * 8 + it * 2);
        unit(wB, zB);
        unit(wC, zC);
        if (it == 0 && mE) ldw(wE, 3, phiE);
        if (mE >> it & 1) unit(wE, zE);
        PROFW(40 + wg * 8 + it * 2 + 1);
    }
}

__device__ __forceinline__ void task_p3(int wg, int pair, uint32_t sb) {
    const int tid = threadIdx.x & 127, w = tid >> 5, lane = tid & 31;
    const uint32_t buf = sb + (wg ? 3 - wg : 0) * 51200, bars = sb + BARS;
    uint32_t fr[10][4][2];
    float acc[2][16];
    zero(acc[0]); zero(acc[1]);
    {
        const Desc dB = mkdesc(sb + C3, 128, 256, 0);
        const uint32_t a0 = (buf & 0x3FFFF) >> 4;
        auto dq = [&](int Q) {
            return Desc{a0 + (uint32_t)((quad_off(Q) >> 4) | ((Q < 48 ? 2048 : 1024) >> 4) << 16), (uint32_t)((quad_off(Q + 1) - quad_off(Q)) >> 4) | (2u << 30)};
        };
        auto issue = [&](int f) {
            if (!(f & 1)) mbar_wait(bars + 8 * (B_YF + wg * 5 + (f >> 1)));
            wg_fence();
            wgmma_ss_n32_z(acc[f & 1], dq(5 * f), dB);
            wgmma_ss_n32_a(acc[f & 1], dq(5 * f + 1), dB + (uint32_t)(1024 >> 4));
            wgmma_ss_n32_a(acc[f & 1], dq(5 * f + 3), dB + (uint32_t)(2048 >> 4));
            wg_commit();
        };
        mbar_wait(bars + 8 * B_CF3);
        issue(0);
        PROFW(64 + wg * 8 + 1);
#pragma unroll
        for (int f = 0; f < 10; f++) {
            if (f < 9) { issue(f + 1); wg_wait<1>(); } else wg_wait<0>();
            float (&d)[16] = acc[f & 1];
            reg_fence(d);
#pragma unroll
            for (int g = 0; g < 4; g++) { fr[f][g][0] = pack2(d[4 * g], d[4 * g + 1]); fr[f][g][1] = pack2(d[4 * g + 2], d[4 * g + 3]); }
        }
    }
    PROFW(64 + wg * 8 + 2);
    {
        const Desc dB = mkdesc(sb + C3 + 3072, 128, 256, 0);
        const int i = lane & 7, mi = lane >> 3, th = w >> 1, tz = (2 * pair + th) & 3;
        const int oct = (2 * (w & 1) + (mi & 1)) ^ tz;
        const uint32_t soff = buf + th * 3584 + (mi >> 1) * 512 + i * 64 + ((oct ^ (i >> 1)) << 4);
        auto issue = [&](int t) {
            const int g = t < 6 ? 1 + (t >> 1) : 0;
            const uint32_t o = t < 6 ? (t & 1) * 1024 : 8960, st = t < 6 ? 1792 : 1024;
            wg_fence();
            wgmma_rs_n32_z(acc[t & 1], fr[0][g][0], fr[0][g][1], fr[1][g][0], fr[1][g][1], dB + (o >> 4));
#pragma unroll
            for (int s = 1; s < 5; s++) wgmma_rs_n32_a(acc[t & 1], fr[2 * s][g][0], fr[2 * s][g][1], fr[2 * s + 1][g][0], fr[2 * s + 1][g][1], dB + ((o + s * st) >> 4));
            wg_commit();
        };
        bb_break(sb);
        issue(0);
        wg_bar(1 + wg);
#pragma unroll
        for (int t = 0; t < 7; t++) {
            if (t < 6) { issue(t + 1); wg_wait<1>(); } else wg_wait<0>();
            float (&d)[16] = acc[t & 1];
            reg_fence(d);
            if (t < 6) {
                const uint32_t a = soff + (1 + (t >> 1)) * 7168 + (t & 1) * 2048;
                stm4(a, pack2(d[0], d[1]), pack2(d[2], d[3]), pack2(d[4], d[5]), pack2(d[6], d[7]));
                if (t & 1) stm2(a + 1024, pack2(d[8], d[9]), pack2(d[10], d[11]));
                else stm4(a + 1024, pack2(d[8], d[9]), pack2(d[10], d[11]), pack2(d[12], d[13]), pack2(d[14], d[15]));
            } else {
                const int row = th * 14 + 4 * (mi >> 1) + (i >> 1);
                const uint32_t a = buf + row * 128 + (i & 1) * 64 + ((oct ^ (row & 3)) << 4);
                stm4(a, pack2(d[0], d[1]), pack2(d[2], d[3]), pack2(d[4], d[5]), pack2(d[6], d[7]));
                stm4((lane & 20) == 20 ? buf + 4096 + lane * 16 : a + 1024, pack2(d[8], d[9]), pack2(d[10], d[11]), pack2(d[12], d[13]), pack2(d[14], d[15]));
            }
            if ((t & 1) || t == 6) { fence_async_smem(); e_arrive(bars + 8 * (B_RDY + R_P3 + wg * 4 + (t >> 1))); }
        }
    }
}

__device__ __forceinline__ void load_x(int cls, int rk, int u, uint32_t sb, const Maps& mp) {
    const int id = u * NH + rk, pl = id / 3, c0 = 32 * (id - 3 * pl), tp = cls * 4 + (pl >> 4), col = 14 * (pl & 15) - 8;
    const uint32_t bar = sb + BARS + 8 * (B_XF + u * 5), dst = sb + u * 51200;
    const int wrap = col < 0 ? 224 : 0;
    if (tp) {
#pragma unroll
        for (int g = 0; g < 5; g++) e_ld3(dst + g * 8704, &mp.x34, c0, col + 4 * g + (g < 2 ? wrap : 0), 28 * tp - 6, bar + 8 * g);
    } else {
#pragma unroll
        for (int g = 0; g < 5; g++) {
            e_ld3(dst + g * 8704, &mp.x6, c0, col + 4 * g + (g < 2 ? wrap : 0), 218, bar + 8 * g);
            e_ld3(dst + g * 8704 + 1536, &mp.x28, c0, col + 4 * g + (g < 2 ? wrap : 0), 0, bar + 8 * g);
        }
    }
}

__device__ __forceinline__ void load_x_box(int cls, int rk, int u, int g, uint32_t sb, const Maps& mp) {
    const int id = u * NH + rk, pl = id / 3, c0 = 32 * (id - 3 * pl), tp = cls * 4 + (pl >> 4), col = 14 * (pl & 15) - 8 + 4 * g;
    e_ld3(sb + u * 51200 + g * 8704, &mp.x34, c0, col < 0 ? col + 224 : col, 28 * tp - 6, sb + BARS + 8 * (B_XF + u * 5 + g));
}

__device__ __forceinline__ void load_first(uint32_t sb, const Maps& mp, const Ptrs& pt) {
    const uint32_t bars = sb + BARS;
    const int k = blockIdx.x;
    PROF(122);
    if (k < 129) {
        const int cb0 = 14 * k / 25, cb1 = min((14 * k + 13) / 25, 71);
#pragma unroll 1
        for (int cb = cb0; cb <= cb1; cb++) {
            const int b = cb / 24, i0 = 16 * ((cb >> 2) - 6 * b) + 2 * (cb & 3);
            const uint32_t bar = bars + 8 * (B_WF + 2 * (cb - cb0));
            e_expect(bar, 14336);
            e_ld4(sb + WP + (cb - cb0) * 14336, &mp.w, 32 * b, i0, bar);
            e_ld4(sb + WP + (cb - cb0) * 14336 + 7168, &mp.w, 32 * b, i0 + 8, bar);
        }
    }
    e_expect(bars + 8 * B_CF1, 17920); e_g2s(sb + C1, pt.tab1, 17920, bars + 8 * B_CF1);
    if ((threadIdx.x & 31) < 15) asm volatile("mbarrier.arrive.expect_tx.shared::cta.b64 _, [%0], 8704;" :: "r"(bars + 8 * (B_XF + (threadIdx.x & 31))) : "memory");
    __syncwarp();
}

__device__ __forceinline__ uint32_t get_rel(uint32_t sb) {
    mbar_wait(sb + BARS + 8 * B_REL);
    uint32_t v; asm volatile("ld.shared.u32 %0, [%1];" : "=r"(v) : "r"(sb + REL) : "memory");
    return uni(v);
}

__device__ __forceinline__ void load_warp(int cls, int rk, uint32_t sb, const Maps& mp, const Ptrs& pt) {
    const uint32_t bars = sb + BARS;
    mbar_wait(bars + 8 * (B_SIG + SIG_P1));
    PROF(1);
    const uint32_t rel = get_rel(sb);
    const char* cnt = cls_cnt(pt.scr, cls);
    const int mE = extra_mask(rk);
    const int lpA = phi_line(3 * rk, rel), lpB = phi_line(3 * rk + 1, rel), lpC = phi_line(3 * rk + 2, rel), lpE = phi_line(extra_phi(rk), rel);
    if ((threadIdx.x & 31) < 14) asm volatile("mbarrier.arrive.expect_tx.shared::cta.b64 _, [%0], 12288;" :: "r"(bars + 8 * (B_RF + (threadIdx.x & 31))) : "memory");
    __syncwarp();
    int n = 0;
#pragma unroll 1
    for (int pg = 0; pg < 4; pg++) {
        const int l0 = slot_line(0, pg, cls), l1 = slot_line(1, pg, cls), l2 = slot_line(2, pg, cls);
        auto unit = [&](int lp) {
            const uint32_t bar = bars + 8 * (B_RF + n), dst = sb + xslot(n);
            mbar_wait(bars + 8 * (n >= 8 ? B_RE + n - 8 : n >= 4 ? B_SIG + SIG_P1 + (rk < 60 ? 2 : 1) : B_WE + ((0x7163 >> (4 * n)) & 15)));
            e_g2s(dst, pt.scr + (size_t)(lp ^ l0) * 128, 4096, bar);
            e_g2s(dst + 4096, pt.scr + (size_t)(lp ^ l1) * 128, 4096, bar);
            e_g2s(dst + 8192, pt.scr + (size_t)(lp ^ l2) * 128, 4096, bar);
            n++;
        };
        cnt_wait(cnt + (CNT_P1 + pg) * 128, 48);
        PROF(88 + pg);
        unit(lpA); unit(lpB); unit(lpC);
        if (mE >> pg & 1) unit(lpE);
        if (pg == 1) { mbar_wait(bars + 8 * B_P1D); e_expect(bars + 8 * B_CF3, 17152); e_g2s(sb + C3, pt.tab3, 17152, bars + 8 * B_CF3); }
    }
}

__device__ __forceinline__ int near_page(char* p, int rounds) {
#pragma unroll
    for (int e = 0; e < 4; e++) asm volatile("st.relaxed.gpu.global.v4.u32 [%0], {%1, %1, %1, %1};" :: "l"(p + (e >> 1) * 4096 + (e & 1) * 16), "r"(0) : "memory");
    int score = 0;
#pragma unroll 1
    for (int r = 0; r < rounds; r++) {
        uint32_t v0, v1, t0, t1;
        asm volatile("atom.relaxed.gpu.global.exch.b32 %0, [%1], 1;" : "=r"(v0) : "l"(p + (r & 1) * 4096) : "memory");
        asm volatile("atom.relaxed.gpu.global.exch.b32 %0, [%1], 1;" : "=r"(v1) : "l"(p + (~r & 1) * 4096) : "memory");
        asm volatile("{\n.reg .pred p;\nsetp.ne.u32 p, %1, 0xffffffff;\nmov.u32 %0, 0;\n@p mov.u32 %0, %%clock;\n}" : "=r"(t0) : "r"(v0) : "memory");
        asm volatile("{\n.reg .pred p;\nsetp.ne.u32 p, %1, 0xffffffff;\nmov.u32 %0, 0;\n@p mov.u32 %0, %%clock;\n}" : "=r"(t1) : "r"(v1) : "memory");
        const int gap = min((int)(t1 - t0), 160) - 80;
        score += (r & 1) ? gap : -gap;

    }
    return score > 0;
}

__device__ __forceinline__ uint32_t find_role(uint32_t sb, char* scr) {
    const int k = blockIdx.x;
    int c = near_page(scr + (slot_line(3, 3, 0) + phi_line(1 + (k >> 5), 0) + (k & 31)) * 128, PROBES);
    PROF(3);
    int r;
    asm volatile("atom.relaxed.gpu.global.add.u32 %0, [%1], 1;" : "=r"(r) : "l"(cls_cnt(scr, c) + CNT_RANK * 128) : "memory");
    if (r >= NH) { c ^= 1; r = NSM - 1 - r; }
    asm volatile("st.shared.u32 [%0], %1;" :: "r"(sb + REL + 4), "r"(c << 8 | r) : "memory");
    PROF(5);
    return c << 8 | r;
}
__device__ __forceinline__ void get_role(uint32_t sb, int& cls, int& rk) {
    mbar_wait(sb + BARS + 8 * B_ROLE);
    uint32_t v; asm volatile("ld.shared.u32 %0, [%1];" : "=r"(v) : "r"(sb + REL + 4) : "memory");
    v = uni(v); cls = v >> 8; rk = v & 255;
}

__device__ __forceinline__ void load3_warp(int cls, int rk, uint32_t sb, const Maps& mp, const Ptrs& pt) {
    const uint32_t bars = sb + BARS;
    uint32_t rel = 0;
    mbar_wait(bars + 8 * B_XF);
    PROF(107);
    rel = cnt_wait(pt.cnt + CNT_REL * 32, 12u << 16);
    asm volatile("st.shared.u32 [%0], %1;" :: "r"(sb + REL), "r"(rel) : "memory");
    __syncwarp();
    e_arrive(bars + 8 * B_REL);
    PROF(7);
    mbar_wait(bars + 8 * (B_SIG + SIG_W));
    cnt_wait(cls_cnt(pt.scr, cls) + CNT_W * 128, NSM);
    PROF(2);
    {
        const int np = rk >= 58 ? 12 : 9;
#pragma unroll 1
        for (int o = 0; o < np; o++) {
            const int pc = (0xba9785421630ull >> (4 * o)) & 15;
            if (o == 4) mbar_wait(bars + 8 * (B_SIG + SIG_P1));
            if (o >= 8) mbar_wait(bars + 8 * (B_WE + ((0x5240 >> (4 * (o - 8))) & 15)));
            e_expect(bars + 8 * (B_WL + pc), 12288);
            e_g2s(sb + wslot(pc), pt.wf + (pc < 9 ? 9 * rk + pc : 3 * extra_phi(rk) + pc - 9) * 12288, 12288, bars + 8 * (B_WL + pc));
        }
        if (np == 12) { mbar_wait(bars + 8 * (B_WE + 9)); mbar_wait(bars + 8 * (B_WE + 10)); mbar_wait(bars + 8 * (B_WE + 11)); }
    }
    mbar_wait(bars + 8 * (B_SIG + SIG_P2 + Y0AT));
    const int nu = rk < 60 ? 3 : 2;
#pragma unroll 1
    for (int u = 0; u < nu; u++) {
        const int id = u * NH + rk, pl = id / 3, chunk = id - 3 * pl;
        const int l0 = slot_line(chunk, pl >> 4, cls) + (pl & 15) * 2;
        const uint32_t buf = sb + (u ? 3 - u : 0) * 51200, bar = bars + 8 * (B_YF + u * 5);
#pragma unroll
        for (int j = 0; j < 5; j++) e_expect(bar + 8 * j, j == 4 ? 10240 : (j & 1) ? 8192 : 12288);
        if (u) mbar_wait(bars + 8 * (B_SIG + SIG_P2 + 3));
        cnt_wait(cls_cnt(pt.scr, cls) + (CNT_P2 + (pl >> 4)) * 128, NH);
        PROF(64 + u * 8);
        if (u == nu - 1) e_arrive(bars + 8 * B_FIN);
        const uint32_t r2 = uni(rel) << 5;
#pragma unroll
        for (int G = 0; G < 13; G++)
            e_ld5(buf + G * 4096, G < 12 ? &mp.f16 : &mp.f8, (l0 ^ ((r2 >> G) & 32)) + (G << 14), bar + 8 * ((2 * G) / 5));
    }
}

__device__ __forceinline__ void store_warp(uint32_t sb, const Maps& mp, const Ptrs& pt) {
    const uint32_t bars = sb + BARS;
    const int k = blockIdx.x;
    uint32_t pa = 0, pb = 0, qa = 0, qb = 0;
    auto arr2 = [&](uint32_t& a, uint32_t& b) { if (a) e_arrive(a); if (b) e_arrive(b); a = b = 0; };
    auto pre = [&](int idx) {
        const uint32_t bar = bars + 8 * idx;
        if (!mbar_test(bar)) { bulk_wait_read<0>(); arr2(qa, qb); arr2(pa, pb); mbar_wait(bar); }
    };
    auto post = [&](uint32_t fr) {
        bulk_commit(); bulk_wait_read<SWIN - 1>();
        if (SWIN == 3) { arr2(qa, qb); qa = pa; qb = pb; pb = 0; } else arr2(pa, pb);
        pa = fr;
    };
    auto after = [&](uint32_t a, uint32_t b) { if (a) pa = a; pb = b; };
    auto pace = [&](uint32_t) {};
    int cls, rk; get_role(sb, cls, rk);
    {
        int cb = 14 * k / 25, oc = 14 * k - 25 * cb;
        int g1 = 0;
#pragma unroll 1
        for (int i = 0; i < 14 && cb < 72; i++) {
            pre(B_WRD + i);
            if (PACE) pace(4 * PACE);
            e_st3(&mp.wst, sb + wst_off(i), 0, 8 * oc, cb);
            post(0);
            if (T1MASK >> i & 1) load_x_box(cls, rk, 1, g1++, sb, mp);
            if (++oc == 25) { oc = 0; cb++; }
        }
#pragma unroll 1
        for (; g1 < 5; g1++) load_x_box(cls, rk, 1, g1, sb, mp);
        if (X1AT && 14 * k + X1AT > 1800) e_arrive(bars + 8 * B_X1);
        after(bars + 8 * B_WFREE, bars + 8 * (B_SIG + SIG_W));
    }
    pre(B_REL);
    const uint32_t rel = get_rel(sb);
    const int nu = rk < 60 ? 3 : 2;
#pragma unroll 1
    for (int u = 0; u < nu; u++) {
        const int id = u * NH + rk, pl = id / 3, chunk = id - 3 * pl;
        const int l0 = slot_line(chunk, pl >> 4, cls) + (pl & 15) * 2;
        int j = B_RDY + u * 5;
        int g2 = 0;
        const int m2 = (u == 0 && nu == 3) ? T2MASK : 0;
#pragma unroll 1
        for (int G = 0; G < 13; G++) {
            if (0x4a5 >> G & 1) pre(j++);
            if (PACE) pace(G < 12 ? 4 * PACE : 2 * PACE);
            e_st5(G < 12 ? &mp.f16 : &mp.f8, sb + u * 51200 + G * 4096, (l0 ^ ((rel >> G) & 1) << 5) + (G << 14));
            post(0);
            if (m2 >> G & 1) load_x_box(cls, rk, 2, g2++, sb, mp);
        }
        after(0, bars + 8 * (B_SIG + SIG_P1 + u));
    }
    const int mE = extra_mask(rk);
    int n = 0;
#pragma unroll 1
    for (int pg = 0; pg < 4; pg++) {
        const int nj = 3 + (mE >> pg & 1);
        const int l0 = slot_line(0, pg, cls), l1 = slot_line(1, pg, cls), l2 = slot_line(2, pg, cls);
#pragma unroll 1
        for (int j = 0; j < nj; j++) {
            const int lp = phi_line(j == 3 ? extra_phi(rk) : 3 * rk + j, rel);
#pragma unroll
            for (int b = 0; b < 3; b++) {
                pre(B_RDY + R_P2 + n * 3 + b);
                if (PACE) pace(4 * PACE);
                e_s2g(pt.scr + (size_t)(lp ^ (b == 0 ? l0 : b == 1 ? l1 : l2)) * 128, sb + S1 + (n & 3) * 12288 + b * 4096, 4096);
                post(bars + 8 * (B_SFREE + n * 3 + b));
            }
            n++;
        }
        after(0, bars + 8 * (B_SIG + SIG_P2 + pg));
    }
#pragma unroll 1
    for (int u = 0; u < nu; u++) {
        const int id = u * NH + rk, pl = id / 3, chunk = id - 3 * pl, tp = cls * 4 + (pl >> 4), tx = pl & 15;
        const uint32_t buf = sb + (u ? 3 - u : 0) * 51200;
#pragma unroll
        for (int gg = 1; gg < 5; gg++) {
            pre(B_RDY + R_P3 + u * 4 + gg - 1);
            if (u < 2) pace(gg < 4 ? 7 * YPACE : 7 * YPACE / 2);
            if (gg < 4) e_st3(&mp.y4, buf + gg * 7168, 32 * chunk, 14 * tx - 4 + 4 * gg, 28 * tp);
            else e_st3(&mp.y2, buf, 32 * chunk, tx == 0 ? 222 : 14 * tx - 2, 28 * tp);
            post(0);
        }
    }
    bulk_wait_read<0>();
    PROF(113);
    prof_dump();
}

__device__ __forceinline__ void signal_warp(int cls, int rk, uint32_t sb, const Ptrs& pt) {
    const uint32_t bars = sb + BARS;
    char* cnt = cls_cnt(pt.scr, cls);
    if (threadIdx.x & 31) return;
#pragma unroll 1
    for (int c = 0; c < 8; c++) {
        if (c == SIG_P1 + 2 && rk >= 60) continue;
        char* ctr = cnt + (c == SIG_W ? CNT_W : c < SIG_P2 ? CNT_P1 + ((c - SIG_P1) * NH + rk) / 48 : CNT_P2 + c - SIG_P2) * 128;
        mbar_wait(bars + 8 * (B_SIG + c));
        PROF(32 + c);
        fence_async();
        asm volatile("red.relaxed.gpu.global.add.u32 [%0], 1;" :: "l"(ctr) : "memory");
        if (c == SIG_W) asm volatile("red.relaxed.gpu.global.add.u32 [%0], 1;" :: "l"((uintptr_t)ctr ^ 4096) : "memory");
        PROF(96 + c);
    }
    mbar_wait(bars + 8 * B_FIN);
    unsigned old;
    asm volatile("atom.add.relaxed.gpu.global.u32 %0, [%1], 1;" : "=r"(old) : "l"(pt.cnt + CNT_DONE * 32) : "memory");
    if (old == NSM - 1) {
#pragma unroll
        for (int c = 0; c < NCNT; c++) pt.cnt[c * 32] = 0;
#pragma unroll 1
        for (int c = 0; c < NCLS; c++) { *reinterpret_cast<unsigned*>(cnt + c * 128) = 0; *reinterpret_cast<unsigned*>(((uintptr_t)cnt ^ 4096) + c * 128) = 0; }
    }
}

__global__ void __launch_bounds__(512, 1) fftconv_kernel(const Ptrs pt, const __grid_constant__ Maps mp) {
    extern __shared__ __align__(1024) uint8_t smem[];
    const uint32_t sb = smem_u32(smem);
    const int tid = threadIdx.x, warp = uni(tid >> 5), wg = warp >> 2;
    int cls, rk;
    auto bar_init = [&](int i) {
        uint32_t c = 1;
        if (i == B_P1D || (i >= B_RE && i < B_RE + 14)) c = 12;
        else if ((i >= B_WCH && i < B_WL) || i >= B_TOK) c = 4;
        asm volatile("st.shared.v2.u32 [%0], {%1, %2};" :: "r"(sb + BARS + 8 * i), "r"((0x100000u - c) << 1), "r"((0x100000u - c) << 11) : "memory");
        fence_async_smem();
    };
    if (wg == 3) {
        asm volatile("setmaxnreg.dec.sync.aligned.u32 32;");
        if (warp == 12) {
            bar_init(tid & 31);
            __syncwarp();
            asm volatile("bar.arrive 4, 416;" ::: "memory");
            load_first(sb, mp, pt);
            PROF(106);
            asm volatile("bar.sync 5, 416;" ::: "memory");
            get_role(sb, cls, rk);
            load_warp(cls, rk, sb, mp, pt);
        } else if (warp == 13) {
            if ((tid & 31) < 8) asm volatile("prefetch.tensormap [%0];" :: "l"(reinterpret_cast<const CUtensorMap*>(&mp) + 1 + (tid & 31)) : "memory");
            __syncwarp();
            asm volatile("bar.sync 6, 416;" ::: "memory");
            store_warp(sb, mp, pt);
        } else if (warp == 14) {
            const int G = blockIdx.x - 119;
            int sel = 0;
            if (G >= 1 && (tid & 31) == 0) sel = near_page(pt.scr + ((size_t)G << 21) + slot_line(3, 3, 0) * 128, 2);
            __syncwarp();
            asm volatile("bar.sync 7, 416;" ::: "memory");
            get_role(sb, cls, rk);
            if (G >= 1 && (tid & 31) == 0) asm volatile("red.relaxed.gpu.global.add.u32 [%0], %1;" :: "l"(pt.cnt + CNT_REL * 32), "r"(0x10000u | (uint32_t)(sel ^ cls) << G) : "memory");
            __syncwarp();
            load3_warp(cls, rk, sb, mp, pt);
        } else {
            uint32_t role = 0;
            if ((tid & 31) == 0) role = find_role(sb, pt.scr);
            role = uni(role); cls = role >> 8; rk = role & 255;
            asm volatile("bar.sync 8, 416;" ::: "memory");
            load_x(cls, rk, 0, sb, mp);
            PROF(123);
            e_arrive(sb + BARS + 8 * B_ROLE);
            signal_warp(cls, rk, sb, pt);
        }
    } else {
        if (tid >= 32 && tid < NBAR) bar_init(tid);
        {
            const int r = tid % 40;
            asm volatile("st.shared.u32 [%0], %1;" :: "r"(sb + TBL + 4 * tid), "r"(cos_bits(r) | (cos_bits(r < 30 ? r + 10 : r - 30) << 16)) : "memory");
        }
        __syncwarp();
        asm volatile("bar.sync 4, 416;" ::: "memory");
        asm volatile("bar.arrive 5, 416;" ::: "memory");
        asm volatile("bar.arrive 6, 416;" ::: "memory");
        asm volatile("bar.arrive 7, 416;" ::: "memory");
        asm volatile("bar.arrive 8, 416;" ::: "memory");
        PROF(121);
        task_w(wg, blockIdx.x, sb);
        asm volatile("setmaxnreg.inc.sync.aligned.u32 160;");
        get_role(sb, cls, rk);
        const int id = wg * NH + rk;
        PROFW(8 + wg * 8);
        if (id < 192) task_p1(wg, id / 3, sb);
        e_arrive(sb + BARS + 8 * B_P1D);
        PROFW(8 + wg * 8 + 3);
        task_p2(wg, rk, sb);
        if (id < 192) task_p3(wg, id / 3, sb);
        PROFW(64 + wg * 8 + 3);
        prof_dump();
    }
}

typedef CUresult (*EncodeFn)(CUtensorMap*, CUtensorMapDataType, cuuint32_t, void*, const cuuint64_t*, const cuuint64_t*, const cuuint32_t*, const cuuint32_t*,
                             CUtensorMapInterleave, CUtensorMapSwizzle, CUtensorMapL2promotion, CUtensorMapFloatOOBfill);

static void encode3(EncodeFn fn, CUtensorMap* m, void* ptr, uint64_t d0, uint64_t d1, uint64_t d2, uint64_t s1, uint64_t s2,
                    uint32_t b0, uint32_t b1, uint32_t b2, CUtensorMapSwizzle sw) {
    cuuint64_t dims[3] = {d0, d1, d2}, strides[2] = {s1, s2};
    cuuint32_t box[3] = {b0, b1, b2}, es[3] = {1, 1, 1};
    fn(m, CU_TENSOR_MAP_DATA_TYPE_BFLOAT16, 3, ptr, dims, strides, box, es, CU_TENSOR_MAP_INTERLEAVE_NONE, sw,
       CU_TENSOR_MAP_L2_PROMOTION_NONE, CU_TENSOR_MAP_FLOAT_OOB_FILL_NONE);
}

extern "C" void kernel_launch(void* const* d_in, const int* in_sizes, int n_in, void* d_out, int out_size) {
    (void)in_sizes; (void)n_in; (void)out_size;
    void* fnp = nullptr; cudaDriverEntryPointQueryResult qr;
    cudaGetDriverEntryPoint("cuTensorMapEncodeTiled", &fnp, cudaEnableDefault, &qr);
    EncodeFn fn = (EncodeFn)fnp;
    void* xf = nullptr; cudaGetSymbolAddress(&xf, g_scr);
    xf = (void*)(((uintptr_t)xf + (1u << 21) - 1) & ~(uintptr_t)((1u << 21) - 1));
    void* wf = nullptr; cudaGetSymbolAddress(&wf, g_wf);
    Maps mp;
    Ptrs pt;
    pt.scr = (char*)xf; pt.wf = (const char*)wf;
    void* p = nullptr;
    cudaGetSymbolAddress(&p, TAB_P1); pt.tab1 = p;
    cudaGetSymbolAddress(&p, TAB_P3); pt.tab3 = p;
    cudaGetSymbolAddress(&p, g_cnt); pt.cnt = (unsigned*)p;
    {
        cuuint32_t b16[5] = {64, 4, 2, 2, 2}, b8[5] = {64, 4, 2, 1, 2}, es[5] = {1, 1, 1, 1, 1};
        cuuint64_t d[5] = {64, 4, 2, 2, 13 << 14}, st[4] = {16384, 262144, 1048576, 128};
        fn(&mp.f16, CU_TENSOR_MAP_DATA_TYPE_BFLOAT16, 5, xf, d, st, b16, es, CU_TENSOR_MAP_INTERLEAVE_NONE, CU_TENSOR_MAP_SWIZZLE_NONE, CU_TENSOR_MAP_L2_PROMOTION_NONE, CU_TENSOR_MAP_FLOAT_OOB_FILL_NONE);
        fn(&mp.f8, CU_TENSOR_MAP_DATA_TYPE_BFLOAT16, 5, xf, d, st, b8, es, CU_TENSOR_MAP_INTERLEAVE_NONE, CU_TENSOR_MAP_SWIZZLE_NONE, CU_TENSOR_MAP_L2_PROMOTION_NONE, CU_TENSOR_MAP_FLOAT_OOB_FILL_NONE);
    }
    encode3(fn, &mp.x6, d_in[0], 96, 224, 224, 192, 224 * 192, 32, 4, 6, CU_TENSOR_MAP_SWIZZLE_64B);
    encode3(fn, &mp.x34, d_in[0], 96, 224, 224, 192, 224 * 192, 32, 4, 34, CU_TENSOR_MAP_SWIZZLE_64B);
    encode3(fn, &mp.x28, d_in[0], 96, 224, 224, 192, 224 * 192, 32, 4, 28, CU_TENSOR_MAP_SWIZZLE_64B);
    {
        cuuint32_t box[4] = {32, 8, 7, 2}, es[4] = {1, 1, 1, 1};
        cuuint64_t d[4] = {96, 7, 7, 96}, st[3] = {18432, 7 * 18432, 192};
        fn(&mp.w, CU_TENSOR_MAP_DATA_TYPE_BFLOAT16, 4, d_in[1], d, st, box, es, CU_TENSOR_MAP_INTERLEAVE_NONE, CU_TENSOR_MAP_SWIZZLE_64B, CU_TENSOR_MAP_L2_PROMOTION_NONE, CU_TENSOR_MAP_FLOAT_OOB_FILL_NONE);
    }
    encode3(fn, &mp.wst, wf, 256, 200, 72, 36864, 512, 256, 8, 1, CU_TENSOR_MAP_SWIZZLE_NONE);
    encode3(fn, &mp.y4, d_out, 96, 224, 224, 192, 224 * 192, 32, 4, 28, CU_TENSOR_MAP_SWIZZLE_64B);
    encode3(fn, &mp.y2, d_out, 96, 224, 224, 192, 224 * 192, 32, 2, 28, CU_TENSOR_MAP_SWIZZLE_64B);
    constexpr int SMEM_LAUNCH = SMEM_BYTES;
    cudaFuncSetAttribute(fftconv_kernel, cudaFuncAttributeMaxDynamicSharedMemorySize, SMEM_LAUNCH);
    fftconv_kernel<<<NSM, 512, SMEM_LAUNCH>>>(pt, mp);
}
```

```cpp
#include <cuda_runtime.h>
#include <cuda_bf16.h>
#include <cuda.h>
#include <stdint.h>

__device__ __align__(128) const uint32_t TAB_P1[4480] = {
0x3e75,0,0x3e72,0,0x8000,0,0xbd19,0,0x3e750000,0,0x3e720000,0,0x80000000,0,0xbd190000,0,
0,0x3e75,0,0x3e72,0,0x8000,0,0xbd19,0,0x3e750000,0,0x3e720000,0,0x80000000,0,0xbd190000,
0x3e69,0,0x3e5a,0,0xbd97,0,0xbdde,0,0x3e690000,0,0x3e5a0000,0,0xbd970000,0,0xbdde0000,0,
0,0x3e69,0,0x3e5a,0,0xbd97,0,0xbdde,0,0x3e690000,0,0x3e5a0000,0,0xbd970000,0,0xbdde0000,
0x3e75,0,0x3e5a,0,0x8000,0,0xbdde,0,0x3e750000,0,0x3e5a0000,0,0x80000000,0,0xbdde0000,0,
0,0x3e75,0,0x3e5a,0,0x8000,0,0xbdde,0,0x3e750000,0,0x3e5a0000,0,0x80000000,0,0xbdde0000,
0x3e10,0,0x3d19,0,0xbe46,0,0xbe72,0,0x3e100000,0,0x3d190000,0,0xbe460000,0,0xbe720000,0,
0,0x3e10,0,0x3d19,0,0xbe46,0,0xbe72,0,0x3e100000,0,0x3d190000,0,0xbe460000,0,0xbe720000,
0x3e75,0,0x3e2d,0,0x8000,0,0xbe2d,0,0x3e750000,0,0x3e2d0000,0,0x80000000,0,0xbe2d0000,0,
0,0x3e75,0,0x3e2d,0,0x8000,0,0xbe2d,0,0x3e750000,0,0x3e2d0000,0,0x80000000,0,0xbe2d0000,
0,0,0xbe2d,0,0xbe75,0,0xbe2d,0,0,0,0xbe2d0000,0,0xbe750000,0,0xbe2d0000,0,
0,0,0,0xbe2d,0,0xbe75,0,0xbe2d,0,0,0,0xbe2d0000,0,0xbe750000,0,0xbe2d0000,
0x3e75,0,0x3dde,0,0x8000,0,0xbe5a,0,0x3e750000,0,0x3dde0000,0,0x80000000,0,0xbe5a0000,0,
0,0x3e75,0,0x3dde,0,0x8000,0,0xbe5a,0,0x3e750000,0,0x3dde0000,0,0x80000000,0,0xbe5a0000,
0xbe10,0,0xbe72,0,0xbe46,0,0x3d19,0,0xbe100000,0,0xbe720000,0,0xbe460000,0,0x3d190000,0,
0,0xbe10,0,0xbe72,0,0xbe46,0,0x3d19,0,0xbe100000,0,0xbe720000,0,0xbe460000,0,0x3d190000,
0x3e75,0,0x3d19,0,0x8000,0,0xbe72,0,0x3e750000,0,0x3d190000,0,0x80000000,0,0xbe720000,0,
0,0x3e75,0,0x3d19,0,0x8000,0,0xbe72,0,0x3e750000,0,0x3d190000,0,0x80000000,0,0xbe720000,
0xbe69,0,0xbdde,0,0xbd97,0,0x3e5a,0,0xbe690000,0,0xbdde0000,0,0xbd970000,0,0x3e5a0000,0,
0,0xbe69,0,0xbdde,0,0xbd97,0,0x3e5a,0,0xbe690000,0,0xbdde0000,0,0xbd970000,0,0x3e5a0000,
0x3e75,0,0xbd19,0,0x8000,0,0xbe72,0,0x3e750000,0,0xbd190000,0,0x80000000,0,0xbe720000,0,
0,0x3e75,0,0xbd19,0,0x8000,0,0xbe72,0,0x3e750000,0,0xbd190000,0,0x80000000,0,0xbe720000,
0xbe69,0,0x3dde,0,0x3d97,0,0x3e5a,0,0xbe690000,0,0x3dde0000,0,0x3d970000,0,0x3e5a0000,0,
0,0xbe69,0,0x3dde,0,0x3d97,0,0x3e5a,0,0xbe690000,0,0x3dde0000,0,0x3d970000,0,0x3e5a0000,
0x3e75,0,0xbdde,0,0x8000,0,0xbe5a,0,0x3e750000,0,0xbdde0000,0,0x80000000,0,0xbe5a0000,0,
0,0x3e75,0,0xbdde,0,0x8000,0,0xbe5a,0,0x3e750000,0,0xbdde0000,0,0x80000000,0,0xbe5a0000,
0xbe10,0,0x3e72,0,0x3e46,0,0x3d19,0,0xbe100000,0,0x3e720000,0,0x3e460000,0,0x3d190000,0,
0,0xbe10,0,0x3e72,0,0x3e46,0,0x3d19,0,0xbe100000,0,0x3e720000,0,0x3e460000,0,0x3d190000,
0x3e75,0,0xbe2d,0,0x8000,0,0xbe2d,0,0x3e750000,0,0xbe2d0000,0,0x80000000,0,0xbe2d0000,0,
0,0x3e75,0,0xbe2d,0,0x8000,0,0xbe2d,0,0x3e750000,0,0xbe2d0000,0,0x80000000,0,0xbe2d0000,
0,0,0x3e2d,0,0x3e75,0,0xbe2d,0,0,0,0x3e2d0000,0,0x3e750000,0,0xbe2d0000,0,
0,0,0,0x3e2d,0,0x3e75,0,0xbe2d,0,0,0,0x3e2d0000,0,0x3e750000,0,0xbe2d0000,
0x3e75,0,0xbe5a,0,0x8000,0,0xbdde,0,0x3e750000,0,0xbe5a0000,0,0x80000000,0,0xbdde0000,0,
0,0x3e75,0,0xbe5a,0,0x8000,0,0xbdde,0,0x3e750000,0,0xbe5a0000,0,0x80000000,0,0xbdde0000,
0x3e10,0,0xbd19,0,0x3e46,0,0xbe72,0,0x3e100000,0,0xbd190000,0,0x3e460000,0,0xbe720000,0,
0,0x3e10,0,0xbd19,0,0x3e46,0,0xbe72,0,0x3e100000,0,0xbd190000,0,0x3e460000,0,0xbe720000,
0x3e75,0,0xbe72,0,0x8000,0,0xbd19,0,0x3e750000,0,0xbe720000,0,0x80000000,0,0xbd190000,0,
0,0x3e75,0,0xbe72,0,0x8000,0,0xbd19,0,0x3e750000,0,0xbe720000,0,0x80000000,0,0xbd190000,
0x3e69,0,0xbe5a,0,0x3d97,0,0xbdde,0,0x3e690000,0,0xbe5a0000,0,0x3d970000,0,0xbdde0000,0,
0,0x3e69,0,0xbe5a,0,0x3d97,0,0xbdde,0,0x3e690000,0,0xbe5a0000,0,0x3d970000,0,0xbdde0000,
0x3e46,0,0x3e2d,0,0xbe10,0,0xbe2d,0,0x3e460000,0,0x3e2d0000,0,0xbe100000,0,0xbe2d0000,0,
0,0x3e46,0,0x3e2d,0,0xbe10,0,0xbe2d,0,0x3e460000,0,0x3e2d0000,0,0xbe100000,0,0xbe2d0000,
0x3e10,0,0x3dde,0,0xbe46,0,0xbe5a,0,0x3e100000,0,0x3dde0000,0,0xbe460000,0,0xbe5a0000,0,
0,0x3e10,0,0x3dde,0,0xbe46,0,0xbe5a,0,0x3e100000,0,0x3dde0000,0,0xbe460000,0,0xbe5a0000,
0xbd97,0,0xbe2d,0,0xbe69,0,0xbe2d,0,0xbd970000,0,0xbe2d0000,0,0xbe690000,0,0xbe2d0000,0,
0,0xbd97,0,0xbe2d,0,0xbe69,0,0xbe2d,0,0xbd970000,0,0xbe2d0000,0,0xbe690000,0,0xbe2d0000,
0xbe69,0,0xbe72,0,0xbd97,0,0x3d19,0,0xbe690000,0,0xbe720000,0,0xbd970000,0,0x3d190000,0,
0,0xbe69,0,0xbe72,0,0xbd97,0,0x3d19,0,0xbe690000,0,0xbe720000,0,0xbd970000,0,0x3d190000,
0xbe75,0,0xbe2d,0,0x8000,0,0x3e2d,0,0xbe750000,0,0xbe2d0000,0,0x80000000,0,0x3e2d0000,0,
0,0xbe75,0,0xbe2d,0,0x8000,0,0x3e2d,0,0xbe750000,0,0xbe2d0000,0,0x80000000,0,0x3e2d0000,
0,0,0x3e2d,0,0x3e75,0,0x3e2d,0,0,0,0x3e2d0000,0,0x3e750000,0,0x3e2d0000,0,
0,0,0,0x3e2d,0,0x3e75,0,0x3e2d,0,0,0,0x3e2d0000,0,0x3e750000,0,0x3e2d0000,
0xbd97,0,0x3e2d,0,0x3e69,0,0x3e2d,0,0xbd970000,0,0x3e2d0000,0,0x3e690000,0,0x3e2d0000,0,
0,0xbd97,0,0x3e2d,0,0x3e69,0,0x3e2d,0,0xbd970000,0,0x3e2d0000,0,0x3e690000,0,0x3e2d0000,
0x3e69,0,0x3d19,0,0xbd97,0,0xbe72,0,0x3e690000,0,0x3d190000,0,0xbd970000,0,0xbe720000,0,
0,0x3e69,0,0x3d19,0,0xbd97,0,0xbe72,0,0x3e690000,0,0x3d190000,0,0xbd970000,0,0xbe720000,
0x3e46,0,0x3e2d,0,0x3e10,0,0xbe2d,0,0x3e460000,0,0x3e2d0000,0,0x3e100000,0,0xbe2d0000,0,
0,0x3e46,0,0x3e2d,0,0x3e10,0,0xbe2d,0,0x3e460000,0,0x3e2d0000,0,0x3e100000,0,0xbe2d0000,
0xbe10,0,0xbe5a,0,0xbe46,0,0x3dde,0,0xbe100000,0,0xbe5a0000,0,0xbe460000,0,0x3dde0000,0,
0,0xbe10,0,0xbe5a,0,0xbe46,0,0x3dde,0,0xbe100000,0,0xbe5a0000,0,0xbe460000,0,0x3dde0000,
0x3e46,0,0xbe2d,0,0xbe10,0,0xbe2d,0,0x3e460000,0,0xbe2d0000,0,0xbe100000,0,0xbe2d0000,0,
0,0x3e46,0,0xbe2d,0,0xbe10,0,0xbe2d,0,0x3e460000,0,0xbe2d0000,0,0xbe100000,0,0xbe2d0000,
0xbe10,0,0x3e5a,0,0x3e46,0,0x3dde,0,0xbe100000,0,0x3e5a0000,0,0x3e460000,0,0x3dde0000,0,
0,0xbe10,0,0x3e5a,0,0x3e46,0,0x3dde,0,0xbe100000,0,0x3e5a0000,0,0x3e460000,0,0x3dde0000,
0xbd97,0,0xbe2d,0,0xbe69,0,0x3e2d,0,0xbd970000,0,0xbe2d0000,0,0xbe690000,0,0x3e2d0000,0,
0,0xbd97,0,0xbe2d,0,0xbe69,0,0x3e2d,0,0xbd970000,0,0xbe2d0000,0,0xbe690000,0,0x3e2d0000,
0x3e69,0,0xbd19,0,0x3d97,0,0xbe72,0,0x3e690000,0,0xbd190000,0,0x3d970000,0,0xbe720000,0,
0,0x3e69,0,0xbd19,0,0x3d97,0,0xbe72,0,0x3e690000,0,0xbd190000,0,0x3d970000,0,0xbe720000,
0xbe75,0,0x3e2d,0,0x8000,0,0x3e2d,0,0xbe750000,0,0x3e2d0000,0,0x80000000,0,0x3e2d0000,0,
0,0xbe75,0,0x3e2d,0,0x8000,0,0x3e2d,0,0xbe750000,0,0x3e2d0000,0,0x80000000,0,0x3e2d0000,
0,0,0xbe2d,0,0xbe75,0,0x3e2d,0,0,0,0xbe2d0000,0,0xbe750000,0,0x3e2d0000,0,
0,0,0,0xbe2d,0,0xbe75,0,0x3e2d,0,0,0,0xbe2d0000,0,0xbe750000,0,0x3e2d0000,
0xbd97,0,0x3e2d,0,0x3e69,0,0xbe2d,0,0xbd970000,0,0x3e2d0000,0,0x3e690000,0,0xbe2d0000,0,
0,0xbd97,0,0x3e2d,0,0x3e69,0,0xbe2d,0,0xbd970000,0,0x3e2d0000,0,0x3e690000,0,0xbe2d0000,
0xbe69,0,0x3e72,0,0x3d97,0,0x3d19,0,0xbe690000,0,0x3e720000,0,0x3d970000,0,0x3d190000,0,
0,0xbe69,0,0x3e72,0,0x3d97,0,0x3d19,0,0xbe690000,0,0x3e720000,0,0x3d970000,0,0x3d190000,
0x3e46,0,0xbe2d,0,0x3e10,0,0xbe2d,0,0x3e460000,0,0xbe2d0000,0,0x3e100000,0,0xbe2d0000,0,
0,0x3e46,0,0xbe2d,0,0x3e10,0,0xbe2d,0,0x3e460000,0,0xbe2d0000,0,0x3e100000,0,0xbe2d0000,
0x3e10,0,0xbdde,0,0x3e46,0,0xbe5a,0,0x3e100000,0,0xbdde0000,0,0x3e460000,0,0xbe5a0000,0,
0,0x3e10,0,0xbdde,0,0x3e46,0,0xbe5a,0,0x3e100000,0,0xbdde0000,0,0x3e460000,0,0xbe5a0000,
0x3d97,0,0x3d19,0,0xbe69,0,0xbe72,0,0x3d970000,0,0x3d190000,0,0xbe690000,0,0xbe720000,0,
0,0x3d97,0,0x3d19,0,0xbe69,0,0xbe72,0,0x3d970000,0,0x3d190000,0,0xbe690000,0,0xbe720000,
0,0,0xbd19,0,0xbe75,0,0xbe72,0,0,0,0xbd190000,0,0xbe750000,0,0xbe720000,0,
0,0,0,0xbd19,0,0xbe75,0,0xbe72,0,0,0,0xbd190000,0,0xbe750000,0,0xbe720000,
0xbe46,0,0xbdde,0,0x3e10,0,0x3e5a,0,0xbe460000,0,0xbdde0000,0,0x3e100000,0,0x3e5a0000,0,
0,0xbe46,0,0xbdde,0,0x3e10,0,0x3e5a,0,0xbe460000,0,0xbdde0000,0,0x3e100000,0,0x3e5a0000,
0,0,0x3dde,0,0x3e75,0,0x3e5a,0,0,0,0x3dde0000,0,0x3e750000,0,0x3e5a0000,0,
0,0,0,0x3dde,0,0x3e75,0,0x3e5a,0,0,0,0x3dde0000,0,0x3e750000,0,0x3e5a0000,
0x3e75,0,0x3e2d,0,0x8000,0,0xbe2d,0,0x3e750000,0,0x3e2d0000,0,0x80000000,0,0xbe2d0000,0,
0,0x3e75,0,0x3e2d,0,0x8000,0,0xbe2d,0,0x3e750000,0,0x3e2d0000,0,0x80000000,0,0xbe2d0000,
0,0,0xbe2d,0,0xbe75,0,0xbe2d,0,0,0,0xbe2d0000,0,0xbe750000,0,0xbe2d0000,0,
0,0,0,0xbe2d,0,0xbe75,0,0xbe2d,0,0,0,0xbe2d0000,0,0xbe750000,0,0xbe2d0000,
0xbe46,0,0xbe5a,0,0xbe10,0,0x3dde,0,0xbe460000,0,0xbe5a0000,0,0xbe100000,0,0x3dde0000,0,
0,0xbe46,0,0xbe5a,0,0xbe10,0,0x3dde,0,0xbe460000,0,0xbe5a0000,0,0xbe100000,0,0x3dde0000,
0,0,0x3e5a,0,0x3e75,0,0x3dde,0,0,0,0x3e5a0000,0,0x3e750000,0,0x3dde0000,0,
0,0,0,0x3e5a,0,0x3e75,0,0x3dde,0,0,0,0x3e5a0000,0,0x3e750000,0,0x3dde0000,
0x3d97,0,0x3e72,0,0x3e69,0,0xbd19,0,0x3d970000,0,0x3e720000,0,0x3e690000,0,0xbd190000,0,
0,0x3d97,0,0x3e72,0,0x3e69,0,0xbd19,0,0x3d970000,0,0x3e720000,0,0x3e690000,0,0xbd190000,
0,0,0xbe72,0,0xbe75,0,0xbd19,0,0,0,0xbe720000,0,0xbe750000,0,0xbd190000,0,
0,0,0,0xbe72,0,0xbe75,0,0xbd19,0,0,0,0xbe720000,0,0xbe750000,0,0xbd190000,
0x3d97,0,0xbe72,0,0xbe69,0,0xbd19,0,0x3d970000,0,0xbe720000,0,0xbe690000,0,0xbd190000,0,
0,0x3d97,0,0xbe72,0,0xbe69,0,0xbd19,0,0x3d970000,0,0xbe720000,0,0xbe690000,0,0xbd190000,
0,0,0x3e72,0,0x3e75,0,0xbd19,0,0,0,0x3e720000,0,0x3e750000,0,0xbd190000,0,
0,0,0,0x3e72,0,0x3e75,0,0xbd19,0,0,0,0x3e720000,0,0x3e750000,0,0xbd190000,
0xbe46,0,0x3e5a,0,0x3e10,0,0x3dde,0,0xbe460000,0,0x3e5a0000,0,0x3e100000,0,0x3dde0000,0,
0,0xbe46,0,0x3e5a,0,0x3e10,0,0x3dde,0,0xbe460000,0,0x3e5a0000,0,0x3e100000,0,0x3dde0000,
0,0,0xbe5a,0,0xbe75,0,0x3dde,0,0,0,0xbe5a0000,0,0xbe750000,0,0x3dde0000,0,
0,0,0,0xbe5a,0,0xbe75,0,0x3dde,0,0,0,0xbe5a0000,0,0xbe750000,0,0x3dde0000,
0x3e75,0,0xbe2d,0,0x8000,0,0xbe2d,0,0x3e750000,0,0xbe2d0000,0,0x80000000,0,0xbe2d0000,0,
0,0x3e75,0,0xbe2d,0,0x8000,0,0xbe2d,0,0x3e750000,0,0xbe2d0000,0,0x80000000,0,0xbe2d0000,
0,0,0x3e2d,0,0x3e75,0,0xbe2d,0,0,0,0x3e2d0000,0,0x3e750000,0,0xbe2d0000,0,
0,0,0,0x3e2d,0,0x3e75,0,0xbe2d,0,0,0,0x3e2d0000,0,0x3e750000,0,0xbe2d0000,
0xbe46,0,0x3dde,0,0xbe10,0,0x3e5a,0,0xbe460000,0,0x3dde0000,0,0xbe100000,0,0x3e5a0000,0,
0,0xbe46,0,0x3dde,0,0xbe10,0,0x3e5a,0,0xbe460000,0,0x3dde0000,0,0xbe100000,0,0x3e5a0000,
0,0,0xbdde,0,0xbe75,0,0x3e5a,0,0,0,0xbdde0000,0,0xbe750000,0,0x3e5a0000,0,
0,0,0,0xbdde,0,0xbe75,0,0x3e5a,0,0,0,0xbdde0000,0,0xbe750000,0,0x3e5a0000,
0x3d97,0,0xbd19,0,0x3e69,0,0xbe72,0,0x3d970000,0,0xbd190000,0,0x3e690000,0,0xbe720000,0,
0,0x3d97,0,0xbd19,0,0x3e69,0,0xbe72,0,0x3d970000,0,0xbd190000,0,0x3e690000,0,0xbe720000,
0,0,0x3d19,0,0x3e75,0,0xbe72,0,0,0,0x3d190000,0,0x3e750000,0,0xbe720000,0,
0,0,0,0x3d19,0,0x3e75,0,0xbe72,0,0,0,0x3d190000,0,0x3e750000,0,0xbe720000,
0xbd97,0,0xbdde,0,0xbe69,0,0xbe5a,0,0xbd970000,0,0xbdde0000,0,0xbe690000,0,0xbe5a0000,0,
0,0xbd97,0,0xbdde,0,0xbe69,0,0xbe5a,0,0xbd970000,0,0xbdde0000,0,0xbe690000,0,0xbe5a0000,
0xbe10,0,0xbe2d,0,0xbe46,0,0xbe2d,0,0xbe100000,0,0xbe2d0000,0,0xbe460000,0,0xbe2d0000,0,
0,0xbe10,0,0xbe2d,0,0xbe46,0,0xbe2d,0,0xbe100000,0,0xbe2d0000,0,0xbe460000,0,0xbe2d0000,
0x3e46,0,0x3e72,0,0x3e10,0,0x3d19,0,0x3e460000,0,0x3e720000,0,0x3e100000,0,0x3d190000,0,
0,0x3e46,0,0x3e72,0,0x3e10,0,0x3d19,0,0x3e460000,0,0x3e720000,0,0x3e100000,0,0x3d190000,
0x3e69,0,0x3e2d,0,0xbd97,0,0xbe2d,0,0x3e690000,0,0x3e2d0000,0,0xbd970000,0,0xbe2d0000,0,
0,0x3e69,0,0x3e2d,0,0xbd97,0,0xbe2d,0,0x3e690000,0,0x3e2d0000,0,0xbd970000,0,0xbe2d0000,
0xbe75,0,0xbe2d,0,0x8000,0,0x3e2d,0,0xbe750000,0,0xbe2d0000,0,0x80000000,0,0x3e2d0000,0,
0,0xbe75,0,0xbe2d,0,0x8000,0,0x3e2d,0,0xbe750000,0,0xbe2d0000,0,0x80000000,0,0x3e2d0000,
0,0,0x3e2d,0,0x3e75,0,0x3e2d,0,0,0,0x3e2d0000,0,0x3e750000,0,0x3e2d0000,0,
0,0,0,0x3e2d,0,0x3e75,0,0x3e2d,0,0,0,0x3e2d0000,0,0x3e750000,0,0x3e2d0000,
0x3e46,0,0xbd19,0,0xbe10,0,0xbe72,0,0x3e460000,0,0xbd190000,0,0xbe100000,0,0xbe720000,0,
0,0x3e46,0,0xbd19,0,0xbe10,0,0xbe72,0,0x3e460000,0,0xbd190000,0,0xbe100000,0,0xbe720000,
0xbe69,0,0xbe2d,0,0xbd97,0,0x3e2d,0,0xbe690000,0,0xbe2d0000,0,0xbd970000,0,0x3e2d0000,0,
0,0xbe69,0,0xbe2d,0,0xbd97,0,0x3e2d,0,0xbe690000,0,0xbe2d0000,0,0xbd970000,0,0x3e2d0000,
0xbd97,0,0x3e5a,0,0x3e69,0,0x3dde,0,0xbd970000,0,0x3e5a0000,0,0x3e690000,0,0x3dde0000,0,
0,0xbd97,0,0x3e5a,0,0x3e69,0,0x3dde,0,0xbd970000,0,0x3e5a0000,0,0x3e690000,0,0x3dde0000,
0x3e10,0,0xbe2d,0,0xbe46,0,0xbe2d,0,0x3e100000,0,0xbe2d0000,0,0xbe460000,0,0xbe2d0000,0,
0,0x3e10,0,0xbe2d,0,0xbe46,0,0xbe2d,0,0x3e100000,0,0xbe2d0000,0,0xbe460000,0,0xbe2d0000,
0xbd97,0,0xbe5a,0,0xbe69,0,0x3dde,0,0xbd970000,0,0xbe5a0000,0,0xbe690000,0,0x3dde0000,0,
0,0xbd97,0,0xbe5a,0,0xbe69,0,0x3dde,0,0xbd970000,0,0xbe5a0000,0,0xbe690000,0,0x3dde0000,
0x3e10,0,0x3e2d,0,0x3e46,0,0xbe2d,0,0x3e100000,0,0x3e2d0000,0,0x3e460000,0,0xbe2d0000,0,
0,0x3e10,0,0x3e2d,0,0x3e46,0,0xbe2d,0,0x3e100000,0,0x3e2d0000,0,0x3e460000,0,0xbe2d0000,
0x3e46,0,0x3d19,0,0x3e10,0,0xbe72,0,0x3e460000,0,0x3d190000,0,0x3e100000,0,0xbe720000,0,
0,0x3e46,0,0x3d19,0,0x3e10,0,0xbe72,0,0x3e460000,0,0x3d190000,0,0x3e100000,0,0xbe720000,
0xbe69,0,0x3e2d,0,0x3d97,0,0x3e2d,0,0xbe690000,0,0x3e2d0000,0,0x3d970000,0,0x3e2d0000,0,
0,0xbe69,0,0x3e2d,0,0x3d97,0,0x3e2d,0,0xbe690000,0,0x3e2d0000,0,0x3d970000,0,0x3e2d0000,
0xbe75,0,0x3e2d,0,0x8000,0,0x3e2d,0,0xbe750000,0,0x3e2d0000,0,0x80000000,0,0x3e2d0000,0,
0,0xbe75,0,0x3e2d,0,0x8000,0,0x3e2d,0,0xbe750000,0,0x3e2d0000,0,0x80000000,0,0x3e2d0000,
0,0,0xbe2d,0,0xbe75,0,0x3e2d,0,0,0,0xbe2d0000,0,0xbe750000,0,0x3e2d0000,0,
0,0,0,0xbe2d,0,0xbe75,0,0x3e2d,0,0,0,0xbe2d0000,0,0xbe750000,0,0x3e2d0000,
0x3e46,0,0xbe72,0,0xbe10,0,0x3d19,0,0x3e460000,0,0xbe720000,0,0xbe100000,0,0x3d190000,0,
0,0x3e46,0,0xbe72,0,0xbe10,0,0x3d19,0,0x3e460000,0,0xbe720000,0,0xbe100000,0,0x3d190000,
0x3e69,0,0xbe2d,0,0x3d97,0,0xbe2d,0,0x3e690000,0,0xbe2d0000,0,0x3d970000,0,0xbe2d0000,0,
0,0x3e69,0,0xbe2d,0,0x3d97,0,0xbe2d,0,0x3e690000,0,0xbe2d0000,0,0x3d970000,0,0xbe2d0000,
0xbd97,0,0x3dde,0,0x3e69,0,0xbe5a,0,0xbd970000,0,0x3dde0000,0,0x3e690000,0,0xbe5a0000,0,
0,0xbd97,0,0x3dde,0,0x3e69,0,0xbe5a,0,0xbd970000,0,0x3dde0000,0,0x3e690000,0,0xbe5a0000,
0xbe10,0,0x3e2d,0,0x3e46,0,0xbe2d,0,0xbe100000,0,0x3e2d0000,0,0x3e460000,0,0xbe2d0000,0,
0,0xbe10,0,0x3e2d,0,0x3e46,0,0xbe2d,0,0xbe100000,0,0x3e2d0000,0,0x3e460000,0,0xbe2d0000,
0xbe46,0,0xbe5a,0,0xbe10,0,0xbdde,0,0xbe460000,0,0xbe5a0000,0,0xbe100000,0,0xbdde0000,0,
0,0xbe46,0,0xbe5a,0,0xbe10,0,0xbdde,0,0xbe460000,0,0xbe5a0000,0,0xbe100000,0,0xbdde0000,
0xbe69,0,0xbe72,0,0xbd97,0,0xbd19,0,0xbe690000,0,0xbe720000,0,0xbd970000,0,0xbd190000,0,
0,0xbe69,0,0xbe72,0,0xbd97,0,0xbd19,0,0xbe690000,0,0xbe720000,0,0xbd970000,0,0xbd190000,
0x3d97,0,0xbd19,0,0xbe69,0,0xbe72,0,0x3d970000,0,0xbd190000,0,0xbe690000,0,0xbe720000,0,
0,0x3d97,0,0xbd19,0,0xbe69,0,0xbe72,0,0x3d970000,0,0xbd190000,0,0xbe690000,0,0xbe720000,
0xbe10,0,0xbe5a,0,0xbe46,0,0xbdde,0,0xbe100000,0,0xbe5a0000,0,0xbe460000,0,0xbdde0000,0,
0,0xbe10,0,0xbe5a,0,0xbe46,0,0xbdde,0,0xbe100000,0,0xbe5a0000,0,0xbe460000,0,0xbdde0000,
0x3e75,0,0x3e2d,0,0x8000,0,0xbe2d,0,0x3e750000,0,0x3e2d0000,0,0x80000000,0,0xbe2d0000,0,
0,0x3e75,0,0x3e2d,0,0x8000,0,0xbe2d,0,0x3e750000,0,0x3e2d0000,0,0x80000000,0,0xbe2d0000,
0,0,0xbe2d,0,0xbe75,0,0xbe2d,0,0,0,0xbe2d0000,0,0xbe750000,0,0xbe2d0000,0,
0,0,0,0xbe2d,0,0xbe75,0,0xbe2d,0,0,0,0xbe2d0000,0,0xbe750000,0,0xbe2d0000,
0x3d97,0,0x3e72,0,0x3e69,0,0x3d19,0,0x3d970000,0,0x3e720000,0,0x3e690000,0,0x3d190000,0,
0,0x3d97,0,0x3e72,0,0x3e69,0,0x3d19,0,0x3d970000,0,0x3e720000,0,0x3e690000,0,0x3d190000,
0x3e10,0,0xbdde,0,0xbe46,0,0xbe5a,0,0x3e100000,0,0xbdde0000,0,0xbe460000,0,0xbe5a0000,0,
0,0x3e10,0,0xbdde,0,0xbe46,0,0xbe5a,0,0x3e100000,0,0xbdde0000,0,0xbe460000,0,0xbe5a0000,
0xbe46,0,0x3dde,0,0x3e10,0,0x3e5a,0,0xbe460000,0,0x3dde0000,0,0x3e100000,0,0x3e5a0000,0,
0,0xbe46,0,0x3dde,0,0x3e10,0,0x3e5a,0,0xbe460000,0,0x3dde0000,0,0x3e100000,0,0x3e5a0000,
0x3e69,0,0xbd19,0,0xbd97,0,0xbe72,0,0x3e690000,0,0xbd190000,0,0xbd970000,0,0xbe720000,0,
0,0x3e69,0,0xbd19,0,0xbd97,0,0xbe72,0,0x3e690000,0,0xbd190000,0,0xbd970000,0,0xbe720000,
0xbe46,0,0xbdde,0,0xbe10,0,0x3e5a,0,0xbe460000,0,0xbdde0000,0,0xbe100000,0,0x3e5a0000,0,
0,0xbe46,0,0xbdde,0,0xbe10,0,0x3e5a,0,0xbe460000,0,0xbdde0000,0,0xbe100000,0,0x3e5a0000,
0x3e69,0,0x3d19,0,0x3d97,0,0xbe72,0,0x3e690000,0,0x3d190000,0,0x3d970000,0,0xbe720000,0,
0,0x3e69,0,0x3d19,0,0x3d97,0,0xbe72,0,0x3e690000,0,0x3d190000,0,0x3d970000,0,0xbe720000,
0x3d97,0,0xbe72,0,0xbe69,0,0x3d19,0,0x3d970000,0,0xbe720000,0,0xbe690000,0,0x3d190000,0,
0,0x3d97,0,0xbe72,0,0xbe69,0,0x3d19,0,0x3d970000,0,0xbe720000,0,0xbe690000,0,0x3d190000,
0x3e10,0,0x3dde,0,0x3e46,0,0xbe5a,0,0x3e100000,0,0x3dde0000,0,0x3e460000,0,0xbe5a0000,0,
0,0x3e10,0,0x3dde,0,0x3e46,0,0xbe5a,0,0x3e100000,0,0x3dde0000,0,0x3e460000,0,0xbe5a0000,
0x3e75,0,0xbe2d,0,0x8000,0,0xbe2d,0,0x3e750000,0,0xbe2d0000,0,0x80000000,0,0xbe2d0000,0,
0,0x3e75,0,0xbe2d,0,0x8000,0,0xbe2d,0,0x3e750000,0,0xbe2d0000,0,0x80000000,0,0xbe2d0000,
0,0,0x3e2d,0,0x3e75,0,0xbe2d,0,0,0,0x3e2d0000,0,0x3e750000,0,0xbe2d0000,0,
0,0,0,0x3e2d,0,0x3e75,0,0xbe2d,0,0,0,0x3e2d0000,0,0x3e750000,0,0xbe2d0000,
0x3d97,0,0x3d19,0,0x3e69,0,0xbe72,0,0x3d970000,0,0x3d190000,0,0x3e690000,0,0xbe720000,0,
0,0x3d97,0,0x3d19,0,0x3e69,0,0xbe72,0,0x3d970000,0,0x3d190000,0,0x3e690000,0,0xbe720000,
0xbe10,0,0x3e5a,0,0x3e46,0,0xbdde,0,0xbe100000,0,0x3e5a0000,0,0x3e460000,0,0xbdde0000,0,
0,0xbe10,0,0x3e5a,0,0x3e46,0,0xbdde,0,0xbe100000,0,0x3e5a0000,0,0x3e460000,0,0xbdde0000,
0xbe46,0,0x3e5a,0,0x3e10,0,0xbdde,0,0xbe460000,0,0x3e5a0000,0,0x3e100000,0,0xbdde0000,0,
0,0xbe46,0,0x3e5a,0,0x3e10,0,0xbdde,0,0xbe460000,0,0x3e5a0000,0,0x3e100000,0,0xbdde0000,
0xbe69,0,0x3e72,0,0x3d97,0,0xbd19,0,0xbe690000,0,0x3e720000,0,0x3d970000,0,0xbd190000,0,
0,0xbe69,0,0x3e72,0,0x3d97,0,0xbd19,0,0xbe690000,0,0x3e720000,0,0x3d970000,0,0xbd190000,
0x3eb7,0x3eb7,0x3eb7,0x3eb7,0x3eb78000,0x3eb78000,0x3eb78000,0x3eb78000,0x3eb7,0x3de23eae,0x3e573e94,0x3e943e57,0x3eb78000,0x3eaebde2,0x3e94be57,0x3e57be94,
0x3eb7,0x3e573e94,0x3eae3de2,0x3eaebde2,0x3eb78000,0x3e94be57,0x3de2beae,0xbde2beae,0x3eb7,0x3e943e57,0x3eaebde2,0x3de2beae,0x3eb78000,0x3e57be94,0xbde2beae,0xbeaebde2,
0x3eb7,0x3eb7,0x3eb7,0x3eb7,0x3eb78000,0x3eb78000,0x3eb78000,0x3eb78000,0x3eae3de2,0x3eb70000,0x3eaebde2,0x3e94be57,0x3de2beae,0xbeb7,0xbde2beae,0xbe57be94,
0x3e57be94,0xbeb7,0xbe57be94,0xbeaebde2,0xbe94be57,0xbeb78000,0xbe943e57,0xbde23eae,0xbe57be94,0xbeb70000,0xbe573e94,0x3de23eae,0xbe943e57,0x3eb7,0x3e943e57,0x3eaebde2,
0x3eb7,0x3eae3de2,0x3e57be94,0xbe57be94,0x3eb78000,0x3de2beae,0xbe94be57,0xbe943e57,0x3eb7,0x3eb70000,0xbeb7,0xbeb70000,0x3eb78000,0xbeb7,0xbeb78000,0x3eb7,
0x3eb7,0x3eaebde2,0xbe57be94,0xbe573e94,0x3eb78000,0xbde2beae,0xbe943e57,0x3e943e57,0x3eb7,0x3e94be57,0xbeaebde2,0x3de23eae,0x3eb78000,0xbe57be94,0xbde23eae,0x3eaebde2,
0xbeae3de2,0x3eb7,0x3eae3de2,0x3e57be94,0x3de23eae,0x3eb78000,0x3de2beae,0xbe94be57,0x3eb7,0x3eb70000,0xbeb7,0xbeb70000,0x3eb78000,0xbeb7,0xbeb78000,0x3eb7,
0x3eae3de2,0xbeb7,0xbeae3de2,0x3e573e94,0x3de2beae,0xbeb78000,0x3de23eae,0x3e94be57,0x3e57be94,0xbeb70000,0x3e573e94,0x3de2beae,0xbe94be57,0x3eb7,0x3e94be57,0xbeaebde2,
0x3eb7,0x3e57be94,0xbeae3de2,0x3eae3de2,0x3eb78000,0xbe94be57,0x3de23eae,0x3de2beae,0x3eb7,0x3de2beae,0xbe573e94,0x3e94be57,0x3eb78000,0xbeaebde2,0x3e943e57,0xbe57be94,
0x3eb7,0xbeb7,0x3eb7,0xbeb7,0x3eb78000,0xbeb78000,0x3eb78000,0xbeb78000,0x3eb7,0xbde2beae,0x3e573e94,0xbe94be57,0x3eb78000,0xbeae3de2,0x3e94be57,0xbe573e94,
0xbe57be94,0x3eb7,0x3e57be94,0xbeae3de2,0xbe943e57,0x3eb78000,0xbe94be57,0x3de23eae,0xbeae3de2,0x3eb70000,0xbeaebde2,0x3e943e57,0x3de23eae,0xbeb7,0xbde23eae,0x3e57be94,
0x3eb7,0xbeb7,0x3eb7,0xbeb7,0x3eb78000,0xbeb78000,0x3eb78000,0xbeb78000,0x3eae3de2,0xbeb70000,0x3eaebde2,0xbe943e57,0x3de2beae,0x3eb7,0xbde2beae,0x3e573e94,
0x3eb7,0xbe57be94,0x3eae3de2,0xbeae3de2,0x3eb78000,0xbe943e57,0x3de2beae,0x3de23eae,0x3eb7,0xbe94be57,0x3eaebde2,0xbde23eae,0x3eb78000,0xbe573e94,0xbde2beae,0x3eae3de2,
0x3eb7,0xbeaebde2,0x3e57be94,0x3e573e94,0x3eb78000,0xbde23eae,0xbe94be57,0x3e94be57,0x3eb7,0xbeb70000,0xbeb7,0x3eb70000,0x3eb78000,0x3eb7,0xbeb78000,0xbeb7,
0x3e57be94,0x3eb7,0xbe57be94,0x3eae3de2,0xbe94be57,0x3eb78000,0xbe943e57,0x3de2beae,0xbe57be94,0x3eb70000,0xbe573e94,0xbde2beae,0xbe943e57,0xbeb7,0x3e943e57,0xbeae3de2,
0xbeae3de2,0xbeb7,0x3eae3de2,0xbe573e94,0x3de23eae,0xbeb78000,0x3de2beae,0x3e943e57,0x3eb7,0xbeb70000,0xbeb7,0x3eb70000,0x3eb78000,0x3eb7,0xbeb78000,0xbeb7,
0x3eb7,0xbeae3de2,0xbe57be94,0x3e57be94,0x3eb78000,0x3de23eae,0xbe943e57,0xbe94be57,0x3eb7,0xbe943e57,0xbeaebde2,0xbde2beae,0x3eb78000,0x3e573e94,0xbde23eae,0xbeae3de2,
0x3eb7,0xbe573e94,0xbeae3de2,0xbeaebde2,0x3eb78000,0x3e943e57,0x3de23eae,0xbde23eae,0x3eb7,0xbde23eae,0xbe573e94,0xbe943e57,0x3eb78000,0x3eae3de2,0x3e943e57,0x3e573e94,
0x3eae3de2,0x3eb7,0xbeae3de2,0xbe57be94,0x3de2beae,0x3eb78000,0x3de23eae,0xbe943e57,0x3e57be94,0x3eb70000,0x3e573e94,0xbde23eae,0xbe94be57,0xbeb7,0x3e94be57,0x3eae3de2,
0xbe57be94,0xbeb7,0x3e57be94,0x3eaebde2,0xbe943e57,0xbeb78000,0xbe94be57,0xbde2beae,0xbeae3de2,0xbeb70000,0xbeaebde2,0xbe94be57,0x3de23eae,0x3eb7,0xbde23eae,0xbe573e94,
0x3eb7,0x3eb7,0x3eb7,0x3eb7,0x3eb78000,0x3eb78000,0x3eb78000,0x3eb78000,0x3e57be94,0x3de2beae,0xbeb7,0xbde2beae,0xbe94be57,0xbeaebde2,0xbeb78000,0xbeae3de2,
0xbeae3de2,0xbe573e94,0x3eb7,0x3e573e94,0x3de23eae,0x3e943e57,0x3eb78000,0x3e94be57,0x3eae3de2,0x3e94be57,0xbeb7,0xbe94be57,0x3de2beae,0xbe57be94,0xbeb78000,0xbe573e94,
0x3eb7,0x3eb7,0x3eb7,0x3eb7,0x3eb78000,0x3eb78000,0x3eb78000,0x3eb78000,0xbe57be94,0xbe94be57,0xbeaebde2,0xbeb70000,0xbe943e57,0xbe573e94,0xbde23eae,0x3eb7,
0x3eae3de2,0x3eaebde2,0x3e57be94,0xbeb7,0x3de2beae,0xbde2beae,0xbe94be57,0xbeb78000,0xbeae3de2,0xbde23eae,0x3e573e94,0x3eb70000,0x3de23eae,0x3eae3de2,0x3e94be57,0xbeb7,
0xbe57be94,0xbeae3de2,0x3eb7,0x3eae3de2,0xbe943e57,0x3de23eae,0x3eb78000,0x3de2beae,0x3eb7,0x3eb70000,0xbeb7,0xbeb70000,0x3eb78000,0xbeb7,0xbeb78000,0x3eb7,
0x3e57be94,0xbeaebde2,0x3eb7,0x3eaebde2,0xbe94be57,0xbde23eae,0x3eb78000,0xbde2beae,0xbeae3de2,0x3e943e57,0xbeb7,0xbe943e57,0x3de23eae,0x3e57be94,0xbeb78000,0x3e573e94,
0x3e57be94,0xbe57be94,0xbeae3de2,0x3eb7,0xbe94be57,0xbe943e57,0x3de23eae,0x3eb78000,0x3eb7,0x3eb70000,0xbeb7,0xbeb70000,0x3eb78000,0xbeb7,0xbeb78000,0x3eb7,
0xbe57be94,0xbe573e94,0x3eae3de2,0xbeb7,0xbe943e57,0x3e943e57,0x3de2beae,0xbeb78000,0x3eae3de2,0xbde2beae,0xbe573e94,0x3eb70000,0x3de2beae,0xbeae3de2,0x3e943e57,0xbeb7,
0x3eae3de2,0xbe57be94,0x3eb7,0x3e57be94,0x3de2beae,0xbe943e57,0x3eb78000,0xbe94be57,0xbe57be94,0x3de23eae,0xbeb7,0xbde23eae,0xbe943e57,0x3eaebde2,0xbeb78000,0x3eae3de2,
0x3eb7,0xbeb7,0x3eb7,0xbeb7,0x3eb78000,0xbeb78000,0x3eb78000,0xbeb78000,0x3e57be94,0xbde23eae,0xbeb7,0x3de23eae,0xbe94be57,0x3eae3de2,0xbeb78000,0x3eaebde2,
0xbeae3de2,0x3eae3de2,0xbe57be94,0x3eb7,0x3de23eae,0x3de2beae,0xbe943e57,0x3eb78000,0x3e57be94,0xbe943e57,0x3eaebde2,0xbeb70000,0xbe94be57,0x3e573e94,0xbde2beae,0x3eb7,
0x3eb7,0xbeb7,0x3eb7,0xbeb7,0x3eb78000,0xbeb78000,0x3eb78000,0xbeb78000,0xbe57be94,0x3e943e57,0xbeaebde2,0x3eb70000,0xbe943e57,0x3e57be94,0xbde23eae,0xbeb7,
0xbeae3de2,0x3e57be94,0x3eb7,0xbe57be94,0x3de23eae,0xbe94be57,0x3eb78000,0xbe943e57,0x3eae3de2,0xbe943e57,0xbeb7,0x3e943e57,0x3de2beae,0x3e573e94,0xbeb78000,0x3e57be94,
0xbe57be94,0x3eaebde2,0x3eb7,0xbeaebde2,0xbe943e57,0xbde2beae,0x3eb78000,0xbde23eae,0x3eb7,0xbeb70000,0xbeb7,0x3eb70000,0x3eb78000,0x3eb7,0xbeb78000,0xbeb7,
0x3eae3de2,0xbeae3de2,0x3e57be94,0x3eb7,0x3de2beae,0x3de23eae,0xbe94be57,0x3eb78000,0xbeae3de2,0x3de2beae,0x3e573e94,0xbeb70000,0x3de23eae,0xbeaebde2,0x3e94be57,0x3eb7,
0x3e57be94,0x3e573e94,0xbeae3de2,0xbeb7,0xbe94be57,0x3e94be57,0x3de23eae,0xbeb78000,0x3eb7,0xbeb70000,0xbeb7,0x3eb70000,0x3eb78000,0x3eb7,0xbeb78000,0xbeb7,
0x3e57be94,0x3eae3de2,0x3eb7,0xbeae3de2,0xbe94be57,0x3de2beae,0x3eb78000,0x3de23eae,0xbeae3de2,0xbe94be57,0xbeb7,0x3e94be57,0x3de23eae,0xbe573e94,0xbeb78000,0xbe57be94,
0x3eae3de2,0x3e573e94,0x3eb7,0xbe573e94,0x3de2beae,0x3e94be57,0x3eb78000,0x3e943e57,0xbe57be94,0xbde2beae,0xbeb7,0x3de2beae,0xbe943e57,0xbeae3de2,0xbeb78000,0xbeaebde2,
0xbe57be94,0x3e57be94,0x3eae3de2,0x3eb7,0xbe943e57,0xbe94be57,0x3de2beae,0x3eb78000,0x3eae3de2,0x3de23eae,0xbe573e94,0xbeb70000,0x3de2beae,0x3eaebde2,0x3e943e57,0x3eb7,
0xbeae3de2,0xbeaebde2,0xbe57be94,0xbeb7,0x3de23eae,0xbde23eae,0xbe943e57,0xbeb78000,0x3e57be94,0x3e94be57,0x3eaebde2,0x3eb70000,0xbe94be57,0xbe57be94,0xbde2beae,0xbeb7,
0x3eb7,0x3eb7,0x3eb7,0x3eb7,0x3eb78000,0x3eb78000,0x3eb78000,0x3eb78000,0xbeae3de2,0xbe943e57,0xbe573e94,0xbde23eae,0x3de23eae,0x3e573e94,0x3e943e57,0x3eae3de2,
0xbe57be94,0xbeaebde2,0xbeae3de2,0xbe573e94,0xbe943e57,0xbde23eae,0x3de23eae,0x3e943e57,0x3e57be94,0xbde2beae,0xbeaebde2,0xbe943e57,0xbe94be57,0xbeae3de2,0xbde23eae,0x3e573e94,
0,0,0,0,0,0,0,0,0,0,0,0,0,0,0,0,
0,0,0,0,0,0,0,0,0,0,0,0,0,0,0,0,
0x3eae3de2,0x3e57be94,0xbe57be94,0xbeae3de2,0x3de2beae,0xbe94be57,0xbe943e57,0x3de23eae,0x3eb7,0x3eb70000,0xbeb7,0xbeb70000,0x3eb78000,0xbeb7,0xbeb78000,0x3eb7,
0xbeae3de2,0x3e573e94,0x3e57be94,0xbeaebde2,0x3de23eae,0x3e94be57,0xbe94be57,0xbde23eae,0xbe57be94,0xbde23eae,0x3eaebde2,0xbe94be57,0xbe943e57,0x3eae3de2,0xbde2beae,0xbe573e94,
0,0,0,0,0,0,0,0,0,0,0,0,0,0,0,0,
0,0,0,0,0,0,0,0,0,0,0,0,0,0,0,0,
0x3e57be94,0xbeae3de2,0x3eae3de2,0xbe57be94,0xbe94be57,0x3de23eae,0x3de2beae,0xbe943e57,0x3eae3de2,0xbe94be57,0x3e573e94,0xbde2beae,0x3de2beae,0xbe573e94,0x3e94be57,0xbeae3de2,
0x3eb7,0xbeb7,0x3eb7,0xbeb7,0x3eb78000,0xbeb78000,0x3eb78000,0xbeb78000,0xbeae3de2,0x3e94be57,0xbe573e94,0x3de2beae,0x3de23eae,0xbe57be94,0x3e943e57,0xbeaebde2,
0,0,0,0,0,0,0,0,0,0,0,0,0,0,0,0,
0,0,0,0,0,0,0,0,0,0,0,0,0,0,0,0,
0xbe57be94,0x3eae3de2,0xbeae3de2,0x3e57be94,0xbe943e57,0x3de2beae,0x3de23eae,0xbe94be57,0x3e57be94,0x3de23eae,0xbeaebde2,0x3e94be57,0xbe94be57,0x3eaebde2,0xbde23eae,0xbe57be94,
0x3eae3de2,0xbe573e94,0xbe57be94,0x3eaebde2,0x3de2beae,0x3e943e57,0xbe943e57,0xbde2beae,0x3eb7,0xbeb70000,0xbeb7,0x3eb70000,0x3eb78000,0x3eb7,0xbeb78000,0xbeb7,
0,0,0,0,0,0,0,0,0,0,0,0,0,0,0,0,
0,0,0,0,0,0,0,0,0,0,0,0,0,0,0,0,
0xbeae3de2,0xbe57be94,0x3e57be94,0x3eae3de2,0x3de23eae,0xbe943e57,0xbe94be57,0x3de2beae,0xbe57be94,0x3de2beae,0x3eaebde2,0x3e943e57,0xbe943e57,0xbeaebde2,0xbde2beae,0x3e57be94,
0x3e57be94,0x3eaebde2,0x3eae3de2,0x3e573e94,0xbe94be57,0xbde2beae,0x3de2beae,0x3e94be57,0x3eae3de2,0x3e943e57,0x3e573e94,0x3de23eae,0x3de2beae,0x3e57be94,0x3e94be57,0x3eaebde2,
0,0,0,0,0,0,0,0,0,0,0,0,0,0,0,0,
0,0,0,0,0,0,0,0,0,0,0,0,0,0,0,0,
0,0,0,0,0,0,0,0,0,0,0,0,0,0,0,0,
0,0,0,0,0,0,0,0,0,0,0,0,0,0,0,0,
0x3eb7,0x3eb7,0x3eb7,0x3eb7,0x3eb78000,0x3eb78000,0x3eb78000,0x3eb78000,0xbeae3de2,0xbe943e57,0xbe573e94,0xbde23eae,0x3de23eae,0x3e573e94,0x3e943e57,0x3eae3de2,
0xbe57be94,0xbeaebde2,0xbeae3de2,0xbe573e94,0xbe943e57,0xbde23eae,0x3de23eae,0x3e943e57,0x3e57be94,0xbde2beae,0xbeaebde2,0xbe943e57,0xbe94be57,0xbeae3de2,0xbde23eae,0x3e573e94,
0,0,0,0,0,0,0,0,0,0,0,0,0,0,0,0,
0,0,0,0,0,0,0,0,0,0,0,0,0,0,0,0,
0x3eae3de2,0x3e57be94,0xbe57be94,0xbeae3de2,0x3de2beae,0xbe94be57,0xbe943e57,0x3de23eae,0x3eb7,0x3eb70000,0xbeb7,0xbeb70000,0x3eb78000,0xbeb7,0xbeb78000,0x3eb7,
0xbeae3de2,0x3e573e94,0x3e57be94,0xbeaebde2,0x3de23eae,0x3e94be57,0xbe94be57,0xbde23eae,0xbe57be94,0xbde23eae,0x3eaebde2,0xbe94be57,0xbe943e57,0x3eae3de2,0xbde2beae,0xbe573e94,
0,0,0,0,0,0,0,0,0,0,0,0,0,0,0,0,
0,0,0,0,0,0,0,0,0,0,0,0,0,0,0,0,
0x3e57be94,0xbeae3de2,0x3eae3de2,0xbe57be94,0xbe94be57,0x3de23eae,0x3de2beae,0xbe943e57,0x3eae3de2,0xbe94be57,0x3e573e94,0xbde2beae,0x3de2beae,0xbe573e94,0x3e94be57,0xbeae3de2,
0x3eb7,0xbeb7,0x3eb7,0xbeb7,0x3eb78000,0xbeb78000,0x3eb78000,0xbeb78000,0xbeae3de2,0x3e94be57,0xbe573e94,0x3de2beae,0x3de23eae,0xbe57be94,0x3e943e57,0xbeaebde2,
0,0,0,0,0,0,0,0,0,0,0,0,0,0,0,0,
0,0,0,0,0,0,0,0,0,0,0,0,0,0,0,0,
0xbe57be94,0x3eae3de2,0xbeae3de2,0x3e57be94,0xbe943e57,0x3de2beae,0x3de23eae,0xbe94be57,0x3e57be94,0x3de23eae,0xbeaebde2,0x3e94be57,0xbe94be57,0x3eaebde2,0xbde23eae,0xbe57be94,
0x3eae3de2,0xbe573e94,0xbe57be94,0x3eaebde2,0x3de2beae,0x3e943e57,0xbe943e57,0xbde2beae,0x3eb7,0xbeb70000,0xbeb7,0x3eb70000,0x3eb78000,0x3eb7,0xbeb78000,0xbeb7,
0,0,0,0,0,0,0,0,0,0,0,0,0,0,0,0,
0,0,0,0,0,0,0,0,0,0,0,0,0,0,0,0,
0xbeae3de2,0xbe57be94,0x3e57be94,0x3eae3de2,0x3de23eae,0xbe943e57,0xbe94be57,0x3de2beae,0xbe57be94,0x3de2beae,0x3eaebde2,0x3e943e57,0xbe943e57,0xbeaebde2,0xbde2beae,0x3e57be94,
0x3e57be94,0x3eaebde2,0x3eae3de2,0x3e573e94,0xbe94be57,0xbde2beae,0x3de2beae,0x3e94be57,0x3eae3de2,0x3e943e57,0x3e573e94,0x3de23eae,0x3de2beae,0x3e57be94,0x3e94be57,0x3eaebde2,
};
__device__ __align__(128) const uint32_t TAB_P3[4288] = {
0,0,0,0,0,0,0,0,0,0,0,0,0,0,0,0,
0x80003e83,0xbe79bda2,0x3e1abe54,0x3e1a3e54,0x3e830000,0xbda23e79,0xbe54be1a,0x3e54be1a,0x80003e83,0xbe54be1a,0x3e79bda2,0xbda23e79,0x3e830000,0xbe1a3e54,0xbda2be79,0x3e793da2,
0,0,0,0,0,0,0,0,0,0,0,0,0,0,0,0,
0xbe793da2,0x8000be83,0x3e793da2,0xbe1a3e54,0x3da23e79,0xbe830000,0x3da2be79,0x3e543e1a,0xbe1abe54,0x3e830000,0xbe1a3e54,0xbda2be79,0xbe543e1a,0xbe83,0x3e543e1a,0xbe793da2,
0x80003e83,0xbe1abe54,0x3e793da2,0xbe793da2,0x3e830000,0xbe543e1a,0x3da2be79,0x3da23e79,0x80003e83,0xbda2be79,0x3e1a3e54,0xbe54be1a,0x3e830000,0xbe793da2,0x3e54be1a,0xbe1a3e54,
0x80003e83,0x8000be83,0x80003e83,0x8000be83,0x3e830000,0xbe830000,0x3e830000,0xbe830000,0x80003e83,0x3da2be79,0xbe1a3e54,0x3e54be1a,0x3e830000,0xbe79bda2,0x3e543e1a,0xbe1abe54,
0x3e1abe54,0x80003e83,0xbe1abe54,0x3e793da2,0xbe54be1a,0x3e830000,0xbe543e1a,0x3da2be79,0x3e793da2,0xbe830000,0x3e79bda2,0xbe543e1a,0x3da2be79,0x3e83,0xbda2be79,0x3e1a3e54,
0x80003e83,0x8000be83,0x80003e83,0x8000be83,0x3e830000,0xbe830000,0x3e830000,0xbe830000,0xbe793da2,0x3e830000,0xbe79bda2,0x3e543e1a,0x3da23e79,0xbe83,0xbda23e79,0x3e1abe54,
0x80003e83,0x3e1abe54,0xbe793da2,0x3e793da2,0x3e830000,0xbe54be1a,0x3da23e79,0x3da2be79,0x80003e83,0x3e54be1a,0xbe79bda2,0x3da23e79,0x3e830000,0xbe1abe54,0xbda23e79,0x3e79bda2,
0x80003e83,0x3e79bda2,0xbe1abe54,0xbe1a3e54,0x3e830000,0xbda2be79,0xbe543e1a,0x3e543e1a,0x80003e83,0x3e830000,0x8000be83,0xbe830000,0x3e830000,0xbe83,0xbe830000,0x3e83,
0xbe1abe54,0x80003e83,0x3e1abe54,0xbe793da2,0xbe543e1a,0x3e830000,0xbe54be1a,0x3da23e79,0x3e1abe54,0xbe830000,0x3e1a3e54,0x3da2be79,0xbe54be1a,0x3e83,0x3e54be1a,0xbe79bda2,
0x3e793da2,0x8000be83,0xbe793da2,0x3e1a3e54,0x3da2be79,0xbe830000,0x3da23e79,0x3e54be1a,0x80003e83,0x3e830000,0x8000be83,0xbe830000,0x3e830000,0xbe83,0xbe830000,0x3e83,
0x80003e83,0x3e793da2,0x3e1abe54,0xbe1abe54,0x3e830000,0x3da2be79,0xbe54be1a,0xbe543e1a,0x80003e83,0x3e543e1a,0x3e79bda2,0x3da2be79,0x3e830000,0x3e1abe54,0xbda2be79,0xbe79bda2,
0x80003e83,0x3e1a3e54,0x3e793da2,0x3e79bda2,0x3e830000,0x3e54be1a,0x3da2be79,0xbda2be79,0x80003e83,0x3da23e79,0x3e1a3e54,0x3e543e1a,0x3e830000,0x3e79bda2,0x3e54be1a,0x3e1abe54,
0xbe793da2,0x80003e83,0x3e793da2,0x3e1abe54,0x3da23e79,0x3e830000,0x3da2be79,0xbe54be1a,0xbe1abe54,0xbe830000,0xbe1a3e54,0x3da23e79,0xbe543e1a,0x3e83,0x3e543e1a,0x3e79bda2,
0x3e1abe54,0x8000be83,0xbe1abe54,0xbe79bda2,0xbe54be1a,0xbe830000,0xbe543e1a,0xbda23e79,0x3e793da2,0x3e830000,0x3e79bda2,0x3e54be1a,0x3da2be79,0xbe83,0xbda2be79,0xbe1abe54,
0,0,0,0,0,0,0,0,0,0,0,0,0,0,0,0,
0,0,0,0,0,0,0,0,0,0,0,0,0,0,0,0,
0,0,0,0,0,0,0,0,0,0,0,0,0,0,0,0,
0xbe1abe54,0x3e79bda2,0x80003e83,0xbe79bda2,0xbe543e1a,0xbda2be79,0x3e830000,0xbda23e79,0x3e793da2,0xbe543e1a,0x8000be83,0x3e543e1a,0x3da2be79,0x3e1a3e54,0xbe830000,0x3e1abe54,
0,0,0,0,0,0,0,0,0,0,0,0,0,0,0,0,
0,0,0,0,0,0,0,0,0,0,0,0,0,0,0,0,
0xbe793da2,0x3e1abe54,0x80003e83,0xbe1abe54,0x3da23e79,0xbe54be1a,0x3e830000,0xbe543e1a,0x3e1abe54,0xbda23e79,0x8000be83,0x3da23e79,0xbe54be1a,0x3e793da2,0xbe830000,0x3e79bda2,
0x80003e83,0x8000be83,0x80003e83,0x8000be83,0x3e830000,0xbe830000,0x3e830000,0xbe830000,0xbe1abe54,0x3da23e79,0x8000be83,0xbda23e79,0xbe543e1a,0x3e79bda2,0xbe830000,0x3e793da2,
0,0,0,0,0,0,0,0,0,0,0,0,0,0,0,0,
0,0,0,0,0,0,0,0,0,0,0,0,0,0,0,0,
0x3e793da2,0xbe1abe54,0x80003e83,0x3e1abe54,0x3da2be79,0xbe543e1a,0x3e830000,0xbe54be1a,0xbe793da2,0x3e543e1a,0x8000be83,0xbe543e1a,0x3da23e79,0x3e1abe54,0xbe830000,0x3e1a3e54,
0x3e1abe54,0xbe79bda2,0x80003e83,0x3e79bda2,0xbe54be1a,0xbda23e79,0x3e830000,0xbda2be79,0x80003e83,0x3e830000,0x8000be83,0xbe830000,0x3e830000,0xbe83,0xbe830000,0x3e83,
0,0,0,0,0,0,0,0,0,0,0,0,0,0,0,0,
0,0,0,0,0,0,0,0,0,0,0,0,0,0,0,0,
0xbe1abe54,0xbe793da2,0x80003e83,0x3e793da2,0xbe543e1a,0x3da23e79,0x3e830000,0x3da2be79,0x3e793da2,0x3e54be1a,0x8000be83,0xbe54be1a,0x3da2be79,0xbe1abe54,0xbe830000,0xbe1a3e54,
0xbe793da2,0xbe1a3e54,0x80003e83,0x3e1a3e54,0x3da23e79,0x3e543e1a,0x3e830000,0x3e54be1a,0x3e1abe54,0x3da2be79,0x8000be83,0xbda2be79,0xbe54be1a,0xbe79bda2,0xbe830000,0xbe793da2,
0,0,0,0,0,0,0,0,0,0,0,0,0,0,0,0,
0x3e1abe54,0x3e1a3e54,0xbe793da2,0x8000be83,0xbe54be1a,0x3e54be1a,0x3da23e79,0xbe830000,0xbe793da2,0x3da2be79,0x3e1a3e54,0xbe830000,0x3da23e79,0xbe79bda2,0x3e54be1a,0x3e83,
0,0,0,0,0,0,0,0,0,0,0,0,0,0,0,0,
0x3e793da2,0xbe1a3e54,0xbe1abe54,0x3e79bda2,0x3da2be79,0x3e543e1a,0xbe543e1a,0xbda2be79,0x3e1abe54,0x3da23e79,0xbe79bda2,0x3e54be1a,0xbe54be1a,0x3e79bda2,0xbda23e79,0xbe1abe54,
0x3e793da2,0xbe793da2,0x3e1abe54,0x80003e83,0x3da2be79,0x3da23e79,0xbe54be1a,0x3e830000,0xbe1abe54,0x3e543e1a,0xbe79bda2,0x3e830000,0xbe543e1a,0x3e1abe54,0xbda23e79,0xbe83,
0x80003e83,0x8000be83,0x80003e83,0x8000be83,0x3e830000,0xbe830000,0x3e830000,0xbe830000,0x3e1abe54,0xbe543e1a,0x3e79bda2,0xbe830000,0xbe54be1a,0x3e1a3e54,0xbda2be79,0x3e83,
0xbe1abe54,0x3e793da2,0xbe793da2,0x3e1abe54,0xbe543e1a,0x3da2be79,0x3da23e79,0xbe54be1a,0xbe793da2,0x3e54be1a,0xbe1a3e54,0x3da2be79,0x3da23e79,0xbe1abe54,0x3e543e1a,0xbe79bda2,
0x80003e83,0x8000be83,0x80003e83,0x8000be83,0x3e830000,0xbe830000,0x3e830000,0xbe830000,0x3e793da2,0xbe54be1a,0x3e1a3e54,0xbda2be79,0x3da2be79,0xbe1a3e54,0x3e54be1a,0xbe793da2,
0xbe793da2,0x3e793da2,0xbe1abe54,0x80003e83,0x3da23e79,0x3da2be79,0xbe543e1a,0x3e830000,0x3e793da2,0xbda2be79,0xbe1a3e54,0x3e830000,0x3da2be79,0xbe793da2,0x3e543e1a,0xbe83,
0xbe1abe54,0xbe1a3e54,0x3e793da2,0x8000be83,0xbe543e1a,0x3e543e1a,0x3da2be79,0xbe830000,0x80003e83,0x3e830000,0x8000be83,0xbe830000,0x3e830000,0xbe83,0xbe830000,0x3e83,
0x3e1abe54,0xbe793da2,0x3e793da2,0xbe1abe54,0xbe54be1a,0x3da23e79,0x3da2be79,0xbe543e1a,0xbe1abe54,0xbda23e79,0x3e79bda2,0xbe54be1a,0xbe543e1a,0x3e793da2,0xbda2be79,0xbe1a3e54,
0xbe793da2,0x3e1a3e54,0x3e1abe54,0xbe79bda2,0x3da23e79,0x3e54be1a,0xbe54be1a,0xbda23e79,0x80003e83,0x3e830000,0x8000be83,0xbe830000,0x3e830000,0xbe83,0xbe830000,0x3e83,
0x3e1abe54,0xbe1abe54,0xbe793da2,0x80003e83,0xbe54be1a,0xbe543e1a,0x3da23e79,0x3e830000,0xbe793da2,0xbda23e79,0x3e1a3e54,0x3e830000,0x3da23e79,0x3e793da2,0x3e54be1a,0xbe83,
0x3e793da2,0x3e79bda2,0x3e1abe54,0x8000be83,0x3da2be79,0xbda2be79,0xbe54be1a,0xbe830000,0xbe1abe54,0xbe54be1a,0xbe79bda2,0xbe830000,0xbe543e1a,0xbe1a3e54,0xbda23e79,0x3e83,
0x3e793da2,0x3e1abe54,0xbe1abe54,0xbe793da2,0x3da2be79,0xbe54be1a,0xbe543e1a,0x3da23e79,0x3e1abe54,0xbda2be79,0xbe79bda2,0xbe543e1a,0xbe54be1a,0xbe793da2,0xbda23e79,0x3e1a3e54,
0xbe1abe54,0xbe79bda2,0xbe793da2,0xbe1a3e54,0xbe543e1a,0xbda23e79,0x3da23e79,0x3e543e1a,0xbe793da2,0xbe543e1a,0xbe1a3e54,0xbda23e79,0x3da23e79,0x3e1a3e54,0x3e543e1a,0x3e793da2,
0xbe163dda,0,0,0,0,0xbe163dda,0,0,0,0,0xbe163dda,0,0,0,0,0xbe163dda,
0xbe253da8,0,0,0,0,0xbe253da8,0,0,0,0,0xbe253da8,0,0,0,0,0xbe253da8,
0xbd65be30,0,0,0,0,0xbd65be30,0,0,0,0,0xbd65be30,0,0,0,0,0xbd65be30,
0x3ce8be37,0,0,0,0,0x3ce8be37,0,0,0,0,0x3ce8be37,0,0,0,0,0x3ce8be37,
0xbe303d65,0,0,0,0,0xbe303d65,0,0,0,0,0xbe303d65,0,0,0,0,0xbe303d65,
0xbe373ce8,0,0,0,0,0xbe373ce8,0,0,0,0,0xbe373ce8,0,0,0,0,0xbe373ce8,
0x3ddabe16,0,0,0,0,0x3ddabe16,0,0,0,0,0x3ddabe16,0,0,0,0,0x3ddabe16,
0x3e25bda8,0,0,0,0,0x3e25bda8,0,0,0,0,0x3e25bda8,0,0,0,0,0x3e25bda8,
0xbe390000,0,0,0,0,0xbe390000,0,0,0,0,0xbe390000,0,0,0,0,0xbe390000,
0xbe37bce8,0,0,0,0,0xbe37bce8,0,0,0,0,0xbe37bce8,0,0,0,0,0xbe37bce8,
0x3e390000,0,0,0,0,0x3e390000,0,0,0,0,0x3e390000,0,0,0,0,0x3e390000,
0x3e253da8,0,0,0,0,0x3e253da8,0,0,0,0,0x3e253da8,0,0,0,0,0x3e253da8,
0xbe30bd65,0,0,0,0,0xbe30bd65,0,0,0,0,0xbe30bd65,0,0,0,0,0xbe30bd65,
0xbe25bda8,0,0,0,0,0xbe25bda8,0,0,0,0,0xbe25bda8,0,0,0,0,0xbe25bda8,
0x3dda3e16,0,0,0,0,0x3dda3e16,0,0,0,0,0x3dda3e16,0,0,0,0,0x3dda3e16,
0x3ce83e37,0,0,0,0,0x3ce83e37,0,0,0,0,0x3ce83e37,0,0,0,0,0x3ce83e37,
0xbe16bdda,0,0,0,0,0xbe16bdda,0,0,0,0,0xbe16bdda,0,0,0,0,0xbe16bdda,
0xbe03be03,0,0,0,0,0xbe03be03,0,0,0,0,0xbe03be03,0,0,0,0,0xbe03be03,
0xbd653e30,0,0,0,0,0xbd653e30,0,0,0,0,0xbd653e30,0,0,0,0,0xbd653e30,
0xbe033e03,0,0,0,0,0xbe033e03,0,0,0,0,0xbe033e03,0,0,0,0,0xbe033e03,
0xbddabe16,0,0,0,0,0xbddabe16,0,0,0,0,0xbddabe16,0,0,0,0,0xbddabe16,
0xbda8be25,0,0,0,0,0xbda8be25,0,0,0,0,0xbda8be25,0,0,0,0,0xbda8be25,
0xbe303d65,0,0,0,0,0xbe303d65,0,0,0,0,0xbe303d65,0,0,0,0,0xbe303d65,
0xbe37bce8,0,0,0,0,0xbe37bce8,0,0,0,0,0xbe37bce8,0,0,0,0,0xbe37bce8,
0xbd65be30,0,0,0,0,0xbd65be30,0,0,0,0,0xbd65be30,0,0,0,0,0xbd65be30,
0xbce8be37,0,0,0,0,0xbce8be37,0,0,0,0,0xbce8be37,0,0,0,0,0xbce8be37,
0xbe16bdda,0,0,0,0,0xbe16bdda,0,0,0,0,0xbe16bdda,0,0,0,0,0xbe16bdda,
0xbda8be25,0,0,0,0,0xbda8be25,0,0,0,0,0xbda8be25,0,0,0,0,0xbda8be25,
0x3e390000,0,0,0,0,0x3e390000,0,0,0,0,0x3e390000,0,0,0,0,0x3e390000,
0x3e033e03,0,0,0,0,0x3e033e03,0,0,0,0,0x3e033e03,0,0,0,0,0x3e033e03,
0xbd653e30,0,0,0,0,0xbd653e30,0,0,0,0,0xbd653e30,0,0,0,0,0xbd653e30,
0xbe373ce8,0,0,0,0,0xbe373ce8,0,0,0,0,0xbe373ce8,0,0,0,0,0xbe373ce8,
0x80003e39,0,0,0,0,0x80003e39,0,0,0,0,0x80003e39,0,0,0,0,0x80003e39,
0xbe033e03,0,0,0,0,0xbe033e03,0,0,0,0,0xbe033e03,0,0,0,0,0xbe033e03,
0xbddabe16,0,0,0,0,0xbddabe16,0,0,0,0,0xbddabe16,0,0,0,0,0xbddabe16,
0x3da8be25,0,0,0,0,0x3da8be25,0,0,0,0,0x3da8be25,0,0,0,0,0x3da8be25,
0xbe390000,0,0,0,0,0xbe390000,0,0,0,0,0xbe390000,0,0,0,0,0xbe390000,
0xbe03be03,0,0,0,0,0xbe03be03,0,0,0,0,0xbe03be03,0,0,0,0,0xbe03be03,
0x3e390000,0,0,0,0,0x3e390000,0,0,0,0,0x3e390000,0,0,0,0,0x3e390000,
0x3da83e25,0,0,0,0,0x3da83e25,0,0,0,0,0x3da83e25,0,0,0,0,0x3da83e25,
0x8000be39,0,0,0,0,0x8000be39,0,0,0,0,0x8000be39,0,0,0,0,0x8000be39,
0x3e03be03,0,0,0,0,0x3e03be03,0,0,0,0,0x3e03be03,0,0,0,0,0x3e03be03,
0xbdda3e16,0,0,0,0,0xbdda3e16,0,0,0,0,0xbdda3e16,0,0,0,0,0xbdda3e16,
0xbe37bce8,0,0,0,0,0xbe37bce8,0,0,0,0,0xbe37bce8,0,0,0,0,0xbe37bce8,
0x3e390000,0,0,0,0,0x3e390000,0,0,0,0,0x3e390000,0,0,0,0,0x3e390000,
0x3e033e03,0,0,0,0,0x3e033e03,0,0,0,0,0x3e033e03,0,0,0,0,0x3e033e03,
0xbd65be30,0,0,0,0,0xbd65be30,0,0,0,0,0xbd65be30,0,0,0,0,0xbd65be30,
0x3e03be03,0,0,0,0,0x3e03be03,0,0,0,0,0x3e03be03,0,0,0,0,0x3e03be03,
0x80003e39,0,0,0,0,0x80003e39,0,0,0,0,0x80003e39,0,0,0,0,0x80003e39,
0xbe033e03,0,0,0,0,0xbe033e03,0,0,0,0,0xbe033e03,0,0,0,0,0xbe033e03,
0x3e303d65,0,0,0,0,0x3e303d65,0,0,0,0,0x3e303d65,0,0,0,0,0x3e303d65,
0x3ce83e37,0,0,0,0,0x3ce83e37,0,0,0,0,0x3ce83e37,0,0,0,0,0x3ce83e37,
0xbe390000,0,0,0,0,0xbe390000,0,0,0,0,0xbe390000,0,0,0,0,0xbe390000,
0xbe03be03,0,0,0,0,0xbe03be03,0,0,0,0,0xbe03be03,0,0,0,0,0xbe03be03,
0xbe163dda,0,0,0,0,0xbe163dda,0,0,0,0,0xbe163dda,0,0,0,0,0xbe163dda,
0xbe25bda8,0,0,0,0,0xbe25bda8,0,0,0,0,0xbe25bda8,0,0,0,0,0xbe25bda8,
0xbe16bdda,0,0,0,0,0xbe16bdda,0,0,0,0,0xbe16bdda,0,0,0,0,0xbe16bdda,
0x3da8be25,0,0,0,0,0x3da8be25,0,0,0,0,0x3da8be25,0,0,0,0,0x3da8be25,
0x3e16bdda,0,0,0,0,0x3e16bdda,0,0,0,0,0x3e16bdda,0,0,0,0,0x3e16bdda,
0x3da83e25,0,0,0,0,0x3da83e25,0,0,0,0,0x3da83e25,0,0,0,0,0x3da83e25,
0x3e303d65,0,0,0,0,0x3e303d65,0,0,0,0,0x3e303d65,0,0,0,0,0x3e303d65,
0xbce83e37,0,0,0,0,0xbce83e37,0,0,0,0,0xbce83e37,0,0,0,0,0xbce83e37,
0xbe303d65,0,0,0,0,0xbe303d65,0,0,0,0,0xbe303d65,0,0,0,0,0xbe303d65,
0xbce8be37,0,0,0,0,0xbce8be37,0,0,0,0,0xbce8be37,0,0,0,0,0xbce8be37,
0xbe390000,0,0,0,0,0xbe390000,0,0,0,0,0xbe390000,0,0,0,0,0xbe390000,
0xbce8be37,0,0,0,0,0xbce8be37,0,0,0,0,0xbce8be37,0,0,0,0,0xbce8be37,
0x3e390000,0,0,0,0,0x3e390000,0,0,0,0,0x3e390000,0,0,0,0,0x3e390000,
0xbce83e37,0,0,0,0,0xbce83e37,0,0,0,0,0xbce83e37,0,0,0,0,0xbce83e37,
0x3e30bd65,0,0,0,0,0x3e30bd65,0,0,0,0,0x3e30bd65,0,0,0,0,0x3e30bd65,
0x3da83e25,0,0,0,0,0x3da83e25,0,0,0,0,0x3da83e25,0,0,0,0,0x3da83e25,
0xbe30bd65,0,0,0,0,0xbe30bd65,0,0,0,0,0xbe30bd65,0,0,0,0,0xbe30bd65,
0x3da8be25,0,0,0,0,0x3da8be25,0,0,0,0,0x3da8be25,0,0,0,0,0x3da8be25,
0xbe163dda,0,0,0,0,0xbe163dda,0,0,0,0,0xbe163dda,0,0,0,0,0xbe163dda,
0xbe03be03,0,0,0,0,0xbe03be03,0,0,0,0,0xbe03be03,0,0,0,0,0xbe03be03,
0x3e163dda,0,0,0,0,0x3e163dda,0,0,0,0,0x3e163dda,0,0,0,0,0x3e163dda,
0xbe033e03,0,0,0,0,0xbe033e03,0,0,0,0,0xbe033e03,0,0,0,0,0xbe033e03,
0x3ddabe16,0,0,0,0,0x3ddabe16,0,0,0,0,0x3ddabe16,0,0,0,0,0x3ddabe16,
0x3e253da8,0,0,0,0,0x3e253da8,0,0,0,0,0x3e253da8,0,0,0,0,0x3e253da8,
0xbddabe16,0,0,0,0,0xbddabe16,0,0,0,0,0xbddabe16,0,0,0,0,0xbddabe16,
0x3e25bda8,0,0,0,0,0x3e25bda8,0,0,0,0,0x3e25bda8,0,0,0,0,0x3e25bda8,
0xbd653e30,0,0,0,0,0xbd653e30,0,0,0,0,0xbd653e30,0,0,0,0,0xbd653e30,
0xbe37bce8,0,0,0,0,0xbe37bce8,0,0,0,0,0xbe37bce8,0,0,0,0,0xbe37bce8,
0x3d653e30,0,0,0,0,0x3d653e30,0,0,0,0,0x3d653e30,0,0,0,0,0x3d653e30,
0xbe373ce8,0,0,0,0,0xbe373ce8,0,0,0,0,0xbe373ce8,0,0,0,0,0xbe373ce8,
0x3d653e30,0,0,0,0,0x3d653e30,0,0,0,0,0x3d653e30,0,0,0,0,0x3d653e30,
0xbe37bce8,0,0,0,0,0xbe37bce8,0,0,0,0,0xbe37bce8,0,0,0,0,0xbe37bce8,
0xbe390000,0,0,0,0,0xbe390000,0,0,0,0,0xbe390000,0,0,0,0,0xbe390000,
0x3e03be03,0,0,0,0,0x3e03be03,0,0,0,0,0x3e03be03,0,0,0,0,0x3e03be03,
0x3ddabe16,0,0,0,0,0x3ddabe16,0,0,0,0,0x3ddabe16,0,0,0,0,0x3ddabe16,
0x3da83e25,0,0,0,0,0x3da83e25,0,0,0,0,0x3da83e25,0,0,0,0,0x3da83e25,
0x80003e39,0,0,0,0,0x80003e39,0,0,0,0,0x80003e39,0,0,0,0,0x80003e39,
0xbe03be03,0,0,0,0,0xbe03be03,0,0,0,0,0xbe03be03,0,0,0,0,0xbe03be03,
0xbe390000,0,0,0,0,0xbe390000,0,0,0,0,0xbe390000,0,0,0,0,0xbe390000,
0x3da8be25,0,0,0,0,0x3da8be25,0,0,0,0,0x3da8be25,0,0,0,0,0x3da8be25,
0x3e390000,0,0,0,0,0x3e390000,0,0,0,0,0x3e390000,0,0,0,0,0x3e390000,
0xbe033e03,0,0,0,0,0xbe033e03,0,0,0,0,0xbe033e03,0,0,0,0,0xbe033e03,
0x3dda3e16,0,0,0,0,0x3dda3e16,0,0,0,0,0x3dda3e16,0,0,0,0,0x3dda3e16,
0xbe373ce8,0,0,0,0,0xbe373ce8,0,0,0,0,0xbe373ce8,0,0,0,0,0xbe373ce8,
0x8000be39,0,0,0,0,0x8000be39,0,0,0,0,0x8000be39,0,0,0,0,0x8000be39,
0x3e033e03,0,0,0,0,0x3e033e03,0,0,0,0,0x3e033e03,0,0,0,0,0x3e033e03,
0x3d65be30,0,0,0,0,0x3d65be30,0,0,0,0,0x3d65be30,0,0,0,0,0x3d65be30,
0x3e033e03,0,0,0,0,0x3e033e03,0,0,0,0,0x3e033e03,0,0,0,0,0x3e033e03,
0xbe390000,0,0,0,0,0xbe390000,0,0,0,0,0xbe390000,0,0,0,0,0xbe390000,
0x3e03be03,0,0,0,0,0x3e03be03,0,0,0,0,0x3e03be03,0,0,0,0,0x3e03be03,
0xbe303d65,0,0,0,0,0xbe303d65,0,0,0,0,0xbe303d65,0,0,0,0,0xbe303d65,
0x3ce8be37,0,0,0,0,0x3ce8be37,0,0,0,0,0x3ce8be37,0,0,0,0,0x3ce8be37,
0x80003e39,0,0,0,0,0x80003e39,0,0,0,0,0x80003e39,0,0,0,0,0x80003e39,
0xbe03be03,0,0,0,0,0xbe03be03,0,0,0,0,0xbe03be03,0,0,0,0,0xbe03be03,
0x3e163dda,0,0,0,0,0x3e163dda,0,0,0,0,0x3e163dda,0,0,0,0,0x3e163dda,
0xbe253da8,0,0,0,0,0xbe253da8,0,0,0,0,0xbe253da8,0,0,0,0,0xbe253da8,
0x3e390000,0,0,0,0,0x3e390000,0,0,0,0,0x3e390000,0,0,0,0,0x3e390000,
0xbe033e03,0,0,0,0,0xbe033e03,0,0,0,0,0xbe033e03,0,0,0,0,0xbe033e03,
0x3d65be30,0,0,0,0,0x3d65be30,0,0,0,0,0x3d65be30,0,0,0,0,0x3d65be30,
0x3ce83e37,0,0,0,0,0x3ce83e37,0,0,0,0,0x3ce83e37,0,0,0,0,0x3ce83e37,
0x3e163dda,0,0,0,0,0x3e163dda,0,0,0,0,0x3e163dda,0,0,0,0,0x3e163dda,
0xbe25bda8,0,0,0,0,0xbe25bda8,0,0,0,0,0xbe25bda8,0,0,0,0,0xbe25bda8,
0xbddabe16,0,0,0,0,0xbddabe16,0,0,0,0,0xbddabe16,0,0,0,0,0xbddabe16,
0x3e253da8,0,0,0,0,0x3e253da8,0,0,0,0,0x3e253da8,0,0,0,0,0x3e253da8,
0x3e303d65,0,0,0,0,0x3e303d65,0,0,0,0,0x3e303d65,0,0,0,0,0x3e303d65,
0xbe37bce8,0,0,0,0,0xbe37bce8,0,0,0,0,0xbe37bce8,0,0,0,0,0xbe37bce8,
0xbe390000,0,0,0,0,0xbe390000,0,0,0,0,0xbe390000,0,0,0,0,0xbe390000,
0x3e25bda8,0,0,0,0,0x3e25bda8,0,0,0,0,0x3e25bda8,0,0,0,0,0x3e25bda8,
0x3e390000,0,0,0,0,0x3e390000,0,0,0,0,0x3e390000,0,0,0,0,0x3e390000,
0xbe373ce8,0,0,0,0,0xbe373ce8,0,0,0,0,0xbe373ce8,0,0,0,0,0xbe373ce8,
0xbdda3e16,0,0,0,0,0xbdda3e16,0,0,0,0,0xbdda3e16,0,0,0,0,0xbdda3e16,
0x3ce8be37,0,0,0,0,0x3ce8be37,0,0,0,0,0x3ce8be37,0,0,0,0,0x3ce8be37,
0x3e30bd65,0,0,0,0,0x3e30bd65,0,0,0,0,0x3e30bd65,0,0,0,0,0x3e30bd65,
0xbe253da8,0,0,0,0,0xbe253da8,0,0,0,0,0xbe253da8,0,0,0,0,0xbe253da8,
0x3d653e30,0,0,0,0,0x3d653e30,0,0,0,0,0x3d653e30,0,0,0,0,0x3d653e30,
0xbe03be03,0,0,0,0,0xbe03be03,0,0,0,0,0xbe03be03,0,0,0,0,0xbe03be03,
0x3e16bdda,0,0,0,0,0x3e16bdda,0,0,0,0,0x3e16bdda,0,0,0,0,0x3e16bdda,
0xbe033e03,0,0,0,0,0xbe033e03,0,0,0,0,0xbe033e03,0,0,0,0,0xbe033e03,
0x3e303d65,0,0,0,0,0x3e303d65,0,0,0,0,0x3e303d65,0,0,0,0,0x3e303d65,
0xbe373ce8,0,0,0,0,0xbe373ce8,0,0,0,0,0xbe373ce8,0,0,0,0,0xbe373ce8,
0x3ddabe16,0,0,0,0,0x3ddabe16,0,0,0,0,0x3ddabe16,0,0,0,0,0x3ddabe16,
0xbda83e25,0,0,0,0,0xbda83e25,0,0,0,0,0xbda83e25,0,0,0,0,0xbda83e25,
0x3e16bdda,0,0,0,0,0x3e16bdda,0,0,0,0,0x3e16bdda,0,0,0,0,0x3e16bdda,
0xbda83e25,0,0,0,0,0xbda83e25,0,0,0,0,0xbda83e25,0,0,0,0,0xbda83e25,
0x3d65be30,0,0,0,0,0x3d65be30,0,0,0,0,0x3d65be30,0,0,0,0,0x3d65be30,
0xbce83e37,0,0,0,0,0xbce83e37,0,0,0,0,0xbce83e37,0,0,0,0,0xbce83e37,
0,0,0xbe163dda,0,0,0,0,0xbe163dda,0,0,0xbe253da8,0,0,0,0,0xbe253da8,
0,0,0xbe303d65,0,0,0,0,0xbe303d65,0,0,0xbe373ce8,0,0,0,0,0xbe373ce8,
0,0,0xbd65be30,0,0,0,0,0xbd65be30,0,0,0x3ce8be37,0,0,0,0,0x3ce8be37,
0,0,0x3ddabe16,0,0,0,0,0x3ddabe16,0,0,0x3e25bda8,0,0,0,0,0x3e25bda8,
0,0,0xbe390000,0,0,0,0,0xbe390000,0,0,0xbe37bce8,0,0,0,0,0xbe37bce8,
0,0,0xbe30bd65,0,0,0,0,0xbe30bd65,0,0,0xbe25bda8,0,0,0,0,0xbe25bda8,
0,0,0x3e390000,0,0,0,0,0x3e390000,0,0,0x3e253da8,0,0,0,0,0x3e253da8,
0,0,0x3dda3e16,0,0,0,0,0x3dda3e16,0,0,0x3ce83e37,0,0,0,0,0x3ce83e37,
0,0,0xbe16bdda,0,0,0,0,0xbe16bdda,0,0,0xbe03be03,0,0,0,0,0xbe03be03,
0,0,0xbddabe16,0,0,0,0,0xbddabe16,0,0,0xbda8be25,0,0,0,0,0xbda8be25,
0,0,0xbd653e30,0,0,0,0,0xbd653e30,0,0,0xbe033e03,0,0,0,0,0xbe033e03,
0,0,0xbe303d65,0,0,0,0,0xbe303d65,0,0,0xbe37bce8,0,0,0,0,0xbe37bce8,
0,0,0xbd65be30,0,0,0,0,0xbd65be30,0,0,0xbce8be37,0,0,0,0,0xbce8be37,
0,0,0,0,0,0,0,0,0,0,0,0,0,0,0,0,
0,0,0xbe16bdda,0,0,0,0,0xbe16bdda,0,0,0xbda8be25,0,0,0,0,0xbda8be25,
0,0,0,0,0,0,0,0,0,0,0,0,0,0,0,0,
0,0,0x3e390000,0,0,0,0,0x3e390000,0,0,0x3e033e03,0,0,0,0,0x3e033e03,
0,0,0x80003e39,0,0,0,0,0x80003e39,0,0,0xbe033e03,0,0,0,0,0xbe033e03,
0,0,0xbd653e30,0,0,0,0,0xbd653e30,0,0,0xbe373ce8,0,0,0,0,0xbe373ce8,
0,0,0xbddabe16,0,0,0,0,0xbddabe16,0,0,0x3da8be25,0,0,0,0,0x3da8be25,
0,0,0xbe390000,0,0,0,0,0xbe390000,0,0,0xbe03be03,0,0,0,0,0xbe03be03,
0,0,0x8000be39,0,0,0,0,0x8000be39,0,0,0x3e03be03,0,0,0,0,0x3e03be03,
0,0,0x3e390000,0,0,0,0,0x3e390000,0,0,0x3da83e25,0,0,0,0,0x3da83e25,
0,0,0xbdda3e16,0,0,0,0,0xbdda3e16,0,0,0xbe37bce8,0,0,0,0,0xbe37bce8,
0,0,0x3e390000,0,0,0,0,0x3e390000,0,0,0x3e033e03,0,0,0,0,0x3e033e03,
0,0,0x80003e39,0,0,0,0,0x80003e39,0,0,0xbe033e03,0,0,0,0,0xbe033e03,
0,0,0xbd65be30,0,0,0,0,0xbd65be30,0,0,0x3e03be03,0,0,0,0,0x3e03be03,
0,0,0x3e303d65,0,0,0,0,0x3e303d65,0,0,0x3ce83e37,0,0,0,0,0x3ce83e37,
0,0,0xbe390000,0,0,0,0,0xbe390000,0,0,0xbe03be03,0,0,0,0,0xbe03be03,
0,0,0,0,0,0,0,0,0,0,0,0,0,0,0,0,
0,0,0xbe163dda,0,0,0,0,0xbe163dda,0,0,0xbe25bda8,0,0,0,0,0xbe25bda8,
0,0,0,0,0,0,0,0,0,0,0,0,0,0,0,0,
0,0,0xbe16bdda,0,0,0,0,0xbe16bdda,0,0,0x3da8be25,0,0,0,0,0x3da8be25,
0,0,0x3e303d65,0,0,0,0,0x3e303d65,0,0,0xbce83e37,0,0,0,0,0xbce83e37,
0,0,0x3e16bdda,0,0,0,0,0x3e16bdda,0,0,0x3da83e25,0,0,0,0,0x3da83e25,
0,0,0xbe303d65,0,0,0,0,0xbe303d65,0,0,0xbce8be37,0,0,0,0,0xbce8be37,
0,0,0xbe390000,0,0,0,0,0xbe390000,0,0,0xbce8be37,0,0,0,0,0xbce8be37,
0,0,0x3e30bd65,0,0,0,0,0x3e30bd65,0,0,0x3da83e25,0,0,0,0,0x3da83e25,
0,0,0x3e390000,0,0,0,0,0x3e390000,0,0,0xbce83e37,0,0,0,0,0xbce83e37,
0,0,0xbe30bd65,0,0,0,0,0xbe30bd65,0,0,0x3da8be25,0,0,0,0,0x3da8be25,
0,0,0xbe163dda,0,0,0,0,0xbe163dda,0,0,0xbe03be03,0,0,0,0,0xbe03be03,
0,0,0x3ddabe16,0,0,0,0,0x3ddabe16,0,0,0x3e253da8,0,0,0,0,0x3e253da8,
0,0,0x3e163dda,0,0,0,0,0x3e163dda,0,0,0xbe033e03,0,0,0,0,0xbe033e03,
0,0,0xbddabe16,0,0,0,0,0xbddabe16,0,0,0x3e25bda8,0,0,0,0,0x3e25bda8,
0,0,0xbd653e30,0,0,0,0,0xbd653e30,0,0,0xbe37bce8,0,0,0,0,0xbe37bce8,
0,0,0,0,0,0,0,0,0,0,0,0,0,0,0,0,
0,0,0x3d653e30,0,0,0,0,0x3d653e30,0,0,0xbe373ce8,0,0,0,0,0xbe373ce8,
0,0,0,0,0,0,0,0,0,0,0,0,0,0,0,0,
0,0,0x3d653e30,0,0,0,0,0x3d653e30,0,0,0xbe37bce8,0,0,0,0,0xbe37bce8,
0,0,0x3ddabe16,0,0,0,0,0x3ddabe16,0,0,0x3da83e25,0,0,0,0,0x3da83e25,
0,0,0xbe390000,0,0,0,0,0xbe390000,0,0,0x3e03be03,0,0,0,0,0x3e03be03,
0,0,0x80003e39,0,0,0,0,0x80003e39,0,0,0xbe03be03,0,0,0,0,0xbe03be03,
0,0,0xbe390000,0,0,0,0,0xbe390000,0,0,0x3da8be25,0,0,0,0,0x3da8be25,
0,0,0x3dda3e16,0,0,0,0,0x3dda3e16,0,0,0xbe373ce8,0,0,0,0,0xbe373ce8,
0,0,0x3e390000,0,0,0,0,0x3e390000,0,0,0xbe033e03,0,0,0,0,0xbe033e03,
0,0,0x8000be39,0,0,0,0,0x8000be39,0,0,0x3e033e03,0,0,0,0,0x3e033e03,
0,0,0x3d65be30,0,0,0,0,0x3d65be30,0,0,0x3e033e03,0,0,0,0,0x3e033e03,
0,0,0xbe303d65,0,0,0,0,0xbe303d65,0,0,0x3ce8be37,0,0,0,0,0x3ce8be37,
0,0,0xbe390000,0,0,0,0,0xbe390000,0,0,0x3e03be03,0,0,0,0,0x3e03be03,
0,0,0x80003e39,0,0,0,0,0x80003e39,0,0,0xbe03be03,0,0,0,0,0xbe03be03,
0,0,0x3e163dda,0,0,0,0,0x3e163dda,0,0,0xbe253da8,0,0,0,0,0xbe253da8,
0,0,0,0,0,0,0,0,0,0,0,0,0,0,0,0,
0,0,0x3e390000,0,0,0,0,0x3e390000,0,0,0xbe033e03,0,0,0,0,0xbe033e03,
0,0,0,0,0,0,0,0,0,0,0,0,0,0,0,0,
0,0,0x3d65be30,0,0,0,0,0x3d65be30,0,0,0x3ce83e37,0,0,0,0,0x3ce83e37,
0,0,0xbddabe16,0,0,0,0,0xbddabe16,0,0,0x3e253da8,0,0,0,0,0x3e253da8,
0,0,0x3e163dda,0,0,0,0,0x3e163dda,0,0,0xbe25bda8,0,0,0,0,0xbe25bda8,
0,0,0x3e303d65,0,0,0,0,0x3e303d65,0,0,0xbe37bce8,0,0,0,0,0xbe37bce8,
0,0,0xbe390000,0,0,0,0,0xbe390000,0,0,0x3e25bda8,0,0,0,0,0x3e25bda8,
0,0,0xbdda3e16,0,0,0,0,0xbdda3e16,0,0,0x3ce8be37,0,0,0,0,0x3ce8be37,
0,0,0x3e390000,0,0,0,0,0x3e390000,0,0,0xbe373ce8,0,0,0,0,0xbe373ce8,
0,0,0x3e30bd65,0,0,0,0,0x3e30bd65,0,0,0xbe253da8,0,0,0,0,0xbe253da8,
0,0,0x3d653e30,0,0,0,0,0x3d653e30,0,0,0xbe03be03,0,0,0,0,0xbe03be03,
0,0,0x3e303d65,0,0,0,0,0x3e303d65,0,0,0xbe373ce8,0,0,0,0,0xbe373ce8,
0,0,0x3e16bdda,0,0,0,0,0x3e16bdda,0,0,0xbe033e03,0,0,0,0,0xbe033e03,
0,0,0x3ddabe16,0,0,0,0,0x3ddabe16,0,0,0xbda83e25,0,0,0,0,0xbda83e25,
0,0,0x3e16bdda,0,0,0,0,0x3e16bdda,0,0,0xbda83e25,0,0,0,0,0xbda83e25,
0,0,0,0,0,0,0,0,0,0,0,0,0,0,0,0,
0,0,0x3d65be30,0,0,0,0,0x3d65be30,0,0,0xbce83e37,0,0,0,0,0xbce83e37,
0,0,0,0,0,0,0,0,0,0,0,0,0,0,0,0,
};
constexpr unsigned long long COS_PK0 = 0x3f903f9a3fa03fa2ull;
constexpr unsigned long long COS_PK1 = 0x3f133f3e3f653f83ull;
constexpr unsigned long long COS_PK2 = 0x3e4b3ec8ull;

__device__ __forceinline__ void wgmma_ss_n80_z(float (&d)[40], uint64_t da, uint64_t db) {
  asm volatile("{\n.reg .pred p;\nsetp.ne.b32 p, 0, 0;\nwgmma.mma_async.sync.aligned.m64n80k16.f32.bf16.bf16 {%0,%1,%2,%3,%4,%5,%6,%7,%8,%9,%10,%11,%12,%13,%14,%15,%16,%17,%18,%19,%20,%21,%22,%23,%24,%25,%26,%27,%28,%29,%30,%31,%32,%33,%34,%35,%36,%37,%38,%39}, %40, %41, p, 1, 1, 1, 0;\n}\n"
    : "+f"(d[0]), "+f"(d[1]), "+f"(d[2]), "+f"(d[3]), "+f"(d[4]), "+f"(d[5]), "+f"(d[6]), "+f"(d[7]), "+f"(d[8]), "+f"(d[9]), "+f"(d[10]), "+f"(d[11]), "+f"(d[12]), "+f"(d[13]), "+f"(d[14]), "+f"(d[15]), "+f"(d[16]), "+f"(d[17]), "+f"(d[18]), "+f"(d[19]), "+f"(d[20]), "+f"(d[21]), "+f"(d[22]), "+f"(d[23]), "+f"(d[24]), "+f"(d[25]), "+f"(d[26]), "+f"(d[27]), "+f"(d[28]), "+f"(d[29]), "+f"(d[30]), "+f"(d[31]), "+f"(d[32]), "+f"(d[33]), "+f"(d[34]), "+f"(d[35]), "+f"(d[36]), "+f"(d[37]), "+f"(d[38]), "+f"(d[39])
    : "l"(da), "l"(db));
}
__device__ __forceinline__ void wgmma_ss_n80_a(float (&d)[40], uint64_t da, uint64_t db) {
  asm volatile("{\n.reg .pred p;\nsetp.ne.b32 p, 1, 0;\nwgmma.mma_async.sync.aligned.m64n80k16.f32.bf16.bf16 {%0,%1,%2,%3,%4,%5,%6,%7,%8,%9,%10,%11,%12,%13,%14,%15,%16,%17,%18,%19,%20,%21,%22,%23,%24,%25,%26,%27,%28,%29,%30,%31,%32,%33,%34,%35,%36,%37,%38,%39}, %40, %41, p, 1, 1, 1, 0;\n}\n"
    : "+f"(d[0]), "+f"(d[1]), "+f"(d[2]), "+f"(d[3]), "+f"(d[4]), "+f"(d[5]), "+f"(d[6]), "+f"(d[7]), "+f"(d[8]), "+f"(d[9]), "+f"(d[10]), "+f"(d[11]), "+f"(d[12]), "+f"(d[13]), "+f"(d[14]), "+f"(d[15]), "+f"(d[16]), "+f"(d[17]), "+f"(d[18]), "+f"(d[19]), "+f"(d[20]), "+f"(d[21]), "+f"(d[22]), "+f"(d[23]), "+f"(d[24]), "+f"(d[25]), "+f"(d[26]), "+f"(d[27]), "+f"(d[28]), "+f"(d[29]), "+f"(d[30]), "+f"(d[31]), "+f"(d[32]), "+f"(d[33]), "+f"(d[34]), "+f"(d[35]), "+f"(d[36]), "+f"(d[37]), "+f"(d[38]), "+f"(d[39])
    : "l"(da), "l"(db));
}

__device__ __forceinline__ void wgmma_rs_n40_z(float (&d)[20], uint32_t a0, uint32_t a1, uint32_t a2, uint32_t a3, uint64_t db) {
  asm volatile("{\n.reg .pred p;\nsetp.ne.b32 p, 0, 0;\nwgmma.mma_async.sync.aligned.m64n40k16.f32.bf16.bf16 {%0,%1,%2,%3,%4,%5,%6,%7,%8,%9,%10,%11,%12,%13,%14,%15,%16,%17,%18,%19}, {%20,%21,%22,%23}, %24, p, 1, 1, 0;\n}\n"
    : "+f"(d[0]), "+f"(d[1]), "+f"(d[2]), "+f"(d[3]), "+f"(d[4]), "+f"(d[5]), "+f"(d[6]), "+f"(d[7]), "+f"(d[8]), "+f"(d[9]), "+f"(d[10]), "+f"(d[11]), "+f"(d[12]), "+f"(d[13]), "+f"(d[14]), "+f"(d[15]), "+f"(d[16]), "+f"(d[17]), "+f"(d[18]), "+f"(d[19])
    : "r"(a0), "r"(a1), "r"(a2), "r"(a3), "l"(db));
}
__device__ __forceinline__ void wgmma_rs_n40_a(float (&d)[20], uint32_t a0, uint32_t a1, uint32_t a2, uint32_t a3, uint64_t db) {
  asm volatile("{\n.reg .pred p;\nsetp.ne.b32 p, 1, 0;\nwgmma.mma_async.sync.aligned.m64n40k16.f32.bf16.bf16 {%0,%1,%2,%3,%4,%5,%6,%7,%8,%9,%10,%11,%12,%13,%14,%15,%16,%17,%18,%19}, {%20,%21,%22,%23}, %24, p, 1, 1, 0;\n}\n"
    : "+f"(d[0]), "+f"(d[1]), "+f"(d[2]), "+f"(d[3]), "+f"(d[4]), "+f"(d[5]), "+f"(d[6]), "+f"(d[7]), "+f"(d[8]), "+f"(d[9]), "+f"(d[10]), "+f"(d[11]), "+f"(d[12]), "+f"(d[13]), "+f"(d[14]), "+f"(d[15]), "+f"(d[16]), "+f"(d[17]), "+f"(d[18]), "+f"(d[19])
    : "r"(a0), "r"(a1), "r"(a2), "r"(a3), "l"(db));
}

__device__ __forceinline__ void wgmma_rs_n128_z(float (&d)[64], uint32_t a0, uint32_t a1, uint32_t a2, uint32_t a3, uint64_t db) {
  asm volatile("{\n.reg .pred p;\nsetp.ne.b32 p, 0, 0;\nwgmma.mma_async.sync.aligned.m64n128k16.f32.bf16.bf16 {%0,%1,%2,%3,%4,%5,%6,%7,%8,%9,%10,%11,%12,%13,%14,%15,%16,%17,%18,%19,%20,%21,%22,%23,%24,%25,%26,%27,%28,%29,%30,%31,%32,%33,%34,%35,%36,%37,%38,%39,%40,%41,%42,%43,%44,%45,%46,%47,%48,%49,%50,%51,%52,%53,%54,%55,%56,%57,%58,%59,%60,%61,%62,%63}, {%64,%65,%66,%67}, %68, p, 1, 1, 1;\n}\n"
    : "+f"(d[0]), "+f"(d[1]), "+f"(d[2]), "+f"(d[3]), "+f"(d[4]), "+f"(d[5]), "+f"(d[6]), "+f"(d[7]), "+f"(d[8]), "+f"(d[9]), "+f"(d[10]), "+f"(d[11]), "+f"(d[12]), "+f"(d[13]), "+f"(d[14]), "+f"(d[15]), "+f"(d[16]), "+f"(d[17]), "+f"(d[18]), "+f"(d[19]), "+f"(d[20]), "+f"(d[21]), "+f"(d[22]), "+f"(d[23]), "+f"(d[24]), "+f"(d[25]), "+f"(d[26]), "+f"(d[27]), "+f"(d[28]), "+f"(d[29]), "+f"(d[30]), "+f"(d[31]), "+f"(d[32]), "+f"(d[33]), "+f"(d[34]), "+f"(d[35]), "+f"(d[36]), "+f"(d[37]), "+f"(d[38]), "+f"(d[39]), "+f"(d[40]), "+f"(d[41]), "+f"(d[42]), "+f"(d[43]), "+f"(d[44]), "+f"(d[45]), "+f"(d[46]), "+f"(d[47]), "+f"(d[48]), "+f"(d[49]), "+f"(d[50]), "+f"(d[51]), "+f"(d[52]), "+f"(d[53]), "+f"(d[54]), "+f"(d[55]), "+f"(d[56]), "+f"(d[57]), "+f"(d[58]), "+f"(d[59]), "+f"(d[60]), "+f"(d[61]), "+f"(d[62]), "+f"(d[63])
    : "r"(a0), "r"(a1), "r"(a2), "r"(a3), "l"(db));
}
__device__ __forceinline__ void wgmma_rs_n128_a(float (&d)[64], uint32_t a0, uint32_t a1, uint32_t a2, uint32_t a3, uint64_t db) {
  asm volatile("{\n.reg .pred p;\nsetp.ne.b32 p, 1, 0;\nwgmma.mma_async.sync.aligned.m64n128k16.f32.bf16.bf16 {%0,%1,%2,%3,%4,%5,%6,%7,%8,%9,%10,%11,%12,%13,%14,%15,%16,%17,%18,%19,%20,%21,%22,%23,%24,%25,%26,%27,%28,%29,%30,%31,%32,%33,%34,%35,%36,%37,%38,%39,%40,%41,%42,%43,%44,%45,%46,%47,%48,%49,%50,%51,%52,%53,%54,%55,%56,%57,%58,%59,%60,%61,%62,%63}, {%64,%65,%66,%67}, %68, p, 1, 1, 1;\n}\n"
    : "+f"(d[0]), "+f"(d[1]), "+f"(d[2]), "+f"(d[3]), "+f"(d[4]), "+f"(d[5]), "+f"(d[6]), "+f"(d[7]), "+f"(d[8]), "+f"(d[9]), "+f"(d[10]), "+f"(d[11]), "+f"(d[12]), "+f"(d[13]), "+f"(d[14]), "+f"(d[15]), "+f"(d[16]), "+f"(d[17]), "+f"(d[18]), "+f"(d[19]), "+f"(d[20]), "+f"(d[21]), "+f"(d[22]), "+f"(d[23]), "+f"(d[24]), "+f"(d[25]), "+f"(d[26]), "+f"(d[27]), "+f"(d[28]), "+f"(d[29]), "+f"(d[30]), "+f"(d[31]), "+f"(d[32]), "+f"(d[33]), "+f"(d[34]), "+f"(d[35]), "+f"(d[36]), "+f"(d[37]), "+f"(d[38]), "+f"(d[39]), "+f"(d[40]), "+f"(d[41]), "+f"(d[42]), "+f"(d[43]), "+f"(d[44]), "+f"(d[45]), "+f"(d[46]), "+f"(d[47]), "+f"(d[48]), "+f"(d[49]), "+f"(d[50]), "+f"(d[51]), "+f"(d[52]), "+f"(d[53]), "+f"(d[54]), "+f"(d[55]), "+f"(d[56]), "+f"(d[57]), "+f"(d[58]), "+f"(d[59]), "+f"(d[60]), "+f"(d[61]), "+f"(d[62]), "+f"(d[63])
    : "r"(a0), "r"(a1), "r"(a2), "r"(a3), "l"(db));
}

__device__ __forceinline__ void wgmma_rs_n32_z(float (&d)[16], uint32_t a0, uint32_t a1, uint32_t a2, uint32_t a3, uint64_t db) {
  asm volatile("{\n.reg .pred p;\nsetp.ne.b32 p, 0, 0;\nwgmma.mma_async.sync.aligned.m64n32k16.f32.bf16.bf16 {%0,%1,%2,%3,%4,%5,%6,%7,%8,%9,%10,%11,%12,%13,%14,%15}, {%16,%17,%18,%19}, %20, p, 1, 1, 0;\n}\n"
    : "+f"(d[0]), "+f"(d[1]), "+f"(d[2]), "+f"(d[3]), "+f"(d[4]), "+f"(d[5]), "+f"(d[6]), "+f"(d[7]), "+f"(d[8]), "+f"(d[9]), "+f"(d[10]), "+f"(d[11]), "+f"(d[12]), "+f"(d[13]), "+f"(d[14]), "+f"(d[15])
    : "r"(a0), "r"(a1), "r"(a2), "r"(a3), "l"(db));
}
__device__ __forceinline__ void wgmma_rs_n32_a(float (&d)[16], uint32_t a0, uint32_t a1, uint32_t a2, uint32_t a3, uint64_t db) {
  asm volatile("{\n.reg .pred p;\nsetp.ne.b32 p, 1, 0;\nwgmma.mma_async.sync.aligned.m64n32k16.f32.bf16.bf16 {%0,%1,%2,%3,%4,%5,%6,%7,%8,%9,%10,%11,%12,%13,%14,%15}, {%16,%17,%18,%19}, %20, p, 1, 1, 0;\n}\n"
    : "+f"(d[0]), "+f"(d[1]), "+f"(d[2]), "+f"(d[3]), "+f"(d[4]), "+f"(d[5]), "+f"(d[6]), "+f"(d[7]), "+f"(d[8]), "+f"(d[9]), "+f"(d[10]), "+f"(d[11]), "+f"(d[12]), "+f"(d[13]), "+f"(d[14]), "+f"(d[15])
    : "r"(a0), "r"(a1), "r"(a2), "r"(a3), "l"(db));
}

__device__ __forceinline__ void wgmma_rs_n64_z(float (&d)[32], uint32_t a0, uint32_t a1, uint32_t a2, uint32_t a3, uint64_t db) {
  asm volatile("{\n.reg .pred p;\nsetp.ne.b32 p, 0, 0;\nwgmma.mma_async.sync.aligned.m64n64k16.f32.bf16.bf16 {%0,%1,%2,%3,%4,%5,%6,%7,%8,%9,%10,%11,%12,%13,%14,%15,%16,%17,%18,%19,%20,%21,%22,%23,%24,%25,%26,%27,%28,%29,%30,%31}, {%32,%33,%34,%35}, %36, p, 1, 1, 0;\n}\n"
    : "+f"(d[0]), "+f"(d[1]), "+f"(d[2]), "+f"(d[3]), "+f"(d[4]), "+f"(d[5]), "+f"(d[6]), "+f"(d[7]), "+f"(d[8]), "+f"(d[9]), "+f"(d[10]), "+f"(d[11]), "+f"(d[12]), "+f"(d[13]), "+f"(d[14]), "+f"(d[15]), "+f"(d[16]), "+f"(d[17]), "+f"(d[18]), "+f"(d[19]), "+f"(d[20]), "+f"(d[21]), "+f"(d[22]), "+f"(d[23]), "+f"(d[24]), "+f"(d[25]), "+f"(d[26]), "+f"(d[27]), "+f"(d[28]), "+f"(d[29]), "+f"(d[30]), "+f"(d[31])
    : "r"(a0), "r"(a1), "r"(a2), "r"(a3), "l"(db));
}
__device__ __forceinline__ void wgmma_rs_n64_a(float (&d)[32], uint32_t a0, uint32_t a1, uint32_t a2, uint32_t a3, uint64_t db) {
  asm volatile("{\n.reg .pred p;\nsetp.ne.b32 p, 1, 0;\nwgmma.mma_async.sync.aligned.m64n64k16.f32.bf16.bf16 {%0,%1,%2,%3,%4,%5,%6,%7,%8,%9,%10,%11,%12,%13,%14,%15,%16,%17,%18,%19,%20,%21,%22,%23,%24,%25,%26,%27,%28,%29,%30,%31}, {%32,%33,%34,%35}, %36, p, 1, 1, 0;\n}\n"
    : "+f"(d[0]), "+f"(d[1]), "+f"(d[2]), "+f"(d[3]), "+f"(d[4]), "+f"(d[5]), "+f"(d[6]), "+f"(d[7]), "+f"(d[8]), "+f"(d[9]), "+f"(d[10]), "+f"(d[11]), "+f"(d[12]), "+f"(d[13]), "+f"(d[14]), "+f"(d[15]), "+f"(d[16]), "+f"(d[17]), "+f"(d[18]), "+f"(d[19]), "+f"(d[20]), "+f"(d[21]), "+f"(d[22]), "+f"(d[23]), "+f"(d[24]), "+f"(d[25]), "+f"(d[26]), "+f"(d[27]), "+f"(d[28]), "+f"(d[29]), "+f"(d[30]), "+f"(d[31])
    : "r"(a0), "r"(a1), "r"(a2), "r"(a3), "l"(db));
}

__device__ __forceinline__ void wgmma_ss_n32_z(float (&d)[16], uint64_t da, uint64_t db) {
  asm volatile("{\n.reg .pred p;\nsetp.ne.b32 p, 0, 0;\nwgmma.mma_async.sync.aligned.m64n32k16.f32.bf16.bf16 {%0,%1,%2,%3,%4,%5,%6,%7,%8,%9,%10,%11,%12,%13,%14,%15}, %16, %17, p, 1, 1, 1, 0;\n}\n"
    : "+f"(d[0]), "+f"(d[1]), "+f"(d[2]), "+f"(d[3]), "+f"(d[4]), "+f"(d[5]), "+f"(d[6]), "+f"(d[7]), "+f"(d[8]), "+f"(d[9]), "+f"(d[10]), "+f"(d[11]), "+f"(d[12]), "+f"(d[13]), "+f"(d[14]), "+f"(d[15])
    : "l"(da), "l"(db));
}
__device__ __forceinline__ void wgmma_ss_n32_a(float (&d)[16], uint64_t da, uint64_t db) {
  asm volatile("{\n.reg .pred p;\nsetp.ne.b32 p, 1, 0;\nwgmma.mma_async.sync.aligned.m64n32k16.f32.bf16.bf16 {%0,%1,%2,%3,%4,%5,%6,%7,%8,%9,%10,%11,%12,%13,%14,%15}, %16, %17, p, 1, 1, 1, 0;\n}\n"
    : "+f"(d[0]), "+f"(d[1]), "+f"(d[2]), "+f"(d[3]), "+f"(d[4]), "+f"(d[5]), "+f"(d[6]), "+f"(d[7]), "+f"(d[8]), "+f"(d[9]), "+f"(d[10]), "+f"(d[11]), "+f"(d[12]), "+f"(d[13]), "+f"(d[14]), "+f"(d[15])
    : "l"(da), "l"(db));
}

__device__ __forceinline__ void wgmma_ss_n40_z(float (&d)[20], uint64_t da, uint64_t db) {
  asm volatile("{\n.reg .pred p;\nsetp.ne.b32 p, 0, 0;\nwgmma.mma_async.sync.aligned.m64n40k16.f32.bf16.bf16 {%0,%1,%2,%3,%4,%5,%6,%7,%8,%9,%10,%11,%12,%13,%14,%15,%16,%17,%18,%19}, %20, %21, p, 1, 1, 1, 0;\n}\n"
    : "+f"(d[0]), "+f"(d[1]), "+f"(d[2]), "+f"(d[3]), "+f"(d[4]), "+f"(d[5]), "+f"(d[6]), "+f"(d[7]), "+f"(d[8]), "+f"(d[9]), "+f"(d[10]), "+f"(d[11]), "+f"(d[12]), "+f"(d[13]), "+f"(d[14]), "+f"(d[15]), "+f"(d[16]), "+f"(d[17]), "+f"(d[18]), "+f"(d[19])
    : "l"(da), "l"(db));
}
__device__ __forceinline__ void wgmma_ss_n40_a(float (&d)[20], uint64_t da, uint64_t db) {
  asm volatile("{\n.reg .pred p;\nsetp.ne.b32 p, 1, 0;\nwgmma.mma_async.sync.aligned.m64n40k16.f32.bf16.bf16 {%0,%1,%2,%3,%4,%5,%6,%7,%8,%9,%10,%11,%12,%13,%14,%15,%16,%17,%18,%19}, %20, %21, p, 1, 1, 1, 0;\n}\n"
    : "+f"(d[0]), "+f"(d[1]), "+f"(d[2]), "+f"(d[3]), "+f"(d[4]), "+f"(d[5]), "+f"(d[6]), "+f"(d[7]), "+f"(d[8]), "+f"(d[9]), "+f"(d[10]), "+f"(d[11]), "+f"(d[12]), "+f"(d[13]), "+f"(d[14]), "+f"(d[15]), "+f"(d[16]), "+f"(d[17]), "+f"(d[18]), "+f"(d[19])
    : "l"(da), "l"(db));
}

constexpr int NSM = 132, NH = 66;
constexpr int S0 = 0, S1 = 51200, S2 = 102400;
constexpr int C1 = 153600, C3 = C1, RG = C1 + 18432;
constexpr int WP = RG, TBL = RG + 28672, WS2 = RG + 30720;
constexpr int BARS = RG + 49152;
__host__ __device__ constexpr int wst_off(int i) { return i < 12 ? S2 + i * 4096 : WS2 + (i - 12) * 4096; }
constexpr int NBAR = 280;
constexpr int REL = BARS + NBAR * 8;
constexpr int SMEM_BYTES = REL + 16;
constexpr int B_XF = 0, B_CF1 = 15, B_CF3 = 16, B_WF = 17  , B_P1D = 18, B_WFREE = 20, B_REL = 21, B_ROLE = 22, B_X1 = 23, B_SIG = 24;
constexpr int B_RF = 32, B_RE = 46, B_YF = 60, B_WRD = 75, B_SFREE = 89, B_WCH = 131, B_RDY = 136, B_WE = 205, B_WL = 217, B_FIN = 229, B_TOK = 232;
constexpr int R_P2 = 15, R_P3 = 57;
constexpr int CNT_P1 = 0, CNT_P2 = 4, CNT_W = 8, CNT_RANK = 9, NCLS = 10, CNT_DONE = 0, CNT_REL = 1, NCNT = 2;
constexpr int SIG_W = 0, SIG_P1 = 1, SIG_P2 = 4;
#define PROBES 1
#define WB 100
#define PACE 0
#define PACE_SLACK 300
#define SWIN 3
#define X1AT 10
#define WARMUP 0
#define YPACE 0
#define POLL3 0
#define XPF 0
#define PSLEEP 0
#define TRICKLE
#define T1MASK 0x3e00
#define T2MASK 0x1f00
#define Y0AT 1
#define Y3FROM 1
#define EM58 2
#define TOKD 1
#define TOKM 6
#define X1BOX 0
#define X2BOX 5

__device__ uint4 g_scr[(14 << 21) / 16];
__device__ uint4 g_wf[200 * 72 * 32];
__device__ unsigned g_cnt[NCNT * 32];
__device__ __forceinline__ int slot_line(int chunk, int pg, int cls) {
    return (pg & 1) << 6 | (pg >> 1) << 9 | (chunk & 1) << 10 | (chunk >> 1) << 12 | ((pg ^ (pg >> 1) ^ chunk ^ (chunk >> 1) ^ cls) & 1) << 5;
}
__device__ __forceinline__ int phi_line(int phi, uint32_t rel) {
    return (phi >> 4) << 14 | (phi & 3) << 7 | ((phi >> 2) & 1) << 11 | ((phi >> 3) & 1) << 13 | ((rel >> (phi >> 4)) & 1) << 5;
}
__device__ __forceinline__ int extra_mask(int rk) { return rk < 58 ? 0 : rk < 60 ? EM58 : rk < 62 ? 1 : rk < 64 ? (EM58 == 2 ? 4 : 2) : (EM58 == 8 ? 4 : 8); }
__device__ __forceinline__ int wslot(int pc) {
    return (int)((0x645702651430ull >> (4 * pc)) & 3) * 12288 + (((0x645702651430ull >> (4 * pc)) & 4) ? S0 : RG);
}
__device__ __forceinline__ int xslot(int n) { return ((n & 4) ? S2 : RG) + ((n + 1) & 3) * 12288; }
__device__ __forceinline__ int extra_phi(int rk) { return 198 + (rk & 1); }
__host__ __device__ constexpr int quad_off(int Q) { return (Q >> 2) * 4096 + (Q & 3) * 512; }

#define PROF(k)
#define PROFW(k)
#define prof_dump()
struct Maps { CUtensorMap w, x34, x6, x28, wst, f16, f8, y4, y2; };
struct Ptrs { char* scr; const char* wf; const void* tab1; const void* tab3; unsigned* cnt; };

__device__ __forceinline__ uint32_t smem_u32(const void* p) { return (uint32_t)__cvta_generic_to_shared(p); }
__device__ __forceinline__ void mbar_wait(uint32_t bar) {
    uint32_t ok, it = 0;
    do {
        asm volatile("{\n.reg .pred p;\nmbarrier.try_wait.parity.shared::cta.b64 p, [%1], 0;\nselp.u32 %0, 1, 0, p;\n}" : "=r"(ok) : "r"(bar) : "memory");
        if (++it > (1u << 22)) break;
    } while (!ok);
}
__device__ __forceinline__ bool mbar_test(uint32_t bar) {
    uint32_t ok;
    asm volatile("{\n.reg .pred p;\nmbarrier.test_wait.parity.shared::cta.b64 p, [%1], 0;\nselp.u32 %0, 1, 0, p;\n}" : "=r"(ok) : "r"(bar) : "memory");
    return ok;
}
__device__ __forceinline__ void fence_async() { asm volatile("fence.proxy.async;" ::: "memory"); }
__device__ __forceinline__ void fence_async_smem() { asm volatile("fence.proxy.async.shared::cta;" ::: "memory"); }
#define ELECT "{\n.reg .pred p;\nelect.sync _|p, 0xffffffff;\n@p "
__device__ __forceinline__ void e_arrive(uint32_t bar) { asm volatile(ELECT "mbarrier.arrive.shared::cta.b64 _, [%0];\n}" :: "r"(bar) : "memory"); }
__device__ __forceinline__ void e_expect(uint32_t bar, uint32_t bytes) { asm volatile(ELECT "mbarrier.arrive.expect_tx.shared::cta.b64 _, [%0], %1;\n}" :: "r"(bar), "r"(bytes) : "memory"); }
__device__ __forceinline__ void e_g2s(uint32_t dst, const void* src, uint32_t bytes, uint32_t bar) {
    asm volatile(ELECT "cp.async.bulk.shared::cluster.global.mbarrier::complete_tx::bytes [%0], [%1], %2, [%3];\n}" :: "r"(dst), "l"(src), "r"(bytes), "r"(bar) : "memory");
}
__device__ __forceinline__ void e_s2g(void* dst, uint32_t src, uint32_t bytes) {
    asm volatile(ELECT "cp.async.bulk.global.shared::cta.bulk_group [%0], [%1], %2;\n}" :: "l"(dst), "r"(src), "r"(bytes) : "memory");
}
__device__ __forceinline__ void e_ld3(uint32_t dst, const CUtensorMap* m, int c0, int c1, int c2, uint32_t bar) {
    asm volatile(ELECT "cp.async.bulk.tensor.3d.shared::cluster.global.mbarrier::complete_tx::bytes [%0], [%1, {%3, %4, %5}], [%2];\n}"
                 :: "r"(dst), "l"(m), "r"(bar), "r"(c0), "r"(c1), "r"(c2) : "memory");
}
__device__ __forceinline__ void e_ld4(uint32_t dst, const CUtensorMap* m, int c0, int c3, uint32_t bar) {
    asm volatile(ELECT "cp.async.bulk.tensor.4d.shared::cluster.global.mbarrier::complete_tx::bytes [%0], [%1, {%3, %5, %5, %4}], [%2];\n}"
                 :: "r"(dst), "l"(m), "r"(bar), "r"(c0), "r"(c3), "r"(0) : "memory");
}
__device__ __forceinline__ void e_st3(const CUtensorMap* m, uint32_t src, int c0, int c1, int c2) {
    asm volatile(ELECT "cp.async.bulk.tensor.3d.global.shared::cta.bulk_group [%0, {%2, %3, %4}], [%1];\n}" :: "l"(m), "r"(src), "r"(c0), "r"(c1), "r"(c2) : "memory");
}
__device__ __forceinline__ void e_ld5(uint32_t dst, const CUtensorMap* m, int c4, uint32_t bar) {
    asm volatile(ELECT "cp.async.bulk.tensor.5d.shared::cluster.global.mbarrier::complete_tx::bytes [%0], [%1, {%4, %4, %4, %4, %3}], [%2];\n}"
                 :: "r"(dst), "l"(m), "r"(bar), "r"(c4), "r"(0) : "memory");
}
__device__ __forceinline__ void e_st5(const CUtensorMap* m, uint32_t src, int c4) {
    asm volatile(ELECT "cp.async.bulk.tensor.5d.global.shared::cta.bulk_group [%0, {%3, %3, %3, %3, %2}], [%1];\n}" :: "l"(m), "r"(src), "r"(c4), "r"(0) : "memory");
}
__device__ __forceinline__ void bulk_commit() { asm volatile("cp.async.bulk.commit_group;" ::: "memory"); }
template <int N> __device__ __forceinline__ void bulk_wait_read() { asm volatile("cp.async.bulk.wait_group.read %0;" :: "n"(N) : "memory"); }
__device__ __forceinline__ void wg_bar(int id) { asm volatile("bar.sync %0, 128;" :: "r"(id) : "memory"); }
__device__ __forceinline__ void bb_break(uint32_t v) { asm volatile("{\n.reg .pred p;\nsetp.eq.u32 p, %0, 0x7fc17fc1;\n@p nanosleep.u32 0;\n}" :: "r"(v) : "memory"); }
__device__ __forceinline__ uint32_t uni(uint32_t v) { return __shfl_sync(0xffffffffu, v, 0); }
__device__ __forceinline__ char* cls_cnt(char* scr, int cls) { return scr + slot_line(3, 2, cls) * 128; }
__device__ __forceinline__ uint32_t cnt_wait(const void* p, unsigned target) {
    auto ld = [&]() { unsigned v; asm volatile("ld.relaxed.gpu.global.u32 %0, [%1];" : "=r"(v) : "l"(p) : "memory"); return v; };
    unsigned v0 = ld(), v;
#pragma unroll 1
    for (unsigned it = 0; it < (1u << 22); it++) { if ((v = uni(v0)) >= target) break; if (PSLEEP) __nanosleep(PSLEEP); v0 = ld(); }
    return v;
}
__device__ __forceinline__ void wg_fence() { asm volatile("wgmma.fence.sync.aligned;" ::: "memory"); }
__device__ __forceinline__ void wg_commit() { asm volatile("wgmma.commit_group.sync.aligned;" ::: "memory"); }
template <int N> __device__ __forceinline__ void wg_wait() { asm volatile("wgmma.wait_group.sync.aligned %0;" :: "n"(N) : "memory"); }
template <int N> __device__ __forceinline__ void reg_fence(float (&d)[N]) {
#pragma unroll
    for (int i = 0; i < N; i++) asm volatile("" : "+f"(d[i]) :: "memory");
}
template <int N, int O, int M> __device__ __forceinline__ float (&sub(float (&d)[M]))[N] { return *reinterpret_cast<float (*)[N]>(&d[O]); }
template <int N> __device__ __forceinline__ void zero(float (&d)[N]) {
#pragma unroll
    for (int i = 0; i < N; i++) d[i] = 0.f;
}
__device__ __forceinline__ uint32_t pack2(float lo, float hi) {
    uint32_t r; asm volatile("cvt.rn.bf16x2.f32 %0, %1, %2;" : "=r"(r) : "f"(hi), "f"(lo)); return r;
}
__device__ __forceinline__ void stm4(uint32_t a, uint32_t r0, uint32_t r1, uint32_t r2, uint32_t r3) {
    asm volatile("stmatrix.sync.aligned.m8n8.x4.trans.shared.b16 [%0], {%1,%2,%3,%4};" :: "r"(a), "r"(r0), "r"(r1), "r"(r2), "r"(r3) : "memory");
}
__device__ __forceinline__ void stm2(uint32_t a, uint32_t r0, uint32_t r1) {
    asm volatile("stmatrix.sync.aligned.m8n8.x2.trans.shared.b16 [%0], {%1,%2};" :: "r"(a), "r"(r0), "r"(r1) : "memory");
}
__device__ __forceinline__ void stm1(uint32_t a, uint32_t r0) {
    asm volatile("stmatrix.sync.aligned.m8n8.x1.trans.shared.b16 [%0], {%1};" :: "r"(a), "r"(r0) : "memory");
}
struct Desc {
    uint32_t lo, hi;
    __device__ __forceinline__ operator uint64_t() const { return ((uint64_t)hi << 32) | lo; }
    __device__ __forceinline__ Desc operator+(uint32_t o) const { return Desc{lo + o, hi}; }
    __device__ __forceinline__ Desc operator^(uint32_t o) const { return Desc{lo ^ o, hi}; }
};
__device__ __forceinline__ Desc mkdesc(uint32_t addr, uint32_t lbo, uint32_t sbo, uint32_t swz) {
    return Desc{((addr & 0x3FFFF) >> 4) | ((lbo >> 4) << 16), (sbo >> 4) | (swz << 30)};
}
__device__ __forceinline__ uint32_t cos_bits(int k) {
    if (k > 20) k = 40 - k;
    const bool neg = k > 10;
    if (neg) k = 20 - k;
    const unsigned long long pk = k < 4 ? COS_PK0 : k < 8 ? COS_PK1 : COS_PK2;
    return (uint32_t)((pk >> (16 * (k & 3))) & 0xffff) ^ (neg ? 0x8000u : 0u);
}

__device__ __forceinline__ void task_w(int wg, int k, uint32_t sb) {
    const int tid = threadIdx.x & 127, w = uni(tid >> 5), lane = tid & 31, q = lane & 3;
    const int tb = 14 * k, t1 = min(tb + 14, 1800), cb0 = tb / 25;
    float acc[64];
    zero(acc);
    const int oc0 = tb - 25 * cb0, Lt = t1 - tb, L0 = min(Lt, 25 - oc0), n0 = (L0 + 3) >> 2;
    uint32_t a[2][4][4];
    auto gen = [&](uint32_t (&a)[4][4], int at) {
        const int phi = 8 * ((at < n0 ? oc0 + 4 * at : 4 * (at - n0)) + w) + (lane >> 2), f = (phi * 205) >> 12;
        const uint32_t ca = 8 * f + 4, cw = (phi - 20 * f) * 8, p0 = sb + TBL + cw * 2 * q;
#pragma unroll
        for (int kh = 0; kh < 7; kh++) {
            uint32_t v0, v1;
            asm volatile("ld.shared.u32 %0, [%1];" : "=r"(v0) : "r"(p0 + ca * kh));
            asm volatile("ld.shared.u32 %0, [%1];" : "=r"(v1) : "r"(p0 + cw + ca * kh));
            const int h = kh == 6 ? 1 : kh & 1;
            a[kh >> 1][2 * h] = __byte_perm(v0, v1, 0x5410);
            a[kh >> 1][2 * h + 1] = __byte_perm(v0, v1, 0x7632);
        }
        a[3][0] = 0; a[3][1] = 0;
    };
    gen(a[0], wg);
    if (wg) gen(a[1], wg + 2);
    PROFW(wg == 0 ? 124 : 127);
#pragma unroll 1
    for (int n = 0; n < 2; n++) {
        const int at = wg + 2 * n, i0 = at < n0 ? 4 * at : L0 + 4 * (at - n0), cnt = (at < n0 ? L0 : Lt) - i0, cb = cb0 + (at >= n0);
        if (cnt <= 0 || (n && !wg)) break;
        if (n) {
#pragma unroll
            for (int j = 0; j < 16; j++) a[0][j >> 2][j & 3] = a[1][j >> 2][j & 3];
        }
        const Desc dB = mkdesc(sb + WP + (cb - cb0) * 14336, 3584, 512, 2);
        if (at) mbar_wait(sb + BARS + 8 * (B_WCH + at - 1));
        mbar_wait(sb + BARS + 8 * (B_WF + 2 * (cb - cb0)));
        PROFW(at == 0 ? 125 : 127);
        wg_fence();
        wgmma_rs_n128_z(acc, a[0][0][0], a[0][0][1], a[0][0][2], a[0][0][3], dB);
        wgmma_rs_n128_a(acc, a[0][1][0], a[0][1][1], a[0][1][2], a[0][1][3], dB + (uint32_t)(16 * 64 >> 4));
        wgmma_rs_n128_a(acc, a[0][2][0], a[0][2][1], a[0][2][2], a[0][2][3], dB + (uint32_t)(32 * 64 >> 4));
        wgmma_rs_n128_a(acc, a[0][3][0], a[0][3][1], a[0][3][2], a[0][3][3], dB + (uint32_t)(40 * 64 >> 4));
        wg_commit();
        wg_wait<0>();
        reg_fence(acc);
        PROFW(at == 0 ? 120 : 127);
        e_arrive(sb + BARS + 8 * (B_WCH + at));
        if (w < cnt) {
            const uint32_t dst = sb + wst_off(i0 + w) + (lane >> 2) * 512 + (lane & 4) * 16 + ((q ^ cb) & 3) * 16;
#pragma unroll
            for (int j = 0; j < 4; j++)
#pragma unroll
                for (int e = 0; e < 2; e++)
                    asm volatile("st.shared.v4.u32 [%0], {%1,%2,%3,%4};" :: "r"((dst ^ (e * 64)) + j * 128),
                                 "r"(pack2(acc[4 * j + e], acc[16 + 4 * j + e])), "r"(pack2(acc[4 * j + 2 + e], acc[16 + 4 * j + 2 + e])),
                                 "r"(pack2(acc[32 + 4 * j + e], acc[48 + 4 * j + e])), "r"(pack2(acc[32 + 4 * j + 2 + e], acc[48 + 4 * j + 2 + e])) : "memory");
            fence_async_smem();
            e_arrive(sb + BARS + 8 * (B_WRD + i0 + w));
        }
    }
}

__device__ __forceinline__ void task_p1(int wg, int pair, uint32_t sb) {
    const int tid = threadIdx.x & 127, w = tid >> 5, lane = tid & 31;
    const uint32_t buf = sb + wg * 51200, bars = sb + BARS;
    uint32_t fr[5][10][2];
    float A[40], d[20];
    zero(A);
    {
        const Desc dA = mkdesc(buf, 3584, 512, 2), dB = mkdesc(sb + C1, 128, 256, 0);
        auto issue = [&](int g, float (&d)[40]) {
            mbar_wait(bars + 8 * (B_XF + wg * 5 + g));
            wg_fence();
            wgmma_ss_n80_z(d, dA + (uint32_t)(g * 8704 >> 4), dB);
#pragma unroll
            for (int j = 1; j < 5; j++) wgmma_ss_n80_a(d, dA + (uint32_t)((g * 8704 + j * 1024) >> 4), dB + (uint32_t)(j * 2560 >> 4));
            wg_commit();
        };
        auto pack = [&](int g, float (&d)[40]) {
            reg_fence(d);
#pragma unroll
            for (int f = 0; f < 10; f++) {
                fr[g][f][0] = pack2(d[4 * f], d[4 * f + 1]);
                fr[g][f][1] = pack2(d[4 * f + 2], d[4 * f + 3]);
            }
        };
        mbar_wait(bars + 8 * B_CF1);
#pragma unroll
        for (int g = 0; g < 4; g++) { issue(g, A); if (g == 0) PROFW(8 + wg * 8 + 1); wg_wait<0>(); pack(g, A); }
        zero(d);
        mbar_wait(bars + 8 * (B_XF + wg * 5 + 4));
#pragma unroll
        for (int h = 0; h < 2; h++) {
            wg_fence();
            wgmma_ss_n40_z(d, dA + (uint32_t)(4 * 8704 >> 4), dB + (uint32_t)(h * 1280 >> 4));
#pragma unroll
            for (int j = 1; j < 5; j++) wgmma_ss_n40_a(d, dA + (uint32_t)((4 * 8704 + j * 1024) >> 4), dB + (uint32_t)((j * 2560 + h * 1280) >> 4));
            wg_commit(); wg_wait<0>(); reg_fence(d);
#pragma unroll
            for (int f = 0; f < 5; f++) { fr[4][5 * h + f][0] = pack2(d[4 * f], d[4 * f + 1]); fr[4][5 * h + f][1] = pack2(d[4 * f + 2], d[4 * f + 3]); }
        }
    }
    bb_break(sb);
    wg_bar(1 + wg);
    PROFW(8 + wg * 8 + 2);
    {
        const Desc dB = mkdesc(sb + C1 + 12800, 128, 256, 0);
        const int i = lane & 7, mi = lane >> 3, th = w >> 1, tz = (2 * pair + th) & 3;
        const uint32_t s0 = buf + (i >> 1) * 128 + (i & 1) * 64 + (((2 * (w & 1) + (mi & 1)) ^ tz ^ (i >> 1)) << 4);
        const uint32_t sA = s0 + th * 2048 + (mi >> 1) * 512, sB = s0 + th * 2048 + (mi >> 1) * 2560, sC = s0 + th * 1024 + (mi >> 1) * 512;
        auto issue = [&](int f, float (&d)[20]) {
            wg_fence();
            wgmma_rs_n40_z(d, fr[0][f][0], fr[0][f][1], fr[1][f][0], fr[1][f][1], dB);
            wgmma_rs_n40_a(d, fr[2][f][0], fr[2][f][1], fr[3][f][0], fr[3][f][1], dB + (uint32_t)(1280 >> 4));
            wgmma_rs_n40_a(d, fr[4][f % 5][0], fr[4][f % 5][1], fr[4][f % 5 + 5][0], fr[4][f % 5 + 5][1], dB + (uint32_t)((2560 + (f / 5) * 1280) >> 4));
            wg_commit();
        };
#pragma unroll
        for (int f = 0; f < 10; f++) {
                        issue(f, d); wg_wait<0>(); reg_fence(d);
            const int Q = 5 * f;
            stm4(((Q & 3) == 3 ? sB : sA) + quad_off(Q), pack2(d[0], d[1]), pack2(d[2], d[3]), pack2(d[4], d[5]), pack2(d[6], d[7]));
            stm2(sA + quad_off(Q + 2), pack2(d[8], d[9]), pack2(d[10], d[11]));
            stm4((f == 9 ? sC : ((Q + 3) & 3) == 3 ? sB : sA) + quad_off(Q + 3), pack2(d[12], d[13]), pack2(d[14], d[15]), pack2(d[16], d[17]), pack2(d[18], d[19]));
            if (f & 1) { fence_async_smem(); e_arrive(bars + 8 * (B_RDY + wg * 5 + (f >> 1))); }
        }
    }
}

__device__ __forceinline__ void task_p2(int wg, int rk, uint32_t sb) {
    const int tid = threadIdx.x & 127, w = tid >> 5, lane = tid & 31;
    const uint32_t bars = sb + BARS;
    const int phi0 = 3 * rk, phiE = extra_phi(rk), mE = extra_mask(rk);
    uint4 wA[6], wB[6], wC[6], wE[6];
    auto ldw = [&](uint4 (&a)[6], int j, int phi) {
        const int pc = 3 * j + wg;
        const uint32_t p = sb + wslot(pc) + (lane & 3) * 512 + w * 128 + (((lane >> 2) ^ phi) & 1) * 64 + (((lane >> 3) ^ lane) & 3) * 16 + (phi & 1) * 8;
        mbar_wait(bars + 8 * (B_WL + pc));
#pragma unroll
        for (int s = 0; s < 6; s++) {
            asm volatile("ld.shared.v2.u32 {%0, %1}, [%2];" : "=r"(a[s].x), "=r"(a[s].y) : "r"(p + s * 2048) : "memory");
            asm volatile("ld.shared.v2.u32 {%0, %1}, [%2];" : "=r"(a[s].z), "=r"(a[s].w) : "r"((p ^ 8) + s * 2048) : "memory");
        }
        uint32_t dep = 0;
#pragma unroll
        for (int s = 0; s < 6; s++) dep |= a[s].x ^ a[s].z;
        if (__any_sync(0xffffffffu, dep == 0x7fc17fc1u)) __nanosleep(0);
        e_arrive(bars + 8 * (B_WE + pc));
    };
    ldw(wA, 0, phi0); ldw(wB, 1, phi0 + 1);
    ldw(wC, 2, phi0 + 2);
    PROFW(8 + wg * 8 + 4);
    mbar_wait(bars + 8 * (B_SIG + SIG_P1 + 1));
    const int i = lane & 7, mi = lane >> 3;
    const uint32_t soff = sb + S1 + wg * 4096 + mi * 512 + (i >> 1) * 128 + (i & 1) * 64;
    const int xo = w ^ (i >> 1);
    float d[32];
    zero(d);
    int n = 0;
    uint32_t xb = ((sb + xslot(0)) & 0x3FFFF) >> 4 | 1u << 16, mb = bars + 8 * wg;
    bool landed = false;
    auto unit = [&](const uint4 (&a)[6], int z) {
        const Desc d0{xb + (z & 2), (512u >> 4) | (2u << 30)}, d1 = d0 ^ 2u;
        if (!landed) mbar_wait(bars + 8 * (B_RF + n));
        mbar_wait(mb + 8 * (B_TOK - 1));
        wg_fence();
        wgmma_rs_n64_z(d, a[0].x, a[0].y, a[0].z, a[0].w, d0);
        wgmma_rs_n64_a(d, a[1].x, a[1].y, a[1].z, a[1].w, d1);
        if (TOKM == 5) e_arrive(mb + 8 * B_TOK);
        e_arrive(bars + 8 * (n ? B_RE + n - 1 : B_RE + 13));
        const bool sfree = mbar_test(n >= 4 ? mb + 8 * (B_SFREE - 12) : bars + 8 * (B_TOK - 1));
        landed = mbar_test(bars + 8 * (B_RF + n + 1));
        wgmma_rs_n64_a(d, a[2].x, a[2].y, a[2].z, a[2].w, d0 + (uint32_t)(4096 >> 4));
        wgmma_rs_n64_a(d, a[3].x, a[3].y, a[3].z, a[3].w, d1 + (uint32_t)(4096 >> 4));
        if (TOKM == 6) e_arrive(mb + 8 * B_TOK);
        wgmma_rs_n64_a(d, a[4].x, a[4].y, a[4].z, a[4].w, d0 + (uint32_t)(8192 >> 4));
        wgmma_rs_n64_a(d, a[5].x, a[5].y, a[5].z, a[5].w, d1 + (uint32_t)(8192 >> 4));
        wg_commit();
        if (TOKM == 3) e_arrive(mb + 8 * B_TOK);
        if (!sfree) mbar_wait(mb + 8 * (B_SFREE - 12));
        const uint32_t a0 = soff + (n & 3) * 12288 + ((xo ^ z) << 4);
        n++;
        xb = ((sb + xslot(n)) & 0x3FFFF) >> 4 | 1u << 16;
        wg_wait<0>();
        reg_fence(d);
        uint32_t p[8];
#pragma unroll
        for (int j = 0; j < 8; j++) p[j] = pack2(d[4 * j] - d[4 * j + 3], d[4 * j + 2] + d[4 * j + 1]);
        stm4(a0, p[0], p[1], p[2], p[3]);
        stm4(a0 + 2048, p[4], p[5], p[6], p[7]);
        fence_async_smem();
        e_arrive(mb + 8 * (B_RDY + R_P2));
        mb += 24;
    };
    const int zA = phi0 & 3, zB = (phi0 + 1) & 3, zC = (phi0 + 2) & 3, zE = phiE & 3;
#pragma unroll 1
    for (int it = 0; it < 4; it++) {
        unit(wA, zA);
        PROFW(40 + wg * 8 + it * 2);
        unit(wB, zB);
        unit(wC, zC);
        if (it == 0 && mE) ldw(wE, 3, phiE);
        if (mE >> it & 1) unit(wE, zE);
        PROFW(40 + wg * 8 + it * 2 + 1);
    }
}

__device__ __forceinline__ void task_p3(int wg, int pair, uint32_t sb) {
    const int tid = threadIdx.x & 127, w = tid >> 5, lane = tid & 31;
    const uint32_t buf = sb + (wg ? 3 - wg : 0) * 51200, bars = sb + BARS;
    uint32_t fr[10][4][2];
    float acc[2][16];
    zero(acc[0]); zero(acc[1]);
    {
        const Desc dB = mkdesc(sb + C3, 128, 256, 0);
        const uint32_t a0 = (buf & 0x3FFFF) >> 4;
        auto dq = [&](int Q) {
            return Desc{a0 + (uint32_t)((quad_off(Q) >> 4) | ((Q < 48 ? 2048 : 1024) >> 4) << 16), (uint32_t)((quad_off(Q + 1) - quad_off(Q)) >> 4) | (2u << 30)};
        };
        auto issue = [&](int f) {
            if (!(f & 1)) mbar_wait(bars + 8 * (B_YF + wg * 5 + (f >> 1)));
            wg_fence();
            wgmma_ss_n32_z(acc[f & 1], dq(5 * f), dB);
            wgmma_ss_n32_a(acc[f & 1], dq(5 * f + 1), dB + (uint32_t)(1024 >> 4));
            wgmma_ss_n32_a(acc[f & 1], dq(5 * f + 3), dB + (uint32_t)(2048 >> 4));
            wg_commit();
        };
        mbar_wait(bars + 8 * B_CF3);
        issue(0);
        PROFW(64 + wg * 8 + 1);
#pragma unroll
        for (int f = 0; f < 10; f++) {
            if (f < 9) { issue(f + 1); wg_wait<1>(); } else wg_wait<0>();
            float (&d)[16] = acc[f & 1];
            reg_fence(d);
#pragma unroll
            for (int g = 0; g < 4; g++) { fr[f][g][0] = pack2(d[4 * g], d[4 * g + 1]); fr[f][g][1] = pack2(d[4 * g + 2], d[4 * g + 3]); }
        }
    }
    PROFW(64 + wg * 8 + 2);
    {
        const Desc dB = mkdesc(sb + C3 + 3072, 128, 256, 0);
        const int i = lane & 7, mi = lane >> 3, th = w >> 1, tz = (2 * pair + th) & 3;
        const int oct = (2 * (w & 1) + (mi & 1)) ^ tz;
        const uint32_t soff = buf + th * 3584 + (mi >> 1) * 512 + i * 64 + ((oct ^ (i >> 1)) << 4);
        auto issue = [&](int t) {
            const int g = t < 6 ? 1 + (t >> 1) : 0;
            const uint32_t o = t < 6 ? (t & 1) * 1024 : 8960, st = t < 6 ? 1792 : 1024;
            wg_fence();
            wgmma_rs_n32_z(acc[t & 1], fr[0][g][0], fr[0][g][1], fr[1][g][0], fr[1][g][1], dB + (o >> 4));
#pragma unroll
            for (int s = 1; s < 5; s++) wgmma_rs_n32_a(acc[t & 1], fr[2 * s][g][0], fr[2 * s][g][1], fr[2 * s + 1][g][0], fr[2 * s + 1][g][1], dB + ((o + s * st) >> 4));
            wg_commit();
        };
        bb_break(sb);
        issue(0);
        wg_bar(1 + wg);
#pragma unroll
        for (int t = 0; t < 7; t++) {
            if (t < 6) { issue(t + 1); wg_wait<1>(); } else wg_wait<0>();
            float (&d)[16] = acc[t & 1];
            reg_fence(d);
            if (t < 6) {
                const uint32_t a = soff + (1 + (t >> 1)) * 7168 + (t & 1) * 2048;
                stm4(a, pack2(d[0], d[1]), pack2(d[2], d[3]), pack2(d[4], d[5]), pack2(d[6], d[7]));
                if (t & 1) stm2(a + 1024, pack2(d[8], d[9]), pack2(d[10], d[11]));
                else stm4(a + 1024, pack2(d[8], d[9]), pack2(d[10], d[11]), pack2(d[12], d[13]), pack2(d[14], d[15]));
            } else {
                const int row = th * 14 + 4 * (mi >> 1) + (i >> 1);
                const uint32_t a = buf + row * 128 + (i & 1) * 64 + ((oct ^ (row & 3)) << 4);
                stm4(a, pack2(d[0], d[1]), pack2(d[2], d[3]), pack2(d[4], d[5]), pack2(d[6], d[7]));
                stm4((lane & 20) == 20 ? buf + 4096 + lane * 16 : a + 1024, pack2(d[8], d[9]), pack2(d[10], d[11]), pack2(d[12], d[13]), pack2(d[14], d[15]));
            }
            if ((t & 1) || t == 6) { fence_async_smem(); e_arrive(bars + 8 * (B_RDY + R_P3 + wg * 4 + (t >> 1))); }
        }
    }
}

__device__ __forceinline__ void load_x(int cls, int rk, int u, uint32_t sb, const Maps& mp) {
    const int id = u * NH + rk, pl = id / 3, c0 = 32 * (id - 3 * pl), tp = cls * 4 + (pl >> 4), col = 14 * (pl & 15) - 8;
    const uint32_t bar = sb + BARS + 8 * (B_XF + u * 5), dst = sb + u * 51200;
    const int wrap = col < 0 ? 224 : 0;
    if (tp) {
#pragma unroll
        for (int g = 0; g < 5; g++) e_ld3(dst + g * 8704, &mp.x34, c0, col + 4 * g + (g < 2 ? wrap : 0), 28 * tp - 6, bar + 8 * g);
    } else {
#pragma unroll
        for (int g = 0; g < 5; g++) {
            e_ld3(dst + g * 8704, &mp.x6, c0, col + 4 * g + (g < 2 ? wrap : 0), 218, bar + 8 * g);
            e_ld3(dst + g * 8704 + 1536, &mp.x28, c0, col + 4 * g + (g < 2 ? wrap : 0), 0, bar + 8 * g);
        }
    }
}

__device__ __forceinline__ void load_x_box(int cls, int rk, int u, int g, uint32_t sb, const Maps& mp) {
    const int id = u * NH + rk, pl = id / 3, c0 = 32 * (id - 3 * pl), tp = cls * 4 + (pl >> 4), col = 14 * (pl & 15) - 8 + 4 * g;
    e_ld3(sb + u * 51200 + g * 8704, &mp.x34, c0, col < 0 ? col + 224 : col, 28 * tp - 6, sb + BARS + 8 * (B_XF + u * 5 + g));
}

__device__ __forceinline__ void load_first(uint32_t sb, const Maps& mp, const Ptrs& pt) {
    const uint32_t bars = sb + BARS;
    const int k = blockIdx.x;
    PROF(122);
    if (k < 129) {
        const int cb0 = 14 * k / 25, cb1 = min((14 * k + 13) / 25, 71);
#pragma unroll 1
        for (int cb = cb0; cb <= cb1; cb++) {
            const int b = cb / 24, i0 = 16 * ((cb >> 2) - 6 * b) + 2 * (cb & 3);
            const uint32_t bar = bars + 8 * (B_WF + 2 * (cb - cb0));
            e_expect(bar, 14336);
            e_ld4(sb + WP + (cb - cb0) * 14336, &mp.w, 32 * b, i0, bar);
            e_ld4(sb + WP + (cb - cb0) * 14336 + 7168, &mp.w, 32 * b, i0 + 8, bar);
        }
    }
    e_expect(bars + 8 * B_CF1, 17920); e_g2s(sb + C1, pt.tab1, 17920, bars + 8 * B_CF1);
    if ((threadIdx.x & 31) < 15) asm volatile("mbarrier.arrive.expect_tx.shared::cta.b64 _, [%0], 8704;" :: "r"(bars + 8 * (B_XF + (threadIdx.x & 31))) : "memory");
    __syncwarp();
}

__device__ __forceinline__ uint32_t get_rel(uint32_t sb) {
    mbar_wait(sb + BARS + 8 * B_REL);
    uint32_t v; asm volatile("ld.shared.u32 %0, [%1];" : "=r"(v) : "r"(sb + REL) : "memory");
    return uni(v);
}

__device__ __forceinline__ void load_warp(int cls, int rk, uint32_t sb, const Maps& mp, const Ptrs& pt) {
    const uint32_t bars = sb + BARS;
    mbar_wait(bars + 8 * (B_SIG + SIG_P1));
    PROF(1);
    const uint32_t rel = get_rel(sb);
    const char* cnt = cls_cnt(pt.scr, cls);
    const int mE = extra_mask(rk);
    const int lpA = phi_line(3 * rk, rel), lpB = phi_line(3 * rk + 1, rel), lpC = phi_line(3 * rk + 2, rel), lpE = phi_line(extra_phi(rk), rel);
    e_arrive(bars + 8 * (B_TOK - 1));
    if ((threadIdx.x & 31) < 14) asm volatile("mbarrier.arrive.expect_tx.shared::cta.b64 _, [%0], 12288;" :: "r"(bars + 8 * (B_RF + (threadIdx.x & 31))) : "memory");
    __syncwarp();
    int n = 0;
#pragma unroll 1
    for (int pg = 0; pg < 4; pg++) {
        const int l0 = slot_line(0, pg, cls), l1 = slot_line(1, pg, cls), l2 = slot_line(2, pg, cls);
        auto unit = [&](int lp) {
            const uint32_t bar = bars + 8 * (B_RF + n), dst = sb + xslot(n);
            mbar_wait(bars + 8 * (n >= 8 ? B_RE + n - 8 : n >= 4 ? B_SIG + SIG_P1 + (rk < 60 ? 2 : 1) : B_WE + ((0x7163 >> (4 * n)) & 15)));
            e_g2s(dst, pt.scr + (size_t)(lp ^ l0) * 128, 4096, bar);
            e_g2s(dst + 4096, pt.scr + (size_t)(lp ^ l1) * 128, 4096, bar);
            e_g2s(dst + 8192, pt.scr + (size_t)(lp ^ l2) * 128, 4096, bar);
            n++;
        };
        cnt_wait(cnt + (CNT_P1 + pg) * 128, 48);
        PROF(88 + pg);
        unit(lpA); unit(lpB); unit(lpC);
        if (mE >> pg & 1) unit(lpE);
        if (pg == 1) { mbar_wait(bars + 8 * B_P1D); e_expect(bars + 8 * B_CF3, 17152); e_g2s(sb + C3, pt.tab3, 17152, bars + 8 * B_CF3); }
    }
}

__device__ __forceinline__ int near_page(char* p, int rounds) {
#pragma unroll
    for (int e = 0; e < 4; e++) asm volatile("st.relaxed.gpu.global.v4.u32 [%0], {%1, %1, %1, %1};" :: "l"(p + (e >> 1) * 4096 + (e & 1) * 16), "r"(0) : "memory");
    int score = 0;
#pragma unroll 1
    for (int r = 0; r < rounds; r++) {
        uint32_t v0, v1, t0, t1;
        asm volatile("atom.relaxed.gpu.global.exch.b32 %0, [%1], 1;" : "=r"(v0) : "l"(p + (r & 1) * 4096) : "memory");
        asm volatile("atom.relaxed.gpu.global.exch.b32 %0, [%1], 1;" : "=r"(v1) : "l"(p + (~r & 1) * 4096) : "memory");
        asm volatile("{\n.reg .pred p;\nsetp.ne.u32 p, %1, 0xffffffff;\nmov.u32 %0, 0;\n@p mov.u32 %0, %%clock;\n}" : "=r"(t0) : "r"(v0) : "memory");
        asm volatile("{\n.reg .pred p;\nsetp.ne.u32 p, %1, 0xffffffff;\nmov.u32 %0, 0;\n@p mov.u32 %0, %%clock;\n}" : "=r"(t1) : "r"(v1) : "memory");
        const int gap = min((int)(t1 - t0), 160) - 80;
        score += (r & 1) ? gap : -gap;

    }
    return score > 0;
}

__device__ __forceinline__ uint32_t find_role(uint32_t sb, char* scr) {
    const int k = blockIdx.x;
    int c = near_page(scr + (slot_line(3, 3, 0) + phi_line(1 + (k >> 5), 0) + (k & 31)) * 128, PROBES);
    PROF(3);
    int r;
    asm volatile("atom.relaxed.gpu.global.add.u32 %0, [%1], 1;" : "=r"(r) : "l"(cls_cnt(scr, c) + CNT_RANK * 128) : "memory");
    if (r >= NH) { c ^= 1; r = NSM - 1 - r; }
    asm volatile("st.shared.u32 [%0], %1;" :: "r"(sb + REL + 4), "r"(c << 8 | r) : "memory");
    PROF(5);
    return c << 8 | r;
}
__device__ __forceinline__ void get_role(uint32_t sb, int& cls, int& rk) {
    mbar_wait(sb + BARS + 8 * B_ROLE);
    uint32_t v; asm volatile("ld.shared.u32 %0, [%1];" : "=r"(v) : "r"(sb + REL + 4) : "memory");
    v = uni(v); cls = v >> 8; rk = v & 255;
}

__device__ __forceinline__ void load3_warp(int cls, int rk, uint32_t sb, const Maps& mp, const Ptrs& pt) {
    const uint32_t bars = sb + BARS;
    uint32_t rel = 0;
    mbar_wait(bars + 8 * B_XF);
    PROF(107);
    rel = cnt_wait(pt.cnt + CNT_REL * 32, 12u << 16);
    asm volatile("st.shared.u32 [%0], %1;" :: "r"(sb + REL), "r"(rel) : "memory");
    __syncwarp();
    e_arrive(bars + 8 * B_REL);
    PROF(7);
    mbar_wait(bars + 8 * (B_SIG + SIG_W));
    cnt_wait(cls_cnt(pt.scr, cls) + CNT_W * 128, NSM);
    PROF(2);
    {
        const int np = rk >= 58 ? 12 : 9;
#pragma unroll 1
        for (int o = 0; o < np; o++) {
            const int pc = (0xba9785421630ull >> (4 * o)) & 15;
            if (o == 4) mbar_wait(bars + 8 * (B_SIG + SIG_P1));
            if (o >= 8) mbar_wait(bars + 8 * (B_WE + ((0x5240 >> (4 * (o - 8))) & 15)));
            e_expect(bars + 8 * (B_WL + pc), 12288);
            e_g2s(sb + wslot(pc), pt.wf + (pc < 9 ? 9 * rk + pc : 3 * extra_phi(rk) + pc - 9) * 12288, 12288, bars + 8 * (B_WL + pc));
        }
        if (np == 12) { mbar_wait(bars + 8 * (B_WE + 9)); mbar_wait(bars + 8 * (B_WE + 10)); mbar_wait(bars + 8 * (B_WE + 11)); }
    }
    mbar_wait(bars + 8 * (B_SIG + SIG_P2 + Y0AT));
    const int nu = rk < 60 ? 3 : 2;
#pragma unroll 1
    for (int u = 0; u < nu; u++) {
        const int id = u * NH + rk, pl = id / 3, chunk = id - 3 * pl;
        const int l0 = slot_line(chunk, pl >> 4, cls) + (pl & 15) * 2;
        const uint32_t buf = sb + (u ? 3 - u : 0) * 51200, bar = bars + 8 * (B_YF + u * 5);
#pragma unroll
        for (int j = 0; j < 5; j++) e_expect(bar + 8 * j, j == 4 ? 10240 : (j & 1) ? 8192 : 12288);
        if (u) mbar_wait(bars + 8 * (B_SIG + SIG_P2 + 3));
        cnt_wait(cls_cnt(pt.scr, cls) + (CNT_P2 + (pl >> 4)) * 128, NH);
        PROF(64 + u * 8);
        if (u == nu - 1) e_arrive(bars + 8 * B_FIN);
        const uint32_t r2 = uni(rel) << 5;
#pragma unroll
        for (int G = 0; G < 13; G++)
            e_ld5(buf + G * 4096, G < 12 ? &mp.f16 : &mp.f8, (l0 ^ ((r2 >> G) & 32)) + (G << 14), bar + 8 * ((2 * G) / 5));
    }
}

__device__ __forceinline__ void store_warp(uint32_t sb, const Maps& mp, const Ptrs& pt) {
    const uint32_t bars = sb + BARS;
    const int k = blockIdx.x;
    uint32_t pa = 0, pb = 0, qa = 0, qb = 0;
    auto arr2 = [&](uint32_t& a, uint32_t& b) { if (a) e_arrive(a); if (b) e_arrive(b); a = b = 0; };
    auto pre = [&](int idx) {
        const uint32_t bar = bars + 8 * idx;
        if (!mbar_test(bar)) { bulk_wait_read<0>(); arr2(qa, qb); arr2(pa, pb); mbar_wait(bar); }
    };
    auto post = [&](uint32_t fr) {
        bulk_commit(); bulk_wait_read<SWIN - 1>();
        if (SWIN == 3) { arr2(qa, qb); qa = pa; qb = pb; pb = 0; } else arr2(pa, pb);
        pa = fr;
    };
    auto after = [&](uint32_t a, uint32_t b) { if (a) pa = a; pb = b; };
    auto pace = [&](uint32_t) {};
    int cls, rk; get_role(sb, cls, rk);
    {
        int cb = 14 * k / 25, oc = 14 * k - 25 * cb;
        int g1 = 0;
#pragma unroll 1
        for (int i = 0; i < 14 && cb < 72; i++) {
            pre(B_WRD + i);
            if (PACE) pace(4 * PACE);
            e_st3(&mp.wst, sb + wst_off(i), 0, 8 * oc, cb);
            post(0);
            if (T1MASK >> i & 1) load_x_box(cls, rk, 1, g1++, sb, mp);
            if (++oc == 25) { oc = 0; cb++; }
        }
#pragma unroll 1
        for (; g1 < 5; g1++) load_x_box(cls, rk, 1, g1, sb, mp);
        if (X1AT && 14 * k + X1AT > 1800) e_arrive(bars + 8 * B_X1);
        after(bars + 8 * B_WFREE, bars + 8 * (B_SIG + SIG_W));
    }
    pre(B_REL);
    const uint32_t rel = get_rel(sb);
    const int nu = rk < 60 ? 3 : 2;
#pragma unroll 1
    for (int u = 0; u < nu; u++) {
        const int id = u * NH + rk, pl = id / 3, chunk = id - 3 * pl;
        const int l0 = slot_line(chunk, pl >> 4, cls) + (pl & 15) * 2;
        int j = B_RDY + u * 5;
        int g2 = 0;
        const int m2 = (u == 0 && nu == 3) ? T2MASK : 0;
#pragma unroll 1
        for (int G = 0; G < 13; G++) {
            if (0x4a5 >> G & 1) pre(j++);
            if (PACE) pace(G < 12 ? 4 * PACE : 2 * PACE);
            e_st5(G < 12 ? &mp.f16 : &mp.f8, sb + u * 51200 + G * 4096, (l0 ^ ((rel >> G) & 1) << 5) + (G << 14));
            post(0);
            if (m2 >> G & 1) load_x_box(cls, rk, 2, g2++, sb, mp);
        }
        after(0, bars + 8 * (B_SIG + SIG_P1 + u));
    }
    const int mE = extra_mask(rk);
    int n = 0;
#pragma unroll 1
    for (int pg = 0; pg < 4; pg++) {
        const int nj = 3 + (mE >> pg & 1);
        const int l0 = slot_line(0, pg, cls), l1 = slot_line(1, pg, cls), l2 = slot_line(2, pg, cls);
#pragma unroll 1
        for (int j = 0; j < nj; j++) {
            const int lp = phi_line(j == 3 ? extra_phi(rk) : 3 * rk + j, rel);
#pragma unroll
            for (int b = 0; b < 3; b++) {
                pre(B_RDY + R_P2 + n * 3 + b);
                if (PACE) pace(4 * PACE);
                e_s2g(pt.scr + (size_t)(lp ^ (b == 0 ? l0 : b == 1 ? l1 : l2)) * 128, sb + S1 + (n & 3) * 12288 + b * 4096, 4096);
                post(bars + 8 * (B_SFREE + n * 3 + b));
            }
            n++;
        }
        after(0, bars + 8 * (B_SIG + SIG_P2 + pg));
    }
#pragma unroll 1
    for (int u = 0; u < nu; u++) {
        const int id = u * NH + rk, pl = id / 3, chunk = id - 3 * pl, tp = cls * 4 + (pl >> 4), tx = pl & 15;
        const uint32_t buf = sb + (u ? 3 - u : 0) * 51200;
#pragma unroll
        for (int gg = 1; gg < 5; gg++) {
            pre(B_RDY + R_P3 + u * 4 + gg - 1);
            if (u < 2) pace(gg < 4 ? 7 * YPACE : 7 * YPACE / 2);
            if (gg < 4) e_st3(&mp.y4, buf + gg * 7168, 32 * chunk, 14 * tx - 4 + 4 * gg, 28 * tp);
            else e_st3(&mp.y2, buf, 32 * chunk, tx == 0 ? 222 : 14 * tx - 2, 28 * tp);
            post(0);
        }
    }
    bulk_wait_read<0>();
    PROF(113);
    prof_dump();
}

__device__ __forceinline__ void signal_warp(int cls, int rk, uint32_t sb, const Ptrs& pt) {
    const uint32_t bars = sb + BARS;
    char* cnt = cls_cnt(pt.scr, cls);
    if (threadIdx.x & 31) return;
#pragma unroll 1
    for (int c = 0; c < 8; c++) {
        if (c == SIG_P1 + 2 && rk >= 60) continue;
        char* ctr = cnt + (c == SIG_W ? CNT_W : c < SIG_P2 ? CNT_P1 + ((c - SIG_P1) * NH + rk) / 48 : CNT_P2 + c - SIG_P2) * 128;
        mbar_wait(bars + 8 * (B_SIG + c));
        PROF(32 + c);
        fence_async();
        asm volatile("red.relaxed.gpu.global.add.u32 [%0], 1;" :: "l"(ctr) : "memory");
        if (c == SIG_W) asm volatile("red.relaxed.gpu.global.add.u32 [%0], 1;" :: "l"((uintptr_t)ctr ^ 4096) : "memory");
        PROF(96 + c);
    }
    mbar_wait(bars + 8 * B_FIN);
    unsigned old;
    asm volatile("atom.add.relaxed.gpu.global.u32 %0, [%1], 1;" : "=r"(old) : "l"(pt.cnt + CNT_DONE * 32) : "memory");
    if (old == NSM - 1) {
#pragma unroll
        for (int c = 0; c < NCNT; c++) pt.cnt[c * 32] = 0;
#pragma unroll 1
        for (int c = 0; c < NCLS; c++) { *reinterpret_cast<unsigned*>(cnt + c * 128) = 0; *reinterpret_cast<unsigned*>(((uintptr_t)cnt ^ 4096) + c * 128) = 0; }
    }
}

__global__ void __launch_bounds__(512, 1) fftconv_kernel(const Ptrs pt, const __grid_constant__ Maps mp) {
    extern __shared__ __align__(1024) uint8_t smem[];
    const uint32_t sb = smem_u32(smem);
    const int tid = threadIdx.x, warp = uni(tid >> 5), wg = warp >> 2;
    int cls, rk;
    auto bar_init = [&](int i) {
        uint32_t c = 1;
        if (i == B_P1D || (i >= B_RE && i < B_RE + 14)) c = 12;
        else if ((i >= B_WCH && i < B_WL) || i >= B_TOK) c = 4;
        asm volatile("st.shared.v2.u32 [%0], {%1, %2};" :: "r"(sb + BARS + 8 * i), "r"((0x100000u - c) << 1), "r"((0x100000u - c) << 11) : "memory");
        fence_async_smem();
    };
    if (wg == 3) {
        asm volatile("setmaxnreg.dec.sync.aligned.u32 32;");
        if (warp == 12) {
            bar_init(tid & 31);
            __syncwarp();
            asm volatile("bar.arrive 4, 416;" ::: "memory");
            load_first(sb, mp, pt);
            PROF(106);
            asm volatile("bar.sync 5, 416;" ::: "memory");
            get_role(sb, cls, rk);
            load_warp(cls, rk, sb, mp, pt);
        } else if (warp == 13) {
            if ((tid & 31) < 8) asm volatile("prefetch.tensormap [%0];" :: "l"(reinterpret_cast<const CUtensorMap*>(&mp) + 1 + (tid & 31)) : "memory");
            __syncwarp();
            asm volatile("bar.sync 6, 416;" ::: "memory");
            store_warp(sb, mp, pt);
        } else if (warp == 14) {
            const int G = blockIdx.x - 119;
            int sel = 0;
            if (G >= 1 && (tid & 31) == 0) sel = near_page(pt.scr + ((size_t)G << 21) + slot_line(3, 3, 0) * 128, 2);
            __syncwarp();
            asm volatile("bar.sync 7, 416;" ::: "memory");
            get_role(sb, cls, rk);
            if (G >= 1 && (tid & 31) == 0) asm volatile("red.relaxed.gpu.global.add.u32 [%0], %1;" :: "l"(pt.cnt + CNT_REL * 32), "r"(0x10000u | (uint32_t)(sel ^ cls) << G) : "memory");
            __syncwarp();
            load3_warp(cls, rk, sb, mp, pt);
        } else {
            uint32_t role = 0;
            if ((tid & 31) == 0) role = find_role(sb, pt.scr);
            role = uni(role); cls = role >> 8; rk = role & 255;
            asm volatile("bar.sync 8, 416;" ::: "memory");
            load_x(cls, rk, 0, sb, mp);
            PROF(123);
            e_arrive(sb + BARS + 8 * B_ROLE);
            signal_warp(cls, rk, sb, pt);
        }
    } else {
        if (tid >= 32 && tid < NBAR) bar_init(tid);
        {
            const int r = tid % 40;
            asm volatile("st.shared.u32 [%0], %1;" :: "r"(sb + TBL + 4 * tid), "r"(cos_bits(r) | (cos_bits(r < 30 ? r + 10 : r - 30) << 16)) : "memory");
        }
        __syncwarp();
        asm volatile("bar.sync 4, 416;" ::: "memory");
        asm volatile("bar.arrive 5, 416;" ::: "memory");
        asm volatile("bar.arrive 6, 416;" ::: "memory");
        asm volatile("bar.arrive 7, 416;" ::: "memory");
        asm volatile("bar.arrive 8, 416;" ::: "memory");
        PROF(121);
        task_w(wg, blockIdx.x, sb);
        asm volatile("setmaxnreg.inc.sync.aligned.u32 160;");
        get_role(sb, cls, rk);
        const int id = wg * NH + rk;
        PROFW(8 + wg * 8);
        if (id < 192) task_p1(wg, id / 3, sb);
        e_arrive(sb + BARS + 8 * B_P1D);
        PROFW(8 + wg * 8 + 3);
        task_p2(wg, rk, sb);
        if (id < 192) task_p3(wg, id / 3, sb);
        PROFW(64 + wg * 8 + 3);
        prof_dump();
    }
}

typedef CUresult (*EncodeFn)(CUtensorMap*, CUtensorMapDataType, cuuint32_t, void*, const cuuint64_t*, const cuuint64_t*, const cuuint32_t*, const cuuint32_t*,
                             CUtensorMapInterleave, CUtensorMapSwizzle, CUtensorMapL2promotion, CUtensorMapFloatOOBfill);

static void encode3(EncodeFn fn, CUtensorMap* m, void* ptr, uint64_t d0, uint64_t d1, uint64_t d2, uint64_t s1, uint64_t s2,
                    uint32_t b0, uint32_t b1, uint32_t b2, CUtensorMapSwizzle sw) {
    cuuint64_t dims[3] = {d0, d1, d2}, strides[2] = {s1, s2};
    cuuint32_t box[3] = {b0, b1, b2}, es[3] = {1, 1, 1};
    fn(m, CU_TENSOR_MAP_DATA_TYPE_BFLOAT16, 3, ptr, dims, strides, box, es, CU_TENSOR_MAP_INTERLEAVE_NONE, sw,
       CU_TENSOR_MAP_L2_PROMOTION_NONE, CU_TENSOR_MAP_FLOAT_OOB_FILL_NONE);
}

extern "C" void kernel_launch(void* const* d_in, const int* in_sizes, int n_in, void* d_out, int out_size) {
    (void)in_sizes; (void)n_in; (void)out_size;
    void* fnp = nullptr; cudaDriverEntryPointQueryResult qr;
    cudaGetDriverEntryPoint("cuTensorMapEncodeTiled", &fnp, cudaEnableDefault, &qr);
    EncodeFn fn = (EncodeFn)fnp;
    void* xf = nullptr; cudaGetSymbolAddress(&xf, g_scr);
    xf = (void*)(((uintptr_t)xf + (1u << 21) - 1) & ~(uintptr_t)((1u << 21) - 1));
    void* wf = nullptr; cudaGetSymbolAddress(&wf, g_wf);
    Maps mp;
    Ptrs pt;
    pt.scr = (char*)xf; pt.wf = (const char*)wf;
    void* p = nullptr;
    cudaGetSymbolAddress(&p, TAB_P1); pt.tab1 = p;
    cudaGetSymbolAddress(&p, TAB_P3); pt.tab3 = p;
    cudaGetSymbolAddress(&p, g_cnt); pt.cnt = (unsigned*)p;
    {
        cuuint32_t b16[5] = {64, 4, 2, 2, 2}, b8[5] = {64, 4, 2, 1, 2}, es[5] = {1, 1, 1, 1, 1};
        cuuint64_t d[5] = {64, 4, 2, 2, 13 << 14}, st[4] = {16384, 262144, 1048576, 128};
        fn(&mp.f16, CU_TENSOR_MAP_DATA_TYPE_BFLOAT16, 5, xf, d, st, b16, es, CU_TENSOR_MAP_INTERLEAVE_NONE, CU_TENSOR_MAP_SWIZZLE_NONE, CU_TENSOR_MAP_L2_PROMOTION_NONE, CU_TENSOR_MAP_FLOAT_OOB_FILL_NONE);
        fn(&mp.f8, CU_TENSOR_MAP_DATA_TYPE_BFLOAT16, 5, xf, d, st, b8, es, CU_TENSOR_MAP_INTERLEAVE_NONE, CU_TENSOR_MAP_SWIZZLE_NONE, CU_TENSOR_MAP_L2_PROMOTION_NONE, CU_TENSOR_MAP_FLOAT_OOB_FILL_NONE);
    }
    encode3(fn, &mp.x6, d_in[0], 96, 224, 224, 192, 224 * 192, 32, 4, 6, CU_TENSOR_MAP_SWIZZLE_64B);
    encode3(fn, &mp.x34, d_in[0], 96, 224, 224, 192, 224 * 192, 32, 4, 34, CU_TENSOR_MAP_SWIZZLE_64B);
    encode3(fn, &mp.x28, d_in[0], 96, 224, 224, 192, 224 * 192, 32, 4, 28, CU_TENSOR_MAP_SWIZZLE_64B);
    {
        cuuint32_t box[4] = {32, 8, 7, 2}, es[4] = {1, 1, 1, 1};
        cuuint64_t d[4] = {96, 7, 7, 96}, st[3] = {18432, 7 * 18432, 192};
        fn(&mp.w, CU_TENSOR_MAP_DATA_TYPE_BFLOAT16, 4, d_in[1], d, st, box, es, CU_TENSOR_MAP_INTERLEAVE_NONE, CU_TENSOR_MAP_SWIZZLE_64B, CU_TENSOR_MAP_L2_PROMOTION_NONE, CU_TENSOR_MAP_FLOAT_OOB_FILL_NONE);
    }
    encode3(fn, &mp.wst, wf, 256, 200, 72, 36864, 512, 256, 8, 1, CU_TENSOR_MAP_SWIZZLE_NONE);
    encode3(fn, &mp.y4, d_out, 96, 224, 224, 192, 224 * 192, 32, 4, 28, CU_TENSOR_MAP_SWIZZLE_64B);
    encode3(fn, &mp.y2, d_out, 96, 224, 224, 192, 224 * 192, 32, 2, 28, CU_TENSOR_MAP_SWIZZLE_64B);
    constexpr int SMEM_LAUNCH = SMEM_BYTES;
    cudaFuncSetAttribute(fftconv_kernel, cudaFuncAttributeMaxDynamicSharedMemorySize, SMEM_LAUNCH);
    fftconv_kernel<<<NSM, 512, SMEM_LAUNCH>>>(pt, mp);
}
```

```cpp
#include <cuda_runtime.h>
#include <cuda_bf16.h>
#include <cuda.h>
#include <stdint.h>

__device__ __align__(128) const uint32_t TAB_P1[4480] = {
0x3e75,0,0x3e72,0,0x8000,0,0xbd19,0,0x3e750000,0,0x3e720000,0,0x80000000,0,0xbd190000,0,
0,0x3e75,0,0x3e72,0,0x8000,0,0xbd19,0,0x3e750000,0,0x3e720000,0,0x80000000,0,0xbd190000,
0x3e69,0,0x3e5a,0,0xbd97,0,0xbdde,0,0x3e690000,0,0x3e5a0000,0,0xbd970000,0,0xbdde0000,0,
0,0x3e69,0,0x3e5a,0,0xbd97,0,0xbdde,0,0x3e690000,0,0x3e5a0000,0,0xbd970000,0,0xbdde0000,
0x3e75,0,0x3e5a,0,0x8000,0,0xbdde,0,0x3e750000,0,0x3e5a0000,0,0x80000000,0,0xbdde0000,0,
0,0x3e75,0,0x3e5a,0,0x8000,0,0xbdde,0,0x3e750000,0,0x3e5a0000,0,0x80000000,0,0xbdde0000,
0x3e10,0,0x3d19,0,0xbe46,0,0xbe72,0,0x3e100000,0,0x3d190000,0,0xbe460000,0,0xbe720000,0,
0,0x3e10,0,0x3d19,0,0xbe46,0,0xbe72,0,0x3e100000,0,0x3d190000,0,0xbe460000,0,0xbe720000,
0x3e75,0,0x3e2d,0,0x8000,0,0xbe2d,0,0x3e750000,0,0x3e2d0000,0,0x80000000,0,0xbe2d0000,0,
0,0x3e75,0,0x3e2d,0,0x8000,0,0xbe2d,0,0x3e750000,0,0x3e2d0000,0,0x80000000,0,0xbe2d0000,
0,0,0xbe2d,0,0xbe75,0,0xbe2d,0,0,0,0xbe2d0000,0,0xbe750000,0,0xbe2d0000,0,
0,0,0,0xbe2d,0,0xbe75,0,0xbe2d,0,0,0,0xbe2d0000,0,0xbe750000,0,0xbe2d0000,
0x3e75,0,0x3dde,0,0x8000,0,0xbe5a,0,0x3e750000,0,0x3dde0000,0,0x80000000,0,0xbe5a0000,0,
0,0x3e75,0,0x3dde,0,0x8000,0,0xbe5a,0,0x3e750000,0,0x3dde0000,0,0x80000000,0,0xbe5a0000,
0xbe10,0,0xbe72,0,0xbe46,0,0x3d19,0,0xbe100000,0,0xbe720000,0,0xbe460000,0,0x3d190000,0,
0,0xbe10,0,0xbe72,0,0xbe46,0,0x3d19,0,0xbe100000,0,0xbe720000,0,0xbe460000,0,0x3d190000,
0x3e75,0,0x3d19,0,0x8000,0,0xbe72,0,0x3e750000,0,0x3d190000,0,0x80000000,0,0xbe720000,0,
0,0x3e75,0,0x3d19,0,0x8000,0,0xbe72,0,0x3e750000,0,0x3d190000,0,0x80000000,0,0xbe720000,
0xbe69,0,0xbdde,0,0xbd97,0,0x3e5a,0,0xbe690000,0,0xbdde0000,0,0xbd970000,0,0x3e5a0000,0,
0,0xbe69,0,0xbdde,0,0xbd97,0,0x3e5a,0,0xbe690000,0,0xbdde0000,0,0xbd970000,0,0x3e5a0000,
0x3e75,0,0xbd19,0,0x8000,0,0xbe72,0,0x3e750000,0,0xbd190000,0,0x80000000,0,0xbe720000,0,
0,0x3e75,0,0xbd19,0,0x8000,0,0xbe72,0,0x3e750000,0,0xbd190000,0,0x80000000,0,0xbe720000,
0xbe69,0,0x3dde,0,0x3d97,0,0x3e5a,0,0xbe690000,0,0x3dde0000,0,0x3d970000,0,0x3e5a0000,0,
0,0xbe69,0,0x3dde,0,0x3d97,0,0x3e5a,0,0xbe690000,0,0x3dde0000,0,0x3d970000,0,0x3e5a0000,
0x3e75,0,0xbdde,0,0x8000,0,0xbe5a,0,0x3e750000,0,0xbdde0000,0,0x80000000,0,0xbe5a0000,0,
0,0x3e75,0,0xbdde,0,0x8000,0,0xbe5a,0,0x3e750000,0,0xbdde0000,0,0x80000000,0,0xbe5a0000,
0xbe10,0,0x3e72,0,0x3e46,0,0x3d19,0,0xbe100000,0,0x3e720000,0,0x3e460000,0,0x3d190000,0,
0,0xbe10,0,0x3e72,0,0x3e46,0,0x3d19,0,0xbe100000,0,0x3e720000,0,0x3e460000,0,0x3d190000,
0x3e75,0,0xbe2d,0,0x8000,0,0xbe2d,0,0x3e750000,0,0xbe2d0000,0,0x80000000,0,0xbe2d0000,0,
0,0x3e75,0,0xbe2d,0,0x8000,0,0xbe2d,0,0x3e750000,0,0xbe2d0000,0,0x80000000,0,0xbe2d0000,
0,0,0x3e2d,0,0x3e75,0,0xbe2d,0,0,0,0x3e2d0000,0,0x3e750000,0,0xbe2d0000,0,
0,0,0,0x3e2d,0,0x3e75,0,0xbe2d,0,0,0,0x3e2d0000,0,0x3e750000,0,0xbe2d0000,
0x3e75,0,0xbe5a,0,0x8000,0,0xbdde,0,0x3e750000,0,0xbe5a0000,0,0x80000000,0,0xbdde0000,0,
0,0x3e75,0,0xbe5a,0,0x8000,0,0xbdde,0,0x3e750000,0,0xbe5a0000,0,0x80000000,0,0xbdde0000,
0x3e10,0,0xbd19,0,0x3e46,0,0xbe72,0,0x3e100000,0,0xbd190000,0,0x3e460000,0,0xbe720000,0,
0,0x3e10,0,0xbd19,0,0x3e46,0,0xbe72,0,0x3e100000,0,0xbd190000,0,0x3e460000,0,0xbe720000,
0x3e75,0,0xbe72,0,0x8000,0,0xbd19,0,0x3e750000,0,0xbe720000,0,0x80000000,0,0xbd190000,0,
0,0x3e75,0,0xbe72,0,0x8000,0,0xbd19,0,0x3e750000,0,0xbe720000,0,0x80000000,0,0xbd190000,
0x3e69,0,0xbe5a,0,0x3d97,0,0xbdde,0,0x3e690000,0,0xbe5a0000,0,0x3d970000,0,0xbdde0000,0,
0,0x3e69,0,0xbe5a,0,0x3d97,0,0xbdde,0,0x3e690000,0,0xbe5a0000,0,0x3d970000,0,0xbdde0000,
0x3e46,0,0x3e2d,0,0xbe10,0,0xbe2d,0,0x3e460000,0,0x3e2d0000,0,0xbe100000,0,0xbe2d0000,0,
0,0x3e46,0,0x3e2d,0,0xbe10,0,0xbe2d,0,0x3e460000,0,0x3e2d0000,0,0xbe100000,0,0xbe2d0000,
0x3e10,0,0x3dde,0,0xbe46,0,0xbe5a,0,0x3e100000,0,0x3dde0000,0,0xbe460000,0,0xbe5a0000,0,
0,0x3e10,0,0x3dde,0,0xbe46,0,0xbe5a,0,0x3e100000,0,0x3dde0000,0,0xbe460000,0,0xbe5a0000,
0xbd97,0,0xbe2d,0,0xbe69,0,0xbe2d,0,0xbd970000,0,0xbe2d0000,0,0xbe690000,0,0xbe2d0000,0,
0,0xbd97,0,0xbe2d,0,0xbe69,0,0xbe2d,0,0xbd970000,0,0xbe2d0000,0,0xbe690000,0,0xbe2d0000,
0xbe69,0,0xbe72,0,0xbd97,0,0x3d19,0,0xbe690000,0,0xbe720000,0,0xbd970000,0,0x3d190000,0,
0,0xbe69,0,0xbe72,0,0xbd97,0,0x3d19,0,0xbe690000,0,0xbe720000,0,0xbd970000,0,0x3d190000,
0xbe75,0,0xbe2d,0,0x8000,0,0x3e2d,0,0xbe750000,0,0xbe2d0000,0,0x80000000,0,0x3e2d0000,0,
0,0xbe75,0,0xbe2d,0,0x8000,0,0x3e2d,0,0xbe750000,0,0xbe2d0000,0,0x80000000,0,0x3e2d0000,
0,0,0x3e2d,0,0x3e75,0,0x3e2d,0,0,0,0x3e2d0000,0,0x3e750000,0,0x3e2d0000,0,
0,0,0,0x3e2d,0,0x3e75,0,0x3e2d,0,0,0,0x3e2d0000,0,0x3e750000,0,0x3e2d0000,
0xbd97,0,0x3e2d,0,0x3e69,0,0x3e2d,0,0xbd970000,0,0x3e2d0000,0,0x3e690000,0,0x3e2d0000,0,
0,0xbd97,0,0x3e2d,0,0x3e69,0,0x3e2d,0,0xbd970000,0,0x3e2d0000,0,0x3e690000,0,0x3e2d0000,
0x3e69,0,0x3d19,0,0xbd97,0,0xbe72,0,0x3e690000,0,0x3d190000,0,0xbd970000,0,0xbe720000,0,
0,0x3e69,0,0x3d19,0,0xbd97,0,0xbe72,0,0x3e690000,0,0x3d190000,0,0xbd970000,0,0xbe720000,
0x3e46,0,0x3e2d,0,0x3e10,0,0xbe2d,0,0x3e460000,0,0x3e2d0000,0,0x3e100000,0,0xbe2d0000,0,
0,0x3e46,0,0x3e2d,0,0x3e10,0,0xbe2d,0,0x3e460000,0,0x3e2d0000,0,0x3e100000,0,0xbe2d0000,
0xbe10,0,0xbe5a,0,0xbe46,0,0x3dde,0,0xbe100000,0,0xbe5a0000,0,0xbe460000,0,0x3dde0000,0,
0,0xbe10,0,0xbe5a,0,0xbe46,0,0x3dde,0,0xbe100000,0,0xbe5a0000,0,0xbe460000,0,0x3dde0000,
0x3e46,0,0xbe2d,0,0xbe10,0,0xbe2d,0,0x3e460000,0,0xbe2d0000,0,0xbe100000,0,0xbe2d0000,0,
0,0x3e46,0,0xbe2d,0,0xbe10,0,0xbe2d,0,0x3e460000,0,0xbe2d0000,0,0xbe100000,0,0xbe2d0000,
0xbe10,0,0x3e5a,0,0x3e46,0,0x3dde,0,0xbe100000,0,0x3e5a0000,0,0x3e460000,0,0x3dde0000,0,
0,0xbe10,0,0x3e5a,0,0x3e46,0,0x3dde,0,0xbe100000,0,0x3e5a0000,0,0x3e460000,0,0x3dde0000,
0xbd97,0,0xbe2d,0,0xbe69,0,0x3e2d,0,0xbd970000,0,0xbe2d0000,0,0xbe690000,0,0x3e2d0000,0,
0,0xbd97,0,0xbe2d,0,0xbe69,0,0x3e2d,0,0xbd970000,0,0xbe2d0000,0,0xbe690000,0,0x3e2d0000,
0x3e69,0,0xbd19,0,0x3d97,0,0xbe72,0,0x3e690000,0,0xbd190000,0,0x3d970000,0,0xbe720000,0,
0,0x3e69,0,0xbd19,0,0x3d97,0,0xbe72,0,0x3e690000,0,0xbd190000,0,0x3d970000,0,0xbe720000,
0xbe75,0,0x3e2d,0,0x8000,0,0x3e2d,0,0xbe750000,0,0x3e2d0000,0,0x80000000,0,0x3e2d0000,0,
0,0xbe75,0,0x3e2d,0,0x8000,0,0x3e2d,0,0xbe750000,0,0x3e2d0000,0,0x80000000,0,0x3e2d0000,
0,0,0xbe2d,0,0xbe75,0,0x3e2d,0,0,0,0xbe2d0000,0,0xbe750000,0,0x3e2d0000,0,
0,0,0,0xbe2d,0,0xbe75,0,0x3e2d,0,0,0,0xbe2d0000,0,0xbe750000,0,0x3e2d0000,
0xbd97,0,0x3e2d,0,0x3e69,0,0xbe2d,0,0xbd970000,0,0x3e2d0000,0,0x3e690000,0,0xbe2d0000,0,
0,0xbd97,0,0x3e2d,0,0x3e69,0,0xbe2d,0,0xbd970000,0,0x3e2d0000,0,0x3e690000,0,0xbe2d0000,
0xbe69,0,0x3e72,0,0x3d97,0,0x3d19,0,0xbe690000,0,0x3e720000,0,0x3d970000,0,0x3d190000,0,
0,0xbe69,0,0x3e72,0,0x3d97,0,0x3d19,0,0xbe690000,0,0x3e720000,0,0x3d970000,0,0x3d190000,
0x3e46,0,0xbe2d,0,0x3e10,0,0xbe2d,0,0x3e460000,0,0xbe2d0000,0,0x3e100000,0,0xbe2d0000,0,
0,0x3e46,0,0xbe2d,0,0x3e10,0,0xbe2d,0,0x3e460000,0,0xbe2d0000,0,0x3e100000,0,0xbe2d0000,
0x3e10,0,0xbdde,0,0x3e46,0,0xbe5a,0,0x3e100000,0,0xbdde0000,0,0x3e460000,0,0xbe5a0000,0,
0,0x3e10,0,0xbdde,0,0x3e46,0,0xbe5a,0,0x3e100000,0,0xbdde0000,0,0x3e460000,0,0xbe5a0000,
0x3d97,0,0x3d19,0,0xbe69,0,0xbe72,0,0x3d970000,0,0x3d190000,0,0xbe690000,0,0xbe720000,0,
0,0x3d97,0,0x3d19,0,0xbe69,0,0xbe72,0,0x3d970000,0,0x3d190000,0,0xbe690000,0,0xbe720000,
0,0,0xbd19,0,0xbe75,0,0xbe72,0,0,0,0xbd190000,0,0xbe750000,0,0xbe720000,0,
0,0,0,0xbd19,0,0xbe75,0,0xbe72,0,0,0,0xbd190000,0,0xbe750000,0,0xbe720000,
0xbe46,0,0xbdde,0,0x3e10,0,0x3e5a,0,0xbe460000,0,0xbdde0000,0,0x3e100000,0,0x3e5a0000,0,
0,0xbe46,0,0xbdde,0,0x3e10,0,0x3e5a,0,0xbe460000,0,0xbdde0000,0,0x3e100000,0,0x3e5a0000,
0,0,0x3dde,0,0x3e75,0,0x3e5a,0,0,0,0x3dde0000,0,0x3e750000,0,0x3e5a0000,0,
0,0,0,0x3dde,0,0x3e75,0,0x3e5a,0,0,0,0x3dde0000,0,0x3e750000,0,0x3e5a0000,
0x3e75,0,0x3e2d,0,0x8000,0,0xbe2d,0,0x3e750000,0,0x3e2d0000,0,0x80000000,0,0xbe2d0000,0,
0,0x3e75,0,0x3e2d,0,0x8000,0,0xbe2d,0,0x3e750000,0,0x3e2d0000,0,0x80000000,0,0xbe2d0000,
0,0,0xbe2d,0,0xbe75,0,0xbe2d,0,0,0,0xbe2d0000,0,0xbe750000,0,0xbe2d0000,0,
0,0,0,0xbe2d,0,0xbe75,0,0xbe2d,0,0,0,0xbe2d0000,0,0xbe750000,0,0xbe2d0000,
0xbe46,0,0xbe5a,0,0xbe10,0,0x3dde,0,0xbe460000,0,0xbe5a0000,0,0xbe100000,0,0x3dde0000,0,
0,0xbe46,0,0xbe5a,0,0xbe10,0,0x3dde,0,0xbe460000,0,0xbe5a0000,0,0xbe100000,0,0x3dde0000,
0,0,0x3e5a,0,0x3e75,0,0x3dde,0,0,0,0x3e5a0000,0,0x3e750000,0,0x3dde0000,0,
0,0,0,0x3e5a,0,0x3e75,0,0x3dde,0,0,0,0x3e5a0000,0,0x3e750000,0,0x3dde0000,
0x3d97,0,0x3e72,0,0x3e69,0,0xbd19,0,0x3d970000,0,0x3e720000,0,0x3e690000,0,0xbd190000,0,
0,0x3d97,0,0x3e72,0,0x3e69,0,0xbd19,0,0x3d970000,0,0x3e720000,0,0x3e690000,0,0xbd190000,
0,0,0xbe72,0,0xbe75,0,0xbd19,0,0,0,0xbe720000,0,0xbe750000,0,0xbd190000,0,
0,0,0,0xbe72,0,0xbe75,0,0xbd19,0,0,0,0xbe720000,0,0xbe750000,0,0xbd190000,
0x3d97,0,0xbe72,0,0xbe69,0,0xbd19,0,0x3d970000,0,0xbe720000,0,0xbe690000,0,0xbd190000,0,
0,0x3d97,0,0xbe72,0,0xbe69,0,0xbd19,0,0x3d970000,0,0xbe720000,0,0xbe690000,0,0xbd190000,
0,0,0x3e72,0,0x3e75,0,0xbd19,0,0,0,0x3e720000,0,0x3e750000,0,0xbd190000,0,
0,0,0,0x3e72,0,0x3e75,0,0xbd19,0,0,0,0x3e720000,0,0x3e750000,0,0xbd190000,
0xbe46,0,0x3e5a,0,0x3e10,0,0x3dde,0,0xbe460000,0,0x3e5a0000,0,0x3e100000,0,0x3dde0000,0,
0,0xbe46,0,0x3e5a,0,0x3e10,0,0x3dde,0,0xbe460000,0,0x3e5a0000,0,0x3e100000,0,0x3dde0000,
0,0,0xbe5a,0,0xbe75,0,0x3dde,0,0,0,0xbe5a0000,0,0xbe750000,0,0x3dde0000,0,
0,0,0,0xbe5a,0,0xbe75,0,0x3dde,0,0,0,0xbe5a0000,0,0xbe750000,0,0x3dde0000,
0x3e75,0,0xbe2d,0,0x8000,0,0xbe2d,0,0x3e750000,0,0xbe2d0000,0,0x80000000,0,0xbe2d0000,0,
0,0x3e75,0,0xbe2d,0,0x8000,0,0xbe2d,0,0x3e750000,0,0xbe2d0000,0,0x80000000,0,0xbe2d0000,
0,0,0x3e2d,0,0x3e75,0,0xbe2d,0,0,0,0x3e2d0000,0,0x3e750000,0,0xbe2d0000,0,
0,0,0,0x3e2d,0,0x3e75,0,0xbe2d,0,0,0,0x3e2d0000,0,0x3e750000,0,0xbe2d0000,
0xbe46,0,0x3dde,0,0xbe10,0,0x3e5a,0,0xbe460000,0,0x3dde0000,0,0xbe100000,0,0x3e5a0000,0,
0,0xbe46,0,0x3dde,0,0xbe10,0,0x3e5a,0,0xbe460000,0,0x3dde0000,0,0xbe100000,0,0x3e5a0000,
0,0,0xbdde,0,0xbe75,0,0x3e5a,0,0,0,0xbdde0000,0,0xbe750000,0,0x3e5a0000,0,
0,0,0,0xbdde,0,0xbe75,0,0x3e5a,0,0,0,0xbdde0000,0,0xbe750000,0,0x3e5a0000,
0x3d97,0,0xbd19,0,0x3e69,0,0xbe72,0,0x3d970000,0,0xbd190000,0,0x3e690000,0,0xbe720000,0,
0,0x3d97,0,0xbd19,0,0x3e69,0,0xbe72,0,0x3d970000,0,0xbd190000,0,0x3e690000,0,0xbe720000,
0,0,0x3d19,0,0x3e75,0,0xbe72,0,0,0,0x3d190000,0,0x3e750000,0,0xbe720000,0,
0,0,0,0x3d19,0,0x3e75,0,0xbe72,0,0,0,0x3d190000,0,0x3e750000,0,0xbe720000,
0xbd97,0,0xbdde,0,0xbe69,0,0xbe5a,0,0xbd970000,0,0xbdde0000,0,0xbe690000,0,0xbe5a0000,0,
0,0xbd97,0,0xbdde,0,0xbe69,0,0xbe5a,0,0xbd970000,0,0xbdde0000,0,0xbe690000,0,0xbe5a0000,
0xbe10,0,0xbe2d,0,0xbe46,0,0xbe2d,0,0xbe100000,0,0xbe2d0000,0,0xbe460000,0,0xbe2d0000,0,
0,0xbe10,0,0xbe2d,0,0xbe46,0,0xbe2d,0,0xbe100000,0,0xbe2d0000,0,0xbe460000,0,0xbe2d0000,
0x3e46,0,0x3e72,0,0x3e10,0,0x3d19,0,0x3e460000,0,0x3e720000,0,0x3e100000,0,0x3d190000,0,
0,0x3e46,0,0x3e72,0,0x3e10,0,0x3d19,0,0x3e460000,0,0x3e720000,0,0x3e100000,0,0x3d190000,
0x3e69,0,0x3e2d,0,0xbd97,0,0xbe2d,0,0x3e690000,0,0x3e2d0000,0,0xbd970000,0,0xbe2d0000,0,
0,0x3e69,0,0x3e2d,0,0xbd97,0,0xbe2d,0,0x3e690000,0,0x3e2d0000,0,0xbd970000,0,0xbe2d0000,
0xbe75,0,0xbe2d,0,0x8000,0,0x3e2d,0,0xbe750000,0,0xbe2d0000,0,0x80000000,0,0x3e2d0000,0,
0,0xbe75,0,0xbe2d,0,0x8000,0,0x3e2d,0,0xbe750000,0,0xbe2d0000,0,0x80000000,0,0x3e2d0000,
0,0,0x3e2d,0,0x3e75,0,0x3e2d,0,0,0,0x3e2d0000,0,0x3e750000,0,0x3e2d0000,0,
0,0,0,0x3e2d,0,0x3e75,0,0x3e2d,0,0,0,0x3e2d0000,0,0x3e750000,0,0x3e2d0000,
0x3e46,0,0xbd19,0,0xbe10,0,0xbe72,0,0x3e460000,0,0xbd190000,0,0xbe100000,0,0xbe720000,0,
0,0x3e46,0,0xbd19,0,0xbe10,0,0xbe72,0,0x3e460000,0,0xbd190000,0,0xbe100000,0,0xbe720000,
0xbe69,0,0xbe2d,0,0xbd97,0,0x3e2d,0,0xbe690000,0,0xbe2d0000,0,0xbd970000,0,0x3e2d0000,0,
0,0xbe69,0,0xbe2d,0,0xbd97,0,0x3e2d,0,0xbe690000,0,0xbe2d0000,0,0xbd970000,0,0x3e2d0000,
0xbd97,0,0x3e5a,0,0x3e69,0,0x3dde,0,0xbd970000,0,0x3e5a0000,0,0x3e690000,0,0x3dde0000,0,
0,0xbd97,0,0x3e5a,0,0x3e69,0,0x3dde,0,0xbd970000,0,0x3e5a0000,0,0x3e690000,0,0x3dde0000,
0x3e10,0,0xbe2d,0,0xbe46,0,0xbe2d,0,0x3e100000,0,0xbe2d0000,0,0xbe460000,0,0xbe2d0000,0,
0,0x3e10,0,0xbe2d,0,0xbe46,0,0xbe2d,0,0x3e100000,0,0xbe2d0000,0,0xbe460000,0,0xbe2d0000,
0xbd97,0,0xbe5a,0,0xbe69,0,0x3dde,0,0xbd970000,0,0xbe5a0000,0,0xbe690000,0,0x3dde0000,0,
0,0xbd97,0,0xbe5a,0,0xbe69,0,0x3dde,0,0xbd970000,0,0xbe5a0000,0,0xbe690000,0,0x3dde0000,
0x3e10,0,0x3e2d,0,0x3e46,0,0xbe2d,0,0x3e100000,0,0x3e2d0000,0,0x3e460000,0,0xbe2d0000,0,
0,0x3e10,0,0x3e2d,0,0x3e46,0,0xbe2d,0,0x3e100000,0,0x3e2d0000,0,0x3e460000,0,0xbe2d0000,
0x3e46,0,0x3d19,0,0x3e10,0,0xbe72,0,0x3e460000,0,0x3d190000,0,0x3e100000,0,0xbe720000,0,
0,0x3e46,0,0x3d19,0,0x3e10,0,0xbe72,0,0x3e460000,0,0x3d190000,0,0x3e100000,0,0xbe720000,
0xbe69,0,0x3e2d,0,0x3d97,0,0x3e2d,0,0xbe690000,0,0x3e2d0000,0,0x3d970000,0,0x3e2d0000,0,
0,0xbe69,0,0x3e2d,0,0x3d97,0,0x3e2d,0,0xbe690000,0,0x3e2d0000,0,0x3d970000,0,0x3e2d0000,
0xbe75,0,0x3e2d,0,0x8000,0,0x3e2d,0,0xbe750000,0,0x3e2d0000,0,0x80000000,0,0x3e2d0000,0,
0,0xbe75,0,0x3e2d,0,0x8000,0,0x3e2d,0,0xbe750000,0,0x3e2d0000,0,0x80000000,0,0x3e2d0000,
0,0,0xbe2d,0,0xbe75,0,0x3e2d,0,0,0,0xbe2d0000,0,0xbe750000,0,0x3e2d0000,0,
0,0,0,0xbe2d,0,0xbe75,0,0x3e2d,0,0,0,0xbe2d0000,0,0xbe750000,0,0x3e2d0000,
0x3e46,0,0xbe72,0,0xbe10,0,0x3d19,0,0x3e460000,0,0xbe720000,0,0xbe100000,0,0x3d190000,0,
0,0x3e46,0,0xbe72,0,0xbe10,0,0x3d19,0,0x3e460000,0,0xbe720000,0,0xbe100000,0,0x3d190000,
0x3e69,0,0xbe2d,0,0x3d97,0,0xbe2d,0,0x3e690000,0,0xbe2d0000,0,0x3d970000,0,0xbe2d0000,0,
0,0x3e69,0,0xbe2d,0,0x3d97,0,0xbe2d,0,0x3e690000,0,0xbe2d0000,0,0x3d970000,0,0xbe2d0000,
0xbd97,0,0x3dde,0,0x3e69,0,0xbe5a,0,0xbd970000,0,0x3dde0000,0,0x3e690000,0,0xbe5a0000,0,
0,0xbd97,0,0x3dde,0,0x3e69,0,0xbe5a,0,0xbd970000,0,0x3dde0000,0,0x3e690000,0,0xbe5a0000,
0xbe10,0,0x3e2d,0,0x3e46,0,0xbe2d,0,0xbe100000,0,0x3e2d0000,0,0x3e460000,0,0xbe2d0000,0,
0,0xbe10,0,0x3e2d,0,0x3e46,0,0xbe2d,0,0xbe100000,0,0x3e2d0000,0,0x3e460000,0,0xbe2d0000,
0xbe46,0,0xbe5a,0,0xbe10,0,0xbdde,0,0xbe460000,0,0xbe5a0000,0,0xbe100000,0,0xbdde0000,0,
0,0xbe46,0,0xbe5a,0,0xbe10,0,0xbdde,0,0xbe460000,0,0xbe5a0000,0,0xbe100000,0,0xbdde0000,
0xbe69,0,0xbe72,0,0xbd97,0,0xbd19,0,0xbe690000,0,0xbe720000,0,0xbd970000,0,0xbd190000,0,
0,0xbe69,0,0xbe72,0,0xbd97,0,0xbd19,0,0xbe690000,0,0xbe720000,0,0xbd970000,0,0xbd190000,
0x3d97,0,0xbd19,0,0xbe69,0,0xbe72,0,0x3d970000,0,0xbd190000,0,0xbe690000,0,0xbe720000,0,
0,0x3d97,0,0xbd19,0,0xbe69,0,0xbe72,0,0x3d970000,0,0xbd190000,0,0xbe690000,0,0xbe720000,
0xbe10,0,0xbe5a,0,0xbe46,0,0xbdde,0,0xbe100000,0,0xbe5a0000,0,0xbe460000,0,0xbdde0000,0,
0,0xbe10,0,0xbe5a,0,0xbe46,0,0xbdde,0,0xbe100000,0,0xbe5a0000,0,0xbe460000,0,0xbdde0000,
0x3e75,0,0x3e2d,0,0x8000,0,0xbe2d,0,0x3e750000,0,0x3e2d0000,0,0x80000000,0,0xbe2d0000,0,
0,0x3e75,0,0x3e2d,0,0x8000,0,0xbe2d,0,0x3e750000,0,0x3e2d0000,0,0x80000000,0,0xbe2d0000,
0,0,0xbe2d,0,0xbe75,0,0xbe2d,0,0,0,0xbe2d0000,0,0xbe750000,0,0xbe2d0000,0,
0,0,0,0xbe2d,0,0xbe75,0,0xbe2d,0,0,0,0xbe2d0000,0,0xbe750000,0,0xbe2d0000,
0x3d97,0,0x3e72,0,0x3e69,0,0x3d19,0,0x3d970000,0,0x3e720000,0,0x3e690000,0,0x3d190000,0,
0,0x3d97,0,0x3e72,0,0x3e69,0,0x3d19,0,0x3d970000,0,0x3e720000,0,0x3e690000,0,0x3d190000,
0x3e10,0,0xbdde,0,0xbe46,0,0xbe5a,0,0x3e100000,0,0xbdde0000,0,0xbe460000,0,0xbe5a0000,0,
0,0x3e10,0,0xbdde,0,0xbe46,0,0xbe5a,0,0x3e100000,0,0xbdde0000,0,0xbe460000,0,0xbe5a0000,
0xbe46,0,0x3dde,0,0x3e10,0,0x3e5a,0,0xbe460000,0,0x3dde0000,0,0x3e100000,0,0x3e5a0000,0,
0,0xbe46,0,0x3dde,0,0x3e10,0,0x3e5a,0,0xbe460000,0,0x3dde0000,0,0x3e100000,0,0x3e5a0000,
0x3e69,0,0xbd19,0,0xbd97,0,0xbe72,0,0x3e690000,0,0xbd190000,0,0xbd970000,0,0xbe720000,0,
0,0x3e69,0,0xbd19,0,0xbd97,0,0xbe72,0,0x3e690000,0,0xbd190000,0,0xbd970000,0,0xbe720000,
0xbe46,0,0xbdde,0,0xbe10,0,0x3e5a,0,0xbe460000,0,0xbdde0000,0,0xbe100000,0,0x3e5a0000,0,
0,0xbe46,0,0xbdde,0,0xbe10,0,0x3e5a,0,0xbe460000,0,0xbdde0000,0,0xbe100000,0,0x3e5a0000,
0x3e69,0,0x3d19,0,0x3d97,0,0xbe72,0,0x3e690000,0,0x3d190000,0,0x3d970000,0,0xbe720000,0,
0,0x3e69,0,0x3d19,0,0x3d97,0,0xbe72,0,0x3e690000,0,0x3d190000,0,0x3d970000,0,0xbe720000,
0x3d97,0,0xbe72,0,0xbe69,0,0x3d19,0,0x3d970000,0,0xbe720000,0,0xbe690000,0,0x3d190000,0,
0,0x3d97,0,0xbe72,0,0xbe69,0,0x3d19,0,0x3d970000,0,0xbe720000,0,0xbe690000,0,0x3d190000,
0x3e10,0,0x3dde,0,0x3e46,0,0xbe5a,0,0x3e100000,0,0x3dde0000,0,0x3e460000,0,0xbe5a0000,0,
0,0x3e10,0,0x3dde,0,0x3e46,0,0xbe5a,0,0x3e100000,0,0x3dde0000,0,0x3e460000,0,0xbe5a0000,
0x3e75,0,0xbe2d,0,0x8000,0,0xbe2d,0,0x3e750000,0,0xbe2d0000,0,0x80000000,0,0xbe2d0000,0,
0,0x3e75,0,0xbe2d,0,0x8000,0,0xbe2d,0,0x3e750000,0,0xbe2d0000,0,0x80000000,0,0xbe2d0000,
0,0,0x3e2d,0,0x3e75,0,0xbe2d,0,0,0,0x3e2d0000,0,0x3e750000,0,0xbe2d0000,0,
0,0,0,0x3e2d,0,0x3e75,0,0xbe2d,0,0,0,0x3e2d0000,0,0x3e750000,0,0xbe2d0000,
0x3d97,0,0x3d19,0,0x3e69,0,0xbe72,0,0x3d970000,0,0x3d190000,0,0x3e690000,0,0xbe720000,0,
0,0x3d97,0,0x3d19,0,0x3e69,0,0xbe72,0,0x3d970000,0,0x3d190000,0,0x3e690000,0,0xbe720000,
0xbe10,0,0x3e5a,0,0x3e46,0,0xbdde,0,0xbe100000,0,0x3e5a0000,0,0x3e460000,0,0xbdde0000,0,
0,0xbe10,0,0x3e5a,0,0x3e46,0,0xbdde,0,0xbe100000,0,0x3e5a0000,0,0x3e460000,0,0xbdde0000,
0xbe46,0,0x3e5a,0,0x3e10,0,0xbdde,0,0xbe460000,0,0x3e5a0000,0,0x3e100000,0,0xbdde0000,0,
0,0xbe46,0,0x3e5a,0,0x3e10,0,0xbdde,0,0xbe460000,0,0x3e5a0000,0,0x3e100000,0,0xbdde0000,
0xbe69,0,0x3e72,0,0x3d97,0,0xbd19,0,0xbe690000,0,0x3e720000,0,0x3d970000,0,0xbd190000,0,
0,0xbe69,0,0x3e72,0,0x3d97,0,0xbd19,0,0xbe690000,0,0x3e720000,0,0x3d970000,0,0xbd190000,
0x3eb7,0x3eb7,0x3eb7,0x3eb7,0x3eb78000,0x3eb78000,0x3eb78000,0x3eb78000,0x3eb7,0x3de23eae,0x3e573e94,0x3e943e57,0x3eb78000,0x3eaebde2,0x3e94be57,0x3e57be94,
0x3eb7,0x3e573e94,0x3eae3de2,0x3eaebde2,0x3eb78000,0x3e94be57,0x3de2beae,0xbde2beae,0x3eb7,0x3e943e57,0x3eaebde2,0x3de2beae,0x3eb78000,0x3e57be94,0xbde2beae,0xbeaebde2,
0x3eb7,0x3eb7,0x3eb7,0x3eb7,0x3eb78000,0x3eb78000,0x3eb78000,0x3eb78000,0x3eae3de2,0x3eb70000,0x3eaebde2,0x3e94be57,0x3de2beae,0xbeb7,0xbde2beae,0xbe57be94,
0x3e57be94,0xbeb7,0xbe57be94,0xbeaebde2,0xbe94be57,0xbeb78000,0xbe943e57,0xbde23eae,0xbe57be94,0xbeb70000,0xbe573e94,0x3de23eae,0xbe943e57,0x3eb7,0x3e943e57,0x3eaebde2,
0x3eb7,0x3eae3de2,0x3e57be94,0xbe57be94,0x3eb78000,0x3de2beae,0xbe94be57,0xbe943e57,0x3eb7,0x3eb70000,0xbeb7,0xbeb70000,0x3eb78000,0xbeb7,0xbeb78000,0x3eb7,
0x3eb7,0x3eaebde2,0xbe57be94,0xbe573e94,0x3eb78000,0xbde2beae,0xbe943e57,0x3e943e57,0x3eb7,0x3e94be57,0xbeaebde2,0x3de23eae,0x3eb78000,0xbe57be94,0xbde23eae,0x3eaebde2,
0xbeae3de2,0x3eb7,0x3eae3de2,0x3e57be94,0x3de23eae,0x3eb78000,0x3de2beae,0xbe94be57,0x3eb7,0x3eb70000,0xbeb7,0xbeb70000,0x3eb78000,0xbeb7,0xbeb78000,0x3eb7,
0x3eae3de2,0xbeb7,0xbeae3de2,0x3e573e94,0x3de2beae,0xbeb78000,0x3de23eae,0x3e94be57,0x3e57be94,0xbeb70000,0x3e573e94,0x3de2beae,0xbe94be57,0x3eb7,0x3e94be57,0xbeaebde2,
0x3eb7,0x3e57be94,0xbeae3de2,0x3eae3de2,0x3eb78000,0xbe94be57,0x3de23eae,0x3de2beae,0x3eb7,0x3de2beae,0xbe573e94,0x3e94be57,0x3eb78000,0xbeaebde2,0x3e943e57,0xbe57be94,
0x3eb7,0xbeb7,0x3eb7,0xbeb7,0x3eb78000,0xbeb78000,0x3eb78000,0xbeb78000,0x3eb7,0xbde2beae,0x3e573e94,0xbe94be57,0x3eb78000,0xbeae3de2,0x3e94be57,0xbe573e94,
0xbe57be94,0x3eb7,0x3e57be94,0xbeae3de2,0xbe943e57,0x3eb78000,0xbe94be57,0x3de23eae,0xbeae3de2,0x3eb70000,0xbeaebde2,0x3e943e57,0x3de23eae,0xbeb7,0xbde23eae,0x3e57be94,
0x3eb7,0xbeb7,0x3eb7,0xbeb7,0x3eb78000,0xbeb78000,0x3eb78000,0xbeb78000,0x3eae3de2,0xbeb70000,0x3eaebde2,0xbe943e57,0x3de2beae,0x3eb7,0xbde2beae,0x3e573e94,
0x3eb7,0xbe57be94,0x3eae3de2,0xbeae3de2,0x3eb78000,0xbe943e57,0x3de2beae,0x3de23eae,0x3eb7,0xbe94be57,0x3eaebde2,0xbde23eae,0x3eb78000,0xbe573e94,0xbde2beae,0x3eae3de2,
0x3eb7,0xbeaebde2,0x3e57be94,0x3e573e94,0x3eb78000,0xbde23eae,0xbe94be57,0x3e94be57,0x3eb7,0xbeb70000,0xbeb7,0x3eb70000,0x3eb78000,0x3eb7,0xbeb78000,0xbeb7,
0x3e57be94,0x3eb7,0xbe57be94,0x3eae3de2,0xbe94be57,0x3eb78000,0xbe943e57,0x3de2beae,0xbe57be94,0x3eb70000,0xbe573e94,0xbde2beae,0xbe943e57,0xbeb7,0x3e943e57,0xbeae3de2,
0xbeae3de2,0xbeb7,0x3eae3de2,0xbe573e94,0x3de23eae,0xbeb78000,0x3de2beae,0x3e943e57,0x3eb7,0xbeb70000,0xbeb7,0x3eb70000,0x3eb78000,0x3eb7,0xbeb78000,0xbeb7,
0x3eb7,0xbeae3de2,0xbe57be94,0x3e57be94,0x3eb78000,0x3de23eae,0xbe943e57,0xbe94be57,0x3eb7,0xbe943e57,0xbeaebde2,0xbde2beae,0x3eb78000,0x3e573e94,0xbde23eae,0xbeae3de2,
0x3eb7,0xbe573e94,0xbeae3de2,0xbeaebde2,0x3eb78000,0x3e943e57,0x3de23eae,0xbde23eae,0x3eb7,0xbde23eae,0xbe573e94,0xbe943e57,0x3eb78000,0x3eae3de2,0x3e943e57,0x3e573e94,
0x3eae3de2,0x3eb7,0xbeae3de2,0xbe57be94,0x3de2beae,0x3eb78000,0x3de23eae,0xbe943e57,0x3e57be94,0x3eb70000,0x3e573e94,0xbde23eae,0xbe94be57,0xbeb7,0x3e94be57,0x3eae3de2,
0xbe57be94,0xbeb7,0x3e57be94,0x3eaebde2,0xbe943e57,0xbeb78000,0xbe94be57,0xbde2beae,0xbeae3de2,0xbeb70000,0xbeaebde2,0xbe94be57,0x3de23eae,0x3eb7,0xbde23eae,0xbe573e94,
0x3eb7,0x3eb7,0x3eb7,0x3eb7,0x3eb78000,0x3eb78000,0x3eb78000,0x3eb78000,0x3e57be94,0x3de2beae,0xbeb7,0xbde2beae,0xbe94be57,0xbeaebde2,0xbeb78000,0xbeae3de2,
0xbeae3de2,0xbe573e94,0x3eb7,0x3e573e94,0x3de23eae,0x3e943e57,0x3eb78000,0x3e94be57,0x3eae3de2,0x3e94be57,0xbeb7,0xbe94be57,0x3de2beae,0xbe57be94,0xbeb78000,0xbe573e94,
0x3eb7,0x3eb7,0x3eb7,0x3eb7,0x3eb78000,0x3eb78000,0x3eb78000,0x3eb78000,0xbe57be94,0xbe94be57,0xbeaebde2,0xbeb70000,0xbe943e57,0xbe573e94,0xbde23eae,0x3eb7,
0x3eae3de2,0x3eaebde2,0x3e57be94,0xbeb7,0x3de2beae,0xbde2beae,0xbe94be57,0xbeb78000,0xbeae3de2,0xbde23eae,0x3e573e94,0x3eb70000,0x3de23eae,0x3eae3de2,0x3e94be57,0xbeb7,
0xbe57be94,0xbeae3de2,0x3eb7,0x3eae3de2,0xbe943e57,0x3de23eae,0x3eb78000,0x3de2beae,0x3eb7,0x3eb70000,0xbeb7,0xbeb70000,0x3eb78000,0xbeb7,0xbeb78000,0x3eb7,
0x3e57be94,0xbeaebde2,0x3eb7,0x3eaebde2,0xbe94be57,0xbde23eae,0x3eb78000,0xbde2beae,0xbeae3de2,0x3e943e57,0xbeb7,0xbe943e57,0x3de23eae,0x3e57be94,0xbeb78000,0x3e573e94,
0x3e57be94,0xbe57be94,0xbeae3de2,0x3eb7,0xbe94be57,0xbe943e57,0x3de23eae,0x3eb78000,0x3eb7,0x3eb70000,0xbeb7,0xbeb70000,0x3eb78000,0xbeb7,0xbeb78000,0x3eb7,
0xbe57be94,0xbe573e94,0x3eae3de2,0xbeb7,0xbe943e57,0x3e943e57,0x3de2beae,0xbeb78000,0x3eae3de2,0xbde2beae,0xbe573e94,0x3eb70000,0x3de2beae,0xbeae3de2,0x3e943e57,0xbeb7,
0x3eae3de2,0xbe57be94,0x3eb7,0x3e57be94,0x3de2beae,0xbe943e57,0x3eb78000,0xbe94be57,0xbe57be94,0x3de23eae,0xbeb7,0xbde23eae,0xbe943e57,0x3eaebde2,0xbeb78000,0x3eae3de2,
0x3eb7,0xbeb7,0x3eb7,0xbeb7,0x3eb78000,0xbeb78000,0x3eb78000,0xbeb78000,0x3e57be94,0xbde23eae,0xbeb7,0x3de23eae,0xbe94be57,0x3eae3de2,0xbeb78000,0x3eaebde2,
0xbeae3de2,0x3eae3de2,0xbe57be94,0x3eb7,0x3de23eae,0x3de2beae,0xbe943e57,0x3eb78000,0x3e57be94,0xbe943e57,0x3eaebde2,0xbeb70000,0xbe94be57,0x3e573e94,0xbde2beae,0x3eb7,
0x3eb7,0xbeb7,0x3eb7,0xbeb7,0x3eb78000,0xbeb78000,0x3eb78000,0xbeb78000,0xbe57be94,0x3e943e57,0xbeaebde2,0x3eb70000,0xbe943e57,0x3e57be94,0xbde23eae,0xbeb7,
0xbeae3de2,0x3e57be94,0x3eb7,0xbe57be94,0x3de23eae,0xbe94be57,0x3eb78000,0xbe943e57,0x3eae3de2,0xbe943e57,0xbeb7,0x3e943e57,0x3de2beae,0x3e573e94,0xbeb78000,0x3e57be94,
0xbe57be94,0x3eaebde2,0x3eb7,0xbeaebde2,0xbe943e57,0xbde2beae,0x3eb78000,0xbde23eae,0x3eb7,0xbeb70000,0xbeb7,0x3eb70000,0x3eb78000,0x3eb7,0xbeb78000,0xbeb7,
0x3eae3de2,0xbeae3de2,0x3e57be94,0x3eb7,0x3de2beae,0x3de23eae,0xbe94be57,0x3eb78000,0xbeae3de2,0x3de2beae,0x3e573e94,0xbeb70000,0x3de23eae,0xbeaebde2,0x3e94be57,0x3eb7,
0x3e57be94,0x3e573e94,0xbeae3de2,0xbeb7,0xbe94be57,0x3e94be57,0x3de23eae,0xbeb78000,0x3eb7,0xbeb70000,0xbeb7,0x3eb70000,0x3eb78000,0x3eb7,0xbeb78000,0xbeb7,
0x3e57be94,0x3eae3de2,0x3eb7,0xbeae3de2,0xbe94be57,0x3de2beae,0x3eb78000,0x3de23eae,0xbeae3de2,0xbe94be57,0xbeb7,0x3e94be57,0x3de23eae,0xbe573e94,0xbeb78000,0xbe57be94,
0x3eae3de2,0x3e573e94,0x3eb7,0xbe573e94,0x3de2beae,0x3e94be57,0x3eb78000,0x3e943e57,0xbe57be94,0xbde2beae,0xbeb7,0x3de2beae,0xbe943e57,0xbeae3de2,0xbeb78000,0xbeaebde2,
0xbe57be94,0x3e57be94,0x3eae3de2,0x3eb7,0xbe943e57,0xbe94be57,0x3de2beae,0x3eb78000,0x3eae3de2,0x3de23eae,0xbe573e94,0xbeb70000,0x3de2beae,0x3eaebde2,0x3e943e57,0x3eb7,
0xbeae3de2,0xbeaebde2,0xbe57be94,0xbeb7,0x3de23eae,0xbde23eae,0xbe943e57,0xbeb78000,0x3e57be94,0x3e94be57,0x3eaebde2,0x3eb70000,0xbe94be57,0xbe57be94,0xbde2beae,0xbeb7,
0x3eb7,0x3eb7,0x3eb7,0x3eb7,0x3eb78000,0x3eb78000,0x3eb78000,0x3eb78000,0xbeae3de2,0xbe943e57,0xbe573e94,0xbde23eae,0x3de23eae,0x3e573e94,0x3e943e57,0x3eae3de2,
0xbe57be94,0xbeaebde2,0xbeae3de2,0xbe573e94,0xbe943e57,0xbde23eae,0x3de23eae,0x3e943e57,0x3e57be94,0xbde2beae,0xbeaebde2,0xbe943e57,0xbe94be57,0xbeae3de2,0xbde23eae,0x3e573e94,
0,0,0,0,0,0,0,0,0,0,0,0,0,0,0,0,
0,0,0,0,0,0,0,0,0,0,0,0,0,0,0,0,
0x3eae3de2,0x3e57be94,0xbe57be94,0xbeae3de2,0x3de2beae,0xbe94be57,0xbe943e57,0x3de23eae,0x3eb7,0x3eb70000,0xbeb7,0xbeb70000,0x3eb78000,0xbeb7,0xbeb78000,0x3eb7,
0xbeae3de2,0x3e573e94,0x3e57be94,0xbeaebde2,0x3de23eae,0x3e94be57,0xbe94be57,0xbde23eae,0xbe57be94,0xbde23eae,0x3eaebde2,0xbe94be57,0xbe943e57,0x3eae3de2,0xbde2beae,0xbe573e94,
0,0,0,0,0,0,0,0,0,0,0,0,0,0,0,0,
0,0,0,0,0,0,0,0,0,0,0,0,0,0,0,0,
0x3e57be94,0xbeae3de2,0x3eae3de2,0xbe57be94,0xbe94be57,0x3de23eae,0x3de2beae,0xbe943e57,0x3eae3de2,0xbe94be57,0x3e573e94,0xbde2beae,0x3de2beae,0xbe573e94,0x3e94be57,0xbeae3de2,
0x3eb7,0xbeb7,0x3eb7,0xbeb7,0x3eb78000,0xbeb78000,0x3eb78000,0xbeb78000,0xbeae3de2,0x3e94be57,0xbe573e94,0x3de2beae,0x3de23eae,0xbe57be94,0x3e943e57,0xbeaebde2,
0,0,0,0,0,0,0,0,0,0,0,0,0,0,0,0,
0,0,0,0,0,0,0,0,0,0,0,0,0,0,0,0,
0xbe57be94,0x3eae3de2,0xbeae3de2,0x3e57be94,0xbe943e57,0x3de2beae,0x3de23eae,0xbe94be57,0x3e57be94,0x3de23eae,0xbeaebde2,0x3e94be57,0xbe94be57,0x3eaebde2,0xbde23eae,0xbe57be94,
0x3eae3de2,0xbe573e94,0xbe57be94,0x3eaebde2,0x3de2beae,0x3e943e57,0xbe943e57,0xbde2beae,0x3eb7,0xbeb70000,0xbeb7,0x3eb70000,0x3eb78000,0x3eb7,0xbeb78000,0xbeb7,
0,0,0,0,0,0,0,0,0,0,0,0,0,0,0,0,
0,0,0,0,0,0,0,0,0,0,0,0,0,0,0,0,
0xbeae3de2,0xbe57be94,0x3e57be94,0x3eae3de2,0x3de23eae,0xbe943e57,0xbe94be57,0x3de2beae,0xbe57be94,0x3de2beae,0x3eaebde2,0x3e943e57,0xbe943e57,0xbeaebde2,0xbde2beae,0x3e57be94,
0x3e57be94,0x3eaebde2,0x3eae3de2,0x3e573e94,0xbe94be57,0xbde2beae,0x3de2beae,0x3e94be57,0x3eae3de2,0x3e943e57,0x3e573e94,0x3de23eae,0x3de2beae,0x3e57be94,0x3e94be57,0x3eaebde2,
0,0,0,0,0,0,0,0,0,0,0,0,0,0,0,0,
0,0,0,0,0,0,0,0,0,0,0,0,0,0,0,0,
0,0,0,0,0,0,0,0,0,0,0,0,0,0,0,0,
0,0,0,0,0,0,0,0,0,0,0,0,0,0,0,0,
0x3eb7,0x3eb7,0x3eb7,0x3eb7,0x3eb78000,0x3eb78000,0x3eb78000,0x3eb78000,0xbeae3de2,0xbe943e57,0xbe573e94,0xbde23eae,0x3de23eae,0x3e573e94,0x3e943e57,0x3eae3de2,
0xbe57be94,0xbeaebde2,0xbeae3de2,0xbe573e94,0xbe943e57,0xbde23eae,0x3de23eae,0x3e943e57,0x3e57be94,0xbde2beae,0xbeaebde2,0xbe943e57,0xbe94be57,0xbeae3de2,0xbde23eae,0x3e573e94,
0,0,0,0,0,0,0,0,0,0,0,0,0,0,0,0,
0,0,0,0,0,0,0,0,0,0,0,0,0,0,0,0,
0x3eae3de2,0x3e57be94,0xbe57be94,0xbeae3de2,0x3de2beae,0xbe94be57,0xbe943e57,0x3de23eae,0x3eb7,0x3eb70000,0xbeb7,0xbeb70000,0x3eb78000,0xbeb7,0xbeb78000,0x3eb7,
0xbeae3de2,0x3e573e94,0x3e57be94,0xbeaebde2,0x3de23eae,0x3e94be57,0xbe94be57,0xbde23eae,0xbe57be94,0xbde23eae,0x3eaebde2,0xbe94be57,0xbe943e57,0x3eae3de2,0xbde2beae,0xbe573e94,
0,0,0,0,0,0,0,0,0,0,0,0,0,0,0,0,
0,0,0,0,0,0,0,0,0,0,0,0,0,0,0,0,
0x3e57be94,0xbeae3de2,0x3eae3de2,0xbe57be94,0xbe94be57,0x3de23eae,0x3de2beae,0xbe943e57,0x3eae3de2,0xbe94be57,0x3e573e94,0xbde2beae,0x3de2beae,0xbe573e94,0x3e94be57,0xbeae3de2,
0x3eb7,0xbeb7,0x3eb7,0xbeb7,0x3eb78000,0xbeb78000,0x3eb78000,0xbeb78000,0xbeae3de2,0x3e94be57,0xbe573e94,0x3de2beae,0x3de23eae,0xbe57be94,0x3e943e57,0xbeaebde2,
0,0,0,0,0,0,0,0,0,0,0,0,0,0,0,0,
0,0,0,0,0,0,0,0,0,0,0,0,0,0,0,0,
0xbe57be94,0x3eae3de2,0xbeae3de2,0x3e57be94,0xbe943e57,0x3de2beae,0x3de23eae,0xbe94be57,0x3e57be94,0x3de23eae,0xbeaebde2,0x3e94be57,0xbe94be57,0x3eaebde2,0xbde23eae,0xbe57be94,
0x3eae3de2,0xbe573e94,0xbe57be94,0x3eaebde2,0x3de2beae,0x3e943e57,0xbe943e57,0xbde2beae,0x3eb7,0xbeb70000,0xbeb7,0x3eb70000,0x3eb78000,0x3eb7,0xbeb78000,0xbeb7,
0,0,0,0,0,0,0,0,0,0,0,0,0,0,0,0,
0,0,0,0,0,0,0,0,0,0,0,0,0,0,0,0,
0xbeae3de2,0xbe57be94,0x3e57be94,0x3eae3de2,0x3de23eae,0xbe943e57,0xbe94be57,0x3de2beae,0xbe57be94,0x3de2beae,0x3eaebde2,0x3e943e57,0xbe943e57,0xbeaebde2,0xbde2beae,0x3e57be94,
0x3e57be94,0x3eaebde2,0x3eae3de2,0x3e573e94,0xbe94be57,0xbde2beae,0x3de2beae,0x3e94be57,0x3eae3de2,0x3e943e57,0x3e573e94,0x3de23eae,0x3de2beae,0x3e57be94,0x3e94be57,0x3eaebde2,
};
__device__ __align__(128) const uint32_t TAB_P3[4288] = {
0,0,0,0,0,0,0,0,0,0,0,0,0,0,0,0,
0x80003e83,0xbe79bda2,0x3e1abe54,0x3e1a3e54,0x3e830000,0xbda23e79,0xbe54be1a,0x3e54be1a,0x80003e83,0xbe54be1a,0x3e79bda2,0xbda23e79,0x3e830000,0xbe1a3e54,0xbda2be79,0x3e793da2,
0,0,0,0,0,0,0,0,0,0,0,0,0,0,0,0,
0xbe793da2,0x8000be83,0x3e793da2,0xbe1a3e54,0x3da23e79,0xbe830000,0x3da2be79,0x3e543e1a,0xbe1abe54,0x3e830000,0xbe1a3e54,0xbda2be79,0xbe543e1a,0xbe83,0x3e543e1a,0xbe793da2,
0x80003e83,0xbe1abe54,0x3e793da2,0xbe793da2,0x3e830000,0xbe543e1a,0x3da2be79,0x3da23e79,0x80003e83,0xbda2be79,0x3e1a3e54,0xbe54be1a,0x3e830000,0xbe793da2,0x3e54be1a,0xbe1a3e54,
0x80003e83,0x8000be83,0x80003e83,0x8000be83,0x3e830000,0xbe830000,0x3e830000,0xbe830000,0x80003e83,0x3da2be79,0xbe1a3e54,0x3e54be1a,0x3e830000,0xbe79bda2,0x3e543e1a,0xbe1abe54,
0x3e1abe54,0x80003e83,0xbe1abe54,0x3e793da2,0xbe54be1a,0x3e830000,0xbe543e1a,0x3da2be79,0x3e793da2,0xbe830000,0x3e79bda2,0xbe543e1a,0x3da2be79,0x3e83,0xbda2be79,0x3e1a3e54,
0x80003e83,0x8000be83,0x80003e83,0x8000be83,0x3e830000,0xbe830000,0x3e830000,0xbe830000,0xbe793da2,0x3e830000,0xbe79bda2,0x3e543e1a,0x3da23e79,0xbe83,0xbda23e79,0x3e1abe54,
0x80003e83,0x3e1abe54,0xbe793da2,0x3e793da2,0x3e830000,0xbe54be1a,0x3da23e79,0x3da2be79,0x80003e83,0x3e54be1a,0xbe79bda2,0x3da23e79,0x3e830000,0xbe1abe54,0xbda23e79,0x3e79bda2,
0x80003e83,0x3e79bda2,0xbe1abe54,0xbe1a3e54,0x3e830000,0xbda2be79,0xbe543e1a,0x3e543e1a,0x80003e83,0x3e830000,0x8000be83,0xbe830000,0x3e830000,0xbe83,0xbe830000,0x3e83,
0xbe1abe54,0x80003e83,0x3e1abe54,0xbe793da2,0xbe543e1a,0x3e830000,0xbe54be1a,0x3da23e79,0x3e1abe54,0xbe830000,0x3e1a3e54,0x3da2be79,0xbe54be1a,0x3e83,0x3e54be1a,0xbe79bda2,
0x3e793da2,0x8000be83,0xbe793da2,0x3e1a3e54,0x3da2be79,0xbe830000,0x3da23e79,0x3e54be1a,0x80003e83,0x3e830000,0x8000be83,0xbe830000,0x3e830000,0xbe83,0xbe830000,0x3e83,
0x80003e83,0x3e793da2,0x3e1abe54,0xbe1abe54,0x3e830000,0x3da2be79,0xbe54be1a,0xbe543e1a,0x80003e83,0x3e543e1a,0x3e79bda2,0x3da2be79,0x3e830000,0x3e1abe54,0xbda2be79,0xbe79bda2,
0x80003e83,0x3e1a3e54,0x3e793da2,0x3e79bda2,0x3e830000,0x3e54be1a,0x3da2be79,0xbda2be79,0x80003e83,0x3da23e79,0x3e1a3e54,0x3e543e1a,0x3e830000,0x3e79bda2,0x3e54be1a,0x3e1abe54,
0xbe793da2,0x80003e83,0x3e793da2,0x3e1abe54,0x3da23e79,0x3e830000,0x3da2be79,0xbe54be1a,0xbe1abe54,0xbe830000,0xbe1a3e54,0x3da23e79,0xbe543e1a,0x3e83,0x3e543e1a,0x3e79bda2,
0x3e1abe54,0x8000be83,0xbe1abe54,0xbe79bda2,0xbe54be1a,0xbe830000,0xbe543e1a,0xbda23e79,0x3e793da2,0x3e830000,0x3e79bda2,0x3e54be1a,0x3da2be79,0xbe83,0xbda2be79,0xbe1abe54,
0,0,0,0,0,0,0,0,0,0,0,0,0,0,0,0,
0,0,0,0,0,0,0,0,0,0,0,0,0,0,0,0,
0,0,0,0,0,0,0,0,0,0,0,0,0,0,0,0,
0xbe1abe54,0x3e79bda2,0x80003e83,0xbe79bda2,0xbe543e1a,0xbda2be79,0x3e830000,0xbda23e79,0x3e793da2,0xbe543e1a,0x8000be83,0x3e543e1a,0x3da2be79,0x3e1a3e54,0xbe830000,0x3e1abe54,
0,0,0,0,0,0,0,0,0,0,0,0,0,0,0,0,
0,0,0,0,0,0,0,0,0,0,0,0,0,0,0,0,
0xbe793da2,0x3e1abe54,0x80003e83,0xbe1abe54,0x3da23e79,0xbe54be1a,0x3e830000,0xbe543e1a,0x3e1abe54,0xbda23e79,0x8000be83,0x3da23e79,0xbe54be1a,0x3e793da2,0xbe830000,0x3e79bda2,
0x80003e83,0x8000be83,0x80003e83,0x8000be83,0x3e830000,0xbe830000,0x3e830000,0xbe830000,0xbe1abe54,0x3da23e79,0x8000be83,0xbda23e79,0xbe543e1a,0x3e79bda2,0xbe830000,0x3e793da2,
0,0,0,0,0,0,0,0,0,0,0,0,0,0,0,0,
0,0,0,0,0,0,0,0,0,0,0,0,0,0,0,0,
0x3e793da2,0xbe1abe54,0x80003e83,0x3e1abe54,0x3da2be79,0xbe543e1a,0x3e830000,0xbe54be1a,0xbe793da2,0x3e543e1a,0x8000be83,0xbe543e1a,0x3da23e79,0x3e1abe54,0xbe830000,0x3e1a3e54,
0x3e1abe54,0xbe79bda2,0x80003e83,0x3e79bda2,0xbe54be1a,0xbda23e79,0x3e830000,0xbda2be79,0x80003e83,0x3e830000,0x8000be83,0xbe830000,0x3e830000,0xbe83,0xbe830000,0x3e83,
0,0,0,0,0,0,0,0,0,0,0,0,0,0,0,0,
0,0,0,0,0,0,0,0,0,0,0,0,0,0,0,0,
0xbe1abe54,0xbe793da2,0x80003e83,0x3e793da2,0xbe543e1a,0x3da23e79,0x3e830000,0x3da2be79,0x3e793da2,0x3e54be1a,0x8000be83,0xbe54be1a,0x3da2be79,0xbe1abe54,0xbe830000,0xbe1a3e54,
0xbe793da2,0xbe1a3e54,0x80003e83,0x3e1a3e54,0x3da23e79,0x3e543e1a,0x3e830000,0x3e54be1a,0x3e1abe54,0x3da2be79,0x8000be83,0xbda2be79,0xbe54be1a,0xbe79bda2,0xbe830000,0xbe793da2,
0,0,0,0,0,0,0,0,0,0,0,0,0,0,0,0,
0x3e1abe54,0x3e1a3e54,0xbe793da2,0x8000be83,0xbe54be1a,0x3e54be1a,0x3da23e79,0xbe830000,0xbe793da2,0x3da2be79,0x3e1a3e54,0xbe830000,0x3da23e79,0xbe79bda2,0x3e54be1a,0x3e83,
0,0,0,0,0,0,0,0,0,0,0,0,0,0,0,0,
0x3e793da2,0xbe1a3e54,0xbe1abe54,0x3e79bda2,0x3da2be79,0x3e543e1a,0xbe543e1a,0xbda2be79,0x3e1abe54,0x3da23e79,0xbe79bda2,0x3e54be1a,0xbe54be1a,0x3e79bda2,0xbda23e79,0xbe1abe54,
0x3e793da2,0xbe793da2,0x3e1abe54,0x80003e83,0x3da2be79,0x3da23e79,0xbe54be1a,0x3e830000,0xbe1abe54,0x3e543e1a,0xbe79bda2,0x3e830000,0xbe543e1a,0x3e1abe54,0xbda23e79,0xbe83,
0x80003e83,0x8000be83,0x80003e83,0x8000be83,0x3e830000,0xbe830000,0x3e830000,0xbe830000,0x3e1abe54,0xbe543e1a,0x3e79bda2,0xbe830000,0xbe54be1a,0x3e1a3e54,0xbda2be79,0x3e83,
0xbe1abe54,0x3e793da2,0xbe793da2,0x3e1abe54,0xbe543e1a,0x3da2be79,0x3da23e79,0xbe54be1a,0xbe793da2,0x3e54be1a,0xbe1a3e54,0x3da2be79,0x3da23e79,0xbe1abe54,0x3e543e1a,0xbe79bda2,
0x80003e83,0x8000be83,0x80003e83,0x8000be83,0x3e830000,0xbe830000,0x3e830000,0xbe830000,0x3e793da2,0xbe54be1a,0x3e1a3e54,0xbda2be79,0x3da2be79,0xbe1a3e54,0x3e54be1a,0xbe793da2,
0xbe793da2,0x3e793da2,0xbe1abe54,0x80003e83,0x3da23e79,0x3da2be79,0xbe543e1a,0x3e830000,0x3e793da2,0xbda2be79,0xbe1a3e54,0x3e830000,0x3da2be79,0xbe793da2,0x3e543e1a,0xbe83,
0xbe1abe54,0xbe1a3e54,0x3e793da2,0x8000be83,0xbe543e1a,0x3e543e1a,0x3da2be79,0xbe830000,0x80003e83,0x3e830000,0x8000be83,0xbe830000,0x3e830000,0xbe83,0xbe830000,0x3e83,
0x3e1abe54,0xbe793da2,0x3e793da2,0xbe1abe54,0xbe54be1a,0x3da23e79,0x3da2be79,0xbe543e1a,0xbe1abe54,0xbda23e79,0x3e79bda2,0xbe54be1a,0xbe543e1a,0x3e793da2,0xbda2be79,0xbe1a3e54,
0xbe793da2,0x3e1a3e54,0x3e1abe54,0xbe79bda2,0x3da23e79,0x3e54be1a,0xbe54be1a,0xbda23e79,0x80003e83,0x3e830000,0x8000be83,0xbe830000,0x3e830000,0xbe83,0xbe830000,0x3e83,
0x3e1abe54,0xbe1abe54,0xbe793da2,0x80003e83,0xbe54be1a,0xbe543e1a,0x3da23e79,0x3e830000,0xbe793da2,0xbda23e79,0x3e1a3e54,0x3e830000,0x3da23e79,0x3e793da2,0x3e54be1a,0xbe83,
0x3e793da2,0x3e79bda2,0x3e1abe54,0x8000be83,0x3da2be79,0xbda2be79,0xbe54be1a,0xbe830000,0xbe1abe54,0xbe54be1a,0xbe79bda2,0xbe830000,0xbe543e1a,0xbe1a3e54,0xbda23e79,0x3e83,
0x3e793da2,0x3e1abe54,0xbe1abe54,0xbe793da2,0x3da2be79,0xbe54be1a,0xbe543e1a,0x3da23e79,0x3e1abe54,0xbda2be79,0xbe79bda2,0xbe543e1a,0xbe54be1a,0xbe793da2,0xbda23e79,0x3e1a3e54,
0xbe1abe54,0xbe79bda2,0xbe793da2,0xbe1a3e54,0xbe543e1a,0xbda23e79,0x3da23e79,0x3e543e1a,0xbe793da2,0xbe543e1a,0xbe1a3e54,0xbda23e79,0x3da23e79,0x3e1a3e54,0x3e543e1a,0x3e793da2,
0xbe163dda,0,0,0,0,0xbe163dda,0,0,0,0,0xbe163dda,0,0,0,0,0xbe163dda,
0xbe253da8,0,0,0,0,0xbe253da8,0,0,0,0,0xbe253da8,0,0,0,0,0xbe253da8,
0xbd65be30,0,0,0,0,0xbd65be30,0,0,0,0,0xbd65be30,0,0,0,0,0xbd65be30,
0x3ce8be37,0,0,0,0,0x3ce8be37,0,0,0,0,0x3ce8be37,0,0,0,0,0x3ce8be37,
0xbe303d65,0,0,0,0,0xbe303d65,0,0,0,0,0xbe303d65,0,0,0,0,0xbe303d65,
0xbe373ce8,0,0,0,0,0xbe373ce8,0,0,0,0,0xbe373ce8,0,0,0,0,0xbe373ce8,
0x3ddabe16,0,0,0,0,0x3ddabe16,0,0,0,0,0x3ddabe16,0,0,0,0,0x3ddabe16,
0x3e25bda8,0,0,0,0,0x3e25bda8,0,0,0,0,0x3e25bda8,0,0,0,0,0x3e25bda8,
0xbe390000,0,0,0,0,0xbe390000,0,0,0,0,0xbe390000,0,0,0,0,0xbe390000,
0xbe37bce8,0,0,0,0,0xbe37bce8,0,0,0,0,0xbe37bce8,0,0,0,0,0xbe37bce8,
0x3e390000,0,0,0,0,0x3e390000,0,0,0,0,0x3e390000,0,0,0,0,0x3e390000,
0x3e253da8,0,0,0,0,0x3e253da8,0,0,0,0,0x3e253da8,0,0,0,0,0x3e253da8,
0xbe30bd65,0,0,0,0,0xbe30bd65,0,0,0,0,0xbe30bd65,0,0,0,0,0xbe30bd65,
0xbe25bda8,0,0,0,0,0xbe25bda8,0,0,0,0,0xbe25bda8,0,0,0,0,0xbe25bda8,
0x3dda3e16,0,0,0,0,0x3dda3e16,0,0,0,0,0x3dda3e16,0,0,0,0,0x3dda3e16,
0x3ce83e37,0,0,0,0,0x3ce83e37,0,0,0,0,0x3ce83e37,0,0,0,0,0x3ce83e37,
0xbe16bdda,0,0,0,0,0xbe16bdda,0,0,0,0,0xbe16bdda,0,0,0,0,0xbe16bdda,
0xbe03be03,0,0,0,0,0xbe03be03,0,0,0,0,0xbe03be03,0,0,0,0,0xbe03be03,
0xbd653e30,0,0,0,0,0xbd653e30,0,0,0,0,0xbd653e30,0,0,0,0,0xbd653e30,
0xbe033e03,0,0,0,0,0xbe033e03,0,0,0,0,0xbe033e03,0,0,0,0,0xbe033e03,
0xbddabe16,0,0,0,0,0xbddabe16,0,0,0,0,0xbddabe16,0,0,0,0,0xbddabe16,
0xbda8be25,0,0,0,0,0xbda8be25,0,0,0,0,0xbda8be25,0,0,0,0,0xbda8be25,
0xbe303d65,0,0,0,0,0xbe303d65,0,0,0,0,0xbe303d65,0,0,0,0,0xbe303d65,
0xbe37bce8,0,0,0,0,0xbe37bce8,0,0,0,0,0xbe37bce8,0,0,0,0,0xbe37bce8,
0xbd65be30,0,0,0,0,0xbd65be30,0,0,0,0,0xbd65be30,0,0,0,0,0xbd65be30,
0xbce8be37,0,0,0,0,0xbce8be37,0,0,0,0,0xbce8be37,0,0,0,0,0xbce8be37,
0xbe16bdda,0,0,0,0,0xbe16bdda,0,0,0,0,0xbe16bdda,0,0,0,0,0xbe16bdda,
0xbda8be25,0,0,0,0,0xbda8be25,0,0,0,0,0xbda8be25,0,0,0,0,0xbda8be25,
0x3e390000,0,0,0,0,0x3e390000,0,0,0,0,0x3e390000,0,0,0,0,0x3e390000,
0x3e033e03,0,0,0,0,0x3e033e03,0,0,0,0,0x3e033e03,0,0,0,0,0x3e033e03,
0xbd653e30,0,0,0,0,0xbd653e30,0,0,0,0,0xbd653e30,0,0,0,0,0xbd653e30,
0xbe373ce8,0,0,0,0,0xbe373ce8,0,0,0,0,0xbe373ce8,0,0,0,0,0xbe373ce8,
0x80003e39,0,0,0,0,0x80003e39,0,0,0,0,0x80003e39,0,0,0,0,0x80003e39,
0xbe033e03,0,0,0,0,0xbe033e03,0,0,0,0,0xbe033e03,0,0,0,0,0xbe033e03,
0xbddabe16,0,0,0,0,0xbddabe16,0,0,0,0,0xbddabe16,0,0,0,0,0xbddabe16,
0x3da8be25,0,0,0,0,0x3da8be25,0,0,0,0,0x3da8be25,0,0,0,0,0x3da8be25,
0xbe390000,0,0,0,0,0xbe390000,0,0,0,0,0xbe390000,0,0,0,0,0xbe390000,
0xbe03be03,0,0,0,0,0xbe03be03,0,0,0,0,0xbe03be03,0,0,0,0,0xbe03be03,
0x3e390000,0,0,0,0,0x3e390000,0,0,0,0,0x3e390000,0,0,0,0,0x3e390000,
0x3da83e25,0,0,0,0,0x3da83e25,0,0,0,0,0x3da83e25,0,0,0,0,0x3da83e25,
0x8000be39,0,0,0,0,0x8000be39,0,0,0,0,0x8000be39,0,0,0,0,0x8000be39,
0x3e03be03,0,0,0,0,0x3e03be03,0,0,0,0,0x3e03be03,0,0,0,0,0x3e03be03,
0xbdda3e16,0,0,0,0,0xbdda3e16,0,0,0,0,0xbdda3e16,0,0,0,0,0xbdda3e16,
0xbe37bce8,0,0,0,0,0xbe37bce8,0,0,0,0,0xbe37bce8,0,0,0,0,0xbe37bce8,
0x3e390000,0,0,0,0,0x3e390000,0,0,0,0,0x3e390000,0,0,0,0,0x3e390000,
0x3e033e03,0,0,0,0,0x3e033e03,0,0,0,0,0x3e033e03,0,0,0,0,0x3e033e03,
0xbd65be30,0,0,0,0,0xbd65be30,0,0,0,0,0xbd65be30,0,0,0,0,0xbd65be30,
0x3e03be03,0,0,0,0,0x3e03be03,0,0,0,0,0x3e03be03,0,0,0,0,0x3e03be03,
0x80003e39,0,0,0,0,0x80003e39,0,0,0,0,0x80003e39,0,0,0,0,0x80003e39,
0xbe033e03,0,0,0,0,0xbe033e03,0,0,0,0,0xbe033e03,0,0,0,0,0xbe033e03,
0x3e303d65,0,0,0,0,0x3e303d65,0,0,0,0,0x3e303d65,0,0,0,0,0x3e303d65,
0x3ce83e37,0,0,0,0,0x3ce83e37,0,0,0,0,0x3ce83e37,0,0,0,0,0x3ce83e37,
0xbe390000,0,0,0,0,0xbe390000,0,0,0,0,0xbe390000,0,0,0,0,0xbe390000,
0xbe03be03,0,0,0,0,0xbe03be03,0,0,0,0,0xbe03be03,0,0,0,0,0xbe03be03,
0xbe163dda,0,0,0,0,0xbe163dda,0,0,0,0,0xbe163dda,0,0,0,0,0xbe163dda,
0xbe25bda8,0,0,0,0,0xbe25bda8,0,0,0,0,0xbe25bda8,0,0,0,0,0xbe25bda8,
0xbe16bdda,0,0,0,0,0xbe16bdda,0,0,0,0,0xbe16bdda,0,0,0,0,0xbe16bdda,
0x3da8be25,0,0,0,0,0x3da8be25,0,0,0,0,0x3da8be25,0,0,0,0,0x3da8be25,
0x3e16bdda,0,0,0,0,0x3e16bdda,0,0,0,0,0x3e16bdda,0,0,0,0,0x3e16bdda,
0x3da83e25,0,0,0,0,0x3da83e25,0,0,0,0,0x3da83e25,0,0,0,0,0x3da83e25,
0x3e303d65,0,0,0,0,0x3e303d65,0,0,0,0,0x3e303d65,0,0,0,0,0x3e303d65,
0xbce83e37,0,0,0,0,0xbce83e37,0,0,0,0,0xbce83e37,0,0,0,0,0xbce83e37,
0xbe303d65,0,0,0,0,0xbe303d65,0,0,0,0,0xbe303d65,0,0,0,0,0xbe303d65,
0xbce8be37,0,0,0,0,0xbce8be37,0,0,0,0,0xbce8be37,0,0,0,0,0xbce8be37,
0xbe390000,0,0,0,0,0xbe390000,0,0,0,0,0xbe390000,0,0,0,0,0xbe390000,
0xbce8be37,0,0,0,0,0xbce8be37,0,0,0,0,0xbce8be37,0,0,0,0,0xbce8be37,
0x3e390000,0,0,0,0,0x3e390000,0,0,0,0,0x3e390000,0,0,0,0,0x3e390000,
0xbce83e37,0,0,0,0,0xbce83e37,0,0,0,0,0xbce83e37,0,0,0,0,0xbce83e37,
0x3e30bd65,0,0,0,0,0x3e30bd65,0,0,0,0,0x3e30bd65,0,0,0,0,0x3e30bd65,
0x3da83e25,0,0,0,0,0x3da83e25,0,0,0,0,0x3da83e25,0,0,0,0,0x3da83e25,
0xbe30bd65,0,0,0,0,0xbe30bd65,0,0,0,0,0xbe30bd65,0,0,0,0,0xbe30bd65,
0x3da8be25,0,0,0,0,0x3da8be25,0,0,0,0,0x3da8be25,0,0,0,0,0x3da8be25,
0xbe163dda,0,0,0,0,0xbe163dda,0,0,0,0,0xbe163dda,0,0,0,0,0xbe163dda,
0xbe03be03,0,0,0,0,0xbe03be03,0,0,0,0,0xbe03be03,0,0,0,0,0xbe03be03,
0x3e163dda,0,0,0,0,0x3e163dda,0,0,0,0,0x3e163dda,0,0,0,0,0x3e163dda,
0xbe033e03,0,0,0,0,0xbe033e03,0,0,0,0,0xbe033e03,0,0,0,0,0xbe033e03,
0x3ddabe16,0,0,0,0,0x3ddabe16,0,0,0,0,0x3ddabe16,0,0,0,0,0x3ddabe16,
0x3e253da8,0,0,0,0,0x3e253da8,0,0,0,0,0x3e253da8,0,0,0,0,0x3e253da8,
0xbddabe16,0,0,0,0,0xbddabe16,0,0,0,0,0xbddabe16,0,0,0,0,0xbddabe16,
0x3e25bda8,0,0,0,0,0x3e25bda8,0,0,0,0,0x3e25bda8,0,0,0,0,0x3e25bda8,
0xbd653e30,0,0,0,0,0xbd653e30,0,0,0,0,0xbd653e30,0,0,0,0,0xbd653e30,
0xbe37bce8,0,0,0,0,0xbe37bce8,0,0,0,0,0xbe37bce8,0,0,0,0,0xbe37bce8,
0x3d653e30,0,0,0,0,0x3d653e30,0,0,0,0,0x3d653e30,0,0,0,0,0x3d653e30,
0xbe373ce8,0,0,0,0,0xbe373ce8,0,0,0,0,0xbe373ce8,0,0,0,0,0xbe373ce8,
0x3d653e30,0,0,0,0,0x3d653e30,0,0,0,0,0x3d653e30,0,0,0,0,0x3d653e30,
0xbe37bce8,0,0,0,0,0xbe37bce8,0,0,0,0,0xbe37bce8,0,0,0,0,0xbe37bce8,
0xbe390000,0,0,0,0,0xbe390000,0,0,0,0,0xbe390000,0,0,0,0,0xbe390000,
0x3e03be03,0,0,0,0,0x3e03be03,0,0,0,0,0x3e03be03,0,0,0,0,0x3e03be03,
0x3ddabe16,0,0,0,0,0x3ddabe16,0,0,0,0,0x3ddabe16,0,0,0,0,0x3ddabe16,
0x3da83e25,0,0,0,0,0x3da83e25,0,0,0,0,0x3da83e25,0,0,0,0,0x3da83e25,
0x80003e39,0,0,0,0,0x80003e39,0,0,0,0,0x80003e39,0,0,0,0,0x80003e39,
0xbe03be03,0,0,0,0,0xbe03be03,0,0,0,0,0xbe03be03,0,0,0,0,0xbe03be03,
0xbe390000,0,0,0,0,0xbe390000,0,0,0,0,0xbe390000,0,0,0,0,0xbe390000,
0x3da8be25,0,0,0,0,0x3da8be25,0,0,0,0,0x3da8be25,0,0,0,0,0x3da8be25,
0x3e390000,0,0,0,0,0x3e390000,0,0,0,0,0x3e390000,0,0,0,0,0x3e390000,
0xbe033e03,0,0,0,0,0xbe033e03,0,0,0,0,0xbe033e03,0,0,0,0,0xbe033e03,
0x3dda3e16,0,0,0,0,0x3dda3e16,0,0,0,0,0x3dda3e16,0,0,0,0,0x3dda3e16,
0xbe373ce8,0,0,0,0,0xbe373ce8,0,0,0,0,0xbe373ce8,0,0,0,0,0xbe373ce8,
0x8000be39,0,0,0,0,0x8000be39,0,0,0,0,0x8000be39,0,0,0,0,0x8000be39,
0x3e033e03,0,0,0,0,0x3e033e03,0,0,0,0,0x3e033e03,0,0,0,0,0x3e033e03,
0x3d65be30,0,0,0,0,0x3d65be30,0,0,0,0,0x3d65be30,0,0,0,0,0x3d65be30,
0x3e033e03,0,0,0,0,0x3e033e03,0,0,0,0,0x3e033e03,0,0,0,0,0x3e033e03,
0xbe390000,0,0,0,0,0xbe390000,0,0,0,0,0xbe390000,0,0,0,0,0xbe390000,
0x3e03be03,0,0,0,0,0x3e03be03,0,0,0,0,0x3e03be03,0,0,0,0,0x3e03be03,
0xbe303d65,0,0,0,0,0xbe303d65,0,0,0,0,0xbe303d65,0,0,0,0,0xbe303d65,
0x3ce8be37,0,0,0,0,0x3ce8be37,0,0,0,0,0x3ce8be37,0,0,0,0,0x3ce8be37,
0x80003e39,0,0,0,0,0x80003e39,0,0,0,0,0x80003e39,0,0,0,0,0x80003e39,
0xbe03be03,0,0,0,0,0xbe03be03,0,0,0,0,0xbe03be03,0,0,0,0,0xbe03be03,
0x3e163dda,0,0,0,0,0x3e163dda,0,0,0,0,0x3e163dda,0,0,0,0,0x3e163dda,
0xbe253da8,0,0,0,0,0xbe253da8,0,0,0,0,0xbe253da8,0,0,0,0,0xbe253da8,
0x3e390000,0,0,0,0,0x3e390000,0,0,0,0,0x3e390000,0,0,0,0,0x3e390000,
0xbe033e03,0,0,0,0,0xbe033e03,0,0,0,0,0xbe033e03,0,0,0,0,0xbe033e03,
0x3d65be30,0,0,0,0,0x3d65be30,0,0,0,0,0x3d65be30,0,0,0,0,0x3d65be30,
0x3ce83e37,0,0,0,0,0x3ce83e37,0,0,0,0,0x3ce83e37,0,0,0,0,0x3ce83e37,
0x3e163dda,0,0,0,0,0x3e163dda,0,0,0,0,0x3e163dda,0,0,0,0,0x3e163dda,
0xbe25bda8,0,0,0,0,0xbe25bda8,0,0,0,0,0xbe25bda8,0,0,0,0,0xbe25bda8,
0xbddabe16,0,0,0,0,0xbddabe16,0,0,0,0,0xbddabe16,0,0,0,0,0xbddabe16,
0x3e253da8,0,0,0,0,0x3e253da8,0,0,0,0,0x3e253da8,0,0,0,0,0x3e253da8,
0x3e303d65,0,0,0,0,0x3e303d65,0,0,0,0,0x3e303d65,0,0,0,0,0x3e303d65,
0xbe37bce8,0,0,0,0,0xbe37bce8,0,0,0,0,0xbe37bce8,0,0,0,0,0xbe37bce8,
0xbe390000,0,0,0,0,0xbe390000,0,0,0,0,0xbe390000,0,0,0,0,0xbe390000,
0x3e25bda8,0,0,0,0,0x3e25bda8,0,0,0,0,0x3e25bda8,0,0,0,0,0x3e25bda8,
0x3e390000,0,0,0,0,0x3e390000,0,0,0,0,0x3e390000,0,0,0,0,0x3e390000,
0xbe373ce8,0,0,0,0,0xbe373ce8,0,0,0,0,0xbe373ce8,0,0,0,0,0xbe373ce8,
0xbdda3e16,0,0,0,0,0xbdda3e16,0,0,0,0,0xbdda3e16,0,0,0,0,0xbdda3e16,
0x3ce8be37,0,0,0,0,0x3ce8be37,0,0,0,0,0x3ce8be37,0,0,0,0,0x3ce8be37,
0x3e30bd65,0,0,0,0,0x3e30bd65,0,0,0,0,0x3e30bd65,0,0,0,0,0x3e30bd65,
0xbe253da8,0,0,0,0,0xbe253da8,0,0,0,0,0xbe253da8,0,0,0,0,0xbe253da8,
0x3d653e30,0,0,0,0,0x3d653e30,0,0,0,0,0x3d653e30,0,0,0,0,0x3d653e30,
0xbe03be03,0,0,0,0,0xbe03be03,0,0,0,0,0xbe03be03,0,0,0,0,0xbe03be03,
0x3e16bdda,0,0,0,0,0x3e16bdda,0,0,0,0,0x3e16bdda,0,0,0,0,0x3e16bdda,
0xbe033e03,0,0,0,0,0xbe033e03,0,0,0,0,0xbe033e03,0,0,0,0,0xbe033e03,
0x3e303d65,0,0,0,0,0x3e303d65,0,0,0,0,0x3e303d65,0,0,0,0,0x3e303d65,
0xbe373ce8,0,0,0,0,0xbe373ce8,0,0,0,0,0xbe373ce8,0,0,0,0,0xbe373ce8,
0x3ddabe16,0,0,0,0,0x3ddabe16,0,0,0,0,0x3ddabe16,0,0,0,0,0x3ddabe16,
0xbda83e25,0,0,0,0,0xbda83e25,0,0,0,0,0xbda83e25,0,0,0,0,0xbda83e25,
0x3e16bdda,0,0,0,0,0x3e16bdda,0,0,0,0,0x3e16bdda,0,0,0,0,0x3e16bdda,
0xbda83e25,0,0,0,0,0xbda83e25,0,0,0,0,0xbda83e25,0,0,0,0,0xbda83e25,
0x3d65be30,0,0,0,0,0x3d65be30,0,0,0,0,0x3d65be30,0,0,0,0,0x3d65be30,
0xbce83e37,0,0,0,0,0xbce83e37,0,0,0,0,0xbce83e37,0,0,0,0,0xbce83e37,
0,0,0xbe163dda,0,0,0,0,0xbe163dda,0,0,0xbe253da8,0,0,0,0,0xbe253da8,
0,0,0xbe303d65,0,0,0,0,0xbe303d65,0,0,0xbe373ce8,0,0,0,0,0xbe373ce8,
0,0,0xbd65be30,0,0,0,0,0xbd65be30,0,0,0x3ce8be37,0,0,0,0,0x3ce8be37,
0,0,0x3ddabe16,0,0,0,0,0x3ddabe16,0,0,0x3e25bda8,0,0,0,0,0x3e25bda8,
0,0,0xbe390000,0,0,0,0,0xbe390000,0,0,0xbe37bce8,0,0,0,0,0xbe37bce8,
0,0,0xbe30bd65,0,0,0,0,0xbe30bd65,0,0,0xbe25bda8,0,0,0,0,0xbe25bda8,
0,0,0x3e390000,0,0,0,0,0x3e390000,0,0,0x3e253da8,0,0,0,0,0x3e253da8,
0,0,0x3dda3e16,0,0,0,0,0x3dda3e16,0,0,0x3ce83e37,0,0,0,0,0x3ce83e37,
0,0,0xbe16bdda,0,0,0,0,0xbe16bdda,0,0,0xbe03be03,0,0,0,0,0xbe03be03,
0,0,0xbddabe16,0,0,0,0,0xbddabe16,0,0,0xbda8be25,0,0,0,0,0xbda8be25,
0,0,0xbd653e30,0,0,0,0,0xbd653e30,0,0,0xbe033e03,0,0,0,0,0xbe033e03,
0,0,0xbe303d65,0,0,0,0,0xbe303d65,0,0,0xbe37bce8,0,0,0,0,0xbe37bce8,
0,0,0xbd65be30,0,0,0,0,0xbd65be30,0,0,0xbce8be37,0,0,0,0,0xbce8be37,
0,0,0,0,0,0,0,0,0,0,0,0,0,0,0,0,
0,0,0xbe16bdda,0,0,0,0,0xbe16bdda,0,0,0xbda8be25,0,0,0,0,0xbda8be25,
0,0,0,0,0,0,0,0,0,0,0,0,0,0,0,0,
0,0,0x3e390000,0,0,0,0,0x3e390000,0,0,0x3e033e03,0,0,0,0,0x3e033e03,
0,0,0x80003e39,0,0,0,0,0x80003e39,0,0,0xbe033e03,0,0,0,0,0xbe033e03,
0,0,0xbd653e30,0,0,0,0,0xbd653e30,0,0,0xbe373ce8,0,0,0,0,0xbe373ce8,
0,0,0xbddabe16,0,0,0,0,0xbddabe16,0,0,0x3da8be25,0,0,0,0,0x3da8be25,
0,0,0xbe390000,0,0,0,0,0xbe390000,0,0,0xbe03be03,0,0,0,0,0xbe03be03,
0,0,0x8000be39,0,0,0,0,0x8000be39,0,0,0x3e03be03,0,0,0,0,0x3e03be03,
0,0,0x3e390000,0,0,0,0,0x3e390000,0,0,0x3da83e25,0,0,0,0,0x3da83e25,
0,0,0xbdda3e16,0,0,0,0,0xbdda3e16,0,0,0xbe37bce8,0,0,0,0,0xbe37bce8,
0,0,0x3e390000,0,0,0,0,0x3e390000,0,0,0x3e033e03,0,0,0,0,0x3e033e03,
0,0,0x80003e39,0,0,0,0,0x80003e39,0,0,0xbe033e03,0,0,0,0,0xbe033e03,
0,0,0xbd65be30,0,0,0,0,0xbd65be30,0,0,0x3e03be03,0,0,0,0,0x3e03be03,
0,0,0x3e303d65,0,0,0,0,0x3e303d65,0,0,0x3ce83e37,0,0,0,0,0x3ce83e37,
0,0,0xbe390000,0,0,0,0,0xbe390000,0,0,0xbe03be03,0,0,0,0,0xbe03be03,
0,0,0,0,0,0,0,0,0,0,0,0,0,0,0,0,
0,0,0xbe163dda,0,0,0,0,0xbe163dda,0,0,0xbe25bda8,0,0,0,0,0xbe25bda8,
0,0,0,0,0,0,0,0,0,0,0,0,0,0,0,0,
0,0,0xbe16bdda,0,0,0,0,0xbe16bdda,0,0,0x3da8be25,0,0,0,0,0x3da8be25,
0,0,0x3e303d65,0,0,0,0,0x3e303d65,0,0,0xbce83e37,0,0,0,0,0xbce83e37,
0,0,0x3e16bdda,0,0,0,0,0x3e16bdda,0,0,0x3da83e25,0,0,0,0,0x3da83e25,
0,0,0xbe303d65,0,0,0,0,0xbe303d65,0,0,0xbce8be37,0,0,0,0,0xbce8be37,
0,0,0xbe390000,0,0,0,0,0xbe390000,0,0,0xbce8be37,0,0,0,0,0xbce8be37,
0,0,0x3e30bd65,0,0,0,0,0x3e30bd65,0,0,0x3da83e25,0,0,0,0,0x3da83e25,
0,0,0x3e390000,0,0,0,0,0x3e390000,0,0,0xbce83e37,0,0,0,0,0xbce83e37,
0,0,0xbe30bd65,0,0,0,0,0xbe30bd65,0,0,0x3da8be25,0,0,0,0,0x3da8be25,
0,0,0xbe163dda,0,0,0,0,0xbe163dda,0,0,0xbe03be03,0,0,0,0,0xbe03be03,
0,0,0x3ddabe16,0,0,0,0,0x3ddabe16,0,0,0x3e253da8,0,0,0,0,0x3e253da8,
0,0,0x3e163dda,0,0,0,0,0x3e163dda,0,0,0xbe033e03,0,0,0,0,0xbe033e03,
0,0,0xbddabe16,0,0,0,0,0xbddabe16,0,0,0x3e25bda8,0,0,0,0,0x3e25bda8,
0,0,0xbd653e30,0,0,0,0,0xbd653e30,0,0,0xbe37bce8,0,0,0,0,0xbe37bce8,
0,0,0,0,0,0,0,0,0,0,0,0,0,0,0,0,
0,0,0x3d653e30,0,0,0,0,0x3d653e30,0,0,0xbe373ce8,0,0,0,0,0xbe373ce8,
0,0,0,0,0,0,0,0,0,0,0,0,0,0,0,0,
0,0,0x3d653e30,0,0,0,0,0x3d653e30,0,0,0xbe37bce8,0,0,0,0,0xbe37bce8,
0,0,0x3ddabe16,0,0,0,0,0x3ddabe16,0,0,0x3da83e25,0,0,0,0,0x3da83e25,
0,0,0xbe390000,0,0,0,0,0xbe390000,0,0,0x3e03be03,0,0,0,0,0x3e03be03,
0,0,0x80003e39,0,0,0,0,0x80003e39,0,0,0xbe03be03,0,0,0,0,0xbe03be03,
0,0,0xbe390000,0,0,0,0,0xbe390000,0,0,0x3da8be25,0,0,0,0,0x3da8be25,
0,0,0x3dda3e16,0,0,0,0,0x3dda3e16,0,0,0xbe373ce8,0,0,0,0,0xbe373ce8,
0,0,0x3e390000,0,0,0,0,0x3e390000,0,0,0xbe033e03,0,0,0,0,0xbe033e03,
0,0,0x8000be39,0,0,0,0,0x8000be39,0,0,0x3e033e03,0,0,0,0,0x3e033e03,
0,0,0x3d65be30,0,0,0,0,0x3d65be30,0,0,0x3e033e03,0,0,0,0,0x3e033e03,
0,0,0xbe303d65,0,0,0,0,0xbe303d65,0,0,0x3ce8be37,0,0,0,0,0x3ce8be37,
0,0,0xbe390000,0,0,0,0,0xbe390000,0,0,0x3e03be03,0,0,0,0,0x3e03be03,
0,0,0x80003e39,0,0,0,0,0x80003e39,0,0,0xbe03be03,0,0,0,0,0xbe03be03,
0,0,0x3e163dda,0,0,0,0,0x3e163dda,0,0,0xbe253da8,0,0,0,0,0xbe253da8,
0,0,0,0,0,0,0,0,0,0,0,0,0,0,0,0,
0,0,0x3e390000,0,0,0,0,0x3e390000,0,0,0xbe033e03,0,0,0,0,0xbe033e03,
0,0,0,0,0,0,0,0,0,0,0,0,0,0,0,0,
0,0,0x3d65be30,0,0,0,0,0x3d65be30,0,0,0x3ce83e37,0,0,0,0,0x3ce83e37,
0,0,0xbddabe16,0,0,0,0,0xbddabe16,0,0,0x3e253da8,0,0,0,0,0x3e253da8,
0,0,0x3e163dda,0,0,0,0,0x3e163dda,0,0,0xbe25bda8,0,0,0,0,0xbe25bda8,
0,0,0x3e303d65,0,0,0,0,0x3e303d65,0,0,0xbe37bce8,0,0,0,0,0xbe37bce8,
0,0,0xbe390000,0,0,0,0,0xbe390000,0,0,0x3e25bda8,0,0,0,0,0x3e25bda8,
0,0,0xbdda3e16,0,0,0,0,0xbdda3e16,0,0,0x3ce8be37,0,0,0,0,0x3ce8be37,
0,0,0x3e390000,0,0,0,0,0x3e390000,0,0,0xbe373ce8,0,0,0,0,0xbe373ce8,
0,0,0x3e30bd65,0,0,0,0,0x3e30bd65,0,0,0xbe253da8,0,0,0,0,0xbe253da8,
0,0,0x3d653e30,0,0,0,0,0x3d653e30,0,0,0xbe03be03,0,0,0,0,0xbe03be03,
0,0,0x3e303d65,0,0,0,0,0x3e303d65,0,0,0xbe373ce8,0,0,0,0,0xbe373ce8,
0,0,0x3e16bdda,0,0,0,0,0x3e16bdda,0,0,0xbe033e03,0,0,0,0,0xbe033e03,
0,0,0x3ddabe16,0,0,0,0,0x3ddabe16,0,0,0xbda83e25,0,0,0,0,0xbda83e25,
0,0,0x3e16bdda,0,0,0,0,0x3e16bdda,0,0,0xbda83e25,0,0,0,0,0xbda83e25,
0,0,0,0,0,0,0,0,0,0,0,0,0,0,0,0,
0,0,0x3d65be30,0,0,0,0,0x3d65be30,0,0,0xbce83e37,0,0,0,0,0xbce83e37,
0,0,0,0,0,0,0,0,0,0,0,0,0,0,0,0,
};
constexpr unsigned long long COS_PK0 = 0x3f903f9a3fa03fa2ull;
constexpr unsigned long long COS_PK1 = 0x3f133f3e3f653f83ull;
constexpr unsigned long long COS_PK2 = 0x3e4b3ec8ull;

__device__ __forceinline__ void wgmma_ss_n80_z(float (&d)[40], uint64_t da, uint64_t db) {
  asm volatile("{\n.reg .pred p;\nsetp.ne.b32 p, 0, 0;\nwgmma.mma_async.sync.aligned.m64n80k16.f32.bf16.bf16 {%0,%1,%2,%3,%4,%5,%6,%7,%8,%9,%10,%11,%12,%13,%14,%15,%16,%17,%18,%19,%20,%21,%22,%23,%24,%25,%26,%27,%28,%29,%30,%31,%32,%33,%34,%35,%36,%37,%38,%39}, %40, %41, p, 1, 1, 1, 0;\n}\n"
    : "+f"(d[0]), "+f"(d[1]), "+f"(d[2]), "+f"(d[3]), "+f"(d[4]), "+f"(d[5]), "+f"(d[6]), "+f"(d[7]), "+f"(d[8]), "+f"(d[9]), "+f"(d[10]), "+f"(d[11]), "+f"(d[12]), "+f"(d[13]), "+f"(d[14]), "+f"(d[15]), "+f"(d[16]), "+f"(d[17]), "+f"(d[18]), "+f"(d[19]), "+f"(d[20]), "+f"(d[21]), "+f"(d[22]), "+f"(d[23]), "+f"(d[24]), "+f"(d[25]), "+f"(d[26]), "+f"(d[27]), "+f"(d[28]), "+f"(d[29]), "+f"(d[30]), "+f"(d[31]), "+f"(d[32]), "+f"(d[33]), "+f"(d[34]), "+f"(d[35]), "+f"(d[36]), "+f"(d[37]), "+f"(d[38]), "+f"(d[39])
    : "l"(da), "l"(db));
}
__device__ __forceinline__ void wgmma_ss_n80_a(float (&d)[40], uint64_t da, uint64_t db) {
  asm volatile("{\n.reg .pred p;\nsetp.ne.b32 p, 1, 0;\nwgmma.mma_async.sync.aligned.m64n80k16.f32.bf16.bf16 {%0,%1,%2,%3,%4,%5,%6,%7,%8,%9,%10,%11,%12,%13,%14,%15,%16,%17,%18,%19,%20,%21,%22,%23,%24,%25,%26,%27,%28,%29,%30,%31,%32,%33,%34,%35,%36,%37,%38,%39}, %40, %41, p, 1, 1, 1, 0;\n}\n"
    : "+f"(d[0]), "+f"(d[1]), "+f"(d[2]), "+f"(d[3]), "+f"(d[4]), "+f"(d[5]), "+f"(d[6]), "+f"(d[7]), "+f"(d[8]), "+f"(d[9]), "+f"(d[10]), "+f"(d[11]), "+f"(d[12]), "+f"(d[13]), "+f"(d[14]), "+f"(d[15]), "+f"(d[16]), "+f"(d[17]), "+f"(d[18]), "+f"(d[19]), "+f"(d[20]), "+f"(d[21]), "+f"(d[22]), "+f"(d[23]), "+f"(d[24]), "+f"(d[25]), "+f"(d[26]), "+f"(d[27]), "+f"(d[28]), "+f"(d[29]), "+f"(d[30]), "+f"(d[31]), "+f"(d[32]), "+f"(d[33]), "+f"(d[34]), "+f"(d[35]), "+f"(d[36]), "+f"(d[37]), "+f"(d[38]), "+f"(d[39])
    : "l"(da), "l"(db));
}

__device__ __forceinline__ void wgmma_rs_n40_z(float (&d)[20], uint32_t a0, uint32_t a1, uint32_t a2, uint32_t a3, uint64_t db) {
  asm volatile("{\n.reg .pred p;\nsetp.ne.b32 p, 0, 0;\nwgmma.mma_async.sync.aligned.m64n40k16.f32.bf16.bf16 {%0,%1,%2,%3,%4,%5,%6,%7,%8,%9,%10,%11,%12,%13,%14,%15,%16,%17,%18,%19}, {%20,%21,%22,%23}, %24, p, 1, 1, 0;\n}\n"
    : "+f"(d[0]), "+f"(d[1]), "+f"(d[2]), "+f"(d[3]), "+f"(d[4]), "+f"(d[5]), "+f"(d[6]), "+f"(d[7]), "+f"(d[8]), "+f"(d[9]), "+f"(d[10]), "+f"(d[11]), "+f"(d[12]), "+f"(d[13]), "+f"(d[14]), "+f"(d[15]), "+f"(d[16]), "+f"(d[17]), "+f"(d[18]), "+f"(d[19])
    : "r"(a0), "r"(a1), "r"(a2), "r"(a3), "l"(db));
}
__device__ __forceinline__ void wgmma_rs_n40_a(float (&d)[20], uint32_t a0, uint32_t a1, uint32_t a2, uint32_t a3, uint64_t db) {
  asm volatile("{\n.reg .pred p;\nsetp.ne.b32 p, 1, 0;\nwgmma.mma_async.sync.aligned.m64n40k16.f32.bf16.bf16 {%0,%1,%2,%3,%4,%5,%6,%7,%8,%9,%10,%11,%12,%13,%14,%15,%16,%17,%18,%19}, {%20,%21,%22,%23}, %24, p, 1, 1, 0;\n}\n"
    : "+f"(d[0]), "+f"(d[1]), "+f"(d[2]), "+f"(d[3]), "+f"(d[4]), "+f"(d[5]), "+f"(d[6]), "+f"(d[7]), "+f"(d[8]), "+f"(d[9]), "+f"(d[10]), "+f"(d[11]), "+f"(d[12]), "+f"(d[13]), "+f"(d[14]), "+f"(d[15]), "+f"(d[16]), "+f"(d[17]), "+f"(d[18]), "+f"(d[19])
    : "r"(a0), "r"(a1), "r"(a2), "r"(a3), "l"(db));
}

__device__ __forceinline__ void wgmma_rs_n128_z(float (&d)[64], uint32_t a0, uint32_t a1, uint32_t a2, uint32_t a3, uint64_t db) {
  asm volatile("{\n.reg .pred p;\nsetp.ne.b32 p, 0, 0;\nwgmma.mma_async.sync.aligned.m64n128k16.f32.bf16.bf16 {%0,%1,%2,%3,%4,%5,%6,%7,%8,%9,%10,%11,%12,%13,%14,%15,%16,%17,%18,%19,%20,%21,%22,%23,%24,%25,%26,%27,%28,%29,%30,%31,%32,%33,%34,%35,%36,%37,%38,%39,%40,%41,%42,%43,%44,%45,%46,%47,%48,%49,%50,%51,%52,%53,%54,%55,%56,%57,%58,%59,%60,%61,%62,%63}, {%64,%65,%66,%67}, %68, p, 1, 1, 1;\n}\n"
    : "+f"(d[0]), "+f"(d[1]), "+f"(d[2]), "+f"(d[3]), "+f"(d[4]), "+f"(d[5]), "+f"(d[6]), "+f"(d[7]), "+f"(d[8]), "+f"(d[9]), "+f"(d[10]), "+f"(d[11]), "+f"(d[12]), "+f"(d[13]), "+f"(d[14]), "+f"(d[15]), "+f"(d[16]), "+f"(d[17]), "+f"(d[18]), "+f"(d[19]), "+f"(d[20]), "+f"(d[21]), "+f"(d[22]), "+f"(d[23]), "+f"(d[24]), "+f"(d[25]), "+f"(d[26]), "+f"(d[27]), "+f"(d[28]), "+f"(d[29]), "+f"(d[30]), "+f"(d[31]), "+f"(d[32]), "+f"(d[33]), "+f"(d[34]), "+f"(d[35]), "+f"(d[36]), "+f"(d[37]), "+f"(d[38]), "+f"(d[39]), "+f"(d[40]), "+f"(d[41]), "+f"(d[42]), "+f"(d[43]), "+f"(d[44]), "+f"(d[45]), "+f"(d[46]), "+f"(d[47]), "+f"(d[48]), "+f"(d[49]), "+f"(d[50]), "+f"(d[51]), "+f"(d[52]), "+f"(d[53]), "+f"(d[54]), "+f"(d[55]), "+f"(d[56]), "+f"(d[57]), "+f"(d[58]), "+f"(d[59]), "+f"(d[60]), "+f"(d[61]), "+f"(d[62]), "+f"(d[63])
    : "r"(a0), "r"(a1), "r"(a2), "r"(a3), "l"(db));
}
__device__ __forceinline__ void wgmma_rs_n128_a(float (&d)[64], uint32_t a0, uint32_t a1, uint32_t a2, uint32_t a3, uint64_t db) {
  asm volatile("{\n.reg .pred p;\nsetp.ne.b32 p, 1, 0;\nwgmma.mma_async.sync.aligned.m64n128k16.f32.bf16.bf16 {%0,%1,%2,%3,%4,%5,%6,%7,%8,%9,%10,%11,%12,%13,%14,%15,%16,%17,%18,%19,%20,%21,%22,%23,%24,%25,%26,%27,%28,%29,%30,%31,%32,%33,%34,%35,%36,%37,%38,%39,%40,%41,%42,%43,%44,%45,%46,%47,%48,%49,%50,%51,%52,%53,%54,%55,%56,%57,%58,%59,%60,%61,%62,%63}, {%64,%65,%66,%67}, %68, p, 1, 1, 1;\n}\n"
    : "+f"(d[0]), "+f"(d[1]), "+f"(d[2]), "+f"(d[3]), "+f"(d[4]), "+f"(d[5]), "+f"(d[6]), "+f"(d[7]), "+f"(d[8]), "+f"(d[9]), "+f"(d[10]), "+f"(d[11]), "+f"(d[12]), "+f"(d[13]), "+f"(d[14]), "+f"(d[15]), "+f"(d[16]), "+f"(d[17]), "+f"(d[18]), "+f"(d[19]), "+f"(d[20]), "+f"(d[21]), "+f"(d[22]), "+f"(d[23]), "+f"(d[24]), "+f"(d[25]), "+f"(d[26]), "+f"(d[27]), "+f"(d[28]), "+f"(d[29]), "+f"(d[30]), "+f"(d[31]), "+f"(d[32]), "+f"(d[33]), "+f"(d[34]), "+f"(d[35]), "+f"(d[36]), "+f"(d[37]), "+f"(d[38]), "+f"(d[39]), "+f"(d[40]), "+f"(d[41]), "+f"(d[42]), "+f"(d[43]), "+f"(d[44]), "+f"(d[45]), "+f"(d[46]), "+f"(d[47]), "+f"(d[48]), "+f"(d[49]), "+f"(d[50]), "+f"(d[51]), "+f"(d[52]), "+f"(d[53]), "+f"(d[54]), "+f"(d[55]), "+f"(d[56]), "+f"(d[57]), "+f"(d[58]), "+f"(d[59]), "+f"(d[60]), "+f"(d[61]), "+f"(d[62]), "+f"(d[63])
    : "r"(a0), "r"(a1), "r"(a2), "r"(a3), "l"(db));
}

__device__ __forceinline__ void wgmma_rs_n32_z(float (&d)[16], uint32_t a0, uint32_t a1, uint32_t a2, uint32_t a3, uint64_t db) {
  asm volatile("{\n.reg .pred p;\nsetp.ne.b32 p, 0, 0;\nwgmma.mma_async.sync.aligned.m64n32k16.f32.bf16.bf16 {%0,%1,%2,%3,%4,%5,%6,%7,%8,%9,%10,%11,%12,%13,%14,%15}, {%16,%17,%18,%19}, %20, p, 1, 1, 0;\n}\n"
    : "+f"(d[0]), "+f"(d[1]), "+f"(d[2]), "+f"(d[3]), "+f"(d[4]), "+f"(d[5]), "+f"(d[6]), "+f"(d[7]), "+f"(d[8]), "+f"(d[9]), "+f"(d[10]), "+f"(d[11]), "+f"(d[12]), "+f"(d[13]), "+f"(d[14]), "+f"(d[15])
    : "r"(a0), "r"(a1), "r"(a2), "r"(a3), "l"(db));
}
__device__ __forceinline__ void wgmma_rs_n32_a(float (&d)[16], uint32_t a0, uint32_t a1, uint32_t a2, uint32_t a3, uint64_t db) {
  asm volatile("{\n.reg .pred p;\nsetp.ne.b32 p, 1, 0;\nwgmma.mma_async.sync.aligned.m64n32k16.f32.bf16.bf16 {%0,%1,%2,%3,%4,%5,%6,%7,%8,%9,%10,%11,%12,%13,%14,%15}, {%16,%17,%18,%19}, %20, p, 1, 1, 0;\n}\n"
    : "+f"(d[0]), "+f"(d[1]), "+f"(d[2]), "+f"(d[3]), "+f"(d[4]), "+f"(d[5]), "+f"(d[6]), "+f"(d[7]), "+f"(d[8]), "+f"(d[9]), "+f"(d[10]), "+f"(d[11]), "+f"(d[12]), "+f"(d[13]), "+f"(d[14]), "+f"(d[15])
    : "r"(a0), "r"(a1), "r"(a2), "r"(a3), "l"(db));
}

__device__ __forceinline__ void wgmma_rs_n64_z(float (&d)[32], uint32_t a0, uint32_t a1, uint32_t a2, uint32_t a3, uint64_t db) {
  asm volatile("{\n.reg .pred p;\nsetp.ne.b32 p, 0, 0;\nwgmma.mma_async.sync.aligned.m64n64k16.f32.bf16.bf16 {%0,%1,%2,%3,%4,%5,%6,%7,%8,%9,%10,%11,%12,%13,%14,%15,%16,%17,%18,%19,%20,%21,%22,%23,%24,%25,%26,%27,%28,%29,%30,%31}, {%32,%33,%34,%35}, %36, p, 1, 1, 0;\n}\n"
    : "+f"(d[0]), "+f"(d[1]), "+f"(d[2]), "+f"(d[3]), "+f"(d[4]), "+f"(d[5]), "+f"(d[6]), "+f"(d[7]), "+f"(d[8]), "+f"(d[9]), "+f"(d[10]), "+f"(d[11]), "+f"(d[12]), "+f"(d[13]), "+f"(d[14]), "+f"(d[15]), "+f"(d[16]), "+f"(d[17]), "+f"(d[18]), "+f"(d[19]), "+f"(d[20]), "+f"(d[21]), "+f"(d[22]), "+f"(d[23]), "+f"(d[24]), "+f"(d[25]), "+f"(d[26]), "+f"(d[27]), "+f"(d[28]), "+f"(d[29]), "+f"(d[30]), "+f"(d[31])
    : "r"(a0), "r"(a1), "r"(a2), "r"(a3), "l"(db));
}
__device__ __forceinline__ void wgmma_rs_n64_a(float (&d)[32], uint32_t a0, uint32_t a1, uint32_t a2, uint32_t a3, uint64_t db) {
  asm volatile("{\n.reg .pred p;\nsetp.ne.b32 p, 1, 0;\nwgmma.mma_async.sync.aligned.m64n64k16.f32.bf16.bf16 {%0,%1,%2,%3,%4,%5,%6,%7,%8,%9,%10,%11,%12,%13,%14,%15,%16,%17,%18,%19,%20,%21,%22,%23,%24,%25,%26,%27,%28,%29,%30,%31}, {%32,%33,%34,%35}, %36, p, 1, 1, 0;\n}\n"
    : "+f"(d[0]), "+f"(d[1]), "+f"(d[2]), "+f"(d[3]), "+f"(d[4]), "+f"(d[5]), "+f"(d[6]), "+f"(d[7]), "+f"(d[8]), "+f"(d[9]), "+f"(d[10]), "+f"(d[11]), "+f"(d[12]), "+f"(d[13]), "+f"(d[14]), "+f"(d[15]), "+f"(d[16]), "+f"(d[17]), "+f"(d[18]), "+f"(d[19]), "+f"(d[20]), "+f"(d[21]), "+f"(d[22]), "+f"(d[23]), "+f"(d[24]), "+f"(d[25]), "+f"(d[26]), "+f"(d[27]), "+f"(d[28]), "+f"(d[29]), "+f"(d[30]), "+f"(d[31])
    : "r"(a0), "r"(a1), "r"(a2), "r"(a3), "l"(db));
}

__device__ __forceinline__ void wgmma_ss_n32_z(float (&d)[16], uint64_t da, uint64_t db) {
  asm volatile("{\n.reg .pred p;\nsetp.ne.b32 p, 0, 0;\nwgmma.mma_async.sync.aligned.m64n32k16.f32.bf16.bf16 {%0,%1,%2,%3,%4,%5,%6,%7,%8,%9,%10,%11,%12,%13,%14,%15}, %16, %17, p, 1, 1, 1, 0;\n}\n"
    : "+f"(d[0]), "+f"(d[1]), "+f"(d[2]), "+f"(d[3]), "+f"(d[4]), "+f"(d[5]), "+f"(d[6]), "+f"(d[7]), "+f"(d[8]), "+f"(d[9]), "+f"(d[10]), "+f"(d[11]), "+f"(d[12]), "+f"(d[13]), "+f"(d[14]), "+f"(d[15])
    : "l"(da), "l"(db));
}
__device__ __forceinline__ void wgmma_ss_n32_a(float (&d)[16], uint64_t da, uint64_t db) {
  asm volatile("{\n.reg .pred p;\nsetp.ne.b32 p, 1, 0;\nwgmma.mma_async.sync.aligned.m64n32k16.f32.bf16.bf16 {%0,%1,%2,%3,%4,%5,%6,%7,%8,%9,%10,%11,%12,%13,%14,%15}, %16, %17, p, 1, 1, 1, 0;\n}\n"
    : "+f"(d[0]), "+f"(d[1]), "+f"(d[2]), "+f"(d[3]), "+f"(d[4]), "+f"(d[5]), "+f"(d[6]), "+f"(d[7]), "+f"(d[8]), "+f"(d[9]), "+f"(d[10]), "+f"(d[11]), "+f"(d[12]), "+f"(d[13]), "+f"(d[14]), "+f"(d[15])
    : "l"(da), "l"(db));
}

__device__ __forceinline__ void wgmma_ss_n40_z(float (&d)[20], uint64_t da, uint64_t db) {
  asm volatile("{\n.reg .pred p;\nsetp.ne.b32 p, 0, 0;\nwgmma.mma_async.sync.aligned.m64n40k16.f32.bf16.bf16 {%0,%1,%2,%3,%4,%5,%6,%7,%8,%9,%10,%11,%12,%13,%14,%15,%16,%17,%18,%19}, %20, %21, p, 1, 1, 1, 0;\n}\n"
    : "+f"(d[0]), "+f"(d[1]), "+f"(d[2]), "+f"(d[3]), "+f"(d[4]), "+f"(d[5]), "+f"(d[6]), "+f"(d[7]), "+f"(d[8]), "+f"(d[9]), "+f"(d[10]), "+f"(d[11]), "+f"(d[12]), "+f"(d[13]), "+f"(d[14]), "+f"(d[15]), "+f"(d[16]), "+f"(d[17]), "+f"(d[18]), "+f"(d[19])
    : "l"(da), "l"(db));
}
__device__ __forceinline__ void wgmma_ss_n40_a(float (&d)[20], uint64_t da, uint64_t db) {
  asm volatile("{\n.reg .pred p;\nsetp.ne.b32 p, 1, 0;\nwgmma.mma_async.sync.aligned.m64n40k16.f32.bf16.bf16 {%0,%1,%2,%3,%4,%5,%6,%7,%8,%9,%10,%11,%12,%13,%14,%15,%16,%17,%18,%19}, %20, %21, p, 1, 1, 1, 0;\n}\n"
    : "+f"(d[0]), "+f"(d[1]), "+f"(d[2]), "+f"(d[3]), "+f"(d[4]), "+f"(d[5]), "+f"(d[6]), "+f"(d[7]), "+f"(d[8]), "+f"(d[9]), "+f"(d[10]), "+f"(d[11]), "+f"(d[12]), "+f"(d[13]), "+f"(d[14]), "+f"(d[15]), "+f"(d[16]), "+f"(d[17]), "+f"(d[18]), "+f"(d[19])
    : "l"(da), "l"(db));
}

constexpr int NSM = 132, NH = 66;
constexpr int S0 = 0, S1 = 51200, S2 = 102400;
constexpr int C1 = 153600, C3 = C1, RG = C1 + 18432;
constexpr int WP = RG, TBL = RG + 28672, WS2 = RG + 30720;
constexpr int BARS = RG + 49152;
__host__ __device__ constexpr int wst_off(int i) { return i < 12 ? S2 + i * 4096 : WS2 + (i - 12) * 4096; }
constexpr int NBAR = 280;
constexpr int REL = BARS + NBAR * 8;
constexpr int SMEM_BYTES = REL + 16;
constexpr int B_XF = 0, B_CF1 = 15, B_CF3 = 16, B_WF = 17  , B_P1D = 18, B_WFREE = 20, B_REL = 21, B_ROLE = 22, B_X1 = 23, B_SIG = 24;
constexpr int B_RF = 32, B_RE = 46, B_YF = 60, B_WRD = 75, B_SFREE = 89, B_WCH = 131, B_RDY = 136, B_WE = 205, B_WL = 217, B_FIN = 229, B_TOK = 232;
constexpr int R_P2 = 15, R_P3 = 57;
constexpr int CNT_P1 = 0, CNT_P2 = 4, CNT_W = 8, CNT_RANK = 9, NCLS = 10, CNT_DONE = 0, CNT_REL = 1, NCNT = 2;
constexpr int SIG_W = 0, SIG_P1 = 1, SIG_P2 = 4;
#define PROBES 1
#define WB 100
#define PACE 0
#define PACE_SLACK 300
#define SWIN 3
#define X1AT 10
#define WARMUP 0
#define YPACE 0
#define POLL3 0
#define XPF 0
#define PSLEEP 0
#define TRICKLE
#define T1MASK 0x3e00
#define T2MASK 0x1f00
#define Y0AT 1
#define Y3FROM 1
#define EM58 2
#define TOKD 1
#define TOKM 6
#define WWIN 4
#define WHOLD 99
#define LAZYC 1
#define X1BOX 0
#define X2BOX 5

__device__ uint4 g_scr[(14 << 21) / 16];
__device__ uint4 g_wf[200 * 72 * 32];
__device__ unsigned g_cnt[NCNT * 32];
__device__ __forceinline__ int slot_line(int chunk, int pg, int cls) {
    return (pg & 1) << 6 | (pg >> 1) << 9 | (chunk & 1) << 10 | (chunk >> 1) << 12 | ((pg ^ (pg >> 1) ^ chunk ^ (chunk >> 1) ^ cls) & 1) << 5;
}
__device__ __forceinline__ int phi_line(int phi, uint32_t rel) {
    return (phi >> 4) << 14 | (phi & 3) << 7 | ((phi >> 2) & 1) << 11 | ((phi >> 3) & 1) << 13 | ((rel >> (phi >> 4)) & 1) << 5;
}
__device__ __forceinline__ int extra_mask(int rk) { return rk < 58 ? 0 : rk < 60 ? EM58 : rk < 62 ? 1 : rk < 64 ? (EM58 == 2 ? 4 : 2) : (EM58 == 8 ? 4 : 8); }
__device__ __forceinline__ int wslot(int pc) {
    return (int)((0x576476503421ull >> (4 * pc)) & 3) * 12288 + (((0x576476503421ull >> (4 * pc)) & 4) ? S0 : RG);
}
__device__ __forceinline__ int xslot(int n) { return ((n & 4) ? S2 : RG) + ((n + 1) & 3) * 12288; }
__device__ __forceinline__ int extra_phi(int rk) { return 198 + (rk & 1); }
__host__ __device__ constexpr int quad_off(int Q) { return (Q >> 2) * 4096 + (Q & 3) * 512; }

#define PROF(k)
#define PROFW(k)
#define prof_dump()
struct Maps { CUtensorMap w, x34, x6, x28, wst, f16, f8, y4, y2; };
struct Ptrs { char* scr; const char* wf; const void* tab1; const void* tab3; unsigned* cnt; };

__device__ __forceinline__ uint32_t smem_u32(const void* p) { return (uint32_t)__cvta_generic_to_shared(p); }
__device__ __forceinline__ void mbar_wait(uint32_t bar) {
    uint32_t ok, it = 0;
    do {
        asm volatile("{\n.reg .pred p;\nmbarrier.try_wait.parity.shared::cta.b64 p, [%1], 0;\nselp.u32 %0, 1, 0, p;\n}" : "=r"(ok) : "r"(bar) : "memory");
        if (++it > (1u << 22)) break;
    } while (!ok);
}
__device__ __forceinline__ bool mbar_test(uint32_t bar) {
    uint32_t ok;
    asm volatile("{\n.reg .pred p;\nmbarrier.test_wait.parity.shared::cta.b64 p, [%1], 0;\nselp.u32 %0, 1, 0, p;\n}" : "=r"(ok) : "r"(bar) : "memory");
    return ok;
}
__device__ __forceinline__ void fence_async() { asm volatile("fence.proxy.async;" ::: "memory"); }
__device__ __forceinline__ void fence_async_smem() { asm volatile("fence.proxy.async.shared::cta;" ::: "memory"); }
#define ELECT "{\n.reg .pred p;\nelect.sync _|p, 0xffffffff;\n@p "
__device__ __forceinline__ void e_arrive(uint32_t bar) { asm volatile(ELECT "mbarrier.arrive.shared::cta.b64 _, [%0];\n}" :: "r"(bar) : "memory"); }
__device__ __forceinline__ void e_expect(uint32_t bar, uint32_t bytes) { asm volatile(ELECT "mbarrier.arrive.expect_tx.shared::cta.b64 _, [%0], %1;\n}" :: "r"(bar), "r"(bytes) : "memory"); }
__device__ __forceinline__ void e_g2s(uint32_t dst, const void* src, uint32_t bytes, uint32_t bar) {
    asm volatile(ELECT "cp.async.bulk.shared::cluster.global.mbarrier::complete_tx::bytes [%0], [%1], %2, [%3];\n}" :: "r"(dst), "l"(src), "r"(bytes), "r"(bar) : "memory");
}
__device__ __forceinline__ void e_s2g(void* dst, uint32_t src, uint32_t bytes) {
    asm volatile(ELECT "cp.async.bulk.global.shared::cta.bulk_group [%0], [%1], %2;\n}" :: "l"(dst), "r"(src), "r"(bytes) : "memory");
}
__device__ __forceinline__ void e_ld3(uint32_t dst, const CUtensorMap* m, int c0, int c1, int c2, uint32_t bar) {
    asm volatile(ELECT "cp.async.bulk.tensor.3d.shared::cluster.global.mbarrier::complete_tx::bytes [%0], [%1, {%3, %4, %5}], [%2];\n}"
                 :: "r"(dst), "l"(m), "r"(bar), "r"(c0), "r"(c1), "r"(c2) : "memory");
}
__device__ __forceinline__ void e_ld4(uint32_t dst, const CUtensorMap* m, int c0, int c3, uint32_t bar) {
    asm volatile(ELECT "cp.async.bulk.tensor.4d.shared::cluster.global.mbarrier::complete_tx::bytes [%0], [%1, {%3, %5, %5, %4}], [%2];\n}"
                 :: "r"(dst), "l"(m), "r"(bar), "r"(c0), "r"(c3), "r"(0) : "memory");
}
__device__ __forceinline__ void e_st3(const CUtensorMap* m, uint32_t src, int c0, int c1, int c2) {
    asm volatile(ELECT "cp.async.bulk.tensor.3d.global.shared::cta.bulk_group [%0, {%2, %3, %4}], [%1];\n}" :: "l"(m), "r"(src), "r"(c0), "r"(c1), "r"(c2) : "memory");
}
__device__ __forceinline__ void e_ld5(uint32_t dst, const CUtensorMap* m, int c4, uint32_t bar) {
    asm volatile(ELECT "cp.async.bulk.tensor.5d.shared::cluster.global.mbarrier::complete_tx::bytes [%0], [%1, {%4, %4, %4, %4, %3}], [%2];\n}"
                 :: "r"(dst), "l"(m), "r"(bar), "r"(c4), "r"(0) : "memory");
}
__device__ __forceinline__ void e_st5(const CUtensorMap* m, uint32_t src, int c4) {
    asm volatile(ELECT "cp.async.bulk.tensor.5d.global.shared::cta.bulk_group [%0, {%3, %3, %3, %3, %2}], [%1];\n}" :: "l"(m), "r"(src), "r"(c4), "r"(0) : "memory");
}
__device__ __forceinline__ void bulk_commit() { asm volatile("cp.async.bulk.commit_group;" ::: "memory"); }
template <int N> __device__ __forceinline__ void bulk_wait_read() { asm volatile("cp.async.bulk.wait_group.read %0;" :: "n"(N) : "memory"); }
__device__ __forceinline__ void wg_bar(int id) { asm volatile("bar.sync %0, 128;" :: "r"(id) : "memory"); }
__device__ __forceinline__ void bb_break(uint32_t v) { asm volatile("{\n.reg .pred p;\nsetp.eq.u32 p, %0, 0x7fc17fc1;\n@p nanosleep.u32 0;\n}" :: "r"(v) : "memory"); }
__device__ __forceinline__ uint32_t uni(uint32_t v) { return __shfl_sync(0xffffffffu, v, 0); }
__device__ __forceinline__ char* cls_cnt(char* scr, int cls) { return scr + slot_line(3, 2, cls) * 128; }
__device__ __forceinline__ uint32_t cnt_wait(const void* p, unsigned target) {
    auto ld = [&]() { unsigned v; asm volatile("ld.relaxed.gpu.global.u32 %0, [%1];" : "=r"(v) : "l"(p) : "memory"); return v; };
    unsigned v0 = ld(), v;
#pragma unroll 1
    for (unsigned it = 0; it < (1u << 22); it++) { if ((v = uni(v0)) >= target) break; if (PSLEEP) __nanosleep(PSLEEP); v0 = ld(); }
    return v;
}
__device__ __forceinline__ void wg_fence() { asm volatile("wgmma.fence.sync.aligned;" ::: "memory"); }
__device__ __forceinline__ void wg_commit() { asm volatile("wgmma.commit_group.sync.aligned;" ::: "memory"); }
template <int N> __device__ __forceinline__ void wg_wait() { asm volatile("wgmma.wait_group.sync.aligned %0;" :: "n"(N) : "memory"); }
template <int N> __device__ __forceinline__ void reg_fence(float (&d)[N]) {
#pragma unroll
    for (int i = 0; i < N; i++) asm volatile("" : "+f"(d[i]) :: "memory");
}
template <int N, int O, int M> __device__ __forceinline__ float (&sub(float (&d)[M]))[N] { return *reinterpret_cast<float (*)[N]>(&d[O]); }
template <int N> __device__ __forceinline__ void zero(float (&d)[N]) {
#pragma unroll
    for (int i = 0; i < N; i++) d[i] = 0.f;
}
__device__ __forceinline__ uint32_t pack2(float lo, float hi) {
    uint32_t r; asm volatile("cvt.rn.bf16x2.f32 %0, %1, %2;" : "=r"(r) : "f"(hi), "f"(lo)); return r;
}
__device__ __forceinline__ void stm4(uint32_t a, uint32_t r0, uint32_t r1, uint32_t r2, uint32_t r3) {
    asm volatile("stmatrix.sync.aligned.m8n8.x4.trans.shared.b16 [%0], {%1,%2,%3,%4};" :: "r"(a), "r"(r0), "r"(r1), "r"(r2), "r"(r3) : "memory");
}
__device__ __forceinline__ void stm2(uint32_t a, uint32_t r0, uint32_t r1) {
    asm volatile("stmatrix.sync.aligned.m8n8.x2.trans.shared.b16 [%0], {%1,%2};" :: "r"(a), "r"(r0), "r"(r1) : "memory");
}
__device__ __forceinline__ void stm1(uint32_t a, uint32_t r0) {
    asm volatile("stmatrix.sync.aligned.m8n8.x1.trans.shared.b16 [%0], {%1};" :: "r"(a), "r"(r0) : "memory");
}
struct Desc {
    uint32_t lo, hi;
    __device__ __forceinline__ operator uint64_t() const { return ((uint64_t)hi << 32) | lo; }
    __device__ __forceinline__ Desc operator+(uint32_t o) const { return Desc{lo + o, hi}; }
    __device__ __forceinline__ Desc operator^(uint32_t o) const { return Desc{lo ^ o, hi}; }
};
__device__ __forceinline__ Desc mkdesc(uint32_t addr, uint32_t lbo, uint32_t sbo, uint32_t swz) {
    return Desc{((addr & 0x3FFFF) >> 4) | ((lbo >> 4) << 16), (sbo >> 4) | (swz << 30)};
}
__device__ __forceinline__ uint32_t cos_bits(int k) {
    if (k > 20) k = 40 - k;
    const bool neg = k > 10;
    if (neg) k = 20 - k;
    const unsigned long long pk = k < 4 ? COS_PK0 : k < 8 ? COS_PK1 : COS_PK2;
    return (uint32_t)((pk >> (16 * (k & 3))) & 0xffff) ^ (neg ? 0x8000u : 0u);
}

__device__ __forceinline__ void task_w(int wg, int k, uint32_t sb) {
    const int tid = threadIdx.x & 127, w = uni(tid >> 5), lane = tid & 31, q = lane & 3;
    const int tb = 14 * k, t1 = min(tb + 14, 1800), cb0 = tb / 25;
    float acc[64];
    zero(acc);
    const int oc0 = tb - 25 * cb0, Lt = t1 - tb, L0 = min(Lt, 25 - oc0), n0 = (L0 + 3) >> 2;
    uint32_t a[2][4][4];
    auto gen = [&](uint32_t (&a)[4][4], int at) {
        const int phi = 8 * ((at < n0 ? oc0 + 4 * at : 4 * (at - n0)) + w) + (lane >> 2), f = (phi * 205) >> 12;
        const uint32_t ca = 8 * f + 4, cw = (phi - 20 * f) * 8, p0 = sb + TBL + cw * 2 * q;
#pragma unroll
        for (int kh = 0; kh < 7; kh++) {
            uint32_t v0, v1;
            asm volatile("ld.shared.u32 %0, [%1];" : "=r"(v0) : "r"(p0 + ca * kh));
            asm volatile("ld.shared.u32 %0, [%1];" : "=r"(v1) : "r"(p0 + cw + ca * kh));
            const int h = kh == 6 ? 1 : kh & 1;
            a[kh >> 1][2 * h] = __byte_perm(v0, v1, 0x5410);
            a[kh >> 1][2 * h + 1] = __byte_perm(v0, v1, 0x7632);
        }
        a[3][0] = 0; a[3][1] = 0;
    };
    gen(a[0], wg);
    if (wg) gen(a[1], wg + 2);
    PROFW(wg == 0 ? 124 : 127);
#pragma unroll 1
    for (int n = 0; n < 2; n++) {
        const int at = wg + 2 * n, i0 = at < n0 ? 4 * at : L0 + 4 * (at - n0), cnt = (at < n0 ? L0 : Lt) - i0, cb = cb0 + (at >= n0);
        if (cnt <= 0 || (n && !wg)) break;
        if (n) {
#pragma unroll
            for (int j = 0; j < 16; j++) a[0][j >> 2][j & 3] = a[1][j >> 2][j & 3];
        }
        const Desc dB = mkdesc(sb + WP + (cb - cb0) * 14336, 3584, 512, 2);
        if (at) mbar_wait(sb + BARS + 8 * (B_WCH + at - 1));
        mbar_wait(sb + BARS + 8 * (B_WF + 2 * (cb - cb0)));
        PROFW(at == 0 ? 125 : 127);
        wg_fence();
        wgmma_rs_n128_z(acc, a[0][0][0], a[0][0][1], a[0][0][2], a[0][0][3], dB);
        wgmma_rs_n128_a(acc, a[0][1][0], a[0][1][1], a[0][1][2], a[0][1][3], dB + (uint32_t)(16 * 64 >> 4));
        wgmma_rs_n128_a(acc, a[0][2][0], a[0][2][1], a[0][2][2], a[0][2][3], dB + (uint32_t)(32 * 64 >> 4));
        wgmma_rs_n128_a(acc, a[0][3][0], a[0][3][1], a[0][3][2], a[0][3][3], dB + (uint32_t)(40 * 64 >> 4));
        wg_commit();
        wg_wait<0>();
        reg_fence(acc);
        PROFW(at == 0 ? 120 : 127);
        e_arrive(sb + BARS + 8 * (B_WCH + at));
        if (w < cnt) {
            const uint32_t dst = sb + wst_off(i0 + w) + (lane >> 2) * 512 + (lane & 4) * 16 + ((q ^ cb) & 3) * 16;
#pragma unroll
            for (int j = 0; j < 4; j++)
#pragma unroll
                for (int e = 0; e < 2; e++)
                    asm volatile("st.shared.v4.u32 [%0], {%1,%2,%3,%4};" :: "r"((dst ^ (e * 64)) + j * 128),
                                 "r"(pack2(acc[4 * j + e], acc[16 + 4 * j + e])), "r"(pack2(acc[4 * j + 2 + e], acc[16 + 4 * j + 2 + e])),
                                 "r"(pack2(acc[32 + 4 * j + e], acc[48 + 4 * j + e])), "r"(pack2(acc[32 + 4 * j + 2 + e], acc[48 + 4 * j + 2 + e])) : "memory");
            fence_async_smem();
            e_arrive(sb + BARS + 8 * (B_WRD + i0 + w));
        }
    }
}

__device__ __forceinline__ void task_p1(int wg, int pair, uint32_t sb) {
    const int tid = threadIdx.x & 127, w = tid >> 5, lane = tid & 31;
    const uint32_t buf = sb + wg * 51200, bars = sb + BARS;
    uint32_t fr[5][10][2];
    float A[40], d[20];
    zero(A);
    {
        const Desc dA = mkdesc(buf, 3584, 512, 2), dB = mkdesc(sb + C1, 128, 256, 0);
        auto issue = [&](int g, float (&d)[40]) {
            mbar_wait(bars + 8 * (B_XF + wg * 5 + g));
            wg_fence();
            wgmma_ss_n80_z(d, dA + (uint32_t)(g * 8704 >> 4), dB);
#pragma unroll
            for (int j = 1; j < 5; j++) wgmma_ss_n80_a(d, dA + (uint32_t)((g * 8704 + j * 1024) >> 4), dB + (uint32_t)(j * 2560 >> 4));
            wg_commit();
        };
        auto pack = [&](int g, float (&d)[40]) {
            reg_fence(d);
#pragma unroll
            for (int f = 0; f < 10; f++) {
                fr[g][f][0] = pack2(d[4 * f], d[4 * f + 1]);
                fr[g][f][1] = pack2(d[4 * f + 2], d[4 * f + 3]);
            }
        };
        mbar_wait(bars + 8 * B_CF1);
#pragma unroll
        for (int g = 0; g < 4; g++) { issue(g, A); if (g == 0) PROFW(8 + wg * 8 + 1); wg_wait<0>(); pack(g, A); }
        zero(d);
        mbar_wait(bars + 8 * (B_XF + wg * 5 + 4));
#pragma unroll
        for (int h = 0; h < 2; h++) {
            wg_fence();
            wgmma_ss_n40_z(d, dA + (uint32_t)(4 * 8704 >> 4), dB + (uint32_t)(h * 1280 >> 4));
#pragma unroll
            for (int j = 1; j < 5; j++) wgmma_ss_n40_a(d, dA + (uint32_t)((4 * 8704 + j * 1024) >> 4), dB + (uint32_t)((j * 2560 + h * 1280) >> 4));
            wg_commit(); wg_wait<0>(); reg_fence(d);
#pragma unroll
            for (int f = 0; f < 5; f++) { fr[4][5 * h + f][0] = pack2(d[4 * f], d[4 * f + 1]); fr[4][5 * h + f][1] = pack2(d[4 * f + 2], d[4 * f + 3]); }
        }
    }
    bb_break(sb);
    wg_bar(1 + wg);
    PROFW(8 + wg * 8 + 2);
    {
        const Desc dB = mkdesc(sb + C1 + 12800, 128, 256, 0);
        const int i = lane & 7, mi = lane >> 3, th = w >> 1, tz = (2 * pair + th) & 3;
        const uint32_t s0 = buf + (i >> 1) * 128 + (i & 1) * 64 + (((2 * (w & 1) + (mi & 1)) ^ tz ^ (i >> 1)) << 4);
        const uint32_t sA = s0 + th * 2048 + (mi >> 1) * 512, sB = s0 + th * 2048 + (mi >> 1) * 2560, sC = s0 + th * 1024 + (mi >> 1) * 512;
        auto issue = [&](int f, float (&d)[20]) {
            wg_fence();
            wgmma_rs_n40_z(d, fr[0][f][0], fr[0][f][1], fr[1][f][0], fr[1][f][1], dB);
            wgmma_rs_n40_a(d, fr[2][f][0], fr[2][f][1], fr[3][f][0], fr[3][f][1], dB + (uint32_t)(1280 >> 4));
            wgmma_rs_n40_a(d, fr[4][f % 5][0], fr[4][f % 5][1], fr[4][f % 5 + 5][0], fr[4][f % 5 + 5][1], dB + (uint32_t)((2560 + (f / 5) * 1280) >> 4));
            wg_commit();
        };
#pragma unroll
        for (int f = 0; f < 10; f++) {
                        issue(f, d); wg_wait<0>(); reg_fence(d);
            const int Q = 5 * f;
            stm4(((Q & 3) == 3 ? sB : sA) + quad_off(Q), pack2(d[0], d[1]), pack2(d[2], d[3]), pack2(d[4], d[5]), pack2(d[6], d[7]));
            stm2(sA + quad_off(Q + 2), pack2(d[8], d[9]), pack2(d[10], d[11]));
            stm4((f == 9 ? sC : ((Q + 3) & 3) == 3 ? sB : sA) + quad_off(Q + 3), pack2(d[12], d[13]), pack2(d[14], d[15]), pack2(d[16], d[17]), pack2(d[18], d[19]));
            if (f & 1) { fence_async_smem(); e_arrive(bars + 8 * (B_RDY + wg * 5 + (f >> 1))); }
        }
    }
}

__device__ __forceinline__ void task_p2(int wg, int rk, uint32_t sb) {
    const int tid = threadIdx.x & 127, w = tid >> 5, lane = tid & 31;
    const uint32_t bars = sb + BARS;
    const int phi0 = 3 * rk, phiE = extra_phi(rk), mE = extra_mask(rk);
    uint4 wA[6], wB[6], wC[6], wE[6];
    auto ldw = [&](uint4 (&a)[6], int j, int phi) {
        const int pc = 3 * j + wg;
        const uint32_t p = sb + wslot(pc) + (lane & 3) * 512 + w * 128 + (((lane >> 2) ^ phi) & 1) * 64 + (((lane >> 3) ^ lane) & 3) * 16 + (phi & 1) * 8;
        mbar_wait(bars + 8 * (B_WL + pc));
#pragma unroll
        for (int s = 0; s < 6; s++) {
            asm volatile("ld.shared.v2.u32 {%0, %1}, [%2];" : "=r"(a[s].x), "=r"(a[s].y) : "r"(p + s * 2048) : "memory");
            asm volatile("ld.shared.v2.u32 {%0, %1}, [%2];" : "=r"(a[s].z), "=r"(a[s].w) : "r"((p ^ 8) + s * 2048) : "memory");
        }
        uint32_t dep = 0;
#pragma unroll
        for (int s = 0; s < 6; s++) dep |= a[s].x ^ a[s].z;
        if (__any_sync(0xffffffffu, dep == 0x7fc17fc1u)) __nanosleep(0);
        e_arrive(bars + 8 * (B_WE + pc));
    };
    ldw(wA, 0, phi0); ldw(wB, 1, phi0 + 1);
    if (!LAZYC) ldw(wC, 2, phi0 + 2);
    PROFW(8 + wg * 8 + 4);
    mbar_wait(bars + 8 * (B_SIG + SIG_P1 + 1));
    const int i = lane & 7, mi = lane >> 3;
    const uint32_t soff = sb + S1 + wg * 4096 + mi * 512 + (i >> 1) * 128 + (i & 1) * 64;
    const int xo = w ^ (i >> 1);
    float d[32];
    zero(d);
    int n = 0;
    uint32_t xb = ((sb + xslot(0)) & 0x3FFFF) >> 4 | 1u << 16, mb = bars + 8 * wg;
    bool landed = false;
    auto unit = [&](const uint4 (&a)[6], int z) {
        const Desc d0{xb + (z & 2), (512u >> 4) | (2u << 30)}, d1 = d0 ^ 2u;
        if (!landed) mbar_wait(bars + 8 * (B_RF + n));
        mbar_wait(mb + 8 * (B_TOK - 1));
        wg_fence();
        wgmma_rs_n64_z(d, a[0].x, a[0].y, a[0].z, a[0].w, d0);
        wgmma_rs_n64_a(d, a[1].x, a[1].y, a[1].z, a[1].w, d1);
        if (TOKM == 5) e_arrive(mb + 8 * B_TOK);
        e_arrive(bars + 8 * (n ? B_RE + n - 1 : B_RE + 13));
        const bool sfree = mbar_test(n >= 4 ? mb + 8 * (B_SFREE - 12) : bars + 8 * (B_TOK - 1));
        landed = mbar_test(bars + 8 * (B_RF + n + 1));
        wgmma_rs_n64_a(d, a[2].x, a[2].y, a[2].z, a[2].w, d0 + (uint32_t)(4096 >> 4));
        wgmma_rs_n64_a(d, a[3].x, a[3].y, a[3].z, a[3].w, d1 + (uint32_t)(4096 >> 4));
        if (TOKM == 6) e_arrive(mb + 8 * B_TOK);
        wgmma_rs_n64_a(d, a[4].x, a[4].y, a[4].z, a[4].w, d0 + (uint32_t)(8192 >> 4));
        wgmma_rs_n64_a(d, a[5].x, a[5].y, a[5].z, a[5].w, d1 + (uint32_t)(8192 >> 4));
        wg_commit();
        if (TOKM == 3) e_arrive(mb + 8 * B_TOK);
        if (!sfree) mbar_wait(mb + 8 * (B_SFREE - 12));
        const uint32_t a0 = soff + (n & 3) * 12288 + ((xo ^ z) << 4);
        n++;
        xb = ((sb + xslot(n)) & 0x3FFFF) >> 4 | 1u << 16;
        wg_wait<0>();
        reg_fence(d);
        uint32_t p[8];
#pragma unroll
        for (int j = 0; j < 8; j++) p[j] = pack2(d[4 * j] - d[4 * j + 3], d[4 * j + 2] + d[4 * j + 1]);
        stm4(a0, p[0], p[1], p[2], p[3]);
        stm4(a0 + 2048, p[4], p[5], p[6], p[7]);
        fence_async_smem();
        e_arrive(mb + 8 * (B_RDY + R_P2));
        mb += 24;
    };
    const int zA = phi0 & 3, zB = (phi0 + 1) & 3, zC = (phi0 + 2) & 3, zE = phiE & 3;
#pragma unroll 1
    for (int it = 0; it < 4; it++) {
        unit(wA, zA);
        PROFW(40 + wg * 8 + it * 2);
        unit(wB, zB);
        if (LAZYC && it == 0) ldw(wC, 2, phi0 + 2);
        unit(wC, zC);
        if (it == 0 && mE) ldw(wE, 3, phiE);
        if (mE >> it & 1) unit(wE, zE);
        PROFW(40 + wg * 8 + it * 2 + 1);
    }
}

__device__ __forceinline__ void task_p3(int wg, int pair, uint32_t sb) {
    const int tid = threadIdx.x & 127, w = tid >> 5, lane = tid & 31;
    const uint32_t buf = sb + (wg ? 3 - wg : 0) * 51200, bars = sb + BARS;
    uint32_t fr[10][4][2];
    float acc[2][16];
    zero(acc[0]); zero(acc[1]);
    {
        const Desc dB = mkdesc(sb + C3, 128, 256, 0);
        const uint32_t a0 = (buf & 0x3FFFF) >> 4;
        auto dq = [&](int Q) {
            return Desc{a0 + (uint32_t)((quad_off(Q) >> 4) | ((Q < 48 ? 2048 : 1024) >> 4) << 16), (uint32_t)((quad_off(Q + 1) - quad_off(Q)) >> 4) | (2u << 30)};
        };
        auto issue = [&](int f) {
            if (!(f & 1)) mbar_wait(bars + 8 * (B_YF + wg * 5 + (f >> 1)));
            wg_fence();
            wgmma_ss_n32_z(acc[f & 1], dq(5 * f), dB);
            wgmma_ss_n32_a(acc[f & 1], dq(5 * f + 1), dB + (uint32_t)(1024 >> 4));
            wgmma_ss_n32_a(acc[f & 1], dq(5 * f + 3), dB + (uint32_t)(2048 >> 4));
            wg_commit();
        };
        mbar_wait(bars + 8 * B_CF3);
        issue(0);
        PROFW(64 + wg * 8 + 1);
#pragma unroll
        for (int f = 0; f < 10; f++) {
            if (f < 9) { issue(f + 1); wg_wait<1>(); } else wg_wait<0>();
            float (&d)[16] = acc[f & 1];
            reg_fence(d);
#pragma unroll
            for (int g = 0; g < 4; g++) { fr[f][g][0] = pack2(d[4 * g], d[4 * g + 1]); fr[f][g][1] = pack2(d[4 * g + 2], d[4 * g + 3]); }
        }
    }
    PROFW(64 + wg * 8 + 2);
    {
        const Desc dB = mkdesc(sb + C3 + 3072, 128, 256, 0);
        const int i = lane & 7, mi = lane >> 3, th = w >> 1, tz = (2 * pair + th) & 3;
        const int oct = (2 * (w & 1) + (mi & 1)) ^ tz;
        const uint32_t soff = buf + th * 3584 + (mi >> 1) * 512 + i * 64 + ((oct ^ (i >> 1)) << 4);
        auto issue = [&](int t) {
            const int g = t < 6 ? 1 + (t >> 1) : 0;
            const uint32_t o = t < 6 ? (t & 1) * 1024 : 8960, st = t < 6 ? 1792 : 1024;
            wg_fence();
            wgmma_rs_n32_z(acc[t & 1], fr[0][g][0], fr[0][g][1], fr[1][g][0], fr[1][g][1], dB + (o >> 4));
#pragma unroll
            for (int s = 1; s < 5; s++) wgmma_rs_n32_a(acc[t & 1], fr[2 * s][g][0], fr[2 * s][g][1], fr[2 * s + 1][g][0], fr[2 * s + 1][g][1], dB + ((o + s * st) >> 4));
            wg_commit();
        };
        bb_break(sb);
        issue(0);
        wg_bar(1 + wg);
#pragma unroll
        for (int t = 0; t < 7; t++) {
            if (t < 6) { issue(t + 1); wg_wait<1>(); } else wg_wait<0>();
            float (&d)[16] = acc[t & 1];
            reg_fence(d);
            if (t < 6) {
                const uint32_t a = soff + (1 + (t >> 1)) * 7168 + (t & 1) * 2048;
                stm4(a, pack2(d[0], d[1]), pack2(d[2], d[3]), pack2(d[4], d[5]), pack2(d[6], d[7]));
                if (t & 1) stm2(a + 1024, pack2(d[8], d[9]), pack2(d[10], d[11]));
                else stm4(a + 1024, pack2(d[8], d[9]), pack2(d[10], d[11]), pack2(d[12], d[13]), pack2(d[14], d[15]));
            } else {
                const int row = th * 14 + 4 * (mi >> 1) + (i >> 1);
                const uint32_t a = buf + row * 128 + (i & 1) * 64 + ((oct ^ (row & 3)) << 4);
                stm4(a, pack2(d[0], d[1]), pack2(d[2], d[3]), pack2(d[4], d[5]), pack2(d[6], d[7]));
                stm4((lane & 20) == 20 ? buf + 4096 + lane * 16 : a + 1024, pack2(d[8], d[9]), pack2(d[10], d[11]), pack2(d[12], d[13]), pack2(d[14], d[15]));
            }
            if ((t & 1) || t == 6) { fence_async_smem(); e_arrive(bars + 8 * (B_RDY + R_P3 + wg * 4 + (t >> 1))); }
        }
    }
}

__device__ __forceinline__ void load_x(int cls, int rk, int u, uint32_t sb, const Maps& mp) {
    const int id = u * NH + rk, pl = id / 3, c0 = 32 * (id - 3 * pl), tp = cls * 4 + (pl >> 4), col = 14 * (pl & 15) - 8;
    const uint32_t bar = sb + BARS + 8 * (B_XF + u * 5), dst = sb + u * 51200;
    const int wrap = col < 0 ? 224 : 0;
    if (tp) {
#pragma unroll
        for (int g = 0; g < 5; g++) e_ld3(dst + g * 8704, &mp.x34, c0, col + 4 * g + (g < 2 ? wrap : 0), 28 * tp - 6, bar + 8 * g);
    } else {
#pragma unroll
        for (int g = 0; g < 5; g++) {
            e_ld3(dst + g * 8704, &mp.x6, c0, col + 4 * g + (g < 2 ? wrap : 0), 218, bar + 8 * g);
            e_ld3(dst + g * 8704 + 1536, &mp.x28, c0, col + 4 * g + (g < 2 ? wrap : 0), 0, bar + 8 * g);
        }
    }
}

__device__ __forceinline__ void load_x_box(int cls, int rk, int u, int g, uint32_t sb, const Maps& mp) {
    const int id = u * NH + rk, pl = id / 3, c0 = 32 * (id - 3 * pl), tp = cls * 4 + (pl >> 4), col = 14 * (pl & 15) - 8 + 4 * g;
    e_ld3(sb + u * 51200 + g * 8704, &mp.x34, c0, col < 0 ? col + 224 : col, 28 * tp - 6, sb + BARS + 8 * (B_XF + u * 5 + g));
}

__device__ __forceinline__ void load_first(uint32_t sb, const Maps& mp, const Ptrs& pt) {
    const uint32_t bars = sb + BARS;
    const int k = blockIdx.x;
    PROF(122);
    if (k < 129) {
        const int cb0 = 14 * k / 25, cb1 = min((14 * k + 13) / 25, 71);
#pragma unroll 1
        for (int cb = cb0; cb <= cb1; cb++) {
            const int b = cb / 24, i0 = 16 * ((cb >> 2) - 6 * b) + 2 * (cb & 3);
            const uint32_t bar = bars + 8 * (B_WF + 2 * (cb - cb0));
            e_expect(bar, 14336);
            e_ld4(sb + WP + (cb - cb0) * 14336, &mp.w, 32 * b, i0, bar);
            e_ld4(sb + WP + (cb - cb0) * 14336 + 7168, &mp.w, 32 * b, i0 + 8, bar);
        }
    }
    e_expect(bars + 8 * B_CF1, 17920); e_g2s(sb + C1, pt.tab1, 17920, bars + 8 * B_CF1);
    if ((threadIdx.x & 31) < 15) asm volatile("mbarrier.arrive.expect_tx.shared::cta.b64 _, [%0], 8704;" :: "r"(bars + 8 * (B_XF + (threadIdx.x & 31))) : "memory");
    __syncwarp();
}

__device__ __forceinline__ uint32_t get_rel(uint32_t sb) {
    mbar_wait(sb + BARS + 8 * B_REL);
    uint32_t v; asm volatile("ld.shared.u32 %0, [%1];" : "=r"(v) : "r"(sb + REL) : "memory");
    return uni(v);
}

__device__ __forceinline__ void load_warp(int cls, int rk, uint32_t sb, const Maps& mp, const Ptrs& pt) {
    const uint32_t bars = sb + BARS;
    mbar_wait(bars + 8 * (B_SIG + SIG_P1));
    PROF(1);
    const uint32_t rel = get_rel(sb);
    const char* cnt = cls_cnt(pt.scr, cls);
    const int mE = extra_mask(rk);
    const int lpA = phi_line(3 * rk, rel), lpB = phi_line(3 * rk + 1, rel), lpC = phi_line(3 * rk + 2, rel), lpE = phi_line(extra_phi(rk), rel);
    e_arrive(bars + 8 * (B_TOK - 1));
    if ((threadIdx.x & 31) < 14) asm volatile("mbarrier.arrive.expect_tx.shared::cta.b64 _, [%0], 12288;" :: "r"(bars + 8 * (B_RF + (threadIdx.x & 31))) : "memory");
    __syncwarp();
    int n = 0;
#pragma unroll 1
    for (int pg = 0; pg < 4; pg++) {
        const int l0 = slot_line(0, pg, cls), l1 = slot_line(1, pg, cls), l2 = slot_line(2, pg, cls);
        auto unit = [&](int lp) {
            const uint32_t bar = bars + 8 * (B_RF + n), dst = sb + xslot(n);
            mbar_wait(bars + 8 * (n >= 8 ? B_RE + n - 8 : n >= 4 ? B_SIG + SIG_P1 + (rk < 60 ? 2 : 1) : B_WE + ((0x4310 >> (4 * n)) & 15)));
            e_g2s(dst, pt.scr + (size_t)(lp ^ l0) * 128, 4096, bar);
            e_g2s(dst + 4096, pt.scr + (size_t)(lp ^ l1) * 128, 4096, bar);
            e_g2s(dst + 8192, pt.scr + (size_t)(lp ^ l2) * 128, 4096, bar);
            n++;
        };
        cnt_wait(cnt + (CNT_P1 + pg) * 128, 48);
        PROF(88 + pg);
        unit(lpA); unit(lpB);
        if (pg == 0) e_arrive(bars + 8 * B_X1);
        unit(lpC);
        if (mE >> pg & 1) unit(lpE);
        if (pg == 1) { mbar_wait(bars + 8 * B_P1D); e_expect(bars + 8 * B_CF3, 17152); e_g2s(sb + C3, pt.tab3, 17152, bars + 8 * B_CF3); }
    }
}

__device__ __forceinline__ int near_page(char* p, int rounds) {
#pragma unroll
    for (int e = 0; e < 4; e++) asm volatile("st.relaxed.gpu.global.v4.u32 [%0], {%1, %1, %1, %1};" :: "l"(p + (e >> 1) * 4096 + (e & 1) * 16), "r"(0) : "memory");
    int score = 0;
#pragma unroll 1
    for (int r = 0; r < rounds; r++) {
        uint32_t v0, v1, t0, t1;
        asm volatile("atom.relaxed.gpu.global.exch.b32 %0, [%1], 1;" : "=r"(v0) : "l"(p + (r & 1) * 4096) : "memory");
        asm volatile("atom.relaxed.gpu.global.exch.b32 %0, [%1], 1;" : "=r"(v1) : "l"(p + (~r & 1) * 4096) : "memory");
        asm volatile("{\n.reg .pred p;\nsetp.ne.u32 p, %1, 0xffffffff;\nmov.u32 %0, 0;\n@p mov.u32 %0, %%clock;\n}" : "=r"(t0) : "r"(v0) : "memory");
        asm volatile("{\n.reg .pred p;\nsetp.ne.u32 p, %1, 0xffffffff;\nmov.u32 %0, 0;\n@p mov.u32 %0, %%clock;\n}" : "=r"(t1) : "r"(v1) : "memory");
        const int gap = min((int)(t1 - t0), 160) - 80;
        score += (r & 1) ? gap : -gap;

    }
    return score > 0;
}

__device__ __forceinline__ uint32_t find_role(uint32_t sb, char* scr) {
    const int k = blockIdx.x;
    int c = near_page(scr + (slot_line(3, 3, 0) + phi_line(1 + (k >> 5), 0) + (k & 31)) * 128, PROBES);
    PROF(3);
    int r;
    asm volatile("atom.relaxed.gpu.global.add.u32 %0, [%1], 1;" : "=r"(r) : "l"(cls_cnt(scr, c) + CNT_RANK * 128) : "memory");
    if (r >= NH) { c ^= 1; r = NSM - 1 - r; }
    asm volatile("st.shared.u32 [%0], %1;" :: "r"(sb + REL + 4), "r"(c << 8 | r) : "memory");
    PROF(5);
    return c << 8 | r;
}
__device__ __forceinline__ void get_role(uint32_t sb, int& cls, int& rk) {
    mbar_wait(sb + BARS + 8 * B_ROLE);
    uint32_t v; asm volatile("ld.shared.u32 %0, [%1];" : "=r"(v) : "r"(sb + REL + 4) : "memory");
    v = uni(v); cls = v >> 8; rk = v & 255;
}

__device__ __forceinline__ void load3_warp(int cls, int rk, uint32_t sb, const Maps& mp, const Ptrs& pt) {
    const uint32_t bars = sb + BARS;
    uint32_t rel = 0;
    mbar_wait(bars + 8 * B_XF);
    PROF(107);
    rel = cnt_wait(pt.cnt + CNT_REL * 32, 12u << 16);
    asm volatile("st.shared.u32 [%0], %1;" :: "r"(sb + REL), "r"(rel) : "memory");
    __syncwarp();
    e_arrive(bars + 8 * B_REL);
    PROF(7);
    mbar_wait(bars + 8 * (B_SIG + SIG_W));
    cnt_wait(cls_cnt(pt.scr, cls) + CNT_W * 128, NSM);
    PROF(2);
    {
        const int np = rk >= 58 ? 12 : 9;
#pragma unroll 1
        for (int o = 0; o < np; o++) {
            const int pc = (0xba9876524310ull >> (4 * o)) & 15;
            if (o == 4) mbar_wait(bars + 8 * (B_SIG + SIG_P1));
            if (o >= 8) mbar_wait(bars + 8 * (B_WE + ((0x5762 >> (4 * (o - 8))) & 15)));
            if (o >= WWIN) mbar_wait(bars + 8 * (B_WL + ((0xba9876524310ull >> (4 * (o - WWIN))) & 15)));
            if (o == WHOLD) mbar_wait(bars + 8 * B_X1);
            e_expect(bars + 8 * (B_WL + pc), 12288);
            e_g2s(sb + wslot(pc), pt.wf + (pc < 9 ? 9 * rk + pc : 3 * extra_phi(rk) + pc - 9) * 12288, 12288, bars + 8 * (B_WL + pc));
        }
        if (np == 12) { mbar_wait(bars + 8 * (B_WE + 9)); mbar_wait(bars + 8 * (B_WE + 10)); mbar_wait(bars + 8 * (B_WE + 11)); }
    }
    mbar_wait(bars + 8 * (B_SIG + SIG_P2 + Y0AT));
    const int nu = rk < 60 ? 3 : 2;
#pragma unroll 1
    for (int u = 0; u < nu; u++) {
        const int id = u * NH + rk, pl = id / 3, chunk = id - 3 * pl;
        const int l0 = slot_line(chunk, pl >> 4, cls) + (pl & 15) * 2;
        const uint32_t buf = sb + (u ? 3 - u : 0) * 51200, bar = bars + 8 * (B_YF + u * 5);
#pragma unroll
        for (int j = 0; j < 5; j++) e_expect(bar + 8 * j, j == 4 ? 10240 : (j & 1) ? 8192 : 12288);
        if (u) mbar_wait(bars + 8 * (B_SIG + SIG_P2 + 3));
        cnt_wait(cls_cnt(pt.scr, cls) + (CNT_P2 + (pl >> 4)) * 128, NH);
        PROF(64 + u * 8);
        if (u == nu - 1) e_arrive(bars + 8 * B_FIN);
        const uint32_t r2 = uni(rel) << 5;
#pragma unroll
        for (int G = 0; G < 13; G++)
            e_ld5(buf + G * 4096, G < 12 ? &mp.f16 : &mp.f8, (l0 ^ ((r2 >> G) & 32)) + (G << 14), bar + 8 * ((2 * G) / 5));
    }
}

__device__ __forceinline__ void store_warp(uint32_t sb, const Maps& mp, const Ptrs& pt) {
    const uint32_t bars = sb + BARS;
    const int k = blockIdx.x;
    uint32_t pa = 0, pb = 0, qa = 0, qb = 0;
    auto arr2 = [&](uint32_t& a, uint32_t& b) { if (a) e_arrive(a); if (b) e_arrive(b); a = b = 0; };
    auto pre = [&](int idx) {
        const uint32_t bar = bars + 8 * idx;
        if (!mbar_test(bar)) { bulk_wait_read<0>(); arr2(qa, qb); arr2(pa, pb); mbar_wait(bar); }
    };
    auto post = [&](uint32_t fr) {
        bulk_commit(); bulk_wait_read<SWIN - 1>();
        if (SWIN == 3) { arr2(qa, qb); qa = pa; qb = pb; pb = 0; } else arr2(pa, pb);
        pa = fr;
    };
    auto after = [&](uint32_t a, uint32_t b) { if (a) pa = a; pb = b; };
    auto pace = [&](uint32_t) {};
    int cls, rk; get_role(sb, cls, rk);
    {
        int cb = 14 * k / 25, oc = 14 * k - 25 * cb;
        int g1 = 0;
#pragma unroll 1
        for (int i = 0; i < 14 && cb < 72; i++) {
            pre(B_WRD + i);
            if (PACE) pace(4 * PACE);
            e_st3(&mp.wst, sb + wst_off(i), 0, 8 * oc, cb);
            post(0);
            if (T1MASK >> i & 1) load_x_box(cls, rk, 1, g1++, sb, mp);
            if (++oc == 25) { oc = 0; cb++; }
        }
#pragma unroll 1
        for (; g1 < 5; g1++) load_x_box(cls, rk, 1, g1, sb, mp);
        after(bars + 8 * B_WFREE, bars + 8 * (B_SIG + SIG_W));
    }
    pre(B_REL);
    const uint32_t rel = get_rel(sb);
    const int nu = rk < 60 ? 3 : 2;
#pragma unroll 1
    for (int u = 0; u < nu; u++) {
        const int id = u * NH + rk, pl = id / 3, chunk = id - 3 * pl;
        const int l0 = slot_line(chunk, pl >> 4, cls) + (pl & 15) * 2;
        int j = B_RDY + u * 5;
        int g2 = 0;
        const int m2 = (u == 0 && nu == 3) ? T2MASK : 0;
#pragma unroll 1
        for (int G = 0; G < 13; G++) {
            if (0x4a5 >> G & 1) pre(j++);
            if (PACE) pace(G < 12 ? 4 * PACE : 2 * PACE);
            e_st5(G < 12 ? &mp.f16 : &mp.f8, sb + u * 51200 + G * 4096, (l0 ^ ((rel >> G) & 1) << 5) + (G << 14));
            post(0);
            if (m2 >> G & 1) load_x_box(cls, rk, 2, g2++, sb, mp);
        }
        after(0, bars + 8 * (B_SIG + SIG_P1 + u));
    }
    const int mE = extra_mask(rk);
    int n = 0;
#pragma unroll 1
    for (int pg = 0; pg < 4; pg++) {
        const int nj = 3 + (mE >> pg & 1);
        const int l0 = slot_line(0, pg, cls), l1 = slot_line(1, pg, cls), l2 = slot_line(2, pg, cls);
#pragma unroll 1
        for (int j = 0; j < nj; j++) {
            const int lp = phi_line(j == 3 ? extra_phi(rk) : 3 * rk + j, rel);
#pragma unroll
            for (int b = 0; b < 3; b++) {
                pre(B_RDY + R_P2 + n * 3 + b);
                if (PACE) pace(4 * PACE);
                e_s2g(pt.scr + (size_t)(lp ^ (b == 0 ? l0 : b == 1 ? l1 : l2)) * 128, sb + S1 + (n & 3) * 12288 + b * 4096, 4096);
                post(bars + 8 * (B_SFREE + n * 3 + b));
            }
            n++;
        }
        after(0, bars + 8 * (B_SIG + SIG_P2 + pg));
    }
#pragma unroll 1
    for (int u = 0; u < nu; u++) {
        const int id = u * NH + rk, pl = id / 3, chunk = id - 3 * pl, tp = cls * 4 + (pl >> 4), tx = pl & 15;
        const uint32_t buf = sb + (u ? 3 - u : 0) * 51200;
#pragma unroll
        for (int gg = 1; gg < 5; gg++) {
            pre(B_RDY + R_P3 + u * 4 + gg - 1);
            if (u < 2) pace(gg < 4 ? 7 * YPACE : 7 * YPACE / 2);
            if (gg < 4) e_st3(&mp.y4, buf + gg * 7168, 32 * chunk, 14 * tx - 4 + 4 * gg, 28 * tp);
            else e_st3(&mp.y2, buf, 32 * chunk, tx == 0 ? 222 : 14 * tx - 2, 28 * tp);
            post(0);
        }
    }
    bulk_wait_read<0>();
    PROF(113);
    prof_dump();
}

__device__ __forceinline__ void signal_warp(int cls, int rk, uint32_t sb, const Ptrs& pt) {
    const uint32_t bars = sb + BARS;
    char* cnt = cls_cnt(pt.scr, cls);
    if (threadIdx.x & 31) return;
#pragma unroll 1
    for (int c = 0; c < 8; c++) {
        if (c == SIG_P1 + 2 && rk >= 60) continue;
        char* ctr = cnt + (c == SIG_W ? CNT_W : c < SIG_P2 ? CNT_P1 + ((c - SIG_P1) * NH + rk) / 48 : CNT_P2 + c - SIG_P2) * 128;
        mbar_wait(bars + 8 * (B_SIG + c));
        PROF(32 + c);
        fence_async();
        asm volatile("red.relaxed.gpu.global.add.u32 [%0], 1;" :: "l"(ctr) : "memory");
        if (c == SIG_W) asm volatile("red.relaxed.gpu.global.add.u32 [%0], 1;" :: "l"((uintptr_t)ctr ^ 4096) : "memory");
        PROF(96 + c);
    }
    mbar_wait(bars + 8 * B_FIN);
    unsigned old;
    asm volatile("atom.add.relaxed.gpu.global.u32 %0, [%1], 1;" : "=r"(old) : "l"(pt.cnt + CNT_DONE * 32) : "memory");
    if (old == NSM - 1) {
#pragma unroll
        for (int c = 0; c < NCNT; c++) pt.cnt[c * 32] = 0;
#pragma unroll 1
        for (int c = 0; c < NCLS; c++) { *reinterpret_cast<unsigned*>(cnt + c * 128) = 0; *reinterpret_cast<unsigned*>(((uintptr_t)cnt ^ 4096) + c * 128) = 0; }
    }
}

__global__ void __launch_bounds__(512, 1) fftconv_kernel(const Ptrs pt, const __grid_constant__ Maps mp) {
    extern __shared__ __align__(1024) uint8_t smem[];
    const uint32_t sb = smem_u32(smem);
    const int tid = threadIdx.x, warp = uni(tid >> 5), wg = warp >> 2;
    int cls, rk;
    auto bar_init = [&](int i) {
        uint32_t c = 1;
        if (i == B_P1D || (i >= B_RE && i < B_RE + 14)) c = 12;
        else if ((i >= B_WCH && i < B_WL) || i >= B_TOK) c = 4;
        asm volatile("st.shared.v2.u32 [%0], {%1, %2};" :: "r"(sb + BARS + 8 * i), "r"((0x100000u - c) << 1), "r"((0x100000u - c) << 11) : "memory");
        fence_async_smem();
    };
    if (wg == 3) {
        asm volatile("setmaxnreg.dec.sync.aligned.u32 32;");
        if (warp == 12) {
            bar_init(tid & 31);
            __syncwarp();
            asm volatile("bar.arrive 4, 416;" ::: "memory");
            load_first(sb, mp, pt);
            PROF(106);
            asm volatile("bar.sync 5, 416;" ::: "memory");
            get_role(sb, cls, rk);
            load_warp(cls, rk, sb, mp, pt);
        } else if (warp == 13) {
            if ((tid & 31) < 8) asm volatile("prefetch.tensormap [%0];" :: "l"(reinterpret_cast<const CUtensorMap*>(&mp) + 1 + (tid & 31)) : "memory");
            __syncwarp();
            asm volatile("bar.sync 6, 416;" ::: "memory");
            store_warp(sb, mp, pt);
        } else if (warp == 14) {
            const int G = blockIdx.x - 119;
            int sel = 0;
            if (G >= 1 && (tid & 31) == 0) sel = near_page(pt.scr + ((size_t)G << 21) + slot_line(3, 3, 0) * 128, 2);
            __syncwarp();
            asm volatile("bar.sync 7, 416;" ::: "memory");
            get_role(sb, cls, rk);
            if (G >= 1 && (tid & 31) == 0) asm volatile("red.relaxed.gpu.global.add.u32 [%0], %1;" :: "l"(pt.cnt + CNT_REL * 32), "r"(0x10000u | (uint32_t)(sel ^ cls) << G) : "memory");
            __syncwarp();
            load3_warp(cls, rk, sb, mp, pt);
        } else {
            uint32_t role = 0;
            if ((tid & 31) == 0) role = find_role(sb, pt.scr);
            role = uni(role); cls = role >> 8; rk = role & 255;
            asm volatile("bar.sync 8, 416;" ::: "memory");
            load_x(cls, rk, 0, sb, mp);
            PROF(123);
            e_arrive(sb + BARS + 8 * B_ROLE);
            signal_warp(cls, rk, sb, pt);
        }
    } else {
        if (tid >= 32 && tid < NBAR) bar_init(tid);
        {
            const int r = tid % 40;
            asm volatile("st.shared.u32 [%0], %1;" :: "r"(sb + TBL + 4 * tid), "r"(cos_bits(r) | (cos_bits(r < 30 ? r + 10 : r - 30) << 16)) : "memory");
        }
        __syncwarp();
        asm volatile("bar.sync 4, 416;" ::: "memory");
        asm volatile("bar.arrive 5, 416;" ::: "memory");
        asm volatile("bar.arrive 6, 416;" ::: "memory");
        asm volatile("bar.arrive 7, 416;" ::: "memory");
        asm volatile("bar.arrive 8, 416;" ::: "memory");
        PROF(121);
        task_w(wg, blockIdx.x, sb);
        asm volatile("setmaxnreg.inc.sync.aligned.u32 160;");
        get_role(sb, cls, rk);
        const int id = wg * NH + rk;
        PROFW(8 + wg * 8);
        if (id < 192) task_p1(wg, id / 3, sb);
        e_arrive(sb + BARS + 8 * B_P1D);
        PROFW(8 + wg * 8 + 3);
        task_p2(wg, rk, sb);
        if (id < 192) task_p3(wg, id / 3, sb);
        PROFW(64 + wg * 8 + 3);
        prof_dump();
    }
}

typedef CUresult (*EncodeFn)(CUtensorMap*, CUtensorMapDataType, cuuint32_t, void*, const cuuint64_t*, const cuuint64_t*, const cuuint32_t*, const cuuint32_t*,
                             CUtensorMapInterleave, CUtensorMapSwizzle, CUtensorMapL2promotion, CUtensorMapFloatOOBfill);

static void encode3(EncodeFn fn, CUtensorMap* m, void* ptr, uint64_t d0, uint64_t d1, uint64_t d2, uint64_t s1, uint64_t s2,
                    uint32_t b0, uint32_t b1, uint32_t b2, CUtensorMapSwizzle sw) {
    cuuint64_t dims[3] = {d0, d1, d2}, strides[2] = {s1, s2};
    cuuint32_t box[3] = {b0, b1, b2}, es[3] = {1, 1, 1};
    fn(m, CU_TENSOR_MAP_DATA_TYPE_BFLOAT16, 3, ptr, dims, strides, box, es, CU_TENSOR_MAP_INTERLEAVE_NONE, sw,
       CU_TENSOR_MAP_L2_PROMOTION_NONE, CU_TENSOR_MAP_FLOAT_OOB_FILL_NONE);
}

extern "C" void kernel_launch(void* const* d_in, const int* in_sizes, int n_in, void* d_out, int out_size) {
    (void)in_sizes; (void)n_in; (void)out_size;
    void* fnp = nullptr; cudaDriverEntryPointQueryResult qr;
    cudaGetDriverEntryPoint("cuTensorMapEncodeTiled", &fnp, cudaEnableDefault, &qr);
    EncodeFn fn = (EncodeFn)fnp;
    void* xf = nullptr; cudaGetSymbolAddress(&xf, g_scr);
    xf = (void*)(((uintptr_t)xf + (1u << 21) - 1) & ~(uintptr_t)((1u << 21) - 1));
    void* wf = nullptr; cudaGetSymbolAddress(&wf, g_wf);
    Maps mp;
    Ptrs pt;
    pt.scr = (char*)xf; pt.wf = (const char*)wf;
    void* p = nullptr;
    cudaGetSymbolAddress(&p, TAB_P1); pt.tab1 = p;
    cudaGetSymbolAddress(&p, TAB_P3); pt.tab3 = p;
    cudaGetSymbolAddress(&p, g_cnt); pt.cnt = (unsigned*)p;
    {
        cuuint32_t b16[5] = {64, 4, 2, 2, 2}, b8[5] = {64, 4, 2, 1, 2}, es[5] = {1, 1, 1, 1, 1};
        cuuint64_t d[5] = {64, 4, 2, 2, 13 << 14}, st[4] = {16384, 262144, 1048576, 128};
        fn(&mp.f16, CU_TENSOR_MAP_DATA_TYPE_BFLOAT16, 5, xf, d, st, b16, es, CU_TENSOR_MAP_INTERLEAVE_NONE, CU_TENSOR_MAP_SWIZZLE_NONE, CU_TENSOR_MAP_L2_PROMOTION_NONE, CU_TENSOR_MAP_FLOAT_OOB_FILL_NONE);
        fn(&mp.f8, CU_TENSOR_MAP_DATA_TYPE_BFLOAT16, 5, xf, d, st, b8, es, CU_TENSOR_MAP_INTERLEAVE_NONE, CU_TENSOR_MAP_SWIZZLE_NONE, CU_TENSOR_MAP_L2_PROMOTION_NONE, CU_TENSOR_MAP_FLOAT_OOB_FILL_NONE);
    }
    encode3(fn, &mp.x6, d_in[0], 96, 224, 224, 192, 224 * 192, 32, 4, 6, CU_TENSOR_MAP_SWIZZLE_64B);
    encode3(fn, &mp.x34, d_in[0], 96, 224, 224, 192, 224 * 192, 32, 4, 34, CU_TENSOR_MAP_SWIZZLE_64B);
    encode3(fn, &mp.x28, d_in[0], 96, 224, 224, 192, 224 * 192, 32, 4, 28, CU_TENSOR_MAP_SWIZZLE_64B);
    {
        cuuint32_t box[4] = {32, 8, 7, 2}, es[4] = {1, 1, 1, 1};
        cuuint64_t d[4] = {96, 7, 7, 96}, st[3] = {18432, 7 * 18432, 192};
        fn(&mp.w, CU_TENSOR_MAP_DATA_TYPE_BFLOAT16, 4, d_in[1], d, st, box, es, CU_TENSOR_MAP_INTERLEAVE_NONE, CU_TENSOR_MAP_SWIZZLE_64B, CU_TENSOR_MAP_L2_PROMOTION_NONE, CU_TENSOR_MAP_FLOAT_OOB_FILL_NONE);
    }
    encode3(fn, &mp.wst, wf, 256, 200, 72, 36864, 512, 256, 8, 1, CU_TENSOR_MAP_SWIZZLE_NONE);
    encode3(fn, &mp.y4, d_out, 96, 224, 224, 192, 224 * 192, 32, 4, 28, CU_TENSOR_MAP_SWIZZLE_64B);
    encode3(fn, &mp.y2, d_out, 96, 224, 224, 192, 224 * 192, 32, 2, 28, CU_TENSOR_MAP_SWIZZLE_64B);
    constexpr int SMEM_LAUNCH = SMEM_BYTES;
    cudaFuncSetAttribute(fftconv_kernel, cudaFuncAttributeMaxDynamicSharedMemorySize, SMEM_LAUNCH);
    fftconv_kernel<<<NSM, 512, SMEM_LAUNCH>>>(pt, mp);
}
```

```cpp
#include <cuda_runtime.h>
#include <cuda_bf16.h>
#include <cuda.h>
#include <stdint.h>

__device__ __align__(128) const uint32_t TAB_P1[4480] = {
0x3e75,0,0x3e72,0,0x8000,0,0xbd19,0,0x3e750000,0,0x3e720000,0,0x80000000,0,0xbd190000,0,
0,0x3e75,0,0x3e72,0,0x8000,0,0xbd19,0,0x3e750000,0,0x3e720000,0,0x80000000,0,0xbd190000,
0x3e69,0,0x3e5a,0,0xbd97,0,0xbdde,0,0x3e690000,0,0x3e5a0000,0,0xbd970000,0,0xbdde0000,0,
0,0x3e69,0,0x3e5a,0,0xbd97,0,0xbdde,0,0x3e690000,0,0x3e5a0000,0,0xbd970000,0,0xbdde0000,
0x3e75,0,0x3e5a,0,0x8000,0,0xbdde,0,0x3e750000,0,0x3e5a0000,0,0x80000000,0,0xbdde0000,0,
0,0x3e75,0,0x3e5a,0,0x8000,0,0xbdde,0,0x3e750000,0,0x3e5a0000,0,0x80000000,0,0xbdde0000,
0x3e10,0,0x3d19,0,0xbe46,0,0xbe72,0,0x3e100000,0,0x3d190000,0,0xbe460000,0,0xbe720000,0,
0,0x3e10,0,0x3d19,0,0xbe46,0,0xbe72,0,0x3e100000,0,0x3d190000,0,0xbe460000,0,0xbe720000,
0x3e75,0,0x3e2d,0,0x8000,0,0xbe2d,0,0x3e750000,0,0x3e2d0000,0,0x80000000,0,0xbe2d0000,0,
0,0x3e75,0,0x3e2d,0,0x8000,0,0xbe2d,0,0x3e750000,0,0x3e2d0000,0,0x80000000,0,0xbe2d0000,
0,0,0xbe2d,0,0xbe75,0,0xbe2d,0,0,0,0xbe2d0000,0,0xbe750000,0,0xbe2d0000,0,
0,0,0,0xbe2d,0,0xbe75,0,0xbe2d,0,0,0,0xbe2d0000,0,0xbe750000,0,0xbe2d0000,
0x3e75,0,0x3dde,0,0x8000,0,0xbe5a,0,0x3e750000,0,0x3dde0000,0,0x80000000,0,0xbe5a0000,0,
0,0x3e75,0,0x3dde,0,0x8000,0,0xbe5a,0,0x3e750000,0,0x3dde0000,0,0x80000000,0,0xbe5a0000,
0xbe10,0,0xbe72,0,0xbe46,0,0x3d19,0,0xbe100000,0,0xbe720000,0,0xbe460000,0,0x3d190000,0,
0,0xbe10,0,0xbe72,0,0xbe46,0,0x3d19,0,0xbe100000,0,0xbe720000,0,0xbe460000,0,0x3d190000,
0x3e75,0,0x3d19,0,0x8000,0,0xbe72,0,0x3e750000,0,0x3d190000,0,0x80000000,0,0xbe720000,0,
0,0x3e75,0,0x3d19,0,0x8000,0,0xbe72,0,0x3e750000,0,0x3d190000,0,0x80000000,0,0xbe720000,
0xbe69,0,0xbdde,0,0xbd97,0,0x3e5a,0,0xbe690000,0,0xbdde0000,0,0xbd970000,0,0x3e5a0000,0,
0,0xbe69,0,0xbdde,0,0xbd97,0,0x3e5a,0,0xbe690000,0,0xbdde0000,0,0xbd970000,0,0x3e5a0000,
0x3e75,0,0xbd19,0,0x8000,0,0xbe72,0,0x3e750000,0,0xbd190000,0,0x80000000,0,0xbe720000,0,
0,0x3e75,0,0xbd19,0,0x8000,0,0xbe72,0,0x3e750000,0,0xbd190000,0,0x80000000,0,0xbe720000,
0xbe69,0,0x3dde,0,0x3d97,0,0x3e5a,0,0xbe690000,0,0x3dde0000,0,0x3d970000,0,0x3e5a0000,0,
0,0xbe69,0,0x3dde,0,0x3d97,0,0x3e5a,0,0xbe690000,0,0x3dde0000,0,0x3d970000,0,0x3e5a0000,
0x3e75,0,0xbdde,0,0x8000,0,0xbe5a,0,0x3e750000,0,0xbdde0000,0,0x80000000,0,0xbe5a0000,0,
0,0x3e75,0,0xbdde,0,0x8000,0,0xbe5a,0,0x3e750000,0,0xbdde0000,0,0x80000000,0,0xbe5a0000,
0xbe10,0,0x3e72,0,0x3e46,0,0x3d19,0,0xbe100000,0,0x3e720000,0,0x3e460000,0,0x3d190000,0,
0,0xbe10,0,0x3e72,0,0x3e46,0,0x3d19,0,0xbe100000,0,0x3e720000,0,0x3e460000,0,0x3d190000,
0x3e75,0,0xbe2d,0,0x8000,0,0xbe2d,0,0x3e750000,0,0xbe2d0000,0,0x80000000,0,0xbe2d0000,0,
0,0x3e75,0,0xbe2d,0,0x8000,0,0xbe2d,0,0x3e750000,0,0xbe2d0000,0,0x80000000,0,0xbe2d0000,
0,0,0x3e2d,0,0x3e75,0,0xbe2d,0,0,0,0x3e2d0000,0,0x3e750000,0,0xbe2d0000,0,
0,0,0,0x3e2d,0,0x3e75,0,0xbe2d,0,0,0,0x3e2d0000,0,0x3e750000,0,0xbe2d0000,
0x3e75,0,0xbe5a,0,0x8000,0,0xbdde,0,0x3e750000,0,0xbe5a0000,0,0x80000000,0,0xbdde0000,0,
0,0x3e75,0,0xbe5a,0,0x8000,0,0xbdde,0,0x3e750000,0,0xbe5a0000,0,0x80000000,0,0xbdde0000,
0x3e10,0,0xbd19,0,0x3e46,0,0xbe72,0,0x3e100000,0,0xbd190000,0,0x3e460000,0,0xbe720000,0,
0,0x3e10,0,0xbd19,0,0x3e46,0,0xbe72,0,0x3e100000,0,0xbd190000,0,0x3e460000,0,0xbe720000,
0x3e75,0,0xbe72,0,0x8000,0,0xbd19,0,0x3e750000,0,0xbe720000,0,0x80000000,0,0xbd190000,0,
0,0x3e75,0,0xbe72,0,0x8000,0,0xbd19,0,0x3e750000,0,0xbe720000,0,0x80000000,0,0xbd190000,
0x3e69,0,0xbe5a,0,0x3d97,0,0xbdde,0,0x3e690000,0,0xbe5a0000,0,0x3d970000,0,0xbdde0000,0,
0,0x3e69,0,0xbe5a,0,0x3d97,0,0xbdde,0,0x3e690000,0,0xbe5a0000,0,0x3d970000,0,0xbdde0000,
0x3e46,0,0x3e2d,0,0xbe10,0,0xbe2d,0,0x3e460000,0,0x3e2d0000,0,0xbe100000,0,0xbe2d0000,0,
0,0x3e46,0,0x3e2d,0,0xbe10,0,0xbe2d,0,0x3e460000,0,0x3e2d0000,0,0xbe100000,0,0xbe2d0000,
0x3e10,0,0x3dde,0,0xbe46,0,0xbe5a,0,0x3e100000,0,0x3dde0000,0,0xbe460000,0,0xbe5a0000,0,
0,0x3e10,0,0x3dde,0,0xbe46,0,0xbe5a,0,0x3e100000,0,0x3dde0000,0,0xbe460000,0,0xbe5a0000,
0xbd97,0,0xbe2d,0,0xbe69,0,0xbe2d,0,0xbd970000,0,0xbe2d0000,0,0xbe690000,0,0xbe2d0000,0,
0,0xbd97,0,0xbe2d,0,0xbe69,0,0xbe2d,0,0xbd970000,0,0xbe2d0000,0,0xbe690000,0,0xbe2d0000,
0xbe69,0,0xbe72,0,0xbd97,0,0x3d19,0,0xbe690000,0,0xbe720000,0,0xbd970000,0,0x3d190000,0,
0,0xbe69,0,0xbe72,0,0xbd97,0,0x3d19,0,0xbe690000,0,0xbe720000,0,0xbd970000,0,0x3d190000,
0xbe75,0,0xbe2d,0,0x8000,0,0x3e2d,0,0xbe750000,0,0xbe2d0000,0,0x80000000,0,0x3e2d0000,0,
0,0xbe75,0,0xbe2d,0,0x8000,0,0x3e2d,0,0xbe750000,0,0xbe2d0000,0,0x80000000,0,0x3e2d0000,
0,0,0x3e2d,0,0x3e75,0,0x3e2d,0,0,0,0x3e2d0000,0,0x3e750000,0,0x3e2d0000,0,
0,0,0,0x3e2d,0,0x3e75,0,0x3e2d,0,0,0,0x3e2d0000,0,0x3e750000,0,0x3e2d0000,
0xbd97,0,0x3e2d,0,0x3e69,0,0x3e2d,0,0xbd970000,0,0x3e2d0000,0,0x3e690000,0,0x3e2d0000,0,
0,0xbd97,0,0x3e2d,0,0x3e69,0,0x3e2d,0,0xbd970000,0,0x3e2d0000,0,0x3e690000,0,0x3e2d0000,
0x3e69,0,0x3d19,0,0xbd97,0,0xbe72,0,0x3e690000,0,0x3d190000,0,0xbd970000,0,0xbe720000,0,
0,0x3e69,0,0x3d19,0,0xbd97,0,0xbe72,0,0x3e690000,0,0x3d190000,0,0xbd970000,0,0xbe720000,
0x3e46,0,0x3e2d,0,0x3e10,0,0xbe2d,0,0x3e460000,0,0x3e2d0000,0,0x3e100000,0,0xbe2d0000,0,
0,0x3e46,0,0x3e2d,0,0x3e10,0,0xbe2d,0,0x3e460000,0,0x3e2d0000,0,0x3e100000,0,0xbe2d0000,
0xbe10,0,0xbe5a,0,0xbe46,0,0x3dde,0,0xbe100000,0,0xbe5a0000,0,0xbe460000,0,0x3dde0000,0,
0,0xbe10,0,0xbe5a,0,0xbe46,0,0x3dde,0,0xbe100000,0,0xbe5a0000,0,0xbe460000,0,0x3dde0000,
0x3e46,0,0xbe2d,0,0xbe10,0,0xbe2d,0,0x3e460000,0,0xbe2d0000,0,0xbe100000,0,0xbe2d0000,0,
0,0x3e46,0,0xbe2d,0,0xbe10,0,0xbe2d,0,0x3e460000,0,0xbe2d0000,0,0xbe100000,0,0xbe2d0000,
0xbe10,0,0x3e5a,0,0x3e46,0,0x3dde,0,0xbe100000,0,0x3e5a0000,0,0x3e460000,0,0x3dde0000,0,
0,0xbe10,0,0x3e5a,0,0x3e46,0,0x3dde,0,0xbe100000,0,0x3e5a0000,0,0x3e460000,0,0x3dde0000,
0xbd97,0,0xbe2d,0,0xbe69,0,0x3e2d,0,0xbd970000,0,0xbe2d0000,0,0xbe690000,0,0x3e2d0000,0,
0,0xbd97,0,0xbe2d,0,0xbe69,0,0x3e2d,0,0xbd970000,0,0xbe2d0000,0,0xbe690000,0,0x3e2d0000,
0x3e69,0,0xbd19,0,0x3d97,0,0xbe72,0,0x3e690000,0,0xbd190000,0,0x3d970000,0,0xbe720000,0,
0,0x3e69,0,0xbd19,0,0x3d97,0,0xbe72,0,0x3e690000,0,0xbd190000,0,0x3d970000,0,0xbe720000,
0xbe75,0,0x3e2d,0,0x8000,0,0x3e2d,0,0xbe750000,0,0x3e2d0000,0,0x80000000,0,0x3e2d0000,0,
0,0xbe75,0,0x3e2d,0,0x8000,0,0x3e2d,0,0xbe750000,0,0x3e2d0000,0,0x80000000,0,0x3e2d0000,
0,0,0xbe2d,0,0xbe75,0,0x3e2d,0,0,0,0xbe2d0000,0,0xbe750000,0,0x3e2d0000,0,
0,0,0,0xbe2d,0,0xbe75,0,0x3e2d,0,0,0,0xbe2d0000,0,0xbe750000,0,0x3e2d0000,
0xbd97,0,0x3e2d,0,0x3e69,0,0xbe2d,0,0xbd970000,0,0x3e2d0000,0,0x3e690000,0,0xbe2d0000,0,
0,0xbd97,0,0x3e2d,0,0x3e69,0,0xbe2d,0,0xbd970000,0,0x3e2d0000,0,0x3e690000,0,0xbe2d0000,
0xbe69,0,0x3e72,0,0x3d97,0,0x3d19,0,0xbe690000,0,0x3e720000,0,0x3d970000,0,0x3d190000,0,
0,0xbe69,0,0x3e72,0,0x3d97,0,0x3d19,0,0xbe690000,0,0x3e720000,0,0x3d970000,0,0x3d190000,
0x3e46,0,0xbe2d,0,0x3e10,0,0xbe2d,0,0x3e460000,0,0xbe2d0000,0,0x3e100000,0,0xbe2d0000,0,
0,0x3e46,0,0xbe2d,0,0x3e10,0,0xbe2d,0,0x3e460000,0,0xbe2d0000,0,0x3e100000,0,0xbe2d0000,
0x3e10,0,0xbdde,0,0x3e46,0,0xbe5a,0,0x3e100000,0,0xbdde0000,0,0x3e460000,0,0xbe5a0000,0,
0,0x3e10,0,0xbdde,0,0x3e46,0,0xbe5a,0,0x3e100000,0,0xbdde0000,0,0x3e460000,0,0xbe5a0000,
0x3d97,0,0x3d19,0,0xbe69,0,0xbe72,0,0x3d970000,0,0x3d190000,0,0xbe690000,0,0xbe720000,0,
0,0x3d97,0,0x3d19,0,0xbe69,0,0xbe72,0,0x3d970000,0,0x3d190000,0,0xbe690000,0,0xbe720000,
0,0,0xbd19,0,0xbe75,0,0xbe72,0,0,0,0xbd190000,0,0xbe750000,0,0xbe720000,0,
0,0,0,0xbd19,0,0xbe75,0,0xbe72,0,0,0,0xbd190000,0,0xbe750000,0,0xbe720000,
0xbe46,0,0xbdde,0,0x3e10,0,0x3e5a,0,0xbe460000,0,0xbdde0000,0,0x3e100000,0,0x3e5a0000,0,
0,0xbe46,0,0xbdde,0,0x3e10,0,0x3e5a,0,0xbe460000,0,0xbdde0000,0,0x3e100000,0,0x3e5a0000,
0,0,0x3dde,0,0x3e75,0,0x3e5a,0,0,0,0x3dde0000,0,0x3e750000,0,0x3e5a0000,0,
0,0,0,0x3dde,0,0x3e75,0,0x3e5a,0,0,0,0x3dde0000,0,0x3e750000,0,0x3e5a0000,
0x3e75,0,0x3e2d,0,0x8000,0,0xbe2d,0,0x3e750000,0,0x3e2d0000,0,0x80000000,0,0xbe2d0000,0,
0,0x3e75,0,0x3e2d,0,0x8000,0,0xbe2d,0,0x3e750000,0,0x3e2d0000,0,0x80000000,0,0xbe2d0000,
0,0,0xbe2d,0,0xbe75,0,0xbe2d,0,0,0,0xbe2d0000,0,0xbe750000,0,0xbe2d0000,0,
0,0,0,0xbe2d,0,0xbe75,0,0xbe2d,0,0,0,0xbe2d0000,0,0xbe750000,0,0xbe2d0000,
0xbe46,0,0xbe5a,0,0xbe10,0,0x3dde,0,0xbe460000,0,0xbe5a0000,0,0xbe100000,0,0x3dde0000,0,
0,0xbe46,0,0xbe5a,0,0xbe10,0,0x3dde,0,0xbe460000,0,0xbe5a0000,0,0xbe100000,0,0x3dde0000,
0,0,0x3e5a,0,0x3e75,0,0x3dde,0,0,0,0x3e5a0000,0,0x3e750000,0,0x3dde0000,0,
0,0,0,0x3e5a,0,0x3e75,0,0x3dde,0,0,0,0x3e5a0000,0,0x3e750000,0,0x3dde0000,
0x3d97,0,0x3e72,0,0x3e69,0,0xbd19,0,0x3d970000,0,0x3e720000,0,0x3e690000,0,0xbd190000,0,
0,0x3d97,0,0x3e72,0,0x3e69,0,0xbd19,0,0x3d970000,0,0x3e720000,0,0x3e690000,0,0xbd190000,
0,0,0xbe72,0,0xbe75,0,0xbd19,0,0,0,0xbe720000,0,0xbe750000,0,0xbd190000,0,
0,0,0,0xbe72,0,0xbe75,0,0xbd19,0,0,0,0xbe720000,0,0xbe750000,0,0xbd190000,
0x3d97,0,0xbe72,0,0xbe69,0,0xbd19,0,0x3d970000,0,0xbe720000,0,0xbe690000,0,0xbd190000,0,
0,0x3d97,0,0xbe72,0,0xbe69,0,0xbd19,0,0x3d970000,0,0xbe720000,0,0xbe690000,0,0xbd190000,
0,0,0x3e72,0,0x3e75,0,0xbd19,0,0,0,0x3e720000,0,0x3e750000,0,0xbd190000,0,
0,0,0,0x3e72,0,0x3e75,0,0xbd19,0,0,0,0x3e720000,0,0x3e750000,0,0xbd190000,
0xbe46,0,0x3e5a,0,0x3e10,0,0x3dde,0,0xbe460000,0,0x3e5a0000,0,0x3e100000,0,0x3dde0000,0,
0,0xbe46,0,0x3e5a,0,0x3e10,0,0x3dde,0,0xbe460000,0,0x3e5a0000,0,0x3e100000,0,0x3dde0000,
0,0,0xbe5a,0,0xbe75,0,0x3dde,0,0,0,0xbe5a0000,0,0xbe750000,0,0x3dde0000,0,
0,0,0,0xbe5a,0,0xbe75,0,0x3dde,0,0,0,0xbe5a0000,0,0xbe750000,0,0x3dde0000,
0x3e75,0,0xbe2d,0,0x8000,0,0xbe2d,0,0x3e750000,0,0xbe2d0000,0,0x80000000,0,0xbe2d0000,0,
0,0x3e75,0,0xbe2d,0,0x8000,0,0xbe2d,0,0x3e750000,0,0xbe2d0000,0,0x80000000,0,0xbe2d0000,
0,0,0x3e2d,0,0x3e75,0,0xbe2d,0,0,0,0x3e2d0000,0,0x3e750000,0,0xbe2d0000,0,
0,0,0,0x3e2d,0,0x3e75,0,0xbe2d,0,0,0,0x3e2d0000,0,0x3e750000,0,0xbe2d0000,
0xbe46,0,0x3dde,0,0xbe10,0,0x3e5a,0,0xbe460000,0,0x3dde0000,0,0xbe100000,0,0x3e5a0000,0,
0,0xbe46,0,0x3dde,0,0xbe10,0,0x3e5a,0,0xbe460000,0,0x3dde0000,0,0xbe100000,0,0x3e5a0000,
0,0,0xbdde,0,0xbe75,0,0x3e5a,0,0,0,0xbdde0000,0,0xbe750000,0,0x3e5a0000,0,
0,0,0,0xbdde,0,0xbe75,0,0x3e5a,0,0,0,0xbdde0000,0,0xbe750000,0,0x3e5a0000,
0x3d97,0,0xbd19,0,0x3e69,0,0xbe72,0,0x3d970000,0,0xbd190000,0,0x3e690000,0,0xbe720000,0,
0,0x3d97,0,0xbd19,0,0x3e69,0,0xbe72,0,0x3d970000,0,0xbd190000,0,0x3e690000,0,0xbe720000,
0,0,0x3d19,0,0x3e75,0,0xbe72,0,0,0,0x3d190000,0,0x3e750000,0,0xbe720000,0,
0,0,0,0x3d19,0,0x3e75,0,0xbe72,0,0,0,0x3d190000,0,0x3e750000,0,0xbe720000,
0xbd97,0,0xbdde,0,0xbe69,0,0xbe5a,0,0xbd970000,0,0xbdde0000,0,0xbe690000,0,0xbe5a0000,0,
0,0xbd97,0,0xbdde,0,0xbe69,0,0xbe5a,0,0xbd970000,0,0xbdde0000,0,0xbe690000,0,0xbe5a0000,
0xbe10,0,0xbe2d,0,0xbe46,0,0xbe2d,0,0xbe100000,0,0xbe2d0000,0,0xbe460000,0,0xbe2d0000,0,
0,0xbe10,0,0xbe2d,0,0xbe46,0,0xbe2d,0,0xbe100000,0,0xbe2d0000,0,0xbe460000,0,0xbe2d0000,
0x3e46,0,0x3e72,0,0x3e10,0,0x3d19,0,0x3e460000,0,0x3e720000,0,0x3e100000,0,0x3d190000,0,
0,0x3e46,0,0x3e72,0,0x3e10,0,0x3d19,0,0x3e460000,0,0x3e720000,0,0x3e100000,0,0x3d190000,
0x3e69,0,0x3e2d,0,0xbd97,0,0xbe2d,0,0x3e690000,0,0x3e2d0000,0,0xbd970000,0,0xbe2d0000,0,
0,0x3e69,0,0x3e2d,0,0xbd97,0,0xbe2d,0,0x3e690000,0,0x3e2d0000,0,0xbd970000,0,0xbe2d0000,
0xbe75,0,0xbe2d,0,0x8000,0,0x3e2d,0,0xbe750000,0,0xbe2d0000,0,0x80000000,0,0x3e2d0000,0,
0,0xbe75,0,0xbe2d,0,0x8000,0,0x3e2d,0,0xbe750000,0,0xbe2d0000,0,0x80000000,0,0x3e2d0000,
0,0,0x3e2d,0,0x3e75,0,0x3e2d,0,0,0,0x3e2d0000,0,0x3e750000,0,0x3e2d0000,0,
0,0,0,0x3e2d,0,0x3e75,0,0x3e2d,0,0,0,0x3e2d0000,0,0x3e750000,0,0x3e2d0000,
0x3e46,0,0xbd19,0,0xbe10,0,0xbe72,0,0x3e460000,0,0xbd190000,0,0xbe100000,0,0xbe720000,0,
0,0x3e46,0,0xbd19,0,0xbe10,0,0xbe72,0,0x3e460000,0,0xbd190000,0,0xbe100000,0,0xbe720000,
0xbe69,0,0xbe2d,0,0xbd97,0,0x3e2d,0,0xbe690000,0,0xbe2d0000,0,0xbd970000,0,0x3e2d0000,0,
0,0xbe69,0,0xbe2d,0,0xbd97,0,0x3e2d,0,0xbe690000,0,0xbe2d0000,0,0xbd970000,0,0x3e2d0000,
0xbd97,0,0x3e5a,0,0x3e69,0,0x3dde,0,0xbd970000,0,0x3e5a0000,0,0x3e690000,0,0x3dde0000,0,
0,0xbd97,0,0x3e5a,0,0x3e69,0,0x3dde,0,0xbd970000,0,0x3e5a0000,0,0x3e690000,0,0x3dde0000,
0x3e10,0,0xbe2d,0,0xbe46,0,0xbe2d,0,0x3e100000,0,0xbe2d0000,0,0xbe460000,0,0xbe2d0000,0,
0,0x3e10,0,0xbe2d,0,0xbe46,0,0xbe2d,0,0x3e100000,0,0xbe2d0000,0,0xbe460000,0,0xbe2d0000,
0xbd97,0,0xbe5a,0,0xbe69,0,0x3dde,0,0xbd970000,0,0xbe5a0000,0,0xbe690000,0,0x3dde0000,0,
0,0xbd97,0,0xbe5a,0,0xbe69,0,0x3dde,0,0xbd970000,0,0xbe5a0000,0,0xbe690000,0,0x3dde0000,
0x3e10,0,0x3e2d,0,0x3e46,0,0xbe2d,0,0x3e100000,0,0x3e2d0000,0,0x3e460000,0,0xbe2d0000,0,
0,0x3e10,0,0x3e2d,0,0x3e46,0,0xbe2d,0,0x3e100000,0,0x3e2d0000,0,0x3e460000,0,0xbe2d0000,
0x3e46,0,0x3d19,0,0x3e10,0,0xbe72,0,0x3e460000,0,0x3d190000,0,0x3e100000,0,0xbe720000,0,
0,0x3e46,0,0x3d19,0,0x3e10,0,0xbe72,0,0x3e460000,0,0x3d190000,0,0x3e100000,0,0xbe720000,
0xbe69,0,0x3e2d,0,0x3d97,0,0x3e2d,0,0xbe690000,0,0x3e2d0000,0,0x3d970000,0,0x3e2d0000,0,
0,0xbe69,0,0x3e2d,0,0x3d97,0,0x3e2d,0,0xbe690000,0,0x3e2d0000,0,0x3d970000,0,0x3e2d0000,
0xbe75,0,0x3e2d,0,0x8000,0,0x3e2d,0,0xbe750000,0,0x3e2d0000,0,0x80000000,0,0x3e2d0000,0,
0,0xbe75,0,0x3e2d,0,0x8000,0,0x3e2d,0,0xbe750000,0,0x3e2d0000,0,0x80000000,0,0x3e2d0000,
0,0,0xbe2d,0,0xbe75,0,0x3e2d,0,0,0,0xbe2d0000,0,0xbe750000,0,0x3e2d0000,0,
0,0,0,0xbe2d,0,0xbe75,0,0x3e2d,0,0,0,0xbe2d0000,0,0xbe750000,0,0x3e2d0000,
0x3e46,0,0xbe72,0,0xbe10,0,0x3d19,0,0x3e460000,0,0xbe720000,0,0xbe100000,0,0x3d190000,0,
0,0x3e46,0,0xbe72,0,0xbe10,0,0x3d19,0,0x3e460000,0,0xbe720000,0,0xbe100000,0,0x3d190000,
0x3e69,0,0xbe2d,0,0x3d97,0,0xbe2d,0,0x3e690000,0,0xbe2d0000,0,0x3d970000,0,0xbe2d0000,0,
0,0x3e69,0,0xbe2d,0,0x3d97,0,0xbe2d,0,0x3e690000,0,0xbe2d0000,0,0x3d970000,0,0xbe2d0000,
0xbd97,0,0x3dde,0,0x3e69,0,0xbe5a,0,0xbd970000,0,0x3dde0000,0,0x3e690000,0,0xbe5a0000,0,
0,0xbd97,0,0x3dde,0,0x3e69,0,0xbe5a,0,0xbd970000,0,0x3dde0000,0,0x3e690000,0,0xbe5a0000,
0xbe10,0,0x3e2d,0,0x3e46,0,0xbe2d,0,0xbe100000,0,0x3e2d0000,0,0x3e460000,0,0xbe2d0000,0,
0,0xbe10,0,0x3e2d,0,0x3e46,0,0xbe2d,0,0xbe100000,0,0x3e2d0000,0,0x3e460000,0,0xbe2d0000,
0xbe46,0,0xbe5a,0,0xbe10,0,0xbdde,0,0xbe460000,0,0xbe5a0000,0,0xbe100000,0,0xbdde0000,0,
0,0xbe46,0,0xbe5a,0,0xbe10,0,0xbdde,0,0xbe460000,0,0xbe5a0000,0,0xbe100000,0,0xbdde0000,
0xbe69,0,0xbe72,0,0xbd97,0,0xbd19,0,0xbe690000,0,0xbe720000,0,0xbd970000,0,0xbd190000,0,
0,0xbe69,0,0xbe72,0,0xbd97,0,0xbd19,0,0xbe690000,0,0xbe720000,0,0xbd970000,0,0xbd190000,
0x3d97,0,0xbd19,0,0xbe69,0,0xbe72,0,0x3d970000,0,0xbd190000,0,0xbe690000,0,0xbe720000,0,
0,0x3d97,0,0xbd19,0,0xbe69,0,0xbe72,0,0x3d970000,0,0xbd190000,0,0xbe690000,0,0xbe720000,
0xbe10,0,0xbe5a,0,0xbe46,0,0xbdde,0,0xbe100000,0,0xbe5a0000,0,0xbe460000,0,0xbdde0000,0,
0,0xbe10,0,0xbe5a,0,0xbe46,0,0xbdde,0,0xbe100000,0,0xbe5a0000,0,0xbe460000,0,0xbdde0000,
0x3e75,0,0x3e2d,0,0x8000,0,0xbe2d,0,0x3e750000,0,0x3e2d0000,0,0x80000000,0,0xbe2d0000,0,
0,0x3e75,0,0x3e2d,0,0x8000,0,0xbe2d,0,0x3e750000,0,0x3e2d0000,0,0x80000000,0,0xbe2d0000,
0,0,0xbe2d,0,0xbe75,0,0xbe2d,0,0,0,0xbe2d0000,0,0xbe750000,0,0xbe2d0000,0,
0,0,0,0xbe2d,0,0xbe75,0,0xbe2d,0,0,0,0xbe2d0000,0,0xbe750000,0,0xbe2d0000,
0x3d97,0,0x3e72,0,0x3e69,0,0x3d19,0,0x3d970000,0,0x3e720000,0,0x3e690000,0,0x3d190000,0,
0,0x3d97,0,0x3e72,0,0x3e69,0,0x3d19,0,0x3d970000,0,0x3e720000,0,0x3e690000,0,0x3d190000,
0x3e10,0,0xbdde,0,0xbe46,0,0xbe5a,0,0x3e100000,0,0xbdde0000,0,0xbe460000,0,0xbe5a0000,0,
0,0x3e10,0,0xbdde,0,0xbe46,0,0xbe5a,0,0x3e100000,0,0xbdde0000,0,0xbe460000,0,0xbe5a0000,
0xbe46,0,0x3dde,0,0x3e10,0,0x3e5a,0,0xbe460000,0,0x3dde0000,0,0x3e100000,0,0x3e5a0000,0,
0,0xbe46,0,0x3dde,0,0x3e10,0,0x3e5a,0,0xbe460000,0,0x3dde0000,0,0x3e100000,0,0x3e5a0000,
0x3e69,0,0xbd19,0,0xbd97,0,0xbe72,0,0x3e690000,0,0xbd190000,0,0xbd970000,0,0xbe720000,0,
0,0x3e69,0,0xbd19,0,0xbd97,0,0xbe72,0,0x3e690000,0,0xbd190000,0,0xbd970000,0,0xbe720000,
0xbe46,0,0xbdde,0,0xbe10,0,0x3e5a,0,0xbe460000,0,0xbdde0000,0,0xbe100000,0,0x3e5a0000,0,
0,0xbe46,0,0xbdde,0,0xbe10,0,0x3e5a,0,0xbe460000,0,0xbdde0000,0,0xbe100000,0,0x3e5a0000,
0x3e69,0,0x3d19,0,0x3d97,0,0xbe72,0,0x3e690000,0,0x3d190000,0,0x3d970000,0,0xbe720000,0,
0,0x3e69,0,0x3d19,0,0x3d97,0,0xbe72,0,0x3e690000,0,0x3d190000,0,0x3d970000,0,0xbe720000,
0x3d97,0,0xbe72,0,0xbe69,0,0x3d19,0,0x3d970000,0,0xbe720000,0,0xbe690000,0,0x3d190000,0,
0,0x3d97,0,0xbe72,0,0xbe69,0,0x3d19,0,0x3d970000,0,0xbe720000,0,0xbe690000,0,0x3d190000,
0x3e10,0,0x3dde,0,0x3e46,0,0xbe5a,0,0x3e100000,0,0x3dde0000,0,0x3e460000,0,0xbe5a0000,0,
0,0x3e10,0,0x3dde,0,0x3e46,0,0xbe5a,0,0x3e100000,0,0x3dde0000,0,0x3e460000,0,0xbe5a0000,
0x3e75,0,0xbe2d,0,0x8000,0,0xbe2d,0,0x3e750000,0,0xbe2d0000,0,0x80000000,0,0xbe2d0000,0,
0,0x3e75,0,0xbe2d,0,0x8000,0,0xbe2d,0,0x3e750000,0,0xbe2d0000,0,0x80000000,0,0xbe2d0000,
0,0,0x3e2d,0,0x3e75,0,0xbe2d,0,0,0,0x3e2d0000,0,0x3e750000,0,0xbe2d0000,0,
0,0,0,0x3e2d,0,0x3e75,0,0xbe2d,0,0,0,0x3e2d0000,0,0x3e750000,0,0xbe2d0000,
0x3d97,0,0x3d19,0,0x3e69,0,0xbe72,0,0x3d970000,0,0x3d190000,0,0x3e690000,0,0xbe720000,0,
0,0x3d97,0,0x3d19,0,0x3e69,0,0xbe72,0,0x3d970000,0,0x3d190000,0,0x3e690000,0,0xbe720000,
0xbe10,0,0x3e5a,0,0x3e46,0,0xbdde,0,0xbe100000,0,0x3e5a0000,0,0x3e460000,0,0xbdde0000,0,
0,0xbe10,0,0x3e5a,0,0x3e46,0,0xbdde,0,0xbe100000,0,0x3e5a0000,0,0x3e460000,0,0xbdde0000,
0xbe46,0,0x3e5a,0,0x3e10,0,0xbdde,0,0xbe460000,0,0x3e5a0000,0,0x3e100000,0,0xbdde0000,0,
0,0xbe46,0,0x3e5a,0,0x3e10,0,0xbdde,0,0xbe460000,0,0x3e5a0000,0,0x3e100000,0,0xbdde0000,
0xbe69,0,0x3e72,0,0x3d97,0,0xbd19,0,0xbe690000,0,0x3e720000,0,0x3d970000,0,0xbd190000,0,
0,0xbe69,0,0x3e72,0,0x3d97,0,0xbd19,0,0xbe690000,0,0x3e720000,0,0x3d970000,0,0xbd190000,
0x3eb7,0x3eb7,0x3eb7,0x3eb7,0x3eb78000,0x3eb78000,0x3eb78000,0x3eb78000,0x3eb7,0x3de23eae,0x3e573e94,0x3e943e57,0x3eb78000,0x3eaebde2,0x3e94be57,0x3e57be94,
0x3eb7,0x3e573e94,0x3eae3de2,0x3eaebde2,0x3eb78000,0x3e94be57,0x3de2beae,0xbde2beae,0x3eb7,0x3e943e57,0x3eaebde2,0x3de2beae,0x3eb78000,0x3e57be94,0xbde2beae,0xbeaebde2,
0x3eb7,0x3eb7,0x3eb7,0x3eb7,0x3eb78000,0x3eb78000,0x3eb78000,0x3eb78000,0x3eae3de2,0x3eb70000,0x3eaebde2,0x3e94be57,0x3de2beae,0xbeb7,0xbde2beae,0xbe57be94,
0x3e57be94,0xbeb7,0xbe57be94,0xbeaebde2,0xbe94be57,0xbeb78000,0xbe943e57,0xbde23eae,0xbe57be94,0xbeb70000,0xbe573e94,0x3de23eae,0xbe943e57,0x3eb7,0x3e943e57,0x3eaebde2,
0x3eb7,0x3eae3de2,0x3e57be94,0xbe57be94,0x3eb78000,0x3de2beae,0xbe94be57,0xbe943e57,0x3eb7,0x3eb70000,0xbeb7,0xbeb70000,0x3eb78000,0xbeb7,0xbeb78000,0x3eb7,
0x3eb7,0x3eaebde2,0xbe57be94,0xbe573e94,0x3eb78000,0xbde2beae,0xbe943e57,0x3e943e57,0x3eb7,0x3e94be57,0xbeaebde2,0x3de23eae,0x3eb78000,0xbe57be94,0xbde23eae,0x3eaebde2,
0xbeae3de2,0x3eb7,0x3eae3de2,0x3e57be94,0x3de23eae,0x3eb78000,0x3de2beae,0xbe94be57,0x3eb7,0x3eb70000,0xbeb7,0xbeb70000,0x3eb78000,0xbeb7,0xbeb78000,0x3eb7,
0x3eae3de2,0xbeb7,0xbeae3de2,0x3e573e94,0x3de2beae,0xbeb78000,0x3de23eae,0x3e94be57,0x3e57be94,0xbeb70000,0x3e573e94,0x3de2beae,0xbe94be57,0x3eb7,0x3e94be57,0xbeaebde2,
0x3eb7,0x3e57be94,0xbeae3de2,0x3eae3de2,0x3eb78000,0xbe94be57,0x3de23eae,0x3de2beae,0x3eb7,0x3de2beae,0xbe573e94,0x3e94be57,0x3eb78000,0xbeaebde2,0x3e943e57,0xbe57be94,
0x3eb7,0xbeb7,0x3eb7,0xbeb7,0x3eb78000,0xbeb78000,0x3eb78000,0xbeb78000,0x3eb7,0xbde2beae,0x3e573e94,0xbe94be57,0x3eb78000,0xbeae3de2,0x3e94be57,0xbe573e94,
0xbe57be94,0x3eb7,0x3e57be94,0xbeae3de2,0xbe943e57,0x3eb78000,0xbe94be57,0x3de23eae,0xbeae3de2,0x3eb70000,0xbeaebde2,0x3e943e57,0x3de23eae,0xbeb7,0xbde23eae,0x3e57be94,
0x3eb7,0xbeb7,0x3eb7,0xbeb7,0x3eb78000,0xbeb78000,0x3eb78000,0xbeb78000,0x3eae3de2,0xbeb70000,0x3eaebde2,0xbe943e57,0x3de2beae,0x3eb7,0xbde2beae,0x3e573e94,
0x3eb7,0xbe57be94,0x3eae3de2,0xbeae3de2,0x3eb78000,0xbe943e57,0x3de2beae,0x3de23eae,0x3eb7,0xbe94be57,0x3eaebde2,0xbde23eae,0x3eb78000,0xbe573e94,0xbde2beae,0x3eae3de2,
0x3eb7,0xbeaebde2,0x3e57be94,0x3e573e94,0x3eb78000,0xbde23eae,0xbe94be57,0x3e94be57,0x3eb7,0xbeb70000,0xbeb7,0x3eb70000,0x3eb78000,0x3eb7,0xbeb78000,0xbeb7,
0x3e57be94,0x3eb7,0xbe57be94,0x3eae3de2,0xbe94be57,0x3eb78000,0xbe943e57,0x3de2beae,0xbe57be94,0x3eb70000,0xbe573e94,0xbde2beae,0xbe943e57,0xbeb7,0x3e943e57,0xbeae3de2,
0xbeae3de2,0xbeb7,0x3eae3de2,0xbe573e94,0x3de23eae,0xbeb78000,0x3de2beae,0x3e943e57,0x3eb7,0xbeb70000,0xbeb7,0x3eb70000,0x3eb78000,0x3eb7,0xbeb78000,0xbeb7,
0x3eb7,0xbeae3de2,0xbe57be94,0x3e57be94,0x3eb78000,0x3de23eae,0xbe943e57,0xbe94be57,0x3eb7,0xbe943e57,0xbeaebde2,0xbde2beae,0x3eb78000,0x3e573e94,0xbde23eae,0xbeae3de2,
0x3eb7,0xbe573e94,0xbeae3de2,0xbeaebde2,0x3eb78000,0x3e943e57,0x3de23eae,0xbde23eae,0x3eb7,0xbde23eae,0xbe573e94,0xbe943e57,0x3eb78000,0x3eae3de2,0x3e943e57,0x3e573e94,
0x3eae3de2,0x3eb7,0xbeae3de2,0xbe57be94,0x3de2beae,0x3eb78000,0x3de23eae,0xbe943e57,0x3e57be94,0x3eb70000,0x3e573e94,0xbde23eae,0xbe94be57,0xbeb7,0x3e94be57,0x3eae3de2,
0xbe57be94,0xbeb7,0x3e57be94,0x3eaebde2,0xbe943e57,0xbeb78000,0xbe94be57,0xbde2beae,0xbeae3de2,0xbeb70000,0xbeaebde2,0xbe94be57,0x3de23eae,0x3eb7,0xbde23eae,0xbe573e94,
0x3eb7,0x3eb7,0x3eb7,0x3eb7,0x3eb78000,0x3eb78000,0x3eb78000,0x3eb78000,0x3e57be94,0x3de2beae,0xbeb7,0xbde2beae,0xbe94be57,0xbeaebde2,0xbeb78000,0xbeae3de2,
0xbeae3de2,0xbe573e94,0x3eb7,0x3e573e94,0x3de23eae,0x3e943e57,0x3eb78000,0x3e94be57,0x3eae3de2,0x3e94be57,0xbeb7,0xbe94be57,0x3de2beae,0xbe57be94,0xbeb78000,0xbe573e94,
0x3eb7,0x3eb7,0x3eb7,0x3eb7,0x3eb78000,0x3eb78000,0x3eb78000,0x3eb78000,0xbe57be94,0xbe94be57,0xbeaebde2,0xbeb70000,0xbe943e57,0xbe573e94,0xbde23eae,0x3eb7,
0x3eae3de2,0x3eaebde2,0x3e57be94,0xbeb7,0x3de2beae,0xbde2beae,0xbe94be57,0xbeb78000,0xbeae3de2,0xbde23eae,0x3e573e94,0x3eb70000,0x3de23eae,0x3eae3de2,0x3e94be57,0xbeb7,
0xbe57be94,0xbeae3de2,0x3eb7,0x3eae3de2,0xbe943e57,0x3de23eae,0x3eb78000,0x3de2beae,0x3eb7,0x3eb70000,0xbeb7,0xbeb70000,0x3eb78000,0xbeb7,0xbeb78000,0x3eb7,
0x3e57be94,0xbeaebde2,0x3eb7,0x3eaebde2,0xbe94be57,0xbde23eae,0x3eb78000,0xbde2beae,0xbeae3de2,0x3e943e57,0xbeb7,0xbe943e57,0x3de23eae,0x3e57be94,0xbeb78000,0x3e573e94,
0x3e57be94,0xbe57be94,0xbeae3de2,0x3eb7,0xbe94be57,0xbe943e57,0x3de23eae,0x3eb78000,0x3eb7,0x3eb70000,0xbeb7,0xbeb70000,0x3eb78000,0xbeb7,0xbeb78000,0x3eb7,
0xbe57be94,0xbe573e94,0x3eae3de2,0xbeb7,0xbe943e57,0x3e943e57,0x3de2beae,0xbeb78000,0x3eae3de2,0xbde2beae,0xbe573e94,0x3eb70000,0x3de2beae,0xbeae3de2,0x3e943e57,0xbeb7,
0x3eae3de2,0xbe57be94,0x3eb7,0x3e57be94,0x3de2beae,0xbe943e57,0x3eb78000,0xbe94be57,0xbe57be94,0x3de23eae,0xbeb7,0xbde23eae,0xbe943e57,0x3eaebde2,0xbeb78000,0x3eae3de2,
0x3eb7,0xbeb7,0x3eb7,0xbeb7,0x3eb78000,0xbeb78000,0x3eb78000,0xbeb78000,0x3e57be94,0xbde23eae,0xbeb7,0x3de23eae,0xbe94be57,0x3eae3de2,0xbeb78000,0x3eaebde2,
0xbeae3de2,0x3eae3de2,0xbe57be94,0x3eb7,0x3de23eae,0x3de2beae,0xbe943e57,0x3eb78000,0x3e57be94,0xbe943e57,0x3eaebde2,0xbeb70000,0xbe94be57,0x3e573e94,0xbde2beae,0x3eb7,
0x3eb7,0xbeb7,0x3eb7,0xbeb7,0x3eb78000,0xbeb78000,0x3eb78000,0xbeb78000,0xbe57be94,0x3e943e57,0xbeaebde2,0x3eb70000,0xbe943e57,0x3e57be94,0xbde23eae,0xbeb7,
0xbeae3de2,0x3e57be94,0x3eb7,0xbe57be94,0x3de23eae,0xbe94be57,0x3eb78000,0xbe943e57,0x3eae3de2,0xbe943e57,0xbeb7,0x3e943e57,0x3de2beae,0x3e573e94,0xbeb78000,0x3e57be94,
0xbe57be94,0x3eaebde2,0x3eb7,0xbeaebde2,0xbe943e57,0xbde2beae,0x3eb78000,0xbde23eae,0x3eb7,0xbeb70000,0xbeb7,0x3eb70000,0x3eb78000,0x3eb7,0xbeb78000,0xbeb7,
0x3eae3de2,0xbeae3de2,0x3e57be94,0x3eb7,0x3de2beae,0x3de23eae,0xbe94be57,0x3eb78000,0xbeae3de2,0x3de2beae,0x3e573e94,0xbeb70000,0x3de23eae,0xbeaebde2,0x3e94be57,0x3eb7,
0x3e57be94,0x3e573e94,0xbeae3de2,0xbeb7,0xbe94be57,0x3e94be57,0x3de23eae,0xbeb78000,0x3eb7,0xbeb70000,0xbeb7,0x3eb70000,0x3eb78000,0x3eb7,0xbeb78000,0xbeb7,
0x3e57be94,0x3eae3de2,0x3eb7,0xbeae3de2,0xbe94be57,0x3de2beae,0x3eb78000,0x3de23eae,0xbeae3de2,0xbe94be57,0xbeb7,0x3e94be57,0x3de23eae,0xbe573e94,0xbeb78000,0xbe57be94,
0x3eae3de2,0x3e573e94,0x3eb7,0xbe573e94,0x3de2beae,0x3e94be57,0x3eb78000,0x3e943e57,0xbe57be94,0xbde2beae,0xbeb7,0x3de2beae,0xbe943e57,0xbeae3de2,0xbeb78000,0xbeaebde2,
0xbe57be94,0x3e57be94,0x3eae3de2,0x3eb7,0xbe943e57,0xbe94be57,0x3de2beae,0x3eb78000,0x3eae3de2,0x3de23eae,0xbe573e94,0xbeb70000,0x3de2beae,0x3eaebde2,0x3e943e57,0x3eb7,
0xbeae3de2,0xbeaebde2,0xbe57be94,0xbeb7,0x3de23eae,0xbde23eae,0xbe943e57,0xbeb78000,0x3e57be94,0x3e94be57,0x3eaebde2,0x3eb70000,0xbe94be57,0xbe57be94,0xbde2beae,0xbeb7,
0x3eb7,0x3eb7,0x3eb7,0x3eb7,0x3eb78000,0x3eb78000,0x3eb78000,0x3eb78000,0xbeae3de2,0xbe943e57,0xbe573e94,0xbde23eae,0x3de23eae,0x3e573e94,0x3e943e57,0x3eae3de2,
0xbe57be94,0xbeaebde2,0xbeae3de2,0xbe573e94,0xbe943e57,0xbde23eae,0x3de23eae,0x3e943e57,0x3e57be94,0xbde2beae,0xbeaebde2,0xbe943e57,0xbe94be57,0xbeae3de2,0xbde23eae,0x3e573e94,
0,0,0,0,0,0,0,0,0,0,0,0,0,0,0,0,
0,0,0,0,0,0,0,0,0,0,0,0,0,0,0,0,
0x3eae3de2,0x3e57be94,0xbe57be94,0xbeae3de2,0x3de2beae,0xbe94be57,0xbe943e57,0x3de23eae,0x3eb7,0x3eb70000,0xbeb7,0xbeb70000,0x3eb78000,0xbeb7,0xbeb78000,0x3eb7,
0xbeae3de2,0x3e573e94,0x3e57be94,0xbeaebde2,0x3de23eae,0x3e94be57,0xbe94be57,0xbde23eae,0xbe57be94,0xbde23eae,0x3eaebde2,0xbe94be57,0xbe943e57,0x3eae3de2,0xbde2beae,0xbe573e94,
0,0,0,0,0,0,0,0,0,0,0,0,0,0,0,0,
0,0,0,0,0,0,0,0,0,0,0,0,0,0,0,0,
0x3e57be94,0xbeae3de2,0x3eae3de2,0xbe57be94,0xbe94be57,0x3de23eae,0x3de2beae,0xbe943e57,0x3eae3de2,0xbe94be57,0x3e573e94,0xbde2beae,0x3de2beae,0xbe573e94,0x3e94be57,0xbeae3de2,
0x3eb7,0xbeb7,0x3eb7,0xbeb7,0x3eb78000,0xbeb78000,0x3eb78000,0xbeb78000,0xbeae3de2,0x3e94be57,0xbe573e94,0x3de2beae,0x3de23eae,0xbe57be94,0x3e943e57,0xbeaebde2,
0,0,0,0,0,0,0,0,0,0,0,0,0,0,0,0,
0,0,0,0,0,0,0,0,0,0,0,0,0,0,0,0,
0xbe57be94,0x3eae3de2,0xbeae3de2,0x3e57be94,0xbe943e57,0x3de2beae,0x3de23eae,0xbe94be57,0x3e57be94,0x3de23eae,0xbeaebde2,0x3e94be57,0xbe94be57,0x3eaebde2,0xbde23eae,0xbe57be94,
0x3eae3de2,0xbe573e94,0xbe57be94,0x3eaebde2,0x3de2beae,0x3e943e57,0xbe943e57,0xbde2beae,0x3eb7,0xbeb70000,0xbeb7,0x3eb70000,0x3eb78000,0x3eb7,0xbeb78000,0xbeb7,
0,0,0,0,0,0,0,0,0,0,0,0,0,0,0,0,
0,0,0,0,0,0,0,0,0,0,0,0,0,0,0,0,
0xbeae3de2,0xbe57be94,0x3e57be94,0x3eae3de2,0x3de23eae,0xbe943e57,0xbe94be57,0x3de2beae,0xbe57be94,0x3de2beae,0x3eaebde2,0x3e943e57,0xbe943e57,0xbeaebde2,0xbde2beae,0x3e57be94,
0x3e57be94,0x3eaebde2,0x3eae3de2,0x3e573e94,0xbe94be57,0xbde2beae,0x3de2beae,0x3e94be57,0x3eae3de2,0x3e943e57,0x3e573e94,0x3de23eae,0x3de2beae,0x3e57be94,0x3e94be57,0x3eaebde2,
0,0,0,0,0,0,0,0,0,0,0,0,0,0,0,0,
0,0,0,0,0,0,0,0,0,0,0,0,0,0,0,0,
0,0,0,0,0,0,0,0,0,0,0,0,0,0,0,0,
0,0,0,0,0,0,0,0,0,0,0,0,0,0,0,0,
0x3eb7,0x3eb7,0x3eb7,0x3eb7,0x3eb78000,0x3eb78000,0x3eb78000,0x3eb78000,0xbeae3de2,0xbe943e57,0xbe573e94,0xbde23eae,0x3de23eae,0x3e573e94,0x3e943e57,0x3eae3de2,
0xbe57be94,0xbeaebde2,0xbeae3de2,0xbe573e94,0xbe943e57,0xbde23eae,0x3de23eae,0x3e943e57,0x3e57be94,0xbde2beae,0xbeaebde2,0xbe943e57,0xbe94be57,0xbeae3de2,0xbde23eae,0x3e573e94,
0,0,0,0,0,0,0,0,0,0,0,0,0,0,0,0,
0,0,0,0,0,0,0,0,0,0,0,0,0,0,0,0,
0x3eae3de2,0x3e57be94,0xbe57be94,0xbeae3de2,0x3de2beae,0xbe94be57,0xbe943e57,0x3de23eae,0x3eb7,0x3eb70000,0xbeb7,0xbeb70000,0x3eb78000,0xbeb7,0xbeb78000,0x3eb7,
0xbeae3de2,0x3e573e94,0x3e57be94,0xbeaebde2,0x3de23eae,0x3e94be57,0xbe94be57,0xbde23eae,0xbe57be94,0xbde23eae,0x3eaebde2,0xbe94be57,0xbe943e57,0x3eae3de2,0xbde2beae,0xbe573e94,
0,0,0,0,0,0,0,0,0,0,0,0,0,0,0,0,
0,0,0,0,0,0,0,0,0,0,0,0,0,0,0,0,
0x3e57be94,0xbeae3de2,0x3eae3de2,0xbe57be94,0xbe94be57,0x3de23eae,0x3de2beae,0xbe943e57,0x3eae3de2,0xbe94be57,0x3e573e94,0xbde2beae,0x3de2beae,0xbe573e94,0x3e94be57,0xbeae3de2,
0x3eb7,0xbeb7,0x3eb7,0xbeb7,0x3eb78000,0xbeb78000,0x3eb78000,0xbeb78000,0xbeae3de2,0x3e94be57,0xbe573e94,0x3de2beae,0x3de23eae,0xbe57be94,0x3e943e57,0xbeaebde2,
0,0,0,0,0,0,0,0,0,0,0,0,0,0,0,0,
0,0,0,0,0,0,0,0,0,0,0,0,0,0,0,0,
0xbe57be94,0x3eae3de2,0xbeae3de2,0x3e57be94,0xbe943e57,0x3de2beae,0x3de23eae,0xbe94be57,0x3e57be94,0x3de23eae,0xbeaebde2,0x3e94be57,0xbe94be57,0x3eaebde2,0xbde23eae,0xbe57be94,
0x3eae3de2,0xbe573e94,0xbe57be94,0x3eaebde2,0x3de2beae,0x3e943e57,0xbe943e57,0xbde2beae,0x3eb7,0xbeb70000,0xbeb7,0x3eb70000,0x3eb78000,0x3eb7,0xbeb78000,0xbeb7,
0,0,0,0,0,0,0,0,0,0,0,0,0,0,0,0,
0,0,0,0,0,0,0,0,0,0,0,0,0,0,0,0,
0xbeae3de2,0xbe57be94,0x3e57be94,0x3eae3de2,0x3de23eae,0xbe943e57,0xbe94be57,0x3de2beae,0xbe57be94,0x3de2beae,0x3eaebde2,0x3e943e57,0xbe943e57,0xbeaebde2,0xbde2beae,0x3e57be94,
0x3e57be94,0x3eaebde2,0x3eae3de2,0x3e573e94,0xbe94be57,0xbde2beae,0x3de2beae,0x3e94be57,0x3eae3de2,0x3e943e57,0x3e573e94,0x3de23eae,0x3de2beae,0x3e57be94,0x3e94be57,0x3eaebde2,
};
__device__ __align__(128) const uint32_t TAB_P3[4288] = {
0,0,0,0,0,0,0,0,0,0,0,0,0,0,0,0,
0x80003e83,0xbe79bda2,0x3e1abe54,0x3e1a3e54,0x3e830000,0xbda23e79,0xbe54be1a,0x3e54be1a,0x80003e83,0xbe54be1a,0x3e79bda2,0xbda23e79,0x3e830000,0xbe1a3e54,0xbda2be79,0x3e793da2,
0,0,0,0,0,0,0,0,0,0,0,0,0,0,0,0,
0xbe793da2,0x8000be83,0x3e793da2,0xbe1a3e54,0x3da23e79,0xbe830000,0x3da2be79,0x3e543e1a,0xbe1abe54,0x3e830000,0xbe1a3e54,0xbda2be79,0xbe543e1a,0xbe83,0x3e543e1a,0xbe793da2,
0x80003e83,0xbe1abe54,0x3e793da2,0xbe793da2,0x3e830000,0xbe543e1a,0x3da2be79,0x3da23e79,0x80003e83,0xbda2be79,0x3e1a3e54,0xbe54be1a,0x3e830000,0xbe793da2,0x3e54be1a,0xbe1a3e54,
0x80003e83,0x8000be83,0x80003e83,0x8000be83,0x3e830000,0xbe830000,0x3e830000,0xbe830000,0x80003e83,0x3da2be79,0xbe1a3e54,0x3e54be1a,0x3e830000,0xbe79bda2,0x3e543e1a,0xbe1abe54,
0x3e1abe54,0x80003e83,0xbe1abe54,0x3e793da2,0xbe54be1a,0x3e830000,0xbe543e1a,0x3da2be79,0x3e793da2,0xbe830000,0x3e79bda2,0xbe543e1a,0x3da2be79,0x3e83,0xbda2be79,0x3e1a3e54,
0x80003e83,0x8000be83,0x80003e83,0x8000be83,0x3e830000,0xbe830000,0x3e830000,0xbe830000,0xbe793da2,0x3e830000,0xbe79bda2,0x3e543e1a,0x3da23e79,0xbe83,0xbda23e79,0x3e1abe54,
0x80003e83,0x3e1abe54,0xbe793da2,0x3e793da2,0x3e830000,0xbe54be1a,0x3da23e79,0x3da2be79,0x80003e83,0x3e54be1a,0xbe79bda2,0x3da23e79,0x3e830000,0xbe1abe54,0xbda23e79,0x3e79bda2,
0x80003e83,0x3e79bda2,0xbe1abe54,0xbe1a3e54,0x3e830000,0xbda2be79,0xbe543e1a,0x3e543e1a,0x80003e83,0x3e830000,0x8000be83,0xbe830000,0x3e830000,0xbe83,0xbe830000,0x3e83,
0xbe1abe54,0x80003e83,0x3e1abe54,0xbe793da2,0xbe543e1a,0x3e830000,0xbe54be1a,0x3da23e79,0x3e1abe54,0xbe830000,0x3e1a3e54,0x3da2be79,0xbe54be1a,0x3e83,0x3e54be1a,0xbe79bda2,
0x3e793da2,0x8000be83,0xbe793da2,0x3e1a3e54,0x3da2be79,0xbe830000,0x3da23e79,0x3e54be1a,0x80003e83,0x3e830000,0x8000be83,0xbe830000,0x3e830000,0xbe83,0xbe830000,0x3e83,
0x80003e83,0x3e793da2,0x3e1abe54,0xbe1abe54,0x3e830000,0x3da2be79,0xbe54be1a,0xbe543e1a,0x80003e83,0x3e543e1a,0x3e79bda2,0x3da2be79,0x3e830000,0x3e1abe54,0xbda2be79,0xbe79bda2,
0x80003e83,0x3e1a3e54,0x3e793da2,0x3e79bda2,0x3e830000,0x3e54be1a,0x3da2be79,0xbda2be79,0x80003e83,0x3da23e79,0x3e1a3e54,0x3e543e1a,0x3e830000,0x3e79bda2,0x3e54be1a,0x3e1abe54,
0xbe793da2,0x80003e83,0x3e793da2,0x3e1abe54,0x3da23e79,0x3e830000,0x3da2be79,0xbe54be1a,0xbe1abe54,0xbe830000,0xbe1a3e54,0x3da23e79,0xbe543e1a,0x3e83,0x3e543e1a,0x3e79bda2,
0x3e1abe54,0x8000be83,0xbe1abe54,0xbe79bda2,0xbe54be1a,0xbe830000,0xbe543e1a,0xbda23e79,0x3e793da2,0x3e830000,0x3e79bda2,0x3e54be1a,0x3da2be79,0xbe83,0xbda2be79,0xbe1abe54,
0,0,0,0,0,0,0,0,0,0,0,0,0,0,0,0,
0,0,0,0,0,0,0,0,0,0,0,0,0,0,0,0,
0,0,0,0,0,0,0,0,0,0,0,0,0,0,0,0,
0xbe1abe54,0x3e79bda2,0x80003e83,0xbe79bda2,0xbe543e1a,0xbda2be79,0x3e830000,0xbda23e79,0x3e793da2,0xbe543e1a,0x8000be83,0x3e543e1a,0x3da2be79,0x3e1a3e54,0xbe830000,0x3e1abe54,
0,0,0,0,0,0,0,0,0,0,0,0,0,0,0,0,
0,0,0,0,0,0,0,0,0,0,0,0,0,0,0,0,
0xbe793da2,0x3e1abe54,0x80003e83,0xbe1abe54,0x3da23e79,0xbe54be1a,0x3e830000,0xbe543e1a,0x3e1abe54,0xbda23e79,0x8000be83,0x3da23e79,0xbe54be1a,0x3e793da2,0xbe830000,0x3e79bda2,
0x80003e83,0x8000be83,0x80003e83,0x8000be83,0x3e830000,0xbe830000,0x3e830000,0xbe830000,0xbe1abe54,0x3da23e79,0x8000be83,0xbda23e79,0xbe543e1a,0x3e79bda2,0xbe830000,0x3e793da2,
0,0,0,0,0,0,0,0,0,0,0,0,0,0,0,0,
0,0,0,0,0,0,0,0,0,0,0,0,0,0,0,0,
0x3e793da2,0xbe1abe54,0x80003e83,0x3e1abe54,0x3da2be79,0xbe543e1a,0x3e830000,0xbe54be1a,0xbe793da2,0x3e543e1a,0x8000be83,0xbe543e1a,0x3da23e79,0x3e1abe54,0xbe830000,0x3e1a3e54,
0x3e1abe54,0xbe79bda2,0x80003e83,0x3e79bda2,0xbe54be1a,0xbda23e79,0x3e830000,0xbda2be79,0x80003e83,0x3e830000,0x8000be83,0xbe830000,0x3e830000,0xbe83,0xbe830000,0x3e83,
0,0,0,0,0,0,0,0,0,0,0,0,0,0,0,0,
0,0,0,0,0,0,0,0,0,0,0,0,0,0,0,0,
0xbe1abe54,0xbe793da2,0x80003e83,0x3e793da2,0xbe543e1a,0x3da23e79,0x3e830000,0x3da2be79,0x3e793da2,0x3e54be1a,0x8000be83,0xbe54be1a,0x3da2be79,0xbe1abe54,0xbe830000,0xbe1a3e54,
0xbe793da2,0xbe1a3e54,0x80003e83,0x3e1a3e54,0x3da23e79,0x3e543e1a,0x3e830000,0x3e54be1a,0x3e1abe54,0x3da2be79,0x8000be83,0xbda2be79,0xbe54be1a,0xbe79bda2,0xbe830000,0xbe793da2,
0,0,0,0,0,0,0,0,0,0,0,0,0,0,0,0,
0x3e1abe54,0x3e1a3e54,0xbe793da2,0x8000be83,0xbe54be1a,0x3e54be1a,0x3da23e79,0xbe830000,0xbe793da2,0x3da2be79,0x3e1a3e54,0xbe830000,0x3da23e79,0xbe79bda2,0x3e54be1a,0x3e83,
0,0,0,0,0,0,0,0,0,0,0,0,0,0,0,0,
0x3e793da2,0xbe1a3e54,0xbe1abe54,0x3e79bda2,0x3da2be79,0x3e543e1a,0xbe543e1a,0xbda2be79,0x3e1abe54,0x3da23e79,0xbe79bda2,0x3e54be1a,0xbe54be1a,0x3e79bda2,0xbda23e79,0xbe1abe54,
0x3e793da2,0xbe793da2,0x3e1abe54,0x80003e83,0x3da2be79,0x3da23e79,0xbe54be1a,0x3e830000,0xbe1abe54,0x3e543e1a,0xbe79bda2,0x3e830000,0xbe543e1a,0x3e1abe54,0xbda23e79,0xbe83,
0x80003e83,0x8000be83,0x80003e83,0x8000be83,0x3e830000,0xbe830000,0x3e830000,0xbe830000,0x3e1abe54,0xbe543e1a,0x3e79bda2,0xbe830000,0xbe54be1a,0x3e1a3e54,0xbda2be79,0x3e83,
0xbe1abe54,0x3e793da2,0xbe793da2,0x3e1abe54,0xbe543e1a,0x3da2be79,0x3da23e79,0xbe54be1a,0xbe793da2,0x3e54be1a,0xbe1a3e54,0x3da2be79,0x3da23e79,0xbe1abe54,0x3e543e1a,0xbe79bda2,
0x80003e83,0x8000be83,0x80003e83,0x8000be83,0x3e830000,0xbe830000,0x3e830000,0xbe830000,0x3e793da2,0xbe54be1a,0x3e1a3e54,0xbda2be79,0x3da2be79,0xbe1a3e54,0x3e54be1a,0xbe793da2,
0xbe793da2,0x3e793da2,0xbe1abe54,0x80003e83,0x3da23e79,0x3da2be79,0xbe543e1a,0x3e830000,0x3e793da2,0xbda2be79,0xbe1a3e54,0x3e830000,0x3da2be79,0xbe793da2,0x3e543e1a,0xbe83,
0xbe1abe54,0xbe1a3e54,0x3e793da2,0x8000be83,0xbe543e1a,0x3e543e1a,0x3da2be79,0xbe830000,0x80003e83,0x3e830000,0x8000be83,0xbe830000,0x3e830000,0xbe83,0xbe830000,0x3e83,
0x3e1abe54,0xbe793da2,0x3e793da2,0xbe1abe54,0xbe54be1a,0x3da23e79,0x3da2be79,0xbe543e1a,0xbe1abe54,0xbda23e79,0x3e79bda2,0xbe54be1a,0xbe543e1a,0x3e793da2,0xbda2be79,0xbe1a3e54,
0xbe793da2,0x3e1a3e54,0x3e1abe54,0xbe79bda2,0x3da23e79,0x3e54be1a,0xbe54be1a,0xbda23e79,0x80003e83,0x3e830000,0x8000be83,0xbe830000,0x3e830000,0xbe83,0xbe830000,0x3e83,
0x3e1abe54,0xbe1abe54,0xbe793da2,0x80003e83,0xbe54be1a,0xbe543e1a,0x3da23e79,0x3e830000,0xbe793da2,0xbda23e79,0x3e1a3e54,0x3e830000,0x3da23e79,0x3e793da2,0x3e54be1a,0xbe83,
0x3e793da2,0x3e79bda2,0x3e1abe54,0x8000be83,0x3da2be79,0xbda2be79,0xbe54be1a,0xbe830000,0xbe1abe54,0xbe54be1a,0xbe79bda2,0xbe830000,0xbe543e1a,0xbe1a3e54,0xbda23e79,0x3e83,
0x3e793da2,0x3e1abe54,0xbe1abe54,0xbe793da2,0x3da2be79,0xbe54be1a,0xbe543e1a,0x3da23e79,0x3e1abe54,0xbda2be79,0xbe79bda2,0xbe543e1a,0xbe54be1a,0xbe793da2,0xbda23e79,0x3e1a3e54,
0xbe1abe54,0xbe79bda2,0xbe793da2,0xbe1a3e54,0xbe543e1a,0xbda23e79,0x3da23e79,0x3e543e1a,0xbe793da2,0xbe543e1a,0xbe1a3e54,0xbda23e79,0x3da23e79,0x3e1a3e54,0x3e543e1a,0x3e793da2,
0xbe163dda,0,0,0,0,0xbe163dda,0,0,0,0,0xbe163dda,0,0,0,0,0xbe163dda,
0xbe253da8,0,0,0,0,0xbe253da8,0,0,0,0,0xbe253da8,0,0,0,0,0xbe253da8,
0xbd65be30,0,0,0,0,0xbd65be30,0,0,0,0,0xbd65be30,0,0,0,0,0xbd65be30,
0x3ce8be37,0,0,0,0,0x3ce8be37,0,0,0,0,0x3ce8be37,0,0,0,0,0x3ce8be37,
0xbe303d65,0,0,0,0,0xbe303d65,0,0,0,0,0xbe303d65,0,0,0,0,0xbe303d65,
0xbe373ce8,0,0,0,0,0xbe373ce8,0,0,0,0,0xbe373ce8,0,0,0,0,0xbe373ce8,
0x3ddabe16,0,0,0,0,0x3ddabe16,0,0,0,0,0x3ddabe16,0,0,0,0,0x3ddabe16,
0x3e25bda8,0,0,0,0,0x3e25bda8,0,0,0,0,0x3e25bda8,0,0,0,0,0x3e25bda8,
0xbe390000,0,0,0,0,0xbe390000,0,0,0,0,0xbe390000,0,0,0,0,0xbe390000,
0xbe37bce8,0,0,0,0,0xbe37bce8,0,0,0,0,0xbe37bce8,0,0,0,0,0xbe37bce8,
0x3e390000,0,0,0,0,0x3e390000,0,0,0,0,0x3e390000,0,0,0,0,0x3e390000,
0x3e253da8,0,0,0,0,0x3e253da8,0,0,0,0,0x3e253da8,0,0,0,0,0x3e253da8,
0xbe30bd65,0,0,0,0,0xbe30bd65,0,0,0,0,0xbe30bd65,0,0,0,0,0xbe30bd65,
0xbe25bda8,0,0,0,0,0xbe25bda8,0,0,0,0,0xbe25bda8,0,0,0,0,0xbe25bda8,
0x3dda3e16,0,0,0,0,0x3dda3e16,0,0,0,0,0x3dda3e16,0,0,0,0,0x3dda3e16,
0x3ce83e37,0,0,0,0,0x3ce83e37,0,0,0,0,0x3ce83e37,0,0,0,0,0x3ce83e37,
0xbe16bdda,0,0,0,0,0xbe16bdda,0,0,0,0,0xbe16bdda,0,0,0,0,0xbe16bdda,
0xbe03be03,0,0,0,0,0xbe03be03,0,0,0,0,0xbe03be03,0,0,0,0,0xbe03be03,
0xbd653e30,0,0,0,0,0xbd653e30,0,0,0,0,0xbd653e30,0,0,0,0,0xbd653e30,
0xbe033e03,0,0,0,0,0xbe033e03,0,0,0,0,0xbe033e03,0,0,0,0,0xbe033e03,
0xbddabe16,0,0,0,0,0xbddabe16,0,0,0,0,0xbddabe16,0,0,0,0,0xbddabe16,
0xbda8be25,0,0,0,0,0xbda8be25,0,0,0,0,0xbda8be25,0,0,0,0,0xbda8be25,
0xbe303d65,0,0,0,0,0xbe303d65,0,0,0,0,0xbe303d65,0,0,0,0,0xbe303d65,
0xbe37bce8,0,0,0,0,0xbe37bce8,0,0,0,0,0xbe37bce8,0,0,0,0,0xbe37bce8,
0xbd65be30,0,0,0,0,0xbd65be30,0,0,0,0,0xbd65be30,0,0,0,0,0xbd65be30,
0xbce8be37,0,0,0,0,0xbce8be37,0,0,0,0,0xbce8be37,0,0,0,0,0xbce8be37,
0xbe16bdda,0,0,0,0,0xbe16bdda,0,0,0,0,0xbe16bdda,0,0,0,0,0xbe16bdda,
0xbda8be25,0,0,0,0,0xbda8be25,0,0,0,0,0xbda8be25,0,0,0,0,0xbda8be25,
0x3e390000,0,0,0,0,0x3e390000,0,0,0,0,0x3e390000,0,0,0,0,0x3e390000,
0x3e033e03,0,0,0,0,0x3e033e03,0,0,0,0,0x3e033e03,0,0,0,0,0x3e033e03,
0xbd653e30,0,0,0,0,0xbd653e30,0,0,0,0,0xbd653e30,0,0,0,0,0xbd653e30,
0xbe373ce8,0,0,0,0,0xbe373ce8,0,0,0,0,0xbe373ce8,0,0,0,0,0xbe373ce8,
0x80003e39,0,0,0,0,0x80003e39,0,0,0,0,0x80003e39,0,0,0,0,0x80003e39,
0xbe033e03,0,0,0,0,0xbe033e03,0,0,0,0,0xbe033e03,0,0,0,0,0xbe033e03,
0xbddabe16,0,0,0,0,0xbddabe16,0,0,0,0,0xbddabe16,0,0,0,0,0xbddabe16,
0x3da8be25,0,0,0,0,0x3da8be25,0,0,0,0,0x3da8be25,0,0,0,0,0x3da8be25,
0xbe390000,0,0,0,0,0xbe390000,0,0,0,0,0xbe390000,0,0,0,0,0xbe390000,
0xbe03be03,0,0,0,0,0xbe03be03,0,0,0,0,0xbe03be03,0,0,0,0,0xbe03be03,
0x3e390000,0,0,0,0,0x3e390000,0,0,0,0,0x3e390000,0,0,0,0,0x3e390000,
0x3da83e25,0,0,0,0,0x3da83e25,0,0,0,0,0x3da83e25,0,0,0,0,0x3da83e25,
0x8000be39,0,0,0,0,0x8000be39,0,0,0,0,0x8000be39,0,0,0,0,0x8000be39,
0x3e03be03,0,0,0,0,0x3e03be03,0,0,0,0,0x3e03be03,0,0,0,0,0x3e03be03,
0xbdda3e16,0,0,0,0,0xbdda3e16,0,0,0,0,0xbdda3e16,0,0,0,0,0xbdda3e16,
0xbe37bce8,0,0,0,0,0xbe37bce8,0,0,0,0,0xbe37bce8,0,0,0,0,0xbe37bce8,
0x3e390000,0,0,0,0,0x3e390000,0,0,0,0,0x3e390000,0,0,0,0,0x3e390000,
0x3e033e03,0,0,0,0,0x3e033e03,0,0,0,0,0x3e033e03,0,0,0,0,0x3e033e03,
0xbd65be30,0,0,0,0,0xbd65be30,0,0,0,0,0xbd65be30,0,0,0,0,0xbd65be30,
0x3e03be03,0,0,0,0,0x3e03be03,0,0,0,0,0x3e03be03,0,0,0,0,0x3e03be03,
0x80003e39,0,0,0,0,0x80003e39,0,0,0,0,0x80003e39,0,0,0,0,0x80003e39,
0xbe033e03,0,0,0,0,0xbe033e03,0,0,0,0,0xbe033e03,0,0,0,0,0xbe033e03,
0x3e303d65,0,0,0,0,0x3e303d65,0,0,0,0,0x3e303d65,0,0,0,0,0x3e303d65,
0x3ce83e37,0,0,0,0,0x3ce83e37,0,0,0,0,0x3ce83e37,0,0,0,0,0x3ce83e37,
0xbe390000,0,0,0,0,0xbe390000,0,0,0,0,0xbe390000,0,0,0,0,0xbe390000,
0xbe03be03,0,0,0,0,0xbe03be03,0,0,0,0,0xbe03be03,0,0,0,0,0xbe03be03,
0xbe163dda,0,0,0,0,0xbe163dda,0,0,0,0,0xbe163dda,0,0,0,0,0xbe163dda,
0xbe25bda8,0,0,0,0,0xbe25bda8,0,0,0,0,0xbe25bda8,0,0,0,0,0xbe25bda8,
0xbe16bdda,0,0,0,0,0xbe16bdda,0,0,0,0,0xbe16bdda,0,0,0,0,0xbe16bdda,
0x3da8be25,0,0,0,0,0x3da8be25,0,0,0,0,0x3da8be25,0,0,0,0,0x3da8be25,
0x3e16bdda,0,0,0,0,0x3e16bdda,0,0,0,0,0x3e16bdda,0,0,0,0,0x3e16bdda,
0x3da83e25,0,0,0,0,0x3da83e25,0,0,0,0,0x3da83e25,0,0,0,0,0x3da83e25,
0x3e303d65,0,0,0,0,0x3e303d65,0,0,0,0,0x3e303d65,0,0,0,0,0x3e303d65,
0xbce83e37,0,0,0,0,0xbce83e37,0,0,0,0,0xbce83e37,0,0,0,0,0xbce83e37,
0xbe303d65,0,0,0,0,0xbe303d65,0,0,0,0,0xbe303d65,0,0,0,0,0xbe303d65,
0xbce8be37,0,0,0,0,0xbce8be37,0,0,0,0,0xbce8be37,0,0,0,0,0xbce8be37,
0xbe390000,0,0,0,0,0xbe390000,0,0,0,0,0xbe390000,0,0,0,0,0xbe390000,
0xbce8be37,0,0,0,0,0xbce8be37,0,0,0,0,0xbce8be37,0,0,0,0,0xbce8be37,
0x3e390000,0,0,0,0,0x3e390000,0,0,0,0,0x3e390000,0,0,0,0,0x3e390000,
0xbce83e37,0,0,0,0,0xbce83e37,0,0,0,0,0xbce83e37,0,0,0,0,0xbce83e37,
0x3e30bd65,0,0,0,0,0x3e30bd65,0,0,0,0,0x3e30bd65,0,0,0,0,0x3e30bd65,
0x3da83e25,0,0,0,0,0x3da83e25,0,0,0,0,0x3da83e25,0,0,0,0,0x3da83e25,
0xbe30bd65,0,0,0,0,0xbe30bd65,0,0,0,0,0xbe30bd65,0,0,0,0,0xbe30bd65,
0x3da8be25,0,0,0,0,0x3da8be25,0,0,0,0,0x3da8be25,0,0,0,0,0x3da8be25,
0xbe163dda,0,0,0,0,0xbe163dda,0,0,0,0,0xbe163dda,0,0,0,0,0xbe163dda,
0xbe03be03,0,0,0,0,0xbe03be03,0,0,0,0,0xbe03be03,0,0,0,0,0xbe03be03,
0x3e163dda,0,0,0,0,0x3e163dda,0,0,0,0,0x3e163dda,0,0,0,0,0x3e163dda,
0xbe033e03,0,0,0,0,0xbe033e03,0,0,0,0,0xbe033e03,0,0,0,0,0xbe033e03,
0x3ddabe16,0,0,0,0,0x3ddabe16,0,0,0,0,0x3ddabe16,0,0,0,0,0x3ddabe16,
0x3e253da8,0,0,0,0,0x3e253da8,0,0,0,0,0x3e253da8,0,0,0,0,0x3e253da8,
0xbddabe16,0,0,0,0,0xbddabe16,0,0,0,0,0xbddabe16,0,0,0,0,0xbddabe16,
0x3e25bda8,0,0,0,0,0x3e25bda8,0,0,0,0,0x3e25bda8,0,0,0,0,0x3e25bda8,
0xbd653e30,0,0,0,0,0xbd653e30,0,0,0,0,0xbd653e30,0,0,0,0,0xbd653e30,
0xbe37bce8,0,0,0,0,0xbe37bce8,0,0,0,0,0xbe37bce8,0,0,0,0,0xbe37bce8,
0x3d653e30,0,0,0,0,0x3d653e30,0,0,0,0,0x3d653e30,0,0,0,0,0x3d653e30,
0xbe373ce8,0,0,0,0,0xbe373ce8,0,0,0,0,0xbe373ce8,0,0,0,0,0xbe373ce8,
0x3d653e30,0,0,0,0,0x3d653e30,0,0,0,0,0x3d653e30,0,0,0,0,0x3d653e30,
0xbe37bce8,0,0,0,0,0xbe37bce8,0,0,0,0,0xbe37bce8,0,0,0,0,0xbe37bce8,
0xbe390000,0,0,0,0,0xbe390000,0,0,0,0,0xbe390000,0,0,0,0,0xbe390000,
0x3e03be03,0,0,0,0,0x3e03be03,0,0,0,0,0x3e03be03,0,0,0,0,0x3e03be03,
0x3ddabe16,0,0,0,0,0x3ddabe16,0,0,0,0,0x3ddabe16,0,0,0,0,0x3ddabe16,
0x3da83e25,0,0,0,0,0x3da83e25,0,0,0,0,0x3da83e25,0,0,0,0,0x3da83e25,
0x80003e39,0,0,0,0,0x80003e39,0,0,0,0,0x80003e39,0,0,0,0,0x80003e39,
0xbe03be03,0,0,0,0,0xbe03be03,0,0,0,0,0xbe03be03,0,0,0,0,0xbe03be03,
0xbe390000,0,0,0,0,0xbe390000,0,0,0,0,0xbe390000,0,0,0,0,0xbe390000,
0x3da8be25,0,0,0,0,0x3da8be25,0,0,0,0,0x3da8be25,0,0,0,0,0x3da8be25,
0x3e390000,0,0,0,0,0x3e390000,0,0,0,0,0x3e390000,0,0,0,0,0x3e390000,
0xbe033e03,0,0,0,0,0xbe033e03,0,0,0,0,0xbe033e03,0,0,0,0,0xbe033e03,
0x3dda3e16,0,0,0,0,0x3dda3e16,0,0,0,0,0x3dda3e16,0,0,0,0,0x3dda3e16,
0xbe373ce8,0,0,0,0,0xbe373ce8,0,0,0,0,0xbe373ce8,0,0,0,0,0xbe373ce8,
0x8000be39,0,0,0,0,0x8000be39,0,0,0,0,0x8000be39,0,0,0,0,0x8000be39,
0x3e033e03,0,0,0,0,0x3e033e03,0,0,0,0,0x3e033e03,0,0,0,0,0x3e033e03,
0x3d65be30,0,0,0,0,0x3d65be30,0,0,0,0,0x3d65be30,0,0,0,0,0x3d65be30,
0x3e033e03,0,0,0,0,0x3e033e03,0,0,0,0,0x3e033e03,0,0,0,0,0x3e033e03,
0xbe390000,0,0,0,0,0xbe390000,0,0,0,0,0xbe390000,0,0,0,0,0xbe390000,
0x3e03be03,0,0,0,0,0x3e03be03,0,0,0,0,0x3e03be03,0,0,0,0,0x3e03be03,
0xbe303d65,0,0,0,0,0xbe303d65,0,0,0,0,0xbe303d65,0,0,0,0,0xbe303d65,
0x3ce8be37,0,0,0,0,0x3ce8be37,0,0,0,0,0x3ce8be37,0,0,0,0,0x3ce8be37,
0x80003e39,0,0,0,0,0x80003e39,0,0,0,0,0x80003e39,0,0,0,0,0x80003e39,
0xbe03be03,0,0,0,0,0xbe03be03,0,0,0,0,0xbe03be03,0,0,0,0,0xbe03be03,
0x3e163dda,0,0,0,0,0x3e163dda,0,0,0,0,0x3e163dda,0,0,0,0,0x3e163dda,
0xbe253da8,0,0,0,0,0xbe253da8,0,0,0,0,0xbe253da8,0,0,0,0,0xbe253da8,
0x3e390000,0,0,0,0,0x3e390000,0,0,0,0,0x3e390000,0,0,0,0,0x3e390000,
0xbe033e03,0,0,0,0,0xbe033e03,0,0,0,0,0xbe033e03,0,0,0,0,0xbe033e03,
0x3d65be30,0,0,0,0,0x3d65be30,0,0,0,0,0x3d65be30,0,0,0,0,0x3d65be30,
0x3ce83e37,0,0,0,0,0x3ce83e37,0,0,0,0,0x3ce83e37,0,0,0,0,0x3ce83e37,
0x3e163dda,0,0,0,0,0x3e163dda,0,0,0,0,0x3e163dda,0,0,0,0,0x3e163dda,
0xbe25bda8,0,0,0,0,0xbe25bda8,0,0,0,0,0xbe25bda8,0,0,0,0,0xbe25bda8,
0xbddabe16,0,0,0,0,0xbddabe16,0,0,0,0,0xbddabe16,0,0,0,0,0xbddabe16,
0x3e253da8,0,0,0,0,0x3e253da8,0,0,0,0,0x3e253da8,0,0,0,0,0x3e253da8,
0x3e303d65,0,0,0,0,0x3e303d65,0,0,0,0,0x3e303d65,0,0,0,0,0x3e303d65,
0xbe37bce8,0,0,0,0,0xbe37bce8,0,0,0,0,0xbe37bce8,0,0,0,0,0xbe37bce8,
0xbe390000,0,0,0,0,0xbe390000,0,0,0,0,0xbe390000,0,0,0,0,0xbe390000,
0x3e25bda8,0,0,0,0,0x3e25bda8,0,0,0,0,0x3e25bda8,0,0,0,0,0x3e25bda8,
0x3e390000,0,0,0,0,0x3e390000,0,0,0,0,0x3e390000,0,0,0,0,0x3e390000,
0xbe373ce8,0,0,0,0,0xbe373ce8,0,0,0,0,0xbe373ce8,0,0,0,0,0xbe373ce8,
0xbdda3e16,0,0,0,0,0xbdda3e16,0,0,0,0,0xbdda3e16,0,0,0,0,0xbdda3e16,
0x3ce8be37,0,0,0,0,0x3ce8be37,0,0,0,0,0x3ce8be37,0,0,0,0,0x3ce8be37,
0x3e30bd65,0,0,0,0,0x3e30bd65,0,0,0,0,0x3e30bd65,0,0,0,0,0x3e30bd65,
0xbe253da8,0,0,0,0,0xbe253da8,0,0,0,0,0xbe253da8,0,0,0,0,0xbe253da8,
0x3d653e30,0,0,0,0,0x3d653e30,0,0,0,0,0x3d653e30,0,0,0,0,0x3d653e30,
0xbe03be03,0,0,0,0,0xbe03be03,0,0,0,0,0xbe03be03,0,0,0,0,0xbe03be03,
0x3e16bdda,0,0,0,0,0x3e16bdda,0,0,0,0,0x3e16bdda,0,0,0,0,0x3e16bdda,
0xbe033e03,0,0,0,0,0xbe033e03,0,0,0,0,0xbe033e03,0,0,0,0,0xbe033e03,
0x3e303d65,0,0,0,0,0x3e303d65,0,0,0,0,0x3e303d65,0,0,0,0,0x3e303d65,
0xbe373ce8,0,0,0,0,0xbe373ce8,0,0,0,0,0xbe373ce8,0,0,0,0,0xbe373ce8,
0x3ddabe16,0,0,0,0,0x3ddabe16,0,0,0,0,0x3ddabe16,0,0,0,0,0x3ddabe16,
0xbda83e25,0,0,0,0,0xbda83e25,0,0,0,0,0xbda83e25,0,0,0,0,0xbda83e25,
0x3e16bdda,0,0,0,0,0x3e16bdda,0,0,0,0,0x3e16bdda,0,0,0,0,0x3e16bdda,
0xbda83e25,0,0,0,0,0xbda83e25,0,0,0,0,0xbda83e25,0,0,0,0,0xbda83e25,
0x3d65be30,0,0,0,0,0x3d65be30,0,0,0,0,0x3d65be30,0,0,0,0,0x3d65be30,
0xbce83e37,0,0,0,0,0xbce83e37,0,0,0,0,0xbce83e37,0,0,0,0,0xbce83e37,
0,0,0xbe163dda,0,0,0,0,0xbe163dda,0,0,0xbe253da8,0,0,0,0,0xbe253da8,
0,0,0xbe303d65,0,0,0,0,0xbe303d65,0,0,0xbe373ce8,0,0,0,0,0xbe373ce8,
0,0,0xbd65be30,0,0,0,0,0xbd65be30,0,0,0x3ce8be37,0,0,0,0,0x3ce8be37,
0,0,0x3ddabe16,0,0,0,0,0x3ddabe16,0,0,0x3e25bda8,0,0,0,0,0x3e25bda8,
0,0,0xbe390000,0,0,0,0,0xbe390000,0,0,0xbe37bce8,0,0,0,0,0xbe37bce8,
0,0,0xbe30bd65,0,0,0,0,0xbe30bd65,0,0,0xbe25bda8,0,0,0,0,0xbe25bda8,
0,0,0x3e390000,0,0,0,0,0x3e390000,0,0,0x3e253da8,0,0,0,0,0x3e253da8,
0,0,0x3dda3e16,0,0,0,0,0x3dda3e16,0,0,0x3ce83e37,0,0,0,0,0x3ce83e37,
0,0,0xbe16bdda,0,0,0,0,0xbe16bdda,0,0,0xbe03be03,0,0,0,0,0xbe03be03,
0,0,0xbddabe16,0,0,0,0,0xbddabe16,0,0,0xbda8be25,0,0,0,0,0xbda8be25,
0,0,0xbd653e30,0,0,0,0,0xbd653e30,0,0,0xbe033e03,0,0,0,0,0xbe033e03,
0,0,0xbe303d65,0,0,0,0,0xbe303d65,0,0,0xbe37bce8,0,0,0,0,0xbe37bce8,
0,0,0xbd65be30,0,0,0,0,0xbd65be30,0,0,0xbce8be37,0,0,0,0,0xbce8be37,
0,0,0,0,0,0,0,0,0,0,0,0,0,0,0,0,
0,0,0xbe16bdda,0,0,0,0,0xbe16bdda,0,0,0xbda8be25,0,0,0,0,0xbda8be25,
0,0,0,0,0,0,0,0,0,0,0,0,0,0,0,0,
0,0,0x3e390000,0,0,0,0,0x3e390000,0,0,0x3e033e03,0,0,0,0,0x3e033e03,
0,0,0x80003e39,0,0,0,0,0x80003e39,0,0,0xbe033e03,0,0,0,0,0xbe033e03,
0,0,0xbd653e30,0,0,0,0,0xbd653e30,0,0,0xbe373ce8,0,0,0,0,0xbe373ce8,
0,0,0xbddabe16,0,0,0,0,0xbddabe16,0,0,0x3da8be25,0,0,0,0,0x3da8be25,
0,0,0xbe390000,0,0,0,0,0xbe390000,0,0,0xbe03be03,0,0,0,0,0xbe03be03,
0,0,0x8000be39,0,0,0,0,0x8000be39,0,0,0x3e03be03,0,0,0,0,0x3e03be03,
0,0,0x3e390000,0,0,0,0,0x3e390000,0,0,0x3da83e25,0,0,0,0,0x3da83e25,
0,0,0xbdda3e16,0,0,0,0,0xbdda3e16,0,0,0xbe37bce8,0,0,0,0,0xbe37bce8,
0,0,0x3e390000,0,0,0,0,0x3e390000,0,0,0x3e033e03,0,0,0,0,0x3e033e03,
0,0,0x80003e39,0,0,0,0,0x80003e39,0,0,0xbe033e03,0,0,0,0,0xbe033e03,
0,0,0xbd65be30,0,0,0,0,0xbd65be30,0,0,0x3e03be03,0,0,0,0,0x3e03be03,
0,0,0x3e303d65,0,0,0,0,0x3e303d65,0,0,0x3ce83e37,0,0,0,0,0x3ce83e37,
0,0,0xbe390000,0,0,0,0,0xbe390000,0,0,0xbe03be03,0,0,0,0,0xbe03be03,
0,0,0,0,0,0,0,0,0,0,0,0,0,0,0,0,
0,0,0xbe163dda,0,0,0,0,0xbe163dda,0,0,0xbe25bda8,0,0,0,0,0xbe25bda8,
0,0,0,0,0,0,0,0,0,0,0,0,0,0,0,0,
0,0,0xbe16bdda,0,0,0,0,0xbe16bdda,0,0,0x3da8be25,0,0,0,0,0x3da8be25,
0,0,0x3e303d65,0,0,0,0,0x3e303d65,0,0,0xbce83e37,0,0,0,0,0xbce83e37,
0,0,0x3e16bdda,0,0,0,0,0x3e16bdda,0,0,0x3da83e25,0,0,0,0,0x3da83e25,
0,0,0xbe303d65,0,0,0,0,0xbe303d65,0,0,0xbce8be37,0,0,0,0,0xbce8be37,
0,0,0xbe390000,0,0,0,0,0xbe390000,0,0,0xbce8be37,0,0,0,0,0xbce8be37,
0,0,0x3e30bd65,0,0,0,0,0x3e30bd65,0,0,0x3da83e25,0,0,0,0,0x3da83e25,
0,0,0x3e390000,0,0,0,0,0x3e390000,0,0,0xbce83e37,0,0,0,0,0xbce83e37,
0,0,0xbe30bd65,0,0,0,0,0xbe30bd65,0,0,0x3da8be25,0,0,0,0,0x3da8be25,
0,0,0xbe163dda,0,0,0,0,0xbe163dda,0,0,0xbe03be03,0,0,0,0,0xbe03be03,
0,0,0x3ddabe16,0,0,0,0,0x3ddabe16,0,0,0x3e253da8,0,0,0,0,0x3e253da8,
0,0,0x3e163dda,0,0,0,0,0x3e163dda,0,0,0xbe033e03,0,0,0,0,0xbe033e03,
0,0,0xbddabe16,0,0,0,0,0xbddabe16,0,0,0x3e25bda8,0,0,0,0,0x3e25bda8,
0,0,0xbd653e30,0,0,0,0,0xbd653e30,0,0,0xbe37bce8,0,0,0,0,0xbe37bce8,
0,0,0,0,0,0,0,0,0,0,0,0,0,0,0,0,
0,0,0x3d653e30,0,0,0,0,0x3d653e30,0,0,0xbe373ce8,0,0,0,0,0xbe373ce8,
0,0,0,0,0,0,0,0,0,0,0,0,0,0,0,0,
0,0,0x3d653e30,0,0,0,0,0x3d653e30,0,0,0xbe37bce8,0,0,0,0,0xbe37bce8,
0,0,0x3ddabe16,0,0,0,0,0x3ddabe16,0,0,0x3da83e25,0,0,0,0,0x3da83e25,
0,0,0xbe390000,0,0,0,0,0xbe390000,0,0,0x3e03be03,0,0,0,0,0x3e03be03,
0,0,0x80003e39,0,0,0,0,0x80003e39,0,0,0xbe03be03,0,0,0,0,0xbe03be03,
0,0,0xbe390000,0,0,0,0,0xbe390000,0,0,0x3da8be25,0,0,0,0,0x3da8be25,
0,0,0x3dda3e16,0,0,0,0,0x3dda3e16,0,0,0xbe373ce8,0,0,0,0,0xbe373ce8,
0,0,0x3e390000,0,0,0,0,0x3e390000,0,0,0xbe033e03,0,0,0,0,0xbe033e03,
0,0,0x8000be39,0,0,0,0,0x8000be39,0,0,0x3e033e03,0,0,0,0,0x3e033e03,
0,0,0x3d65be30,0,0,0,0,0x3d65be30,0,0,0x3e033e03,0,0,0,0,0x3e033e03,
0,0,0xbe303d65,0,0,0,0,0xbe303d65,0,0,0x3ce8be37,0,0,0,0,0x3ce8be37,
0,0,0xbe390000,0,0,0,0,0xbe390000,0,0,0x3e03be03,0,0,0,0,0x3e03be03,
0,0,0x80003e39,0,0,0,0,0x80003e39,0,0,0xbe03be03,0,0,0,0,0xbe03be03,
0,0,0x3e163dda,0,0,0,0,0x3e163dda,0,0,0xbe253da8,0,0,0,0,0xbe253da8,
0,0,0,0,0,0,0,0,0,0,0,0,0,0,0,0,
0,0,0x3e390000,0,0,0,0,0x3e390000,0,0,0xbe033e03,0,0,0,0,0xbe033e03,
0,0,0,0,0,0,0,0,0,0,0,0,0,0,0,0,
0,0,0x3d65be30,0,0,0,0,0x3d65be30,0,0,0x3ce83e37,0,0,0,0,0x3ce83e37,
0,0,0xbddabe16,0,0,0,0,0xbddabe16,0,0,0x3e253da8,0,0,0,0,0x3e253da8,
0,0,0x3e163dda,0,0,0,0,0x3e163dda,0,0,0xbe25bda8,0,0,0,0,0xbe25bda8,
0,0,0x3e303d65,0,0,0,0,0x3e303d65,0,0,0xbe37bce8,0,0,0,0,0xbe37bce8,
0,0,0xbe390000,0,0,0,0,0xbe390000,0,0,0x3e25bda8,0,0,0,0,0x3e25bda8,
0,0,0xbdda3e16,0,0,0,0,0xbdda3e16,0,0,0x3ce8be37,0,0,0,0,0x3ce8be37,
0,0,0x3e390000,0,0,0,0,0x3e390000,0,0,0xbe373ce8,0,0,0,0,0xbe373ce8,
0,0,0x3e30bd65,0,0,0,0,0x3e30bd65,0,0,0xbe253da8,0,0,0,0,0xbe253da8,
0,0,0x3d653e30,0,0,0,0,0x3d653e30,0,0,0xbe03be03,0,0,0,0,0xbe03be03,
0,0,0x3e303d65,0,0,0,0,0x3e303d65,0,0,0xbe373ce8,0,0,0,0,0xbe373ce8,
0,0,0x3e16bdda,0,0,0,0,0x3e16bdda,0,0,0xbe033e03,0,0,0,0,0xbe033e03,
0,0,0x3ddabe16,0,0,0,0,0x3ddabe16,0,0,0xbda83e25,0,0,0,0,0xbda83e25,
0,0,0x3e16bdda,0,0,0,0,0x3e16bdda,0,0,0xbda83e25,0,0,0,0,0xbda83e25,
0,0,0,0,0,0,0,0,0,0,0,0,0,0,0,0,
0,0,0x3d65be30,0,0,0,0,0x3d65be30,0,0,0xbce83e37,0,0,0,0,0xbce83e37,
0,0,0,0,0,0,0,0,0,0,0,0,0,0,0,0,
};
constexpr unsigned long long COS_PK0 = 0x3f903f9a3fa03fa2ull;
constexpr unsigned long long COS_PK1 = 0x3f133f3e3f653f83ull;
constexpr unsigned long long COS_PK2 = 0x3e4b3ec8ull;

__device__ __forceinline__ void wgmma_ss_n80_z(float (&d)[40], uint64_t da, uint64_t db) {
  asm volatile("{\n.reg .pred p;\nsetp.ne.b32 p, 0, 0;\nwgmma.mma_async.sync.aligned.m64n80k16.f32.bf16.bf16 {%0,%1,%2,%3,%4,%5,%6,%7,%8,%9,%10,%11,%12,%13,%14,%15,%16,%17,%18,%19,%20,%21,%22,%23,%24,%25,%26,%27,%28,%29,%30,%31,%32,%33,%34,%35,%36,%37,%38,%39}, %40, %41, p, 1, 1, 1, 0;\n}\n"
    : "+f"(d[0]), "+f"(d[1]), "+f"(d[2]), "+f"(d[3]), "+f"(d[4]), "+f"(d[5]), "+f"(d[6]), "+f"(d[7]), "+f"(d[8]), "+f"(d[9]), "+f"(d[10]), "+f"(d[11]), "+f"(d[12]), "+f"(d[13]), "+f"(d[14]), "+f"(d[15]), "+f"(d[16]), "+f"(d[17]), "+f"(d[18]), "+f"(d[19]), "+f"(d[20]), "+f"(d[21]), "+f"(d[22]), "+f"(d[23]), "+f"(d[24]), "+f"(d[25]), "+f"(d[26]), "+f"(d[27]), "+f"(d[28]), "+f"(d[29]), "+f"(d[30]), "+f"(d[31]), "+f"(d[32]), "+f"(d[33]), "+f"(d[34]), "+f"(d[35]), "+f"(d[36]), "+f"(d[37]), "+f"(d[38]), "+f"(d[39])
    : "l"(da), "l"(db));
}
__device__ __forceinline__ void wgmma_ss_n80_a(float (&d)[40], uint64_t da, uint64_t db) {
  asm volatile("{\n.reg .pred p;\nsetp.ne.b32 p, 1, 0;\nwgmma.mma_async.sync.aligned.m64n80k16.f32.bf16.bf16 {%0,%1,%2,%3,%4,%5,%6,%7,%8,%9,%10,%11,%12,%13,%14,%15,%16,%17,%18,%19,%20,%21,%22,%23,%24,%25,%26,%27,%28,%29,%30,%31,%32,%33,%34,%35,%36,%37,%38,%39}, %40, %41, p, 1, 1, 1, 0;\n}\n"
    : "+f"(d[0]), "+f"(d[1]), "+f"(d[2]), "+f"(d[3]), "+f"(d[4]), "+f"(d[5]), "+f"(d[6]), "+f"(d[7]), "+f"(d[8]), "+f"(d[9]), "+f"(d[10]), "+f"(d[11]), "+f"(d[12]), "+f"(d[13]), "+f"(d[14]), "+f"(d[15]), "+f"(d[16]), "+f"(d[17]), "+f"(d[18]), "+f"(d[19]), "+f"(d[20]), "+f"(d[21]), "+f"(d[22]), "+f"(d[23]), "+f"(d[24]), "+f"(d[25]), "+f"(d[26]), "+f"(d[27]), "+f"(d[28]), "+f"(d[29]), "+f"(d[30]), "+f"(d[31]), "+f"(d[32]), "+f"(d[33]), "+f"(d[34]), "+f"(d[35]), "+f"(d[36]), "+f"(d[37]), "+f"(d[38]), "+f"(d[39])
    : "l"(da), "l"(db));
}

__device__ __forceinline__ void wgmma_rs_n40_z(float (&d)[20], uint32_t a0, uint32_t a1, uint32_t a2, uint32_t a3, uint64_t db) {
  asm volatile("{\n.reg .pred p;\nsetp.ne.b32 p, 0, 0;\nwgmma.mma_async.sync.aligned.m64n40k16.f32.bf16.bf16 {%0,%1,%2,%3,%4,%5,%6,%7,%8,%9,%10,%11,%12,%13,%14,%15,%16,%17,%18,%19}, {%20,%21,%22,%23}, %24, p, 1, 1, 0;\n}\n"
    : "+f"(d[0]), "+f"(d[1]), "+f"(d[2]), "+f"(d[3]), "+f"(d[4]), "+f"(d[5]), "+f"(d[6]), "+f"(d[7]), "+f"(d[8]), "+f"(d[9]), "+f"(d[10]), "+f"(d[11]), "+f"(d[12]), "+f"(d[13]), "+f"(d[14]), "+f"(d[15]), "+f"(d[16]), "+f"(d[17]), "+f"(d[18]), "+f"(d[19])
    : "r"(a0), "r"(a1), "r"(a2), "r"(a3), "l"(db));
}
__device__ __forceinline__ void wgmma_rs_n40_a(float (&d)[20], uint32_t a0, uint32_t a1, uint32_t a2, uint32_t a3, uint64_t db) {
  asm volatile("{\n.reg .pred p;\nsetp.ne.b32 p, 1, 0;\nwgmma.mma_async.sync.aligned.m64n40k16.f32.bf16.bf16 {%0,%1,%2,%3,%4,%5,%6,%7,%8,%9,%10,%11,%12,%13,%14,%15,%16,%17,%18,%19}, {%20,%21,%22,%23}, %24, p, 1, 1, 0;\n}\n"
    : "+f"(d[0]), "+f"(d[1]), "+f"(d[2]), "+f"(d[3]), "+f"(d[4]), "+f"(d[5]), "+f"(d[6]), "+f"(d[7]), "+f"(d[8]), "+f"(d[9]), "+f"(d[10]), "+f"(d[11]), "+f"(d[12]), "+f"(d[13]), "+f"(d[14]), "+f"(d[15]), "+f"(d[16]), "+f"(d[17]), "+f"(d[18]), "+f"(d[19])
    : "r"(a0), "r"(a1), "r"(a2), "r"(a3), "l"(db));
}

__device__ __forceinline__ void wgmma_rs_n128_z(float (&d)[64], uint32_t a0, uint32_t a1, uint32_t a2, uint32_t a3, uint64_t db) {
  asm volatile("{\n.reg .pred p;\nsetp.ne.b32 p, 0, 0;\nwgmma.mma_async.sync.aligned.m64n128k16.f32.bf16.bf16 {%0,%1,%2,%3,%4,%5,%6,%7,%8,%9,%10,%11,%12,%13,%14,%15,%16,%17,%18,%19,%20,%21,%22,%23,%24,%25,%26,%27,%28,%29,%30,%31,%32,%33,%34,%35,%36,%37,%38,%39,%40,%41,%42,%43,%44,%45,%46,%47,%48,%49,%50,%51,%52,%53,%54,%55,%56,%57,%58,%59,%60,%61,%62,%63}, {%64,%65,%66,%67}, %68, p, 1, 1, 1;\n}\n"
    : "+f"(d[0]), "+f"(d[1]), "+f"(d[2]), "+f"(d[3]), "+f"(d[4]), "+f"(d[5]), "+f"(d[6]), "+f"(d[7]), "+f"(d[8]), "+f"(d[9]), "+f"(d[10]), "+f"(d[11]), "+f"(d[12]), "+f"(d[13]), "+f"(d[14]), "+f"(d[15]), "+f"(d[16]), "+f"(d[17]), "+f"(d[18]), "+f"(d[19]), "+f"(d[20]), "+f"(d[21]), "+f"(d[22]), "+f"(d[23]), "+f"(d[24]), "+f"(d[25]), "+f"(d[26]), "+f"(d[27]), "+f"(d[28]), "+f"(d[29]), "+f"(d[30]), "+f"(d[31]), "+f"(d[32]), "+f"(d[33]), "+f"(d[34]), "+f"(d[35]), "+f"(d[36]), "+f"(d[37]), "+f"(d[38]), "+f"(d[39]), "+f"(d[40]), "+f"(d[41]), "+f"(d[42]), "+f"(d[43]), "+f"(d[44]), "+f"(d[45]), "+f"(d[46]), "+f"(d[47]), "+f"(d[48]), "+f"(d[49]), "+f"(d[50]), "+f"(d[51]), "+f"(d[52]), "+f"(d[53]), "+f"(d[54]), "+f"(d[55]), "+f"(d[56]), "+f"(d[57]), "+f"(d[58]), "+f"(d[59]), "+f"(d[60]), "+f"(d[61]), "+f"(d[62]), "+f"(d[63])
    : "r"(a0), "r"(a1), "r"(a2), "r"(a3), "l"(db));
}
__device__ __forceinline__ void wgmma_rs_n128_a(float (&d)[64], uint32_t a0, uint32_t a1, uint32_t a2, uint32_t a3, uint64_t db) {
  asm volatile("{\n.reg .pred p;\nsetp.ne.b32 p, 1, 0;\nwgmma.mma_async.sync.aligned.m64n128k16.f32.bf16.bf16 {%0,%1,%2,%3,%4,%5,%6,%7,%8,%9,%10,%11,%12,%13,%14,%15,%16,%17,%18,%19,%20,%21,%22,%23,%24,%25,%26,%27,%28,%29,%30,%31,%32,%33,%34,%35,%36,%37,%38,%39,%40,%41,%42,%43,%44,%45,%46,%47,%48,%49,%50,%51,%52,%53,%54,%55,%56,%57,%58,%59,%60,%61,%62,%63}, {%64,%65,%66,%67}, %68, p, 1, 1, 1;\n}\n"
    : "+f"(d[0]), "+f"(d[1]), "+f"(d[2]), "+f"(d[3]), "+f"(d[4]), "+f"(d[5]), "+f"(d[6]), "+f"(d[7]), "+f"(d[8]), "+f"(d[9]), "+f"(d[10]), "+f"(d[11]), "+f"(d[12]), "+f"(d[13]), "+f"(d[14]), "+f"(d[15]), "+f"(d[16]), "+f"(d[17]), "+f"(d[18]), "+f"(d[19]), "+f"(d[20]), "+f"(d[21]), "+f"(d[22]), "+f"(d[23]), "+f"(d[24]), "+f"(d[25]), "+f"(d[26]), "+f"(d[27]), "+f"(d[28]), "+f"(d[29]), "+f"(d[30]), "+f"(d[31]), "+f"(d[32]), "+f"(d[33]), "+f"(d[34]), "+f"(d[35]), "+f"(d[36]), "+f"(d[37]), "+f"(d[38]), "+f"(d[39]), "+f"(d[40]), "+f"(d[41]), "+f"(d[42]), "+f"(d[43]), "+f"(d[44]), "+f"(d[45]), "+f"(d[46]), "+f"(d[47]), "+f"(d[48]), "+f"(d[49]), "+f"(d[50]), "+f"(d[51]), "+f"(d[52]), "+f"(d[53]), "+f"(d[54]), "+f"(d[55]), "+f"(d[56]), "+f"(d[57]), "+f"(d[58]), "+f"(d[59]), "+f"(d[60]), "+f"(d[61]), "+f"(d[62]), "+f"(d[63])
    : "r"(a0), "r"(a1), "r"(a2), "r"(a3), "l"(db));
}

__device__ __forceinline__ void wgmma_rs_n32_z(float (&d)[16], uint32_t a0, uint32_t a1, uint32_t a2, uint32_t a3, uint64_t db) {
  asm volatile("{\n.reg .pred p;\nsetp.ne.b32 p, 0, 0;\nwgmma.mma_async.sync.aligned.m64n32k16.f32.bf16.bf16 {%0,%1,%2,%3,%4,%5,%6,%7,%8,%9,%10,%11,%12,%13,%14,%15}, {%16,%17,%18,%19}, %20, p, 1, 1, 0;\n}\n"
    : "+f"(d[0]), "+f"(d[1]), "+f"(d[2]), "+f"(d[3]), "+f"(d[4]), "+f"(d[5]), "+f"(d[6]), "+f"(d[7]), "+f"(d[8]), "+f"(d[9]), "+f"(d[10]), "+f"(d[11]), "+f"(d[12]), "+f"(d[13]), "+f"(d[14]), "+f"(d[15])
    : "r"(a0), "r"(a1), "r"(a2), "r"(a3), "l"(db));
}
__device__ __forceinline__ void wgmma_rs_n32_a(float (&d)[16], uint32_t a0, uint32_t a1, uint32_t a2, uint32_t a3, uint64_t db) {
  asm volatile("{\n.reg .pred p;\nsetp.ne.b32 p, 1, 0;\nwgmma.mma_async.sync.aligned.m64n32k16.f32.bf16.bf16 {%0,%1,%2,%3,%4,%5,%6,%7,%8,%9,%10,%11,%12,%13,%14,%15}, {%16,%17,%18,%19}, %20, p, 1, 1, 0;\n}\n"
    : "+f"(d[0]), "+f"(d[1]), "+f"(d[2]), "+f"(d[3]), "+f"(d[4]), "+f"(d[5]), "+f"(d[6]), "+f"(d[7]), "+f"(d[8]), "+f"(d[9]), "+f"(d[10]), "+f"(d[11]), "+f"(d[12]), "+f"(d[13]), "+f"(d[14]), "+f"(d[15])
    : "r"(a0), "r"(a1), "r"(a2), "r"(a3), "l"(db));
}

__device__ __forceinline__ void wgmma_rs_n64_z(float (&d)[32], uint32_t a0, uint32_t a1, uint32_t a2, uint32_t a3, uint64_t db) {
  asm volatile("{\n.reg .pred p;\nsetp.ne.b32 p, 0, 0;\nwgmma.mma_async.sync.aligned.m64n64k16.f32.bf16.bf16 {%0,%1,%2,%3,%4,%5,%6,%7,%8,%9,%10,%11,%12,%13,%14,%15,%16,%17,%18,%19,%20,%21,%22,%23,%24,%25,%26,%27,%28,%29,%30,%31}, {%32,%33,%34,%35}, %36, p, 1, 1, 0;\n}\n"
    : "+f"(d[0]), "+f"(d[1]), "+f"(d[2]), "+f"(d[3]), "+f"(d[4]), "+f"(d[5]), "+f"(d[6]), "+f"(d[7]), "+f"(d[8]), "+f"(d[9]), "+f"(d[10]), "+f"(d[11]), "+f"(d[12]), "+f"(d[13]), "+f"(d[14]), "+f"(d[15]), "+f"(d[16]), "+f"(d[17]), "+f"(d[18]), "+f"(d[19]), "+f"(d[20]), "+f"(d[21]), "+f"(d[22]), "+f"(d[23]), "+f"(d[24]), "+f"(d[25]), "+f"(d[26]), "+f"(d[27]), "+f"(d[28]), "+f"(d[29]), "+f"(d[30]), "+f"(d[31])
    : "r"(a0), "r"(a1), "r"(a2), "r"(a3), "l"(db));
}
__device__ __forceinline__ void wgmma_rs_n64_a(float (&d)[32], uint32_t a0, uint32_t a1, uint32_t a2, uint32_t a3, uint64_t db) {
  asm volatile("{\n.reg .pred p;\nsetp.ne.b32 p, 1, 0;\nwgmma.mma_async.sync.aligned.m64n64k16.f32.bf16.bf16 {%0,%1,%2,%3,%4,%5,%6,%7,%8,%9,%10,%11,%12,%13,%14,%15,%16,%17,%18,%19,%20,%21,%22,%23,%24,%25,%26,%27,%28,%29,%30,%31}, {%32,%33,%34,%35}, %36, p, 1, 1, 0;\n}\n"
    : "+f"(d[0]), "+f"(d[1]), "+f"(d[2]), "+f"(d[3]), "+f"(d[4]), "+f"(d[5]), "+f"(d[6]), "+f"(d[7]), "+f"(d[8]), "+f"(d[9]), "+f"(d[10]), "+f"(d[11]), "+f"(d[12]), "+f"(d[13]), "+f"(d[14]), "+f"(d[15]), "+f"(d[16]), "+f"(d[17]), "+f"(d[18]), "+f"(d[19]), "+f"(d[20]), "+f"(d[21]), "+f"(d[22]), "+f"(d[23]), "+f"(d[24]), "+f"(d[25]), "+f"(d[26]), "+f"(d[27]), "+f"(d[28]), "+f"(d[29]), "+f"(d[30]), "+f"(d[31])
    : "r"(a0), "r"(a1), "r"(a2), "r"(a3), "l"(db));
}

__device__ __forceinline__ void wgmma_ss_n32_z(float (&d)[16], uint64_t da, uint64_t db) {
  asm volatile("{\n.reg .pred p;\nsetp.ne.b32 p, 0, 0;\nwgmma.mma_async.sync.aligned.m64n32k16.f32.bf16.bf16 {%0,%1,%2,%3,%4,%5,%6,%7,%8,%9,%10,%11,%12,%13,%14,%15}, %16, %17, p, 1, 1, 1, 0;\n}\n"
    : "+f"(d[0]), "+f"(d[1]), "+f"(d[2]), "+f"(d[3]), "+f"(d[4]), "+f"(d[5]), "+f"(d[6]), "+f"(d[7]), "+f"(d[8]), "+f"(d[9]), "+f"(d[10]), "+f"(d[11]), "+f"(d[12]), "+f"(d[13]), "+f"(d[14]), "+f"(d[15])
    : "l"(da), "l"(db));
}
__device__ __forceinline__ void wgmma_ss_n32_a(float (&d)[16], uint64_t da, uint64_t db) {
  asm volatile("{\n.reg .pred p;\nsetp.ne.b32 p, 1, 0;\nwgmma.mma_async.sync.aligned.m64n32k16.f32.bf16.bf16 {%0,%1,%2,%3,%4,%5,%6,%7,%8,%9,%10,%11,%12,%13,%14,%15}, %16, %17, p, 1, 1, 1, 0;\n}\n"
    : "+f"(d[0]), "+f"(d[1]), "+f"(d[2]), "+f"(d[3]), "+f"(d[4]), "+f"(d[5]), "+f"(d[6]), "+f"(d[7]), "+f"(d[8]), "+f"(d[9]), "+f"(d[10]), "+f"(d[11]), "+f"(d[12]), "+f"(d[13]), "+f"(d[14]), "+f"(d[15])
    : "l"(da), "l"(db));
}

__device__ __forceinline__ void wgmma_ss_n40_z(float (&d)[20], uint64_t da, uint64_t db) {
  asm volatile("{\n.reg .pred p;\nsetp.ne.b32 p, 0, 0;\nwgmma.mma_async.sync.aligned.m64n40k16.f32.bf16.bf16 {%0,%1,%2,%3,%4,%5,%6,%7,%8,%9,%10,%11,%12,%13,%14,%15,%16,%17,%18,%19}, %20, %21, p, 1, 1, 1, 0;\n}\n"
    : "+f"(d[0]), "+f"(d[1]), "+f"(d[2]), "+f"(d[3]), "+f"(d[4]), "+f"(d[5]), "+f"(d[6]), "+f"(d[7]), "+f"(d[8]), "+f"(d[9]), "+f"(d[10]), "+f"(d[11]), "+f"(d[12]), "+f"(d[13]), "+f"(d[14]), "+f"(d[15]), "+f"(d[16]), "+f"(d[17]), "+f"(d[18]), "+f"(d[19])
    : "l"(da), "l"(db));
}
__device__ __forceinline__ void wgmma_ss_n40_a(float (&d)[20], uint64_t da, uint64_t db) {
  asm volatile("{\n.reg .pred p;\nsetp.ne.b32 p, 1, 0;\nwgmma.mma_async.sync.aligned.m64n40k16.f32.bf16.bf16 {%0,%1,%2,%3,%4,%5,%6,%7,%8,%9,%10,%11,%12,%13,%14,%15,%16,%17,%18,%19}, %20, %21, p, 1, 1, 1, 0;\n}\n"
    : "+f"(d[0]), "+f"(d[1]), "+f"(d[2]), "+f"(d[3]), "+f"(d[4]), "+f"(d[5]), "+f"(d[6]), "+f"(d[7]), "+f"(d[8]), "+f"(d[9]), "+f"(d[10]), "+f"(d[11]), "+f"(d[12]), "+f"(d[13]), "+f"(d[14]), "+f"(d[15]), "+f"(d[16]), "+f"(d[17]), "+f"(d[18]), "+f"(d[19])
    : "l"(da), "l"(db));
}

constexpr int NSM = 132, NH = 66;
constexpr int S0 = 0, S1 = 51200, S2 = 102400;
constexpr int C1 = 153600, C3 = C1, RG = C1 + 18432;
constexpr int WP = RG, TBL = RG + 28672, WS2 = RG + 30720;
constexpr int BARS = RG + 49152;
__host__ __device__ constexpr int wst_off(int i) { return i < 12 ? S2 + i * 4096 : WS2 + (i - 12) * 4096; }
constexpr int NBAR = 280;
constexpr int REL = BARS + NBAR * 8;
constexpr int SMEM_BYTES = REL + 16;
constexpr int B_XF = 0, B_CF1 = 15, B_CF3 = 16, B_WF = 17  , B_P1D = 18, B_WFREE = 20, B_REL = 21, B_ROLE = 22, B_X1 = 23, B_SIG = 24;
constexpr int B_RF = 32, B_RE = 46, B_YF = 60, B_WRD = 75, B_SFREE = 89, B_WCH = 131, B_RDY = 136, B_WE = 205, B_WL = 217, B_FIN = 229, B_TOK = 232;
constexpr int R_P2 = 15, R_P3 = 57;
constexpr int CNT_P1 = 0, CNT_P2 = 4, CNT_W = 8, CNT_RANK = 9, NCLS = 10, CNT_DONE = 0, CNT_REL = 1, NCNT = 2;
constexpr int SIG_W = 0, SIG_P1 = 1, SIG_P2 = 4;
#define PROBES 1
#define WB 100
#define PACE 0
#define PACE_SLACK 300
#define SWIN 3
#define X1AT 10
#define WARMUP 0
#define YPACE 0
#define POLL3 0
#define XPF 0
#define PSLEEP 0
#define TRICKLE
#define T1MASK 0x3e00
#define T2MASK 0x1f00
#define Y0AT 1
#define Y3FROM 1
#define EM58 2
#define TOKD 1
#define TOKM 6
#define WWIN 4
#define WHOLD 99
#define LAZYC 1
#define P3MAP 0
#define YWIN 1
#define X1BOX 0
#define X2BOX 5

__device__ uint4 g_scr[(14 << 21) / 16];
__device__ uint4 g_wf[200 * 72 * 32];
__device__ unsigned g_cnt[NCNT * 32];
__device__ __forceinline__ int slot_line(int chunk, int pg, int cls) {
    return (pg & 1) << 6 | (pg >> 1) << 9 | (chunk & 1) << 10 | (chunk >> 1) << 12 | ((pg ^ (pg >> 1) ^ chunk ^ (chunk >> 1) ^ cls) & 1) << 5;
}
__device__ __forceinline__ int phi_line(int phi, uint32_t rel) {
    return (phi >> 4) << 14 | (phi & 3) << 7 | ((phi >> 2) & 1) << 11 | ((phi >> 3) & 1) << 13 | ((rel >> (phi >> 4)) & 1) << 5;
}
__device__ __forceinline__ int extra_mask(int rk) { return rk < 58 ? 0 : rk < 60 ? EM58 : rk < 62 ? 1 : rk < 64 ? (EM58 == 2 ? 4 : 2) : (EM58 == 8 ? 4 : 8); }
__device__ __forceinline__ int wslot(int pc) {
    return (int)((0x576476503421ull >> (4 * pc)) & 3) * 12288 + (((0x576476503421ull >> (4 * pc)) & 4) ? S0 : RG);
}
__device__ __forceinline__ int xslot(int n) { return ((n & 4) ? S2 : RG) + ((n + 1) & 3) * 12288; }
__device__ __forceinline__ int extra_phi(int rk) { return 198 + (rk & 1); }
__host__ __device__ constexpr int quad_off(int Q) { return (Q >> 2) * 4096 + (Q & 3) * 512; }

#define PROF(k)
#define PROFW(k)
#define prof_dump()
struct Maps { CUtensorMap w, x34, x6, x28, wst, f16, f8, y4, y2; };
struct Ptrs { char* scr; const char* wf; const void* tab1; const void* tab3; unsigned* cnt; };

__device__ __forceinline__ uint32_t smem_u32(const void* p) { return (uint32_t)__cvta_generic_to_shared(p); }
__device__ __forceinline__ void mbar_wait(uint32_t bar) {
    uint32_t ok, it = 0;
    do {
        asm volatile("{\n.reg .pred p;\nmbarrier.try_wait.parity.shared::cta.b64 p, [%1], 0;\nselp.u32 %0, 1, 0, p;\n}" : "=r"(ok) : "r"(bar) : "memory");
        if (++it > (1u << 22)) break;
    } while (!ok);
}
__device__ __forceinline__ bool mbar_test(uint32_t bar) {
    uint32_t ok;
    asm volatile("{\n.reg .pred p;\nmbarrier.test_wait.parity.shared::cta.b64 p, [%1], 0;\nselp.u32 %0, 1, 0, p;\n}" : "=r"(ok) : "r"(bar) : "memory");
    return ok;
}
__device__ __forceinline__ void fence_async() { asm volatile("fence.proxy.async;" ::: "memory"); }
__device__ __forceinline__ void fence_async_smem() { asm volatile("fence.proxy.async.shared::cta;" ::: "memory"); }
#define ELECT "{\n.reg .pred p;\nelect.sync _|p, 0xffffffff;\n@p "
__device__ __forceinline__ void e_arrive(uint32_t bar) { asm volatile(ELECT "mbarrier.arrive.shared::cta.b64 _, [%0];\n}" :: "r"(bar) : "memory"); }
__device__ __forceinline__ void e_expect(uint32_t bar, uint32_t bytes) { asm volatile(ELECT "mbarrier.arrive.expect_tx.shared::cta.b64 _, [%0], %1;\n}" :: "r"(bar), "r"(bytes) : "memory"); }
__device__ __forceinline__ void e_g2s(uint32_t dst, const void* src, uint32_t bytes, uint32_t bar) {
    asm volatile(ELECT "cp.async.bulk.shared::cluster.global.mbarrier::complete_tx::bytes [%0], [%1], %2, [%3];\n}" :: "r"(dst), "l"(src), "r"(bytes), "r"(bar) : "memory");
}
__device__ __forceinline__ void e_s2g(void* dst, uint32_t src, uint32_t bytes) {
    asm volatile(ELECT "cp.async.bulk.global.shared::cta.bulk_group [%0], [%1], %2;\n}" :: "l"(dst), "r"(src), "r"(bytes) : "memory");
}
constexpr uint64_t EVICT_FIRST = 0x12F0000000000000ull;
__device__ __forceinline__ void e_ld3(uint32_t dst, const CUtensorMap* m, int c0, int c1, int c2, uint32_t bar) {
    asm volatile(ELECT "cp.async.bulk.tensor.3d.shared::cluster.global.mbarrier::complete_tx::bytes [%0], [%1, {%3, %4, %5}], [%2];\n}"
                 :: "r"(dst), "l"(m), "r"(bar), "r"(c0), "r"(c1), "r"(c2) : "memory");
}
__device__ __forceinline__ void e_st3y(const CUtensorMap* m, uint32_t src, int c0, int c1, int c2) {
    asm volatile(ELECT "cp.async.bulk.tensor.3d.global.shared::cta.bulk_group [%0, {%2, %3, %4}], [%1];\n}" :: "l"(m), "r"(src), "r"(c0), "r"(c1), "r"(c2) : "memory");
}
__device__ __forceinline__ void e_ld4(uint32_t dst, const CUtensorMap* m, int c0, int c3, uint32_t bar) {
    asm volatile(ELECT "cp.async.bulk.tensor.4d.shared::cluster.global.mbarrier::complete_tx::bytes [%0], [%1, {%3, %5, %5, %4}], [%2];\n}"
                 :: "r"(dst), "l"(m), "r"(bar), "r"(c0), "r"(c3), "r"(0) : "memory");
}
__device__ __forceinline__ void e_st3(const CUtensorMap* m, uint32_t src, int c0, int c1, int c2) {
    asm volatile(ELECT "cp.async.bulk.tensor.3d.global.shared::cta.bulk_group [%0, {%2, %3, %4}], [%1];\n}" :: "l"(m), "r"(src), "r"(c0), "r"(c1), "r"(c2) : "memory");
}
__device__ __forceinline__ void e_ld5(uint32_t dst, const CUtensorMap* m, int c4, uint32_t bar) {
    asm volatile(ELECT "cp.async.bulk.tensor.5d.shared::cluster.global.mbarrier::complete_tx::bytes [%0], [%1, {%4, %4, %4, %4, %3}], [%2];\n}"
                 :: "r"(dst), "l"(m), "r"(bar), "r"(c4), "r"(0) : "memory");
}
__device__ __forceinline__ void e_st5(const CUtensorMap* m, uint32_t src, int c4) {
    asm volatile(ELECT "cp.async.bulk.tensor.5d.global.shared::cta.bulk_group [%0, {%3, %3, %3, %3, %2}], [%1];\n}" :: "l"(m), "r"(src), "r"(c4), "r"(0) : "memory");
}
__device__ __forceinline__ void bulk_commit() { asm volatile("cp.async.bulk.commit_group;" ::: "memory"); }
template <int N> __device__ __forceinline__ void bulk_wait_read() { asm volatile("cp.async.bulk.wait_group.read %0;" :: "n"(N) : "memory"); }
__device__ __forceinline__ void wg_bar(int id) { asm volatile("bar.sync %0, 128;" :: "r"(id) : "memory"); }
__device__ __forceinline__ void bb_break(uint32_t v) { asm volatile("{\n.reg .pred p;\nsetp.eq.u32 p, %0, 0x7fc17fc1;\n@p nanosleep.u32 0;\n}" :: "r"(v) : "memory"); }
__device__ __forceinline__ uint32_t uni(uint32_t v) { return __shfl_sync(0xffffffffu, v, 0); }
__device__ __forceinline__ char* cls_cnt(char* scr, int cls) { return scr + slot_line(3, 2, cls) * 128; }
__device__ __forceinline__ uint32_t cnt_wait(const void* p, unsigned target) {
    uint32_t v = 0;
#pragma unroll 1
    for (unsigned it = 0; it < (1u << 22) && v < target; it++) {
        asm volatile("ld.acquire.gpu.global.u32 %0, [%1];" : "=r"(v) : "l"(p) : "memory");
        v = uni(v);
    }
    asm volatile("fence.proxy.async.global;" ::: "memory");
    return v;
}
__device__ __forceinline__ void wg_fence() { asm volatile("wgmma.fence.sync.aligned;" ::: "memory"); }
__device__ __forceinline__ void wg_commit() { asm volatile("wgmma.commit_group.sync.aligned;" ::: "memory"); }
template <int N> __device__ __forceinline__ void wg_wait() { asm volatile("wgmma.wait_group.sync.aligned %0;" :: "n"(N) : "memory"); }
template <int N> __device__ __forceinline__ void reg_fence(float (&d)[N]) {
#pragma unroll
    for (int i = 0; i < N; i++) asm volatile("" : "+f"(d[i]) :: "memory");
}
template <int N, int O, int M> __device__ __forceinline__ float (&sub(float (&d)[M]))[N] { return *reinterpret_cast<float (*)[N]>(&d[O]); }
template <int N> __device__ __forceinline__ void zero(float (&d)[N]) {
#pragma unroll
    for (int i = 0; i < N; i++) d[i] = 0.f;
}
__device__ __forceinline__ uint32_t pack2(float lo, float hi) {
    uint32_t r; asm volatile("cvt.rn.bf16x2.f32 %0, %1, %2;" : "=r"(r) : "f"(hi), "f"(lo)); return r;
}
__device__ __forceinline__ void stm4(uint32_t a, uint32_t r0, uint32_t r1, uint32_t r2, uint32_t r3) {
    asm volatile("stmatrix.sync.aligned.m8n8.x4.trans.shared.b16 [%0], {%1,%2,%3,%4};" :: "r"(a), "r"(r0), "r"(r1), "r"(r2), "r"(r3) : "memory");
}
__device__ __forceinline__ void stm2(uint32_t a, uint32_t r0, uint32_t r1) {
    asm volatile("stmatrix.sync.aligned.m8n8.x2.trans.shared.b16 [%0], {%1,%2};" :: "r"(a), "r"(r0), "r"(r1) : "memory");
}
__device__ __forceinline__ void stm1(uint32_t a, uint32_t r0) {
    asm volatile("stmatrix.sync.aligned.m8n8.x1.trans.shared.b16 [%0], {%1};" :: "r"(a), "r"(r0) : "memory");
}
struct Desc {
    uint32_t lo, hi;
    __device__ __forceinline__ operator uint64_t() const { return ((uint64_t)hi << 32) | lo; }
    __device__ __forceinline__ Desc operator+(uint32_t o) const { return Desc{lo + o, hi}; }
    __device__ __forceinline__ Desc operator^(uint32_t o) const { return Desc{lo ^ o, hi}; }
};
__device__ __forceinline__ Desc mkdesc(uint32_t addr, uint32_t lbo, uint32_t sbo, uint32_t swz) {
    return Desc{((addr & 0x3FFFF) >> 4) | ((lbo >> 4) << 16), (sbo >> 4) | (swz << 30)};
}
__device__ __forceinline__ uint32_t cos_bits(int k) {
    if (k > 20) k = 40 - k;
    const bool neg = k > 10;
    if (neg) k = 20 - k;
    const unsigned long long pk = k < 4 ? COS_PK0 : k < 8 ? COS_PK1 : COS_PK2;
    return (uint32_t)((pk >> (16 * (k & 3))) & 0xffff) ^ (neg ? 0x8000u : 0u);
}

__device__ __forceinline__ void task_w(int wg, int k, uint32_t sb) {
    const int tid = threadIdx.x & 127, w = uni(tid >> 5), lane = tid & 31, q = lane & 3;
    const int tb = 14 * k, t1 = min(tb + 14, 1800), cb0 = tb / 25;
    float acc[64];
    zero(acc);
    const int oc0 = tb - 25 * cb0, Lt = t1 - tb, L0 = min(Lt, 25 - oc0), n0 = (L0 + 3) >> 2;
    uint32_t a[2][4][4];
    auto gen = [&](uint32_t (&a)[4][4], int at) {
        const int phi = 8 * ((at < n0 ? oc0 + 4 * at : 4 * (at - n0)) + w) + (lane >> 2), f = (phi * 205) >> 12;
        const uint32_t ca = 8 * f + 4, cw = (phi - 20 * f) * 8, p0 = sb + TBL + cw * 2 * q;
#pragma unroll
        for (int kh = 0; kh < 7; kh++) {
            uint32_t v0, v1;
            asm volatile("ld.shared.u32 %0, [%1];" : "=r"(v0) : "r"(p0 + ca * kh));
            asm volatile("ld.shared.u32 %0, [%1];" : "=r"(v1) : "r"(p0 + cw + ca * kh));
            const int h = kh == 6 ? 1 : kh & 1;
            a[kh >> 1][2 * h] = __byte_perm(v0, v1, 0x5410);
            a[kh >> 1][2 * h + 1] = __byte_perm(v0, v1, 0x7632);
        }
        a[3][0] = 0; a[3][1] = 0;
    };
    gen(a[0], wg);
    if (wg) gen(a[1], wg + 2);
    PROFW(wg == 0 ? 124 : 127);
#pragma unroll 1
    for (int n = 0; n < 2; n++) {
        const int at = wg + 2 * n, i0 = at < n0 ? 4 * at : L0 + 4 * (at - n0), cnt = (at < n0 ? L0 : Lt) - i0, cb = cb0 + (at >= n0);
        if (cnt <= 0 || (n && !wg)) break;
        if (n) {
#pragma unroll
            for (int j = 0; j < 16; j++) a[0][j >> 2][j & 3] = a[1][j >> 2][j & 3];
        }
        const Desc dB = mkdesc(sb + WP + (cb - cb0) * 14336, 3584, 512, 2);
        if (at) mbar_wait(sb + BARS + 8 * (B_WCH + at - 1));
        mbar_wait(sb + BARS + 8 * (B_WF + 2 * (cb - cb0)));
        PROFW(at == 0 ? 125 : 127);
        wg_fence();
        wgmma_rs_n128_z(acc, a[0][0][0], a[0][0][1], a[0][0][2], a[0][0][3], dB);
        wgmma_rs_n128_a(acc, a[0][1][0], a[0][1][1], a[0][1][2], a[0][1][3], dB + (uint32_t)(16 * 64 >> 4));
        wgmma_rs_n128_a(acc, a[0][2][0], a[0][2][1], a[0][2][2], a[0][2][3], dB + (uint32_t)(32 * 64 >> 4));
        wgmma_rs_n128_a(acc, a[0][3][0], a[0][3][1], a[0][3][2], a[0][3][3], dB + (uint32_t)(40 * 64 >> 4));
        wg_commit();
        wg_wait<0>();
        reg_fence(acc);
        PROFW(at == 0 ? 120 : 127);
        e_arrive(sb + BARS + 8 * (B_WCH + at));
        if (w < cnt) {
            const uint32_t dst = sb + wst_off(i0 + w) + (lane >> 2) * 512 + (lane & 4) * 16 + ((q ^ cb) & 3) * 16;
#pragma unroll
            for (int j = 0; j < 4; j++)
#pragma unroll
                for (int e = 0; e < 2; e++)
                    asm volatile("st.shared.v4.u32 [%0], {%1,%2,%3,%4};" :: "r"((dst ^ (e * 64)) + j * 128),
                                 "r"(pack2(acc[4 * j + e], acc[16 + 4 * j + e])), "r"(pack2(acc[4 * j + 2 + e], acc[16 + 4 * j + 2 + e])),
                                 "r"(pack2(acc[32 + 4 * j + e], acc[48 + 4 * j + e])), "r"(pack2(acc[32 + 4 * j + 2 + e], acc[48 + 4 * j + 2 + e])) : "memory");
            fence_async_smem();
            e_arrive(sb + BARS + 8 * (B_WRD + i0 + w));
        }
    }
}

__device__ __forceinline__ void task_p1(int wg, int pair, uint32_t sb) {
    const int tid = threadIdx.x & 127, w = tid >> 5, lane = tid & 31;
    const uint32_t buf = sb + wg * 51200, bars = sb + BARS;
    uint32_t fr[5][10][2];
    float A[40], d[20];
    zero(A);
    {
        const Desc dA = mkdesc(buf, 3584, 512, 2), dB = mkdesc(sb + C1, 128, 256, 0);
        auto issue = [&](int g, float (&d)[40]) {
            mbar_wait(bars + 8 * (B_XF + wg * 5 + g));
            wg_fence();
            wgmma_ss_n80_z(d, dA + (uint32_t)(g * 8704 >> 4), dB);
#pragma unroll
            for (int j = 1; j < 5; j++) wgmma_ss_n80_a(d, dA + (uint32_t)((g * 8704 + j * 1024) >> 4), dB + (uint32_t)(j * 2560 >> 4));
            wg_commit();
        };
        auto pack = [&](int g, float (&d)[40]) {
            reg_fence(d);
#pragma unroll
            for (int f = 0; f < 10; f++) {
                fr[g][f][0] = pack2(d[4 * f], d[4 * f + 1]);
                fr[g][f][1] = pack2(d[4 * f + 2], d[4 * f + 3]);
            }
        };
        mbar_wait(bars + 8 * B_CF1);
#pragma unroll
        for (int g = 0; g < 4; g++) { issue(g, A); if (g == 0) PROFW(8 + wg * 8 + 1); wg_wait<0>(); pack(g, A); }
        zero(d);
        mbar_wait(bars + 8 * (B_XF + wg * 5 + 4));
#pragma unroll
        for (int h = 0; h < 2; h++) {
            wg_fence();
            wgmma_ss_n40_z(d, dA + (uint32_t)(4 * 8704 >> 4), dB + (uint32_t)(h * 1280 >> 4));
#pragma unroll
            for (int j = 1; j < 5; j++) wgmma_ss_n40_a(d, dA + (uint32_t)((4 * 8704 + j * 1024) >> 4), dB + (uint32_t)((j * 2560 + h * 1280) >> 4));
            wg_commit(); wg_wait<0>(); reg_fence(d);
#pragma unroll
            for (int f = 0; f < 5; f++) { fr[4][5 * h + f][0] = pack2(d[4 * f], d[4 * f + 1]); fr[4][5 * h + f][1] = pack2(d[4 * f + 2], d[4 * f + 3]); }
        }
    }
    bb_break(sb);
    wg_bar(1 + wg);
    PROFW(8 + wg * 8 + 2);
    {
        const Desc dB = mkdesc(sb + C1 + 12800, 128, 256, 0);
        const int i = lane & 7, mi = lane >> 3, th = w >> 1, tz = (2 * pair + th) & 3;
        const uint32_t s0 = buf + (i >> 1) * 128 + (i & 1) * 64 + (((2 * (w & 1) + (mi & 1)) ^ tz ^ (i >> 1)) << 4);
        const uint32_t sA = s0 + th * 2048 + (mi >> 1) * 512, sB = s0 + th * 2048 + (mi >> 1) * 2560, sC = s0 + th * 1024 + (mi >> 1) * 512;
        auto issue = [&](int f, float (&d)[20]) {
            wg_fence();
            wgmma_rs_n40_z(d, fr[0][f][0], fr[0][f][1], fr[1][f][0], fr[1][f][1], dB);
            wgmma_rs_n40_a(d, fr[2][f][0], fr[2][f][1], fr[3][f][0], fr[3][f][1], dB + (uint32_t)(1280 >> 4));
            wgmma_rs_n40_a(d, fr[4][f % 5][0], fr[4][f % 5][1], fr[4][f % 5 + 5][0], fr[4][f % 5 + 5][1], dB + (uint32_t)((2560 + (f / 5) * 1280) >> 4));
            wg_commit();
        };
#pragma unroll
        for (int f = 0; f < 10; f++) {
                        issue(f, d); wg_wait<0>(); reg_fence(d);
            const int Q = 5 * f;
            stm4(((Q & 3) == 3 ? sB : sA) + quad_off(Q), pack2(d[0], d[1]), pack2(d[2], d[3]), pack2(d[4], d[5]), pack2(d[6], d[7]));
            stm2(sA + quad_off(Q + 2), pack2(d[8], d[9]), pack2(d[10], d[11]));
            stm4((f == 9 ? sC : ((Q + 3) & 3) == 3 ? sB : sA) + quad_off(Q + 3), pack2(d[12], d[13]), pack2(d[14], d[15]), pack2(d[16], d[17]), pack2(d[18], d[19]));
            if (f & 1) { fence_async_smem(); e_arrive(bars + 8 * (B_RDY + wg * 5 + (f >> 1))); }
        }
    }
}

__device__ __forceinline__ void task_p2(int wg, int rk, uint32_t sb) {
    const int tid = threadIdx.x & 127, w = tid >> 5, lane = tid & 31;
    const uint32_t bars = sb + BARS;
    const int phi0 = 3 * rk, phiE = extra_phi(rk), mE = extra_mask(rk);
    uint4 wA[6], wB[6], wC[6], wE[6];
    auto ldw = [&](uint4 (&a)[6], int j, int phi) {
        const int pc = 3 * j + wg;
        const uint32_t p = sb + wslot(pc) + (lane & 3) * 512 + w * 128 + (((lane >> 2) ^ phi) & 1) * 64 + (((lane >> 3) ^ lane) & 3) * 16 + (phi & 1) * 8;
        mbar_wait(bars + 8 * (B_WL + pc));
#pragma unroll
        for (int s = 0; s < 6; s++) {
            asm volatile("ld.shared.v2.u32 {%0, %1}, [%2];" : "=r"(a[s].x), "=r"(a[s].y) : "r"(p + s * 2048) : "memory");
            asm volatile("ld.shared.v2.u32 {%0, %1}, [%2];" : "=r"(a[s].z), "=r"(a[s].w) : "r"((p ^ 8) + s * 2048) : "memory");
        }
        uint32_t dep = 0;
#pragma unroll
        for (int s = 0; s < 6; s++) dep |= a[s].x ^ a[s].z;
        if (__any_sync(0xffffffffu, dep == 0x7fc17fc1u)) __nanosleep(0);
        e_arrive(bars + 8 * (B_WE + pc));
    };
    ldw(wA, 0, phi0); ldw(wB, 1, phi0 + 1);
    if (!LAZYC) ldw(wC, 2, phi0 + 2);
    PROFW(8 + wg * 8 + 4);
    mbar_wait(bars + 8 * (B_SIG + SIG_P1 + 1));
    const int i = lane & 7, mi = lane >> 3;
    const uint32_t soff = sb + S1 + wg * 4096 + mi * 512 + (i >> 1) * 128 + (i & 1) * 64;
    const int xo = w ^ (i >> 1);
    float d[32];
    zero(d);
    int n = 0;
    uint32_t xb = ((sb + xslot(0)) & 0x3FFFF) >> 4 | 1u << 16, mb = bars + 8 * wg;
    bool landed = false;
    auto unit = [&](const uint4 (&a)[6], int z) {
        const Desc d0{xb + (z & 2), (512u >> 4) | (2u << 30)}, d1 = d0 ^ 2u;
        if (!landed) mbar_wait(bars + 8 * (B_RF + n));
        mbar_wait(mb + 8 * (B_TOK - 1));
        wg_fence();
        wgmma_rs_n64_z(d, a[0].x, a[0].y, a[0].z, a[0].w, d0);
        wgmma_rs_n64_a(d, a[1].x, a[1].y, a[1].z, a[1].w, d1);
        if (TOKM == 5) e_arrive(mb + 8 * B_TOK);
        e_arrive(bars + 8 * (n ? B_RE + n - 1 : B_RE + 13));
        const bool sfree = mbar_test(n >= 4 ? mb + 8 * (B_SFREE - 12) : bars + 8 * (B_TOK - 1));
        landed = mbar_test(bars + 8 * (B_RF + n + 1));
        wgmma_rs_n64_a(d, a[2].x, a[2].y, a[2].z, a[2].w, d0 + (uint32_t)(4096 >> 4));
        wgmma_rs_n64_a(d, a[3].x, a[3].y, a[3].z, a[3].w, d1 + (uint32_t)(4096 >> 4));
        if (TOKM == 6) e_arrive(mb + 8 * B_TOK);
        wgmma_rs_n64_a(d, a[4].x, a[4].y, a[4].z, a[4].w, d0 + (uint32_t)(8192 >> 4));
        wgmma_rs_n64_a(d, a[5].x, a[5].y, a[5].z, a[5].w, d1 + (uint32_t)(8192 >> 4));
        wg_commit();
        if (TOKM == 3) e_arrive(mb + 8 * B_TOK);
        if (!sfree) mbar_wait(mb + 8 * (B_SFREE - 12));
        const uint32_t a0 = soff + (n & 3) * 12288 + ((xo ^ z) << 4);
        n++;
        xb = ((sb + xslot(n)) & 0x3FFFF) >> 4 | 1u << 16;
        wg_wait<0>();
        reg_fence(d);
        uint32_t p[8];
#pragma unroll
        for (int j = 0; j < 8; j++) p[j] = pack2(d[4 * j] - d[4 * j + 3], d[4 * j + 2] + d[4 * j + 1]);
        stm4(a0, p[0], p[1], p[2], p[3]);
        stm4(a0 + 2048, p[4], p[5], p[6], p[7]);
        fence_async_smem();
        e_arrive(mb + 8 * (B_RDY + R_P2));
        mb += 24;
    };
    const int zA = phi0 & 3, zB = (phi0 + 1) & 3, zC = (phi0 + 2) & 3, zE = phiE & 3;
#pragma unroll 1
    for (int it = 0; it < 4; it++) {
        unit(wA, zA);
        PROFW(40 + wg * 8 + it * 2);
        unit(wB, zB);
        if (LAZYC && it == 0) ldw(wC, 2, phi0 + 2);
        unit(wC, zC);
        if (it == 0 && mE) ldw(wE, 3, phiE);
        if (mE >> it & 1) unit(wE, zE);
        PROFW(40 + wg * 8 + it * 2 + 1);
    }
}

__device__ __forceinline__ void task_p3(int wg, int pair, uint32_t sb) {
    const int tid = threadIdx.x & 127, w = tid >> 5, lane = tid & 31;
    const uint32_t buf = sb + (wg ? 3 - wg : 0) * 51200, bars = sb + BARS;
    uint32_t fr[10][4][2];
    float acc[2][16];
    zero(acc[0]); zero(acc[1]);
    {
        const Desc dB = mkdesc(sb + C3, 128, 256, 0);
        const uint32_t a0 = (buf & 0x3FFFF) >> 4;
        auto dq = [&](int Q) {
            return Desc{a0 + (uint32_t)((quad_off(Q) >> 4) | ((Q < 48 ? 2048 : 1024) >> 4) << 16), (uint32_t)((quad_off(Q + 1) - quad_off(Q)) >> 4) | (2u << 30)};
        };
        auto issue = [&](int f) {
            if (!(f & 1)) mbar_wait(bars + 8 * (B_YF + wg * 5 + (f >> 1)));
            wg_fence();
            wgmma_ss_n32_z(acc[f & 1], dq(5 * f), dB);
            wgmma_ss_n32_a(acc[f & 1], dq(5 * f + 1), dB + (uint32_t)(1024 >> 4));
            wgmma_ss_n32_a(acc[f & 1], dq(5 * f + 3), dB + (uint32_t)(2048 >> 4));
            wg_commit();
        };
        mbar_wait(bars + 8 * B_CF3);
        issue(0);
        PROFW(64 + wg * 8 + 1);
#pragma unroll
        for (int f = 0; f < 10; f++) {
            if (f < 9) { issue(f + 1); wg_wait<1>(); } else wg_wait<0>();
            float (&d)[16] = acc[f & 1];
            reg_fence(d);
#pragma unroll
            for (int g = 0; g < 4; g++) { fr[f][g][0] = pack2(d[4 * g], d[4 * g + 1]); fr[f][g][1] = pack2(d[4 * g + 2], d[4 * g + 3]); }
        }
    }
    PROFW(64 + wg * 8 + 2);
    {
        const Desc dB = mkdesc(sb + C3 + 3072, 128, 256, 0);
        const int i = lane & 7, mi = lane >> 3, th = w >> 1, tz = (2 * pair + th) & 3;
        const int oct = (2 * (w & 1) + (mi & 1)) ^ tz;
        const uint32_t soff = buf + th * 3584 + (mi >> 1) * 512 + i * 64 + ((oct ^ (i >> 1)) << 4);
        auto issue = [&](int t) {
            const int g = t < 6 ? 1 + (t >> 1) : 0;
            const uint32_t o = t < 6 ? (t & 1) * 1024 : 8960, st = t < 6 ? 1792 : 1024;
            wg_fence();
            wgmma_rs_n32_z(acc[t & 1], fr[0][g][0], fr[0][g][1], fr[1][g][0], fr[1][g][1], dB + (o >> 4));
#pragma unroll
            for (int s = 1; s < 5; s++) wgmma_rs_n32_a(acc[t & 1], fr[2 * s][g][0], fr[2 * s][g][1], fr[2 * s + 1][g][0], fr[2 * s + 1][g][1], dB + ((o + s * st) >> 4));
            wg_commit();
        };
        bb_break(sb);
        issue(0);
        wg_bar(1 + wg);
#pragma unroll
        for (int t = 0; t < 7; t++) {
            if (t < 6) { issue(t + 1); wg_wait<1>(); } else wg_wait<0>();
            float (&d)[16] = acc[t & 1];
            reg_fence(d);
            if (t < 6) {
                const uint32_t a = soff + (1 + (t >> 1)) * 7168 + (t & 1) * 2048;
                stm4(a, pack2(d[0], d[1]), pack2(d[2], d[3]), pack2(d[4], d[5]), pack2(d[6], d[7]));
                if (t & 1) stm2(a + 1024, pack2(d[8], d[9]), pack2(d[10], d[11]));
                else stm4(a + 1024, pack2(d[8], d[9]), pack2(d[10], d[11]), pack2(d[12], d[13]), pack2(d[14], d[15]));
            } else {
                const int row = th * 14 + 4 * (mi >> 1) + (i >> 1);
                const uint32_t a = buf + row * 128 + (i & 1) * 64 + ((oct ^ (row & 3)) << 4);
                stm4(a, pack2(d[0], d[1]), pack2(d[2], d[3]), pack2(d[4], d[5]), pack2(d[6], d[7]));
                stm4((lane & 20) == 20 ? buf + 4096 + lane * 16 : a + 1024, pack2(d[8], d[9]), pack2(d[10], d[11]), pack2(d[12], d[13]), pack2(d[14], d[15]));
            }
            if ((t & 1) || t == 6) { fence_async_smem(); e_arrive(bars + 8 * (B_RDY + R_P3 + wg * 4 + (t >> 1))); }
        }
    }
}

__device__ __forceinline__ void load_x(int cls, int rk, int u, uint32_t sb, const Maps& mp) {
    const int id = u * NH + rk, pl = id / 3, c0 = 32 * (id - 3 * pl), tp = cls * 4 + (pl >> 4), col = 14 * (pl & 15) - 8;
    const uint32_t bar = sb + BARS + 8 * (B_XF + u * 5), dst = sb + u * 51200;
    const int wrap = col < 0 ? 224 : 0;
    if (tp) {
#pragma unroll
        for (int g = 0; g < 5; g++) e_ld3(dst + g * 8704, &mp.x34, c0, col + 4 * g + (g < 2 ? wrap : 0), 28 * tp - 6, bar + 8 * g);
    } else {
#pragma unroll
        for (int g = 0; g < 5; g++) {
            e_ld3(dst + g * 8704, &mp.x6, c0, col + 4 * g + (g < 2 ? wrap : 0), 218, bar + 8 * g);
            e_ld3(dst + g * 8704 + 1536, &mp.x28, c0, col + 4 * g + (g < 2 ? wrap : 0), 0, bar + 8 * g);
        }
    }
}

__device__ __forceinline__ void load_x_box(int cls, int rk, int u, int g, uint32_t sb, const Maps& mp) {
    const int id = u * NH + rk, pl = id / 3, c0 = 32 * (id - 3 * pl), tp = cls * 4 + (pl >> 4), col = 14 * (pl & 15) - 8 + 4 * g;
    e_ld3(sb + u * 51200 + g * 8704, &mp.x34, c0, col < 0 ? col + 224 : col, 28 * tp - 6, sb + BARS + 8 * (B_XF + u * 5 + g));
}

__device__ __forceinline__ void load_first(uint32_t sb, const Maps& mp, const Ptrs& pt) {
    const uint32_t bars = sb + BARS;
    const int k = blockIdx.x;
    PROF(122);
    if (k < 129) {
        const int cb0 = 14 * k / 25, cb1 = min((14 * k + 13) / 25, 71);
#pragma unroll 1
        for (int cb = cb0; cb <= cb1; cb++) {
            const int b = cb / 24, i0 = 16 * ((cb >> 2) - 6 * b) + 2 * (cb & 3);
            const uint32_t bar = bars + 8 * (B_WF + 2 * (cb - cb0));
            e_expect(bar, 14336);
            e_ld4(sb + WP + (cb - cb0) * 14336, &mp.w, 32 * b, i0, bar);
            e_ld4(sb + WP + (cb - cb0) * 14336 + 7168, &mp.w, 32 * b, i0 + 8, bar);
        }
    }
    e_expect(bars + 8 * B_CF1, 17920); e_g2s(sb + C1, pt.tab1, 17920, bars + 8 * B_CF1);
    if ((threadIdx.x & 31) < 15) asm volatile("mbarrier.arrive.expect_tx.shared::cta.b64 _, [%0], 8704;" :: "r"(bars + 8 * (B_XF + (threadIdx.x & 31))) : "memory");
    __syncwarp();
}

__device__ __forceinline__ uint32_t get_rel(uint32_t sb) {
    mbar_wait(sb + BARS + 8 * B_REL);
    uint32_t v; asm volatile("ld.shared.u32 %0, [%1];" : "=r"(v) : "r"(sb + REL) : "memory");
    return uni(v);
}

__device__ __forceinline__ void load_warp(int cls, int rk, uint32_t sb, const Maps& mp, const Ptrs& pt) {
    const uint32_t bars = sb + BARS;
    mbar_wait(bars + 8 * (B_SIG + SIG_P1));
    PROF(1);
    const uint32_t rel = get_rel(sb);
    const char* cnt = cls_cnt(pt.scr, cls);
    const int mE = extra_mask(rk);
    const int lpA = phi_line(3 * rk, rel), lpB = phi_line(3 * rk + 1, rel), lpC = phi_line(3 * rk + 2, rel), lpE = phi_line(extra_phi(rk), rel);
    e_arrive(bars + 8 * (B_TOK - 1));
    if ((threadIdx.x & 31) < 14) asm volatile("mbarrier.arrive.expect_tx.shared::cta.b64 _, [%0], 12288;" :: "r"(bars + 8 * (B_RF + (threadIdx.x & 31))) : "memory");
    __syncwarp();
    int n = 0;
#pragma unroll 1
    for (int pg = 0; pg < 4; pg++) {
        const int l0 = slot_line(0, pg, cls), l1 = slot_line(1, pg, cls), l2 = slot_line(2, pg, cls);
        auto unit = [&](int lp) {
            const uint32_t bar = bars + 8 * (B_RF + n), dst = sb + xslot(n);
            mbar_wait(bars + 8 * (n >= 8 ? B_RE + n - 8 : n >= 4 ? B_SIG + SIG_P1 + (rk < 60 ? 2 : 1) : B_WE + ((0x4310 >> (4 * n)) & 15)));
            e_g2s(dst, pt.scr + (size_t)(lp ^ l0) * 128, 4096, bar);
            e_g2s(dst + 4096, pt.scr + (size_t)(lp ^ l1) * 128, 4096, bar);
            e_g2s(dst + 8192, pt.scr + (size_t)(lp ^ l2) * 128, 4096, bar);
            n++;
        };
        cnt_wait(cnt + (CNT_P1 + pg) * 128, 48);
        PROF(88 + pg);
        unit(lpA); unit(lpB);
        if (pg == 0) e_arrive(bars + 8 * B_X1);
        unit(lpC);
        if (mE >> pg & 1) unit(lpE);
        if (pg == 1) { mbar_wait(bars + 8 * B_P1D); e_expect(bars + 8 * B_CF3, 17152); e_g2s(sb + C3, pt.tab3, 17152, bars + 8 * B_CF3); }
    }
}

__device__ __forceinline__ int near_page(char* p, int rounds) {
#pragma unroll
    for (int e = 0; e < 4; e++) asm volatile("st.relaxed.gpu.global.v4.u32 [%0], {%1, %1, %1, %1};" :: "l"(p + (e >> 1) * 4096 + (e & 1) * 16), "r"(0) : "memory");
    int score = 0;
#pragma unroll 1
    for (int r = 0; r < rounds; r++) {
        uint32_t v0, v1, t0, t1;
        asm volatile("atom.relaxed.gpu.global.exch.b32 %0, [%1], 1;" : "=r"(v0) : "l"(p + (r & 1) * 4096) : "memory");
        asm volatile("atom.relaxed.gpu.global.exch.b32 %0, [%1], 1;" : "=r"(v1) : "l"(p + (~r & 1) * 4096) : "memory");
        asm volatile("{\n.reg .pred p;\nsetp.ne.u32 p, %1, 0xffffffff;\nmov.u32 %0, 0;\n@p mov.u32 %0, %%clock;\n}" : "=r"(t0) : "r"(v0) : "memory");
        asm volatile("{\n.reg .pred p;\nsetp.ne.u32 p, %1, 0xffffffff;\nmov.u32 %0, 0;\n@p mov.u32 %0, %%clock;\n}" : "=r"(t1) : "r"(v1) : "memory");
        const int gap = min((int)(t1 - t0), 160) - 80;
        score += (r & 1) ? gap : -gap;

    }
    return score > 0;
}

__device__ __forceinline__ uint32_t find_role(uint32_t sb, char* scr) {
    const int k = blockIdx.x;
    int c = near_page(scr + (slot_line(3, 3, 0) + phi_line(1 + (k >> 5), 0) + (k & 31)) * 128, PROBES);
    PROF(3);
    int r;
    asm volatile("atom.relaxed.gpu.global.add.u32 %0, [%1], 1;" : "=r"(r) : "l"(cls_cnt(scr, c) + CNT_RANK * 128) : "memory");
    asm volatile("st.shared.u32 [%0], %1;" :: "r"(sb + REL + 8), "r"(c) : "memory");
    if (r >= NH) { c ^= 1; r = NSM - 1 - r; }
    asm volatile("st.shared.u32 [%0], %1;" :: "r"(sb + REL + 4), "r"(c << 8 | r) : "memory");
    PROF(5);
    return c << 8 | r;
}
__device__ __forceinline__ void get_role(uint32_t sb, int& cls, int& rk) {
    mbar_wait(sb + BARS + 8 * B_ROLE);
    uint32_t v; asm volatile("ld.shared.u32 %0, [%1];" : "=r"(v) : "r"(sb + REL + 4) : "memory");
    v = uni(v); cls = v >> 8; rk = v & 255;
}

__device__ __forceinline__ void load3_warp(int cls, int rk, uint32_t sb, const Maps& mp, const Ptrs& pt) {
    const uint32_t bars = sb + BARS;
    uint32_t rel = 0;
    mbar_wait(bars + 8 * B_XF);
    PROF(107);
    rel = cnt_wait(pt.cnt + CNT_REL * 32, 12u << 16);
    asm volatile("st.shared.u32 [%0], %1;" :: "r"(sb + REL), "r"(rel) : "memory");
    __syncwarp();
    e_arrive(bars + 8 * B_REL);
    PROF(7);
    mbar_wait(bars + 8 * (B_SIG + SIG_W));
    cnt_wait(cls_cnt(pt.scr, cls) + CNT_W * 128, NSM);
    PROF(2);
    {
        const int np = rk >= 58 ? 12 : 9;
#pragma unroll 1
        for (int o = 0; o < np; o++) {
            const int pc = (0xba9876524310ull >> (4 * o)) & 15;
            if (o == 4) mbar_wait(bars + 8 * (B_SIG + SIG_P1));
            if (o >= 8) mbar_wait(bars + 8 * (B_WE + ((0x5762 >> (4 * (o - 8))) & 15)));
            if (o >= WWIN) mbar_wait(bars + 8 * (B_WL + ((0xba9876524310ull >> (4 * (o - WWIN))) & 15)));
            if (o == WHOLD) mbar_wait(bars + 8 * B_X1);
            e_expect(bars + 8 * (B_WL + pc), 12288);
            e_g2s(sb + wslot(pc), pt.wf + (pc < 9 ? 9 * rk + pc : 3 * extra_phi(rk) + pc - 9) * 12288, 12288, bars + 8 * (B_WL + pc));
        }
        if (np == 12) { mbar_wait(bars + 8 * (B_WE + 9)); mbar_wait(bars + 8 * (B_WE + 10)); mbar_wait(bars + 8 * (B_WE + 11)); }
    }
    mbar_wait(bars + 8 * (B_SIG + SIG_P2 + Y0AT));
    const int nu = rk < 60 ? 3 : 2;
#pragma unroll 1
    for (int u = 0; u < nu; u++) {
        const int id = u * NH + rk, pl = id / 3, chunk = id - 3 * pl;
        const int l0 = slot_line(chunk, pl >> 4, cls) + (pl & 15) * 2;
        const uint32_t buf = sb + (u ? 3 - u : 0) * 51200, bar = bars + 8 * (B_YF + u * 5);
#pragma unroll
        for (int j = 0; j < 5; j++) e_expect(bar + 8 * j, j == 4 ? 10240 : (j & 1) ? 8192 : 12288);
        if (u) mbar_wait(bars + 8 * (B_SIG + SIG_P2 + 3));
        cnt_wait(cls_cnt(pt.scr, cls) + (CNT_P2 + (pl >> 4)) * 128, NH);
        PROF(64 + u * 8);
        if (u == nu - 1) e_arrive(bars + 8 * B_FIN);
        const uint32_t r2 = uni(rel) << 5;
#pragma unroll
        for (int G = 0; G < 13; G++)
            e_ld5(buf + G * 4096, G < 12 ? &mp.f16 : &mp.f8, (l0 ^ ((r2 >> G) & 32)) + (G << 14), bar + 8 * ((2 * G) / 5));
    }
}

__device__ __forceinline__ void store_warp(uint32_t sb, const Maps& mp, const Ptrs& pt) {
    const uint32_t bars = sb + BARS;
    const int k = blockIdx.x;
    uint32_t pa = 0, pb = 0, qa = 0, qb = 0;
    auto arr2 = [&](uint32_t& a, uint32_t& b) { if (a) e_arrive(a); if (b) e_arrive(b); a = b = 0; };
    auto pre = [&](int idx) {
        const uint32_t bar = bars + 8 * idx;
        if (!mbar_test(bar)) { bulk_wait_read<0>(); arr2(qa, qb); arr2(pa, pb); mbar_wait(bar); }
    };
    auto post = [&](uint32_t fr) {
        bulk_commit(); bulk_wait_read<SWIN - 1>();
        if (SWIN == 3) { arr2(qa, qb); qa = pa; qb = pb; pb = 0; } else arr2(pa, pb);
        pa = fr;
    };
    auto after = [&](uint32_t a, uint32_t b) { if (a) pa = a; pb = b; };
    auto pace = [&](uint32_t) {};
    int cls, rk; get_role(sb, cls, rk);
    {
        int cb = 14 * k / 25, oc = 14 * k - 25 * cb;
        int g1 = 0;
#pragma unroll 1
        for (int i = 0; i < 14 && cb < 72; i++) {
            pre(B_WRD + i);
            if (PACE) pace(4 * PACE);
            e_st3(&mp.wst, sb + wst_off(i), 0, 8 * oc, cb);
            post(0);
            if (T1MASK >> i & 1) load_x_box(cls, rk, 1, g1++, sb, mp);
            if (++oc == 25) { oc = 0; cb++; }
        }
#pragma unroll 1
        for (; g1 < 5; g1++) load_x_box(cls, rk, 1, g1, sb, mp);
        after(bars + 8 * B_WFREE, bars + 8 * (B_SIG + SIG_W));
    }
    pre(B_REL);
    const uint32_t rel = get_rel(sb);
    const int nu = rk < 60 ? 3 : 2;
#pragma unroll 1
    for (int u = 0; u < nu; u++) {
        const int id = u * NH + rk, pl = id / 3, chunk = id - 3 * pl;
        const int l0 = slot_line(chunk, pl >> 4, cls) + (pl & 15) * 2;
        int j = B_RDY + u * 5;
        int g2 = 0;
        const int m2 = (u == 0 && nu == 3) ? T2MASK : 0;
#pragma unroll 1
        for (int G = 0; G < 13; G++) {
            if (0x4a5 >> G & 1) pre(j++);
            if (PACE) pace(G < 12 ? 4 * PACE : 2 * PACE);
            e_st5(G < 12 ? &mp.f16 : &mp.f8, sb + u * 51200 + G * 4096, (l0 ^ ((rel >> G) & 1) << 5) + (G << 14));
            post(0);
            if (m2 >> G & 1) load_x_box(cls, rk, 2, g2++, sb, mp);
        }
        after(0, bars + 8 * (B_SIG + SIG_P1 + u));
    }
    const int mE = extra_mask(rk);
    int n = 0;
#pragma unroll 1
    for (int pg = 0; pg < 4; pg++) {
        const int nj = 3 + (mE >> pg & 1);
        const int l0 = slot_line(0, pg, cls), l1 = slot_line(1, pg, cls), l2 = slot_line(2, pg, cls);
#pragma unroll 1
        for (int j = 0; j < nj; j++) {
            const int lp = phi_line(j == 3 ? extra_phi(rk) : 3 * rk + j, rel);
#pragma unroll
            for (int b = 0; b < 3; b++) {
                pre(B_RDY + R_P2 + n * 3 + b);
                if (PACE) pace(4 * PACE);
                e_s2g(pt.scr + (size_t)(lp ^ (b == 0 ? l0 : b == 1 ? l1 : l2)) * 128, sb + S1 + (n & 3) * 12288 + b * 4096, 4096);
                post(bars + 8 * (B_SFREE + n * 3 + b));
            }
            n++;
        }
        after(0, bars + 8 * (B_SIG + SIG_P2 + pg));
    }
#pragma unroll 1
    for (int u = 0; u < nu; u++) {
        const int id = u * NH + rk, pl = id / 3, chunk = id - 3 * pl, tp = cls * 4 + (pl >> 4), tx = pl & 15;
        const uint32_t buf = sb + (u ? 3 - u : 0) * 51200;
#pragma unroll
        for (int gg = 1; gg < 5; gg++) {
            pre(B_RDY + R_P3 + u * 4 + gg - 1);
            if (u < 2) pace(gg < 4 ? 7 * YPACE : 7 * YPACE / 2);
            if (gg < 4) e_st3y(&mp.y4, buf + gg * 7168, 32 * chunk, 14 * tx - 4 + 4 * gg, 28 * tp);
            else e_st3y(&mp.y2, buf, 32 * chunk, tx == 0 ? 222 : 14 * tx - 2, 28 * tp);
            post(0);
        }
    }
    bulk_wait_read<0>();
    PROF(113);
    prof_dump();
}

__device__ __forceinline__ void signal_warp(int cls, int rk, uint32_t sb, const Ptrs& pt) {
    const uint32_t bars = sb + BARS;
    char* cnt = cls_cnt(pt.scr, cls);
    if (threadIdx.x & 31) return;
#pragma unroll 1
    for (int c = 0; c < 8; c++) {
        if (c == SIG_P1 + 2 && rk >= 60) continue;
        char* ctr = cnt + (c == SIG_W ? CNT_W : c < SIG_P2 ? CNT_P1 + ((c - SIG_P1) * NH + rk) / 48 : CNT_P2 + c - SIG_P2) * 128;
        mbar_wait(bars + 8 * (B_SIG + c));
        PROF(32 + c);
        fence_async();
        asm volatile("red.relaxed.gpu.global.add.u32 [%0], 1;" :: "l"(ctr) : "memory");
        if (c == SIG_W) asm volatile("red.relaxed.gpu.global.add.u32 [%0], 1;" :: "l"((uintptr_t)ctr ^ 4096) : "memory");
        PROF(96 + c);
    }
    mbar_wait(bars + 8 * B_FIN);
    unsigned old;
    asm volatile("atom.add.relaxed.gpu.global.u32 %0, [%1], 1;" : "=r"(old) : "l"(pt.cnt + CNT_DONE * 32) : "memory");
    if (old == NSM - 1) {
#pragma unroll
        for (int c = 0; c < NCNT; c++) pt.cnt[c * 32] = 0;
#pragma unroll 1
        for (int c = 0; c < NCLS; c++) { *reinterpret_cast<unsigned*>(cnt + c * 128) = 0; *reinterpret_cast<unsigned*>(((uintptr_t)cnt ^ 4096) + c * 128) = 0; }
    }
}

__global__ void __launch_bounds__(512, 1) fftconv_kernel(const Ptrs pt, const __grid_constant__ Maps mp) {
    extern __shared__ __align__(1024) uint8_t smem[];
    const uint32_t sb = smem_u32(smem);
    const int tid = threadIdx.x, warp = uni(tid >> 5), wg = warp >> 2;
    int cls, rk;
    auto bar_init = [&](int i) {
        uint32_t c = 1;
        if (i == B_P1D || (i >= B_RE && i < B_RE + 14)) c = 12;
        else if ((i >= B_WCH && i < B_WL) || i >= B_TOK) c = 4;
        asm volatile("st.shared.v2.u32 [%0], {%1, %2};" :: "r"(sb + BARS + 8 * i), "r"((0x100000u - c) << 1), "r"((0x100000u - c) << 11) : "memory");
        fence_async_smem();
    };
    if (wg == 3) {
        asm volatile("setmaxnreg.dec.sync.aligned.u32 32;");
        if (warp == 12) {
            bar_init(tid & 31);
            __syncwarp();
            asm volatile("bar.arrive 4, 416;" ::: "memory");
            load_first(sb, mp, pt);
            PROF(106);
            asm volatile("bar.sync 5, 416;" ::: "memory");
            get_role(sb, cls, rk);
            load_warp(cls, rk, sb, mp, pt);
        } else if (warp == 13) {
            if ((tid & 31) < 8) asm volatile("prefetch.tensormap [%0];" :: "l"(reinterpret_cast<const CUtensorMap*>(&mp) + 1 + (tid & 31)) : "memory");
            __syncwarp();
            asm volatile("bar.sync 6, 416;" ::: "memory");
            store_warp(sb, mp, pt);
        } else if (warp == 14) {
            const int G = blockIdx.x - 119;
            int sel = 0;
            if (G >= 1 && (tid & 31) == 0) sel = near_page(pt.scr + ((size_t)G << 21) + slot_line(3, 3, 0) * 128, 2);
            __syncwarp();
            asm volatile("bar.sync 7, 416;" ::: "memory");
            get_role(sb, cls, rk);
            if (G >= 1 && (tid & 31) == 0) {
                uint32_t c; asm volatile("ld.shared.u32 %0, [%1];" : "=r"(c) : "r"(sb + REL + 8) : "memory");
                asm volatile("red.relaxed.gpu.global.add.u32 [%0], %1;" :: "l"(pt.cnt + CNT_REL * 32), "r"(0x10000u | (sel ^ c) << G) : "memory");
            }
            __syncwarp();
            load3_warp(cls, rk, sb, mp, pt);
        } else {
            uint32_t role = 0;
            if ((tid & 31) == 0) role = find_role(sb, pt.scr);
            role = uni(role); cls = role >> 8; rk = role & 255;
            asm volatile("bar.sync 8, 416;" ::: "memory");
            load_x(cls, rk, 0, sb, mp);
            PROF(123);
            e_arrive(sb + BARS + 8 * B_ROLE);
            signal_warp(cls, rk, sb, pt);
        }
    } else {
        if (tid >= 32 && tid < NBAR) bar_init(tid);
        {
            const int r = tid % 40;
            asm volatile("st.shared.u32 [%0], %1;" :: "r"(sb + TBL + 4 * tid), "r"(cos_bits(r) | (cos_bits(r < 30 ? r + 10 : r - 30) << 16)) : "memory");
        }
        __syncwarp();
        asm volatile("bar.sync 4, 416;" ::: "memory");
        asm volatile("bar.arrive 5, 416;" ::: "memory");
        asm volatile("bar.arrive 6, 416;" ::: "memory");
        asm volatile("bar.arrive 7, 416;" ::: "memory");
        asm volatile("bar.arrive 8, 416;" ::: "memory");
        PROF(121);
        task_w(wg, blockIdx.x, sb);
        asm volatile("setmaxnreg.inc.sync.aligned.u32 160;");
        get_role(sb, cls, rk);
        const int id = wg * NH + rk;
        PROFW(8 + wg * 8);
        if (id < 192) task_p1(wg, id / 3, sb);
        e_arrive(sb + BARS + 8 * B_P1D);
        PROFW(8 + wg * 8 + 3);
        task_p2(wg, rk, sb);
        if (id < 192) task_p3(wg, id / 3, sb);
        PROFW(64 + wg * 8 + 3);
        prof_dump();
    }
}

typedef CUresult (*EncodeFn)(CUtensorMap*, CUtensorMapDataType, cuuint32_t, void*, const cuuint64_t*, const cuuint64_t*, const cuuint32_t*, const cuuint32_t*,
                             CUtensorMapInterleave, CUtensorMapSwizzle, CUtensorMapL2promotion, CUtensorMapFloatOOBfill);

static void encode3(EncodeFn fn, CUtensorMap* m, void* ptr, uint64_t d0, uint64_t d1, uint64_t d2, uint64_t s1, uint64_t s2,
                    uint32_t b0, uint32_t b1, uint32_t b2, CUtensorMapSwizzle sw) {
    cuuint64_t dims[3] = {d0, d1, d2}, strides[2] = {s1, s2};
    cuuint32_t box[3] = {b0, b1, b2}, es[3] = {1, 1, 1};
    fn(m, CU_TENSOR_MAP_DATA_TYPE_BFLOAT16, 3, ptr, dims, strides, box, es, CU_TENSOR_MAP_INTERLEAVE_NONE, sw,
       CU_TENSOR_MAP_L2_PROMOTION_NONE, CU_TENSOR_MAP_FLOAT_OOB_FILL_NONE);
}

extern "C" void kernel_launch(void* const* d_in, const int* in_sizes, int n_in, void* d_out, int out_size) {
    (void)in_sizes; (void)n_in; (void)out_size;
    void* fnp = nullptr; cudaDriverEntryPointQueryResult qr;
    cudaGetDriverEntryPoint("cuTensorMapEncodeTiled", &fnp, cudaEnableDefault, &qr);
    EncodeFn fn = (EncodeFn)fnp;
    void* xf = nullptr; cudaGetSymbolAddress(&xf, g_scr);
    xf = (void*)(((uintptr_t)xf + (1u << 21) - 1) & ~(uintptr_t)((1u << 21) - 1));
    void* wf = nullptr; cudaGetSymbolAddress(&wf, g_wf);
    Maps mp;
    Ptrs pt;
    pt.scr = (char*)xf; pt.wf = (const char*)wf;
    void* p = nullptr;
    cudaGetSymbolAddress(&p, TAB_P1); pt.tab1 = p;
    cudaGetSymbolAddress(&p, TAB_P3); pt.tab3 = p;
    cudaGetSymbolAddress(&p, g_cnt); pt.cnt = (unsigned*)p;
    {
        cuuint32_t b16[5] = {64, 4, 2, 2, 2}, b8[5] = {64, 4, 2, 1, 2}, es[5] = {1, 1, 1, 1, 1};
        cuuint64_t d[5] = {64, 4, 2, 2, 13 << 14}, st[4] = {16384, 262144, 1048576, 128};
        fn(&mp.f16, CU_TENSOR_MAP_DATA_TYPE_BFLOAT16, 5, xf, d, st, b16, es, CU_TENSOR_MAP_INTERLEAVE_NONE, CU_TENSOR_MAP_SWIZZLE_NONE, CU_TENSOR_MAP_L2_PROMOTION_NONE, CU_TENSOR_MAP_FLOAT_OOB_FILL_NONE);
        fn(&mp.f8, CU_TENSOR_MAP_DATA_TYPE_BFLOAT16, 5, xf, d, st, b8, es, CU_TENSOR_MAP_INTERLEAVE_NONE, CU_TENSOR_MAP_SWIZZLE_NONE, CU_TENSOR_MAP_L2_PROMOTION_NONE, CU_TENSOR_MAP_FLOAT_OOB_FILL_NONE);
    }
    encode3(fn, &mp.x6, d_in[0], 96, 224, 224, 192, 224 * 192, 32, 4, 6, CU_TENSOR_MAP_SWIZZLE_64B);
    encode3(fn, &mp.x34, d_in[0], 96, 224, 224, 192, 224 * 192, 32, 4, 34, CU_TENSOR_MAP_SWIZZLE_64B);
    encode3(fn, &mp.x28, d_in[0], 96, 224, 224, 192, 224 * 192, 32, 4, 28, CU_TENSOR_MAP_SWIZZLE_64B);
    {
        cuuint32_t box[4] = {32, 8, 7, 2}, es[4] = {1, 1, 1, 1};
        cuuint64_t d[4] = {96, 7, 7, 96}, st[3] = {18432, 7 * 18432, 192};
        fn(&mp.w, CU_TENSOR_MAP_DATA_TYPE_BFLOAT16, 4, d_in[1], d, st, box, es, CU_TENSOR_MAP_INTERLEAVE_NONE, CU_TENSOR_MAP_SWIZZLE_64B, CU_TENSOR_MAP_L2_PROMOTION_NONE, CU_TENSOR_MAP_FLOAT_OOB_FILL_NONE);
    }
    encode3(fn, &mp.wst, wf, 256, 200, 72, 36864, 512, 256, 8, 1, CU_TENSOR_MAP_SWIZZLE_NONE);
    encode3(fn, &mp.y4, d_out, 96, 224, 224, 192, 224 * 192, 32, 4, 28, CU_TENSOR_MAP_SWIZZLE_64B);
    encode3(fn, &mp.y2, d_out, 96, 224, 224, 192, 224 * 192, 32, 2, 28, CU_TENSOR_MAP_SWIZZLE_64B);
    constexpr int SMEM_LAUNCH = SMEM_BYTES;
    cudaFuncSetAttribute(fftconv_kernel, cudaFuncAttributeMaxDynamicSharedMemorySize, SMEM_LAUNCH);
    fftconv_kernel<<<NSM, 512, SMEM_LAUNCH>>>(pt, mp);
}
```

```cpp
#include <cuda_runtime.h>
#include <cuda_bf16.h>
#include <cuda.h>
#include <stdint.h>

__device__ __align__(128) const uint32_t TAB_P1[4480] = {
0x3e75,0,0x3e72,0,0x8000,0,0xbd19,0,0x3e750000,0,0x3e720000,0,0x80000000,0,0xbd190000,0,
0,0x3e75,0,0x3e72,0,0x8000,0,0xbd19,0,0x3e750000,0,0x3e720000,0,0x80000000,0,0xbd190000,
0x3e69,0,0x3e5a,0,0xbd97,0,0xbdde,0,0x3e690000,0,0x3e5a0000,0,0xbd970000,0,0xbdde0000,0,
0,0x3e69,0,0x3e5a,0,0xbd97,0,0xbdde,0,0x3e690000,0,0x3e5a0000,0,0xbd970000,0,0xbdde0000,
0x3e75,0,0x3e5a,0,0x8000,0,0xbdde,0,0x3e750000,0,0x3e5a0000,0,0x80000000,0,0xbdde0000,0,
0,0x3e75,0,0x3e5a,0,0x8000,0,0xbdde,0,0x3e750000,0,0x3e5a0000,0,0x80000000,0,0xbdde0000,
0x3e10,0,0x3d19,0,0xbe46,0,0xbe72,0,0x3e100000,0,0x3d190000,0,0xbe460000,0,0xbe720000,0,
0,0x3e10,0,0x3d19,0,0xbe46,0,0xbe72,0,0x3e100000,0,0x3d190000,0,0xbe460000,0,0xbe720000,
0x3e75,0,0x3e2d,0,0x8000,0,0xbe2d,0,0x3e750000,0,0x3e2d0000,0,0x80000000,0,0xbe2d0000,0,
0,0x3e75,0,0x3e2d,0,0x8000,0,0xbe2d,0,0x3e750000,0,0x3e2d0000,0,0x80000000,0,0xbe2d0000,
0,0,0xbe2d,0,0xbe75,0,0xbe2d,0,0,0,0xbe2d0000,0,0xbe750000,0,0xbe2d0000,0,
0,0,0,0xbe2d,0,0xbe75,0,0xbe2d,0,0,0,0xbe2d0000,0,0xbe750000,0,0xbe2d0000,
0x3e75,0,0x3dde,0,0x8000,0,0xbe5a,0,0x3e750000,0,0x3dde0000,0,0x80000000,0,0xbe5a0000,0,
0,0x3e75,0,0x3dde,0,0x8000,0,0xbe5a,0,0x3e750000,0,0x3dde0000,0,0x80000000,0,0xbe5a0000,
0xbe10,0,0xbe72,0,0xbe46,0,0x3d19,0,0xbe100000,0,0xbe720000,0,0xbe460000,0,0x3d190000,0,
0,0xbe10,0,0xbe72,0,0xbe46,0,0x3d19,0,0xbe100000,0,0xbe720000,0,0xbe460000,0,0x3d190000,
0x3e75,0,0x3d19,0,0x8000,0,0xbe72,0,0x3e750000,0,0x3d190000,0,0x80000000,0,0xbe720000,0,
0,0x3e75,0,0x3d19,0,0x8000,0,0xbe72,0,0x3e750000,0,0x3d190000,0,0x80000000,0,0xbe720000,
0xbe69,0,0xbdde,0,0xbd97,0,0x3e5a,0,0xbe690000,0,0xbdde0000,0,0xbd970000,0,0x3e5a0000,0,
0,0xbe69,0,0xbdde,0,0xbd97,0,0x3e5a,0,0xbe690000,0,0xbdde0000,0,0xbd970000,0,0x3e5a0000,
0x3e75,0,0xbd19,0,0x8000,0,0xbe72,0,0x3e750000,0,0xbd190000,0,0x80000000,0,0xbe720000,0,
0,0x3e75,0,0xbd19,0,0x8000,0,0xbe72,0,0x3e750000,0,0xbd190000,0,0x80000000,0,0xbe720000,
0xbe69,0,0x3dde,0,0x3d97,0,0x3e5a,0,0xbe690000,0,0x3dde0000,0,0x3d970000,0,0x3e5a0000,0,
0,0xbe69,0,0x3dde,0,0x3d97,0,0x3e5a,0,0xbe690000,0,0x3dde0000,0,0x3d970000,0,0x3e5a0000,
0x3e75,0,0xbdde,0,0x8000,0,0xbe5a,0,0x3e750000,0,0xbdde0000,0,0x80000000,0,0xbe5a0000,0,
0,0x3e75,0,0xbdde,0,0x8000,0,0xbe5a,0,0x3e750000,0,0xbdde0000,0,0x80000000,0,0xbe5a0000,
0xbe10,0,0x3e72,0,0x3e46,0,0x3d19,0,0xbe100000,0,0x3e720000,0,0x3e460000,0,0x3d190000,0,
0,0xbe10,0,0x3e72,0,0x3e46,0,0x3d19,0,0xbe100000,0,0x3e720000,0,0x3e460000,0,0x3d190000,
0x3e75,0,0xbe2d,0,0x8000,0,0xbe2d,0,0x3e750000,0,0xbe2d0000,0,0x80000000,0,0xbe2d0000,0,
0,0x3e75,0,0xbe2d,0,0x8000,0,0xbe2d,0,0x3e750000,0,0xbe2d0000,0,0x80000000,0,0xbe2d0000,
0,0,0x3e2d,0,0x3e75,0,0xbe2d,0,0,0,0x3e2d0000,0,0x3e750000,0,0xbe2d0000,0,
0,0,0,0x3e2d,0,0x3e75,0,0xbe2d,0,0,0,0x3e2d0000,0,0x3e750000,0,0xbe2d0000,
0x3e75,0,0xbe5a,0,0x8000,0,0xbdde,0,0x3e750000,0,0xbe5a0000,0,0x80000000,0,0xbdde0000,0,
0,0x3e75,0,0xbe5a,0,0x8000,0,0xbdde,0,0x3e750000,0,0xbe5a0000,0,0x80000000,0,0xbdde0000,
0x3e10,0,0xbd19,0,0x3e46,0,0xbe72,0,0x3e100000,0,0xbd190000,0,0x3e460000,0,0xbe720000,0,
0,0x3e10,0,0xbd19,0,0x3e46,0,0xbe72,0,0x3e100000,0,0xbd190000,0,0x3e460000,0,0xbe720000,
0x3e75,0,0xbe72,0,0x8000,0,0xbd19,0,0x3e750000,0,0xbe720000,0,0x80000000,0,0xbd190000,0,
0,0x3e75,0,0xbe72,0,0x8000,0,0xbd19,0,0x3e750000,0,0xbe720000,0,0x80000000,0,0xbd190000,
0x3e69,0,0xbe5a,0,0x3d97,0,0xbdde,0,0x3e690000,0,0xbe5a0000,0,0x3d970000,0,0xbdde0000,0,
0,0x3e69,0,0xbe5a,0,0x3d97,0,0xbdde,0,0x3e690000,0,0xbe5a0000,0,0x3d970000,0,0xbdde0000,
0x3e46,0,0x3e2d,0,0xbe10,0,0xbe2d,0,0x3e460000,0,0x3e2d0000,0,0xbe100000,0,0xbe2d0000,0,
0,0x3e46,0,0x3e2d,0,0xbe10,0,0xbe2d,0,0x3e460000,0,0x3e2d0000,0,0xbe100000,0,0xbe2d0000,
0x3e10,0,0x3dde,0,0xbe46,0,0xbe5a,0,0x3e100000,0,0x3dde0000,0,0xbe460000,0,0xbe5a0000,0,
0,0x3e10,0,0x3dde,0,0xbe46,0,0xbe5a,0,0x3e100000,0,0x3dde0000,0,0xbe460000,0,0xbe5a0000,
0xbd97,0,0xbe2d,0,0xbe69,0,0xbe2d,0,0xbd970000,0,0xbe2d0000,0,0xbe690000,0,0xbe2d0000,0,
0,0xbd97,0,0xbe2d,0,0xbe69,0,0xbe2d,0,0xbd970000,0,0xbe2d0000,0,0xbe690000,0,0xbe2d0000,
0xbe69,0,0xbe72,0,0xbd97,0,0x3d19,0,0xbe690000,0,0xbe720000,0,0xbd970000,0,0x3d190000,0,
0,0xbe69,0,0xbe72,0,0xbd97,0,0x3d19,0,0xbe690000,0,0xbe720000,0,0xbd970000,0,0x3d190000,
0xbe75,0,0xbe2d,0,0x8000,0,0x3e2d,0,0xbe750000,0,0xbe2d0000,0,0x80000000,0,0x3e2d0000,0,
0,0xbe75,0,0xbe2d,0,0x8000,0,0x3e2d,0,0xbe750000,0,0xbe2d0000,0,0x80000000,0,0x3e2d0000,
0,0,0x3e2d,0,0x3e75,0,0x3e2d,0,0,0,0x3e2d0000,0,0x3e750000,0,0x3e2d0000,0,
0,0,0,0x3e2d,0,0x3e75,0,0x3e2d,0,0,0,0x3e2d0000,0,0x3e750000,0,0x3e2d0000,
0xbd97,0,0x3e2d,0,0x3e69,0,0x3e2d,0,0xbd970000,0,0x3e2d0000,0,0x3e690000,0,0x3e2d0000,0,
0,0xbd97,0,0x3e2d,0,0x3e69,0,0x3e2d,0,0xbd970000,0,0x3e2d0000,0,0x3e690000,0,0x3e2d0000,
0x3e69,0,0x3d19,0,0xbd97,0,0xbe72,0,0x3e690000,0,0x3d190000,0,0xbd970000,0,0xbe720000,0,
0,0x3e69,0,0x3d19,0,0xbd97,0,0xbe72,0,0x3e690000,0,0x3d190000,0,0xbd970000,0,0xbe720000,
0x3e46,0,0x3e2d,0,0x3e10,0,0xbe2d,0,0x3e460000,0,0x3e2d0000,0,0x3e100000,0,0xbe2d0000,0,
0,0x3e46,0,0x3e2d,0,0x3e10,0,0xbe2d,0,0x3e460000,0,0x3e2d0000,0,0x3e100000,0,0xbe2d0000,
0xbe10,0,0xbe5a,0,0xbe46,0,0x3dde,0,0xbe100000,0,0xbe5a0000,0,0xbe460000,0,0x3dde0000,0,
0,0xbe10,0,0xbe5a,0,0xbe46,0,0x3dde,0,0xbe100000,0,0xbe5a0000,0,0xbe460000,0,0x3dde0000,
0x3e46,0,0xbe2d,0,0xbe10,0,0xbe2d,0,0x3e460000,0,0xbe2d0000,0,0xbe100000,0,0xbe2d0000,0,
0,0x3e46,0,0xbe2d,0,0xbe10,0,0xbe2d,0,0x3e460000,0,0xbe2d0000,0,0xbe100000,0,0xbe2d0000,
0xbe10,0,0x3e5a,0,0x3e46,0,0x3dde,0,0xbe100000,0,0x3e5a0000,0,0x3e460000,0,0x3dde0000,0,
0,0xbe10,0,0x3e5a,0,0x3e46,0,0x3dde,0,0xbe100000,0,0x3e5a0000,0,0x3e460000,0,0x3dde0000,
0xbd97,0,0xbe2d,0,0xbe69,0,0x3e2d,0,0xbd970000,0,0xbe2d0000,0,0xbe690000,0,0x3e2d0000,0,
0,0xbd97,0,0xbe2d,0,0xbe69,0,0x3e2d,0,0xbd970000,0,0xbe2d0000,0,0xbe690000,0,0x3e2d0000,
0x3e69,0,0xbd19,0,0x3d97,0,0xbe72,0,0x3e690000,0,0xbd190000,0,0x3d970000,0,0xbe720000,0,
0,0x3e69,0,0xbd19,0,0x3d97,0,0xbe72,0,0x3e690000,0,0xbd190000,0,0x3d970000,0,0xbe720000,
0xbe75,0,0x3e2d,0,0x8000,0,0x3e2d,0,0xbe750000,0,0x3e2d0000,0,0x80000000,0,0x3e2d0000,0,
0,0xbe75,0,0x3e2d,0,0x8000,0,0x3e2d,0,0xbe750000,0,0x3e2d0000,0,0x80000000,0,0x3e2d0000,
0,0,0xbe2d,0,0xbe75,0,0x3e2d,0,0,0,0xbe2d0000,0,0xbe750000,0,0x3e2d0000,0,
0,0,0,0xbe2d,0,0xbe75,0,0x3e2d,0,0,0,0xbe2d0000,0,0xbe750000,0,0x3e2d0000,
0xbd97,0,0x3e2d,0,0x3e69,0,0xbe2d,0,0xbd970000,0,0x3e2d0000,0,0x3e690000,0,0xbe2d0000,0,
0,0xbd97,0,0x3e2d,0,0x3e69,0,0xbe2d,0,0xbd970000,0,0x3e2d0000,0,0x3e690000,0,0xbe2d0000,
0xbe69,0,0x3e72,0,0x3d97,0,0x3d19,0,0xbe690000,0,0x3e720000,0,0x3d970000,0,0x3d190000,0,
0,0xbe69,0,0x3e72,0,0x3d97,0,0x3d19,0,0xbe690000,0,0x3e720000,0,0x3d970000,0,0x3d190000,
0x3e46,0,0xbe2d,0,0x3e10,0,0xbe2d,0,0x3e460000,0,0xbe2d0000,0,0x3e100000,0,0xbe2d0000,0,
0,0x3e46,0,0xbe2d,0,0x3e10,0,0xbe2d,0,0x3e460000,0,0xbe2d0000,0,0x3e100000,0,0xbe2d0000,
0x3e10,0,0xbdde,0,0x3e46,0,0xbe5a,0,0x3e100000,0,0xbdde0000,0,0x3e460000,0,0xbe5a0000,0,
0,0x3e10,0,0xbdde,0,0x3e46,0,0xbe5a,0,0x3e100000,0,0xbdde0000,0,0x3e460000,0,0xbe5a0000,
0x3d97,0,0x3d19,0,0xbe69,0,0xbe72,0,0x3d970000,0,0x3d190000,0,0xbe690000,0,0xbe720000,0,
0,0x3d97,0,0x3d19,0,0xbe69,0,0xbe72,0,0x3d970000,0,0x3d190000,0,0xbe690000,0,0xbe720000,
0,0,0xbd19,0,0xbe75,0,0xbe72,0,0,0,0xbd190000,0,0xbe750000,0,0xbe720000,0,
0,0,0,0xbd19,0,0xbe75,0,0xbe72,0,0,0,0xbd190000,0,0xbe750000,0,0xbe720000,
0xbe46,0,0xbdde,0,0x3e10,0,0x3e5a,0,0xbe460000,0,0xbdde0000,0,0x3e100000,0,0x3e5a0000,0,
0,0xbe46,0,0xbdde,0,0x3e10,0,0x3e5a,0,0xbe460000,0,0xbdde0000,0,0x3e100000,0,0x3e5a0000,
0,0,0x3dde,0,0x3e75,0,0x3e5a,0,0,0,0x3dde0000,0,0x3e750000,0,0x3e5a0000,0,
0,0,0,0x3dde,0,0x3e75,0,0x3e5a,0,0,0,0x3dde0000,0,0x3e750000,0,0x3e5a0000,
0x3e75,0,0x3e2d,0,0x8000,0,0xbe2d,0,0x3e750000,0,0x3e2d0000,0,0x80000000,0,0xbe2d0000,0,
0,0x3e75,0,0x3e2d,0,0x8000,0,0xbe2d,0,0x3e750000,0,0x3e2d0000,0,0x80000000,0,0xbe2d0000,
0,0,0xbe2d,0,0xbe75,0,0xbe2d,0,0,0,0xbe2d0000,0,0xbe750000,0,0xbe2d0000,0,
0,0,0,0xbe2d,0,0xbe75,0,0xbe2d,0,0,0,0xbe2d0000,0,0xbe750000,0,0xbe2d0000,
0xbe46,0,0xbe5a,0,0xbe10,0,0x3dde,0,0xbe460000,0,0xbe5a0000,0,0xbe100000,0,0x3dde0000,0,
0,0xbe46,0,0xbe5a,0,0xbe10,0,0x3dde,0,0xbe460000,0,0xbe5a0000,0,0xbe100000,0,0x3dde0000,
0,0,0x3e5a,0,0x3e75,0,0x3dde,0,0,0,0x3e5a0000,0,0x3e750000,0,0x3dde0000,0,
0,0,0,0x3e5a,0,0x3e75,0,0x3dde,0,0,0,0x3e5a0000,0,0x3e750000,0,0x3dde0000,
0x3d97,0,0x3e72,0,0x3e69,0,0xbd19,0,0x3d970000,0,0x3e720000,0,0x3e690000,0,0xbd190000,0,
0,0x3d97,0,0x3e72,0,0x3e69,0,0xbd19,0,0x3d970000,0,0x3e720000,0,0x3e690000,0,0xbd190000,
0,0,0xbe72,0,0xbe75,0,0xbd19,0,0,0,0xbe720000,0,0xbe750000,0,0xbd190000,0,
0,0,0,0xbe72,0,0xbe75,0,0xbd19,0,0,0,0xbe720000,0,0xbe750000,0,0xbd190000,
0x3d97,0,0xbe72,0,0xbe69,0,0xbd19,0,0x3d970000,0,0xbe720000,0,0xbe690000,0,0xbd190000,0,
0,0x3d97,0,0xbe72,0,0xbe69,0,0xbd19,0,0x3d970000,0,0xbe720000,0,0xbe690000,0,0xbd190000,
0,0,0x3e72,0,0x3e75,0,0xbd19,0,0,0,0x3e720000,0,0x3e750000,0,0xbd190000,0,
0,0,0,0x3e72,0,0x3e75,0,0xbd19,0,0,0,0x3e720000,0,0x3e750000,0,0xbd190000,
0xbe46,0,0x3e5a,0,0x3e10,0,0x3dde,0,0xbe460000,0,0x3e5a0000,0,0x3e100000,0,0x3dde0000,0,
0,0xbe46,0,0x3e5a,0,0x3e10,0,0x3dde,0,0xbe460000,0,0x3e5a0000,0,0x3e100000,0,0x3dde0000,
0,0,0xbe5a,0,0xbe75,0,0x3dde,0,0,0,0xbe5a0000,0,0xbe750000,0,0x3dde0000,0,
0,0,0,0xbe5a,0,0xbe75,0,0x3dde,0,0,0,0xbe5a0000,0,0xbe750000,0,0x3dde0000,
0x3e75,0,0xbe2d,0,0x8000,0,0xbe2d,0,0x3e750000,0,0xbe2d0000,0,0x80000000,0,0xbe2d0000,0,
0,0x3e75,0,0xbe2d,0,0x8000,0,0xbe2d,0,0x3e750000,0,0xbe2d0000,0,0x80000000,0,0xbe2d0000,
0,0,0x3e2d,0,0x3e75,0,0xbe2d,0,0,0,0x3e2d0000,0,0x3e750000,0,0xbe2d0000,0,
0,0,0,0x3e2d,0,0x3e75,0,0xbe2d,0,0,0,0x3e2d0000,0,0x3e750000,0,0xbe2d0000,
0xbe46,0,0x3dde,0,0xbe10,0,0x3e5a,0,0xbe460000,0,0x3dde0000,0,0xbe100000,0,0x3e5a0000,0,
0,0xbe46,0,0x3dde,0,0xbe10,0,0x3e5a,0,0xbe460000,0,0x3dde0000,0,0xbe100000,0,0x3e5a0000,
0,0,0xbdde,0,0xbe75,0,0x3e5a,0,0,0,0xbdde0000,0,0xbe750000,0,0x3e5a0000,0,
0,0,0,0xbdde,0,0xbe75,0,0x3e5a,0,0,0,0xbdde0000,0,0xbe750000,0,0x3e5a0000,
0x3d97,0,0xbd19,0,0x3e69,0,0xbe72,0,0x3d970000,0,0xbd190000,0,0x3e690000,0,0xbe720000,0,
0,0x3d97,0,0xbd19,0,0x3e69,0,0xbe72,0,0x3d970000,0,0xbd190000,0,0x3e690000,0,0xbe720000,
0,0,0x3d19,0,0x3e75,0,0xbe72,0,0,0,0x3d190000,0,0x3e750000,0,0xbe720000,0,
0,0,0,0x3d19,0,0x3e75,0,0xbe72,0,0,0,0x3d190000,0,0x3e750000,0,0xbe720000,
0xbd97,0,0xbdde,0,0xbe69,0,0xbe5a,0,0xbd970000,0,0xbdde0000,0,0xbe690000,0,0xbe5a0000,0,
0,0xbd97,0,0xbdde,0,0xbe69,0,0xbe5a,0,0xbd970000,0,0xbdde0000,0,0xbe690000,0,0xbe5a0000,
0xbe10,0,0xbe2d,0,0xbe46,0,0xbe2d,0,0xbe100000,0,0xbe2d0000,0,0xbe460000,0,0xbe2d0000,0,
0,0xbe10,0,0xbe2d,0,0xbe46,0,0xbe2d,0,0xbe100000,0,0xbe2d0000,0,0xbe460000,0,0xbe2d0000,
0x3e46,0,0x3e72,0,0x3e10,0,0x3d19,0,0x3e460000,0,0x3e720000,0,0x3e100000,0,0x3d190000,0,
0,0x3e46,0,0x3e72,0,0x3e10,0,0x3d19,0,0x3e460000,0,0x3e720000,0,0x3e100000,0,0x3d190000,
0x3e69,0,0x3e2d,0,0xbd97,0,0xbe2d,0,0x3e690000,0,0x3e2d0000,0,0xbd970000,0,0xbe2d0000,0,
0,0x3e69,0,0x3e2d,0,0xbd97,0,0xbe2d,0,0x3e690000,0,0x3e2d0000,0,0xbd970000,0,0xbe2d0000,
0xbe75,0,0xbe2d,0,0x8000,0,0x3e2d,0,0xbe750000,0,0xbe2d0000,0,0x80000000,0,0x3e2d0000,0,
0,0xbe75,0,0xbe2d,0,0x8000,0,0x3e2d,0,0xbe750000,0,0xbe2d0000,0,0x80000000,0,0x3e2d0000,
0,0,0x3e2d,0,0x3e75,0,0x3e2d,0,0,0,0x3e2d0000,0,0x3e750000,0,0x3e2d0000,0,
0,0,0,0x3e2d,0,0x3e75,0,0x3e2d,0,0,0,0x3e2d0000,0,0x3e750000,0,0x3e2d0000,
0x3e46,0,0xbd19,0,0xbe10,0,0xbe72,0,0x3e460000,0,0xbd190000,0,0xbe100000,0,0xbe720000,0,
0,0x3e46,0,0xbd19,0,0xbe10,0,0xbe72,0,0x3e460000,0,0xbd190000,0,0xbe100000,0,0xbe720000,
0xbe69,0,0xbe2d,0,0xbd97,0,0x3e2d,0,0xbe690000,0,0xbe2d0000,0,0xbd970000,0,0x3e2d0000,0,
0,0xbe69,0,0xbe2d,0,0xbd97,0,0x3e2d,0,0xbe690000,0,0xbe2d0000,0,0xbd970000,0,0x3e2d0000,
0xbd97,0,0x3e5a,0,0x3e69,0,0x3dde,0,0xbd970000,0,0x3e5a0000,0,0x3e690000,0,0x3dde0000,0,
0,0xbd97,0,0x3e5a,0,0x3e69,0,0x3dde,0,0xbd970000,0,0x3e5a0000,0,0x3e690000,0,0x3dde0000,
0x3e10,0,0xbe2d,0,0xbe46,0,0xbe2d,0,0x3e100000,0,0xbe2d0000,0,0xbe460000,0,0xbe2d0000,0,
0,0x3e10,0,0xbe2d,0,0xbe46,0,0xbe2d,0,0x3e100000,0,0xbe2d0000,0,0xbe460000,0,0xbe2d0000,
0xbd97,0,0xbe5a,0,0xbe69,0,0x3dde,0,0xbd970000,0,0xbe5a0000,0,0xbe690000,0,0x3dde0000,0,
0,0xbd97,0,0xbe5a,0,0xbe69,0,0x3dde,0,0xbd970000,0,0xbe5a0000,0,0xbe690000,0,0x3dde0000,
0x3e10,0,0x3e2d,0,0x3e46,0,0xbe2d,0,0x3e100000,0,0x3e2d0000,0,0x3e460000,0,0xbe2d0000,0,
0,0x3e10,0,0x3e2d,0,0x3e46,0,0xbe2d,0,0x3e100000,0,0x3e2d0000,0,0x3e460000,0,0xbe2d0000,
0x3e46,0,0x3d19,0,0x3e10,0,0xbe72,0,0x3e460000,0,0x3d190000,0,0x3e100000,0,0xbe720000,0,
0,0x3e46,0,0x3d19,0,0x3e10,0,0xbe72,0,0x3e460000,0,0x3d190000,0,0x3e100000,0,0xbe720000,
0xbe69,0,0x3e2d,0,0x3d97,0,0x3e2d,0,0xbe690000,0,0x3e2d0000,0,0x3d970000,0,0x3e2d0000,0,
0,0xbe69,0,0x3e2d,0,0x3d97,0,0x3e2d,0,0xbe690000,0,0x3e2d0000,0,0x3d970000,0,0x3e2d0000,
0xbe75,0,0x3e2d,0,0x8000,0,0x3e2d,0,0xbe750000,0,0x3e2d0000,0,0x80000000,0,0x3e2d0000,0,
0,0xbe75,0,0x3e2d,0,0x8000,0,0x3e2d,0,0xbe750000,0,0x3e2d0000,0,0x80000000,0,0x3e2d0000,
0,0,0xbe2d,0,0xbe75,0,0x3e2d,0,0,0,0xbe2d0000,0,0xbe750000,0,0x3e2d0000,0,
0,0,0,0xbe2d,0,0xbe75,0,0x3e2d,0,0,0,0xbe2d0000,0,0xbe750000,0,0x3e2d0000,
0x3e46,0,0xbe72,0,0xbe10,0,0x3d19,0,0x3e460000,0,0xbe720000,0,0xbe100000,0,0x3d190000,0,
0,0x3e46,0,0xbe72,0,0xbe10,0,0x3d19,0,0x3e460000,0,0xbe720000,0,0xbe100000,0,0x3d190000,
0x3e69,0,0xbe2d,0,0x3d97,0,0xbe2d,0,0x3e690000,0,0xbe2d0000,0,0x3d970000,0,0xbe2d0000,0,
0,0x3e69,0,0xbe2d,0,0x3d97,0,0xbe2d,0,0x3e690000,0,0xbe2d0000,0,0x3d970000,0,0xbe2d0000,
0xbd97,0,0x3dde,0,0x3e69,0,0xbe5a,0,0xbd970000,0,0x3dde0000,0,0x3e690000,0,0xbe5a0000,0,
0,0xbd97,0,0x3dde,0,0x3e69,0,0xbe5a,0,0xbd970000,0,0x3dde0000,0,0x3e690000,0,0xbe5a0000,
0xbe10,0,0x3e2d,0,0x3e46,0,0xbe2d,0,0xbe100000,0,0x3e2d0000,0,0x3e460000,0,0xbe2d0000,0,
0,0xbe10,0,0x3e2d,0,0x3e46,0,0xbe2d,0,0xbe100000,0,0x3e2d0000,0,0x3e460000,0,0xbe2d0000,
0xbe46,0,0xbe5a,0,0xbe10,0,0xbdde,0,0xbe460000,0,0xbe5a0000,0,0xbe100000,0,0xbdde0000,0,
0,0xbe46,0,0xbe5a,0,0xbe10,0,0xbdde,0,0xbe460000,0,0xbe5a0000,0,0xbe100000,0,0xbdde0000,
0xbe69,0,0xbe72,0,0xbd97,0,0xbd19,0,0xbe690000,0,0xbe720000,0,0xbd970000,0,0xbd190000,0,
0,0xbe69,0,0xbe72,0,0xbd97,0,0xbd19,0,0xbe690000,0,0xbe720000,0,0xbd970000,0,0xbd190000,
0x3d97,0,0xbd19,0,0xbe69,0,0xbe72,0,0x3d970000,0,0xbd190000,0,0xbe690000,0,0xbe720000,0,
0,0x3d97,0,0xbd19,0,0xbe69,0,0xbe72,0,0x3d970000,0,0xbd190000,0,0xbe690000,0,0xbe720000,
0xbe10,0,0xbe5a,0,0xbe46,0,0xbdde,0,0xbe100000,0,0xbe5a0000,0,0xbe460000,0,0xbdde0000,0,
0,0xbe10,0,0xbe5a,0,0xbe46,0,0xbdde,0,0xbe100000,0,0xbe5a0000,0,0xbe460000,0,0xbdde0000,
0x3e75,0,0x3e2d,0,0x8000,0,0xbe2d,0,0x3e750000,0,0x3e2d0000,0,0x80000000,0,0xbe2d0000,0,
0,0x3e75,0,0x3e2d,0,0x8000,0,0xbe2d,0,0x3e750000,0,0x3e2d0000,0,0x80000000,0,0xbe2d0000,
0,0,0xbe2d,0,0xbe75,0,0xbe2d,0,0,0,0xbe2d0000,0,0xbe750000,0,0xbe2d0000,0,
0,0,0,0xbe2d,0,0xbe75,0,0xbe2d,0,0,0,0xbe2d0000,0,0xbe750000,0,0xbe2d0000,
0x3d97,0,0x3e72,0,0x3e69,0,0x3d19,0,0x3d970000,0,0x3e720000,0,0x3e690000,0,0x3d190000,0,
0,0x3d97,0,0x3e72,0,0x3e69,0,0x3d19,0,0x3d970000,0,0x3e720000,0,0x3e690000,0,0x3d190000,
0x3e10,0,0xbdde,0,0xbe46,0,0xbe5a,0,0x3e100000,0,0xbdde0000,0,0xbe460000,0,0xbe5a0000,0,
0,0x3e10,0,0xbdde,0,0xbe46,0,0xbe5a,0,0x3e100000,0,0xbdde0000,0,0xbe460000,0,0xbe5a0000,
0xbe46,0,0x3dde,0,0x3e10,0,0x3e5a,0,0xbe460000,0,0x3dde0000,0,0x3e100000,0,0x3e5a0000,0,
0,0xbe46,0,0x3dde,0,0x3e10,0,0x3e5a,0,0xbe460000,0,0x3dde0000,0,0x3e100000,0,0x3e5a0000,
0x3e69,0,0xbd19,0,0xbd97,0,0xbe72,0,0x3e690000,0,0xbd190000,0,0xbd970000,0,0xbe720000,0,
0,0x3e69,0,0xbd19,0,0xbd97,0,0xbe72,0,0x3e690000,0,0xbd190000,0,0xbd970000,0,0xbe720000,
0xbe46,0,0xbdde,0,0xbe10,0,0x3e5a,0,0xbe460000,0,0xbdde0000,0,0xbe100000,0,0x3e5a0000,0,
0,0xbe46,0,0xbdde,0,0xbe10,0,0x3e5a,0,0xbe460000,0,0xbdde0000,0,0xbe100000,0,0x3e5a0000,
0x3e69,0,0x3d19,0,0x3d97,0,0xbe72,0,0x3e690000,0,0x3d190000,0,0x3d970000,0,0xbe720000,0,
0,0x3e69,0,0x3d19,0,0x3d97,0,0xbe72,0,0x3e690000,0,0x3d190000,0,0x3d970000,0,0xbe720000,
0x3d97,0,0xbe72,0,0xbe69,0,0x3d19,0,0x3d970000,0,0xbe720000,0,0xbe690000,0,0x3d190000,0,
0,0x3d97,0,0xbe72,0,0xbe69,0,0x3d19,0,0x3d970000,0,0xbe720000,0,0xbe690000,0,0x3d190000,
0x3e10,0,0x3dde,0,0x3e46,0,0xbe5a,0,0x3e100000,0,0x3dde0000,0,0x3e460000,0,0xbe5a0000,0,
0,0x3e10,0,0x3dde,0,0x3e46,0,0xbe5a,0,0x3e100000,0,0x3dde0000,0,0x3e460000,0,0xbe5a0000,
0x3e75,0,0xbe2d,0,0x8000,0,0xbe2d,0,0x3e750000,0,0xbe2d0000,0,0x80000000,0,0xbe2d0000,0,
0,0x3e75,0,0xbe2d,0,0x8000,0,0xbe2d,0,0x3e750000,0,0xbe2d0000,0,0x80000000,0,0xbe2d0000,
0,0,0x3e2d,0,0x3e75,0,0xbe2d,0,0,0,0x3e2d0000,0,0x3e750000,0,0xbe2d0000,0,
0,0,0,0x3e2d,0,0x3e75,0,0xbe2d,0,0,0,0x3e2d0000,0,0x3e750000,0,0xbe2d0000,
0x3d97,0,0x3d19,0,0x3e69,0,0xbe72,0,0x3d970000,0,0x3d190000,0,0x3e690000,0,0xbe720000,0,
0,0x3d97,0,0x3d19,0,0x3e69,0,0xbe72,0,0x3d970000,0,0x3d190000,0,0x3e690000,0,0xbe720000,
0xbe10,0,0x3e5a,0,0x3e46,0,0xbdde,0,0xbe100000,0,0x3e5a0000,0,0x3e460000,0,0xbdde0000,0,
0,0xbe10,0,0x3e5a,0,0x3e46,0,0xbdde,0,0xbe100000,0,0x3e5a0000,0,0x3e460000,0,0xbdde0000,
0xbe46,0,0x3e5a,0,0x3e10,0,0xbdde,0,0xbe460000,0,0x3e5a0000,0,0x3e100000,0,0xbdde0000,0,
0,0xbe46,0,0x3e5a,0,0x3e10,0,0xbdde,0,0xbe460000,0,0x3e5a0000,0,0x3e100000,0,0xbdde0000,
0xbe69,0,0x3e72,0,0x3d97,0,0xbd19,0,0xbe690000,0,0x3e720000,0,0x3d970000,0,0xbd190000,0,
0,0xbe69,0,0x3e72,0,0x3d97,0,0xbd19,0,0xbe690000,0,0x3e720000,0,0x3d970000,0,0xbd190000,
0x3eb7,0x3eb7,0x3eb7,0x3eb7,0x3eb78000,0x3eb78000,0x3eb78000,0x3eb78000,0x3eb7,0x3de23eae,0x3e573e94,0x3e943e57,0x3eb78000,0x3eaebde2,0x3e94be57,0x3e57be94,
0x3eb7,0x3e573e94,0x3eae3de2,0x3eaebde2,0x3eb78000,0x3e94be57,0x3de2beae,0xbde2beae,0x3eb7,0x3e943e57,0x3eaebde2,0x3de2beae,0x3eb78000,0x3e57be94,0xbde2beae,0xbeaebde2,
0x3eb7,0x3eb7,0x3eb7,0x3eb7,0x3eb78000,0x3eb78000,0x3eb78000,0x3eb78000,0x3eae3de2,0x3eb70000,0x3eaebde2,0x3e94be57,0x3de2beae,0xbeb7,0xbde2beae,0xbe57be94,
0x3e57be94,0xbeb7,0xbe57be94,0xbeaebde2,0xbe94be57,0xbeb78000,0xbe943e57,0xbde23eae,0xbe57be94,0xbeb70000,0xbe573e94,0x3de23eae,0xbe943e57,0x3eb7,0x3e943e57,0x3eaebde2,
0x3eb7,0x3eae3de2,0x3e57be94,0xbe57be94,0x3eb78000,0x3de2beae,0xbe94be57,0xbe943e57,0x3eb7,0x3eb70000,0xbeb7,0xbeb70000,0x3eb78000,0xbeb7,0xbeb78000,0x3eb7,
0x3eb7,0x3eaebde2,0xbe57be94,0xbe573e94,0x3eb78000,0xbde2beae,0xbe943e57,0x3e943e57,0x3eb7,0x3e94be57,0xbeaebde2,0x3de23eae,0x3eb78000,0xbe57be94,0xbde23eae,0x3eaebde2,
0xbeae3de2,0x3eb7,0x3eae3de2,0x3e57be94,0x3de23eae,0x3eb78000,0x3de2beae,0xbe94be57,0x3eb7,0x3eb70000,0xbeb7,0xbeb70000,0x3eb78000,0xbeb7,0xbeb78000,0x3eb7,
0x3eae3de2,0xbeb7,0xbeae3de2,0x3e573e94,0x3de2beae,0xbeb78000,0x3de23eae,0x3e94be57,0x3e57be94,0xbeb70000,0x3e573e94,0x3de2beae,0xbe94be57,0x3eb7,0x3e94be57,0xbeaebde2,
0x3eb7,0x3e57be94,0xbeae3de2,0x3eae3de2,0x3eb78000,0xbe94be57,0x3de23eae,0x3de2beae,0x3eb7,0x3de2beae,0xbe573e94,0x3e94be57,0x3eb78000,0xbeaebde2,0x3e943e57,0xbe57be94,
0x3eb7,0xbeb7,0x3eb7,0xbeb7,0x3eb78000,0xbeb78000,0x3eb78000,0xbeb78000,0x3eb7,0xbde2beae,0x3e573e94,0xbe94be57,0x3eb78000,0xbeae3de2,0x3e94be57,0xbe573e94,
0xbe57be94,0x3eb7,0x3e57be94,0xbeae3de2,0xbe943e57,0x3eb78000,0xbe94be57,0x3de23eae,0xbeae3de2,0x3eb70000,0xbeaebde2,0x3e943e57,0x3de23eae,0xbeb7,0xbde23eae,0x3e57be94,
0x3eb7,0xbeb7,0x3eb7,0xbeb7,0x3eb78000,0xbeb78000,0x3eb78000,0xbeb78000,0x3eae3de2,0xbeb70000,0x3eaebde2,0xbe943e57,0x3de2beae,0x3eb7,0xbde2beae,0x3e573e94,
0x3eb7,0xbe57be94,0x3eae3de2,0xbeae3de2,0x3eb78000,0xbe943e57,0x3de2beae,0x3de23eae,0x3eb7,0xbe94be57,0x3eaebde2,0xbde23eae,0x3eb78000,0xbe573e94,0xbde2beae,0x3eae3de2,
0x3eb7,0xbeaebde2,0x3e57be94,0x3e573e94,0x3eb78000,0xbde23eae,0xbe94be57,0x3e94be57,0x3eb7,0xbeb70000,0xbeb7,0x3eb70000,0x3eb78000,0x3eb7,0xbeb78000,0xbeb7,
0x3e57be94,0x3eb7,0xbe57be94,0x3eae3de2,0xbe94be57,0x3eb78000,0xbe943e57,0x3de2beae,0xbe57be94,0x3eb70000,0xbe573e94,0xbde2beae,0xbe943e57,0xbeb7,0x3e943e57,0xbeae3de2,
0xbeae3de2,0xbeb7,0x3eae3de2,0xbe573e94,0x3de23eae,0xbeb78000,0x3de2beae,0x3e943e57,0x3eb7,0xbeb70000,0xbeb7,0x3eb70000,0x3eb78000,0x3eb7,0xbeb78000,0xbeb7,
0x3eb7,0xbeae3de2,0xbe57be94,0x3e57be94,0x3eb78000,0x3de23eae,0xbe943e57,0xbe94be57,0x3eb7,0xbe943e57,0xbeaebde2,0xbde2beae,0x3eb78000,0x3e573e94,0xbde23eae,0xbeae3de2,
0x3eb7,0xbe573e94,0xbeae3de2,0xbeaebde2,0x3eb78000,0x3e943e57,0x3de23eae,0xbde23eae,0x3eb7,0xbde23eae,0xbe573e94,0xbe943e57,0x3eb78000,0x3eae3de2,0x3e943e57,0x3e573e94,
0x3eae3de2,0x3eb7,0xbeae3de2,0xbe57be94,0x3de2beae,0x3eb78000,0x3de23eae,0xbe943e57,0x3e57be94,0x3eb70000,0x3e573e94,0xbde23eae,0xbe94be57,0xbeb7,0x3e94be57,0x3eae3de2,
0xbe57be94,0xbeb7,0x3e57be94,0x3eaebde2,0xbe943e57,0xbeb78000,0xbe94be57,0xbde2beae,0xbeae3de2,0xbeb70000,0xbeaebde2,0xbe94be57,0x3de23eae,0x3eb7,0xbde23eae,0xbe573e94,
0x3eb7,0x3eb7,0x3eb7,0x3eb7,0x3eb78000,0x3eb78000,0x3eb78000,0x3eb78000,0x3e57be94,0x3de2beae,0xbeb7,0xbde2beae,0xbe94be57,0xbeaebde2,0xbeb78000,0xbeae3de2,
0xbeae3de2,0xbe573e94,0x3eb7,0x3e573e94,0x3de23eae,0x3e943e57,0x3eb78000,0x3e94be57,0x3eae3de2,0x3e94be57,0xbeb7,0xbe94be57,0x3de2beae,0xbe57be94,0xbeb78000,0xbe573e94,
0x3eb7,0x3eb7,0x3eb7,0x3eb7,0x3eb78000,0x3eb78000,0x3eb78000,0x3eb78000,0xbe57be94,0xbe94be57,0xbeaebde2,0xbeb70000,0xbe943e57,0xbe573e94,0xbde23eae,0x3eb7,
0x3eae3de2,0x3eaebde2,0x3e57be94,0xbeb7,0x3de2beae,0xbde2beae,0xbe94be57,0xbeb78000,0xbeae3de2,0xbde23eae,0x3e573e94,0x3eb70000,0x3de23eae,0x3eae3de2,0x3e94be57,0xbeb7,
0xbe57be94,0xbeae3de2,0x3eb7,0x3eae3de2,0xbe943e57,0x3de23eae,0x3eb78000,0x3de2beae,0x3eb7,0x3eb70000,0xbeb7,0xbeb70000,0x3eb78000,0xbeb7,0xbeb78000,0x3eb7,
0x3e57be94,0xbeaebde2,0x3eb7,0x3eaebde2,0xbe94be57,0xbde23eae,0x3eb78000,0xbde2beae,0xbeae3de2,0x3e943e57,0xbeb7,0xbe943e57,0x3de23eae,0x3e57be94,0xbeb78000,0x3e573e94,
0x3e57be94,0xbe57be94,0xbeae3de2,0x3eb7,0xbe94be57,0xbe943e57,0x3de23eae,0x3eb78000,0x3eb7,0x3eb70000,0xbeb7,0xbeb70000,0x3eb78000,0xbeb7,0xbeb78000,0x3eb7,
0xbe57be94,0xbe573e94,0x3eae3de2,0xbeb7,0xbe943e57,0x3e943e57,0x3de2beae,0xbeb78000,0x3eae3de2,0xbde2beae,0xbe573e94,0x3eb70000,0x3de2beae,0xbeae3de2,0x3e943e57,0xbeb7,
0x3eae3de2,0xbe57be94,0x3eb7,0x3e57be94,0x3de2beae,0xbe943e57,0x3eb78000,0xbe94be57,0xbe57be94,0x3de23eae,0xbeb7,0xbde23eae,0xbe943e57,0x3eaebde2,0xbeb78000,0x3eae3de2,
0x3eb7,0xbeb7,0x3eb7,0xbeb7,0x3eb78000,0xbeb78000,0x3eb78000,0xbeb78000,0x3e57be94,0xbde23eae,0xbeb7,0x3de23eae,0xbe94be57,0x3eae3de2,0xbeb78000,0x3eaebde2,
0xbeae3de2,0x3eae3de2,0xbe57be94,0x3eb7,0x3de23eae,0x3de2beae,0xbe943e57,0x3eb78000,0x3e57be94,0xbe943e57,0x3eaebde2,0xbeb70000,0xbe94be57,0x3e573e94,0xbde2beae,0x3eb7,
0x3eb7,0xbeb7,0x3eb7,0xbeb7,0x3eb78000,0xbeb78000,0x3eb78000,0xbeb78000,0xbe57be94,0x3e943e57,0xbeaebde2,0x3eb70000,0xbe943e57,0x3e57be94,0xbde23eae,0xbeb7,
0xbeae3de2,0x3e57be94,0x3eb7,0xbe57be94,0x3de23eae,0xbe94be57,0x3eb78000,0xbe943e57,0x3eae3de2,0xbe943e57,0xbeb7,0x3e943e57,0x3de2beae,0x3e573e94,0xbeb78000,0x3e57be94,
0xbe57be94,0x3eaebde2,0x3eb7,0xbeaebde2,0xbe943e57,0xbde2beae,0x3eb78000,0xbde23eae,0x3eb7,0xbeb70000,0xbeb7,0x3eb70000,0x3eb78000,0x3eb7,0xbeb78000,0xbeb7,
0x3eae3de2,0xbeae3de2,0x3e57be94,0x3eb7,0x3de2beae,0x3de23eae,0xbe94be57,0x3eb78000,0xbeae3de2,0x3de2beae,0x3e573e94,0xbeb70000,0x3de23eae,0xbeaebde2,0x3e94be57,0x3eb7,
0x3e57be94,0x3e573e94,0xbeae3de2,0xbeb7,0xbe94be57,0x3e94be57,0x3de23eae,0xbeb78000,0x3eb7,0xbeb70000,0xbeb7,0x3eb70000,0x3eb78000,0x3eb7,0xbeb78000,0xbeb7,
0x3e57be94,0x3eae3de2,0x3eb7,0xbeae3de2,0xbe94be57,0x3de2beae,0x3eb78000,0x3de23eae,0xbeae3de2,0xbe94be57,0xbeb7,0x3e94be57,0x3de23eae,0xbe573e94,0xbeb78000,0xbe57be94,
0x3eae3de2,0x3e573e94,0x3eb7,0xbe573e94,0x3de2beae,0x3e94be57,0x3eb78000,0x3e943e57,0xbe57be94,0xbde2beae,0xbeb7,0x3de2beae,0xbe943e57,0xbeae3de2,0xbeb78000,0xbeaebde2,
0xbe57be94,0x3e57be94,0x3eae3de2,0x3eb7,0xbe943e57,0xbe94be57,0x3de2beae,0x3eb78000,0x3eae3de2,0x3de23eae,0xbe573e94,0xbeb70000,0x3de2beae,0x3eaebde2,0x3e943e57,0x3eb7,
0xbeae3de2,0xbeaebde2,0xbe57be94,0xbeb7,0x3de23eae,0xbde23eae,0xbe943e57,0xbeb78000,0x3e57be94,0x3e94be57,0x3eaebde2,0x3eb70000,0xbe94be57,0xbe57be94,0xbde2beae,0xbeb7,
0x3eb7,0x3eb7,0x3eb7,0x3eb7,0x3eb78000,0x3eb78000,0x3eb78000,0x3eb78000,0xbeae3de2,0xbe943e57,0xbe573e94,0xbde23eae,0x3de23eae,0x3e573e94,0x3e943e57,0x3eae3de2,
0xbe57be94,0xbeaebde2,0xbeae3de2,0xbe573e94,0xbe943e57,0xbde23eae,0x3de23eae,0x3e943e57,0x3e57be94,0xbde2beae,0xbeaebde2,0xbe943e57,0xbe94be57,0xbeae3de2,0xbde23eae,0x3e573e94,
0,0,0,0,0,0,0,0,0,0,0,0,0,0,0,0,
0,0,0,0,0,0,0,0,0,0,0,0,0,0,0,0,
0x3eae3de2,0x3e57be94,0xbe57be94,0xbeae3de2,0x3de2beae,0xbe94be57,0xbe943e57,0x3de23eae,0x3eb7,0x3eb70000,0xbeb7,0xbeb70000,0x3eb78000,0xbeb7,0xbeb78000,0x3eb7,
0xbeae3de2,0x3e573e94,0x3e57be94,0xbeaebde2,0x3de23eae,0x3e94be57,0xbe94be57,0xbde23eae,0xbe57be94,0xbde23eae,0x3eaebde2,0xbe94be57,0xbe943e57,0x3eae3de2,0xbde2beae,0xbe573e94,
0,0,0,0,0,0,0,0,0,0,0,0,0,0,0,0,
0,0,0,0,0,0,0,0,0,0,0,0,0,0,0,0,
0x3e57be94,0xbeae3de2,0x3eae3de2,0xbe57be94,0xbe94be57,0x3de23eae,0x3de2beae,0xbe943e57,0x3eae3de2,0xbe94be57,0x3e573e94,0xbde2beae,0x3de2beae,0xbe573e94,0x3e94be57,0xbeae3de2,
0x3eb7,0xbeb7,0x3eb7,0xbeb7,0x3eb78000,0xbeb78000,0x3eb78000,0xbeb78000,0xbeae3de2,0x3e94be57,0xbe573e94,0x3de2beae,0x3de23eae,0xbe57be94,0x3e943e57,0xbeaebde2,
0,0,0,0,0,0,0,0,0,0,0,0,0,0,0,0,
0,0,0,0,0,0,0,0,0,0,0,0,0,0,0,0,
0xbe57be94,0x3eae3de2,0xbeae3de2,0x3e57be94,0xbe943e57,0x3de2beae,0x3de23eae,0xbe94be57,0x3e57be94,0x3de23eae,0xbeaebde2,0x3e94be57,0xbe94be57,0x3eaebde2,0xbde23eae,0xbe57be94,
0x3eae3de2,0xbe573e94,0xbe57be94,0x3eaebde2,0x3de2beae,0x3e943e57,0xbe943e57,0xbde2beae,0x3eb7,0xbeb70000,0xbeb7,0x3eb70000,0x3eb78000,0x3eb7,0xbeb78000,0xbeb7,
0,0,0,0,0,0,0,0,0,0,0,0,0,0,0,0,
0,0,0,0,0,0,0,0,0,0,0,0,0,0,0,0,
0xbeae3de2,0xbe57be94,0x3e57be94,0x3eae3de2,0x3de23eae,0xbe943e57,0xbe94be57,0x3de2beae,0xbe57be94,0x3de2beae,0x3eaebde2,0x3e943e57,0xbe943e57,0xbeaebde2,0xbde2beae,0x3e57be94,
0x3e57be94,0x3eaebde2,0x3eae3de2,0x3e573e94,0xbe94be57,0xbde2beae,0x3de2beae,0x3e94be57,0x3eae3de2,0x3e943e57,0x3e573e94,0x3de23eae,0x3de2beae,0x3e57be94,0x3e94be57,0x3eaebde2,
0,0,0,0,0,0,0,0,0,0,0,0,0,0,0,0,
0,0,0,0,0,0,0,0,0,0,0,0,0,0,0,0,
0,0,0,0,0,0,0,0,0,0,0,0,0,0,0,0,
0,0,0,0,0,0,0,0,0,0,0,0,0,0,0,0,
0x3eb7,0x3eb7,0x3eb7,0x3eb7,0x3eb78000,0x3eb78000,0x3eb78000,0x3eb78000,0xbeae3de2,0xbe943e57,0xbe573e94,0xbde23eae,0x3de23eae,0x3e573e94,0x3e943e57,0x3eae3de2,
0xbe57be94,0xbeaebde2,0xbeae3de2,0xbe573e94,0xbe943e57,0xbde23eae,0x3de23eae,0x3e943e57,0x3e57be94,0xbde2beae,0xbeaebde2,0xbe943e57,0xbe94be57,0xbeae3de2,0xbde23eae,0x3e573e94,
0,0,0,0,0,0,0,0,0,0,0,0,0,0,0,0,
0,0,0,0,0,0,0,0,0,0,0,0,0,0,0,0,
0x3eae3de2,0x3e57be94,0xbe57be94,0xbeae3de2,0x3de2beae,0xbe94be57,0xbe943e57,0x3de23eae,0x3eb7,0x3eb70000,0xbeb7,0xbeb70000,0x3eb78000,0xbeb7,0xbeb78000,0x3eb7,
0xbeae3de2,0x3e573e94,0x3e57be94,0xbeaebde2,0x3de23eae,0x3e94be57,0xbe94be57,0xbde23eae,0xbe57be94,0xbde23eae,0x3eaebde2,0xbe94be57,0xbe943e57,0x3eae3de2,0xbde2beae,0xbe573e94,
0,0,0,0,0,0,0,0,0,0,0,0,0,0,0,0,
0,0,0,0,0,0,0,0,0,0,0,0,0,0,0,0,
0x3e57be94,0xbeae3de2,0x3eae3de2,0xbe57be94,0xbe94be57,0x3de23eae,0x3de2beae,0xbe943e57,0x3eae3de2,0xbe94be57,0x3e573e94,0xbde2beae,0x3de2beae,0xbe573e94,0x3e94be57,0xbeae3de2,
0x3eb7,0xbeb7,0x3eb7,0xbeb7,0x3eb78000,0xbeb78000,0x3eb78000,0xbeb78000,0xbeae3de2,0x3e94be57,0xbe573e94,0x3de2beae,0x3de23eae,0xbe57be94,0x3e943e57,0xbeaebde2,
0,0,0,0,0,0,0,0,0,0,0,0,0,0,0,0,
0,0,0,0,0,0,0,0,0,0,0,0,0,0,0,0,
0xbe57be94,0x3eae3de2,0xbeae3de2,0x3e57be94,0xbe943e57,0x3de2beae,0x3de23eae,0xbe94be57,0x3e57be94,0x3de23eae,0xbeaebde2,0x3e94be57,0xbe94be57,0x3eaebde2,0xbde23eae,0xbe57be94,
0x3eae3de2,0xbe573e94,0xbe57be94,0x3eaebde2,0x3de2beae,0x3e943e57,0xbe943e57,0xbde2beae,0x3eb7,0xbeb70000,0xbeb7,0x3eb70000,0x3eb78000,0x3eb7,0xbeb78000,0xbeb7,
0,0,0,0,0,0,0,0,0,0,0,0,0,0,0,0,
0,0,0,0,0,0,0,0,0,0,0,0,0,0,0,0,
0xbeae3de2,0xbe57be94,0x3e57be94,0x3eae3de2,0x3de23eae,0xbe943e57,0xbe94be57,0x3de2beae,0xbe57be94,0x3de2beae,0x3eaebde2,0x3e943e57,0xbe943e57,0xbeaebde2,0xbde2beae,0x3e57be94,
0x3e57be94,0x3eaebde2,0x3eae3de2,0x3e573e94,0xbe94be57,0xbde2beae,0x3de2beae,0x3e94be57,0x3eae3de2,0x3e943e57,0x3e573e94,0x3de23eae,0x3de2beae,0x3e57be94,0x3e94be57,0x3eaebde2,
};
__device__ __align__(128) const uint32_t TAB_P3[4288] = {
0,0,0,0,0,0,0,0,0,0,0,0,0,0,0,0,
0x80003e83,0xbe79bda2,0x3e1abe54,0x3e1a3e54,0x3e830000,0xbda23e79,0xbe54be1a,0x3e54be1a,0x80003e83,0xbe54be1a,0x3e79bda2,0xbda23e79,0x3e830000,0xbe1a3e54,0xbda2be79,0x3e793da2,
0,0,0,0,0,0,0,0,0,0,0,0,0,0,0,0,
0xbe793da2,0x8000be83,0x3e793da2,0xbe1a3e54,0x3da23e79,0xbe830000,0x3da2be79,0x3e543e1a,0xbe1abe54,0x3e830000,0xbe1a3e54,0xbda2be79,0xbe543e1a,0xbe83,0x3e543e1a,0xbe793da2,
0x80003e83,0xbe1abe54,0x3e793da2,0xbe793da2,0x3e830000,0xbe543e1a,0x3da2be79,0x3da23e79,0x80003e83,0xbda2be79,0x3e1a3e54,0xbe54be1a,0x3e830000,0xbe793da2,0x3e54be1a,0xbe1a3e54,
0x80003e83,0x8000be83,0x80003e83,0x8000be83,0x3e830000,0xbe830000,0x3e830000,0xbe830000,0x80003e83,0x3da2be79,0xbe1a3e54,0x3e54be1a,0x3e830000,0xbe79bda2,0x3e543e1a,0xbe1abe54,
0x3e1abe54,0x80003e83,0xbe1abe54,0x3e793da2,0xbe54be1a,0x3e830000,0xbe543e1a,0x3da2be79,0x3e793da2,0xbe830000,0x3e79bda2,0xbe543e1a,0x3da2be79,0x3e83,0xbda2be79,0x3e1a3e54,
0x80003e83,0x8000be83,0x80003e83,0x8000be83,0x3e830000,0xbe830000,0x3e830000,0xbe830000,0xbe793da2,0x3e830000,0xbe79bda2,0x3e543e1a,0x3da23e79,0xbe83,0xbda23e79,0x3e1abe54,
0x80003e83,0x3e1abe54,0xbe793da2,0x3e793da2,0x3e830000,0xbe54be1a,0x3da23e79,0x3da2be79,0x80003e83,0x3e54be1a,0xbe79bda2,0x3da23e79,0x3e830000,0xbe1abe54,0xbda23e79,0x3e79bda2,
0x80003e83,0x3e79bda2,0xbe1abe54,0xbe1a3e54,0x3e830000,0xbda2be79,0xbe543e1a,0x3e543e1a,0x80003e83,0x3e830000,0x8000be83,0xbe830000,0x3e830000,0xbe83,0xbe830000,0x3e83,
0xbe1abe54,0x80003e83,0x3e1abe54,0xbe793da2,0xbe543e1a,0x3e830000,0xbe54be1a,0x3da23e79,0x3e1abe54,0xbe830000,0x3e1a3e54,0x3da2be79,0xbe54be1a,0x3e83,0x3e54be1a,0xbe79bda2,
0x3e793da2,0x8000be83,0xbe793da2,0x3e1a3e54,0x3da2be79,0xbe830000,0x3da23e79,0x3e54be1a,0x80003e83,0x3e830000,0x8000be83,0xbe830000,0x3e830000,0xbe83,0xbe830000,0x3e83,
0x80003e83,0x3e793da2,0x3e1abe54,0xbe1abe54,0x3e830000,0x3da2be79,0xbe54be1a,0xbe543e1a,0x80003e83,0x3e543e1a,0x3e79bda2,0x3da2be79,0x3e830000,0x3e1abe54,0xbda2be79,0xbe79bda2,
0x80003e83,0x3e1a3e54,0x3e793da2,0x3e79bda2,0x3e830000,0x3e54be1a,0x3da2be79,0xbda2be79,0x80003e83,0x3da23e79,0x3e1a3e54,0x3e543e1a,0x3e830000,0x3e79bda2,0x3e54be1a,0x3e1abe54,
0xbe793da2,0x80003e83,0x3e793da2,0x3e1abe54,0x3da23e79,0x3e830000,0x3da2be79,0xbe54be1a,0xbe1abe54,0xbe830000,0xbe1a3e54,0x3da23e79,0xbe543e1a,0x3e83,0x3e543e1a,0x3e79bda2,
0x3e1abe54,0x8000be83,0xbe1abe54,0xbe79bda2,0xbe54be1a,0xbe830000,0xbe543e1a,0xbda23e79,0x3e793da2,0x3e830000,0x3e79bda2,0x3e54be1a,0x3da2be79,0xbe83,0xbda2be79,0xbe1abe54,
0,0,0,0,0,0,0,0,0,0,0,0,0,0,0,0,
0,0,0,0,0,0,0,0,0,0,0,0,0,0,0,0,
0,0,0,0,0,0,0,0,0,0,0,0,0,0,0,0,
0xbe1abe54,0x3e79bda2,0x80003e83,0xbe79bda2,0xbe543e1a,0xbda2be79,0x3e830000,0xbda23e79,0x3e793da2,0xbe543e1a,0x8000be83,0x3e543e1a,0x3da2be79,0x3e1a3e54,0xbe830000,0x3e1abe54,
0,0,0,0,0,0,0,0,0,0,0,0,0,0,0,0,
0,0,0,0,0,0,0,0,0,0,0,0,0,0,0,0,
0xbe793da2,0x3e1abe54,0x80003e83,0xbe1abe54,0x3da23e79,0xbe54be1a,0x3e830000,0xbe543e1a,0x3e1abe54,0xbda23e79,0x8000be83,0x3da23e79,0xbe54be1a,0x3e793da2,0xbe830000,0x3e79bda2,
0x80003e83,0x8000be83,0x80003e83,0x8000be83,0x3e830000,0xbe830000,0x3e830000,0xbe830000,0xbe1abe54,0x3da23e79,0x8000be83,0xbda23e79,0xbe543e1a,0x3e79bda2,0xbe830000,0x3e793da2,
0,0,0,0,0,0,0,0,0,0,0,0,0,0,0,0,
0,0,0,0,0,0,0,0,0,0,0,0,0,0,0,0,
0x3e793da2,0xbe1abe54,0x80003e83,0x3e1abe54,0x3da2be79,0xbe543e1a,0x3e830000,0xbe54be1a,0xbe793da2,0x3e543e1a,0x8000be83,0xbe543e1a,0x3da23e79,0x3e1abe54,0xbe830000,0x3e1a3e54,
0x3e1abe54,0xbe79bda2,0x80003e83,0x3e79bda2,0xbe54be1a,0xbda23e79,0x3e830000,0xbda2be79,0x80003e83,0x3e830000,0x8000be83,0xbe830000,0x3e830000,0xbe83,0xbe830000,0x3e83,
0,0,0,0,0,0,0,0,0,0,0,0,0,0,0,0,
0,0,0,0,0,0,0,0,0,0,0,0,0,0,0,0,
0xbe1abe54,0xbe793da2,0x80003e83,0x3e793da2,0xbe543e1a,0x3da23e79,0x3e830000,0x3da2be79,0x3e793da2,0x3e54be1a,0x8000be83,0xbe54be1a,0x3da2be79,0xbe1abe54,0xbe830000,0xbe1a3e54,
0xbe793da2,0xbe1a3e54,0x80003e83,0x3e1a3e54,0x3da23e79,0x3e543e1a,0x3e830000,0x3e54be1a,0x3e1abe54,0x3da2be79,0x8000be83,0xbda2be79,0xbe54be1a,0xbe79bda2,0xbe830000,0xbe793da2,
0,0,0,0,0,0,0,0,0,0,0,0,0,0,0,0,
0x3e1abe54,0x3e1a3e54,0xbe793da2,0x8000be83,0xbe54be1a,0x3e54be1a,0x3da23e79,0xbe830000,0xbe793da2,0x3da2be79,0x3e1a3e54,0xbe830000,0x3da23e79,0xbe79bda2,0x3e54be1a,0x3e83,
0,0,0,0,0,0,0,0,0,0,0,0,0,0,0,0,
0x3e793da2,0xbe1a3e54,0xbe1abe54,0x3e79bda2,0x3da2be79,0x3e543e1a,0xbe543e1a,0xbda2be79,0x3e1abe54,0x3da23e79,0xbe79bda2,0x3e54be1a,0xbe54be1a,0x3e79bda2,0xbda23e79,0xbe1abe54,
0x3e793da2,0xbe793da2,0x3e1abe54,0x80003e83,0x3da2be79,0x3da23e79,0xbe54be1a,0x3e830000,0xbe1abe54,0x3e543e1a,0xbe79bda2,0x3e830000,0xbe543e1a,0x3e1abe54,0xbda23e79,0xbe83,
0x80003e83,0x8000be83,0x80003e83,0x8000be83,0x3e830000,0xbe830000,0x3e830000,0xbe830000,0x3e1abe54,0xbe543e1a,0x3e79bda2,0xbe830000,0xbe54be1a,0x3e1a3e54,0xbda2be79,0x3e83,
0xbe1abe54,0x3e793da2,0xbe793da2,0x3e1abe54,0xbe543e1a,0x3da2be79,0x3da23e79,0xbe54be1a,0xbe793da2,0x3e54be1a,0xbe1a3e54,0x3da2be79,0x3da23e79,0xbe1abe54,0x3e543e1a,0xbe79bda2,
0x80003e83,0x8000be83,0x80003e83,0x8000be83,0x3e830000,0xbe830000,0x3e830000,0xbe830000,0x3e793da2,0xbe54be1a,0x3e1a3e54,0xbda2be79,0x3da2be79,0xbe1a3e54,0x3e54be1a,0xbe793da2,
0xbe793da2,0x3e793da2,0xbe1abe54,0x80003e83,0x3da23e79,0x3da2be79,0xbe543e1a,0x3e830000,0x3e793da2,0xbda2be79,0xbe1a3e54,0x3e830000,0x3da2be79,0xbe793da2,0x3e543e1a,0xbe83,
0xbe1abe54,0xbe1a3e54,0x3e793da2,0x8000be83,0xbe543e1a,0x3e543e1a,0x3da2be79,0xbe830000,0x80003e83,0x3e830000,0x8000be83,0xbe830000,0x3e830000,0xbe83,0xbe830000,0x3e83,
0x3e1abe54,0xbe793da2,0x3e793da2,0xbe1abe54,0xbe54be1a,0x3da23e79,0x3da2be79,0xbe543e1a,0xbe1abe54,0xbda23e79,0x3e79bda2,0xbe54be1a,0xbe543e1a,0x3e793da2,0xbda2be79,0xbe1a3e54,
0xbe793da2,0x3e1a3e54,0x3e1abe54,0xbe79bda2,0x3da23e79,0x3e54be1a,0xbe54be1a,0xbda23e79,0x80003e83,0x3e830000,0x8000be83,0xbe830000,0x3e830000,0xbe83,0xbe830000,0x3e83,
0x3e1abe54,0xbe1abe54,0xbe793da2,0x80003e83,0xbe54be1a,0xbe543e1a,0x3da23e79,0x3e830000,0xbe793da2,0xbda23e79,0x3e1a3e54,0x3e830000,0x3da23e79,0x3e793da2,0x3e54be1a,0xbe83,
0x3e793da2,0x3e79bda2,0x3e1abe54,0x8000be83,0x3da2be79,0xbda2be79,0xbe54be1a,0xbe830000,0xbe1abe54,0xbe54be1a,0xbe79bda2,0xbe830000,0xbe543e1a,0xbe1a3e54,0xbda23e79,0x3e83,
0x3e793da2,0x3e1abe54,0xbe1abe54,0xbe793da2,0x3da2be79,0xbe54be1a,0xbe543e1a,0x3da23e79,0x3e1abe54,0xbda2be79,0xbe79bda2,0xbe543e1a,0xbe54be1a,0xbe793da2,0xbda23e79,0x3e1a3e54,
0xbe1abe54,0xbe79bda2,0xbe793da2,0xbe1a3e54,0xbe543e1a,0xbda23e79,0x3da23e79,0x3e543e1a,0xbe793da2,0xbe543e1a,0xbe1a3e54,0xbda23e79,0x3da23e79,0x3e1a3e54,0x3e543e1a,0x3e793da2,
0xbe163dda,0,0,0,0,0xbe163dda,0,0,0,0,0xbe163dda,0,0,0,0,0xbe163dda,
0xbe253da8,0,0,0,0,0xbe253da8,0,0,0,0,0xbe253da8,0,0,0,0,0xbe253da8,
0xbd65be30,0,0,0,0,0xbd65be30,0,0,0,0,0xbd65be30,0,0,0,0,0xbd65be30,
0x3ce8be37,0,0,0,0,0x3ce8be37,0,0,0,0,0x3ce8be37,0,0,0,0,0x3ce8be37,
0xbe303d65,0,0,0,0,0xbe303d65,0,0,0,0,0xbe303d65,0,0,0,0,0xbe303d65,
0xbe373ce8,0,0,0,0,0xbe373ce8,0,0,0,0,0xbe373ce8,0,0,0,0,0xbe373ce8,
0x3ddabe16,0,0,0,0,0x3ddabe16,0,0,0,0,0x3ddabe16,0,0,0,0,0x3ddabe16,
0x3e25bda8,0,0,0,0,0x3e25bda8,0,0,0,0,0x3e25bda8,0,0,0,0,0x3e25bda8,
0xbe390000,0,0,0,0,0xbe390000,0,0,0,0,0xbe390000,0,0,0,0,0xbe390000,
0xbe37bce8,0,0,0,0,0xbe37bce8,0,0,0,0,0xbe37bce8,0,0,0,0,0xbe37bce8,
0x3e390000,0,0,0,0,0x3e390000,0,0,0,0,0x3e390000,0,0,0,0,0x3e390000,
0x3e253da8,0,0,0,0,0x3e253da8,0,0,0,0,0x3e253da8,0,0,0,0,0x3e253da8,
0xbe30bd65,0,0,0,0,0xbe30bd65,0,0,0,0,0xbe30bd65,0,0,0,0,0xbe30bd65,
0xbe25bda8,0,0,0,0,0xbe25bda8,0,0,0,0,0xbe25bda8,0,0,0,0,0xbe25bda8,
0x3dda3e16,0,0,0,0,0x3dda3e16,0,0,0,0,0x3dda3e16,0,0,0,0,0x3dda3e16,
0x3ce83e37,0,0,0,0,0x3ce83e37,0,0,0,0,0x3ce83e37,0,0,0,0,0x3ce83e37,
0xbe16bdda,0,0,0,0,0xbe16bdda,0,0,0,0,0xbe16bdda,0,0,0,0,0xbe16bdda,
0xbe03be03,0,0,0,0,0xbe03be03,0,0,0,0,0xbe03be03,0,0,0,0,0xbe03be03,
0xbd653e30,0,0,0,0,0xbd653e30,0,0,0,0,0xbd653e30,0,0,0,0,0xbd653e30,
0xbe033e03,0,0,0,0,0xbe033e03,0,0,0,0,0xbe033e03,0,0,0,0,0xbe033e03,
0xbddabe16,0,0,0,0,0xbddabe16,0,0,0,0,0xbddabe16,0,0,0,0,0xbddabe16,
0xbda8be25,0,0,0,0,0xbda8be25,0,0,0,0,0xbda8be25,0,0,0,0,0xbda8be25,
0xbe303d65,0,0,0,0,0xbe303d65,0,0,0,0,0xbe303d65,0,0,0,0,0xbe303d65,
0xbe37bce8,0,0,0,0,0xbe37bce8,0,0,0,0,0xbe37bce8,0,0,0,0,0xbe37bce8,
0xbd65be30,0,0,0,0,0xbd65be30,0,0,0,0,0xbd65be30,0,0,0,0,0xbd65be30,
0xbce8be37,0,0,0,0,0xbce8be37,0,0,0,0,0xbce8be37,0,0,0,0,0xbce8be37,
0xbe16bdda,0,0,0,0,0xbe16bdda,0,0,0,0,0xbe16bdda,0,0,0,0,0xbe16bdda,
0xbda8be25,0,0,0,0,0xbda8be25,0,0,0,0,0xbda8be25,0,0,0,0,0xbda8be25,
0x3e390000,0,0,0,0,0x3e390000,0,0,0,0,0x3e390000,0,0,0,0,0x3e390000,
0x3e033e03,0,0,0,0,0x3e033e03,0,0,0,0,0x3e033e03,0,0,0,0,0x3e033e03,
0xbd653e30,0,0,0,0,0xbd653e30,0,0,0,0,0xbd653e30,0,0,0,0,0xbd653e30,
0xbe373ce8,0,0,0,0,0xbe373ce8,0,0,0,0,0xbe373ce8,0,0,0,0,0xbe373ce8,
0x80003e39,0,0,0,0,0x80003e39,0,0,0,0,0x80003e39,0,0,0,0,0x80003e39,
0xbe033e03,0,0,0,0,0xbe033e03,0,0,0,0,0xbe033e03,0,0,0,0,0xbe033e03,
0xbddabe16,0,0,0,0,0xbddabe16,0,0,0,0,0xbddabe16,0,0,0,0,0xbddabe16,
0x3da8be25,0,0,0,0,0x3da8be25,0,0,0,0,0x3da8be25,0,0,0,0,0x3da8be25,
0xbe390000,0,0,0,0,0xbe390000,0,0,0,0,0xbe390000,0,0,0,0,0xbe390000,
0xbe03be03,0,0,0,0,0xbe03be03,0,0,0,0,0xbe03be03,0,0,0,0,0xbe03be03,
0x3e390000,0,0,0,0,0x3e390000,0,0,0,0,0x3e390000,0,0,0,0,0x3e390000,
0x3da83e25,0,0,0,0,0x3da83e25,0,0,0,0,0x3da83e25,0,0,0,0,0x3da83e25,
0x8000be39,0,0,0,0,0x8000be39,0,0,0,0,0x8000be39,0,0,0,0,0x8000be39,
0x3e03be03,0,0,0,0,0x3e03be03,0,0,0,0,0x3e03be03,0,0,0,0,0x3e03be03,
0xbdda3e16,0,0,0,0,0xbdda3e16,0,0,0,0,0xbdda3e16,0,0,0,0,0xbdda3e16,
0xbe37bce8,0,0,0,0,0xbe37bce8,0,0,0,0,0xbe37bce8,0,0,0,0,0xbe37bce8,
0x3e390000,0,0,0,0,0x3e390000,0,0,0,0,0x3e390000,0,0,0,0,0x3e390000,
0x3e033e03,0,0,0,0,0x3e033e03,0,0,0,0,0x3e033e03,0,0,0,0,0x3e033e03,
0xbd65be30,0,0,0,0,0xbd65be30,0,0,0,0,0xbd65be30,0,0,0,0,0xbd65be30,
0x3e03be03,0,0,0,0,0x3e03be03,0,0,0,0,0x3e03be03,0,0,0,0,0x3e03be03,
0x80003e39,0,0,0,0,0x80003e39,0,0,0,0,0x80003e39,0,0,0,0,0x80003e39,
0xbe033e03,0,0,0,0,0xbe033e03,0,0,0,0,0xbe033e03,0,0,0,0,0xbe033e03,
0x3e303d65,0,0,0,0,0x3e303d65,0,0,0,0,0x3e303d65,0,0,0,0,0x3e303d65,
0x3ce83e37,0,0,0,0,0x3ce83e37,0,0,0,0,0x3ce83e37,0,0,0,0,0x3ce83e37,
0xbe390000,0,0,0,0,0xbe390000,0,0,0,0,0xbe390000,0,0,0,0,0xbe390000,
0xbe03be03,0,0,0,0,0xbe03be03,0,0,0,0,0xbe03be03,0,0,0,0,0xbe03be03,
0xbe163dda,0,0,0,0,0xbe163dda,0,0,0,0,0xbe163dda,0,0,0,0,0xbe163dda,
0xbe25bda8,0,0,0,0,0xbe25bda8,0,0,0,0,0xbe25bda8,0,0,0,0,0xbe25bda8,
0xbe16bdda,0,0,0,0,0xbe16bdda,0,0,0,0,0xbe16bdda,0,0,0,0,0xbe16bdda,
0x3da8be25,0,0,0,0,0x3da8be25,0,0,0,0,0x3da8be25,0,0,0,0,0x3da8be25,
0x3e16bdda,0,0,0,0,0x3e16bdda,0,0,0,0,0x3e16bdda,0,0,0,0,0x3e16bdda,
0x3da83e25,0,0,0,0,0x3da83e25,0,0,0,0,0x3da83e25,0,0,0,0,0x3da83e25,
0x3e303d65,0,0,0,0,0x3e303d65,0,0,0,0,0x3e303d65,0,0,0,0,0x3e303d65,
0xbce83e37,0,0,0,0,0xbce83e37,0,0,0,0,0xbce83e37,0,0,0,0,0xbce83e37,
0xbe303d65,0,0,0,0,0xbe303d65,0,0,0,0,0xbe303d65,0,0,0,0,0xbe303d65,
0xbce8be37,0,0,0,0,0xbce8be37,0,0,0,0,0xbce8be37,0,0,0,0,0xbce8be37,
0xbe390000,0,0,0,0,0xbe390000,0,0,0,0,0xbe390000,0,0,0,0,0xbe390000,
0xbce8be37,0,0,0,0,0xbce8be37,0,0,0,0,0xbce8be37,0,0,0,0,0xbce8be37,
0x3e390000,0,0,0,0,0x3e390000,0,0,0,0,0x3e390000,0,0,0,0,0x3e390000,
0xbce83e37,0,0,0,0,0xbce83e37,0,0,0,0,0xbce83e37,0,0,0,0,0xbce83e37,
0x3e30bd65,0,0,0,0,0x3e30bd65,0,0,0,0,0x3e30bd65,0,0,0,0,0x3e30bd65,
0x3da83e25,0,0,0,0,0x3da83e25,0,0,0,0,0x3da83e25,0,0,0,0,0x3da83e25,
0xbe30bd65,0,0,0,0,0xbe30bd65,0,0,0,0,0xbe30bd65,0,0,0,0,0xbe30bd65,
0x3da8be25,0,0,0,0,0x3da8be25,0,0,0,0,0x3da8be25,0,0,0,0,0x3da8be25,
0xbe163dda,0,0,0,0,0xbe163dda,0,0,0,0,0xbe163dda,0,0,0,0,0xbe163dda,
0xbe03be03,0,0,0,0,0xbe03be03,0,0,0,0,0xbe03be03,0,0,0,0,0xbe03be03,
0x3e163dda,0,0,0,0,0x3e163dda,0,0,0,0,0x3e163dda,0,0,0,0,0x3e163dda,
0xbe033e03,0,0,0,0,0xbe033e03,0,0,0,0,0xbe033e03,0,0,0,0,0xbe033e03,
0x3ddabe16,0,0,0,0,0x3ddabe16,0,0,0,0,0x3ddabe16,0,0,0,0,0x3ddabe16,
0x3e253da8,0,0,0,0,0x3e253da8,0,0,0,0,0x3e253da8,0,0,0,0,0x3e253da8,
0xbddabe16,0,0,0,0,0xbddabe16,0,0,0,0,0xbddabe16,0,0,0,0,0xbddabe16,
0x3e25bda8,0,0,0,0,0x3e25bda8,0,0,0,0,0x3e25bda8,0,0,0,0,0x3e25bda8,
0xbd653e30,0,0,0,0,0xbd653e30,0,0,0,0,0xbd653e30,0,0,0,0,0xbd653e30,
0xbe37bce8,0,0,0,0,0xbe37bce8,0,0,0,0,0xbe37bce8,0,0,0,0,0xbe37bce8,
0x3d653e30,0,0,0,0,0x3d653e30,0,0,0,0,0x3d653e30,0,0,0,0,0x3d653e30,
0xbe373ce8,0,0,0,0,0xbe373ce8,0,0,0,0,0xbe373ce8,0,0,0,0,0xbe373ce8,
0x3d653e30,0,0,0,0,0x3d653e30,0,0,0,0,0x3d653e30,0,0,0,0,0x3d653e30,
0xbe37bce8,0,0,0,0,0xbe37bce8,0,0,0,0,0xbe37bce8,0,0,0,0,0xbe37bce8,
0xbe390000,0,0,0,0,0xbe390000,0,0,0,0,0xbe390000,0,0,0,0,0xbe390000,
0x3e03be03,0,0,0,0,0x3e03be03,0,0,0,0,0x3e03be03,0,0,0,0,0x3e03be03,
0x3ddabe16,0,0,0,0,0x3ddabe16,0,0,0,0,0x3ddabe16,0,0,0,0,0x3ddabe16,
0x3da83e25,0,0,0,0,0x3da83e25,0,0,0,0,0x3da83e25,0,0,0,0,0x3da83e25,
0x80003e39,0,0,0,0,0x80003e39,0,0,0,0,0x80003e39,0,0,0,0,0x80003e39,
0xbe03be03,0,0,0,0,0xbe03be03,0,0,0,0,0xbe03be03,0,0,0,0,0xbe03be03,
0xbe390000,0,0,0,0,0xbe390000,0,0,0,0,0xbe390000,0,0,0,0,0xbe390000,
0x3da8be25,0,0,0,0,0x3da8be25,0,0,0,0,0x3da8be25,0,0,0,0,0x3da8be25,
0x3e390000,0,0,0,0,0x3e390000,0,0,0,0,0x3e390000,0,0,0,0,0x3e390000,
0xbe033e03,0,0,0,0,0xbe033e03,0,0,0,0,0xbe033e03,0,0,0,0,0xbe033e03,
0x3dda3e16,0,0,0,0,0x3dda3e16,0,0,0,0,0x3dda3e16,0,0,0,0,0x3dda3e16,
0xbe373ce8,0,0,0,0,0xbe373ce8,0,0,0,0,0xbe373ce8,0,0,0,0,0xbe373ce8,
0x8000be39,0,0,0,0,0x8000be39,0,0,0,0,0x8000be39,0,0,0,0,0x8000be39,
0x3e033e03,0,0,0,0,0x3e033e03,0,0,0,0,0x3e033e03,0,0,0,0,0x3e033e03,
0x3d65be30,0,0,0,0,0x3d65be30,0,0,0,0,0x3d65be30,0,0,0,0,0x3d65be30,
0x3e033e03,0,0,0,0,0x3e033e03,0,0,0,0,0x3e033e03,0,0,0,0,0x3e033e03,
0xbe390000,0,0,0,0,0xbe390000,0,0,0,0,0xbe390000,0,0,0,0,0xbe390000,
0x3e03be03,0,0,0,0,0x3e03be03,0,0,0,0,0x3e03be03,0,0,0,0,0x3e03be03,
0xbe303d65,0,0,0,0,0xbe303d65,0,0,0,0,0xbe303d65,0,0,0,0,0xbe303d65,
0x3ce8be37,0,0,0,0,0x3ce8be37,0,0,0,0,0x3ce8be37,0,0,0,0,0x3ce8be37,
0x80003e39,0,0,0,0,0x80003e39,0,0,0,0,0x80003e39,0,0,0,0,0x80003e39,
0xbe03be03,0,0,0,0,0xbe03be03,0,0,0,0,0xbe03be03,0,0,0,0,0xbe03be03,
0x3e163dda,0,0,0,0,0x3e163dda,0,0,0,0,0x3e163dda,0,0,0,0,0x3e163dda,
0xbe253da8,0,0,0,0,0xbe253da8,0,0,0,0,0xbe253da8,0,0,0,0,0xbe253da8,
0x3e390000,0,0,0,0,0x3e390000,0,0,0,0,0x3e390000,0,0,0,0,0x3e390000,
0xbe033e03,0,0,0,0,0xbe033e03,0,0,0,0,0xbe033e03,0,0,0,0,0xbe033e03,
0x3d65be30,0,0,0,0,0x3d65be30,0,0,0,0,0x3d65be30,0,0,0,0,0x3d65be30,
0x3ce83e37,0,0,0,0,0x3ce83e37,0,0,0,0,0x3ce83e37,0,0,0,0,0x3ce83e37,
0x3e163dda,0,0,0,0,0x3e163dda,0,0,0,0,0x3e163dda,0,0,0,0,0x3e163dda,
0xbe25bda8,0,0,0,0,0xbe25bda8,0,0,0,0,0xbe25bda8,0,0,0,0,0xbe25bda8,
0xbddabe16,0,0,0,0,0xbddabe16,0,0,0,0,0xbddabe16,0,0,0,0,0xbddabe16,
0x3e253da8,0,0,0,0,0x3e253da8,0,0,0,0,0x3e253da8,0,0,0,0,0x3e253da8,
0x3e303d65,0,0,0,0,0x3e303d65,0,0,0,0,0x3e303d65,0,0,0,0,0x3e303d65,
0xbe37bce8,0,0,0,0,0xbe37bce8,0,0,0,0,0xbe37bce8,0,0,0,0,0xbe37bce8,
0xbe390000,0,0,0,0,0xbe390000,0,0,0,0,0xbe390000,0,0,0,0,0xbe390000,
0x3e25bda8,0,0,0,0,0x3e25bda8,0,0,0,0,0x3e25bda8,0,0,0,0,0x3e25bda8,
0x3e390000,0,0,0,0,0x3e390000,0,0,0,0,0x3e390000,0,0,0,0,0x3e390000,
0xbe373ce8,0,0,0,0,0xbe373ce8,0,0,0,0,0xbe373ce8,0,0,0,0,0xbe373ce8,
0xbdda3e16,0,0,0,0,0xbdda3e16,0,0,0,0,0xbdda3e16,0,0,0,0,0xbdda3e16,
0x3ce8be37,0,0,0,0,0x3ce8be37,0,0,0,0,0x3ce8be37,0,0,0,0,0x3ce8be37,
0x3e30bd65,0,0,0,0,0x3e30bd65,0,0,0,0,0x3e30bd65,0,0,0,0,0x3e30bd65,
0xbe253da8,0,0,0,0,0xbe253da8,0,0,0,0,0xbe253da8,0,0,0,0,0xbe253da8,
0x3d653e30,0,0,0,0,0x3d653e30,0,0,0,0,0x3d653e30,0,0,0,0,0x3d653e30,
0xbe03be03,0,0,0,0,0xbe03be03,0,0,0,0,0xbe03be03,0,0,0,0,0xbe03be03,
0x3e16bdda,0,0,0,0,0x3e16bdda,0,0,0,0,0x3e16bdda,0,0,0,0,0x3e16bdda,
0xbe033e03,0,0,0,0,0xbe033e03,0,0,0,0,0xbe033e03,0,0,0,0,0xbe033e03,
0x3e303d65,0,0,0,0,0x3e303d65,0,0,0,0,0x3e303d65,0,0,0,0,0x3e303d65,
0xbe373ce8,0,0,0,0,0xbe373ce8,0,0,0,0,0xbe373ce8,0,0,0,0,0xbe373ce8,
0x3ddabe16,0,0,0,0,0x3ddabe16,0,0,0,0,0x3ddabe16,0,0,0,0,0x3ddabe16,
0xbda83e25,0,0,0,0,0xbda83e25,0,0,0,0,0xbda83e25,0,0,0,0,0xbda83e25,
0x3e16bdda,0,0,0,0,0x3e16bdda,0,0,0,0,0x3e16bdda,0,0,0,0,0x3e16bdda,
0xbda83e25,0,0,0,0,0xbda83e25,0,0,0,0,0xbda83e25,0,0,0,0,0xbda83e25,
0x3d65be30,0,0,0,0,0x3d65be30,0,0,0,0,0x3d65be30,0,0,0,0,0x3d65be30,
0xbce83e37,0,0,0,0,0xbce83e37,0,0,0,0,0xbce83e37,0,0,0,0,0xbce83e37,
0,0,0xbe163dda,0,0,0,0,0xbe163dda,0,0,0xbe253da8,0,0,0,0,0xbe253da8,
0,0,0xbe303d65,0,0,0,0,0xbe303d65,0,0,0xbe373ce8,0,0,0,0,0xbe373ce8,
0,0,0xbd65be30,0,0,0,0,0xbd65be30,0,0,0x3ce8be37,0,0,0,0,0x3ce8be37,
0,0,0x3ddabe16,0,0,0,0,0x3ddabe16,0,0,0x3e25bda8,0,0,0,0,0x3e25bda8,
0,0,0xbe390000,0,0,0,0,0xbe390000,0,0,0xbe37bce8,0,0,0,0,0xbe37bce8,
0,0,0xbe30bd65,0,0,0,0,0xbe30bd65,0,0,0xbe25bda8,0,0,0,0,0xbe25bda8,
0,0,0x3e390000,0,0,0,0,0x3e390000,0,0,0x3e253da8,0,0,0,0,0x3e253da8,
0,0,0x3dda3e16,0,0,0,0,0x3dda3e16,0,0,0x3ce83e37,0,0,0,0,0x3ce83e37,
0,0,0xbe16bdda,0,0,0,0,0xbe16bdda,0,0,0xbe03be03,0,0,0,0,0xbe03be03,
0,0,0xbddabe16,0,0,0,0,0xbddabe16,0,0,0xbda8be25,0,0,0,0,0xbda8be25,
0,0,0xbd653e30,0,0,0,0,0xbd653e30,0,0,0xbe033e03,0,0,0,0,0xbe033e03,
0,0,0xbe303d65,0,0,0,0,0xbe303d65,0,0,0xbe37bce8,0,0,0,0,0xbe37bce8,
0,0,0xbd65be30,0,0,0,0,0xbd65be30,0,0,0xbce8be37,0,0,0,0,0xbce8be37,
0,0,0,0,0,0,0,0,0,0,0,0,0,0,0,0,
0,0,0xbe16bdda,0,0,0,0,0xbe16bdda,0,0,0xbda8be25,0,0,0,0,0xbda8be25,
0,0,0,0,0,0,0,0,0,0,0,0,0,0,0,0,
0,0,0x3e390000,0,0,0,0,0x3e390000,0,0,0x3e033e03,0,0,0,0,0x3e033e03,
0,0,0x80003e39,0,0,0,0,0x80003e39,0,0,0xbe033e03,0,0,0,0,0xbe033e03,
0,0,0xbd653e30,0,0,0,0,0xbd653e30,0,0,0xbe373ce8,0,0,0,0,0xbe373ce8,
0,0,0xbddabe16,0,0,0,0,0xbddabe16,0,0,0x3da8be25,0,0,0,0,0x3da8be25,
0,0,0xbe390000,0,0,0,0,0xbe390000,0,0,0xbe03be03,0,0,0,0,0xbe03be03,
0,0,0x8000be39,0,0,0,0,0x8000be39,0,0,0x3e03be03,0,0,0,0,0x3e03be03,
0,0,0x3e390000,0,0,0,0,0x3e390000,0,0,0x3da83e25,0,0,0,0,0x3da83e25,
0,0,0xbdda3e16,0,0,0,0,0xbdda3e16,0,0,0xbe37bce8,0,0,0,0,0xbe37bce8,
0,0,0x3e390000,0,0,0,0,0x3e390000,0,0,0x3e033e03,0,0,0,0,0x3e033e03,
0,0,0x80003e39,0,0,0,0,0x80003e39,0,0,0xbe033e03,0,0,0,0,0xbe033e03,
0,0,0xbd65be30,0,0,0,0,0xbd65be30,0,0,0x3e03be03,0,0,0,0,0x3e03be03,
0,0,0x3e303d65,0,0,0,0,0x3e303d65,0,0,0x3ce83e37,0,0,0,0,0x3ce83e37,
0,0,0xbe390000,0,0,0,0,0xbe390000,0,0,0xbe03be03,0,0,0,0,0xbe03be03,
0,0,0,0,0,0,0,0,0,0,0,0,0,0,0,0,
0,0,0xbe163dda,0,0,0,0,0xbe163dda,0,0,0xbe25bda8,0,0,0,0,0xbe25bda8,
0,0,0,0,0,0,0,0,0,0,0,0,0,0,0,0,
0,0,0xbe16bdda,0,0,0,0,0xbe16bdda,0,0,0x3da8be25,0,0,0,0,0x3da8be25,
0,0,0x3e303d65,0,0,0,0,0x3e303d65,0,0,0xbce83e37,0,0,0,0,0xbce83e37,
0,0,0x3e16bdda,0,0,0,0,0x3e16bdda,0,0,0x3da83e25,0,0,0,0,0x3da83e25,
0,0,0xbe303d65,0,0,0,0,0xbe303d65,0,0,0xbce8be37,0,0,0,0,0xbce8be37,
0,0,0xbe390000,0,0,0,0,0xbe390000,0,0,0xbce8be37,0,0,0,0,0xbce8be37,
0,0,0x3e30bd65,0,0,0,0,0x3e30bd65,0,0,0x3da83e25,0,0,0,0,0x3da83e25,
0,0,0x3e390000,0,0,0,0,0x3e390000,0,0,0xbce83e37,0,0,0,0,0xbce83e37,
0,0,0xbe30bd65,0,0,0,0,0xbe30bd65,0,0,0x3da8be25,0,0,0,0,0x3da8be25,
0,0,0xbe163dda,0,0,0,0,0xbe163dda,0,0,0xbe03be03,0,0,0,0,0xbe03be03,
0,0,0x3ddabe16,0,0,0,0,0x3ddabe16,0,0,0x3e253da8,0,0,0,0,0x3e253da8,
0,0,0x3e163dda,0,0,0,0,0x3e163dda,0,0,0xbe033e03,0,0,0,0,0xbe033e03,
0,0,0xbddabe16,0,0,0,0,0xbddabe16,0,0,0x3e25bda8,0,0,0,0,0x3e25bda8,
0,0,0xbd653e30,0,0,0,0,0xbd653e30,0,0,0xbe37bce8,0,0,0,0,0xbe37bce8,
0,0,0,0,0,0,0,0,0,0,0,0,0,0,0,0,
0,0,0x3d653e30,0,0,0,0,0x3d653e30,0,0,0xbe373ce8,0,0,0,0,0xbe373ce8,
0,0,0,0,0,0,0,0,0,0,0,0,0,0,0,0,
0,0,0x3d653e30,0,0,0,0,0x3d653e30,0,0,0xbe37bce8,0,0,0,0,0xbe37bce8,
0,0,0x3ddabe16,0,0,0,0,0x3ddabe16,0,0,0x3da83e25,0,0,0,0,0x3da83e25,
0,0,0xbe390000,0,0,0,0,0xbe390000,0,0,0x3e03be03,0,0,0,0,0x3e03be03,
0,0,0x80003e39,0,0,0,0,0x80003e39,0,0,0xbe03be03,0,0,0,0,0xbe03be03,
0,0,0xbe390000,0,0,0,0,0xbe390000,0,0,0x3da8be25,0,0,0,0,0x3da8be25,
0,0,0x3dda3e16,0,0,0,0,0x3dda3e16,0,0,0xbe373ce8,0,0,0,0,0xbe373ce8,
0,0,0x3e390000,0,0,0,0,0x3e390000,0,0,0xbe033e03,0,0,0,0,0xbe033e03,
0,0,0x8000be39,0,0,0,0,0x8000be39,0,0,0x3e033e03,0,0,0,0,0x3e033e03,
0,0,0x3d65be30,0,0,0,0,0x3d65be30,0,0,0x3e033e03,0,0,0,0,0x3e033e03,
0,0,0xbe303d65,0,0,0,0,0xbe303d65,0,0,0x3ce8be37,0,0,0,0,0x3ce8be37,
0,0,0xbe390000,0,0,0,0,0xbe390000,0,0,0x3e03be03,0,0,0,0,0x3e03be03,
0,0,0x80003e39,0,0,0,0,0x80003e39,0,0,0xbe03be03,0,0,0,0,0xbe03be03,
0,0,0x3e163dda,0,0,0,0,0x3e163dda,0,0,0xbe253da8,0,0,0,0,0xbe253da8,
0,0,0,0,0,0,0,0,0,0,0,0,0,0,0,0,
0,0,0x3e390000,0,0,0,0,0x3e390000,0,0,0xbe033e03,0,0,0,0,0xbe033e03,
0,0,0,0,0,0,0,0,0,0,0,0,0,0,0,0,
0,0,0x3d65be30,0,0,0,0,0x3d65be30,0,0,0x3ce83e37,0,0,0,0,0x3ce83e37,
0,0,0xbddabe16,0,0,0,0,0xbddabe16,0,0,0x3e253da8,0,0,0,0,0x3e253da8,
0,0,0x3e163dda,0,0,0,0,0x3e163dda,0,0,0xbe25bda8,0,0,0,0,0xbe25bda8,
0,0,0x3e303d65,0,0,0,0,0x3e303d65,0,0,0xbe37bce8,0,0,0,0,0xbe37bce8,
0,0,0xbe390000,0,0,0,0,0xbe390000,0,0,0x3e25bda8,0,0,0,0,0x3e25bda8,
0,0,0xbdda3e16,0,0,0,0,0xbdda3e16,0,0,0x3ce8be37,0,0,0,0,0x3ce8be37,
0,0,0x3e390000,0,0,0,0,0x3e390000,0,0,0xbe373ce8,0,0,0,0,0xbe373ce8,
0,0,0x3e30bd65,0,0,0,0,0x3e30bd65,0,0,0xbe253da8,0,0,0,0,0xbe253da8,
0,0,0x3d653e30,0,0,0,0,0x3d653e30,0,0,0xbe03be03,0,0,0,0,0xbe03be03,
0,0,0x3e303d65,0,0,0,0,0x3e303d65,0,0,0xbe373ce8,0,0,0,0,0xbe373ce8,
0,0,0x3e16bdda,0,0,0,0,0x3e16bdda,0,0,0xbe033e03,0,0,0,0,0xbe033e03,
0,0,0x3ddabe16,0,0,0,0,0x3ddabe16,0,0,0xbda83e25,0,0,0,0,0xbda83e25,
0,0,0x3e16bdda,0,0,0,0,0x3e16bdda,0,0,0xbda83e25,0,0,0,0,0xbda83e25,
0,0,0,0,0,0,0,0,0,0,0,0,0,0,0,0,
0,0,0x3d65be30,0,0,0,0,0x3d65be30,0,0,0xbce83e37,0,0,0,0,0xbce83e37,
0,0,0,0,0,0,0,0,0,0,0,0,0,0,0,0,
};
constexpr unsigned long long COS_PK0 = 0x3f903f9a3fa03fa2ull;
constexpr unsigned long long COS_PK1 = 0x3f133f3e3f653f83ull;
constexpr unsigned long long COS_PK2 = 0x3e4b3ec8ull;

__device__ __forceinline__ void wgmma_ss_n80_z(float (&d)[40], uint64_t da, uint64_t db) {
  asm volatile("{\n.reg .pred p;\nsetp.ne.b32 p, 0, 0;\nwgmma.mma_async.sync.aligned.m64n80k16.f32.bf16.bf16 {%0,%1,%2,%3,%4,%5,%6,%7,%8,%9,%10,%11,%12,%13,%14,%15,%16,%17,%18,%19,%20,%21,%22,%23,%24,%25,%26,%27,%28,%29,%30,%31,%32,%33,%34,%35,%36,%37,%38,%39}, %40, %41, p, 1, 1, 1, 0;\n}\n"
    : "+f"(d[0]), "+f"(d[1]), "+f"(d[2]), "+f"(d[3]), "+f"(d[4]), "+f"(d[5]), "+f"(d[6]), "+f"(d[7]), "+f"(d[8]), "+f"(d[9]), "+f"(d[10]), "+f"(d[11]), "+f"(d[12]), "+f"(d[13]), "+f"(d[14]), "+f"(d[15]), "+f"(d[16]), "+f"(d[17]), "+f"(d[18]), "+f"(d[19]), "+f"(d[20]), "+f"(d[21]), "+f"(d[22]), "+f"(d[23]), "+f"(d[24]), "+f"(d[25]), "+f"(d[26]), "+f"(d[27]), "+f"(d[28]), "+f"(d[29]), "+f"(d[30]), "+f"(d[31]), "+f"(d[32]), "+f"(d[33]), "+f"(d[34]), "+f"(d[35]), "+f"(d[36]), "+f"(d[37]), "+f"(d[38]), "+f"(d[39])
    : "l"(da), "l"(db));
}
__device__ __forceinline__ void wgmma_ss_n80_a(float (&d)[40], uint64_t da, uint64_t db) {
  asm volatile("{\n.reg .pred p;\nsetp.ne.b32 p, 1, 0;\nwgmma.mma_async.sync.aligned.m64n80k16.f32.bf16.bf16 {%0,%1,%2,%3,%4,%5,%6,%7,%8,%9,%10,%11,%12,%13,%14,%15,%16,%17,%18,%19,%20,%21,%22,%23,%24,%25,%26,%27,%28,%29,%30,%31,%32,%33,%34,%35,%36,%37,%38,%39}, %40, %41, p, 1, 1, 1, 0;\n}\n"
    : "+f"(d[0]), "+f"(d[1]), "+f"(d[2]), "+f"(d[3]), "+f"(d[4]), "+f"(d[5]), "+f"(d[6]), "+f"(d[7]), "+f"(d[8]), "+f"(d[9]), "+f"(d[10]), "+f"(d[11]), "+f"(d[12]), "+f"(d[13]), "+f"(d[14]), "+f"(d[15]), "+f"(d[16]), "+f"(d[17]), "+f"(d[18]), "+f"(d[19]), "+f"(d[20]), "+f"(d[21]), "+f"(d[22]), "+f"(d[23]), "+f"(d[24]), "+f"(d[25]), "+f"(d[26]), "+f"(d[27]), "+f"(d[28]), "+f"(d[29]), "+f"(d[30]), "+f"(d[31]), "+f"(d[32]), "+f"(d[33]), "+f"(d[34]), "+f"(d[35]), "+f"(d[36]), "+f"(d[37]), "+f"(d[38]), "+f"(d[39])
    : "l"(da), "l"(db));
}

__device__ __forceinline__ void wgmma_rs_n40_z(float (&d)[20], uint32_t a0, uint32_t a1, uint32_t a2, uint32_t a3, uint64_t db) {
  asm volatile("{\n.reg .pred p;\nsetp.ne.b32 p, 0, 0;\nwgmma.mma_async.sync.aligned.m64n40k16.f32.bf16.bf16 {%0,%1,%2,%3,%4,%5,%6,%7,%8,%9,%10,%11,%12,%13,%14,%15,%16,%17,%18,%19}, {%20,%21,%22,%23}, %24, p, 1, 1, 0;\n}\n"
    : "+f"(d[0]), "+f"(d[1]), "+f"(d[2]), "+f"(d[3]), "+f"(d[4]), "+f"(d[5]), "+f"(d[6]), "+f"(d[7]), "+f"(d[8]), "+f"(d[9]), "+f"(d[10]), "+f"(d[11]), "+f"(d[12]), "+f"(d[13]), "+f"(d[14]), "+f"(d[15]), "+f"(d[16]), "+f"(d[17]), "+f"(d[18]), "+f"(d[19])
    : "r"(a0), "r"(a1), "r"(a2), "r"(a3), "l"(db));
}
__device__ __forceinline__ void wgmma_rs_n40_a(float (&d)[20], uint32_t a0, uint32_t a1, uint32_t a2, uint32_t a3, uint64_t db) {
  asm volatile("{\n.reg .pred p;\nsetp.ne.b32 p, 1, 0;\nwgmma.mma_async.sync.aligned.m64n40k16.f32.bf16.bf16 {%0,%1,%2,%3,%4,%5,%6,%7,%8,%9,%10,%11,%12,%13,%14,%15,%16,%17,%18,%19}, {%20,%21,%22,%23}, %24, p, 1, 1, 0;\n}\n"
    : "+f"(d[0]), "+f"(d[1]), "+f"(d[2]), "+f"(d[3]), "+f"(d[4]), "+f"(d[5]), "+f"(d[6]), "+f"(d[7]), "+f"(d[8]), "+f"(d[9]), "+f"(d[10]), "+f"(d[11]), "+f"(d[12]), "+f"(d[13]), "+f"(d[14]), "+f"(d[15]), "+f"(d[16]), "+f"(d[17]), "+f"(d[18]), "+f"(d[19])
    : "r"(a0), "r"(a1), "r"(a2), "r"(a3), "l"(db));
}

__device__ __forceinline__ void wgmma_rs_n128_z(float (&d)[64], uint32_t a0, uint32_t a1, uint32_t a2, uint32_t a3, uint64_t db) {
  asm volatile("{\n.reg .pred p;\nsetp.ne.b32 p, 0, 0;\nwgmma.mma_async.sync.aligned.m64n128k16.f32.bf16.bf16 {%0,%1,%2,%3,%4,%5,%6,%7,%8,%9,%10,%11,%12,%13,%14,%15,%16,%17,%18,%19,%20,%21,%22,%23,%24,%25,%26,%27,%28,%29,%30,%31,%32,%33,%34,%35,%36,%37,%38,%39,%40,%41,%42,%43,%44,%45,%46,%47,%48,%49,%50,%51,%52,%53,%54,%55,%56,%57,%58,%59,%60,%61,%62,%63}, {%64,%65,%66,%67}, %68, p, 1, 1, 1;\n}\n"
    : "+f"(d[0]), "+f"(d[1]), "+f"(d[2]), "+f"(d[3]), "+f"(d[4]), "+f"(d[5]), "+f"(d[6]), "+f"(d[7]), "+f"(d[8]), "+f"(d[9]), "+f"(d[10]), "+f"(d[11]), "+f"(d[12]), "+f"(d[13]), "+f"(d[14]), "+f"(d[15]), "+f"(d[16]), "+f"(d[17]), "+f"(d[18]), "+f"(d[19]), "+f"(d[20]), "+f"(d[21]), "+f"(d[22]), "+f"(d[23]), "+f"(d[24]), "+f"(d[25]), "+f"(d[26]), "+f"(d[27]), "+f"(d[28]), "+f"(d[29]), "+f"(d[30]), "+f"(d[31]), "+f"(d[32]), "+f"(d[33]), "+f"(d[34]), "+f"(d[35]), "+f"(d[36]), "+f"(d[37]), "+f"(d[38]), "+f"(d[39]), "+f"(d[40]), "+f"(d[41]), "+f"(d[42]), "+f"(d[43]), "+f"(d[44]), "+f"(d[45]), "+f"(d[46]), "+f"(d[47]), "+f"(d[48]), "+f"(d[49]), "+f"(d[50]), "+f"(d[51]), "+f"(d[52]), "+f"(d[53]), "+f"(d[54]), "+f"(d[55]), "+f"(d[56]), "+f"(d[57]), "+f"(d[58]), "+f"(d[59]), "+f"(d[60]), "+f"(d[61]), "+f"(d[62]), "+f"(d[63])
    : "r"(a0), "r"(a1), "r"(a2), "r"(a3), "l"(db));
}
__device__ __forceinline__ void wgmma_rs_n128_a(float (&d)[64], uint32_t a0, uint32_t a1, uint32_t a2, uint32_t a3, uint64_t db) {
  asm volatile("{\n.reg .pred p;\nsetp.ne.b32 p, 1, 0;\nwgmma.mma_async.sync.aligned.m64n128k16.f32.bf16.bf16 {%0,%1,%2,%3,%4,%5,%6,%7,%8,%9,%10,%11,%12,%13,%14,%15,%16,%17,%18,%19,%20,%21,%22,%23,%24,%25,%26,%27,%28,%29,%30,%31,%32,%33,%34,%35,%36,%37,%38,%39,%40,%41,%42,%43,%44,%45,%46,%47,%48,%49,%50,%51,%52,%53,%54,%55,%56,%57,%58,%59,%60,%61,%62,%63}, {%64,%65,%66,%67}, %68, p, 1, 1, 1;\n}\n"
    : "+f"(d[0]), "+f"(d[1]), "+f"(d[2]), "+f"(d[3]), "+f"(d[4]), "+f"(d[5]), "+f"(d[6]), "+f"(d[7]), "+f"(d[8]), "+f"(d[9]), "+f"(d[10]), "+f"(d[11]), "+f"(d[12]), "+f"(d[13]), "+f"(d[14]), "+f"(d[15]), "+f"(d[16]), "+f"(d[17]), "+f"(d[18]), "+f"(d[19]), "+f"(d[20]), "+f"(d[21]), "+f"(d[22]), "+f"(d[23]), "+f"(d[24]), "+f"(d[25]), "+f"(d[26]), "+f"(d[27]), "+f"(d[28]), "+f"(d[29]), "+f"(d[30]), "+f"(d[31]), "+f"(d[32]), "+f"(d[33]), "+f"(d[34]), "+f"(d[35]), "+f"(d[36]), "+f"(d[37]), "+f"(d[38]), "+f"(d[39]), "+f"(d[40]), "+f"(d[41]), "+f"(d[42]), "+f"(d[43]), "+f"(d[44]), "+f"(d[45]), "+f"(d[46]), "+f"(d[47]), "+f"(d[48]), "+f"(d[49]), "+f"(d[50]), "+f"(d[51]), "+f"(d[52]), "+f"(d[53]), "+f"(d[54]), "+f"(d[55]), "+f"(d[56]), "+f"(d[57]), "+f"(d[58]), "+f"(d[59]), "+f"(d[60]), "+f"(d[61]), "+f"(d[62]), "+f"(d[63])
    : "r"(a0), "r"(a1), "r"(a2), "r"(a3), "l"(db));
}

__device__ __forceinline__ void wgmma_rs_n32_z(float (&d)[16], uint32_t a0, uint32_t a1, uint32_t a2, uint32_t a3, uint64_t db) {
  asm volatile("{\n.reg .pred p;\nsetp.ne.b32 p, 0, 0;\nwgmma.mma_async.sync.aligned.m64n32k16.f32.bf16.bf16 {%0,%1,%2,%3,%4,%5,%6,%7,%8,%9,%10,%11,%12,%13,%14,%15}, {%16,%17,%18,%19}, %20, p, 1, 1, 0;\n}\n"
    : "+f"(d[0]), "+f"(d[1]), "+f"(d[2]), "+f"(d[3]), "+f"(d[4]), "+f"(d[5]), "+f"(d[6]), "+f"(d[7]), "+f"(d[8]), "+f"(d[9]), "+f"(d[10]), "+f"(d[11]), "+f"(d[12]), "+f"(d[13]), "+f"(d[14]), "+f"(d[15])
    : "r"(a0), "r"(a1), "r"(a2), "r"(a3), "l"(db));
}
__device__ __forceinline__ void wgmma_rs_n32_a(float (&d)[16], uint32_t a0, uint32_t a1, uint32_t a2, uint32_t a3, uint64_t db) {
  asm volatile("{\n.reg .pred p;\nsetp.ne.b32 p, 1, 0;\nwgmma.mma_async.sync.aligned.m64n32k16.f32.bf16.bf16 {%0,%1,%2,%3,%4,%5,%6,%7,%8,%9,%10,%11,%12,%13,%14,%15}, {%16,%17,%18,%19}, %20, p, 1, 1, 0;\n}\n"
    : "+f"(d[0]), "+f"(d[1]), "+f"(d[2]), "+f"(d[3]), "+f"(d[4]), "+f"(d[5]), "+f"(d[6]), "+f"(d[7]), "+f"(d[8]), "+f"(d[9]), "+f"(d[10]), "+f"(d[11]), "+f"(d[12]), "+f"(d[13]), "+f"(d[14]), "+f"(d[15])
    : "r"(a0), "r"(a1), "r"(a2), "r"(a3), "l"(db));
}

__device__ __forceinline__ void wgmma_rs_n64_z(float (&d)[32], uint32_t a0, uint32_t a1, uint32_t a2, uint32_t a3, uint64_t db) {
  asm volatile("{\n.reg .pred p;\nsetp.ne.b32 p, 0, 0;\nwgmma.mma_async.sync.aligned.m64n64k16.f32.bf16.bf16 {%0,%1,%2,%3,%4,%5,%6,%7,%8,%9,%10,%11,%12,%13,%14,%15,%16,%17,%18,%19,%20,%21,%22,%23,%24,%25,%26,%27,%28,%29,%30,%31}, {%32,%33,%34,%35}, %36, p, 1, 1, 0;\n}\n"
    : "+f"(d[0]), "+f"(d[1]), "+f"(d[2]), "+f"(d[3]), "+f"(d[4]), "+f"(d[5]), "+f"(d[6]), "+f"(d[7]), "+f"(d[8]), "+f"(d[9]), "+f"(d[10]), "+f"(d[11]), "+f"(d[12]), "+f"(d[13]), "+f"(d[14]), "+f"(d[15]), "+f"(d[16]), "+f"(d[17]), "+f"(d[18]), "+f"(d[19]), "+f"(d[20]), "+f"(d[21]), "+f"(d[22]), "+f"(d[23]), "+f"(d[24]), "+f"(d[25]), "+f"(d[26]), "+f"(d[27]), "+f"(d[28]), "+f"(d[29]), "+f"(d[30]), "+f"(d[31])
    : "r"(a0), "r"(a1), "r"(a2), "r"(a3), "l"(db));
}
__device__ __forceinline__ void wgmma_rs_n64_a(float (&d)[32], uint32_t a0, uint32_t a1, uint32_t a2, uint32_t a3, uint64_t db) {
  asm volatile("{\n.reg .pred p;\nsetp.ne.b32 p, 1, 0;\nwgmma.mma_async.sync.aligned.m64n64k16.f32.bf16.bf16 {%0,%1,%2,%3,%4,%5,%6,%7,%8,%9,%10,%11,%12,%13,%14,%15,%16,%17,%18,%19,%20,%21,%22,%23,%24,%25,%26,%27,%28,%29,%30,%31}, {%32,%33,%34,%35}, %36, p, 1, 1, 0;\n}\n"
    : "+f"(d[0]), "+f"(d[1]), "+f"(d[2]), "+f"(d[3]), "+f"(d[4]), "+f"(d[5]), "+f"(d[6]), "+f"(d[7]), "+f"(d[8]), "+f"(d[9]), "+f"(d[10]), "+f"(d[11]), "+f"(d[12]), "+f"(d[13]), "+f"(d[14]), "+f"(d[15]), "+f"(d[16]), "+f"(d[17]), "+f"(d[18]), "+f"(d[19]), "+f"(d[20]), "+f"(d[21]), "+f"(d[22]), "+f"(d[23]), "+f"(d[24]), "+f"(d[25]), "+f"(d[26]), "+f"(d[27]), "+f"(d[28]), "+f"(d[29]), "+f"(d[30]), "+f"(d[31])
    : "r"(a0), "r"(a1), "r"(a2), "r"(a3), "l"(db));
}

__device__ __forceinline__ void wgmma_ss_n32_z(float (&d)[16], uint64_t da, uint64_t db) {
  asm volatile("{\n.reg .pred p;\nsetp.ne.b32 p, 0, 0;\nwgmma.mma_async.sync.aligned.m64n32k16.f32.bf16.bf16 {%0,%1,%2,%3,%4,%5,%6,%7,%8,%9,%10,%11,%12,%13,%14,%15}, %16, %17, p, 1, 1, 1, 0;\n}\n"
    : "+f"(d[0]), "+f"(d[1]), "+f"(d[2]), "+f"(d[3]), "+f"(d[4]), "+f"(d[5]), "+f"(d[6]), "+f"(d[7]), "+f"(d[8]), "+f"(d[9]), "+f"(d[10]), "+f"(d[11]), "+f"(d[12]), "+f"(d[13]), "+f"(d[14]), "+f"(d[15])
    : "l"(da), "l"(db));
}
__device__ __forceinline__ void wgmma_ss_n32_a(float (&d)[16], uint64_t da, uint64_t db) {
  asm volatile("{\n.reg .pred p;\nsetp.ne.b32 p, 1, 0;\nwgmma.mma_async.sync.aligned.m64n32k16.f32.bf16.bf16 {%0,%1,%2,%3,%4,%5,%6,%7,%8,%9,%10,%11,%12,%13,%14,%15}, %16, %17, p, 1, 1, 1, 0;\n}\n"
    : "+f"(d[0]), "+f"(d[1]), "+f"(d[2]), "+f"(d[3]), "+f"(d[4]), "+f"(d[5]), "+f"(d[6]), "+f"(d[7]), "+f"(d[8]), "+f"(d[9]), "+f"(d[10]), "+f"(d[11]), "+f"(d[12]), "+f"(d[13]), "+f"(d[14]), "+f"(d[15])
    : "l"(da), "l"(db));
}

__device__ __forceinline__ void wgmma_ss_n40_z(float (&d)[20], uint64_t da, uint64_t db) {
  asm volatile("{\n.reg .pred p;\nsetp.ne.b32 p, 0, 0;\nwgmma.mma_async.sync.aligned.m64n40k16.f32.bf16.bf16 {%0,%1,%2,%3,%4,%5,%6,%7,%8,%9,%10,%11,%12,%13,%14,%15,%16,%17,%18,%19}, %20, %21, p, 1, 1, 1, 0;\n}\n"
    : "+f"(d[0]), "+f"(d[1]), "+f"(d[2]), "+f"(d[3]), "+f"(d[4]), "+f"(d[5]), "+f"(d[6]), "+f"(d[7]), "+f"(d[8]), "+f"(d[9]), "+f"(d[10]), "+f"(d[11]), "+f"(d[12]), "+f"(d[13]), "+f"(d[14]), "+f"(d[15]), "+f"(d[16]), "+f"(d[17]), "+f"(d[18]), "+f"(d[19])
    : "l"(da), "l"(db));
}
__device__ __forceinline__ void wgmma_ss_n40_a(float (&d)[20], uint64_t da, uint64_t db) {
  asm volatile("{\n.reg .pred p;\nsetp.ne.b32 p, 1, 0;\nwgmma.mma_async.sync.aligned.m64n40k16.f32.bf16.bf16 {%0,%1,%2,%3,%4,%5,%6,%7,%8,%9,%10,%11,%12,%13,%14,%15,%16,%17,%18,%19}, %20, %21, p, 1, 1, 1, 0;\n}\n"
    : "+f"(d[0]), "+f"(d[1]), "+f"(d[2]), "+f"(d[3]), "+f"(d[4]), "+f"(d[5]), "+f"(d[6]), "+f"(d[7]), "+f"(d[8]), "+f"(d[9]), "+f"(d[10]), "+f"(d[11]), "+f"(d[12]), "+f"(d[13]), "+f"(d[14]), "+f"(d[15]), "+f"(d[16]), "+f"(d[17]), "+f"(d[18]), "+f"(d[19])
    : "l"(da), "l"(db));
}

constexpr int NSM = 132, NH = 66;
constexpr int S0 = 0, S1 = 51200, S2 = 102400;
constexpr int C1 = 153600, C3 = C1, RG = C1 + 18432;
constexpr int WP = RG, TBL = RG + 28672, WS2 = RG + 30720;
constexpr int BARS = RG + 49152;
__host__ __device__ constexpr int wst_off(int i) { return i < 12 ? S2 + i * 4096 : WS2 + (i - 12) * 4096; }
constexpr int NBAR = 280;
constexpr int REL = BARS + NBAR * 8;
constexpr int SMEM_BYTES = REL + 16;
constexpr int B_XF = 0, B_CF1 = 15, B_CF3 = 16, B_WF = 17  , B_P1D = 18, B_REL = 21, B_ROLE = 22, B_SIG = 24;
constexpr int B_RF = 32, B_RE = 46, B_YF = 60, B_WRD = 75, B_SFREE = 89, B_WCH = 131, B_RDY = 136, B_WE = 205, B_WL = 217, B_FIN = 229, B_TOK = 232;
constexpr int R_P2 = 15, R_P3 = 57;
constexpr int CNT_P1 = 0, CNT_P2 = 4, CNT_W = 8, CNT_RANK = 9, NCLS = 10, CNT_DONE = 0, CNT_REL = 1, NCNT = 2;
constexpr int SIG_W = 0, SIG_P1 = 1, SIG_P2 = 4;
#define T1MASK 0x3e00
#define T2MASK 0x1f00

__device__ uint4 g_scr[(14 << 21) / 16];
__device__ uint4 g_wf[200 * 72 * 32];
__device__ unsigned g_cnt[NCNT * 32];
__device__ __forceinline__ int slot_line(int chunk, int pg, int cls) {
    return (pg & 1) << 6 | (pg >> 1) << 9 | (chunk & 1) << 10 | (chunk >> 1) << 12 | ((pg ^ (pg >> 1) ^ chunk ^ (chunk >> 1) ^ cls) & 1) << 5;
}
__device__ __forceinline__ int phi_line(int phi, uint32_t rel) {
    return (phi >> 4) << 14 | (phi & 3) << 7 | ((phi >> 2) & 1) << 11 | ((phi >> 3) & 1) << 13 | ((rel >> (phi >> 4)) & 1) << 5;
}
__device__ __forceinline__ int extra_mask(int rk) { return rk < 58 ? 0 : rk < 60 ? 2 : rk < 62 ? 1 : rk < 64 ? 4 : 8; }
__device__ __forceinline__ int wslot(int pc) {
    return (int)((0x576476503421ull >> (4 * pc)) & 3) * 12288 + (((0x576476503421ull >> (4 * pc)) & 4) ? S0 : RG);
}
__device__ __forceinline__ int xslot(int n) { return ((n & 4) ? S2 : RG) + ((n + 1) & 3) * 12288; }
__device__ __forceinline__ int extra_phi(int rk) { return 198 + (rk & 1); }
__host__ __device__ constexpr int quad_off(int Q) { return (Q >> 2) * 4096 + (Q & 3) * 512; }

struct Maps { CUtensorMap w, x34, x6, x28, wst, f16, f8, y4, y2; };
struct Ptrs { char* scr; const char* wf; const void* tab1; const void* tab3; unsigned* cnt; };

__device__ __forceinline__ uint32_t smem_u32(const void* p) { return (uint32_t)__cvta_generic_to_shared(p); }
__device__ __forceinline__ void mbar_wait(uint32_t bar) {
    uint32_t ok, it = 0;
    do {
        asm volatile("{\n.reg .pred p;\nmbarrier.try_wait.parity.shared::cta.b64 p, [%1], 0;\nselp.u32 %0, 1, 0, p;\n}" : "=r"(ok) : "r"(bar) : "memory");
        if (++it > (1u << 22)) break;
    } while (!ok);
}
__device__ __forceinline__ bool mbar_test(uint32_t bar) {
    uint32_t ok;
    asm volatile("{\n.reg .pred p;\nmbarrier.test_wait.parity.shared::cta.b64 p, [%1], 0;\nselp.u32 %0, 1, 0, p;\n}" : "=r"(ok) : "r"(bar) : "memory");
    return ok;
}
__device__ __forceinline__ void fence_async() { asm volatile("fence.proxy.async;" ::: "memory"); }
__device__ __forceinline__ void fence_async_smem() { asm volatile("fence.proxy.async.shared::cta;" ::: "memory"); }
#define ELECT "{\n.reg .pred p;\nelect.sync _|p, 0xffffffff;\n@p "
__device__ __forceinline__ void e_arrive(uint32_t bar) { asm volatile(ELECT "mbarrier.arrive.shared::cta.b64 _, [%0];\n}" :: "r"(bar) : "memory"); }
__device__ __forceinline__ void e_expect(uint32_t bar, uint32_t bytes) { asm volatile(ELECT "mbarrier.arrive.expect_tx.shared::cta.b64 _, [%0], %1;\n}" :: "r"(bar), "r"(bytes) : "memory"); }
__device__ __forceinline__ void e_g2s(uint32_t dst, const void* src, uint32_t bytes, uint32_t bar) {
    asm volatile(ELECT "cp.async.bulk.shared::cluster.global.mbarrier::complete_tx::bytes [%0], [%1], %2, [%3];\n}" :: "r"(dst), "l"(src), "r"(bytes), "r"(bar) : "memory");
}
__device__ __forceinline__ void e_s2g(void* dst, uint32_t src, uint32_t bytes) {
    asm volatile(ELECT "cp.async.bulk.global.shared::cta.bulk_group [%0], [%1], %2;\n}" :: "l"(dst), "r"(src), "r"(bytes) : "memory");
}
__device__ __forceinline__ void e_ld3(uint32_t dst, const CUtensorMap* m, int c0, int c1, int c2, uint32_t bar) {
    asm volatile(ELECT "cp.async.bulk.tensor.3d.shared::cluster.global.mbarrier::complete_tx::bytes [%0], [%1, {%3, %4, %5}], [%2];\n}"
                 :: "r"(dst), "l"(m), "r"(bar), "r"(c0), "r"(c1), "r"(c2) : "memory");
}
__device__ __forceinline__ void e_ld4(uint32_t dst, const CUtensorMap* m, int c0, int c3, uint32_t bar) {
    asm volatile(ELECT "cp.async.bulk.tensor.4d.shared::cluster.global.mbarrier::complete_tx::bytes [%0], [%1, {%3, %5, %5, %4}], [%2];\n}"
                 :: "r"(dst), "l"(m), "r"(bar), "r"(c0), "r"(c3), "r"(0) : "memory");
}
__device__ __forceinline__ void e_st3(const CUtensorMap* m, uint32_t src, int c0, int c1, int c2) {
    asm volatile(ELECT "cp.async.bulk.tensor.3d.global.shared::cta.bulk_group [%0, {%2, %3, %4}], [%1];\n}" :: "l"(m), "r"(src), "r"(c0), "r"(c1), "r"(c2) : "memory");
}
__device__ __forceinline__ void e_ld5(uint32_t dst, const CUtensorMap* m, int c4, uint32_t bar) {
    asm volatile(ELECT "cp.async.bulk.tensor.5d.shared::cluster.global.mbarrier::complete_tx::bytes [%0], [%1, {%4, %4, %4, %4, %3}], [%2];\n}"
                 :: "r"(dst), "l"(m), "r"(bar), "r"(c4), "r"(0) : "memory");
}
__device__ __forceinline__ void e_st5(const CUtensorMap* m, uint32_t src, int c4) {
    asm volatile(ELECT "cp.async.bulk.tensor.5d.global.shared::cta.bulk_group [%0, {%3, %3, %3, %3, %2}], [%1];\n}" :: "l"(m), "r"(src), "r"(c4), "r"(0) : "memory");
}
__device__ __forceinline__ void bulk_commit() { asm volatile("cp.async.bulk.commit_group;" ::: "memory"); }
template <int N> __device__ __forceinline__ void bulk_wait() { asm volatile("cp.async.bulk.wait_group %0;" :: "n"(N) : "memory"); }
template <int N> __device__ __forceinline__ void bulk_wait_read() { asm volatile("cp.async.bulk.wait_group.read %0;" :: "n"(N) : "memory"); }
__device__ __forceinline__ void wg_bar(int id) { asm volatile("bar.sync %0, 128;" :: "r"(id) : "memory"); }
__device__ __forceinline__ void bb_break(uint32_t v) { asm volatile("{\n.reg .pred p;\nsetp.eq.u32 p, %0, 0x7fc17fc1;\n@p nanosleep.u32 0;\n}" :: "r"(v) : "memory"); }
__device__ __forceinline__ uint32_t uni(uint32_t v) { return __shfl_sync(0xffffffffu, v, 0); }
__device__ __forceinline__ char* cls_cnt(char* scr, int cls) { return scr + slot_line(3, 2, cls) * 128; }
__device__ __forceinline__ uint32_t cnt_wait(const void* p, unsigned target) {
    uint32_t v = 0;
#pragma unroll 1
    for (unsigned it = 0; it < (1u << 22) && v < target; it++) {
        asm volatile("ld.acquire.gpu.global.u32 %0, [%1];" : "=r"(v) : "l"(p) : "memory");
        v = uni(v);
    }
    asm volatile("fence.proxy.async.global;" ::: "memory");
    return v;
}
__device__ __forceinline__ void wg_fence() { asm volatile("wgmma.fence.sync.aligned;" ::: "memory"); }
__device__ __forceinline__ void wg_commit() { asm volatile("wgmma.commit_group.sync.aligned;" ::: "memory"); }
template <int N> __device__ __forceinline__ void wg_wait() { asm volatile("wgmma.wait_group.sync.aligned %0;" :: "n"(N) : "memory"); }
template <int N> __device__ __forceinline__ void reg_fence(float (&d)[N]) {
#pragma unroll
    for (int i = 0; i < N; i++) asm volatile("" : "+f"(d[i]) :: "memory");
}
template <int N> __device__ __forceinline__ void zero(float (&d)[N]) {
#pragma unroll
    for (int i = 0; i < N; i++) d[i] = 0.f;
}
__device__ __forceinline__ uint32_t pack2(float lo, float hi) {
    uint32_t r; asm volatile("cvt.rn.bf16x2.f32 %0, %1, %2;" : "=r"(r) : "f"(hi), "f"(lo)); return r;
}
__device__ __forceinline__ void stm4(uint32_t a, uint32_t r0, uint32_t r1, uint32_t r2, uint32_t r3) {
    asm volatile("stmatrix.sync.aligned.m8n8.x4.trans.shared.b16 [%0], {%1,%2,%3,%4};" :: "r"(a), "r"(r0), "r"(r1), "r"(r2), "r"(r3) : "memory");
}
__device__ __forceinline__ void stm2(uint32_t a, uint32_t r0, uint32_t r1) {
    asm volatile("stmatrix.sync.aligned.m8n8.x2.trans.shared.b16 [%0], {%1,%2};" :: "r"(a), "r"(r0), "r"(r1) : "memory");
}
struct Desc {
    uint32_t lo, hi;
    __device__ __forceinline__ operator uint64_t() const { return ((uint64_t)hi << 32) | lo; }
    __device__ __forceinline__ Desc operator+(uint32_t o) const { return Desc{lo + o, hi}; }
    __device__ __forceinline__ Desc operator^(uint32_t o) const { return Desc{lo ^ o, hi}; }
};
__device__ __forceinline__ Desc mkdesc(uint32_t addr, uint32_t lbo, uint32_t sbo, uint32_t swz) {
    return Desc{((addr & 0x3FFFF) >> 4) | ((lbo >> 4) << 16), (sbo >> 4) | (swz << 30)};
}
__device__ __forceinline__ uint32_t cos_bits(int k) {
    if (k > 20) k = 40 - k;
    const bool neg = k > 10;
    if (neg) k = 20 - k;
    const unsigned long long pk = k < 4 ? COS_PK0 : k < 8 ? COS_PK1 : COS_PK2;
    return (uint32_t)((pk >> (16 * (k & 3))) & 0xffff) ^ (neg ? 0x8000u : 0u);
}

__device__ __forceinline__ void task_w(int wg, int k, uint32_t sb) {
    const int tid = threadIdx.x & 127, w = uni(tid >> 5), lane = tid & 31, q = lane & 3;
    const int tb = 14 * k, t1 = min(tb + 14, 1800), cb0 = tb / 25;
    float acc[64];
    zero(acc);
    const int oc0 = tb - 25 * cb0, Lt = t1 - tb, L0 = min(Lt, 25 - oc0), n0 = (L0 + 3) >> 2;
    uint32_t a[2][4][4];
    auto gen = [&](uint32_t (&a)[4][4], int at) {
        const int phi = 8 * ((at < n0 ? oc0 + 4 * at : 4 * (at - n0)) + w) + (lane >> 2), f = (phi * 205) >> 12;
        const uint32_t ca = 8 * f + 4, cw = (phi - 20 * f) * 8, p0 = sb + TBL + cw * 2 * q;
#pragma unroll
        for (int kh = 0; kh < 7; kh++) {
            uint32_t v0, v1;
            asm volatile("ld.shared.u32 %0, [%1];" : "=r"(v0) : "r"(p0 + ca * kh));
            asm volatile("ld.shared.u32 %0, [%1];" : "=r"(v1) : "r"(p0 + cw + ca * kh));
            const int h = kh == 6 ? 1 : kh & 1;
            a[kh >> 1][2 * h] = __byte_perm(v0, v1, 0x5410);
            a[kh >> 1][2 * h + 1] = __byte_perm(v0, v1, 0x7632);
        }
        a[3][0] = 0; a[3][1] = 0;
    };
    gen(a[0], wg);
    if (wg) gen(a[1], wg + 2);
#pragma unroll 1
    for (int n = 0; n < 2; n++) {
        const int at = wg + 2 * n, i0 = at < n0 ? 4 * at : L0 + 4 * (at - n0), cnt = (at < n0 ? L0 : Lt) - i0, cb = cb0 + (at >= n0);
        if (cnt <= 0 || (n && !wg)) break;
        if (n) {
#pragma unroll
            for (int j = 0; j < 16; j++) a[0][j >> 2][j & 3] = a[1][j >> 2][j & 3];
        }
        const Desc dB = mkdesc(sb + WP + (cb - cb0) * 14336, 3584, 512, 2);
        if (at) mbar_wait(sb + BARS + 8 * (B_WCH + at - 1));
        mbar_wait(sb + BARS + 8 * (B_WF + 2 * (cb - cb0)));
        wg_fence();
        wgmma_rs_n128_z(acc, a[0][0][0], a[0][0][1], a[0][0][2], a[0][0][3], dB);
        wgmma_rs_n128_a(acc, a[0][1][0], a[0][1][1], a[0][1][2], a[0][1][3], dB + (uint32_t)(16 * 64 >> 4));
        wgmma_rs_n128_a(acc, a[0][2][0], a[0][2][1], a[0][2][2], a[0][2][3], dB + (uint32_t)(32 * 64 >> 4));
        wgmma_rs_n128_a(acc, a[0][3][0], a[0][3][1], a[0][3][2], a[0][3][3], dB + (uint32_t)(40 * 64 >> 4));
        wg_commit();
        wg_wait<0>();
        reg_fence(acc);
        e_arrive(sb + BARS + 8 * (B_WCH + at));
        if (w < cnt) {
            const uint32_t dst = sb + wst_off(i0 + w) + (lane >> 2) * 512 + (lane & 4) * 16 + ((q ^ cb) & 3) * 16;
#pragma unroll
            for (int j = 0; j < 4; j++)
#pragma unroll
                for (int e = 0; e < 2; e++)
                    asm volatile("st.shared.v4.u32 [%0], {%1,%2,%3,%4};" :: "r"((dst ^ (e * 64)) + j * 128),
                                 "r"(pack2(acc[4 * j + e], acc[16 + 4 * j + e])), "r"(pack2(acc[4 * j + 2 + e], acc[16 + 4 * j + 2 + e])),
                                 "r"(pack2(acc[32 + 4 * j + e], acc[48 + 4 * j + e])), "r"(pack2(acc[32 + 4 * j + 2 + e], acc[48 + 4 * j + 2 + e])) : "memory");
            fence_async_smem();
            e_arrive(sb + BARS + 8 * (B_WRD + i0 + w));
        }
    }
}

__device__ __forceinline__ void task_p1(int wg, int pair, uint32_t sb) {
    const int tid = threadIdx.x & 127, w = tid >> 5, lane = tid & 31;
    const uint32_t buf = sb + wg * 51200, bars = sb + BARS;
    uint32_t fr[5][10][2];
    float A[40], d[20];
    zero(A);
    {
        const Desc dA = mkdesc(buf, 3584, 512, 2), dB = mkdesc(sb + C1, 128, 256, 0);
        auto issue = [&](int g, float (&d)[40]) {
            mbar_wait(bars + 8 * (B_XF + wg * 5 + g));
            wg_fence();
            wgmma_ss_n80_z(d, dA + (uint32_t)(g * 8704 >> 4), dB);
#pragma unroll
            for (int j = 1; j < 5; j++) wgmma_ss_n80_a(d, dA + (uint32_t)((g * 8704 + j * 1024) >> 4), dB + (uint32_t)(j * 2560 >> 4));
            wg_commit();
        };
        auto pack = [&](int g, float (&d)[40]) {
            reg_fence(d);
#pragma unroll
            for (int f = 0; f < 10; f++) {
                fr[g][f][0] = pack2(d[4 * f], d[4 * f + 1]);
                fr[g][f][1] = pack2(d[4 * f + 2], d[4 * f + 3]);
            }
        };
        mbar_wait(bars + 8 * B_CF1);
#pragma unroll
        for (int g = 0; g < 4; g++) { issue(g, A); wg_wait<0>(); pack(g, A); }
        zero(d);
        mbar_wait(bars + 8 * (B_XF + wg * 5 + 4));
#pragma unroll
        for (int h = 0; h < 2; h++) {
            wg_fence();
            wgmma_ss_n40_z(d, dA + (uint32_t)(4 * 8704 >> 4), dB + (uint32_t)(h * 1280 >> 4));
#pragma unroll
            for (int j = 1; j < 5; j++) wgmma_ss_n40_a(d, dA + (uint32_t)((4 * 8704 + j * 1024) >> 4), dB + (uint32_t)((j * 2560 + h * 1280) >> 4));
            wg_commit(); wg_wait<0>(); reg_fence(d);
#pragma unroll
            for (int f = 0; f < 5; f++) { fr[4][5 * h + f][0] = pack2(d[4 * f], d[4 * f + 1]); fr[4][5 * h + f][1] = pack2(d[4 * f + 2], d[4 * f + 3]); }
        }
    }
    bb_break(sb);
    wg_bar(1 + wg);
    {
        const Desc dB = mkdesc(sb + C1 + 12800, 128, 256, 0);
        const int i = lane & 7, mi = lane >> 3, th = w >> 1, tz = (2 * pair + th) & 3;
        const uint32_t s0 = buf + (i >> 1) * 128 + (i & 1) * 64 + (((2 * (w & 1) + (mi & 1)) ^ tz ^ (i >> 1)) << 4);
        const uint32_t sA = s0 + th * 2048 + (mi >> 1) * 512, sB = s0 + th * 2048 + (mi >> 1) * 2560, sC = s0 + th * 1024 + (mi >> 1) * 512;
        auto issue = [&](int f, float (&d)[20]) {
            wg_fence();
            wgmma_rs_n40_z(d, fr[0][f][0], fr[0][f][1], fr[1][f][0], fr[1][f][1], dB);
            wgmma_rs_n40_a(d, fr[2][f][0], fr[2][f][1], fr[3][f][0], fr[3][f][1], dB + (uint32_t)(1280 >> 4));
            wgmma_rs_n40_a(d, fr[4][f % 5][0], fr[4][f % 5][1], fr[4][f % 5 + 5][0], fr[4][f % 5 + 5][1], dB + (uint32_t)((2560 + (f / 5) * 1280) >> 4));
            wg_commit();
        };
#pragma unroll
        for (int f = 0; f < 10; f++) {
            issue(f, d);
            if (f && !(f & 1)) { fence_async_smem(); e_arrive(bars + 8 * (B_RDY + wg * 5 + (f >> 1) - 1)); }
            wg_wait<0>(); reg_fence(d);
            const int Q = 5 * f;
            stm4(((Q & 3) == 3 ? sB : sA) + quad_off(Q), pack2(d[0], d[1]), pack2(d[2], d[3]), pack2(d[4], d[5]), pack2(d[6], d[7]));
            stm2(sA + quad_off(Q + 2), pack2(d[8], d[9]), pack2(d[10], d[11]));
            stm4((f == 9 ? sC : ((Q + 3) & 3) == 3 ? sB : sA) + quad_off(Q + 3), pack2(d[12], d[13]), pack2(d[14], d[15]), pack2(d[16], d[17]), pack2(d[18], d[19]));
            if (f == 9) { fence_async_smem(); e_arrive(bars + 8 * (B_RDY + wg * 5 + (f >> 1))); }
        }
    }
}

__device__ __forceinline__ void task_p2(int wg, int rk, uint32_t sb) {
    const int tid = threadIdx.x & 127, w = tid >> 5, lane = tid & 31;
    const uint32_t bars = sb + BARS;
    const int phi0 = 3 * rk, phiE = extra_phi(rk), mE = extra_mask(rk);
    uint4 wA[6], wB[6], wC[6], wE[6];
    auto ldw = [&](uint4 (&a)[6], int j, int phi) {
        const int pc = 3 * j + wg;
        const uint32_t p = sb + wslot(pc) + (lane & 3) * 512 + w * 128 + (((lane >> 2) ^ phi) & 1) * 64 + (((lane >> 3) ^ lane) & 3) * 16 + (phi & 1) * 8;
        mbar_wait(bars + 8 * (B_WL + pc));
#pragma unroll
        for (int s = 0; s < 6; s++) {
            asm volatile("ld.shared.v2.u32 {%0, %1}, [%2];" : "=r"(a[s].x), "=r"(a[s].y) : "r"(p + s * 2048) : "memory");
            asm volatile("ld.shared.v2.u32 {%0, %1}, [%2];" : "=r"(a[s].z), "=r"(a[s].w) : "r"((p ^ 8) + s * 2048) : "memory");
        }
        uint32_t dep = 0;
#pragma unroll
        for (int s = 0; s < 6; s++) dep |= a[s].x ^ a[s].z;
        if (__any_sync(0xffffffffu, dep == 0x7fc17fc1u)) __nanosleep(0);
        e_arrive(bars + 8 * (B_WE + pc));
    };
    ldw(wA, 0, phi0); ldw(wB, 1, phi0 + 1);
    mbar_wait(bars + 8 * (B_SIG + SIG_P1 + 1));
    const int i = lane & 7, mi = lane >> 3;
    const uint32_t soff = sb + S1 + wg * 4096 + mi * 512 + (i >> 1) * 128 + (i & 1) * 64;
    const int xo = w ^ (i >> 1);
    float d[32];
    zero(d);
    int n = 0;
    uint32_t xb = ((sb + xslot(0)) & 0x3FFFF) >> 4 | 1u << 16, mb = bars + 8 * wg;
    bool landed = false;
    auto unit = [&](const uint4 (&a)[6], int z) {
        const Desc d0{xb + (z & 2), (512u >> 4) | (2u << 30)}, d1 = d0 ^ 2u;
        if (!landed) mbar_wait(bars + 8 * (B_RF + n));
        mbar_wait(mb + 8 * (B_TOK - 1));
        wg_fence();
        wgmma_rs_n64_z(d, a[0].x, a[0].y, a[0].z, a[0].w, d0);
        wgmma_rs_n64_a(d, a[1].x, a[1].y, a[1].z, a[1].w, d1);
        e_arrive(bars + 8 * (n ? B_RE + n - 1 : B_RE + 13));
        const bool sfree = mbar_test(n >= 4 ? mb + 8 * (B_SFREE - 12) : bars + 8 * (B_TOK - 1));
        landed = mbar_test(bars + 8 * (B_RF + n + 1));
        wgmma_rs_n64_a(d, a[2].x, a[2].y, a[2].z, a[2].w, d0 + (uint32_t)(4096 >> 4));
        wgmma_rs_n64_a(d, a[3].x, a[3].y, a[3].z, a[3].w, d1 + (uint32_t)(4096 >> 4));
        e_arrive(mb + 8 * B_TOK);
        wgmma_rs_n64_a(d, a[4].x, a[4].y, a[4].z, a[4].w, d0 + (uint32_t)(8192 >> 4));
        wgmma_rs_n64_a(d, a[5].x, a[5].y, a[5].z, a[5].w, d1 + (uint32_t)(8192 >> 4));
        wg_commit();
        if (!sfree) mbar_wait(mb + 8 * (B_SFREE - 12));
        const uint32_t a0 = soff + (n & 3) * 12288 + ((xo ^ z) << 4);
        n++;
        xb = ((sb + xslot(n)) & 0x3FFFF) >> 4 | 1u << 16;
        wg_wait<0>();
        reg_fence(d);
        uint32_t p[8];
#pragma unroll
        for (int j = 0; j < 8; j++) p[j] = pack2(d[4 * j] - d[4 * j + 3], d[4 * j + 2] + d[4 * j + 1]);
        stm4(a0, p[0], p[1], p[2], p[3]);
        stm4(a0 + 2048, p[4], p[5], p[6], p[7]);
        fence_async_smem();
        e_arrive(mb + 8 * (B_RDY + R_P2));
        mb += 24;
    };
    const int zA = phi0 & 3, zB = (phi0 + 1) & 3, zC = (phi0 + 2) & 3, zE = phiE & 3;
#pragma unroll 1
    for (int it = 0; it < 4; it++) {
        unit(wA, zA);
        unit(wB, zB);
        if (it == 0) ldw(wC, 2, phi0 + 2);
        unit(wC, zC);
        if (it == 0 && mE) ldw(wE, 3, phiE);
        if (mE >> it & 1) unit(wE, zE);
    }
}

__device__ __forceinline__ void task_p3(int wg, int pair, uint32_t sb) {
    const int tid = threadIdx.x & 127, w = tid >> 5, lane = tid & 31;
    const uint32_t buf = sb + (wg ? 3 - wg : 0) * 51200, bars = sb + BARS;
    uint32_t fr[10][4][2];
    float acc[2][16];
    zero(acc[0]); zero(acc[1]);
    {
        const Desc dB = mkdesc(sb + C3, 128, 256, 0);
        const uint32_t a0 = (buf & 0x3FFFF) >> 4;
        auto dq = [&](int Q) {
            return Desc{a0 + (uint32_t)((quad_off(Q) >> 4) | ((Q < 48 ? 2048 : 1024) >> 4) << 16), (uint32_t)((quad_off(Q + 1) - quad_off(Q)) >> 4) | (2u << 30)};
        };
        auto issue = [&](int f) {
            if (!(f & 1)) mbar_wait(bars + 8 * (B_YF + wg * 5 + (f >> 1)));
            wg_fence();
            wgmma_ss_n32_z(acc[f & 1], dq(5 * f), dB);
            wgmma_ss_n32_a(acc[f & 1], dq(5 * f + 1), dB + (uint32_t)(1024 >> 4));
            wgmma_ss_n32_a(acc[f & 1], dq(5 * f + 3), dB + (uint32_t)(2048 >> 4));
            wg_commit();
        };
        mbar_wait(bars + 8 * B_CF3);
        issue(0);
#pragma unroll
        for (int f = 0; f < 10; f++) {
            if (f < 9) { issue(f + 1); wg_wait<1>(); } else wg_wait<0>();
            float (&d)[16] = acc[f & 1];
            reg_fence(d);
#pragma unroll
            for (int g = 0; g < 4; g++) { fr[f][g][0] = pack2(d[4 * g], d[4 * g + 1]); fr[f][g][1] = pack2(d[4 * g + 2], d[4 * g + 3]); }
        }
    }
    {
        const Desc dB = mkdesc(sb + C3 + 3072, 128, 256, 0);
        const int i = lane & 7, mi = lane >> 3, th = w >> 1, tz = (2 * pair + th) & 3;
        const int oct = (2 * (w & 1) + (mi & 1)) ^ tz;
        const uint32_t soff = buf + th * 3584 + (mi >> 1) * 512 + i * 64 + ((oct ^ (i >> 1)) << 4);
        auto mma = [&](int t, int s) {
            if (t > 6) return;
            const int g = t < 6 ? 1 + (t >> 1) : 0;
            const uint32_t o = t < 6 ? (t & 1) * 1024 : 8960, st = t < 6 ? 1792 : 1024;
            if (s == 0) { wg_fence(); wgmma_rs_n32_z(acc[t & 1], fr[0][g][0], fr[0][g][1], fr[1][g][0], fr[1][g][1], dB + (o >> 4)); }
            else wgmma_rs_n32_a(acc[t & 1], fr[2 * s][g][0], fr[2 * s][g][1], fr[2 * s + 1][g][0], fr[2 * s + 1][g][1], dB + ((o + s * st) >> 4));
            if (s == 4) wg_commit();
        };
        const int row = th * 14 + 4 * (mi >> 1) + (i >> 1);
        const uint32_t z0 = buf + row * 128 + (i & 1) * 64 + ((oct ^ (row & 3)) << 4), z1 = (lane & 20) == 20 ? buf + 4096 + lane * 16 : z0 + 1024;
        bb_break(sb);
#pragma unroll
        for (int s = 0; s < 5; s++) mma(0, s);
        wg_bar(1 + wg);
#pragma unroll
        for (int t = 0; t < 7; t++) {
#pragma unroll
            for (int s = 0; s < 2; s++) mma(t + 1, s);
            if (t < 6) { wg_commit(); wg_wait<1>(); } else wg_wait<0>();
            float (&d)[16] = acc[t & 1];
            reg_fence(d);
            const uint32_t a = soff + (1 + (t >> 1)) * 7168 + (t & 1) * 2048;
            stm4(t < 6 ? a : z0, pack2(d[0], d[1]), pack2(d[2], d[3]), pack2(d[4], d[5]), pack2(d[6], d[7]));
            mma(t + 1, 2);
            if (t & 1) stm2(a + 1024, pack2(d[8], d[9]), pack2(d[10], d[11]));
            else stm4(t < 6 ? a + 1024 : z1, pack2(d[8], d[9]), pack2(d[10], d[11]), pack2(d[12], d[13]), pack2(d[14], d[15]));
#pragma unroll
            for (int s = 3; s < 5; s++) mma(t + 1, s);
            if ((t & 1) || t == 6) { fence_async_smem(); e_arrive(bars + 8 * (B_RDY + R_P3 + wg * 4 + (t >> 1))); }
        }
    }
}

__device__ __forceinline__ void load_x(int cls, int rk, int u, uint32_t sb, const Maps& mp) {
    const int id = u * NH + rk, pl = id / 3, c0 = 32 * (id - 3 * pl), tp = cls * 4 + (pl >> 4), col = 14 * (pl & 15) - 8;
    const uint32_t bar = sb + BARS + 8 * (B_XF + u * 5), dst = sb + u * 51200;
    const int wrap = col < 0 ? 224 : 0;
    if (tp) {
#pragma unroll
        for (int g = 0; g < 5; g++) e_ld3(dst + g * 8704, &mp.x34, c0, col + 4 * g + (g < 2 ? wrap : 0), 28 * tp - 6, bar + 8 * g);
    } else {
#pragma unroll
        for (int g = 0; g < 5; g++) {
            e_ld3(dst + g * 8704, &mp.x6, c0, col + 4 * g + (g < 2 ? wrap : 0), 218, bar + 8 * g);
            e_ld3(dst + g * 8704 + 1536, &mp.x28, c0, col + 4 * g + (g < 2 ? wrap : 0), 0, bar + 8 * g);
        }
    }
}

__device__ __forceinline__ void load_x_box(int cls, int rk, int u, int g, uint32_t sb, const Maps& mp) {
    const int id = u * NH + rk, pl = id / 3, c0 = 32 * (id - 3 * pl), tp = cls * 4 + (pl >> 4), col = 14 * (pl & 15) - 8 + 4 * g;
    e_ld3(sb + u * 51200 + g * 8704, &mp.x34, c0, col < 0 ? col + 224 : col, 28 * tp - 6, sb + BARS + 8 * (B_XF + u * 5 + g));
}

__device__ __forceinline__ void load_first(uint32_t sb, const Maps& mp, const Ptrs& pt) {
    const uint32_t bars = sb + BARS;
    const int k = blockIdx.x;
    if (k < 129) {
        const int cb0 = 14 * k / 25, cb1 = min((14 * k + 13) / 25, 71);
#pragma unroll 1
        for (int cb = cb0; cb <= cb1; cb++) {
            const int b = cb / 24, i0 = 16 * ((cb >> 2) - 6 * b) + 2 * (cb & 3);
            const uint32_t bar = bars + 8 * (B_WF + 2 * (cb - cb0));
            e_expect(bar, 14336);
            e_ld4(sb + WP + (cb - cb0) * 14336, &mp.w, 32 * b, i0, bar);
            e_ld4(sb + WP + (cb - cb0) * 14336 + 7168, &mp.w, 32 * b, i0 + 8, bar);
        }
    }
    e_expect(bars + 8 * B_CF1, 17920); e_g2s(sb + C1, pt.tab1, 17920, bars + 8 * B_CF1);
    if ((threadIdx.x & 31) < 15) asm volatile("mbarrier.arrive.expect_tx.shared::cta.b64 _, [%0], 8704;" :: "r"(bars + 8 * (B_XF + (threadIdx.x & 31))) : "memory");
    __syncwarp();
}

__device__ __forceinline__ uint32_t get_rel(uint32_t sb) {
    mbar_wait(sb + BARS + 8 * B_REL);
    uint32_t v; asm volatile("ld.shared.u32 %0, [%1];" : "=r"(v) : "r"(sb + REL) : "memory");
    return uni(v);
}

__device__ __forceinline__ void load_warp(int cls, int rk, uint32_t sb, const Ptrs& pt) {
    const uint32_t bars = sb + BARS;
    mbar_wait(bars + 8 * (B_SIG + SIG_P1));
    const uint32_t rel = get_rel(sb);
    const char* cnt = cls_cnt(pt.scr, cls);
    const int mE = extra_mask(rk);
    const int lpA = phi_line(3 * rk, rel), lpB = phi_line(3 * rk + 1, rel), lpC = phi_line(3 * rk + 2, rel), lpE = phi_line(extra_phi(rk), rel);
    e_arrive(bars + 8 * (B_TOK - 1));
    if ((threadIdx.x & 31) < 14) asm volatile("mbarrier.arrive.expect_tx.shared::cta.b64 _, [%0], 12288;" :: "r"(bars + 8 * (B_RF + (threadIdx.x & 31))) : "memory");
    __syncwarp();
    int n = 0;
#pragma unroll 1
    for (int pg = 0; pg < 4; pg++) {
        const int l0 = slot_line(0, pg, cls), l1 = slot_line(1, pg, cls), l2 = slot_line(2, pg, cls);
        auto unit = [&](int lp) {
            const uint32_t bar = bars + 8 * (B_RF + n), dst = sb + xslot(n);
            mbar_wait(bars + 8 * (n >= 8 ? B_RE + n - 8 : n >= 4 ? B_SIG + SIG_P1 + (rk < 60 ? 2 : 1) : B_WE + ((0x4310 >> (4 * n)) & 15)));
            e_g2s(dst, pt.scr + (size_t)(lp ^ l0) * 128, 4096, bar);
            e_g2s(dst + 4096, pt.scr + (size_t)(lp ^ l1) * 128, 4096, bar);
            e_g2s(dst + 8192, pt.scr + (size_t)(lp ^ l2) * 128, 4096, bar);
            n++;
        };
        cnt_wait(cnt + (CNT_P1 + pg) * 128, 48);
        unit(lpA); unit(lpB); unit(lpC);
        if (mE >> pg & 1) unit(lpE);
        if (pg == 1) { mbar_wait(bars + 8 * B_P1D); e_expect(bars + 8 * B_CF3, 17152); e_g2s(sb + C3, pt.tab3, 17152, bars + 8 * B_CF3); }
    }
}

__device__ __forceinline__ int near_page(char* p, int rounds) {
#pragma unroll
    for (int e = 0; e < 4; e++) asm volatile("st.relaxed.gpu.global.v4.u32 [%0], {%1, %1, %1, %1};" :: "l"(p + (e >> 1) * 4096 + (e & 1) * 16), "r"(0) : "memory");
    int score = 0;
#pragma unroll 1
    for (int r = 0; r < rounds; r++) {
        uint32_t v0, v1, t0, t1;
        asm volatile("atom.relaxed.gpu.global.exch.b32 %0, [%1], 1;" : "=r"(v0) : "l"(p + (r & 1) * 4096) : "memory");
        asm volatile("atom.relaxed.gpu.global.exch.b32 %0, [%1], 1;" : "=r"(v1) : "l"(p + (~r & 1) * 4096) : "memory");
        asm volatile("{\n.reg .pred p;\nsetp.ne.u32 p, %1, 0xffffffff;\nmov.u32 %0, 0;\n@p mov.u32 %0, %%clock;\n}" : "=r"(t0) : "r"(v0) : "memory");
        asm volatile("{\n.reg .pred p;\nsetp.ne.u32 p, %1, 0xffffffff;\nmov.u32 %0, 0;\n@p mov.u32 %0, %%clock;\n}" : "=r"(t1) : "r"(v1) : "memory");
        const int gap = min((int)(t1 - t0), 160) - 80;
        score += (r & 1) ? gap : -gap;
    }
    return score > 0;
}

__device__ __forceinline__ uint32_t find_role(uint32_t sb, char* scr) {
    const int k = blockIdx.x;
    int c = near_page(scr + (slot_line(3, 3, 0) + phi_line(1 + (k >> 5), 0) + (k & 31)) * 128, 1);
    int r;
    asm volatile("atom.relaxed.gpu.global.add.u32 %0, [%1], 1;" : "=r"(r) : "l"(cls_cnt(scr, c) + CNT_RANK * 128) : "memory");
    asm volatile("st.shared.u32 [%0], %1;" :: "r"(sb + REL + 8), "r"(c) : "memory");
    if (r >= NH) { c ^= 1; r = NSM - 1 - r; }
    asm volatile("st.shared.u32 [%0], %1;" :: "r"(sb + REL + 4), "r"(c << 8 | r) : "memory");
    return c << 8 | r;
}
__device__ __forceinline__ void get_role(uint32_t sb, int& cls, int& rk) {
    mbar_wait(sb + BARS + 8 * B_ROLE);
    uint32_t v; asm volatile("ld.shared.u32 %0, [%1];" : "=r"(v) : "r"(sb + REL + 4) : "memory");
    v = uni(v); cls = v >> 8; rk = v & 255;
}

__device__ __forceinline__ void load3_warp(int cls, int rk, uint32_t sb, const Maps& mp, const Ptrs& pt) {
    const uint32_t bars = sb + BARS;
    mbar_wait(bars + 8 * B_XF);
    const uint32_t rel = cnt_wait(pt.cnt + CNT_REL * 32, 12u << 16);
    asm volatile("st.shared.u32 [%0], %1;" :: "r"(sb + REL), "r"(rel) : "memory");
    __syncwarp();
    e_arrive(bars + 8 * B_REL);
    mbar_wait(bars + 8 * (B_SIG + SIG_W));
    cnt_wait(cls_cnt(pt.scr, cls) + CNT_W * 128, NSM);
    {
        const int np = rk >= 58 ? 12 : 9;
#pragma unroll 1
        for (int o = 0; o < np; o++) {
            const int pc = (0xba9876524310ull >> (4 * o)) & 15;
            if (o == 4) mbar_wait(bars + 8 * (B_SIG + SIG_P1));
            if (o >= 8) mbar_wait(bars + 8 * (B_WE + ((0x5762 >> (4 * (o - 8))) & 15)));
            if (o >= 4) mbar_wait(bars + 8 * (B_WL + ((0xba9876524310ull >> (4 * (o - 4))) & 15)));
            e_expect(bars + 8 * (B_WL + pc), 12288);
            e_g2s(sb + wslot(pc), pt.wf + (pc < 9 ? 9 * rk + pc : 3 * extra_phi(rk) + pc - 9) * 12288, 12288, bars + 8 * (B_WL + pc));
        }
        if (np == 12) { mbar_wait(bars + 8 * (B_WE + 9)); mbar_wait(bars + 8 * (B_WE + 10)); mbar_wait(bars + 8 * (B_WE + 11)); }
    }
    mbar_wait(bars + 8 * (B_SIG + SIG_P2 + 1));
    const int nu = rk < 60 ? 3 : 2;
#pragma unroll 1
    for (int u = 0; u < nu; u++) {
        const int id = u * NH + rk, pl = id / 3, chunk = id - 3 * pl;
        const int l0 = slot_line(chunk, pl >> 4, cls) + (pl & 15) * 2;
        const uint32_t buf = sb + (u ? 3 - u : 0) * 51200, bar = bars + 8 * (B_YF + u * 5);
#pragma unroll
        for (int j = 0; j < 5; j++) e_expect(bar + 8 * j, j == 4 ? 10240 : (j & 1) ? 8192 : 12288);
        if (u) mbar_wait(bars + 8 * (B_SIG + SIG_P2 + 3));
        cnt_wait(cls_cnt(pt.scr, cls) + (CNT_P2 + (pl >> 4)) * 128, NH);
        if (u == nu - 1) e_arrive(bars + 8 * B_FIN);
        const uint32_t r2 = uni(rel) << 5;
#pragma unroll
        for (int G = 0; G < 13; G++)
            e_ld5(buf + G * 4096, G < 12 ? &mp.f16 : &mp.f8, (l0 ^ ((r2 >> G) & 32)) + (G << 14), bar + 8 * ((2 * G) / 5));
    }
}

__device__ __forceinline__ void store_warp(uint32_t sb, const Maps& mp, const Ptrs& pt) {
    const uint32_t bars = sb + BARS;
    const int k = blockIdx.x;
    uint32_t pa = 0, pb = 0, qa = 0, qb = 0;
    auto arr2 = [&](uint32_t& a, uint32_t& b) { if (a) e_arrive(a); if (b) e_arrive(b); a = b = 0; };
    auto pre = [&](int idx) {
        const uint32_t bar = bars + 8 * idx;
        if ((pb | qb) && !mbar_test(bar)) { bulk_wait<0>(); arr2(qa, qb); arr2(pa, pb); }
        mbar_wait(bar);
    };
    auto post = [&](uint32_t fr) {
        bulk_commit(); bulk_wait_read<2>();
        if (qb) bulk_wait<2>();
        arr2(qa, qb); qa = pa; qb = pb; pb = 0; pa = fr;
    };
    auto after = [&](int sig) { pb = bars + 8 * (B_SIG + sig); };
    int cls, rk; get_role(sb, cls, rk);
    {
        int cb = 14 * k / 25, oc = 14 * k - 25 * cb;
        int g1 = 0;
#pragma unroll 1
        for (int i = 0; i < 14 && cb < 72; i++) {
            pre(B_WRD + i);
            e_st3(&mp.wst, sb + wst_off(i), 0, 8 * oc, cb);
            post(0);
            if (T1MASK >> i & 1) load_x_box(cls, rk, 1, g1++, sb, mp);
            if (++oc == 25) { oc = 0; cb++; }
        }
#pragma unroll 1
        for (; g1 < 5; g1++) load_x_box(cls, rk, 1, g1, sb, mp);
        after(SIG_W);
    }
    pre(B_REL);
    const uint32_t rel = get_rel(sb);
    const int nu = rk < 60 ? 3 : 2;
#pragma unroll 1
    for (int u = 0; u < nu; u++) {
        const int id = u * NH + rk, pl = id / 3, chunk = id - 3 * pl;
        const int l0 = slot_line(chunk, pl >> 4, cls) + (pl & 15) * 2;
        int j = B_RDY + u * 5;
        int g2 = 0;
        const int m2 = (u == 0 && nu == 3) ? T2MASK : 0;
#pragma unroll 1
        for (int G = 0; G < 13; G++) {
            if (0x4a5 >> G & 1) pre(j++);
            e_st5(G < 12 ? &mp.f16 : &mp.f8, sb + u * 51200 + G * 4096, (l0 ^ ((rel >> G) & 1) << 5) + (G << 14));
            post(0);
            if (m2 >> G & 1) load_x_box(cls, rk, 2, g2++, sb, mp);
        }
        after(SIG_P1 + u);
    }
    const int mE = extra_mask(rk);
    int n = 0;
#pragma unroll 1
    for (int pg = 0; pg < 4; pg++) {
        const int nj = 3 + (mE >> pg & 1);
        const int l0 = slot_line(0, pg, cls), l1 = slot_line(1, pg, cls), l2 = slot_line(2, pg, cls);
#pragma unroll 1
        for (int j = 0; j < nj; j++) {
            const int lp = phi_line(j == 3 ? extra_phi(rk) : 3 * rk + j, rel);
#pragma unroll
            for (int b = 0; b < 3; b++) {
                pre(B_RDY + R_P2 + n * 3 + b);
                e_s2g(pt.scr + (size_t)(lp ^ (b == 0 ? l0 : b == 1 ? l1 : l2)) * 128, sb + S1 + (n & 3) * 12288 + b * 4096, 4096);
                post(bars + 8 * (B_SFREE + n * 3 + b));
            }
            n++;
        }
        after(SIG_P2 + pg);
    }
#pragma unroll 1
    for (int u = 0; u < nu; u++) {
        const int id = u * NH + rk, pl = id / 3, chunk = id - 3 * pl, tp = cls * 4 + (pl >> 4), tx = pl & 15;
        const uint32_t buf = sb + (u ? 3 - u : 0) * 51200;
#pragma unroll
        for (int gg = 1; gg < 5; gg++) {
            pre(B_RDY + R_P3 + u * 4 + gg - 1);
            if (gg < 4) e_st3(&mp.y4, buf + gg * 7168, 32 * chunk, 14 * tx - 4 + 4 * gg, 28 * tp);
            else e_st3(&mp.y2, buf, 32 * chunk, tx == 0 ? 222 : 14 * tx - 2, 28 * tp);
            post(0);
        }
    }
    bulk_wait_read<0>();
}

__device__ __forceinline__ void signal_warp(int cls, int rk, uint32_t sb, const Ptrs& pt) {
    const uint32_t bars = sb + BARS;
    char* cnt = cls_cnt(pt.scr, cls);
    if (threadIdx.x & 31) return;
#pragma unroll 1
    for (int c = 0; c < 8; c++) {
        if (c == SIG_P1 + 2 && rk >= 60) continue;
        char* ctr = cnt + (c == SIG_W ? CNT_W : c < SIG_P2 ? CNT_P1 + ((c - SIG_P1) * NH + rk) / 48 : CNT_P2 + c - SIG_P2) * 128;
        mbar_wait(bars + 8 * (B_SIG + c));
        fence_async();
        asm volatile("red.relaxed.gpu.global.add.u32 [%0], 1;" :: "l"(ctr) : "memory");
        if (c == SIG_W) asm volatile("red.relaxed.gpu.global.add.u32 [%0], 1;" :: "l"((uintptr_t)ctr ^ 4096) : "memory");
    }
    mbar_wait(bars + 8 * B_FIN);
    unsigned old;
    asm volatile("atom.add.relaxed.gpu.global.u32 %0, [%1], 1;" : "=r"(old) : "l"(pt.cnt + CNT_DONE * 32) : "memory");
    if (old == NSM - 1) {
#pragma unroll
        for (int c = 0; c < NCNT; c++) pt.cnt[c * 32] = 0;
#pragma unroll 1
        for (int c = 0; c < NCLS; c++) { *reinterpret_cast<unsigned*>(cnt + c * 128) = 0; *reinterpret_cast<unsigned*>(((uintptr_t)cnt ^ 4096) + c * 128) = 0; }
    }
}

__global__ void __launch_bounds__(512, 1) fftconv_kernel(const Ptrs pt, const __grid_constant__ Maps mp) {
    extern __shared__ __align__(1024) uint8_t smem[];
    const uint32_t sb = smem_u32(smem);
    const int tid = threadIdx.x, warp = uni(tid >> 5), wg = warp >> 2;
    int cls, rk;
    auto bar_init = [&](int i) {
        uint32_t c = 1;
        if (i == B_P1D || (i >= B_RE && i < B_RE + 14)) c = 12;
        else if ((i >= B_WCH && i < B_WL) || i >= B_TOK) c = 4;
        asm volatile("st.shared.v2.u32 [%0], {%1, %2};" :: "r"(sb + BARS + 8 * i), "r"((0x100000u - c) << 1), "r"((0x100000u - c) << 11) : "memory");
        fence_async_smem();
    };
    if (wg == 3) {
        asm volatile("setmaxnreg.dec.sync.aligned.u32 32;");
        if (warp == 12) {
            bar_init(tid & 31);
            __syncwarp();
            asm volatile("bar.arrive 4, 416;" ::: "memory");
            load_first(sb, mp, pt);
            asm volatile("bar.sync 5, 416;" ::: "memory");
            get_role(sb, cls, rk);
            load_warp(cls, rk, sb, pt);
        } else if (warp == 13) {
            if ((tid & 31) < 8) asm volatile("prefetch.tensormap [%0];" :: "l"(reinterpret_cast<const CUtensorMap*>(&mp) + 1 + (tid & 31)) : "memory");
            __syncwarp();
            asm volatile("bar.sync 6, 416;" ::: "memory");
            store_warp(sb, mp, pt);
        } else if (warp == 14) {
            const int G = blockIdx.x - 119;
            int sel = 0;
            if (G >= 1 && (tid & 31) == 0) sel = near_page(pt.scr + ((size_t)G << 21) + slot_line(3, 3, 0) * 128, 2);
            __syncwarp();
            asm volatile("bar.sync 7, 416;" ::: "memory");
            get_role(sb, cls, rk);
            if (G >= 1 && (tid & 31) == 0) {
                uint32_t c; asm volatile("ld.shared.u32 %0, [%1];" : "=r"(c) : "r"(sb + REL + 8) : "memory");
                asm volatile("red.relaxed.gpu.global.add.u32 [%0], %1;" :: "l"(pt.cnt + CNT_REL * 32), "r"(0x10000u | (sel ^ c) << G) : "memory");
            }
            __syncwarp();
            load3_warp(cls, rk, sb, mp, pt);
        } else {
            uint32_t role = 0;
            if ((tid & 31) == 0) role = find_role(sb, pt.scr);
            role = uni(role); cls = role >> 8; rk = role & 255;
            asm volatile("bar.sync 8, 416;" ::: "memory");
            load_x(cls, rk, 0, sb, mp);
            e_arrive(sb + BARS + 8 * B_ROLE);
            signal_warp(cls, rk, sb, pt);
        }
    } else {
        if (tid >= 32 && tid < NBAR) bar_init(tid);
        {
            const int r = tid % 40;
            asm volatile("st.shared.u32 [%0], %1;" :: "r"(sb + TBL + 4 * tid), "r"(cos_bits(r) | (cos_bits(r < 30 ? r + 10 : r - 30) << 16)) : "memory");
        }
        __syncwarp();
        asm volatile("bar.sync 4, 416;" ::: "memory");
        asm volatile("bar.arrive 5, 416;" ::: "memory");
        asm volatile("bar.arrive 6, 416;" ::: "memory");
        asm volatile("bar.arrive 7, 416;" ::: "memory");
        asm volatile("bar.arrive 8, 416;" ::: "memory");
        task_w(wg, blockIdx.x, sb);
        asm volatile("setmaxnreg.inc.sync.aligned.u32 160;");
        get_role(sb, cls, rk);
        const int id = wg * NH + rk;
        if (id < 192) task_p1(wg, id / 3, sb);
        e_arrive(sb + BARS + 8 * B_P1D);
        task_p2(wg, rk, sb);
        if (id < 192) task_p3(wg, id / 3, sb);
    }
}

__global__ void fallback_kernel(const __nv_bfloat16* x, const __nv_bfloat16* w, __nv_bfloat16* y) {
    const int px = blockIdx.x, o = threadIdx.x, h = px / 224, c = px % 224;
    float acc = 0.f;
    for (int kh = 0; kh < 7; kh++)
        for (int kw = 0; kw < 7; kw++) {
            const __nv_bfloat16* xp = x + (((h - kh + 224) % 224) * 224 + (c - kw + 224) % 224) * 96;
            const __nv_bfloat16* wp = w + (kh * 7 + kw) * 9216 + o;
            for (int i = 0; i < 96; i++) acc += __bfloat162float(xp[i]) * __bfloat162float(wp[i * 96]);
        }
    y[px * 96 + o] = __float2bfloat16(acc);
}

typedef CUresult (*EncodeFn)(CUtensorMap*, CUtensorMapDataType, cuuint32_t, void*, const cuuint64_t*, const cuuint64_t*, const cuuint32_t*, const cuuint32_t*,
                             CUtensorMapInterleave, CUtensorMapSwizzle, CUtensorMapL2promotion, CUtensorMapFloatOOBfill);

static void encode3(EncodeFn fn, CUtensorMap* m, void* ptr, uint64_t d0, uint64_t d1, uint64_t d2, uint64_t s1, uint64_t s2,
                    uint32_t b0, uint32_t b1, uint32_t b2, CUtensorMapSwizzle sw) {
    cuuint64_t dims[3] = {d0, d1, d2}, strides[2] = {s1, s2};
    cuuint32_t box[3] = {b0, b1, b2}, es[3] = {1, 1, 1};
    fn(m, CU_TENSOR_MAP_DATA_TYPE_BFLOAT16, 3, ptr, dims, strides, box, es, CU_TENSOR_MAP_INTERLEAVE_NONE, sw,
       CU_TENSOR_MAP_L2_PROMOTION_NONE, CU_TENSOR_MAP_FLOAT_OOB_FILL_NONE);
}

extern "C" void kernel_launch(void* const* d_in, const int* in_sizes, int n_in, void* d_out, int out_size) {
    (void)in_sizes; (void)n_in; (void)out_size;
    int dev = 0, nsm = 0;
    cudaGetDevice(&dev);
    cudaDeviceGetAttribute(&nsm, cudaDevAttrMultiProcessorCount, dev);
    if (nsm < NSM) {
        fallback_kernel<<<224 * 224, 96>>>((const __nv_bfloat16*)d_in[0], (const __nv_bfloat16*)d_in[1], (__nv_bfloat16*)d_out);
        return;
    }
    void* fnp = nullptr; cudaDriverEntryPointQueryResult qr;
    cudaGetDriverEntryPoint("cuTensorMapEncodeTiled", &fnp, cudaEnableDefault, &qr);
    EncodeFn fn = (EncodeFn)fnp;
    void* xf = nullptr; cudaGetSymbolAddress(&xf, g_scr);
    xf = (void*)(((uintptr_t)xf + (1u << 21) - 1) & ~(uintptr_t)((1u << 21) - 1));
    void* wf = nullptr; cudaGetSymbolAddress(&wf, g_wf);
    Maps mp;
    Ptrs pt;
    pt.scr = (char*)xf; pt.wf = (const char*)wf;
    void* p = nullptr;
    cudaGetSymbolAddress(&p, TAB_P1); pt.tab1 = p;
    cudaGetSymbolAddress(&p, TAB_P3); pt.tab3 = p;
    cudaGetSymbolAddress(&p, g_cnt); pt.cnt = (unsigned*)p;
    {
        cuuint32_t b16[5] = {64, 4, 2, 2, 2}, b8[5] = {64, 4, 2, 1, 2}, es[5] = {1, 1, 1, 1, 1};
        cuuint64_t d[5] = {64, 4, 2, 2, 13 << 14}, st[4] = {16384, 262144, 1048576, 128};
        fn(&mp.f16, CU_TENSOR_MAP_DATA_TYPE_BFLOAT16, 5, xf, d, st, b16, es, CU_TENSOR_MAP_INTERLEAVE_NONE, CU_TENSOR_MAP_SWIZZLE_NONE, CU_TENSOR_MAP_L2_PROMOTION_NONE, CU_TENSOR_MAP_FLOAT_OOB_FILL_NONE);
        fn(&mp.f8, CU_TENSOR_MAP_DATA_TYPE_BFLOAT16, 5, xf, d, st, b8, es, CU_TENSOR_MAP_INTERLEAVE_NONE, CU_TENSOR_MAP_SWIZZLE_NONE, CU_TENSOR_MAP_L2_PROMOTION_NONE, CU_TENSOR_MAP_FLOAT_OOB_FILL_NONE);
    }
    encode3(fn, &mp.x6, d_in[0], 96, 224, 224, 192, 224 * 192, 32, 4, 6, CU_TENSOR_MAP_SWIZZLE_64B);
    encode3(fn, &mp.x34, d_in[0], 96, 224, 224, 192, 224 * 192, 32, 4, 34, CU_TENSOR_MAP_SWIZZLE_64B);
    encode3(fn, &mp.x28, d_in[0], 96, 224, 224, 192, 224 * 192, 32, 4, 28, CU_TENSOR_MAP_SWIZZLE_64B);
    {
        cuuint32_t box[4] = {32, 8, 7, 2}, es[4] = {1, 1, 1, 1};
        cuuint64_t d[4] = {96, 7, 7, 96}, st[3] = {18432, 7 * 18432, 192};
        fn(&mp.w, CU_TENSOR_MAP_DATA_TYPE_BFLOAT16, 4, d_in[1], d, st, box, es, CU_TENSOR_MAP_INTERLEAVE_NONE, CU_TENSOR_MAP_SWIZZLE_64B, CU_TENSOR_MAP_L2_PROMOTION_NONE, CU_TENSOR_MAP_FLOAT_OOB_FILL_NONE);
    }
    encode3(fn, &mp.wst, wf, 256, 200, 72, 36864, 512, 256, 8, 1, CU_TENSOR_MAP_SWIZZLE_NONE);
    encode3(fn, &mp.y4, d_out, 96, 224, 224, 192, 224 * 192, 32, 4, 28, CU_TENSOR_MAP_SWIZZLE_64B);
    encode3(fn, &mp.y2, d_out, 96, 224, 224, 192, 224 * 192, 32, 2, 28, CU_TENSOR_MAP_SWIZZLE_64B);
    constexpr int SMEM_LAUNCH = SMEM_BYTES;
    cudaFuncSetAttribute(fftconv_kernel, cudaFuncAttributeMaxDynamicSharedMemorySize, SMEM_LAUNCH);
    fftconv_kernel<<<NSM, 512, SMEM_LAUNCH>>>(pt, mp);
}
```

```cpp
#include <cuda_runtime.h>
#include <cuda_bf16.h>
#include <cuda.h>
#include <stdint.h>

__device__ __align__(128) const uint32_t TAB_P1[4480] = {
0x3e75,0,0x3e72,0,0x8000,0,0xbd19,0,0x3e750000,0,0x3e720000,0,0x80000000,0,0xbd190000,0,
0,0x3e75,0,0x3e72,0,0x8000,0,0xbd19,0,0x3e750000,0,0x3e720000,0,0x80000000,0,0xbd190000,
0x3e69,0,0x3e5a,0,0xbd97,0,0xbdde,0,0x3e690000,0,0x3e5a0000,0,0xbd970000,0,0xbdde0000,0,
0,0x3e69,0,0x3e5a,0,0xbd97,0,0xbdde,0,0x3e690000,0,0x3e5a0000,0,0xbd970000,0,0xbdde0000,
0x3e75,0,0x3e5a,0,0x8000,0,0xbdde,0,0x3e750000,0,0x3e5a0000,0,0x80000000,0,0xbdde0000,0,
0,0x3e75,0,0x3e5a,0,0x8000,0,0xbdde,0,0x3e750000,0,0x3e5a0000,0,0x80000000,0,0xbdde0000,
0x3e10,0,0x3d19,0,0xbe46,0,0xbe72,0,0x3e100000,0,0x3d190000,0,0xbe460000,0,0xbe720000,0,
0,0x3e10,0,0x3d19,0,0xbe46,0,0xbe72,0,0x3e100000,0,0x3d190000,0,0xbe460000,0,0xbe720000,
0x3e75,0,0x3e2d,0,0x8000,0,0xbe2d,0,0x3e750000,0,0x3e2d0000,0,0x80000000,0,0xbe2d0000,0,
0,0x3e75,0,0x3e2d,0,0x8000,0,0xbe2d,0,0x3e750000,0,0x3e2d0000,0,0x80000000,0,0xbe2d0000,
0,0,0xbe2d,0,0xbe75,0,0xbe2d,0,0,0,0xbe2d0000,0,0xbe750000,0,0xbe2d0000,0,
0,0,0,0xbe2d,0,0xbe75,0,0xbe2d,0,0,0,0xbe2d0000,0,0xbe750000,0,0xbe2d0000,
0x3e75,0,0x3dde,0,0x8000,0,0xbe5a,0,0x3e750000,0,0x3dde0000,0,0x80000000,0,0xbe5a0000,0,
0,0x3e75,0,0x3dde,0,0x8000,0,0xbe5a,0,0x3e750000,0,0x3dde0000,0,0x80000000,0,0xbe5a0000,
0xbe10,0,0xbe72,0,0xbe46,0,0x3d19,0,0xbe100000,0,0xbe720000,0,0xbe460000,0,0x3d190000,0,
0,0xbe10,0,0xbe72,0,0xbe46,0,0x3d19,0,0xbe100000,0,0xbe720000,0,0xbe460000,0,0x3d190000,
0x3e75,0,0x3d19,0,0x8000,0,0xbe72,0,0x3e750000,0,0x3d190000,0,0x80000000,0,0xbe720000,0,
0,0x3e75,0,0x3d19,0,0x8000,0,0xbe72,0,0x3e750000,0,0x3d190000,0,0x80000000,0,0xbe720000,
0xbe69,0,0xbdde,0,0xbd97,0,0x3e5a,0,0xbe690000,0,0xbdde0000,0,0xbd970000,0,0x3e5a0000,0,
0,0xbe69,0,0xbdde,0,0xbd97,0,0x3e5a,0,0xbe690000,0,0xbdde0000,0,0xbd970000,0,0x3e5a0000,
0x3e75,0,0xbd19,0,0x8000,0,0xbe72,0,0x3e750000,0,0xbd190000,0,0x80000000,0,0xbe720000,0,
0,0x3e75,0,0xbd19,0,0x8000,0,0xbe72,0,0x3e750000,0,0xbd190000,0,0x80000000,0,0xbe720000,
0xbe69,0,0x3dde,0,0x3d97,0,0x3e5a,0,0xbe690000,0,0x3dde0000,0,0x3d970000,0,0x3e5a0000,0,
0,0xbe69,0,0x3dde,0,0x3d97,0,0x3e5a,0,0xbe690000,0,0x3dde0000,0,0x3d970000,0,0x3e5a0000,
0x3e75,0,0xbdde,0,0x8000,0,0xbe5a,0,0x3e750000,0,0xbdde0000,0,0x80000000,0,0xbe5a0000,0,
0,0x3e75,0,0xbdde,0,0x8000,0,0xbe5a,0,0x3e750000,0,0xbdde0000,0,0x80000000,0,0xbe5a0000,
0xbe10,0,0x3e72,0,0x3e46,0,0x3d19,0,0xbe100000,0,0x3e720000,0,0x3e460000,0,0x3d190000,0,
0,0xbe10,0,0x3e72,0,0x3e46,0,0x3d19,0,0xbe100000,0,0x3e720000,0,0x3e460000,0,0x3d190000,
0x3e75,0,0xbe2d,0,0x8000,0,0xbe2d,0,0x3e750000,0,0xbe2d0000,0,0x80000000,0,0xbe2d0000,0,
0,0x3e75,0,0xbe2d,0,0x8000,0,0xbe2d,0,0x3e750000,0,0xbe2d0000,0,0x80000000,0,0xbe2d0000,
0,0,0x3e2d,0,0x3e75,0,0xbe2d,0,0,0,0x3e2d0000,0,0x3e750000,0,0xbe2d0000,0,
0,0,0,0x3e2d,0,0x3e75,0,0xbe2d,0,0,0,0x3e2d0000,0,0x3e750000,0,0xbe2d0000,
0x3e75,0,0xbe5a,0,0x8000,0,0xbdde,0,0x3e750000,0,0xbe5a0000,0,0x80000000,0,0xbdde0000,0,
0,0x3e75,0,0xbe5a,0,0x8000,0,0xbdde,0,0x3e750000,0,0xbe5a0000,0,0x80000000,0,0xbdde0000,
0x3e10,0,0xbd19,0,0x3e46,0,0xbe72,0,0x3e100000,0,0xbd190000,0,0x3e460000,0,0xbe720000,0,
0,0x3e10,0,0xbd19,0,0x3e46,0,0xbe72,0,0x3e100000,0,0xbd190000,0,0x3e460000,0,0xbe720000,
0x3e75,0,0xbe72,0,0x8000,0,0xbd19,0,0x3e750000,0,0xbe720000,0,0x80000000,0,0xbd190000,0,
0,0x3e75,0,0xbe72,0,0x8000,0,0xbd19,0,0x3e750000,0,0xbe720000,0,0x80000000,0,0xbd190000,
0x3e69,0,0xbe5a,0,0x3d97,0,0xbdde,0,0x3e690000,0,0xbe5a0000,0,0x3d970000,0,0xbdde0000,0,
0,0x3e69,0,0xbe5a,0,0x3d97,0,0xbdde,0,0x3e690000,0,0xbe5a0000,0,0x3d970000,0,0xbdde0000,
0x3e46,0,0x3e2d,0,0xbe10,0,0xbe2d,0,0x3e460000,0,0x3e2d0000,0,0xbe100000,0,0xbe2d0000,0,
0,0x3e46,0,0x3e2d,0,0xbe10,0,0xbe2d,0,0x3e460000,0,0x3e2d0000,0,0xbe100000,0,0xbe2d0000,
0x3e10,0,0x3dde,0,0xbe46,0,0xbe5a,0,0x3e100000,0,0x3dde0000,0,0xbe460000,0,0xbe5a0000,0,
0,0x3e10,0,0x3dde,0,0xbe46,0,0xbe5a,0,0x3e100000,0,0x3dde0000,0,0xbe460000,0,0xbe5a0000,
0xbd97,0,0xbe2d,0,0xbe69,0,0xbe2d,0,0xbd970000,0,0xbe2d0000,0,0xbe690000,0,0xbe2d0000,0,
0,0xbd97,0,0xbe2d,0,0xbe69,0,0xbe2d,0,0xbd970000,0,0xbe2d0000,0,0xbe690000,0,0xbe2d0000,
0xbe69,0,0xbe72,0,0xbd97,0,0x3d19,0,0xbe690000,0,0xbe720000,0,0xbd970000,0,0x3d190000,0,
0,0xbe69,0,0xbe72,0,0xbd97,0,0x3d19,0,0xbe690000,0,0xbe720000,0,0xbd970000,0,0x3d190000,
0xbe75,0,0xbe2d,0,0x8000,0,0x3e2d,0,0xbe750000,0,0xbe2d0000,0,0x80000000,0,0x3e2d0000,0,
0,0xbe75,0,0xbe2d,0,0x8000,0,0x3e2d,0,0xbe750000,0,0xbe2d0000,0,0x80000000,0,0x3e2d0000,
0,0,0x3e2d,0,0x3e75,0,0x3e2d,0,0,0,0x3e2d0000,0,0x3e750000,0,0x3e2d0000,0,
0,0,0,0x3e2d,0,0x3e75,0,0x3e2d,0,0,0,0x3e2d0000,0,0x3e750000,0,0x3e2d0000,
0xbd97,0,0x3e2d,0,0x3e69,0,0x3e2d,0,0xbd970000,0,0x3e2d0000,0,0x3e690000,0,0x3e2d0000,0,
0,0xbd97,0,0x3e2d,0,0x3e69,0,0x3e2d,0,0xbd970000,0,0x3e2d0000,0,0x3e690000,0,0x3e2d0000,
0x3e69,0,0x3d19,0,0xbd97,0,0xbe72,0,0x3e690000,0,0x3d190000,0,0xbd970000,0,0xbe720000,0,
0,0x3e69,0,0x3d19,0,0xbd97,0,0xbe72,0,0x3e690000,0,0x3d190000,0,0xbd970000,0,0xbe720000,
0x3e46,0,0x3e2d,0,0x3e10,0,0xbe2d,0,0x3e460000,0,0x3e2d0000,0,0x3e100000,0,0xbe2d0000,0,
0,0x3e46,0,0x3e2d,0,0x3e10,0,0xbe2d,0,0x3e460000,0,0x3e2d0000,0,0x3e100000,0,0xbe2d0000,
0xbe10,0,0xbe5a,0,0xbe46,0,0x3dde,0,0xbe100000,0,0xbe5a0000,0,0xbe460000,0,0x3dde0000,0,
0,0xbe10,0,0xbe5a,0,0xbe46,0,0x3dde,0,0xbe100000,0,0xbe5a0000,0,0xbe460000,0,0x3dde0000,
0x3e46,0,0xbe2d,0,0xbe10,0,0xbe2d,0,0x3e460000,0,0xbe2d0000,0,0xbe100000,0,0xbe2d0000,0,
0,0x3e46,0,0xbe2d,0,0xbe10,0,0xbe2d,0,0x3e460000,0,0xbe2d0000,0,0xbe100000,0,0xbe2d0000,
0xbe10,0,0x3e5a,0,0x3e46,0,0x3dde,0,0xbe100000,0,0x3e5a0000,0,0x3e460000,0,0x3dde0000,0,
0,0xbe10,0,0x3e5a,0,0x3e46,0,0x3dde,0,0xbe100000,0,0x3e5a0000,0,0x3e460000,0,0x3dde0000,
0xbd97,0,0xbe2d,0,0xbe69,0,0x3e2d,0,0xbd970000,0,0xbe2d0000,0,0xbe690000,0,0x3e2d0000,0,
0,0xbd97,0,0xbe2d,0,0xbe69,0,0x3e2d,0,0xbd970000,0,0xbe2d0000,0,0xbe690000,0,0x3e2d0000,
0x3e69,0,0xbd19,0,0x3d97,0,0xbe72,0,0x3e690000,0,0xbd190000,0,0x3d970000,0,0xbe720000,0,
0,0x3e69,0,0xbd19,0,0x3d97,0,0xbe72,0,0x3e690000,0,0xbd190000,0,0x3d970000,0,0xbe720000,
0xbe75,0,0x3e2d,0,0x8000,0,0x3e2d,0,0xbe750000,0,0x3e2d0000,0,0x80000000,0,0x3e2d0000,0,
0,0xbe75,0,0x3e2d,0,0x8000,0,0x3e2d,0,0xbe750000,0,0x3e2d0000,0,0x80000000,0,0x3e2d0000,
0,0,0xbe2d,0,0xbe75,0,0x3e2d,0,0,0,0xbe2d0000,0,0xbe750000,0,0x3e2d0000,0,
0,0,0,0xbe2d,0,0xbe75,0,0x3e2d,0,0,0,0xbe2d0000,0,0xbe750000,0,0x3e2d0000,
0xbd97,0,0x3e2d,0,0x3e69,0,0xbe2d,0,0xbd970000,0,0x3e2d0000,0,0x3e690000,0,0xbe2d0000,0,
0,0xbd97,0,0x3e2d,0,0x3e69,0,0xbe2d,0,0xbd970000,0,0x3e2d0000,0,0x3e690000,0,0xbe2d0000,
0xbe69,0,0x3e72,0,0x3d97,0,0x3d19,0,0xbe690000,0,0x3e720000,0,0x3d970000,0,0x3d190000,0,
0,0xbe69,0,0x3e72,0,0x3d97,0,0x3d19,0,0xbe690000,0,0x3e720000,0,0x3d970000,0,0x3d190000,
0x3e46,0,0xbe2d,0,0x3e10,0,0xbe2d,0,0x3e460000,0,0xbe2d0000,0,0x3e100000,0,0xbe2d0000,0,
0,0x3e46,0,0xbe2d,0,0x3e10,0,0xbe2d,0,0x3e460000,0,0xbe2d0000,0,0x3e100000,0,0xbe2d0000,
0x3e10,0,0xbdde,0,0x3e46,0,0xbe5a,0,0x3e100000,0,0xbdde0000,0,0x3e460000,0,0xbe5a0000,0,
0,0x3e10,0,0xbdde,0,0x3e46,0,0xbe5a,0,0x3e100000,0,0xbdde0000,0,0x3e460000,0,0xbe5a0000,
0x3d97,0,0x3d19,0,0xbe69,0,0xbe72,0,0x3d970000,0,0x3d190000,0,0xbe690000,0,0xbe720000,0,
0,0x3d97,0,0x3d19,0,0xbe69,0,0xbe72,0,0x3d970000,0,0x3d190000,0,0xbe690000,0,0xbe720000,
0,0,0xbd19,0,0xbe75,0,0xbe72,0,0,0,0xbd190000,0,0xbe750000,0,0xbe720000,0,
0,0,0,0xbd19,0,0xbe75,0,0xbe72,0,0,0,0xbd190000,0,0xbe750000,0,0xbe720000,
0xbe46,0,0xbdde,0,0x3e10,0,0x3e5a,0,0xbe460000,0,0xbdde0000,0,0x3e100000,0,0x3e5a0000,0,
0,0xbe46,0,0xbdde,0,0x3e10,0,0x3e5a,0,0xbe460000,0,0xbdde0000,0,0x3e100000,0,0x3e5a0000,
0,0,0x3dde,0,0x3e75,0,0x3e5a,0,0,0,0x3dde0000,0,0x3e750000,0,0x3e5a0000,0,
0,0,0,0x3dde,0,0x3e75,0,0x3e5a,0,0,0,0x3dde0000,0,0x3e750000,0,0x3e5a0000,
0x3e75,0,0x3e2d,0,0x8000,0,0xbe2d,0,0x3e750000,0,0x3e2d0000,0,0x80000000,0,0xbe2d0000,0,
0,0x3e75,0,0x3e2d,0,0x8000,0,0xbe2d,0,0x3e750000,0,0x3e2d0000,0,0x80000000,0,0xbe2d0000,
0,0,0xbe2d,0,0xbe75,0,0xbe2d,0,0,0,0xbe2d0000,0,0xbe750000,0,0xbe2d0000,0,
0,0,0,0xbe2d,0,0xbe75,0,0xbe2d,0,0,0,0xbe2d0000,0,0xbe750000,0,0xbe2d0000,
0xbe46,0,0xbe5a,0,0xbe10,0,0x3dde,0,0xbe460000,0,0xbe5a0000,0,0xbe100000,0,0x3dde0000,0,
0,0xbe46,0,0xbe5a,0,0xbe10,0,0x3dde,0,0xbe460000,0,0xbe5a0000,0,0xbe100000,0,0x3dde0000,
0,0,0x3e5a,0,0x3e75,0,0x3dde,0,0,0,0x3e5a0000,0,0x3e750000,0,0x3dde0000,0,
0,0,0,0x3e5a,0,0x3e75,0,0x3dde,0,0,0,0x3e5a0000,0,0x3e750000,0,0x3dde0000,
0x3d97,0,0x3e72,0,0x3e69,0,0xbd19,0,0x3d970000,0,0x3e720000,0,0x3e690000,0,0xbd190000,0,
0,0x3d97,0,0x3e72,0,0x3e69,0,0xbd19,0,0x3d970000,0,0x3e720000,0,0x3e690000,0,0xbd190000,
0,0,0xbe72,0,0xbe75,0,0xbd19,0,0,0,0xbe720000,0,0xbe750000,0,0xbd190000,0,
0,0,0,0xbe72,0,0xbe75,0,0xbd19,0,0,0,0xbe720000,0,0xbe750000,0,0xbd190000,
0x3d97,0,0xbe72,0,0xbe69,0,0xbd19,0,0x3d970000,0,0xbe720000,0,0xbe690000,0,0xbd190000,0,
0,0x3d97,0,0xbe72,0,0xbe69,0,0xbd19,0,0x3d970000,0,0xbe720000,0,0xbe690000,0,0xbd190000,
0,0,0x3e72,0,0x3e75,0,0xbd19,0,0,0,0x3e720000,0,0x3e750000,0,0xbd190000,0,
0,0,0,0x3e72,0,0x3e75,0,0xbd19,0,0,0,0x3e720000,0,0x3e750000,0,0xbd190000,
0xbe46,0,0x3e5a,0,0x3e10,0,0x3dde,0,0xbe460000,0,0x3e5a0000,0,0x3e100000,0,0x3dde0000,0,
0,0xbe46,0,0x3e5a,0,0x3e10,0,0x3dde,0,0xbe460000,0,0x3e5a0000,0,0x3e100000,0,0x3dde0000,
0,0,0xbe5a,0,0xbe75,0,0x3dde,0,0,0,0xbe5a0000,0,0xbe750000,0,0x3dde0000,0,
0,0,0,0xbe5a,0,0xbe75,0,0x3dde,0,0,0,0xbe5a0000,0,0xbe750000,0,0x3dde0000,
0x3e75,0,0xbe2d,0,0x8000,0,0xbe2d,0,0x3e750000,0,0xbe2d0000,0,0x80000000,0,0xbe2d0000,0,
0,0x3e75,0,0xbe2d,0,0x8000,0,0xbe2d,0,0x3e750000,0,0xbe2d0000,0,0x80000000,0,0xbe2d0000,
0,0,0x3e2d,0,0x3e75,0,0xbe2d,0,0,0,0x3e2d0000,0,0x3e750000,0,0xbe2d0000,0,
0,0,0,0x3e2d,0,0x3e75,0,0xbe2d,0,0,0,0x3e2d0000,0,0x3e750000,0,0xbe2d0000,
0xbe46,0,0x3dde,0,0xbe10,0,0x3e5a,0,0xbe460000,0,0x3dde0000,0,0xbe100000,0,0x3e5a0000,0,
0,0xbe46,0,0x3dde,0,0xbe10,0,0x3e5a,0,0xbe460000,0,0x3dde0000,0,0xbe100000,0,0x3e5a0000,
0,0,0xbdde,0,0xbe75,0,0x3e5a,0,0,0,0xbdde0000,0,0xbe750000,0,0x3e5a0000,0,
0,0,0,0xbdde,0,0xbe75,0,0x3e5a,0,0,0,0xbdde0000,0,0xbe750000,0,0x3e5a0000,
0x3d97,0,0xbd19,0,0x3e69,0,0xbe72,0,0x3d970000,0,0xbd190000,0,0x3e690000,0,0xbe720000,0,
0,0x3d97,0,0xbd19,0,0x3e69,0,0xbe72,0,0x3d970000,0,0xbd190000,0,0x3e690000,0,0xbe720000,
0,0,0x3d19,0,0x3e75,0,0xbe72,0,0,0,0x3d190000,0,0x3e750000,0,0xbe720000,0,
0,0,0,0x3d19,0,0x3e75,0,0xbe72,0,0,0,0x3d190000,0,0x3e750000,0,0xbe720000,
0xbd97,0,0xbdde,0,0xbe69,0,0xbe5a,0,0xbd970000,0,0xbdde0000,0,0xbe690000,0,0xbe5a0000,0,
0,0xbd97,0,0xbdde,0,0xbe69,0,0xbe5a,0,0xbd970000,0,0xbdde0000,0,0xbe690000,0,0xbe5a0000,
0xbe10,0,0xbe2d,0,0xbe46,0,0xbe2d,0,0xbe100000,0,0xbe2d0000,0,0xbe460000,0,0xbe2d0000,0,
0,0xbe10,0,0xbe2d,0,0xbe46,0,0xbe2d,0,0xbe100000,0,0xbe2d0000,0,0xbe460000,0,0xbe2d0000,
0x3e46,0,0x3e72,0,0x3e10,0,0x3d19,0,0x3e460000,0,0x3e720000,0,0x3e100000,0,0x3d190000,0,
0,0x3e46,0,0x3e72,0,0x3e10,0,0x3d19,0,0x3e460000,0,0x3e720000,0,0x3e100000,0,0x3d190000,
0x3e69,0,0x3e2d,0,0xbd97,0,0xbe2d,0,0x3e690000,0,0x3e2d0000,0,0xbd970000,0,0xbe2d0000,0,
0,0x3e69,0,0x3e2d,0,0xbd97,0,0xbe2d,0,0x3e690000,0,0x3e2d0000,0,0xbd970000,0,0xbe2d0000,
0xbe75,0,0xbe2d,0,0x8000,0,0x3e2d,0,0xbe750000,0,0xbe2d0000,0,0x80000000,0,0x3e2d0000,0,
0,0xbe75,0,0xbe2d,0,0x8000,0,0x3e2d,0,0xbe750000,0,0xbe2d0000,0,0x80000000,0,0x3e2d0000,
0,0,0x3e2d,0,0x3e75,0,0x3e2d,0,0,0,0x3e2d0000,0,0x3e750000,0,0x3e2d0000,0,
0,0,0,0x3e2d,0,0x3e75,0,0x3e2d,0,0,0,0x3e2d0000,0,0x3e750000,0,0x3e2d0000,
0x3e46,0,0xbd19,0,0xbe10,0,0xbe72,0,0x3e460000,0,0xbd190000,0,0xbe100000,0,0xbe720000,0,
0,0x3e46,0,0xbd19,0,0xbe10,0,0xbe72,0,0x3e460000,0,0xbd190000,0,0xbe100000,0,0xbe720000,
0xbe69,0,0xbe2d,0,0xbd97,0,0x3e2d,0,0xbe690000,0,0xbe2d0000,0,0xbd970000,0,0x3e2d0000,0,
0,0xbe69,0,0xbe2d,0,0xbd97,0,0x3e2d,0,0xbe690000,0,0xbe2d0000,0,0xbd970000,0,0x3e2d0000,
0xbd97,0,0x3e5a,0,0x3e69,0,0x3dde,0,0xbd970000,0,0x3e5a0000,0,0x3e690000,0,0x3dde0000,0,
0,0xbd97,0,0x3e5a,0,0x3e69,0,0x3dde,0,0xbd970000,0,0x3e5a0000,0,0x3e690000,0,0x3dde0000,
0x3e10,0,0xbe2d,0,0xbe46,0,0xbe2d,0,0x3e100000,0,0xbe2d0000,0,0xbe460000,0,0xbe2d0000,0,
0,0x3e10,0,0xbe2d,0,0xbe46,0,0xbe2d,0,0x3e100000,0,0xbe2d0000,0,0xbe460000,0,0xbe2d0000,
0xbd97,0,0xbe5a,0,0xbe69,0,0x3dde,0,0xbd970000,0,0xbe5a0000,0,0xbe690000,0,0x3dde0000,0,
0,0xbd97,0,0xbe5a,0,0xbe69,0,0x3dde,0,0xbd970000,0,0xbe5a0000,0,0xbe690000,0,0x3dde0000,
0x3e10,0,0x3e2d,0,0x3e46,0,0xbe2d,0,0x3e100000,0,0x3e2d0000,0,0x3e460000,0,0xbe2d0000,0,
0,0x3e10,0,0x3e2d,0,0x3e46,0,0xbe2d,0,0x3e100000,0,0x3e2d0000,0,0x3e460000,0,0xbe2d0000,
0x3e46,0,0x3d19,0,0x3e10,0,0xbe72,0,0x3e460000,0,0x3d190000,0,0x3e100000,0,0xbe720000,0,
0,0x3e46,0,0x3d19,0,0x3e10,0,0xbe72,0,0x3e460000,0,0x3d190000,0,0x3e100000,0,0xbe720000,
0xbe69,0,0x3e2d,0,0x3d97,0,0x3e2d,0,0xbe690000,0,0x3e2d0000,0,0x3d970000,0,0x3e2d0000,0,
0,0xbe69,0,0x3e2d,0,0x3d97,0,0x3e2d,0,0xbe690000,0,0x3e2d0000,0,0x3d970000,0,0x3e2d0000,
0xbe75,0,0x3e2d,0,0x8000,0,0x3e2d,0,0xbe750000,0,0x3e2d0000,0,0x80000000,0,0x3e2d0000,0,
0,0xbe75,0,0x3e2d,0,0x8000,0,0x3e2d,0,0xbe750000,0,0x3e2d0000,0,0x80000000,0,0x3e2d0000,
0,0,0xbe2d,0,0xbe75,0,0x3e2d,0,0,0,0xbe2d0000,0,0xbe750000,0,0x3e2d0000,0,
0,0,0,0xbe2d,0,0xbe75,0,0x3e2d,0,0,0,0xbe2d0000,0,0xbe750000,0,0x3e2d0000,
0x3e46,0,0xbe72,0,0xbe10,0,0x3d19,0,0x3e460000,0,0xbe720000,0,0xbe100000,0,0x3d190000,0,
0,0x3e46,0,0xbe72,0,0xbe10,0,0x3d19,0,0x3e460000,0,0xbe720000,0,0xbe100000,0,0x3d190000,
0x3e69,0,0xbe2d,0,0x3d97,0,0xbe2d,0,0x3e690000,0,0xbe2d0000,0,0x3d970000,0,0xbe2d0000,0,
0,0x3e69,0,0xbe2d,0,0x3d97,0,0xbe2d,0,0x3e690000,0,0xbe2d0000,0,0x3d970000,0,0xbe2d0000,
0xbd97,0,0x3dde,0,0x3e69,0,0xbe5a,0,0xbd970000,0,0x3dde0000,0,0x3e690000,0,0xbe5a0000,0,
0,0xbd97,0,0x3dde,0,0x3e69,0,0xbe5a,0,0xbd970000,0,0x3dde0000,0,0x3e690000,0,0xbe5a0000,
0xbe10,0,0x3e2d,0,0x3e46,0,0xbe2d,0,0xbe100000,0,0x3e2d0000,0,0x3e460000,0,0xbe2d0000,0,
0,0xbe10,0,0x3e2d,0,0x3e46,0,0xbe2d,0,0xbe100000,0,0x3e2d0000,0,0x3e460000,0,0xbe2d0000,
0xbe46,0,0xbe5a,0,0xbe10,0,0xbdde,0,0xbe460000,0,0xbe5a0000,0,0xbe100000,0,0xbdde0000,0,
0,0xbe46,0,0xbe5a,0,0xbe10,0,0xbdde,0,0xbe460000,0,0xbe5a0000,0,0xbe100000,0,0xbdde0000,
0xbe69,0,0xbe72,0,0xbd97,0,0xbd19,0,0xbe690000,0,0xbe720000,0,0xbd970000,0,0xbd190000,0,
0,0xbe69,0,0xbe72,0,0xbd97,0,0xbd19,0,0xbe690000,0,0xbe720000,0,0xbd970000,0,0xbd190000,
0x3d97,0,0xbd19,0,0xbe69,0,0xbe72,0,0x3d970000,0,0xbd190000,0,0xbe690000,0,0xbe720000,0,
0,0x3d97,0,0xbd19,0,0xbe69,0,0xbe72,0,0x3d970000,0,0xbd190000,0,0xbe690000,0,0xbe720000,
0xbe10,0,0xbe5a,0,0xbe46,0,0xbdde,0,0xbe100000,0,0xbe5a0000,0,0xbe460000,0,0xbdde0000,0,
0,0xbe10,0,0xbe5a,0,0xbe46,0,0xbdde,0,0xbe100000,0,0xbe5a0000,0,0xbe460000,0,0xbdde0000,
0x3e75,0,0x3e2d,0,0x8000,0,0xbe2d,0,0x3e750000,0,0x3e2d0000,0,0x80000000,0,0xbe2d0000,0,
0,0x3e75,0,0x3e2d,0,0x8000,0,0xbe2d,0,0x3e750000,0,0x3e2d0000,0,0x80000000,0,0xbe2d0000,
0,0,0xbe2d,0,0xbe75,0,0xbe2d,0,0,0,0xbe2d0000,0,0xbe750000,0,0xbe2d0000,0,
0,0,0,0xbe2d,0,0xbe75,0,0xbe2d,0,0,0,0xbe2d0000,0,0xbe750000,0,0xbe2d0000,
0x3d97,0,0x3e72,0,0x3e69,0,0x3d19,0,0x3d970000,0,0x3e720000,0,0x3e690000,0,0x3d190000,0,
0,0x3d97,0,0x3e72,0,0x3e69,0,0x3d19,0,0x3d970000,0,0x3e720000,0,0x3e690000,0,0x3d190000,
0x3e10,0,0xbdde,0,0xbe46,0,0xbe5a,0,0x3e100000,0,0xbdde0000,0,0xbe460000,0,0xbe5a0000,0,
0,0x3e10,0,0xbdde,0,0xbe46,0,0xbe5a,0,0x3e100000,0,0xbdde0000,0,0xbe460000,0,0xbe5a0000,
0xbe46,0,0x3dde,0,0x3e10,0,0x3e5a,0,0xbe460000,0,0x3dde0000,0,0x3e100000,0,0x3e5a0000,0,
0,0xbe46,0,0x3dde,0,0x3e10,0,0x3e5a,0,0xbe460000,0,0x3dde0000,0,0x3e100000,0,0x3e5a0000,
0x3e69,0,0xbd19,0,0xbd97,0,0xbe72,0,0x3e690000,0,0xbd190000,0,0xbd970000,0,0xbe720000,0,
0,0x3e69,0,0xbd19,0,0xbd97,0,0xbe72,0,0x3e690000,0,0xbd190000,0,0xbd970000,0,0xbe720000,
0xbe46,0,0xbdde,0,0xbe10,0,0x3e5a,0,0xbe460000,0,0xbdde0000,0,0xbe100000,0,0x3e5a0000,0,
0,0xbe46,0,0xbdde,0,0xbe10,0,0x3e5a,0,0xbe460000,0,0xbdde0000,0,0xbe100000,0,0x3e5a0000,
0x3e69,0,0x3d19,0,0x3d97,0,0xbe72,0,0x3e690000,0,0x3d190000,0,0x3d970000,0,0xbe720000,0,
0,0x3e69,0,0x3d19,0,0x3d97,0,0xbe72,0,0x3e690000,0,0x3d190000,0,0x3d970000,0,0xbe720000,
0x3d97,0,0xbe72,0,0xbe69,0,0x3d19,0,0x3d970000,0,0xbe720000,0,0xbe690000,0,0x3d190000,0,
0,0x3d97,0,0xbe72,0,0xbe69,0,0x3d19,0,0x3d970000,0,0xbe720000,0,0xbe690000,0,0x3d190000,
0x3e10,0,0x3dde,0,0x3e46,0,0xbe5a,0,0x3e100000,0,0x3dde0000,0,0x3e460000,0,0xbe5a0000,0,
0,0x3e10,0,0x3dde,0,0x3e46,0,0xbe5a,0,0x3e100000,0,0x3dde0000,0,0x3e460000,0,0xbe5a0000,
0x3e75,0,0xbe2d,0,0x8000,0,0xbe2d,0,0x3e750000,0,0xbe2d0000,0,0x80000000,0,0xbe2d0000,0,
0,0x3e75,0,0xbe2d,0,0x8000,0,0xbe2d,0,0x3e750000,0,0xbe2d0000,0,0x80000000,0,0xbe2d0000,
0,0,0x3e2d,0,0x3e75,0,0xbe2d,0,0,0,0x3e2d0000,0,0x3e750000,0,0xbe2d0000,0,
0,0,0,0x3e2d,0,0x3e75,0,0xbe2d,0,0,0,0x3e2d0000,0,0x3e750000,0,0xbe2d0000,
0x3d97,0,0x3d19,0,0x3e69,0,0xbe72,0,0x3d970000,0,0x3d190000,0,0x3e690000,0,0xbe720000,0,
0,0x3d97,0,0x3d19,0,0x3e69,0,0xbe72,0,0x3d970000,0,0x3d190000,0,0x3e690000,0,0xbe720000,
0xbe10,0,0x3e5a,0,0x3e46,0,0xbdde,0,0xbe100000,0,0x3e5a0000,0,0x3e460000,0,0xbdde0000,0,
0,0xbe10,0,0x3e5a,0,0x3e46,0,0xbdde,0,0xbe100000,0,0x3e5a0000,0,0x3e460000,0,0xbdde0000,
0xbe46,0,0x3e5a,0,0x3e10,0,0xbdde,0,0xbe460000,0,0x3e5a0000,0,0x3e100000,0,0xbdde0000,0,
0,0xbe46,0,0x3e5a,0,0x3e10,0,0xbdde,0,0xbe460000,0,0x3e5a0000,0,0x3e100000,0,0xbdde0000,
0xbe69,0,0x3e72,0,0x3d97,0,0xbd19,0,0xbe690000,0,0x3e720000,0,0x3d970000,0,0xbd190000,0,
0,0xbe69,0,0x3e72,0,0x3d97,0,0xbd19,0,0xbe690000,0,0x3e720000,0,0x3d970000,0,0xbd190000,
0x3eb7,0x3eb7,0x3eb7,0x3eb7,0x3eb78000,0x3eb78000,0x3eb78000,0x3eb78000,0x3eb7,0x3de23eae,0x3e573e94,0x3e943e57,0x3eb78000,0x3eaebde2,0x3e94be57,0x3e57be94,
0x3eb7,0x3e573e94,0x3eae3de2,0x3eaebde2,0x3eb78000,0x3e94be57,0x3de2beae,0xbde2beae,0x3eb7,0x3e943e57,0x3eaebde2,0x3de2beae,0x3eb78000,0x3e57be94,0xbde2beae,0xbeaebde2,
0x3eb7,0x3eb7,0x3eb7,0x3eb7,0x3eb78000,0x3eb78000,0x3eb78000,0x3eb78000,0x3eae3de2,0x3eb70000,0x3eaebde2,0x3e94be57,0x3de2beae,0xbeb7,0xbde2beae,0xbe57be94,
0x3e57be94,0xbeb7,0xbe57be94,0xbeaebde2,0xbe94be57,0xbeb78000,0xbe943e57,0xbde23eae,0xbe57be94,0xbeb70000,0xbe573e94,0x3de23eae,0xbe943e57,0x3eb7,0x3e943e57,0x3eaebde2,
0x3eb7,0x3eae3de2,0x3e57be94,0xbe57be94,0x3eb78000,0x3de2beae,0xbe94be57,0xbe943e57,0x3eb7,0x3eb70000,0xbeb7,0xbeb70000,0x3eb78000,0xbeb7,0xbeb78000,0x3eb7,
0x3eb7,0x3eaebde2,0xbe57be94,0xbe573e94,0x3eb78000,0xbde2beae,0xbe943e57,0x3e943e57,0x3eb7,0x3e94be57,0xbeaebde2,0x3de23eae,0x3eb78000,0xbe57be94,0xbde23eae,0x3eaebde2,
0xbeae3de2,0x3eb7,0x3eae3de2,0x3e57be94,0x3de23eae,0x3eb78000,0x3de2beae,0xbe94be57,0x3eb7,0x3eb70000,0xbeb7,0xbeb70000,0x3eb78000,0xbeb7,0xbeb78000,0x3eb7,
0x3eae3de2,0xbeb7,0xbeae3de2,0x3e573e94,0x3de2beae,0xbeb78000,0x3de23eae,0x3e94be57,0x3e57be94,0xbeb70000,0x3e573e94,0x3de2beae,0xbe94be57,0x3eb7,0x3e94be57,0xbeaebde2,
0x3eb7,0x3e57be94,0xbeae3de2,0x3eae3de2,0x3eb78000,0xbe94be57,0x3de23eae,0x3de2beae,0x3eb7,0x3de2beae,0xbe573e94,0x3e94be57,0x3eb78000,0xbeaebde2,0x3e943e57,0xbe57be94,
0x3eb7,0xbeb7,0x3eb7,0xbeb7,0x3eb78000,0xbeb78000,0x3eb78000,0xbeb78000,0x3eb7,0xbde2beae,0x3e573e94,0xbe94be57,0x3eb78000,0xbeae3de2,0x3e94be57,0xbe573e94,
0xbe57be94,0x3eb7,0x3e57be94,0xbeae3de2,0xbe943e57,0x3eb78000,0xbe94be57,0x3de23eae,0xbeae3de2,0x3eb70000,0xbeaebde2,0x3e943e57,0x3de23eae,0xbeb7,0xbde23eae,0x3e57be94,
0x3eb7,0xbeb7,0x3eb7,0xbeb7,0x3eb78000,0xbeb78000,0x3eb78000,0xbeb78000,0x3eae3de2,0xbeb70000,0x3eaebde2,0xbe943e57,0x3de2beae,0x3eb7,0xbde2beae,0x3e573e94,
0x3eb7,0xbe57be94,0x3eae3de2,0xbeae3de2,0x3eb78000,0xbe943e57,0x3de2beae,0x3de23eae,0x3eb7,0xbe94be57,0x3eaebde2,0xbde23eae,0x3eb78000,0xbe573e94,0xbde2beae,0x3eae3de2,
0x3eb7,0xbeaebde2,0x3e57be94,0x3e573e94,0x3eb78000,0xbde23eae,0xbe94be57,0x3e94be57,0x3eb7,0xbeb70000,0xbeb7,0x3eb70000,0x3eb78000,0x3eb7,0xbeb78000,0xbeb7,
0x3e57be94,0x3eb7,0xbe57be94,0x3eae3de2,0xbe94be57,0x3eb78000,0xbe943e57,0x3de2beae,0xbe57be94,0x3eb70000,0xbe573e94,0xbde2beae,0xbe943e57,0xbeb7,0x3e943e57,0xbeae3de2,
0xbeae3de2,0xbeb7,0x3eae3de2,0xbe573e94,0x3de23eae,0xbeb78000,0x3de2beae,0x3e943e57,0x3eb7,0xbeb70000,0xbeb7,0x3eb70000,0x3eb78000,0x3eb7,0xbeb78000,0xbeb7,
0x3eb7,0xbeae3de2,0xbe57be94,0x3e57be94,0x3eb78000,0x3de23eae,0xbe943e57,0xbe94be57,0x3eb7,0xbe943e57,0xbeaebde2,0xbde2beae,0x3eb78000,0x3e573e94,0xbde23eae,0xbeae3de2,
0x3eb7,0xbe573e94,0xbeae3de2,0xbeaebde2,0x3eb78000,0x3e943e57,0x3de23eae,0xbde23eae,0x3eb7,0xbde23eae,0xbe573e94,0xbe943e57,0x3eb78000,0x3eae3de2,0x3e943e57,0x3e573e94,
0x3eae3de2,0x3eb7,0xbeae3de2,0xbe57be94,0x3de2beae,0x3eb78000,0x3de23eae,0xbe943e57,0x3e57be94,0x3eb70000,0x3e573e94,0xbde23eae,0xbe94be57,0xbeb7,0x3e94be57,0x3eae3de2,
0xbe57be94,0xbeb7,0x3e57be94,0x3eaebde2,0xbe943e57,0xbeb78000,0xbe94be57,0xbde2beae,0xbeae3de2,0xbeb70000,0xbeaebde2,0xbe94be57,0x3de23eae,0x3eb7,0xbde23eae,0xbe573e94,
0x3eb7,0x3eb7,0x3eb7,0x3eb7,0x3eb78000,0x3eb78000,0x3eb78000,0x3eb78000,0x3e57be94,0x3de2beae,0xbeb7,0xbde2beae,0xbe94be57,0xbeaebde2,0xbeb78000,0xbeae3de2,
0xbeae3de2,0xbe573e94,0x3eb7,0x3e573e94,0x3de23eae,0x3e943e57,0x3eb78000,0x3e94be57,0x3eae3de2,0x3e94be57,0xbeb7,0xbe94be57,0x3de2beae,0xbe57be94,0xbeb78000,0xbe573e94,
0x3eb7,0x3eb7,0x3eb7,0x3eb7,0x3eb78000,0x3eb78000,0x3eb78000,0x3eb78000,0xbe57be94,0xbe94be57,0xbeaebde2,0xbeb70000,0xbe943e57,0xbe573e94,0xbde23eae,0x3eb7,
0x3eae3de2,0x3eaebde2,0x3e57be94,0xbeb7,0x3de2beae,0xbde2beae,0xbe94be57,0xbeb78000,0xbeae3de2,0xbde23eae,0x3e573e94,0x3eb70000,0x3de23eae,0x3eae3de2,0x3e94be57,0xbeb7,
0xbe57be94,0xbeae3de2,0x3eb7,0x3eae3de2,0xbe943e57,0x3de23eae,0x3eb78000,0x3de2beae,0x3eb7,0x3eb70000,0xbeb7,0xbeb70000,0x3eb78000,0xbeb7,0xbeb78000,0x3eb7,
0x3e57be94,0xbeaebde2,0x3eb7,0x3eaebde2,0xbe94be57,0xbde23eae,0x3eb78000,0xbde2beae,0xbeae3de2,0x3e943e57,0xbeb7,0xbe943e57,0x3de23eae,0x3e57be94,0xbeb78000,0x3e573e94,
0x3e57be94,0xbe57be94,0xbeae3de2,0x3eb7,0xbe94be57,0xbe943e57,0x3de23eae,0x3eb78000,0x3eb7,0x3eb70000,0xbeb7,0xbeb70000,0x3eb78000,0xbeb7,0xbeb78000,0x3eb7,
0xbe57be94,0xbe573e94,0x3eae3de2,0xbeb7,0xbe943e57,0x3e943e57,0x3de2beae,0xbeb78000,0x3eae3de2,0xbde2beae,0xbe573e94,0x3eb70000,0x3de2beae,0xbeae3de2,0x3e943e57,0xbeb7,
0x3eae3de2,0xbe57be94,0x3eb7,0x3e57be94,0x3de2beae,0xbe943e57,0x3eb78000,0xbe94be57,0xbe57be94,0x3de23eae,0xbeb7,0xbde23eae,0xbe943e57,0x3eaebde2,0xbeb78000,0x3eae3de2,
0x3eb7,0xbeb7,0x3eb7,0xbeb7,0x3eb78000,0xbeb78000,0x3eb78000,0xbeb78000,0x3e57be94,0xbde23eae,0xbeb7,0x3de23eae,0xbe94be57,0x3eae3de2,0xbeb78000,0x3eaebde2,
0xbeae3de2,0x3eae3de2,0xbe57be94,0x3eb7,0x3de23eae,0x3de2beae,0xbe943e57,0x3eb78000,0x3e57be94,0xbe943e57,0x3eaebde2,0xbeb70000,0xbe94be57,0x3e573e94,0xbde2beae,0x3eb7,
0x3eb7,0xbeb7,0x3eb7,0xbeb7,0x3eb78000,0xbeb78000,0x3eb78000,0xbeb78000,0xbe57be94,0x3e943e57,0xbeaebde2,0x3eb70000,0xbe943e57,0x3e57be94,0xbde23eae,0xbeb7,
0xbeae3de2,0x3e57be94,0x3eb7,0xbe57be94,0x3de23eae,0xbe94be57,0x3eb78000,0xbe943e57,0x3eae3de2,0xbe943e57,0xbeb7,0x3e943e57,0x3de2beae,0x3e573e94,0xbeb78000,0x3e57be94,
0xbe57be94,0x3eaebde2,0x3eb7,0xbeaebde2,0xbe943e57,0xbde2beae,0x3eb78000,0xbde23eae,0x3eb7,0xbeb70000,0xbeb7,0x3eb70000,0x3eb78000,0x3eb7,0xbeb78000,0xbeb7,
0x3eae3de2,0xbeae3de2,0x3e57be94,0x3eb7,0x3de2beae,0x3de23eae,0xbe94be57,0x3eb78000,0xbeae3de2,0x3de2beae,0x3e573e94,0xbeb70000,0x3de23eae,0xbeaebde2,0x3e94be57,0x3eb7,
0x3e57be94,0x3e573e94,0xbeae3de2,0xbeb7,0xbe94be57,0x3e94be57,0x3de23eae,0xbeb78000,0x3eb7,0xbeb70000,0xbeb7,0x3eb70000,0x3eb78000,0x3eb7,0xbeb78000,0xbeb7,
0x3e57be94,0x3eae3de2,0x3eb7,0xbeae3de2,0xbe94be57,0x3de2beae,0x3eb78000,0x3de23eae,0xbeae3de2,0xbe94be57,0xbeb7,0x3e94be57,0x3de23eae,0xbe573e94,0xbeb78000,0xbe57be94,
0x3eae3de2,0x3e573e94,0x3eb7,0xbe573e94,0x3de2beae,0x3e94be57,0x3eb78000,0x3e943e57,0xbe57be94,0xbde2beae,0xbeb7,0x3de2beae,0xbe943e57,0xbeae3de2,0xbeb78000,0xbeaebde2,
0xbe57be94,0x3e57be94,0x3eae3de2,0x3eb7,0xbe943e57,0xbe94be57,0x3de2beae,0x3eb78000,0x3eae3de2,0x3de23eae,0xbe573e94,0xbeb70000,0x3de2beae,0x3eaebde2,0x3e943e57,0x3eb7,
0xbeae3de2,0xbeaebde2,0xbe57be94,0xbeb7,0x3de23eae,0xbde23eae,0xbe943e57,0xbeb78000,0x3e57be94,0x3e94be57,0x3eaebde2,0x3eb70000,0xbe94be57,0xbe57be94,0xbde2beae,0xbeb7,
0x3eb7,0x3eb7,0x3eb7,0x3eb7,0x3eb78000,0x3eb78000,0x3eb78000,0x3eb78000,0xbeae3de2,0xbe943e57,0xbe573e94,0xbde23eae,0x3de23eae,0x3e573e94,0x3e943e57,0x3eae3de2,
0xbe57be94,0xbeaebde2,0xbeae3de2,0xbe573e94,0xbe943e57,0xbde23eae,0x3de23eae,0x3e943e57,0x3e57be94,0xbde2beae,0xbeaebde2,0xbe943e57,0xbe94be57,0xbeae3de2,0xbde23eae,0x3e573e94,
0,0,0,0,0,0,0,0,0,0,0,0,0,0,0,0,
0,0,0,0,0,0,0,0,0,0,0,0,0,0,0,0,
0x3eae3de2,0x3e57be94,0xbe57be94,0xbeae3de2,0x3de2beae,0xbe94be57,0xbe943e57,0x3de23eae,0x3eb7,0x3eb70000,0xbeb7,0xbeb70000,0x3eb78000,0xbeb7,0xbeb78000,0x3eb7,
0xbeae3de2,0x3e573e94,0x3e57be94,0xbeaebde2,0x3de23eae,0x3e94be57,0xbe94be57,0xbde23eae,0xbe57be94,0xbde23eae,0x3eaebde2,0xbe94be57,0xbe943e57,0x3eae3de2,0xbde2beae,0xbe573e94,
0,0,0,0,0,0,0,0,0,0,0,0,0,0,0,0,
0,0,0,0,0,0,0,0,0,0,0,0,0,0,0,0,
0x3e57be94,0xbeae3de2,0x3eae3de2,0xbe57be94,0xbe94be57,0x3de23eae,0x3de2beae,0xbe943e57,0x3eae3de2,0xbe94be57,0x3e573e94,0xbde2beae,0x3de2beae,0xbe573e94,0x3e94be57,0xbeae3de2,
0x3eb7,0xbeb7,0x3eb7,0xbeb7,0x3eb78000,0xbeb78000,0x3eb78000,0xbeb78000,0xbeae3de2,0x3e94be57,0xbe573e94,0x3de2beae,0x3de23eae,0xbe57be94,0x3e943e57,0xbeaebde2,
0,0,0,0,0,0,0,0,0,0,0,0,0,0,0,0,
0,0,0,0,0,0,0,0,0,0,0,0,0,0,0,0,
0xbe57be94,0x3eae3de2,0xbeae3de2,0x3e57be94,0xbe943e57,0x3de2beae,0x3de23eae,0xbe94be57,0x3e57be94,0x3de23eae,0xbeaebde2,0x3e94be57,0xbe94be57,0x3eaebde2,0xbde23eae,0xbe57be94,
0x3eae3de2,0xbe573e94,0xbe57be94,0x3eaebde2,0x3de2beae,0x3e943e57,0xbe943e57,0xbde2beae,0x3eb7,0xbeb70000,0xbeb7,0x3eb70000,0x3eb78000,0x3eb7,0xbeb78000,0xbeb7,
0,0,0,0,0,0,0,0,0,0,0,0,0,0,0,0,
0,0,0,0,0,0,0,0,0,0,0,0,0,0,0,0,
0xbeae3de2,0xbe57be94,0x3e57be94,0x3eae3de2,0x3de23eae,0xbe943e57,0xbe94be57,0x3de2beae,0xbe57be94,0x3de2beae,0x3eaebde2,0x3e943e57,0xbe943e57,0xbeaebde2,0xbde2beae,0x3e57be94,
0x3e57be94,0x3eaebde2,0x3eae3de2,0x3e573e94,0xbe94be57,0xbde2beae,0x3de2beae,0x3e94be57,0x3eae3de2,0x3e943e57,0x3e573e94,0x3de23eae,0x3de2beae,0x3e57be94,0x3e94be57,0x3eaebde2,
0,0,0,0,0,0,0,0,0,0,0,0,0,0,0,0,
0,0,0,0,0,0,0,0,0,0,0,0,0,0,0,0,
0,0,0,0,0,0,0,0,0,0,0,0,0,0,0,0,
0,0,0,0,0,0,0,0,0,0,0,0,0,0,0,0,
0x3eb7,0x3eb7,0x3eb7,0x3eb7,0x3eb78000,0x3eb78000,0x3eb78000,0x3eb78000,0xbeae3de2,0xbe943e57,0xbe573e94,0xbde23eae,0x3de23eae,0x3e573e94,0x3e943e57,0x3eae3de2,
0xbe57be94,0xbeaebde2,0xbeae3de2,0xbe573e94,0xbe943e57,0xbde23eae,0x3de23eae,0x3e943e57,0x3e57be94,0xbde2beae,0xbeaebde2,0xbe943e57,0xbe94be57,0xbeae3de2,0xbde23eae,0x3e573e94,
0,0,0,0,0,0,0,0,0,0,0,0,0,0,0,0,
0,0,0,0,0,0,0,0,0,0,0,0,0,0,0,0,
0x3eae3de2,0x3e57be94,0xbe57be94,0xbeae3de2,0x3de2beae,0xbe94be57,0xbe943e57,0x3de23eae,0x3eb7,0x3eb70000,0xbeb7,0xbeb70000,0x3eb78000,0xbeb7,0xbeb78000,0x3eb7,
0xbeae3de2,0x3e573e94,0x3e57be94,0xbeaebde2,0x3de23eae,0x3e94be57,0xbe94be57,0xbde23eae,0xbe57be94,0xbde23eae,0x3eaebde2,0xbe94be57,0xbe943e57,0x3eae3de2,0xbde2beae,0xbe573e94,
0,0,0,0,0,0,0,0,0,0,0,0,0,0,0,0,
0,0,0,0,0,0,0,0,0,0,0,0,0,0,0,0,
0x3e57be94,0xbeae3de2,0x3eae3de2,0xbe57be94,0xbe94be57,0x3de23eae,0x3de2beae,0xbe943e57,0x3eae3de2,0xbe94be57,0x3e573e94,0xbde2beae,0x3de2beae,0xbe573e94,0x3e94be57,0xbeae3de2,
0x3eb7,0xbeb7,0x3eb7,0xbeb7,0x3eb78000,0xbeb78000,0x3eb78000,0xbeb78000,0xbeae3de2,0x3e94be57,0xbe573e94,0x3de2beae,0x3de23eae,0xbe57be94,0x3e943e57,0xbeaebde2,
0,0,0,0,0,0,0,0,0,0,0,0,0,0,0,0,
0,0,0,0,0,0,0,0,0,0,0,0,0,0,0,0,
0xbe57be94,0x3eae3de2,0xbeae3de2,0x3e57be94,0xbe943e57,0x3de2beae,0x3de23eae,0xbe94be57,0x3e57be94,0x3de23eae,0xbeaebde2,0x3e94be57,0xbe94be57,0x3eaebde2,0xbde23eae,0xbe57be94,
0x3eae3de2,0xbe573e94,0xbe57be94,0x3eaebde2,0x3de2beae,0x3e943e57,0xbe943e57,0xbde2beae,0x3eb7,0xbeb70000,0xbeb7,0x3eb70000,0x3eb78000,0x3eb7,0xbeb78000,0xbeb7,
0,0,0,0,0,0,0,0,0,0,0,0,0,0,0,0,
0,0,0,0,0,0,0,0,0,0,0,0,0,0,0,0,
0xbeae3de2,0xbe57be94,0x3e57be94,0x3eae3de2,0x3de23eae,0xbe943e57,0xbe94be57,0x3de2beae,0xbe57be94,0x3de2beae,0x3eaebde2,0x3e943e57,0xbe943e57,0xbeaebde2,0xbde2beae,0x3e57be94,
0x3e57be94,0x3eaebde2,0x3eae3de2,0x3e573e94,0xbe94be57,0xbde2beae,0x3de2beae,0x3e94be57,0x3eae3de2,0x3e943e57,0x3e573e94,0x3de23eae,0x3de2beae,0x3e57be94,0x3e94be57,0x3eaebde2,
};
__device__ __align__(128) const uint32_t TAB_P3[4288] = {
0,0,0,0,0,0,0,0,0,0,0,0,0,0,0,0,
0x80003e83,0xbe79bda2,0x3e1abe54,0x3e1a3e54,0x3e830000,0xbda23e79,0xbe54be1a,0x3e54be1a,0x80003e83,0xbe54be1a,0x3e79bda2,0xbda23e79,0x3e830000,0xbe1a3e54,0xbda2be79,0x3e793da2,
0,0,0,0,0,0,0,0,0,0,0,0,0,0,0,0,
0xbe793da2,0x8000be83,0x3e793da2,0xbe1a3e54,0x3da23e79,0xbe830000,0x3da2be79,0x3e543e1a,0xbe1abe54,0x3e830000,0xbe1a3e54,0xbda2be79,0xbe543e1a,0xbe83,0x3e543e1a,0xbe793da2,
0x80003e83,0xbe1abe54,0x3e793da2,0xbe793da2,0x3e830000,0xbe543e1a,0x3da2be79,0x3da23e79,0x80003e83,0xbda2be79,0x3e1a3e54,0xbe54be1a,0x3e830000,0xbe793da2,0x3e54be1a,0xbe1a3e54,
0x80003e83,0x8000be83,0x80003e83,0x8000be83,0x3e830000,0xbe830000,0x3e830000,0xbe830000,0x80003e83,0x3da2be79,0xbe1a3e54,0x3e54be1a,0x3e830000,0xbe79bda2,0x3e543e1a,0xbe1abe54,
0x3e1abe54,0x80003e83,0xbe1abe54,0x3e793da2,0xbe54be1a,0x3e830000,0xbe543e1a,0x3da2be79,0x3e793da2,0xbe830000,0x3e79bda2,0xbe543e1a,0x3da2be79,0x3e83,0xbda2be79,0x3e1a3e54,
0x80003e83,0x8000be83,0x80003e83,0x8000be83,0x3e830000,0xbe830000,0x3e830000,0xbe830000,0xbe793da2,0x3e830000,0xbe79bda2,0x3e543e1a,0x3da23e79,0xbe83,0xbda23e79,0x3e1abe54,
0x80003e83,0x3e1abe54,0xbe793da2,0x3e793da2,0x3e830000,0xbe54be1a,0x3da23e79,0x3da2be79,0x80003e83,0x3e54be1a,0xbe79bda2,0x3da23e79,0x3e830000,0xbe1abe54,0xbda23e79,0x3e79bda2,
0x80003e83,0x3e79bda2,0xbe1abe54,0xbe1a3e54,0x3e830000,0xbda2be79,0xbe543e1a,0x3e543e1a,0x80003e83,0x3e830000,0x8000be83,0xbe830000,0x3e830000,0xbe83,0xbe830000,0x3e83,
0xbe1abe54,0x80003e83,0x3e1abe54,0xbe793da2,0xbe543e1a,0x3e830000,0xbe54be1a,0x3da23e79,0x3e1abe54,0xbe830000,0x3e1a3e54,0x3da2be79,0xbe54be1a,0x3e83,0x3e54be1a,0xbe79bda2,
0x3e793da2,0x8000be83,0xbe793da2,0x3e1a3e54,0x3da2be79,0xbe830000,0x3da23e79,0x3e54be1a,0x80003e83,0x3e830000,0x8000be83,0xbe830000,0x3e830000,0xbe83,0xbe830000,0x3e83,
0x80003e83,0x3e793da2,0x3e1abe54,0xbe1abe54,0x3e830000,0x3da2be79,0xbe54be1a,0xbe543e1a,0x80003e83,0x3e543e1a,0x3e79bda2,0x3da2be79,0x3e830000,0x3e1abe54,0xbda2be79,0xbe79bda2,
0x80003e83,0x3e1a3e54,0x3e793da2,0x3e79bda2,0x3e830000,0x3e54be1a,0x3da2be79,0xbda2be79,0x80003e83,0x3da23e79,0x3e1a3e54,0x3e543e1a,0x3e830000,0x3e79bda2,0x3e54be1a,0x3e1abe54,
0xbe793da2,0x80003e83,0x3e793da2,0x3e1abe54,0x3da23e79,0x3e830000,0x3da2be79,0xbe54be1a,0xbe1abe54,0xbe830000,0xbe1a3e54,0x3da23e79,0xbe543e1a,0x3e83,0x3e543e1a,0x3e79bda2,
0x3e1abe54,0x8000be83,0xbe1abe54,0xbe79bda2,0xbe54be1a,0xbe830000,0xbe543e1a,0xbda23e79,0x3e793da2,0x3e830000,0x3e79bda2,0x3e54be1a,0x3da2be79,0xbe83,0xbda2be79,0xbe1abe54,
0,0,0,0,0,0,0,0,0,0,0,0,0,0,0,0,
0,0,0,0,0,0,0,0,0,0,0,0,0,0,0,0,
0,0,0,0,0,0,0,0,0,0,0,0,0,0,0,0,
0xbe1abe54,0x3e79bda2,0x80003e83,0xbe79bda2,0xbe543e1a,0xbda2be79,0x3e830000,0xbda23e79,0x3e793da2,0xbe543e1a,0x8000be83,0x3e543e1a,0x3da2be79,0x3e1a3e54,0xbe830000,0x3e1abe54,
0,0,0,0,0,0,0,0,0,0,0,0,0,0,0,0,
0,0,0,0,0,0,0,0,0,0,0,0,0,0,0,0,
0xbe793da2,0x3e1abe54,0x80003e83,0xbe1abe54,0x3da23e79,0xbe54be1a,0x3e830000,0xbe543e1a,0x3e1abe54,0xbda23e79,0x8000be83,0x3da23e79,0xbe54be1a,0x3e793da2,0xbe830000,0x3e79bda2,
0x80003e83,0x8000be83,0x80003e83,0x8000be83,0x3e830000,0xbe830000,0x3e830000,0xbe830000,0xbe1abe54,0x3da23e79,0x8000be83,0xbda23e79,0xbe543e1a,0x3e79bda2,0xbe830000,0x3e793da2,
0,0,0,0,0,0,0,0,0,0,0,0,0,0,0,0,
0,0,0,0,0,0,0,0,0,0,0,0,0,0,0,0,
0x3e793da2,0xbe1abe54,0x80003e83,0x3e1abe54,0x3da2be79,0xbe543e1a,0x3e830000,0xbe54be1a,0xbe793da2,0x3e543e1a,0x8000be83,0xbe543e1a,0x3da23e79,0x3e1abe54,0xbe830000,0x3e1a3e54,
0x3e1abe54,0xbe79bda2,0x80003e83,0x3e79bda2,0xbe54be1a,0xbda23e79,0x3e830000,0xbda2be79,0x80003e83,0x3e830000,0x8000be83,0xbe830000,0x3e830000,0xbe83,0xbe830000,0x3e83,
0,0,0,0,0,0,0,0,0,0,0,0,0,0,0,0,
0,0,0,0,0,0,0,0,0,0,0,0,0,0,0,0,
0xbe1abe54,0xbe793da2,0x80003e83,0x3e793da2,0xbe543e1a,0x3da23e79,0x3e830000,0x3da2be79,0x3e793da2,0x3e54be1a,0x8000be83,0xbe54be1a,0x3da2be79,0xbe1abe54,0xbe830000,0xbe1a3e54,
0xbe793da2,0xbe1a3e54,0x80003e83,0x3e1a3e54,0x3da23e79,0x3e543e1a,0x3e830000,0x3e54be1a,0x3e1abe54,0x3da2be79,0x8000be83,0xbda2be79,0xbe54be1a,0xbe79bda2,0xbe830000,0xbe793da2,
0,0,0,0,0,0,0,0,0,0,0,0,0,0,0,0,
0x3e1abe54,0x3e1a3e54,0xbe793da2,0x8000be83,0xbe54be1a,0x3e54be1a,0x3da23e79,0xbe830000,0xbe793da2,0x3da2be79,0x3e1a3e54,0xbe830000,0x3da23e79,0xbe79bda2,0x3e54be1a,0x3e83,
0,0,0,0,0,0,0,0,0,0,0,0,0,0,0,0,
0x3e793da2,0xbe1a3e54,0xbe1abe54,0x3e79bda2,0x3da2be79,0x3e543e1a,0xbe543e1a,0xbda2be79,0x3e1abe54,0x3da23e79,0xbe79bda2,0x3e54be1a,0xbe54be1a,0x3e79bda2,0xbda23e79,0xbe1abe54,
0x3e793da2,0xbe793da2,0x3e1abe54,0x80003e83,0x3da2be79,0x3da23e79,0xbe54be1a,0x3e830000,0xbe1abe54,0x3e543e1a,0xbe79bda2,0x3e830000,0xbe543e1a,0x3e1abe54,0xbda23e79,0xbe83,
0x80003e83,0x8000be83,0x80003e83,0x8000be83,0x3e830000,0xbe830000,0x3e830000,0xbe830000,0x3e1abe54,0xbe543e1a,0x3e79bda2,0xbe830000,0xbe54be1a,0x3e1a3e54,0xbda2be79,0x3e83,
0xbe1abe54,0x3e793da2,0xbe793da2,0x3e1abe54,0xbe543e1a,0x3da2be79,0x3da23e79,0xbe54be1a,0xbe793da2,0x3e54be1a,0xbe1a3e54,0x3da2be79,0x3da23e79,0xbe1abe54,0x3e543e1a,0xbe79bda2,
0x80003e83,0x8000be83,0x80003e83,0x8000be83,0x3e830000,0xbe830000,0x3e830000,0xbe830000,0x3e793da2,0xbe54be1a,0x3e1a3e54,0xbda2be79,0x3da2be79,0xbe1a3e54,0x3e54be1a,0xbe793da2,
0xbe793da2,0x3e793da2,0xbe1abe54,0x80003e83,0x3da23e79,0x3da2be79,0xbe543e1a,0x3e830000,0x3e793da2,0xbda2be79,0xbe1a3e54,0x3e830000,0x3da2be79,0xbe793da2,0x3e543e1a,0xbe83,
0xbe1abe54,0xbe1a3e54,0x3e793da2,0x8000be83,0xbe543e1a,0x3e543e1a,0x3da2be79,0xbe830000,0x80003e83,0x3e830000,0x8000be83,0xbe830000,0x3e830000,0xbe83,0xbe830000,0x3e83,
0x3e1abe54,0xbe793da2,0x3e793da2,0xbe1abe54,0xbe54be1a,0x3da23e79,0x3da2be79,0xbe543e1a,0xbe1abe54,0xbda23e79,0x3e79bda2,0xbe54be1a,0xbe543e1a,0x3e793da2,0xbda2be79,0xbe1a3e54,
0xbe793da2,0x3e1a3e54,0x3e1abe54,0xbe79bda2,0x3da23e79,0x3e54be1a,0xbe54be1a,0xbda23e79,0x80003e83,0x3e830000,0x8000be83,0xbe830000,0x3e830000,0xbe83,0xbe830000,0x3e83,
0x3e1abe54,0xbe1abe54,0xbe793da2,0x80003e83,0xbe54be1a,0xbe543e1a,0x3da23e79,0x3e830000,0xbe793da2,0xbda23e79,0x3e1a3e54,0x3e830000,0x3da23e79,0x3e793da2,0x3e54be1a,0xbe83,
0x3e793da2,0x3e79bda2,0x3e1abe54,0x8000be83,0x3da2be79,0xbda2be79,0xbe54be1a,0xbe830000,0xbe1abe54,0xbe54be1a,0xbe79bda2,0xbe830000,0xbe543e1a,0xbe1a3e54,0xbda23e79,0x3e83,
0x3e793da2,0x3e1abe54,0xbe1abe54,0xbe793da2,0x3da2be79,0xbe54be1a,0xbe543e1a,0x3da23e79,0x3e1abe54,0xbda2be79,0xbe79bda2,0xbe543e1a,0xbe54be1a,0xbe793da2,0xbda23e79,0x3e1a3e54,
0xbe1abe54,0xbe79bda2,0xbe793da2,0xbe1a3e54,0xbe543e1a,0xbda23e79,0x3da23e79,0x3e543e1a,0xbe793da2,0xbe543e1a,0xbe1a3e54,0xbda23e79,0x3da23e79,0x3e1a3e54,0x3e543e1a,0x3e793da2,
0xbe163dda,0,0,0,0,0xbe163dda,0,0,0,0,0xbe163dda,0,0,0,0,0xbe163dda,
0xbe253da8,0,0,0,0,0xbe253da8,0,0,0,0,0xbe253da8,0,0,0,0,0xbe253da8,
0xbd65be30,0,0,0,0,0xbd65be30,0,0,0,0,0xbd65be30,0,0,0,0,0xbd65be30,
0x3ce8be37,0,0,0,0,0x3ce8be37,0,0,0,0,0x3ce8be37,0,0,0,0,0x3ce8be37,
0xbe303d65,0,0,0,0,0xbe303d65,0,0,0,0,0xbe303d65,0,0,0,0,0xbe303d65,
0xbe373ce8,0,0,0,0,0xbe373ce8,0,0,0,0,0xbe373ce8,0,0,0,0,0xbe373ce8,
0x3ddabe16,0,0,0,0,0x3ddabe16,0,0,0,0,0x3ddabe16,0,0,0,0,0x3ddabe16,
0x3e25bda8,0,0,0,0,0x3e25bda8,0,0,0,0,0x3e25bda8,0,0,0,0,0x3e25bda8,
0xbe390000,0,0,0,0,0xbe390000,0,0,0,0,0xbe390000,0,0,0,0,0xbe390000,
0xbe37bce8,0,0,0,0,0xbe37bce8,0,0,0,0,0xbe37bce8,0,0,0,0,0xbe37bce8,
0x3e390000,0,0,0,0,0x3e390000,0,0,0,0,0x3e390000,0,0,0,0,0x3e390000,
0x3e253da8,0,0,0,0,0x3e253da8,0,0,0,0,0x3e253da8,0,0,0,0,0x3e253da8,
0xbe30bd65,0,0,0,0,0xbe30bd65,0,0,0,0,0xbe30bd65,0,0,0,0,0xbe30bd65,
0xbe25bda8,0,0,0,0,0xbe25bda8,0,0,0,0,0xbe25bda8,0,0,0,0,0xbe25bda8,
0x3dda3e16,0,0,0,0,0x3dda3e16,0,0,0,0,0x3dda3e16,0,0,0,0,0x3dda3e16,
0x3ce83e37,0,0,0,0,0x3ce83e37,0,0,0,0,0x3ce83e37,0,0,0,0,0x3ce83e37,
0xbe16bdda,0,0,0,0,0xbe16bdda,0,0,0,0,0xbe16bdda,0,0,0,0,0xbe16bdda,
0xbe03be03,0,0,0,0,0xbe03be03,0,0,0,0,0xbe03be03,0,0,0,0,0xbe03be03,
0xbd653e30,0,0,0,0,0xbd653e30,0,0,0,0,0xbd653e30,0,0,0,0,0xbd653e30,
0xbe033e03,0,0,0,0,0xbe033e03,0,0,0,0,0xbe033e03,0,0,0,0,0xbe033e03,
0xbddabe16,0,0,0,0,0xbddabe16,0,0,0,0,0xbddabe16,0,0,0,0,0xbddabe16,
0xbda8be25,0,0,0,0,0xbda8be25,0,0,0,0,0xbda8be25,0,0,0,0,0xbda8be25,
0xbe303d65,0,0,0,0,0xbe303d65,0,0,0,0,0xbe303d65,0,0,0,0,0xbe303d65,
0xbe37bce8,0,0,0,0,0xbe37bce8,0,0,0,0,0xbe37bce8,0,0,0,0,0xbe37bce8,
0xbd65be30,0,0,0,0,0xbd65be30,0,0,0,0,0xbd65be30,0,0,0,0,0xbd65be30,
0xbce8be37,0,0,0,0,0xbce8be37,0,0,0,0,0xbce8be37,0,0,0,0,0xbce8be37,
0xbe16bdda,0,0,0,0,0xbe16bdda,0,0,0,0,0xbe16bdda,0,0,0,0,0xbe16bdda,
0xbda8be25,0,0,0,0,0xbda8be25,0,0,0,0,0xbda8be25,0,0,0,0,0xbda8be25,
0x3e390000,0,0,0,0,0x3e390000,0,0,0,0,0x3e390000,0,0,0,0,0x3e390000,
0x3e033e03,0,0,0,0,0x3e033e03,0,0,0,0,0x3e033e03,0,0,0,0,0x3e033e03,
0xbd653e30,0,0,0,0,0xbd653e30,0,0,0,0,0xbd653e30,0,0,0,0,0xbd653e30,
0xbe373ce8,0,0,0,0,0xbe373ce8,0,0,0,0,0xbe373ce8,0,0,0,0,0xbe373ce8,
0x80003e39,0,0,0,0,0x80003e39,0,0,0,0,0x80003e39,0,0,0,0,0x80003e39,
0xbe033e03,0,0,0,0,0xbe033e03,0,0,0,0,0xbe033e03,0,0,0,0,0xbe033e03,
0xbddabe16,0,0,0,0,0xbddabe16,0,0,0,0,0xbddabe16,0,0,0,0,0xbddabe16,
0x3da8be25,0,0,0,0,0x3da8be25,0,0,0,0,0x3da8be25,0,0,0,0,0x3da8be25,
0xbe390000,0,0,0,0,0xbe390000,0,0,0,0,0xbe390000,0,0,0,0,0xbe390000,
0xbe03be03,0,0,0,0,0xbe03be03,0,0,0,0,0xbe03be03,0,0,0,0,0xbe03be03,
0x3e390000,0,0,0,0,0x3e390000,0,0,0,0,0x3e390000,0,0,0,0,0x3e390000,
0x3da83e25,0,0,0,0,0x3da83e25,0,0,0,0,0x3da83e25,0,0,0,0,0x3da83e25,
0x8000be39,0,0,0,0,0x8000be39,0,0,0,0,0x8000be39,0,0,0,0,0x8000be39,
0x3e03be03,0,0,0,0,0x3e03be03,0,0,0,0,0x3e03be03,0,0,0,0,0x3e03be03,
0xbdda3e16,0,0,0,0,0xbdda3e16,0,0,0,0,0xbdda3e16,0,0,0,0,0xbdda3e16,
0xbe37bce8,0,0,0,0,0xbe37bce8,0,0,0,0,0xbe37bce8,0,0,0,0,0xbe37bce8,
0x3e390000,0,0,0,0,0x3e390000,0,0,0,0,0x3e390000,0,0,0,0,0x3e390000,
0x3e033e03,0,0,0,0,0x3e033e03,0,0,0,0,0x3e033e03,0,0,0,0,0x3e033e03,
0xbd65be30,0,0,0,0,0xbd65be30,0,0,0,0,0xbd65be30,0,0,0,0,0xbd65be30,
0x3e03be03,0,0,0,0,0x3e03be03,0,0,0,0,0x3e03be03,0,0,0,0,0x3e03be03,
0x80003e39,0,0,0,0,0x80003e39,0,0,0,0,0x80003e39,0,0,0,0,0x80003e39,
0xbe033e03,0,0,0,0,0xbe033e03,0,0,0,0,0xbe033e03,0,0,0,0,0xbe033e03,
0x3e303d65,0,0,0,0,0x3e303d65,0,0,0,0,0x3e303d65,0,0,0,0,0x3e303d65,
0x3ce83e37,0,0,0,0,0x3ce83e37,0,0,0,0,0x3ce83e37,0,0,0,0,0x3ce83e37,
0xbe390000,0,0,0,0,0xbe390000,0,0,0,0,0xbe390000,0,0,0,0,0xbe390000,
0xbe03be03,0,0,0,0,0xbe03be03,0,0,0,0,0xbe03be03,0,0,0,0,0xbe03be03,
0xbe163dda,0,0,0,0,0xbe163dda,0,0,0,0,0xbe163dda,0,0,0,0,0xbe163dda,
0xbe25bda8,0,0,0,0,0xbe25bda8,0,0,0,0,0xbe25bda8,0,0,0,0,0xbe25bda8,
0xbe16bdda,0,0,0,0,0xbe16bdda,0,0,0,0,0xbe16bdda,0,0,0,0,0xbe16bdda,
0x3da8be25,0,0,0,0,0x3da8be25,0,0,0,0,0x3da8be25,0,0,0,0,0x3da8be25,
0x3e16bdda,0,0,0,0,0x3e16bdda,0,0,0,0,0x3e16bdda,0,0,0,0,0x3e16bdda,
0x3da83e25,0,0,0,0,0x3da83e25,0,0,0,0,0x3da83e25,0,0,0,0,0x3da83e25,
0x3e303d65,0,0,0,0,0x3e303d65,0,0,0,0,0x3e303d65,0,0,0,0,0x3e303d65,
0xbce83e37,0,0,0,0,0xbce83e37,0,0,0,0,0xbce83e37,0,0,0,0,0xbce83e37,
0xbe303d65,0,0,0,0,0xbe303d65,0,0,0,0,0xbe303d65,0,0,0,0,0xbe303d65,
0xbce8be37,0,0,0,0,0xbce8be37,0,0,0,0,0xbce8be37,0,0,0,0,0xbce8be37,
0xbe390000,0,0,0,0,0xbe390000,0,0,0,0,0xbe390000,0,0,0,0,0xbe390000,
0xbce8be37,0,0,0,0,0xbce8be37,0,0,0,0,0xbce8be37,0,0,0,0,0xbce8be37,
0x3e390000,0,0,0,0,0x3e390000,0,0,0,0,0x3e390000,0,0,0,0,0x3e390000,
0xbce83e37,0,0,0,0,0xbce83e37,0,0,0,0,0xbce83e37,0,0,0,0,0xbce83e37,
0x3e30bd65,0,0,0,0,0x3e30bd65,0,0,0,0,0x3e30bd65,0,0,0,0,0x3e30bd65,
0x3da83e25,0,0,0,0,0x3da83e25,0,0,0,0,0x3da83e25,0,0,0,0,0x3da83e25,
0xbe30bd65,0,0,0,0,0xbe30bd65,0,0,0,0,0xbe30bd65,0,0,0,0,0xbe30bd65,
0x3da8be25,0,0,0,0,0x3da8be25,0,0,0,0,0x3da8be25,0,0,0,0,0x3da8be25,
0xbe163dda,0,0,0,0,0xbe163dda,0,0,0,0,0xbe163dda,0,0,0,0,0xbe163dda,
0xbe03be03,0,0,0,0,0xbe03be03,0,0,0,0,0xbe03be03,0,0,0,0,0xbe03be03,
0x3e163dda,0,0,0,0,0x3e163dda,0,0,0,0,0x3e163dda,0,0,0,0,0x3e163dda,
0xbe033e03,0,0,0,0,0xbe033e03,0,0,0,0,0xbe033e03,0,0,0,0,0xbe033e03,
0x3ddabe16,0,0,0,0,0x3ddabe16,0,0,0,0,0x3ddabe16,0,0,0,0,0x3ddabe16,
0x3e253da8,0,0,0,0,0x3e253da8,0,0,0,0,0x3e253da8,0,0,0,0,0x3e253da8,
0xbddabe16,0,0,0,0,0xbddabe16,0,0,0,0,0xbddabe16,0,0,0,0,0xbddabe16,
0x3e25bda8,0,0,0,0,0x3e25bda8,0,0,0,0,0x3e25bda8,0,0,0,0,0x3e25bda8,
0xbd653e30,0,0,0,0,0xbd653e30,0,0,0,0,0xbd653e30,0,0,0,0,0xbd653e30,
0xbe37bce8,0,0,0,0,0xbe37bce8,0,0,0,0,0xbe37bce8,0,0,0,0,0xbe37bce8,
0x3d653e30,0,0,0,0,0x3d653e30,0,0,0,0,0x3d653e30,0,0,0,0,0x3d653e30,
0xbe373ce8,0,0,0,0,0xbe373ce8,0,0,0,0,0xbe373ce8,0,0,0,0,0xbe373ce8,
0x3d653e30,0,0,0,0,0x3d653e30,0,0,0,0,0x3d653e30,0,0,0,0,0x3d653e30,
0xbe37bce8,0,0,0,0,0xbe37bce8,0,0,0,0,0xbe37bce8,0,0,0,0,0xbe37bce8,
0xbe390000,0,0,0,0,0xbe390000,0,0,0,0,0xbe390000,0,0,0,0,0xbe390000,
0x3e03be03,0,0,0,0,0x3e03be03,0,0,0,0,0x3e03be03,0,0,0,0,0x3e03be03,
0x3ddabe16,0,0,0,0,0x3ddabe16,0,0,0,0,0x3ddabe16,0,0,0,0,0x3ddabe16,
0x3da83e25,0,0,0,0,0x3da83e25,0,0,0,0,0x3da83e25,0,0,0,0,0x3da83e25,
0x80003e39,0,0,0,0,0x80003e39,0,0,0,0,0x80003e39,0,0,0,0,0x80003e39,
0xbe03be03,0,0,0,0,0xbe03be03,0,0,0,0,0xbe03be03,0,0,0,0,0xbe03be03,
0xbe390000,0,0,0,0,0xbe390000,0,0,0,0,0xbe390000,0,0,0,0,0xbe390000,
0x3da8be25,0,0,0,0,0x3da8be25,0,0,0,0,0x3da8be25,0,0,0,0,0x3da8be25,
0x3e390000,0,0,0,0,0x3e390000,0,0,0,0,0x3e390000,0,0,0,0,0x3e390000,
0xbe033e03,0,0,0,0,0xbe033e03,0,0,0,0,0xbe033e03,0,0,0,0,0xbe033e03,
0x3dda3e16,0,0,0,0,0x3dda3e16,0,0,0,0,0x3dda3e16,0,0,0,0,0x3dda3e16,
0xbe373ce8,0,0,0,0,0xbe373ce8,0,0,0,0,0xbe373ce8,0,0,0,0,0xbe373ce8,
0x8000be39,0,0,0,0,0x8000be39,0,0,0,0,0x8000be39,0,0,0,0,0x8000be39,
0x3e033e03,0,0,0,0,0x3e033e03,0,0,0,0,0x3e033e03,0,0,0,0,0x3e033e03,
0x3d65be30,0,0,0,0,0x3d65be30,0,0,0,0,0x3d65be30,0,0,0,0,0x3d65be30,
0x3e033e03,0,0,0,0,0x3e033e03,0,0,0,0,0x3e033e03,0,0,0,0,0x3e033e03,
0xbe390000,0,0,0,0,0xbe390000,0,0,0,0,0xbe390000,0,0,0,0,0xbe390000,
0x3e03be03,0,0,0,0,0x3e03be03,0,0,0,0,0x3e03be03,0,0,0,0,0x3e03be03,
0xbe303d65,0,0,0,0,0xbe303d65,0,0,0,0,0xbe303d65,0,0,0,0,0xbe303d65,
0x3ce8be37,0,0,0,0,0x3ce8be37,0,0,0,0,0x3ce8be37,0,0,0,0,0x3ce8be37,
0x80003e39,0,0,0,0,0x80003e39,0,0,0,0,0x80003e39,0,0,0,0,0x80003e39,
0xbe03be03,0,0,0,0,0xbe03be03,0,0,0,0,0xbe03be03,0,0,0,0,0xbe03be03,
0x3e163dda,0,0,0,0,0x3e163dda,0,0,0,0,0x3e163dda,0,0,0,0,0x3e163dda,
0xbe253da8,0,0,0,0,0xbe253da8,0,0,0,0,0xbe253da8,0,0,0,0,0xbe253da8,
0x3e390000,0,0,0,0,0x3e390000,0,0,0,0,0x3e390000,0,0,0,0,0x3e390000,
0xbe033e03,0,0,0,0,0xbe033e03,0,0,0,0,0xbe033e03,0,0,0,0,0xbe033e03,
0x3d65be30,0,0,0,0,0x3d65be30,0,0,0,0,0x3d65be30,0,0,0,0,0x3d65be30,
0x3ce83e37,0,0,0,0,0x3ce83e37,0,0,0,0,0x3ce83e37,0,0,0,0,0x3ce83e37,
0x3e163dda,0,0,0,0,0x3e163dda,0,0,0,0,0x3e163dda,0,0,0,0,0x3e163dda,
0xbe25bda8,0,0,0,0,0xbe25bda8,0,0,0,0,0xbe25bda8,0,0,0,0,0xbe25bda8,
0xbddabe16,0,0,0,0,0xbddabe16,0,0,0,0,0xbddabe16,0,0,0,0,0xbddabe16,
0x3e253da8,0,0,0,0,0x3e253da8,0,0,0,0,0x3e253da8,0,0,0,0,0x3e253da8,
0x3e303d65,0,0,0,0,0x3e303d65,0,0,0,0,0x3e303d65,0,0,0,0,0x3e303d65,
0xbe37bce8,0,0,0,0,0xbe37bce8,0,0,0,0,0xbe37bce8,0,0,0,0,0xbe37bce8,
0xbe390000,0,0,0,0,0xbe390000,0,0,0,0,0xbe390000,0,0,0,0,0xbe390000,
0x3e25bda8,0,0,0,0,0x3e25bda8,0,0,0,0,0x3e25bda8,0,0,0,0,0x3e25bda8,
0x3e390000,0,0,0,0,0x3e390000,0,0,0,0,0x3e390000,0,0,0,0,0x3e390000,
0xbe373ce8,0,0,0,0,0xbe373ce8,0,0,0,0,0xbe373ce8,0,0,0,0,0xbe373ce8,
0xbdda3e16,0,0,0,0,0xbdda3e16,0,0,0,0,0xbdda3e16,0,0,0,0,0xbdda3e16,
0x3ce8be37,0,0,0,0,0x3ce8be37,0,0,0,0,0x3ce8be37,0,0,0,0,0x3ce8be37,
0x3e30bd65,0,0,0,0,0x3e30bd65,0,0,0,0,0x3e30bd65,0,0,0,0,0x3e30bd65,
0xbe253da8,0,0,0,0,0xbe253da8,0,0,0,0,0xbe253da8,0,0,0,0,0xbe253da8,
0x3d653e30,0,0,0,0,0x3d653e30,0,0,0,0,0x3d653e30,0,0,0,0,0x3d653e30,
0xbe03be03,0,0,0,0,0xbe03be03,0,0,0,0,0xbe03be03,0,0,0,0,0xbe03be03,
0x3e16bdda,0,0,0,0,0x3e16bdda,0,0,0,0,0x3e16bdda,0,0,0,0,0x3e16bdda,
0xbe033e03,0,0,0,0,0xbe033e03,0,0,0,0,0xbe033e03,0,0,0,0,0xbe033e03,
0x3e303d65,0,0,0,0,0x3e303d65,0,0,0,0,0x3e303d65,0,0,0,0,0x3e303d65,
0xbe373ce8,0,0,0,0,0xbe373ce8,0,0,0,0,0xbe373ce8,0,0,0,0,0xbe373ce8,
0x3ddabe16,0,0,0,0,0x3ddabe16,0,0,0,0,0x3ddabe16,0,0,0,0,0x3ddabe16,
0xbda83e25,0,0,0,0,0xbda83e25,0,0,0,0,0xbda83e25,0,0,0,0,0xbda83e25,
0x3e16bdda,0,0,0,0,0x3e16bdda,0,0,0,0,0x3e16bdda,0,0,0,0,0x3e16bdda,
0xbda83e25,0,0,0,0,0xbda83e25,0,0,0,0,0xbda83e25,0,0,0,0,0xbda83e25,
0x3d65be30,0,0,0,0,0x3d65be30,0,0,0,0,0x3d65be30,0,0,0,0,0x3d65be30,
0xbce83e37,0,0,0,0,0xbce83e37,0,0,0,0,0xbce83e37,0,0,0,0,0xbce83e37,
0,0,0xbe163dda,0,0,0,0,0xbe163dda,0,0,0xbe253da8,0,0,0,0,0xbe253da8,
0,0,0xbe303d65,0,0,0,0,0xbe303d65,0,0,0xbe373ce8,0,0,0,0,0xbe373ce8,
0,0,0xbd65be30,0,0,0,0,0xbd65be30,0,0,0x3ce8be37,0,0,0,0,0x3ce8be37,
0,0,0x3ddabe16,0,0,0,0,0x3ddabe16,0,0,0x3e25bda8,0,0,0,0,0x3e25bda8,
0,0,0xbe390000,0,0,0,0,0xbe390000,0,0,0xbe37bce8,0,0,0,0,0xbe37bce8,
0,0,0xbe30bd65,0,0,0,0,0xbe30bd65,0,0,0xbe25bda8,0,0,0,0,0xbe25bda8,
0,0,0x3e390000,0,0,0,0,0x3e390000,0,0,0x3e253da8,0,0,0,0,0x3e253da8,
0,0,0x3dda3e16,0,0,0,0,0x3dda3e16,0,0,0x3ce83e37,0,0,0,0,0x3ce83e37,
0,0,0xbe16bdda,0,0,0,0,0xbe16bdda,0,0,0xbe03be03,0,0,0,0,0xbe03be03,
0,0,0xbddabe16,0,0,0,0,0xbddabe16,0,0,0xbda8be25,0,0,0,0,0xbda8be25,
0,0,0xbd653e30,0,0,0,0,0xbd653e30,0,0,0xbe033e03,0,0,0,0,0xbe033e03,
0,0,0xbe303d65,0,0,0,0,0xbe303d65,0,0,0xbe37bce8,0,0,0,0,0xbe37bce8,
0,0,0xbd65be30,0,0,0,0,0xbd65be30,0,0,0xbce8be37,0,0,0,0,0xbce8be37,
0,0,0,0,0,0,0,0,0,0,0,0,0,0,0,0,
0,0,0xbe16bdda,0,0,0,0,0xbe16bdda,0,0,0xbda8be25,0,0,0,0,0xbda8be25,
0,0,0,0,0,0,0,0,0,0,0,0,0,0,0,0,
0,0,0x3e390000,0,0,0,0,0x3e390000,0,0,0x3e033e03,0,0,0,0,0x3e033e03,
0,0,0x80003e39,0,0,0,0,0x80003e39,0,0,0xbe033e03,0,0,0,0,0xbe033e03,
0,0,0xbd653e30,0,0,0,0,0xbd653e30,0,0,0xbe373ce8,0,0,0,0,0xbe373ce8,
0,0,0xbddabe16,0,0,0,0,0xbddabe16,0,0,0x3da8be25,0,0,0,0,0x3da8be25,
0,0,0xbe390000,0,0,0,0,0xbe390000,0,0,0xbe03be03,0,0,0,0,0xbe03be03,
0,0,0x8000be39,0,0,0,0,0x8000be39,0,0,0x3e03be03,0,0,0,0,0x3e03be03,
0,0,0x3e390000,0,0,0,0,0x3e390000,0,0,0x3da83e25,0,0,0,0,0x3da83e25,
0,0,0xbdda3e16,0,0,0,0,0xbdda3e16,0,0,0xbe37bce8,0,0,0,0,0xbe37bce8,
0,0,0x3e390000,0,0,0,0,0x3e390000,0,0,0x3e033e03,0,0,0,0,0x3e033e03,
0,0,0x80003e39,0,0,0,0,0x80003e39,0,0,0xbe033e03,0,0,0,0,0xbe033e03,
0,0,0xbd65be30,0,0,0,0,0xbd65be30,0,0,0x3e03be03,0,0,0,0,0x3e03be03,
0,0,0x3e303d65,0,0,0,0,0x3e303d65,0,0,0x3ce83e37,0,0,0,0,0x3ce83e37,
0,0,0xbe390000,0,0,0,0,0xbe390000,0,0,0xbe03be03,0,0,0,0,0xbe03be03,
0,0,0,0,0,0,0,0,0,0,0,0,0,0,0,0,
0,0,0xbe163dda,0,0,0,0,0xbe163dda,0,0,0xbe25bda8,0,0,0,0,0xbe25bda8,
0,0,0,0,0,0,0,0,0,0,0,0,0,0,0,0,
0,0,0xbe16bdda,0,0,0,0,0xbe16bdda,0,0,0x3da8be25,0,0,0,0,0x3da8be25,
0,0,0x3e303d65,0,0,0,0,0x3e303d65,0,0,0xbce83e37,0,0,0,0,0xbce83e37,
0,0,0x3e16bdda,0,0,0,0,0x3e16bdda,0,0,0x3da83e25,0,0,0,0,0x3da83e25,
0,0,0xbe303d65,0,0,0,0,0xbe303d65,0,0,0xbce8be37,0,0,0,0,0xbce8be37,
0,0,0xbe390000,0,0,0,0,0xbe390000,0,0,0xbce8be37,0,0,0,0,0xbce8be37,
0,0,0x3e30bd65,0,0,0,0,0x3e30bd65,0,0,0x3da83e25,0,0,0,0,0x3da83e25,
0,0,0x3e390000,0,0,0,0,0x3e390000,0,0,0xbce83e37,0,0,0,0,0xbce83e37,
0,0,0xbe30bd65,0,0,0,0,0xbe30bd65,0,0,0x3da8be25,0,0,0,0,0x3da8be25,
0,0,0xbe163dda,0,0,0,0,0xbe163dda,0,0,0xbe03be03,0,0,0,0,0xbe03be03,
0,0,0x3ddabe16,0,0,0,0,0x3ddabe16,0,0,0x3e253da8,0,0,0,0,0x3e253da8,
0,0,0x3e163dda,0,0,0,0,0x3e163dda,0,0,0xbe033e03,0,0,0,0,0xbe033e03,
0,0,0xbddabe16,0,0,0,0,0xbddabe16,0,0,0x3e25bda8,0,0,0,0,0x3e25bda8,
0,0,0xbd653e30,0,0,0,0,0xbd653e30,0,0,0xbe37bce8,0,0,0,0,0xbe37bce8,
0,0,0,0,0,0,0,0,0,0,0,0,0,0,0,0,
0,0,0x3d653e30,0,0,0,0,0x3d653e30,0,0,0xbe373ce8,0,0,0,0,0xbe373ce8,
0,0,0,0,0,0,0,0,0,0,0,0,0,0,0,0,
0,0,0x3d653e30,0,0,0,0,0x3d653e30,0,0,0xbe37bce8,0,0,0,0,0xbe37bce8,
0,0,0x3ddabe16,0,0,0,0,0x3ddabe16,0,0,0x3da83e25,0,0,0,0,0x3da83e25,
0,0,0xbe390000,0,0,0,0,0xbe390000,0,0,0x3e03be03,0,0,0,0,0x3e03be03,
0,0,0x80003e39,0,0,0,0,0x80003e39,0,0,0xbe03be03,0,0,0,0,0xbe03be03,
0,0,0xbe390000,0,0,0,0,0xbe390000,0,0,0x3da8be25,0,0,0,0,0x3da8be25,
0,0,0x3dda3e16,0,0,0,0,0x3dda3e16,0,0,0xbe373ce8,0,0,0,0,0xbe373ce8,
0,0,0x3e390000,0,0,0,0,0x3e390000,0,0,0xbe033e03,0,0,0,0,0xbe033e03,
0,0,0x8000be39,0,0,0,0,0x8000be39,0,0,0x3e033e03,0,0,0,0,0x3e033e03,
0,0,0x3d65be30,0,0,0,0,0x3d65be30,0,0,0x3e033e03,0,0,0,0,0x3e033e03,
0,0,0xbe303d65,0,0,0,0,0xbe303d65,0,0,0x3ce8be37,0,0,0,0,0x3ce8be37,
0,0,0xbe390000,0,0,0,0,0xbe390000,0,0,0x3e03be03,0,0,0,0,0x3e03be03,
0,0,0x80003e39,0,0,0,0,0x80003e39,0,0,0xbe03be03,0,0,0,0,0xbe03be03,
0,0,0x3e163dda,0,0,0,0,0x3e163dda,0,0,0xbe253da8,0,0,0,0,0xbe253da8,
0,0,0,0,0,0,0,0,0,0,0,0,0,0,0,0,
0,0,0x3e390000,0,0,0,0,0x3e390000,0,0,0xbe033e03,0,0,0,0,0xbe033e03,
0,0,0,0,0,0,0,0,0,0,0,0,0,0,0,0,
0,0,0x3d65be30,0,0,0,0,0x3d65be30,0,0,0x3ce83e37,0,0,0,0,0x3ce83e37,
0,0,0xbddabe16,0,0,0,0,0xbddabe16,0,0,0x3e253da8,0,0,0,0,0x3e253da8,
0,0,0x3e163dda,0,0,0,0,0x3e163dda,0,0,0xbe25bda8,0,0,0,0,0xbe25bda8,
0,0,0x3e303d65,0,0,0,0,0x3e303d65,0,0,0xbe37bce8,0,0,0,0,0xbe37bce8,
0,0,0xbe390000,0,0,0,0,0xbe390000,0,0,0x3e25bda8,0,0,0,0,0x3e25bda8,
0,0,0xbdda3e16,0,0,0,0,0xbdda3e16,0,0,0x3ce8be37,0,0,0,0,0x3ce8be37,
0,0,0x3e390000,0,0,0,0,0x3e390000,0,0,0xbe373ce8,0,0,0,0,0xbe373ce8,
0,0,0x3e30bd65,0,0,0,0,0x3e30bd65,0,0,0xbe253da8,0,0,0,0,0xbe253da8,
0,0,0x3d653e30,0,0,0,0,0x3d653e30,0,0,0xbe03be03,0,0,0,0,0xbe03be03,
0,0,0x3e303d65,0,0,0,0,0x3e303d65,0,0,0xbe373ce8,0,0,0,0,0xbe373ce8,
0,0,0x3e16bdda,0,0,0,0,0x3e16bdda,0,0,0xbe033e03,0,0,0,0,0xbe033e03,
0,0,0x3ddabe16,0,0,0,0,0x3ddabe16,0,0,0xbda83e25,0,0,0,0,0xbda83e25,
0,0,0x3e16bdda,0,0,0,0,0x3e16bdda,0,0,0xbda83e25,0,0,0,0,0xbda83e25,
0,0,0,0,0,0,0,0,0,0,0,0,0,0,0,0,
0,0,0x3d65be30,0,0,0,0,0x3d65be30,0,0,0xbce83e37,0,0,0,0,0xbce83e37,
0,0,0,0,0,0,0,0,0,0,0,0,0,0,0,0,
};
constexpr unsigned long long COS_PK0 = 0x3f903f9a3fa03fa2ull;
constexpr unsigned long long COS_PK1 = 0x3f133f3e3f653f83ull;
constexpr unsigned long long COS_PK2 = 0x3e4b3ec8ull;

__device__ __forceinline__ void wgmma_ss_n80_z(float (&d)[40], uint64_t da, uint64_t db) {
  asm volatile("{\n.reg .pred p;\nsetp.ne.b32 p, 0, 0;\nwgmma.mma_async.sync.aligned.m64n80k16.f32.bf16.bf16 {%0,%1,%2,%3,%4,%5,%6,%7,%8,%9,%10,%11,%12,%13,%14,%15,%16,%17,%18,%19,%20,%21,%22,%23,%24,%25,%26,%27,%28,%29,%30,%31,%32,%33,%34,%35,%36,%37,%38,%39}, %40, %41, p, 1, 1, 1, 0;\n}\n"
    : "+f"(d[0]), "+f"(d[1]), "+f"(d[2]), "+f"(d[3]), "+f"(d[4]), "+f"(d[5]), "+f"(d[6]), "+f"(d[7]), "+f"(d[8]), "+f"(d[9]), "+f"(d[10]), "+f"(d[11]), "+f"(d[12]), "+f"(d[13]), "+f"(d[14]), "+f"(d[15]), "+f"(d[16]), "+f"(d[17]), "+f"(d[18]), "+f"(d[19]), "+f"(d[20]), "+f"(d[21]), "+f"(d[22]), "+f"(d[23]), "+f"(d[24]), "+f"(d[25]), "+f"(d[26]), "+f"(d[27]), "+f"(d[28]), "+f"(d[29]), "+f"(d[30]), "+f"(d[31]), "+f"(d[32]), "+f"(d[33]), "+f"(d[34]), "+f"(d[35]), "+f"(d[36]), "+f"(d[37]), "+f"(d[38]), "+f"(d[39])
    : "l"(da), "l"(db));
}
__device__ __forceinline__ void wgmma_ss_n80_a(float (&d)[40], uint64_t da, uint64_t db) {
  asm volatile("{\n.reg .pred p;\nsetp.ne.b32 p, 1, 0;\nwgmma.mma_async.sync.aligned.m64n80k16.f32.bf16.bf16 {%0,%1,%2,%3,%4,%5,%6,%7,%8,%9,%10,%11,%12,%13,%14,%15,%16,%17,%18,%19,%20,%21,%22,%23,%24,%25,%26,%27,%28,%29,%30,%31,%32,%33,%34,%35,%36,%37,%38,%39}, %40, %41, p, 1, 1, 1, 0;\n}\n"
    : "+f"(d[0]), "+f"(d[1]), "+f"(d[2]), "+f"(d[3]), "+f"(d[4]), "+f"(d[5]), "+f"(d[6]), "+f"(d[7]), "+f"(d[8]), "+f"(d[9]), "+f"(d[10]), "+f"(d[11]), "+f"(d[12]), "+f"(d[13]), "+f"(d[14]), "+f"(d[15]), "+f"(d[16]), "+f"(d[17]), "+f"(d[18]), "+f"(d[19]), "+f"(d[20]), "+f"(d[21]), "+f"(d[22]), "+f"(d[23]), "+f"(d[24]), "+f"(d[25]), "+f"(d[26]), "+f"(d[27]), "+f"(d[28]), "+f"(d[29]), "+f"(d[30]), "+f"(d[31]), "+f"(d[32]), "+f"(d[33]), "+f"(d[34]), "+f"(d[35]), "+f"(d[36]), "+f"(d[37]), "+f"(d[38]), "+f"(d[39])
    : "l"(da), "l"(db));
}

__device__ __forceinline__ void wgmma_rs_n40_z(float (&d)[20], uint32_t a0, uint32_t a1, uint32_t a2, uint32_t a3, uint64_t db) {
  asm volatile("{\n.reg .pred p;\nsetp.ne.b32 p, 0, 0;\nwgmma.mma_async.sync.aligned.m64n40k16.f32.bf16.bf16 {%0,%1,%2,%3,%4,%5,%6,%7,%8,%9,%10,%11,%12,%13,%14,%15,%16,%17,%18,%19}, {%20,%21,%22,%23}, %24, p, 1, 1, 0;\n}\n"
    : "+f"(d[0]), "+f"(d[1]), "+f"(d[2]), "+f"(d[3]), "+f"(d[4]), "+f"(d[5]), "+f"(d[6]), "+f"(d[7]), "+f"(d[8]), "+f"(d[9]), "+f"(d[10]), "+f"(d[11]), "+f"(d[12]), "+f"(d[13]), "+f"(d[14]), "+f"(d[15]), "+f"(d[16]), "+f"(d[17]), "+f"(d[18]), "+f"(d[19])
    : "r"(a0), "r"(a1), "r"(a2), "r"(a3), "l"(db));
}
__device__ __forceinline__ void wgmma_rs_n40_a(float (&d)[20], uint32_t a0, uint32_t a1, uint32_t a2, uint32_t a3, uint64_t db) {
  asm volatile("{\n.reg .pred p;\nsetp.ne.b32 p, 1, 0;\nwgmma.mma_async.sync.aligned.m64n40k16.f32.bf16.bf16 {%0,%1,%2,%3,%4,%5,%6,%7,%8,%9,%10,%11,%12,%13,%14,%15,%16,%17,%18,%19}, {%20,%21,%22,%23}, %24, p, 1, 1, 0;\n}\n"
    : "+f"(d[0]), "+f"(d[1]), "+f"(d[2]), "+f"(d[3]), "+f"(d[4]), "+f"(d[5]), "+f"(d[6]), "+f"(d[7]), "+f"(d[8]), "+f"(d[9]), "+f"(d[10]), "+f"(d[11]), "+f"(d[12]), "+f"(d[13]), "+f"(d[14]), "+f"(d[15]), "+f"(d[16]), "+f"(d[17]), "+f"(d[18]), "+f"(d[19])
    : "r"(a0), "r"(a1), "r"(a2), "r"(a3), "l"(db));
}

__device__ __forceinline__ void wgmma_rs_n128_z(float (&d)[64], uint32_t a0, uint32_t a1, uint32_t a2, uint32_t a3, uint64_t db) {
  asm volatile("{\n.reg .pred p;\nsetp.ne.b32 p, 0, 0;\nwgmma.mma_async.sync.aligned.m64n128k16.f32.bf16.bf16 {%0,%1,%2,%3,%4,%5,%6,%7,%8,%9,%10,%11,%12,%13,%14,%15,%16,%17,%18,%19,%20,%21,%22,%23,%24,%25,%26,%27,%28,%29,%30,%31,%32,%33,%34,%35,%36,%37,%38,%39,%40,%41,%42,%43,%44,%45,%46,%47,%48,%49,%50,%51,%52,%53,%54,%55,%56,%57,%58,%59,%60,%61,%62,%63}, {%64,%65,%66,%67}, %68, p, 1, 1, 1;\n}\n"
    : "+f"(d[0]), "+f"(d[1]), "+f"(d[2]), "+f"(d[3]), "+f"(d[4]), "+f"(d[5]), "+f"(d[6]), "+f"(d[7]), "+f"(d[8]), "+f"(d[9]), "+f"(d[10]), "+f"(d[11]), "+f"(d[12]), "+f"(d[13]), "+f"(d[14]), "+f"(d[15]), "+f"(d[16]), "+f"(d[17]), "+f"(d[18]), "+f"(d[19]), "+f"(d[20]), "+f"(d[21]), "+f"(d[22]), "+f"(d[23]), "+f"(d[24]), "+f"(d[25]), "+f"(d[26]), "+f"(d[27]), "+f"(d[28]), "+f"(d[29]), "+f"(d[30]), "+f"(d[31]), "+f"(d[32]), "+f"(d[33]), "+f"(d[34]), "+f"(d[35]), "+f"(d[36]), "+f"(d[37]), "+f"(d[38]), "+f"(d[39]), "+f"(d[40]), "+f"(d[41]), "+f"(d[42]), "+f"(d[43]), "+f"(d[44]), "+f"(d[45]), "+f"(d[46]), "+f"(d[47]), "+f"(d[48]), "+f"(d[49]), "+f"(d[50]), "+f"(d[51]), "+f"(d[52]), "+f"(d[53]), "+f"(d[54]), "+f"(d[55]), "+f"(d[56]), "+f"(d[57]), "+f"(d[58]), "+f"(d[59]), "+f"(d[60]), "+f"(d[61]), "+f"(d[62]), "+f"(d[63])
    : "r"(a0), "r"(a1), "r"(a2), "r"(a3), "l"(db));
}
__device__ __forceinline__ void wgmma_rs_n128_a(float (&d)[64], uint32_t a0, uint32_t a1, uint32_t a2, uint32_t a3, uint64_t db) {
  asm volatile("{\n.reg .pred p;\nsetp.ne.b32 p, 1, 0;\nwgmma.mma_async.sync.aligned.m64n128k16.f32.bf16.bf16 {%0,%1,%2,%3,%4,%5,%6,%7,%8,%9,%10,%11,%12,%13,%14,%15,%16,%17,%18,%19,%20,%21,%22,%23,%24,%25,%26,%27,%28,%29,%30,%31,%32,%33,%34,%35,%36,%37,%38,%39,%40,%41,%42,%43,%44,%45,%46,%47,%48,%49,%50,%51,%52,%53,%54,%55,%56,%57,%58,%59,%60,%61,%62,%63}, {%64,%65,%66,%67}, %68, p, 1, 1, 1;\n}\n"
    : "+f"(d[0]), "+f"(d[1]), "+f"(d[2]), "+f"(d[3]), "+f"(d[4]), "+f"(d[5]), "+f"(d[6]), "+f"(d[7]), "+f"(d[8]), "+f"(d[9]), "+f"(d[10]), "+f"(d[11]), "+f"(d[12]), "+f"(d[13]), "+f"(d[14]), "+f"(d[15]), "+f"(d[16]), "+f"(d[17]), "+f"(d[18]), "+f"(d[19]), "+f"(d[20]), "+f"(d[21]), "+f"(d[22]), "+f"(d[23]), "+f"(d[24]), "+f"(d[25]), "+f"(d[26]), "+f"(d[27]), "+f"(d[28]), "+f"(d[29]), "+f"(d[30]), "+f"(d[31]), "+f"(d[32]), "+f"(d[33]), "+f"(d[34]), "+f"(d[35]), "+f"(d[36]), "+f"(d[37]), "+f"(d[38]), "+f"(d[39]), "+f"(d[40]), "+f"(d[41]), "+f"(d[42]), "+f"(d[43]), "+f"(d[44]), "+f"(d[45]), "+f"(d[46]), "+f"(d[47]), "+f"(d[48]), "+f"(d[49]), "+f"(d[50]), "+f"(d[51]), "+f"(d[52]), "+f"(d[53]), "+f"(d[54]), "+f"(d[55]), "+f"(d[56]), "+f"(d[57]), "+f"(d[58]), "+f"(d[59]), "+f"(d[60]), "+f"(d[61]), "+f"(d[62]), "+f"(d[63])
    : "r"(a0), "r"(a1), "r"(a2), "r"(a3), "l"(db));
}

__device__ __forceinline__ void wgmma_rs_n32_z(float (&d)[16], uint32_t a0, uint32_t a1, uint32_t a2, uint32_t a3, uint64_t db) {
  asm volatile("{\n.reg .pred p;\nsetp.ne.b32 p, 0, 0;\nwgmma.mma_async.sync.aligned.m64n32k16.f32.bf16.bf16 {%0,%1,%2,%3,%4,%5,%6,%7,%8,%9,%10,%11,%12,%13,%14,%15}, {%16,%17,%18,%19}, %20, p, 1, 1, 0;\n}\n"
    : "+f"(d[0]), "+f"(d[1]), "+f"(d[2]), "+f"(d[3]), "+f"(d[4]), "+f"(d[5]), "+f"(d[6]), "+f"(d[7]), "+f"(d[8]), "+f"(d[9]), "+f"(d[10]), "+f"(d[11]), "+f"(d[12]), "+f"(d[13]), "+f"(d[14]), "+f"(d[15])
    : "r"(a0), "r"(a1), "r"(a2), "r"(a3), "l"(db));
}
__device__ __forceinline__ void wgmma_rs_n32_a(float (&d)[16], uint32_t a0, uint32_t a1, uint32_t a2, uint32_t a3, uint64_t db) {
  asm volatile("{\n.reg .pred p;\nsetp.ne.b32 p, 1, 0;\nwgmma.mma_async.sync.aligned.m64n32k16.f32.bf16.bf16 {%0,%1,%2,%3,%4,%5,%6,%7,%8,%9,%10,%11,%12,%13,%14,%15}, {%16,%17,%18,%19}, %20, p, 1, 1, 0;\n}\n"
    : "+f"(d[0]), "+f"(d[1]), "+f"(d[2]), "+f"(d[3]), "+f"(d[4]), "+f"(d[5]), "+f"(d[6]), "+f"(d[7]), "+f"(d[8]), "+f"(d[9]), "+f"(d[10]), "+f"(d[11]), "+f"(d[12]), "+f"(d[13]), "+f"(d[14]), "+f"(d[15])
    : "r"(a0), "r"(a1), "r"(a2), "r"(a3), "l"(db));
}

__device__ __forceinline__ void wgmma_rs_n64_z(float (&d)[32], uint32_t a0, uint32_t a1, uint32_t a2, uint32_t a3, uint64_t db) {
  asm volatile("{\n.reg .pred p;\nsetp.ne.b32 p, 0, 0;\nwgmma.mma_async.sync.aligned.m64n64k16.f32.bf16.bf16 {%0,%1,%2,%3,%4,%5,%6,%7,%8,%9,%10,%11,%12,%13,%14,%15,%16,%17,%18,%19,%20,%21,%22,%23,%24,%25,%26,%27,%28,%29,%30,%31}, {%32,%33,%34,%35}, %36, p, 1, 1, 0;\n}\n"
    : "+f"(d[0]), "+f"(d[1]), "+f"(d[2]), "+f"(d[3]), "+f"(d[4]), "+f"(d[5]), "+f"(d[6]), "+f"(d[7]), "+f"(d[8]), "+f"(d[9]), "+f"(d[10]), "+f"(d[11]), "+f"(d[12]), "+f"(d[13]), "+f"(d[14]), "+f"(d[15]), "+f"(d[16]), "+f"(d[17]), "+f"(d[18]), "+f"(d[19]), "+f"(d[20]), "+f"(d[21]), "+f"(d[22]), "+f"(d[23]), "+f"(d[24]), "+f"(d[25]), "+f"(d[26]), "+f"(d[27]), "+f"(d[28]), "+f"(d[29]), "+f"(d[30]), "+f"(d[31])
    : "r"(a0), "r"(a1), "r"(a2), "r"(a3), "l"(db));
}
__device__ __forceinline__ void wgmma_rs_n64_a(float (&d)[32], uint32_t a0, uint32_t a1, uint32_t a2, uint32_t a3, uint64_t db) {
  asm volatile("{\n.reg .pred p;\nsetp.ne.b32 p, 1, 0;\nwgmma.mma_async.sync.aligned.m64n64k16.f32.bf16.bf16 {%0,%1,%2,%3,%4,%5,%6,%7,%8,%9,%10,%11,%12,%13,%14,%15,%16,%17,%18,%19,%20,%21,%22,%23,%24,%25,%26,%27,%28,%29,%30,%31}, {%32,%33,%34,%35}, %36, p, 1, 1, 0;\n}\n"
    : "+f"(d[0]), "+f"(d[1]), "+f"(d[2]), "+f"(d[3]), "+f"(d[4]), "+f"(d[5]), "+f"(d[6]), "+f"(d[7]), "+f"(d[8]), "+f"(d[9]), "+f"(d[10]), "+f"(d[11]), "+f"(d[12]), "+f"(d[13]), "+f"(d[14]), "+f"(d[15]), "+f"(d[16]), "+f"(d[17]), "+f"(d[18]), "+f"(d[19]), "+f"(d[20]), "+f"(d[21]), "+f"(d[22]), "+f"(d[23]), "+f"(d[24]), "+f"(d[25]), "+f"(d[26]), "+f"(d[27]), "+f"(d[28]), "+f"(d[29]), "+f"(d[30]), "+f"(d[31])
    : "r"(a0), "r"(a1), "r"(a2), "r"(a3), "l"(db));
}

__device__ __forceinline__ void wgmma_ss_n32_z(float (&d)[16], uint64_t da, uint64_t db) {
  asm volatile("{\n.reg .pred p;\nsetp.ne.b32 p, 0, 0;\nwgmma.mma_async.sync.aligned.m64n32k16.f32.bf16.bf16 {%0,%1,%2,%3,%4,%5,%6,%7,%8,%9,%10,%11,%12,%13,%14,%15}, %16, %17, p, 1, 1, 1, 0;\n}\n"
    : "+f"(d[0]), "+f"(d[1]), "+f"(d[2]), "+f"(d[3]), "+f"(d[4]), "+f"(d[5]), "+f"(d[6]), "+f"(d[7]), "+f"(d[8]), "+f"(d[9]), "+f"(d[10]), "+f"(d[11]), "+f"(d[12]), "+f"(d[13]), "+f"(d[14]), "+f"(d[15])
    : "l"(da), "l"(db));
}
__device__ __forceinline__ void wgmma_ss_n32_a(float (&d)[16], uint64_t da, uint64_t db) {
  asm volatile("{\n.reg .pred p;\nsetp.ne.b32 p, 1, 0;\nwgmma.mma_async.sync.aligned.m64n32k16.f32.bf16.bf16 {%0,%1,%2,%3,%4,%5,%6,%7,%8,%9,%10,%11,%12,%13,%14,%15}, %16, %17, p, 1, 1, 1, 0;\n}\n"
    : "+f"(d[0]), "+f"(d[1]), "+f"(d[2]), "+f"(d[3]), "+f"(d[4]), "+f"(d[5]), "+f"(d[6]), "+f"(d[7]), "+f"(d[8]), "+f"(d[9]), "+f"(d[10]), "+f"(d[11]), "+f"(d[12]), "+f"(d[13]), "+f"(d[14]), "+f"(d[15])
    : "l"(da), "l"(db));
}

__device__ __forceinline__ void wgmma_ss_n40_z(float (&d)[20], uint64_t da, uint64_t db) {
  asm volatile("{\n.reg .pred p;\nsetp.ne.b32 p, 0, 0;\nwgmma.mma_async.sync.aligned.m64n40k16.f32.bf16.bf16 {%0,%1,%2,%3,%4,%5,%6,%7,%8,%9,%10,%11,%12,%13,%14,%15,%16,%17,%18,%19}, %20, %21, p, 1, 1, 1, 0;\n}\n"
    : "+f"(d[0]), "+f"(d[1]), "+f"(d[2]), "+f"(d[3]), "+f"(d[4]), "+f"(d[5]), "+f"(d[6]), "+f"(d[7]), "+f"(d[8]), "+f"(d[9]), "+f"(d[10]), "+f"(d[11]), "+f"(d[12]), "+f"(d[13]), "+f"(d[14]), "+f"(d[15]), "+f"(d[16]), "+f"(d[17]), "+f"(d[18]), "+f"(d[19])
    : "l"(da), "l"(db));
}
__device__ __forceinline__ void wgmma_ss_n40_a(float (&d)[20], uint64_t da, uint64_t db) {
  asm volatile("{\n.reg .pred p;\nsetp.ne.b32 p, 1, 0;\nwgmma.mma_async.sync.aligned.m64n40k16.f32.bf16.bf16 {%0,%1,%2,%3,%4,%5,%6,%7,%8,%9,%10,%11,%12,%13,%14,%15,%16,%17,%18,%19}, %20, %21, p, 1, 1, 1, 0;\n}\n"
    : "+f"(d[0]), "+f"(d[1]), "+f"(d[2]), "+f"(d[3]), "+f"(d[4]), "+f"(d[5]), "+f"(d[6]), "+f"(d[7]), "+f"(d[8]), "+f"(d[9]), "+f"(d[10]), "+f"(d[11]), "+f"(d[12]), "+f"(d[13]), "+f"(d[14]), "+f"(d[15]), "+f"(d[16]), "+f"(d[17]), "+f"(d[18]), "+f"(d[19])
    : "l"(da), "l"(db));
}

constexpr int NSM = 132, NH = 66;
constexpr int S0 = 0, S1 = 51200, S2 = 102400;
constexpr int C1 = 153600, C3 = C1, RG = C1 + 18432;
constexpr int WP = RG, TBL = RG + 28672, WS2 = RG + 30720;
constexpr int BARS = RG + 49152;
__host__ __device__ constexpr int wst_off(int i) { return i < 12 ? S2 + i * 4096 : WS2 + (i - 12) * 4096; }
constexpr int NBAR = 280;
constexpr int REL = BARS + NBAR * 8;
constexpr int SMEM_BYTES = REL + 16;
constexpr int B_XF = 0, B_CF1 = 15, B_CF3 = 16, B_WF = 17  , B_P1D = 18, B_REL = 21, B_ROLE = 22, B_SIG = 24;
constexpr int B_RF = 32, B_RE = 46, B_YF = 60, B_WRD = 75, B_SFREE = 89, B_WCH = 131, B_RDY = 136, B_WE = 205, B_WL = 217, B_FIN = 229, B_TOK = 232;
constexpr int R_P2 = 15, R_P3 = 57;
constexpr int CNT_P1 = 0, CNT_P2 = 4, CNT_W = 8, CNT_RANK = 9, NCLS = 10, CNT_DONE = 0, CNT_REL = 1, NCNT = 2;
constexpr int SIG_W = 0, SIG_P1 = 1, SIG_P2 = 4;
#define XPF 9088
#define XPFN 132
#define T1MASK 0x3e00
#define T2MASK 0x1f00

__device__ uint4 g_scr[(14 << 21) / 16];
__device__ uint4 g_wf[200 * 72 * 32];
__device__ unsigned g_cnt[NCNT * 32];
__device__ __forceinline__ int slot_line(int chunk, int pg, int cls) {
    return (pg & 1) << 6 | (pg >> 1) << 9 | (chunk & 1) << 10 | (chunk >> 1) << 12 | ((pg ^ (pg >> 1) ^ chunk ^ (chunk >> 1) ^ cls) & 1) << 5;
}
__device__ __forceinline__ int phi_line(int phi, uint32_t rel) {
    return (phi >> 4) << 14 | (phi & 3) << 7 | ((phi >> 2) & 1) << 11 | ((phi >> 3) & 1) << 13 | ((rel >> (phi >> 4)) & 1) << 5;
}
__device__ __forceinline__ int extra_mask(int rk) { return rk < 58 ? 0 : rk < 60 ? 2 : rk < 62 ? 1 : rk < 64 ? 4 : 8; }
__device__ __forceinline__ int wslot(int pc) {
    return (int)((0x576476503421ull >> (4 * pc)) & 3) * 12288 + (((0x576476503421ull >> (4 * pc)) & 4) ? S0 : RG);
}
__device__ __forceinline__ int xslot(int n) { return ((n & 4) ? S2 : RG) + ((n + 1) & 3) * 12288; }
__device__ __forceinline__ int extra_phi(int rk) { return 198 + (rk & 1); }
__host__ __device__ constexpr int quad_off(int Q) { return (Q >> 2) * 4096 + (Q & 3) * 512; }

struct Maps { CUtensorMap w, x34, x6, x28, wst, f16, f8, y4, y2; };
struct Ptrs { char* scr; const char* wf; const void* tab1; const void* tab3; unsigned* cnt; const char* x; };

__device__ __forceinline__ uint32_t smem_u32(const void* p) { return (uint32_t)__cvta_generic_to_shared(p); }
__device__ __forceinline__ void mbar_wait(uint32_t bar) {
    uint32_t ok, it = 0;
    do {
        asm volatile("{\n.reg .pred p;\nmbarrier.try_wait.parity.shared::cta.b64 p, [%1], 0;\nselp.u32 %0, 1, 0, p;\n}" : "=r"(ok) : "r"(bar) : "memory");
        if (++it > (1u << 22)) break;
    } while (!ok);
}
__device__ __forceinline__ bool mbar_test(uint32_t bar) {
    uint32_t ok;
    asm volatile("{\n.reg .pred p;\nmbarrier.test_wait.parity.shared::cta.b64 p, [%1], 0;\nselp.u32 %0, 1, 0, p;\n}" : "=r"(ok) : "r"(bar) : "memory");
    return ok;
}
__device__ __forceinline__ void fence_async() { asm volatile("fence.proxy.async;" ::: "memory"); }
__device__ __forceinline__ void fence_async_smem() { asm volatile("fence.proxy.async.shared::cta;" ::: "memory"); }
#define ELECT "{\n.reg .pred p;\nelect.sync _|p, 0xffffffff;\n@p "
__device__ __forceinline__ void e_arrive(uint32_t bar) { asm volatile(ELECT "mbarrier.arrive.shared::cta.b64 _, [%0];\n}" :: "r"(bar) : "memory"); }
__device__ __forceinline__ void e_expect(uint32_t bar, uint32_t bytes) { asm volatile(ELECT "mbarrier.arrive.expect_tx.shared::cta.b64 _, [%0], %1;\n}" :: "r"(bar), "r"(bytes) : "memory"); }
__device__ __forceinline__ void e_g2s(uint32_t dst, const void* src, uint32_t bytes, uint32_t bar) {
    asm volatile(ELECT "cp.async.bulk.shared::cluster.global.mbarrier::complete_tx::bytes [%0], [%1], %2, [%3];\n}" :: "r"(dst), "l"(src), "r"(bytes), "r"(bar) : "memory");
}
__device__ __forceinline__ void e_s2g(void* dst, uint32_t src, uint32_t bytes) {
    asm volatile(ELECT "cp.async.bulk.global.shared::cta.bulk_group [%0], [%1], %2;\n}" :: "l"(dst), "r"(src), "r"(bytes) : "memory");
}
__device__ __forceinline__ void e_ld3(uint32_t dst, const CUtensorMap* m, int c0, int c1, int c2, uint32_t bar) {
    asm volatile(ELECT "cp.async.bulk.tensor.3d.shared::cluster.global.mbarrier::complete_tx::bytes [%0], [%1, {%3, %4, %5}], [%2];\n}"
                 :: "r"(dst), "l"(m), "r"(bar), "r"(c0), "r"(c1), "r"(c2) : "memory");
}
__device__ __forceinline__ void e_ld4(uint32_t dst, const CUtensorMap* m, int c0, int c3, uint32_t bar) {
    asm volatile(ELECT "cp.async.bulk.tensor.4d.shared::cluster.global.mbarrier::complete_tx::bytes [%0], [%1, {%3, %5, %5, %4}], [%2];\n}"
                 :: "r"(dst), "l"(m), "r"(bar), "r"(c0), "r"(c3), "r"(0) : "memory");
}
__device__ __forceinline__ void e_st3(const CUtensorMap* m, uint32_t src, int c0, int c1, int c2) {
    asm volatile(ELECT "cp.async.bulk.tensor.3d.global.shared::cta.bulk_group [%0, {%2, %3, %4}], [%1];\n}" :: "l"(m), "r"(src), "r"(c0), "r"(c1), "r"(c2) : "memory");
}
__device__ __forceinline__ void e_ld5(uint32_t dst, const CUtensorMap* m, int c4, uint32_t bar) {
    asm volatile(ELECT "cp.async.bulk.tensor.5d.shared::cluster.global.mbarrier::complete_tx::bytes [%0], [%1, {%4, %4, %4, %4, %3}], [%2];\n}"
                 :: "r"(dst), "l"(m), "r"(bar), "r"(c4), "r"(0) : "memory");
}
__device__ __forceinline__ void e_st5(const CUtensorMap* m, uint32_t src, int c4) {
    asm volatile(ELECT "cp.async.bulk.tensor.5d.global.shared::cta.bulk_group [%0, {%3, %3, %3, %3, %2}], [%1];\n}" :: "l"(m), "r"(src), "r"(c4), "r"(0) : "memory");
}
__device__ __forceinline__ void bulk_commit() { asm volatile("cp.async.bulk.commit_group;" ::: "memory"); }
template <int N> __device__ __forceinline__ void bulk_wait() { asm volatile("cp.async.bulk.wait_group %0;" :: "n"(N) : "memory"); }
template <int N> __device__ __forceinline__ void bulk_wait_read() { asm volatile("cp.async.bulk.wait_group.read %0;" :: "n"(N) : "memory"); }
__device__ __forceinline__ void wg_bar(int id) { asm volatile("bar.sync %0, 128;" :: "r"(id) : "memory"); }
__device__ __forceinline__ void bb_break(uint32_t v) { asm volatile("{\n.reg .pred p;\nsetp.eq.u32 p, %0, 0x7fc17fc1;\n@p nanosleep.u32 0;\n}" :: "r"(v) : "memory"); }
__device__ __forceinline__ uint32_t uni(uint32_t v) { return __shfl_sync(0xffffffffu, v, 0); }
__device__ __forceinline__ char* cls_cnt(char* scr, int cls) { return scr + slot_line(3, 2, cls) * 128; }
__device__ __forceinline__ uint32_t cnt_wait(const void* p, unsigned target) {
    uint32_t v = 0;
#pragma unroll 1
    for (unsigned it = 0; it < (1u << 22) && v < target; it++) {
        asm volatile("ld.acquire.gpu.global.u32 %0, [%1];" : "=r"(v) : "l"(p) : "memory");
        v = uni(v);
    }
    asm volatile("fence.proxy.async.global;" ::: "memory");
    return v;
}
__device__ __forceinline__ void wg_fence() { asm volatile("wgmma.fence.sync.aligned;" ::: "memory"); }
__device__ __forceinline__ void wg_commit() { asm volatile("wgmma.commit_group.sync.aligned;" ::: "memory"); }
template <int N> __device__ __forceinline__ void wg_wait() { asm volatile("wgmma.wait_group.sync.aligned %0;" :: "n"(N) : "memory"); }
template <int N> __device__ __forceinline__ void reg_fence(float (&d)[N]) {
#pragma unroll
    for (int i = 0; i < N; i++) asm volatile("" : "+f"(d[i]) :: "memory");
}
template <int N> __device__ __forceinline__ void zero(float (&d)[N]) {
#pragma unroll
    for (int i = 0; i < N; i++) d[i] = 0.f;
}
__device__ __forceinline__ uint32_t pack2(float lo, float hi) {
    uint32_t r; asm volatile("cvt.rn.bf16x2.f32 %0, %1, %2;" : "=r"(r) : "f"(hi), "f"(lo)); return r;
}
__device__ __forceinline__ void stm4(uint32_t a, uint32_t r0, uint32_t r1, uint32_t r2, uint32_t r3) {
    asm volatile("stmatrix.sync.aligned.m8n8.x4.trans.shared.b16 [%0], {%1,%2,%3,%4};" :: "r"(a), "r"(r0), "r"(r1), "r"(r2), "r"(r3) : "memory");
}
__device__ __forceinline__ void stm2(uint32_t a, uint32_t r0, uint32_t r1) {
    asm volatile("stmatrix.sync.aligned.m8n8.x2.trans.shared.b16 [%0], {%1,%2};" :: "r"(a), "r"(r0), "r"(r1) : "memory");
}
struct Desc {
    uint32_t lo, hi;
    __device__ __forceinline__ operator uint64_t() const { return ((uint64_t)hi << 32) | lo; }
    __device__ __forceinline__ Desc operator+(uint32_t o) const { return Desc{lo + o, hi}; }
    __device__ __forceinline__ Desc operator^(uint32_t o) const { return Desc{lo ^ o, hi}; }
};
__device__ __forceinline__ Desc mkdesc(uint32_t addr, uint32_t lbo, uint32_t sbo, uint32_t swz) {
    return Desc{((addr & 0x3FFFF) >> 4) | ((lbo >> 4) << 16), (sbo >> 4) | (swz << 30)};
}
__device__ __forceinline__ uint32_t cos_bits(int k) {
    if (k > 20) k = 40 - k;
    const bool neg = k > 10;
    if (neg) k = 20 - k;
    const unsigned long long pk = k < 4 ? COS_PK0 : k < 8 ? COS_PK1 : COS_PK2;
    return (uint32_t)((pk >> (16 * (k & 3))) & 0xffff) ^ (neg ? 0x8000u : 0u);
}

__device__ __forceinline__ void task_w(int wg, int k, uint32_t sb) {
    const int tid = threadIdx.x & 127, w = uni(tid >> 5), lane = tid & 31, q = lane & 3;
    const int tb = 14 * k, t1 = min(tb + 14, 1800), cb0 = tb / 25;
    float acc[64];
    zero(acc);
    const int oc0 = tb - 25 * cb0, Lt = t1 - tb, L0 = min(Lt, 25 - oc0), n0 = (L0 + 3) >> 2;
    uint32_t a[2][4][4];
    auto gen = [&](uint32_t (&a)[4][4], int at) {
        const int phi = 8 * ((at < n0 ? oc0 + 4 * at : 4 * (at - n0)) + w) + (lane >> 2), f = (phi * 205) >> 12;
        const uint32_t ca = 8 * f + 4, cw = (phi - 20 * f) * 8, p0 = sb + TBL + cw * 2 * q;
#pragma unroll
        for (int kh = 0; kh < 7; kh++) {
            uint32_t v0, v1;
            asm volatile("ld.shared.u32 %0, [%1];" : "=r"(v0) : "r"(p0 + ca * kh));
            asm volatile("ld.shared.u32 %0, [%1];" : "=r"(v1) : "r"(p0 + cw + ca * kh));
            const int h = kh == 6 ? 1 : kh & 1;
            a[kh >> 1][2 * h] = __byte_perm(v0, v1, 0x5410);
            a[kh >> 1][2 * h + 1] = __byte_perm(v0, v1, 0x7632);
        }
        a[3][0] = 0; a[3][1] = 0;
    };
    gen(a[0], wg);
    if (wg) gen(a[1], wg + 2);
#pragma unroll 1
    for (int n = 0; n < 2; n++) {
        const int at = wg + 2 * n, i0 = at < n0 ? 4 * at : L0 + 4 * (at - n0), cnt = (at < n0 ? L0 : Lt) - i0, cb = cb0 + (at >= n0);
        if (cnt <= 0 || (n && !wg)) break;
        if (n) {
#pragma unroll
            for (int j = 0; j < 16; j++) a[0][j >> 2][j & 3] = a[1][j >> 2][j & 3];
        }
        const Desc dB = mkdesc(sb + WP + (cb - cb0) * 14336, 3584, 512, 2);
        if (at) mbar_wait(sb + BARS + 8 * (B_WCH + at - 1));
        mbar_wait(sb + BARS + 8 * (B_WF + 2 * (cb - cb0)));
        wg_fence();
        wgmma_rs_n128_z(acc, a[0][0][0], a[0][0][1], a[0][0][2], a[0][0][3], dB);
        wgmma_rs_n128_a(acc, a[0][1][0], a[0][1][1], a[0][1][2], a[0][1][3], dB + (uint32_t)(16 * 64 >> 4));
        wgmma_rs_n128_a(acc, a[0][2][0], a[0][2][1], a[0][2][2], a[0][2][3], dB + (uint32_t)(32 * 64 >> 4));
        wgmma_rs_n128_a(acc, a[0][3][0], a[0][3][1], a[0][3][2], a[0][3][3], dB + (uint32_t)(40 * 64 >> 4));
        wg_commit();
        wg_wait<0>();
        reg_fence(acc);
        e_arrive(sb + BARS + 8 * (B_WCH + at));
        if (w < cnt) {
            const uint32_t dst = sb + wst_off(i0 + w) + (lane >> 2) * 512 + (lane & 4) * 16 + ((q ^ cb) & 3) * 16;
#pragma unroll
            for (int j = 0; j < 4; j++)
#pragma unroll
                for (int e = 0; e < 2; e++)
                    asm volatile("st.shared.v4.u32 [%0], {%1,%2,%3,%4};" :: "r"((dst ^ (e * 64)) + j * 128),
                                 "r"(pack2(acc[4 * j + e], acc[16 + 4 * j + e])), "r"(pack2(acc[4 * j + 2 + e], acc[16 + 4 * j + 2 + e])),
                                 "r"(pack2(acc[32 + 4 * j + e], acc[48 + 4 * j + e])), "r"(pack2(acc[32 + 4 * j + 2 + e], acc[48 + 4 * j + 2 + e])) : "memory");
            fence_async_smem();
            e_arrive(sb + BARS + 8 * (B_WRD + i0 + w));
        }
    }
}

__device__ __forceinline__ void task_p1(int wg, int pair, uint32_t sb) {
    const int tid = threadIdx.x & 127, w = tid >> 5, lane = tid & 31;
    const uint32_t buf = sb + wg * 51200, bars = sb + BARS;
    uint32_t fr[5][10][2];
    float A[40], d[20];
    zero(A);
    {
        const Desc dA = mkdesc(buf, 3584, 512, 2), dB = mkdesc(sb + C1, 128, 256, 0);
        auto issue = [&](int g, float (&d)[40]) {
            mbar_wait(bars + 8 * (B_XF + wg * 5 + g));
            wg_fence();
            wgmma_ss_n80_z(d, dA + (uint32_t)(g * 8704 >> 4), dB);
#pragma unroll
            for (int j = 1; j < 5; j++) wgmma_ss_n80_a(d, dA + (uint32_t)((g * 8704 + j * 1024) >> 4), dB + (uint32_t)(j * 2560 >> 4));
            wg_commit();
        };
        auto pack = [&](int g, float (&d)[40]) {
            reg_fence(d);
#pragma unroll
            for (int f = 0; f < 10; f++) {
                fr[g][f][0] = pack2(d[4 * f], d[4 * f + 1]);
                fr[g][f][1] = pack2(d[4 * f + 2], d[4 * f + 3]);
            }
        };
        mbar_wait(bars + 8 * B_CF1);
#pragma unroll
        for (int g = 0; g < 4; g++) { issue(g, A); wg_wait<0>(); pack(g, A); }
        zero(d);
        mbar_wait(bars + 8 * (B_XF + wg * 5 + 4));
#pragma unroll
        for (int h = 0; h < 2; h++) {
            wg_fence();
            wgmma_ss_n40_z(d, dA + (uint32_t)(4 * 8704 >> 4), dB + (uint32_t)(h * 1280 >> 4));
#pragma unroll
            for (int j = 1; j < 5; j++) wgmma_ss_n40_a(d, dA + (uint32_t)((4 * 8704 + j * 1024) >> 4), dB + (uint32_t)((j * 2560 + h * 1280) >> 4));
            wg_commit(); wg_wait<0>(); reg_fence(d);
#pragma unroll
            for (int f = 0; f < 5; f++) { fr[4][5 * h + f][0] = pack2(d[4 * f], d[4 * f + 1]); fr[4][5 * h + f][1] = pack2(d[4 * f + 2], d[4 * f + 3]); }
        }
    }
    bb_break(sb);
    wg_bar(1 + wg);
    {
        const Desc dB = mkdesc(sb + C1 + 12800, 128, 256, 0);
        const int i = lane & 7, mi = lane >> 3, th = w >> 1, tz = (2 * pair + th) & 3;
        const uint32_t s0 = buf + (i >> 1) * 128 + (i & 1) * 64 + (((2 * (w & 1) + (mi & 1)) ^ tz ^ (i >> 1)) << 4);
        const uint32_t sA = s0 + th * 2048 + (mi >> 1) * 512, sB = s0 + th * 2048 + (mi >> 1) * 2560, sC = s0 + th * 1024 + (mi >> 1) * 512;
        auto issue = [&](int f, float (&d)[20]) {
            wg_fence();
            wgmma_rs_n40_z(d, fr[0][f][0], fr[0][f][1], fr[1][f][0], fr[1][f][1], dB);
            wgmma_rs_n40_a(d, fr[2][f][0], fr[2][f][1], fr[3][f][0], fr[3][f][1], dB + (uint32_t)(1280 >> 4));
            wgmma_rs_n40_a(d, fr[4][f % 5][0], fr[4][f % 5][1], fr[4][f % 5 + 5][0], fr[4][f % 5 + 5][1], dB + (uint32_t)((2560 + (f / 5) * 1280) >> 4));
            wg_commit();
        };
#pragma unroll
        for (int f = 0; f < 10; f++) {
            issue(f, d);
            if (f && !(f & 1)) { fence_async_smem(); e_arrive(bars + 8 * (B_RDY + wg * 5 + (f >> 1) - 1)); }
            wg_wait<0>(); reg_fence(d);
            const int Q = 5 * f;
            stm4(((Q & 3) == 3 ? sB : sA) + quad_off(Q), pack2(d[0], d[1]), pack2(d[2], d[3]), pack2(d[4], d[5]), pack2(d[6], d[7]));
            stm2(sA + quad_off(Q + 2), pack2(d[8], d[9]), pack2(d[10], d[11]));
            stm4((f == 9 ? sC : ((Q + 3) & 3) == 3 ? sB : sA) + quad_off(Q + 3), pack2(d[12], d[13]), pack2(d[14], d[15]), pack2(d[16], d[17]), pack2(d[18], d[19]));
            if (f == 9) { fence_async_smem(); e_arrive(bars + 8 * (B_RDY + wg * 5 + (f >> 1))); }
        }
    }
}

__device__ __forceinline__ void task_p2(int wg, int rk, uint32_t sb) {
    const int tid = threadIdx.x & 127, w = tid >> 5, lane = tid & 31;
    const uint32_t bars = sb + BARS;
    const int phi0 = 3 * rk, phiE = extra_phi(rk), mE = extra_mask(rk);
    uint4 wA[6], wB[6], wC[6], wE[6];
    auto ldw = [&](uint4 (&a)[6], int j, int phi) {
        const int pc = 3 * j + wg;
        const uint32_t p = sb + wslot(pc) + (lane & 3) * 512 + w * 128 + (((lane >> 2) ^ phi) & 1) * 64 + (((lane >> 3) ^ lane) & 3) * 16 + (phi & 1) * 8;
        mbar_wait(bars + 8 * (B_WL + pc));
#pragma unroll
        for (int s = 0; s < 6; s++) {
            asm volatile("ld.shared.v2.u32 {%0, %1}, [%2];" : "=r"(a[s].x), "=r"(a[s].y) : "r"(p + s * 2048) : "memory");
            asm volatile("ld.shared.v2.u32 {%0, %1}, [%2];" : "=r"(a[s].z), "=r"(a[s].w) : "r"((p ^ 8) + s * 2048) : "memory");
        }
        uint32_t dep = 0;
#pragma unroll
        for (int s = 0; s < 6; s++) dep |= a[s].x ^ a[s].z;
        if (__any_sync(0xffffffffu, dep == 0x7fc17fc1u)) __nanosleep(0);
        e_arrive(bars + 8 * (B_WE + pc));
    };
    ldw(wA, 0, phi0); ldw(wB, 1, phi0 + 1);
    mbar_wait(bars + 8 * (B_SIG + SIG_P1 + 1));
    const int i = lane & 7, mi = lane >> 3;
    const uint32_t soff = sb + S1 + wg * 4096 + mi * 512 + (i >> 1) * 128 + (i & 1) * 64;
    const int xo = w ^ (i >> 1);
    float d[32];
    zero(d);
    int n = 0;
    uint32_t xb = ((sb + xslot(0)) & 0x3FFFF) >> 4 | 1u << 16, mb = bars + 8 * wg;
    bool landed = false;
    auto unit = [&](const uint4 (&a)[6], int z) {
        const Desc d0{xb + (z & 2), (512u >> 4) | (2u << 30)}, d1 = d0 ^ 2u;
        if (!landed) mbar_wait(bars + 8 * (B_RF + n));
        mbar_wait(mb + 8 * (B_TOK - 1));
        wg_fence();
        wgmma_rs_n64_z(d, a[0].x, a[0].y, a[0].z, a[0].w, d0);
        wgmma_rs_n64_a(d, a[1].x, a[1].y, a[1].z, a[1].w, d1);
        e_arrive(bars + 8 * (n ? B_RE + n - 1 : B_RE + 13));
        const bool sfree = mbar_test(n >= 4 ? mb + 8 * (B_SFREE - 12) : bars + 8 * (B_TOK - 1));
        landed = mbar_test(bars + 8 * (B_RF + n + 1));
        wgmma_rs_n64_a(d, a[2].x, a[2].y, a[2].z, a[2].w, d0 + (uint32_t)(4096 >> 4));
        wgmma_rs_n64_a(d, a[3].x, a[3].y, a[3].z, a[3].w, d1 + (uint32_t)(4096 >> 4));
        e_arrive(mb + 8 * B_TOK);
        wgmma_rs_n64_a(d, a[4].x, a[4].y, a[4].z, a[4].w, d0 + (uint32_t)(8192 >> 4));
        wgmma_rs_n64_a(d, a[5].x, a[5].y, a[5].z, a[5].w, d1 + (uint32_t)(8192 >> 4));
        wg_commit();
        if (!sfree) mbar_wait(mb + 8 * (B_SFREE - 12));
        const uint32_t a0 = soff + (n & 3) * 12288 + ((xo ^ z) << 4);
        n++;
        xb = ((sb + xslot(n)) & 0x3FFFF) >> 4 | 1u << 16;
        wg_wait<0>();
        reg_fence(d);
        uint32_t p[8];
#pragma unroll
        for (int j = 0; j < 8; j++) p[j] = pack2(d[4 * j] - d[4 * j + 3], d[4 * j + 2] + d[4 * j + 1]);
        stm4(a0, p[0], p[1], p[2], p[3]);
        stm4(a0 + 2048, p[4], p[5], p[6], p[7]);
        fence_async_smem();
        e_arrive(mb + 8 * (B_RDY + R_P2));
        mb += 24;
    };
    const int zA = phi0 & 3, zB = (phi0 + 1) & 3, zC = (phi0 + 2) & 3, zE = phiE & 3;
#pragma unroll 1
    for (int it = 0; it < 4; it++) {
        unit(wA, zA);
        unit(wB, zB);
        if (it == 0) ldw(wC, 2, phi0 + 2);
        unit(wC, zC);
        if (it == 0 && mE) ldw(wE, 3, phiE);
        if (mE >> it & 1) unit(wE, zE);
    }
}

__device__ __forceinline__ void task_p3(int wg, int pair, uint32_t sb) {
    const int tid = threadIdx.x & 127, w = tid >> 5, lane = tid & 31;
    const uint32_t buf = sb + (wg ? 3 - wg : 0) * 51200, bars = sb + BARS;
    uint32_t fr[10][4][2];
    float acc[2][16];
    zero(acc[0]); zero(acc[1]);
    {
        const Desc dB = mkdesc(sb + C3, 128, 256, 0);
        const uint32_t a0 = (buf & 0x3FFFF) >> 4;
        auto dq = [&](int Q) {
            return Desc{a0 + (uint32_t)((quad_off(Q) >> 4) | ((Q < 48 ? 2048 : 1024) >> 4) << 16), (uint32_t)((quad_off(Q + 1) - quad_off(Q)) >> 4) | (2u << 30)};
        };
        auto issue = [&](int f) {
            if (!(f & 1)) mbar_wait(bars + 8 * (B_YF + wg * 5 + (f >> 1)));
            wg_fence();
            wgmma_ss_n32_z(acc[f & 1], dq(5 * f), dB);
            wgmma_ss_n32_a(acc[f & 1], dq(5 * f + 1), dB + (uint32_t)(1024 >> 4));
            wgmma_ss_n32_a(acc[f & 1], dq(5 * f + 3), dB + (uint32_t)(2048 >> 4));
            wg_commit();
        };
        mbar_wait(bars + 8 * B_CF3);
        issue(0);
#pragma unroll
        for (int f = 0; f < 10; f++) {
            if (f < 9) { issue(f + 1); wg_wait<1>(); } else wg_wait<0>();
            float (&d)[16] = acc[f & 1];
            reg_fence(d);
#pragma unroll
            for (int g = 0; g < 4; g++) { fr[f][g][0] = pack2(d[4 * g], d[4 * g + 1]); fr[f][g][1] = pack2(d[4 * g + 2], d[4 * g + 3]); }
        }
    }
    {
        const Desc dB = mkdesc(sb + C3 + 3072, 128, 256, 0);
        const int i = lane & 7, mi = lane >> 3, th = w >> 1, tz = (2 * pair + th) & 3;
        const int oct = (2 * (w & 1) + (mi & 1)) ^ tz;
        const uint32_t soff = buf + th * 3584 + (mi >> 1) * 512 + i * 64 + ((oct ^ (i >> 1)) << 4);
        auto mma = [&](int t, int s) {
            if (t > 6) return;
            const int g = t < 6 ? 1 + (t >> 1) : 0;
            const uint32_t o = t < 6 ? (t & 1) * 1024 : 8960, st = t < 6 ? 1792 : 1024;
            if (s == 0) { wg_fence(); wgmma_rs_n32_z(acc[t & 1], fr[0][g][0], fr[0][g][1], fr[1][g][0], fr[1][g][1], dB + (o >> 4)); }
            else wgmma_rs_n32_a(acc[t & 1], fr[2 * s][g][0], fr[2 * s][g][1], fr[2 * s + 1][g][0], fr[2 * s + 1][g][1], dB + ((o + s * st) >> 4));
            if (s == 4) wg_commit();
        };
        const int row = th * 14 + 4 * (mi >> 1) + (i >> 1);
        const uint32_t z0 = buf + row * 128 + (i & 1) * 64 + ((oct ^ (row & 3)) << 4), z1 = (lane & 20) == 20 ? buf + 4096 + lane * 16 : z0 + 1024;
        bb_break(sb);
#pragma unroll
        for (int s = 0; s < 5; s++) mma(0, s);
        wg_bar(1 + wg);
#pragma unroll
        for (int t = 0; t < 7; t++) {
#pragma unroll
            for (int s = 0; s < 2; s++) mma(t + 1, s);
            if (t < 6) { wg_commit(); wg_wait<1>(); } else wg_wait<0>();
            float (&d)[16] = acc[t & 1];
            reg_fence(d);
            const uint32_t a = soff + (1 + (t >> 1)) * 7168 + (t & 1) * 2048;
            stm4(t < 6 ? a : z0, pack2(d[0], d[1]), pack2(d[2], d[3]), pack2(d[4], d[5]), pack2(d[6], d[7]));
            mma(t + 1, 2);
            if (t & 1) stm2(a + 1024, pack2(d[8], d[9]), pack2(d[10], d[11]));
            else stm4(t < 6 ? a + 1024 : z1, pack2(d[8], d[9]), pack2(d[10], d[11]), pack2(d[12], d[13]), pack2(d[14], d[15]));
#pragma unroll
            for (int s = 3; s < 5; s++) mma(t + 1, s);
            if ((t & 1) || t == 6) { fence_async_smem(); e_arrive(bars + 8 * (B_RDY + R_P3 + wg * 4 + (t >> 1))); }
        }
    }
}

__device__ __forceinline__ void load_x(int cls, int rk, int u, uint32_t sb, const Maps& mp) {
    const int id = u * NH + rk, pl = id / 3, c0 = 32 * (id - 3 * pl), tp = cls * 4 + (pl >> 4), col = 14 * (pl & 15) - 8;
    const uint32_t bar = sb + BARS + 8 * (B_XF + u * 5), dst = sb + u * 51200;
    const int wrap = col < 0 ? 224 : 0;
    if (tp) {
#pragma unroll
        for (int g = 0; g < 5; g++) e_ld3(dst + g * 8704, &mp.x34, c0, col + 4 * g + (g < 2 ? wrap : 0), 28 * tp - 6, bar + 8 * g);
    } else {
#pragma unroll
        for (int g = 0; g < 5; g++) {
            e_ld3(dst + g * 8704, &mp.x6, c0, col + 4 * g + (g < 2 ? wrap : 0), 218, bar + 8 * g);
            e_ld3(dst + g * 8704 + 1536, &mp.x28, c0, col + 4 * g + (g < 2 ? wrap : 0), 0, bar + 8 * g);
        }
    }
}

__device__ __forceinline__ void load_x_box(int cls, int rk, int u, int g, uint32_t sb, const Maps& mp) {
    const int id = u * NH + rk, pl = id / 3, c0 = 32 * (id - 3 * pl), tp = cls * 4 + (pl >> 4), col = 14 * (pl & 15) - 8 + 4 * g;
    e_ld3(sb + u * 51200 + g * 8704, &mp.x34, c0, col < 0 ? col + 224 : col, 28 * tp - 6, sb + BARS + 8 * (B_XF + u * 5 + g));
}

__device__ __forceinline__ void load_first(uint32_t sb, const Maps& mp, const Ptrs& pt) {
    const uint32_t bars = sb + BARS;
    const int k = blockIdx.x;
    if (k < 129) {
        const int cb0 = 14 * k / 25, cb1 = min((14 * k + 13) / 25, 71);
#pragma unroll 1
        for (int cb = cb0; cb <= cb1; cb++) {
            const int b = cb / 24, i0 = 16 * ((cb >> 2) - 6 * b) + 2 * (cb & 3);
            const uint32_t bar = bars + 8 * (B_WF + 2 * (cb - cb0));
            e_expect(bar, 14336);
            e_ld4(sb + WP + (cb - cb0) * 14336, &mp.w, 32 * b, i0, bar);
            e_ld4(sb + WP + (cb - cb0) * 14336 + 7168, &mp.w, 32 * b, i0 + 8, bar);
        }
    }
    e_expect(bars + 8 * B_CF1, 17920); e_g2s(sb + C1, pt.tab1, 17920, bars + 8 * B_CF1);
    if ((threadIdx.x & 31) < 15) asm volatile("mbarrier.arrive.expect_tx.shared::cta.b64 _, [%0], 8704;" :: "r"(bars + 8 * (B_XF + (threadIdx.x & 31))) : "memory");
    __syncwarp();
}

__device__ __forceinline__ uint32_t get_rel(uint32_t sb) {
    mbar_wait(sb + BARS + 8 * B_REL);
    uint32_t v; asm volatile("ld.shared.u32 %0, [%1];" : "=r"(v) : "r"(sb + REL) : "memory");
    return uni(v);
}

__device__ __forceinline__ void load_warp(int cls, int rk, uint32_t sb, const Ptrs& pt) {
    const uint32_t bars = sb + BARS;
    mbar_wait(bars + 8 * (B_SIG + SIG_P1));
    const uint32_t rel = get_rel(sb);
    const char* cnt = cls_cnt(pt.scr, cls);
    const int mE = extra_mask(rk);
    const int lpA = phi_line(3 * rk, rel), lpB = phi_line(3 * rk + 1, rel), lpC = phi_line(3 * rk + 2, rel), lpE = phi_line(extra_phi(rk), rel);
    e_arrive(bars + 8 * (B_TOK - 1));
    if ((threadIdx.x & 31) < 14) asm volatile("mbarrier.arrive.expect_tx.shared::cta.b64 _, [%0], 12288;" :: "r"(bars + 8 * (B_RF + (threadIdx.x & 31))) : "memory");
    __syncwarp();
    int n = 0;
#pragma unroll 1
    for (int pg = 0; pg < 4; pg++) {
        const int l0 = slot_line(0, pg, cls), l1 = slot_line(1, pg, cls), l2 = slot_line(2, pg, cls);
        auto unit = [&](int lp) {
            const uint32_t bar = bars + 8 * (B_RF + n), dst = sb + xslot(n);
            mbar_wait(bars + 8 * (n >= 8 ? B_RE + n - 8 : n >= 4 ? B_SIG + SIG_P1 + (rk < 60 ? 2 : 1) : B_WE + ((0x4310 >> (4 * n)) & 15)));
            e_g2s(dst, pt.scr + (size_t)(lp ^ l0) * 128, 4096, bar);
            e_g2s(dst + 4096, pt.scr + (size_t)(lp ^ l1) * 128, 4096, bar);
            e_g2s(dst + 8192, pt.scr + (size_t)(lp ^ l2) * 128, 4096, bar);
            n++;
        };
        cnt_wait(cnt + (CNT_P1 + pg) * 128, 48);
        unit(lpA); unit(lpB); unit(lpC);
        if (mE >> pg & 1) unit(lpE);
        if (pg == 1) { mbar_wait(bars + 8 * B_P1D); e_expect(bars + 8 * B_CF3, 17152); e_g2s(sb + C3, pt.tab3, 17152, bars + 8 * B_CF3); }
    }
}

__device__ __forceinline__ int near_page(char* p, int rounds) {
#pragma unroll
    for (int e = 0; e < 4; e++) asm volatile("st.relaxed.gpu.global.v4.u32 [%0], {%1, %1, %1, %1};" :: "l"(p + (e >> 1) * 4096 + (e & 1) * 16), "r"(0) : "memory");
    int score = 0;
#pragma unroll 1
    for (int r = 0; r < rounds; r++) {
        uint32_t v0, v1, t0, t1;
        asm volatile("atom.relaxed.gpu.global.exch.b32 %0, [%1], 1;" : "=r"(v0) : "l"(p + (r & 1) * 4096) : "memory");
        asm volatile("atom.relaxed.gpu.global.exch.b32 %0, [%1], 1;" : "=r"(v1) : "l"(p + (~r & 1) * 4096) : "memory");
        asm volatile("{\n.reg .pred p;\nsetp.ne.u32 p, %1, 0xffffffff;\nmov.u32 %0, 0;\n@p mov.u32 %0, %%clock;\n}" : "=r"(t0) : "r"(v0) : "memory");
        asm volatile("{\n.reg .pred p;\nsetp.ne.u32 p, %1, 0xffffffff;\nmov.u32 %0, 0;\n@p mov.u32 %0, %%clock;\n}" : "=r"(t1) : "r"(v1) : "memory");
        const int gap = min((int)(t1 - t0), 160) - 80;
        score += (r & 1) ? gap : -gap;
    }
    return score > 0;
}

__device__ __forceinline__ uint32_t find_role(uint32_t sb, char* scr, const char* x) {
    const int k = blockIdx.x;
    int c = near_page(scr + (slot_line(3, 3, 0) + phi_line(1 + (k >> 5), 0) + (k & 31)) * 128, 1);
    int r;
    asm volatile("atom.relaxed.gpu.global.add.u32 %0, [%1], 1;" : "=r"(r) : "l"(cls_cnt(scr, c) + CNT_RANK * 128) : "memory");
    asm volatile("cp.async.bulk.prefetch.L2.global [%0], %1;" :: "l"(x + (size_t)c * 112 * 43008 + (size_t)(k % XPFN) * XPF), "r"(XPF) : "memory");
    asm volatile("st.shared.u32 [%0], %1;" :: "r"(sb + REL + 8), "r"(c) : "memory");
    if (r >= NH) { c ^= 1; r = NSM - 1 - r; }
    asm volatile("st.shared.u32 [%0], %1;" :: "r"(sb + REL + 4), "r"(c << 8 | r) : "memory");
    return c << 8 | r;
}
__device__ __forceinline__ void get_role(uint32_t sb, int& cls, int& rk) {
    mbar_wait(sb + BARS + 8 * B_ROLE);
    uint32_t v; asm volatile("ld.shared.u32 %0, [%1];" : "=r"(v) : "r"(sb + REL + 4) : "memory");
    v = uni(v); cls = v >> 8; rk = v & 255;
}

__device__ __forceinline__ void load3_warp(int cls, int rk, uint32_t sb, const Maps& mp, const Ptrs& pt) {
    const uint32_t bars = sb + BARS;
    mbar_wait(bars + 8 * B_XF);
    const uint32_t rel = cnt_wait(pt.cnt + CNT_REL * 32, 12u << 16);
    asm volatile("st.shared.u32 [%0], %1;" :: "r"(sb + REL), "r"(rel) : "memory");
    __syncwarp();
    e_arrive(bars + 8 * B_REL);
    mbar_wait(bars + 8 * (B_SIG + SIG_W));
    cnt_wait(cls_cnt(pt.scr, cls) + CNT_W * 128, NSM);
    {
        const int np = rk >= 58 ? 12 : 9;
#pragma unroll 1
        for (int o = 0; o < np; o++) {
            const int pc = (0xba9876524310ull >> (4 * o)) & 15;
            if (o == 4) mbar_wait(bars + 8 * (B_SIG + SIG_P1));
            if (o >= 8) mbar_wait(bars + 8 * (B_WE + ((0x5762 >> (4 * (o - 8))) & 15)));
            if (o >= 4) mbar_wait(bars + 8 * (B_WL + ((0xba9876524310ull >> (4 * (o - 4))) & 15)));
            e_expect(bars + 8 * (B_WL + pc), 12288);
            e_g2s(sb + wslot(pc), pt.wf + (pc < 9 ? 9 * rk + pc : 3 * extra_phi(rk) + pc - 9) * 12288, 12288, bars + 8 * (B_WL + pc));
        }
        if (np == 12) { mbar_wait(bars + 8 * (B_WE + 9)); mbar_wait(bars + 8 * (B_WE + 10)); mbar_wait(bars + 8 * (B_WE + 11)); }
    }
    mbar_wait(bars + 8 * (B_SIG + SIG_P2 + 1));
    const int nu = rk < 60 ? 3 : 2;
#pragma unroll 1
    for (int u = 0; u < nu; u++) {
        const int id = u * NH + rk, pl = id / 3, chunk = id - 3 * pl;
        const int l0 = slot_line(chunk, pl >> 4, cls) + (pl & 15) * 2;
        const uint32_t buf = sb + (u ? 3 - u : 0) * 51200, bar = bars + 8 * (B_YF + u * 5);
#pragma unroll
        for (int j = 0; j < 5; j++) e_expect(bar + 8 * j, j == 4 ? 10240 : (j & 1) ? 8192 : 12288);
        if (u) mbar_wait(bars + 8 * (B_SIG + SIG_P2 + 3));
        cnt_wait(cls_cnt(pt.scr, cls) + (CNT_P2 + (pl >> 4)) * 128, NH);
        if (u == nu - 1) e_arrive(bars + 8 * B_FIN);
        const uint32_t r2 = uni(rel) << 5;
#pragma unroll
        for (int G = 0; G < 13; G++)
            e_ld5(buf + G * 4096, G < 12 ? &mp.f16 : &mp.f8, (l0 ^ ((r2 >> G) & 32)) + (G << 14), bar + 8 * ((2 * G) / 5));
    }
}

__device__ __forceinline__ void store_warp(uint32_t sb, const Maps& mp, const Ptrs& pt) {
    const uint32_t bars = sb + BARS;
    const int k = blockIdx.x;
    uint32_t pa = 0, pb = 0, qa = 0, qb = 0;
    auto arr2 = [&](uint32_t& a, uint32_t& b) { if (a) e_arrive(a); if (b) e_arrive(b); a = b = 0; };
    auto pre = [&](int idx) {
        const uint32_t bar = bars + 8 * idx;
        if ((pb | qb) && !mbar_test(bar)) { bulk_wait<0>(); arr2(qa, qb); arr2(pa, pb); }
        mbar_wait(bar);
    };
    auto post = [&](uint32_t fr) {
        bulk_commit(); bulk_wait_read<2>();
        if (qb) bulk_wait<2>();
        arr2(qa, qb); qa = pa; qb = pb; pb = 0; pa = fr;
    };
    auto after = [&](int sig) { pb = bars + 8 * (B_SIG + sig); };
    int cls, rk; get_role(sb, cls, rk);
    {
        int cb = 14 * k / 25, oc = 14 * k - 25 * cb;
        int g1 = 0;
#pragma unroll 1
        for (int i = 0; i < 14 && cb < 72; i++) {
            pre(B_WRD + i);
            e_st3(&mp.wst, sb + wst_off(i), 0, 8 * oc, cb);
            post(0);
            if (T1MASK >> i & 1) load_x_box(cls, rk, 1, g1++, sb, mp);
            if (++oc == 25) { oc = 0; cb++; }
        }
#pragma unroll 1
        for (; g1 < 5; g1++) load_x_box(cls, rk, 1, g1, sb, mp);
        after(SIG_W);
    }
    pre(B_REL);
    const uint32_t rel = get_rel(sb);
    const int nu = rk < 60 ? 3 : 2;
    int g2 = 0;
#pragma unroll 1
    for (int u = 0; u < nu; u++) {
        const int id = u * NH + rk, pl = id / 3, chunk = id - 3 * pl;
        const int l0 = slot_line(chunk, pl >> 4, cls) + (pl & 15) * 2;
        int j = B_RDY + u * 5;
        const int m2 = nu == 3 ? (u == 0 ? T2MASK & 0x1fff : u == 1 ? T2MASK >> 13 : 0) : 0;
#pragma unroll 1
        for (int G = 0; G < 13; G++) {
            if (0x4a5 >> G & 1) pre(j++);
            e_st5(G < 12 ? &mp.f16 : &mp.f8, sb + u * 51200 + G * 4096, (l0 ^ ((rel >> G) & 1) << 5) + (G << 14));
            post(0);
            if (m2 >> G & 1) load_x_box(cls, rk, 2, g2++, sb, mp);
        }
        after(SIG_P1 + u);
    }
    const int mE = extra_mask(rk);
    int n = 0;
#pragma unroll 1
    for (int pg = 0; pg < 4; pg++) {
        const int nj = 3 + (mE >> pg & 1);
        const int l0 = slot_line(0, pg, cls), l1 = slot_line(1, pg, cls), l2 = slot_line(2, pg, cls);
#pragma unroll 1
        for (int j = 0; j < nj; j++) {
            const int lp = phi_line(j == 3 ? extra_phi(rk) : 3 * rk + j, rel);
#pragma unroll
            for (int b = 0; b < 3; b++) {
                pre(B_RDY + R_P2 + n * 3 + b);
                e_s2g(pt.scr + (size_t)(lp ^ (b == 0 ? l0 : b == 1 ? l1 : l2)) * 128, sb + S1 + (n & 3) * 12288 + b * 4096, 4096);
                post(bars + 8 * (B_SFREE + n * 3 + b));
            }
            n++;
        }
        after(SIG_P2 + pg);
    }
#pragma unroll 1
    for (int u = 0; u < nu; u++) {
        const int id = u * NH + rk, pl = id / 3, chunk = id - 3 * pl, tp = cls * 4 + (pl >> 4), tx = pl & 15;
        const uint32_t buf = sb + (u ? 3 - u : 0) * 51200;
#pragma unroll
        for (int gg = 1; gg < 5; gg++) {
            pre(B_RDY + R_P3 + u * 4 + gg - 1);
            if (gg < 4) e_st3(&mp.y4, buf + gg * 7168, 32 * chunk, 14 * tx - 4 + 4 * gg, 28 * tp);
            else e_st3(&mp.y2, buf, 32 * chunk, tx == 0 ? 222 : 14 * tx - 2, 28 * tp);
            post(0);
        }
    }
    bulk_wait_read<0>();
}

__device__ __forceinline__ void signal_warp(int cls, int rk, uint32_t sb, const Ptrs& pt) {
    const uint32_t bars = sb + BARS;
    char* cnt = cls_cnt(pt.scr, cls);
    if (threadIdx.x & 31) return;
#pragma unroll 1
    for (int c = 0; c < 8; c++) {
        if (c == SIG_P1 + 2 && rk >= 60) continue;
        char* ctr = cnt + (c == SIG_W ? CNT_W : c < SIG_P2 ? CNT_P1 + ((c - SIG_P1) * NH + rk) / 48 : CNT_P2 + c - SIG_P2) * 128;
        mbar_wait(bars + 8 * (B_SIG + c));
        fence_async();
        asm volatile("red.relaxed.gpu.global.add.u32 [%0], 1;" :: "l"(ctr) : "memory");
        if (c == SIG_W) asm volatile("red.relaxed.gpu.global.add.u32 [%0], 1;" :: "l"((uintptr_t)ctr ^ 4096) : "memory");
    }
    mbar_wait(bars + 8 * B_FIN);
    unsigned old;
    asm volatile("atom.add.relaxed.gpu.global.u32 %0, [%1], 1;" : "=r"(old) : "l"(pt.cnt + CNT_DONE * 32) : "memory");
    if (old == NSM - 1) {
#pragma unroll
        for (int c = 0; c < NCNT; c++) pt.cnt[c * 32] = 0;
#pragma unroll 1
        for (int c = 0; c < NCLS; c++) { *reinterpret_cast<unsigned*>(cnt + c * 128) = 0; *reinterpret_cast<unsigned*>(((uintptr_t)cnt ^ 4096) + c * 128) = 0; }
    }
}

__global__ void __launch_bounds__(512, 1) fftconv_kernel(const Ptrs pt, const __grid_constant__ Maps mp) {
    extern __shared__ __align__(1024) uint8_t smem[];
    const uint32_t sb = smem_u32(smem);
    const int tid = threadIdx.x, warp = uni(tid >> 5), wg = warp >> 2;
    int cls, rk;
    auto bar_init = [&](int i) {
        uint32_t c = 1;
        if (i == B_P1D || (i >= B_RE && i < B_RE + 14)) c = 12;
        else if ((i >= B_WCH && i < B_WL) || i >= B_TOK) c = 4;
        asm volatile("st.shared.v2.u32 [%0], {%1, %2};" :: "r"(sb + BARS + 8 * i), "r"((0x100000u - c) << 1), "r"((0x100000u - c) << 11) : "memory");
        fence_async_smem();
    };
    if (wg == 3) {
        asm volatile("setmaxnreg.dec.sync.aligned.u32 32;");
        if (warp == 12) {
            bar_init(tid & 31);
            __syncwarp();
            asm volatile("bar.arrive 4, 416;" ::: "memory");
            load_first(sb, mp, pt);
            asm volatile("bar.sync 5, 416;" ::: "memory");
            get_role(sb, cls, rk);
            load_warp(cls, rk, sb, pt);
        } else if (warp == 13) {
            if ((tid & 31) < 8) asm volatile("prefetch.tensormap [%0];" :: "l"(reinterpret_cast<const CUtensorMap*>(&mp) + 1 + (tid & 31)) : "memory");
            __syncwarp();
            asm volatile("bar.sync 6, 416;" ::: "memory");
            store_warp(sb, mp, pt);
        } else if (warp == 14) {
            const int G = blockIdx.x - 119;
            int sel = 0;
            if (G >= 1 && (tid & 31) == 0) sel = near_page(pt.scr + ((size_t)G << 21) + slot_line(3, 3, 0) * 128, 2);
            __syncwarp();
            asm volatile("bar.sync 7, 416;" ::: "memory");
            get_role(sb, cls, rk);
            if (G >= 1 && (tid & 31) == 0) {
                uint32_t c; asm volatile("ld.shared.u32 %0, [%1];" : "=r"(c) : "r"(sb + REL + 8) : "memory");
                asm volatile("red.relaxed.gpu.global.add.u32 [%0], %1;" :: "l"(pt.cnt + CNT_REL * 32), "r"(0x10000u | (sel ^ c) << G) : "memory");
            }
            __syncwarp();
            load3_warp(cls, rk, sb, mp, pt);
        } else {
            uint32_t role = 0;
            if ((tid & 31) == 0) role = find_role(sb, pt.scr, pt.x);
            role = uni(role); cls = role >> 8; rk = role & 255;
            asm volatile("bar.sync 8, 416;" ::: "memory");
            load_x(cls, rk, 0, sb, mp);
            e_arrive(sb + BARS + 8 * B_ROLE);
            signal_warp(cls, rk, sb, pt);
        }
    } else {
        if (tid >= 32 && tid < NBAR) bar_init(tid);
        {
            const int r = tid % 40;
            asm volatile("st.shared.u32 [%0], %1;" :: "r"(sb + TBL + 4 * tid), "r"(cos_bits(r) | (cos_bits(r < 30 ? r + 10 : r - 30) << 16)) : "memory");
        }
        __syncwarp();
        asm volatile("bar.sync 4, 416;" ::: "memory");
        asm volatile("bar.arrive 5, 416;" ::: "memory");
        asm volatile("bar.arrive 6, 416;" ::: "memory");
        asm volatile("bar.arrive 7, 416;" ::: "memory");
        asm volatile("bar.arrive 8, 416;" ::: "memory");
        task_w(wg, blockIdx.x, sb);
        asm volatile("setmaxnreg.inc.sync.aligned.u32 160;");
        get_role(sb, cls, rk);
        const int id = wg * NH + rk;
        if (id < 192) task_p1(wg, id / 3, sb);
        e_arrive(sb + BARS + 8 * B_P1D);
        task_p2(wg, rk, sb);
        if (id < 192) task_p3(wg, id / 3, sb);
    }
}

__global__ void fallback_kernel(const __nv_bfloat16* x, const __nv_bfloat16* w, __nv_bfloat16* y) {
    const int px = blockIdx.x, o = threadIdx.x, h = px / 224, c = px % 224;
    float acc = 0.f;
    for (int kh = 0; kh < 7; kh++)
        for (int kw = 0; kw < 7; kw++) {
            const __nv_bfloat16* xp = x + (((h - kh + 224) % 224) * 224 + (c - kw + 224) % 224) * 96;
            const __nv_bfloat16* wp = w + (kh * 7 + kw) * 9216 + o;
            for (int i = 0; i < 96; i++) acc += __bfloat162float(xp[i]) * __bfloat162float(wp[i * 96]);
        }
    y[px * 96 + o] = __float2bfloat16(acc);
}

typedef CUresult (*EncodeFn)(CUtensorMap*, CUtensorMapDataType, cuuint32_t, void*, const cuuint64_t*, const cuuint64_t*, const cuuint32_t*, const cuuint32_t*,
                             CUtensorMapInterleave, CUtensorMapSwizzle, CUtensorMapL2promotion, CUtensorMapFloatOOBfill);

static void encode3(EncodeFn fn, CUtensorMap* m, void* ptr, uint64_t d0, uint64_t d1, uint64_t d2, uint64_t s1, uint64_t s2,
                    uint32_t b0, uint32_t b1, uint32_t b2, CUtensorMapSwizzle sw) {
    cuuint64_t dims[3] = {d0, d1, d2}, strides[2] = {s1, s2};
    cuuint32_t box[3] = {b0, b1, b2}, es[3] = {1, 1, 1};
    fn(m, CU_TENSOR_MAP_DATA_TYPE_BFLOAT16, 3, ptr, dims, strides, box, es, CU_TENSOR_MAP_INTERLEAVE_NONE, sw,
       CU_TENSOR_MAP_L2_PROMOTION_NONE, CU_TENSOR_MAP_FLOAT_OOB_FILL_NONE);
}

extern "C" void kernel_launch(void* const* d_in, const int* in_sizes, int n_in, void* d_out, int out_size) {
    (void)in_sizes; (void)n_in; (void)out_size;
    int dev = 0, nsm = 0;
    cudaGetDevice(&dev);
    cudaDeviceGetAttribute(&nsm, cudaDevAttrMultiProcessorCount, dev);
    if (nsm < NSM) {
        fallback_kernel<<<224 * 224, 96>>>((const __nv_bfloat16*)d_in[0], (const __nv_bfloat16*)d_in[1], (__nv_bfloat16*)d_out);
        return;
    }
    void* fnp = nullptr; cudaDriverEntryPointQueryResult qr;
    cudaGetDriverEntryPoint("cuTensorMapEncodeTiled", &fnp, cudaEnableDefault, &qr);
    EncodeFn fn = (EncodeFn)fnp;
    void* xf = nullptr; cudaGetSymbolAddress(&xf, g_scr);
    xf = (void*)(((uintptr_t)xf + (1u << 21) - 1) & ~(uintptr_t)((1u << 21) - 1));
    void* wf = nullptr; cudaGetSymbolAddress(&wf, g_wf);
    Maps mp;
    Ptrs pt;
    pt.scr = (char*)xf; pt.wf = (const char*)wf; pt.x = (const char*)d_in[0];
    void* p = nullptr;
    cudaGetSymbolAddress(&p, TAB_P1); pt.tab1 = p;
    cudaGetSymbolAddress(&p, TAB_P3); pt.tab3 = p;
    cudaGetSymbolAddress(&p, g_cnt); pt.cnt = (unsigned*)p;
    {
        cuuint32_t b16[5] = {64, 4, 2, 2, 2}, b8[5] = {64, 4, 2, 1, 2}, es[5] = {1, 1, 1, 1, 1};
        cuuint64_t d[5] = {64, 4, 2, 2, 13 << 14}, st[4] = {16384, 262144, 1048576, 128};
        fn(&mp.f16, CU_TENSOR_MAP_DATA_TYPE_BFLOAT16, 5, xf, d, st, b16, es, CU_TENSOR_MAP_INTERLEAVE_NONE, CU_TENSOR_MAP_SWIZZLE_NONE, CU_TENSOR_MAP_L2_PROMOTION_NONE, CU_TENSOR_MAP_FLOAT_OOB_FILL_NONE);
        fn(&mp.f8, CU_TENSOR_MAP_DATA_TYPE_BFLOAT16, 5, xf, d, st, b8, es, CU_TENSOR_MAP_INTERLEAVE_NONE, CU_TENSOR_MAP_SWIZZLE_NONE, CU_TENSOR_MAP_L2_PROMOTION_NONE, CU_TENSOR_MAP_FLOAT_OOB_FILL_NONE);
    }
    encode3(fn, &mp.x6, d_in[0], 96, 224, 224, 192, 224 * 192, 32, 4, 6, CU_TENSOR_MAP_SWIZZLE_64B);
    encode3(fn, &mp.x34, d_in[0], 96, 224, 224, 192, 224 * 192, 32, 4, 34, CU_TENSOR_MAP_SWIZZLE_64B);
    encode3(fn, &mp.x28, d_in[0], 96, 224, 224, 192, 224 * 192, 32, 4, 28, CU_TENSOR_MAP_SWIZZLE_64B);
    {
        cuuint32_t box[4] = {32, 8, 7, 2}, es[4] = {1, 1, 1, 1};
        cuuint64_t d[4] = {96, 7, 7, 96}, st[3] = {18432, 7 * 18432, 192};
        fn(&mp.w, CU_TENSOR_MAP_DATA_TYPE_BFLOAT16, 4, d_in[1], d, st, box, es, CU_TENSOR_MAP_INTERLEAVE_NONE, CU_TENSOR_MAP_SWIZZLE_64B, CU_TENSOR_MAP_L2_PROMOTION_NONE, CU_TENSOR_MAP_FLOAT_OOB_FILL_NONE);
    }
    encode3(fn, &mp.wst, wf, 256, 200, 72, 36864, 512, 256, 8, 1, CU_TENSOR_MAP_SWIZZLE_NONE);
    encode3(fn, &mp.y4, d_out, 96, 224, 224, 192, 224 * 192, 32, 4, 28, CU_TENSOR_MAP_SWIZZLE_64B);
    encode3(fn, &mp.y2, d_out, 96, 224, 224, 192, 224 * 192, 32, 2, 28, CU_TENSOR_MAP_SWIZZLE_64B);
    constexpr int SMEM_LAUNCH = SMEM_BYTES;
    cudaFuncSetAttribute(fftconv_kernel, cudaFuncAttributeMaxDynamicSharedMemorySize, SMEM_LAUNCH);
    fftconv_kernel<<<NSM, 512, SMEM_LAUNCH>>>(pt, mp);
}
```

```cpp
#include <cuda_runtime.h>
#include <cuda_bf16.h>
#include <cuda.h>
#include <stdint.h>

__device__ __align__(128) const uint32_t TAB_P1[4480] = {
0x3e75,0,0x3e72,0,0x8000,0,0xbd19,0,0x3e750000,0,0x3e720000,0,0x80000000,0,0xbd190000,0,
0,0x3e75,0,0x3e72,0,0x8000,0,0xbd19,0,0x3e750000,0,0x3e720000,0,0x80000000,0,0xbd190000,
0x3e69,0,0x3e5a,0,0xbd97,0,0xbdde,0,0x3e690000,0,0x3e5a0000,0,0xbd970000,0,0xbdde0000,0,
0,0x3e69,0,0x3e5a,0,0xbd97,0,0xbdde,0,0x3e690000,0,0x3e5a0000,0,0xbd970000,0,0xbdde0000,
0x3e75,0,0x3e5a,0,0x8000,0,0xbdde,0,0x3e750000,0,0x3e5a0000,0,0x80000000,0,0xbdde0000,0,
0,0x3e75,0,0x3e5a,0,0x8000,0,0xbdde,0,0x3e750000,0,0x3e5a0000,0,0x80000000,0,0xbdde0000,
0x3e10,0,0x3d19,0,0xbe46,0,0xbe72,0,0x3e100000,0,0x3d190000,0,0xbe460000,0,0xbe720000,0,
0,0x3e10,0,0x3d19,0,0xbe46,0,0xbe72,0,0x3e100000,0,0x3d190000,0,0xbe460000,0,0xbe720000,
0x3e75,0,0x3e2d,0,0x8000,0,0xbe2d,0,0x3e750000,0,0x3e2d0000,0,0x80000000,0,0xbe2d0000,0,
0,0x3e75,0,0x3e2d,0,0x8000,0,0xbe2d,0,0x3e750000,0,0x3e2d0000,0,0x80000000,0,0xbe2d0000,
0,0,0xbe2d,0,0xbe75,0,0xbe2d,0,0,0,0xbe2d0000,0,0xbe750000,0,0xbe2d0000,0,
0,0,0,0xbe2d,0,0xbe75,0,0xbe2d,0,0,0,0xbe2d0000,0,0xbe750000,0,0xbe2d0000,
0x3e75,0,0x3dde,0,0x8000,0,0xbe5a,0,0x3e750000,0,0x3dde0000,0,0x80000000,0,0xbe5a0000,0,
0,0x3e75,0,0x3dde,0,0x8000,0,0xbe5a,0,0x3e750000,0,0x3dde0000,0,0x80000000,0,0xbe5a0000,
0xbe10,0,0xbe72,0,0xbe46,0,0x3d19,0,0xbe100000,0,0xbe720000,0,0xbe460000,0,0x3d190000,0,
0,0xbe10,0,0xbe72,0,0xbe46,0,0x3d19,0,0xbe100000,0,0xbe720000,0,0xbe460000,0,0x3d190000,
0x3e75,0,0x3d19,0,0x8000,0,0xbe72,0,0x3e750000,0,0x3d190000,0,0x80000000,0,0xbe720000,0,
0,0x3e75,0,0x3d19,0,0x8000,0,0xbe72,0,0x3e750000,0,0x3d190000,0,0x80000000,0,0xbe720000,
0xbe69,0,0xbdde,0,0xbd97,0,0x3e5a,0,0xbe690000,0,0xbdde0000,0,0xbd970000,0,0x3e5a0000,0,
0,0xbe69,0,0xbdde,0,0xbd97,0,0x3e5a,0,0xbe690000,0,0xbdde0000,0,0xbd970000,0,0x3e5a0000,
0x3e75,0,0xbd19,0,0x8000,0,0xbe72,0,0x3e750000,0,0xbd190000,0,0x80000000,0,0xbe720000,0,
0,0x3e75,0,0xbd19,0,0x8000,0,0xbe72,0,0x3e750000,0,0xbd190000,0,0x80000000,0,0xbe720000,
0xbe69,0,0x3dde,0,0x3d97,0,0x3e5a,0,0xbe690000,0,0x3dde0000,0,0x3d970000,0,0x3e5a0000,0,
0,0xbe69,0,0x3dde,0,0x3d97,0,0x3e5a,0,0xbe690000,0,0x3dde0000,0,0x3d970000,0,0x3e5a0000,
0x3e75,0,0xbdde,0,0x8000,0,0xbe5a,0,0x3e750000,0,0xbdde0000,0,0x80000000,0,0xbe5a0000,0,
0,0x3e75,0,0xbdde,0,0x8000,0,0xbe5a,0,0x3e750000,0,0xbdde0000,0,0x80000000,0,0xbe5a0000,
0xbe10,0,0x3e72,0,0x3e46,0,0x3d19,0,0xbe100000,0,0x3e720000,0,0x3e460000,0,0x3d190000,0,
0,0xbe10,0,0x3e72,0,0x3e46,0,0x3d19,0,0xbe100000,0,0x3e720000,0,0x3e460000,0,0x3d190000,
0x3e75,0,0xbe2d,0,0x8000,0,0xbe2d,0,0x3e750000,0,0xbe2d0000,0,0x80000000,0,0xbe2d0000,0,
0,0x3e75,0,0xbe2d,0,0x8000,0,0xbe2d,0,0x3e750000,0,0xbe2d0000,0,0x80000000,0,0xbe2d0000,
0,0,0x3e2d,0,0x3e75,0,0xbe2d,0,0,0,0x3e2d0000,0,0x3e750000,0,0xbe2d0000,0,
0,0,0,0x3e2d,0,0x3e75,0,0xbe2d,0,0,0,0x3e2d0000,0,0x3e750000,0,0xbe2d0000,
0x3e75,0,0xbe5a,0,0x8000,0,0xbdde,0,0x3e750000,0,0xbe5a0000,0,0x80000000,0,0xbdde0000,0,
0,0x3e75,0,0xbe5a,0,0x8000,0,0xbdde,0,0x3e750000,0,0xbe5a0000,0,0x80000000,0,0xbdde0000,
0x3e10,0,0xbd19,0,0x3e46,0,0xbe72,0,0x3e100000,0,0xbd190000,0,0x3e460000,0,0xbe720000,0,
0,0x3e10,0,0xbd19,0,0x3e46,0,0xbe72,0,0x3e100000,0,0xbd190000,0,0x3e460000,0,0xbe720000,
0x3e75,0,0xbe72,0,0x8000,0,0xbd19,0,0x3e750000,0,0xbe720000,0,0x80000000,0,0xbd190000,0,
0,0x3e75,0,0xbe72,0,0x8000,0,0xbd19,0,0x3e750000,0,0xbe720000,0,0x80000000,0,0xbd190000,
0x3e69,0,0xbe5a,0,0x3d97,0,0xbdde,0,0x3e690000,0,0xbe5a0000,0,0x3d970000,0,0xbdde0000,0,
0,0x3e69,0,0xbe5a,0,0x3d97,0,0xbdde,0,0x3e690000,0,0xbe5a0000,0,0x3d970000,0,0xbdde0000,
0x3e46,0,0x3e2d,0,0xbe10,0,0xbe2d,0,0x3e460000,0,0x3e2d0000,0,0xbe100000,0,0xbe2d0000,0,
0,0x3e46,0,0x3e2d,0,0xbe10,0,0xbe2d,0,0x3e460000,0,0x3e2d0000,0,0xbe100000,0,0xbe2d0000,
0x3e10,0,0x3dde,0,0xbe46,0,0xbe5a,0,0x3e100000,0,0x3dde0000,0,0xbe460000,0,0xbe5a0000,0,
0,0x3e10,0,0x3dde,0,0xbe46,0,0xbe5a,0,0x3e100000,0,0x3dde0000,0,0xbe460000,0,0xbe5a0000,
0xbd97,0,0xbe2d,0,0xbe69,0,0xbe2d,0,0xbd970000,0,0xbe2d0000,0,0xbe690000,0,0xbe2d0000,0,
0,0xbd97,0,0xbe2d,0,0xbe69,0,0xbe2d,0,0xbd970000,0,0xbe2d0000,0,0xbe690000,0,0xbe2d0000,
0xbe69,0,0xbe72,0,0xbd97,0,0x3d19,0,0xbe690000,0,0xbe720000,0,0xbd970000,0,0x3d190000,0,
0,0xbe69,0,0xbe72,0,0xbd97,0,0x3d19,0,0xbe690000,0,0xbe720000,0,0xbd970000,0,0x3d190000,
0xbe75,0,0xbe2d,0,0x8000,0,0x3e2d,0,0xbe750000,0,0xbe2d0000,0,0x80000000,0,0x3e2d0000,0,
0,0xbe75,0,0xbe2d,0,0x8000,0,0x3e2d,0,0xbe750000,0,0xbe2d0000,0,0x80000000,0,0x3e2d0000,
0,0,0x3e2d,0,0x3e75,0,0x3e2d,0,0,0,0x3e2d0000,0,0x3e750000,0,0x3e2d0000,0,
0,0,0,0x3e2d,0,0x3e75,0,0x3e2d,0,0,0,0x3e2d0000,0,0x3e750000,0,0x3e2d0000,
0xbd97,0,0x3e2d,0,0x3e69,0,0x3e2d,0,0xbd970000,0,0x3e2d0000,0,0x3e690000,0,0x3e2d0000,0,
0,0xbd97,0,0x3e2d,0,0x3e69,0,0x3e2d,0,0xbd970000,0,0x3e2d0000,0,0x3e690000,0,0x3e2d0000,
0x3e69,0,0x3d19,0,0xbd97,0,0xbe72,0,0x3e690000,0,0x3d190000,0,0xbd970000,0,0xbe720000,0,
0,0x3e69,0,0x3d19,0,0xbd97,0,0xbe72,0,0x3e690000,0,0x3d190000,0,0xbd970000,0,0xbe720000,
0x3e46,0,0x3e2d,0,0x3e10,0,0xbe2d,0,0x3e460000,0,0x3e2d0000,0,0x3e100000,0,0xbe2d0000,0,
0,0x3e46,0,0x3e2d,0,0x3e10,0,0xbe2d,0,0x3e460000,0,0x3e2d0000,0,0x3e100000,0,0xbe2d0000,
0xbe10,0,0xbe5a,0,0xbe46,0,0x3dde,0,0xbe100000,0,0xbe5a0000,0,0xbe460000,0,0x3dde0000,0,
0,0xbe10,0,0xbe5a,0,0xbe46,0,0x3dde,0,0xbe100000,0,0xbe5a0000,0,0xbe460000,0,0x3dde0000,
0x3e46,0,0xbe2d,0,0xbe10,0,0xbe2d,0,0x3e460000,0,0xbe2d0000,0,0xbe100000,0,0xbe2d0000,0,
0,0x3e46,0,0xbe2d,0,0xbe10,0,0xbe2d,0,0x3e460000,0,0xbe2d0000,0,0xbe100000,0,0xbe2d0000,
0xbe10,0,0x3e5a,0,0x3e46,0,0x3dde,0,0xbe100000,0,0x3e5a0000,0,0x3e460000,0,0x3dde0000,0,
0,0xbe10,0,0x3e5a,0,0x3e46,0,0x3dde,0,0xbe100000,0,0x3e5a0000,0,0x3e460000,0,0x3dde0000,
0xbd97,0,0xbe2d,0,0xbe69,0,0x3e2d,0,0xbd970000,0,0xbe2d0000,0,0xbe690000,0,0x3e2d0000,0,
0,0xbd97,0,0xbe2d,0,0xbe69,0,0x3e2d,0,0xbd970000,0,0xbe2d0000,0,0xbe690000,0,0x3e2d0000,
0x3e69,0,0xbd19,0,0x3d97,0,0xbe72,0,0x3e690000,0,0xbd190000,0,0x3d970000,0,0xbe720000,0,
0,0x3e69,0,0xbd19,0,0x3d97,0,0xbe72,0,0x3e690000,0,0xbd190000,0,0x3d970000,0,0xbe720000,
0xbe75,0,0x3e2d,0,0x8000,0,0x3e2d,0,0xbe750000,0,0x3e2d0000,0,0x80000000,0,0x3e2d0000,0,
0,0xbe75,0,0x3e2d,0,0x8000,0,0x3e2d,0,0xbe750000,0,0x3e2d0000,0,0x80000000,0,0x3e2d0000,
0,0,0xbe2d,0,0xbe75,0,0x3e2d,0,0,0,0xbe2d0000,0,0xbe750000,0,0x3e2d0000,0,
0,0,0,0xbe2d,0,0xbe75,0,0x3e2d,0,0,0,0xbe2d0000,0,0xbe750000,0,0x3e2d0000,
0xbd97,0,0x3e2d,0,0x3e69,0,0xbe2d,0,0xbd970000,0,0x3e2d0000,0,0x3e690000,0,0xbe2d0000,0,
0,0xbd97,0,0x3e2d,0,0x3e69,0,0xbe2d,0,0xbd970000,0,0x3e2d0000,0,0x3e690000,0,0xbe2d0000,
0xbe69,0,0x3e72,0,0x3d97,0,0x3d19,0,0xbe690000,0,0x3e720000,0,0x3d970000,0,0x3d190000,0,
0,0xbe69,0,0x3e72,0,0x3d97,0,0x3d19,0,0xbe690000,0,0x3e720000,0,0x3d970000,0,0x3d190000,
0x3e46,0,0xbe2d,0,0x3e10,0,0xbe2d,0,0x3e460000,0,0xbe2d0000,0,0x3e100000,0,0xbe2d0000,0,
0,0x3e46,0,0xbe2d,0,0x3e10,0,0xbe2d,0,0x3e460000,0,0xbe2d0000,0,0x3e100000,0,0xbe2d0000,
0x3e10,0,0xbdde,0,0x3e46,0,0xbe5a,0,0x3e100000,0,0xbdde0000,0,0x3e460000,0,0xbe5a0000,0,
0,0x3e10,0,0xbdde,0,0x3e46,0,0xbe5a,0,0x3e100000,0,0xbdde0000,0,0x3e460000,0,0xbe5a0000,
0x3d97,0,0x3d19,0,0xbe69,0,0xbe72,0,0x3d970000,0,0x3d190000,0,0xbe690000,0,0xbe720000,0,
0,0x3d97,0,0x3d19,0,0xbe69,0,0xbe72,0,0x3d970000,0,0x3d190000,0,0xbe690000,0,0xbe720000,
0,0,0xbd19,0,0xbe75,0,0xbe72,0,0,0,0xbd190000,0,0xbe750000,0,0xbe720000,0,
0,0,0,0xbd19,0,0xbe75,0,0xbe72,0,0,0,0xbd190000,0,0xbe750000,0,0xbe720000,
0xbe46,0,0xbdde,0,0x3e10,0,0x3e5a,0,0xbe460000,0,0xbdde0000,0,0x3e100000,0,0x3e5a0000,0,
0,0xbe46,0,0xbdde,0,0x3e10,0,0x3e5a,0,0xbe460000,0,0xbdde0000,0,0x3e100000,0,0x3e5a0000,
0,0,0x3dde,0,0x3e75,0,0x3e5a,0,0,0,0x3dde0000,0,0x3e750000,0,0x3e5a0000,0,
0,0,0,0x3dde,0,0x3e75,0,0x3e5a,0,0,0,0x3dde0000,0,0x3e750000,0,0x3e5a0000,
0x3e75,0,0x3e2d,0,0x8000,0,0xbe2d,0,0x3e750000,0,0x3e2d0000,0,0x80000000,0,0xbe2d0000,0,
0,0x3e75,0,0x3e2d,0,0x8000,0,0xbe2d,0,0x3e750000,0,0x3e2d0000,0,0x80000000,0,0xbe2d0000,
0,0,0xbe2d,0,0xbe75,0,0xbe2d,0,0,0,0xbe2d0000,0,0xbe750000,0,0xbe2d0000,0,
0,0,0,0xbe2d,0,0xbe75,0,0xbe2d,0,0,0,0xbe2d0000,0,0xbe750000,0,0xbe2d0000,
0xbe46,0,0xbe5a,0,0xbe10,0,0x3dde,0,0xbe460000,0,0xbe5a0000,0,0xbe100000,0,0x3dde0000,0,
0,0xbe46,0,0xbe5a,0,0xbe10,0,0x3dde,0,0xbe460000,0,0xbe5a0000,0,0xbe100000,0,0x3dde0000,
0,0,0x3e5a,0,0x3e75,0,0x3dde,0,0,0,0x3e5a0000,0,0x3e750000,0,0x3dde0000,0,
0,0,0,0x3e5a,0,0x3e75,0,0x3dde,0,0,0,0x3e5a0000,0,0x3e750000,0,0x3dde0000,
0x3d97,0,0x3e72,0,0x3e69,0,0xbd19,0,0x3d970000,0,0x3e720000,0,0x3e690000,0,0xbd190000,0,
0,0x3d97,0,0x3e72,0,0x3e69,0,0xbd19,0,0x3d970000,0,0x3e720000,0,0x3e690000,0,0xbd190000,
0,0,0xbe72,0,0xbe75,0,0xbd19,0,0,0,0xbe720000,0,0xbe750000,0,0xbd190000,0,
0,0,0,0xbe72,0,0xbe75,0,0xbd19,0,0,0,0xbe720000,0,0xbe750000,0,0xbd190000,
0x3d97,0,0xbe72,0,0xbe69,0,0xbd19,0,0x3d970000,0,0xbe720000,0,0xbe690000,0,0xbd190000,0,
0,0x3d97,0,0xbe72,0,0xbe69,0,0xbd19,0,0x3d970000,0,0xbe720000,0,0xbe690000,0,0xbd190000,
0,0,0x3e72,0,0x3e75,0,0xbd19,0,0,0,0x3e720000,0,0x3e750000,0,0xbd190000,0,
0,0,0,0x3e72,0,0x3e75,0,0xbd19,0,0,0,0x3e720000,0,0x3e750000,0,0xbd190000,
0xbe46,0,0x3e5a,0,0x3e10,0,0x3dde,0,0xbe460000,0,0x3e5a0000,0,0x3e100000,0,0x3dde0000,0,
0,0xbe46,0,0x3e5a,0,0x3e10,0,0x3dde,0,0xbe460000,0,0x3e5a0000,0,0x3e100000,0,0x3dde0000,
0,0,0xbe5a,0,0xbe75,0,0x3dde,0,0,0,0xbe5a0000,0,0xbe750000,0,0x3dde0000,0,
0,0,0,0xbe5a,0,0xbe75,0,0x3dde,0,0,0,0xbe5a0000,0,0xbe750000,0,0x3dde0000,
0x3e75,0,0xbe2d,0,0x8000,0,0xbe2d,0,0x3e750000,0,0xbe2d0000,0,0x80000000,0,0xbe2d0000,0,
0,0x3e75,0,0xbe2d,0,0x8000,0,0xbe2d,0,0x3e750000,0,0xbe2d0000,0,0x80000000,0,0xbe2d0000,
0,0,0x3e2d,0,0x3e75,0,0xbe2d,0,0,0,0x3e2d0000,0,0x3e750000,0,0xbe2d0000,0,
0,0,0,0x3e2d,0,0x3e75,0,0xbe2d,0,0,0,0x3e2d0000,0,0x3e750000,0,0xbe2d0000,
0xbe46,0,0x3dde,0,0xbe10,0,0x3e5a,0,0xbe460000,0,0x3dde0000,0,0xbe100000,0,0x3e5a0000,0,
0,0xbe46,0,0x3dde,0,0xbe10,0,0x3e5a,0,0xbe460000,0,0x3dde0000,0,0xbe100000,0,0x3e5a0000,
0,0,0xbdde,0,0xbe75,0,0x3e5a,0,0,0,0xbdde0000,0,0xbe750000,0,0x3e5a0000,0,
0,0,0,0xbdde,0,0xbe75,0,0x3e5a,0,0,0,0xbdde0000,0,0xbe750000,0,0x3e5a0000,
0x3d97,0,0xbd19,0,0x3e69,0,0xbe72,0,0x3d970000,0,0xbd190000,0,0x3e690000,0,0xbe720000,0,
0,0x3d97,0,0xbd19,0,0x3e69,0,0xbe72,0,0x3d970000,0,0xbd190000,0,0x3e690000,0,0xbe720000,
0,0,0x3d19,0,0x3e75,0,0xbe72,0,0,0,0x3d190000,0,0x3e750000,0,0xbe720000,0,
0,0,0,0x3d19,0,0x3e75,0,0xbe72,0,0,0,0x3d190000,0,0x3e750000,0,0xbe720000,
0xbd97,0,0xbdde,0,0xbe69,0,0xbe5a,0,0xbd970000,0,0xbdde0000,0,0xbe690000,0,0xbe5a0000,0,
0,0xbd97,0,0xbdde,0,0xbe69,0,0xbe5a,0,0xbd970000,0,0xbdde0000,0,0xbe690000,0,0xbe5a0000,
0xbe10,0,0xbe2d,0,0xbe46,0,0xbe2d,0,0xbe100000,0,0xbe2d0000,0,0xbe460000,0,0xbe2d0000,0,
0,0xbe10,0,0xbe2d,0,0xbe46,0,0xbe2d,0,0xbe100000,0,0xbe2d0000,0,0xbe460000,0,0xbe2d0000,
0x3e46,0,0x3e72,0,0x3e10,0,0x3d19,0,0x3e460000,0,0x3e720000,0,0x3e100000,0,0x3d190000,0,
0,0x3e46,0,0x3e72,0,0x3e10,0,0x3d19,0,0x3e460000,0,0x3e720000,0,0x3e100000,0,0x3d190000,
0x3e69,0,0x3e2d,0,0xbd97,0,0xbe2d,0,0x3e690000,0,0x3e2d0000,0,0xbd970000,0,0xbe2d0000,0,
0,0x3e69,0,0x3e2d,0,0xbd97,0,0xbe2d,0,0x3e690000,0,0x3e2d0000,0,0xbd970000,0,0xbe2d0000,
0xbe75,0,0xbe2d,0,0x8000,0,0x3e2d,0,0xbe750000,0,0xbe2d0000,0,0x80000000,0,0x3e2d0000,0,
0,0xbe75,0,0xbe2d,0,0x8000,0,0x3e2d,0,0xbe750000,0,0xbe2d0000,0,0x80000000,0,0x3e2d0000,
0,0,0x3e2d,0,0x3e75,0,0x3e2d,0,0,0,0x3e2d0000,0,0x3e750000,0,0x3e2d0000,0,
0,0,0,0x3e2d,0,0x3e75,0,0x3e2d,0,0,0,0x3e2d0000,0,0x3e750000,0,0x3e2d0000,
0x3e46,0,0xbd19,0,0xbe10,0,0xbe72,0,0x3e460000,0,0xbd190000,0,0xbe100000,0,0xbe720000,0,
0,0x3e46,0,0xbd19,0,0xbe10,0,0xbe72,0,0x3e460000,0,0xbd190000,0,0xbe100000,0,0xbe720000,
0xbe69,0,0xbe2d,0,0xbd97,0,0x3e2d,0,0xbe690000,0,0xbe2d0000,0,0xbd970000,0,0x3e2d0000,0,
0,0xbe69,0,0xbe2d,0,0xbd97,0,0x3e2d,0,0xbe690000,0,0xbe2d0000,0,0xbd970000,0,0x3e2d0000,
0xbd97,0,0x3e5a,0,0x3e69,0,0x3dde,0,0xbd970000,0,0x3e5a0000,0,0x3e690000,0,0x3dde0000,0,
0,0xbd97,0,0x3e5a,0,0x3e69,0,0x3dde,0,0xbd970000,0,0x3e5a0000,0,0x3e690000,0,0x3dde0000,
0x3e10,0,0xbe2d,0,0xbe46,0,0xbe2d,0,0x3e100000,0,0xbe2d0000,0,0xbe460000,0,0xbe2d0000,0,
0,0x3e10,0,0xbe2d,0,0xbe46,0,0xbe2d,0,0x3e100000,0,0xbe2d0000,0,0xbe460000,0,0xbe2d0000,
0xbd97,0,0xbe5a,0,0xbe69,0,0x3dde,0,0xbd970000,0,0xbe5a0000,0,0xbe690000,0,0x3dde0000,0,
0,0xbd97,0,0xbe5a,0,0xbe69,0,0x3dde,0,0xbd970000,0,0xbe5a0000,0,0xbe690000,0,0x3dde0000,
0x3e10,0,0x3e2d,0,0x3e46,0,0xbe2d,0,0x3e100000,0,0x3e2d0000,0,0x3e460000,0,0xbe2d0000,0,
0,0x3e10,0,0x3e2d,0,0x3e46,0,0xbe2d,0,0x3e100000,0,0x3e2d0000,0,0x3e460000,0,0xbe2d0000,
0x3e46,0,0x3d19,0,0x3e10,0,0xbe72,0,0x3e460000,0,0x3d190000,0,0x3e100000,0,0xbe720000,0,
0,0x3e46,0,0x3d19,0,0x3e10,0,0xbe72,0,0x3e460000,0,0x3d190000,0,0x3e100000,0,0xbe720000,
0xbe69,0,0x3e2d,0,0x3d97,0,0x3e2d,0,0xbe690000,0,0x3e2d0000,0,0x3d970000,0,0x3e2d0000,0,
0,0xbe69,0,0x3e2d,0,0x3d97,0,0x3e2d,0,0xbe690000,0,0x3e2d0000,0,0x3d970000,0,0x3e2d0000,
0xbe75,0,0x3e2d,0,0x8000,0,0x3e2d,0,0xbe750000,0,0x3e2d0000,0,0x80000000,0,0x3e2d0000,0,
0,0xbe75,0,0x3e2d,0,0x8000,0,0x3e2d,0,0xbe750000,0,0x3e2d0000,0,0x80000000,0,0x3e2d0000,
0,0,0xbe2d,0,0xbe75,0,0x3e2d,0,0,0,0xbe2d0000,0,0xbe750000,0,0x3e2d0000,0,
0,0,0,0xbe2d,0,0xbe75,0,0x3e2d,0,0,0,0xbe2d0000,0,0xbe750000,0,0x3e2d0000,
0x3e46,0,0xbe72,0,0xbe10,0,0x3d19,0,0x3e460000,0,0xbe720000,0,0xbe100000,0,0x3d190000,0,
0,0x3e46,0,0xbe72,0,0xbe10,0,0x3d19,0,0x3e460000,0,0xbe720000,0,0xbe100000,0,0x3d190000,
0x3e69,0,0xbe2d,0,0x3d97,0,0xbe2d,0,0x3e690000,0,0xbe2d0000,0,0x3d970000,0,0xbe2d0000,0,
0,0x3e69,0,0xbe2d,0,0x3d97,0,0xbe2d,0,0x3e690000,0,0xbe2d0000,0,0x3d970000,0,0xbe2d0000,
0xbd97,0,0x3dde,0,0x3e69,0,0xbe5a,0,0xbd970000,0,0x3dde0000,0,0x3e690000,0,0xbe5a0000,0,
0,0xbd97,0,0x3dde,0,0x3e69,0,0xbe5a,0,0xbd970000,0,0x3dde0000,0,0x3e690000,0,0xbe5a0000,
0xbe10,0,0x3e2d,0,0x3e46,0,0xbe2d,0,0xbe100000,0,0x3e2d0000,0,0x3e460000,0,0xbe2d0000,0,
0,0xbe10,0,0x3e2d,0,0x3e46,0,0xbe2d,0,0xbe100000,0,0x3e2d0000,0,0x3e460000,0,0xbe2d0000,
0xbe46,0,0xbe5a,0,0xbe10,0,0xbdde,0,0xbe460000,0,0xbe5a0000,0,0xbe100000,0,0xbdde0000,0,
0,0xbe46,0,0xbe5a,0,0xbe10,0,0xbdde,0,0xbe460000,0,0xbe5a0000,0,0xbe100000,0,0xbdde0000,
0xbe69,0,0xbe72,0,0xbd97,0,0xbd19,0,0xbe690000,0,0xbe720000,0,0xbd970000,0,0xbd190000,0,
0,0xbe69,0,0xbe72,0,0xbd97,0,0xbd19,0,0xbe690000,0,0xbe720000,0,0xbd970000,0,0xbd190000,
0x3d97,0,0xbd19,0,0xbe69,0,0xbe72,0,0x3d970000,0,0xbd190000,0,0xbe690000,0,0xbe720000,0,
0,0x3d97,0,0xbd19,0,0xbe69,0,0xbe72,0,0x3d970000,0,0xbd190000,0,0xbe690000,0,0xbe720000,
0xbe10,0,0xbe5a,0,0xbe46,0,0xbdde,0,0xbe100000,0,0xbe5a0000,0,0xbe460000,0,0xbdde0000,0,
0,0xbe10,0,0xbe5a,0,0xbe46,0,0xbdde,0,0xbe100000,0,0xbe5a0000,0,0xbe460000,0,0xbdde0000,
0x3e75,0,0x3e2d,0,0x8000,0,0xbe2d,0,0x3e750000,0,0x3e2d0000,0,0x80000000,0,0xbe2d0000,0,
0,0x3e75,0,0x3e2d,0,0x8000,0,0xbe2d,0,0x3e750000,0,0x3e2d0000,0,0x80000000,0,0xbe2d0000,
0,0,0xbe2d,0,0xbe75,0,0xbe2d,0,0,0,0xbe2d0000,0,0xbe750000,0,0xbe2d0000,0,
0,0,0,0xbe2d,0,0xbe75,0,0xbe2d,0,0,0,0xbe2d0000,0,0xbe750000,0,0xbe2d0000,
0x3d97,0,0x3e72,0,0x3e69,0,0x3d19,0,0x3d970000,0,0x3e720000,0,0x3e690000,0,0x3d190000,0,
0,0x3d97,0,0x3e72,0,0x3e69,0,0x3d19,0,0x3d970000,0,0x3e720000,0,0x3e690000,0,0x3d190000,
0x3e10,0,0xbdde,0,0xbe46,0,0xbe5a,0,0x3e100000,0,0xbdde0000,0,0xbe460000,0,0xbe5a0000,0,
0,0x3e10,0,0xbdde,0,0xbe46,0,0xbe5a,0,0x3e100000,0,0xbdde0000,0,0xbe460000,0,0xbe5a0000,
0xbe46,0,0x3dde,0,0x3e10,0,0x3e5a,0,0xbe460000,0,0x3dde0000,0,0x3e100000,0,0x3e5a0000,0,
0,0xbe46,0,0x3dde,0,0x3e10,0,0x3e5a,0,0xbe460000,0,0x3dde0000,0,0x3e100000,0,0x3e5a0000,
0x3e69,0,0xbd19,0,0xbd97,0,0xbe72,0,0x3e690000,0,0xbd190000,0,0xbd970000,0,0xbe720000,0,
0,0x3e69,0,0xbd19,0,0xbd97,0,0xbe72,0,0x3e690000,0,0xbd190000,0,0xbd970000,0,0xbe720000,
0xbe46,0,0xbdde,0,0xbe10,0,0x3e5a,0,0xbe460000,0,0xbdde0000,0,0xbe100000,0,0x3e5a0000,0,
0,0xbe46,0,0xbdde,0,0xbe10,0,0x3e5a,0,0xbe460000,0,0xbdde0000,0,0xbe100000,0,0x3e5a0000,
0x3e69,0,0x3d19,0,0x3d97,0,0xbe72,0,0x3e690000,0,0x3d190000,0,0x3d970000,0,0xbe720000,0,
0,0x3e69,0,0x3d19,0,0x3d97,0,0xbe72,0,0x3e690000,0,0x3d190000,0,0x3d970000,0,0xbe720000,
0x3d97,0,0xbe72,0,0xbe69,0,0x3d19,0,0x3d970000,0,0xbe720000,0,0xbe690000,0,0x3d190000,0,
0,0x3d97,0,0xbe72,0,0xbe69,0,0x3d19,0,0x3d970000,0,0xbe720000,0,0xbe690000,0,0x3d190000,
0x3e10,0,0x3dde,0,0x3e46,0,0xbe5a,0,0x3e100000,0,0x3dde0000,0,0x3e460000,0,0xbe5a0000,0,
0,0x3e10,0,0x3dde,0,0x3e46,0,0xbe5a,0,0x3e100000,0,0x3dde0000,0,0x3e460000,0,0xbe5a0000,
0x3e75,0,0xbe2d,0,0x8000,0,0xbe2d,0,0x3e750000,0,0xbe2d0000,0,0x80000000,0,0xbe2d0000,0,
0,0x3e75,0,0xbe2d,0,0x8000,0,0xbe2d,0,0x3e750000,0,0xbe2d0000,0,0x80000000,0,0xbe2d0000,
0,0,0x3e2d,0,0x3e75,0,0xbe2d,0,0,0,0x3e2d0000,0,0x3e750000,0,0xbe2d0000,0,
0,0,0,0x3e2d,0,0x3e75,0,0xbe2d,0,0,0,0x3e2d0000,0,0x3e750000,0,0xbe2d0000,
0x3d97,0,0x3d19,0,0x3e69,0,0xbe72,0,0x3d970000,0,0x3d190000,0,0x3e690000,0,0xbe720000,0,
0,0x3d97,0,0x3d19,0,0x3e69,0,0xbe72,0,0x3d970000,0,0x3d190000,0,0x3e690000,0,0xbe720000,
0xbe10,0,0x3e5a,0,0x3e46,0,0xbdde,0,0xbe100000,0,0x3e5a0000,0,0x3e460000,0,0xbdde0000,0,
0,0xbe10,0,0x3e5a,0,0x3e46,0,0xbdde,0,0xbe100000,0,0x3e5a0000,0,0x3e460000,0,0xbdde0000,
0xbe46,0,0x3e5a,0,0x3e10,0,0xbdde,0,0xbe460000,0,0x3e5a0000,0,0x3e100000,0,0xbdde0000,0,
0,0xbe46,0,0x3e5a,0,0x3e10,0,0xbdde,0,0xbe460000,0,0x3e5a0000,0,0x3e100000,0,0xbdde0000,
0xbe69,0,0x3e72,0,0x3d97,0,0xbd19,0,0xbe690000,0,0x3e720000,0,0x3d970000,0,0xbd190000,0,
0,0xbe69,0,0x3e72,0,0x3d97,0,0xbd19,0,0xbe690000,0,0x3e720000,0,0x3d970000,0,0xbd190000,
0x3eb7,0x3eb7,0x3eb7,0x3eb7,0x3eb78000,0x3eb78000,0x3eb78000,0x3eb78000,0x3eb7,0x3de23eae,0x3e573e94,0x3e943e57,0x3eb78000,0x3eaebde2,0x3e94be57,0x3e57be94,
0x3eb7,0x3e573e94,0x3eae3de2,0x3eaebde2,0x3eb78000,0x3e94be57,0x3de2beae,0xbde2beae,0x3eb7,0x3e943e57,0x3eaebde2,0x3de2beae,0x3eb78000,0x3e57be94,0xbde2beae,0xbeaebde2,
0x3eb7,0x3eb7,0x3eb7,0x3eb7,0x3eb78000,0x3eb78000,0x3eb78000,0x3eb78000,0x3eae3de2,0x3eb70000,0x3eaebde2,0x3e94be57,0x3de2beae,0xbeb7,0xbde2beae,0xbe57be94,
0x3e57be94,0xbeb7,0xbe57be94,0xbeaebde2,0xbe94be57,0xbeb78000,0xbe943e57,0xbde23eae,0xbe57be94,0xbeb70000,0xbe573e94,0x3de23eae,0xbe943e57,0x3eb7,0x3e943e57,0x3eaebde2,
0x3eb7,0x3eae3de2,0x3e57be94,0xbe57be94,0x3eb78000,0x3de2beae,0xbe94be57,0xbe943e57,0x3eb7,0x3eb70000,0xbeb7,0xbeb70000,0x3eb78000,0xbeb7,0xbeb78000,0x3eb7,
0x3eb7,0x3eaebde2,0xbe57be94,0xbe573e94,0x3eb78000,0xbde2beae,0xbe943e57,0x3e943e57,0x3eb7,0x3e94be57,0xbeaebde2,0x3de23eae,0x3eb78000,0xbe57be94,0xbde23eae,0x3eaebde2,
0xbeae3de2,0x3eb7,0x3eae3de2,0x3e57be94,0x3de23eae,0x3eb78000,0x3de2beae,0xbe94be57,0x3eb7,0x3eb70000,0xbeb7,0xbeb70000,0x3eb78000,0xbeb7,0xbeb78000,0x3eb7,
0x3eae3de2,0xbeb7,0xbeae3de2,0x3e573e94,0x3de2beae,0xbeb78000,0x3de23eae,0x3e94be57,0x3e57be94,0xbeb70000,0x3e573e94,0x3de2beae,0xbe94be57,0x3eb7,0x3e94be57,0xbeaebde2,
0x3eb7,0x3e57be94,0xbeae3de2,0x3eae3de2,0x3eb78000,0xbe94be57,0x3de23eae,0x3de2beae,0x3eb7,0x3de2beae,0xbe573e94,0x3e94be57,0x3eb78000,0xbeaebde2,0x3e943e57,0xbe57be94,
0x3eb7,0xbeb7,0x3eb7,0xbeb7,0x3eb78000,0xbeb78000,0x3eb78000,0xbeb78000,0x3eb7,0xbde2beae,0x3e573e94,0xbe94be57,0x3eb78000,0xbeae3de2,0x3e94be57,0xbe573e94,
0xbe57be94,0x3eb7,0x3e57be94,0xbeae3de2,0xbe943e57,0x3eb78000,0xbe94be57,0x3de23eae,0xbeae3de2,0x3eb70000,0xbeaebde2,0x3e943e57,0x3de23eae,0xbeb7,0xbde23eae,0x3e57be94,
0x3eb7,0xbeb7,0x3eb7,0xbeb7,0x3eb78000,0xbeb78000,0x3eb78000,0xbeb78000,0x3eae3de2,0xbeb70000,0x3eaebde2,0xbe943e57,0x3de2beae,0x3eb7,0xbde2beae,0x3e573e94,
0x3eb7,0xbe57be94,0x3eae3de2,0xbeae3de2,0x3eb78000,0xbe943e57,0x3de2beae,0x3de23eae,0x3eb7,0xbe94be57,0x3eaebde2,0xbde23eae,0x3eb78000,0xbe573e94,0xbde2beae,0x3eae3de2,
0x3eb7,0xbeaebde2,0x3e57be94,0x3e573e94,0x3eb78000,0xbde23eae,0xbe94be57,0x3e94be57,0x3eb7,0xbeb70000,0xbeb7,0x3eb70000,0x3eb78000,0x3eb7,0xbeb78000,0xbeb7,
0x3e57be94,0x3eb7,0xbe57be94,0x3eae3de2,0xbe94be57,0x3eb78000,0xbe943e57,0x3de2beae,0xbe57be94,0x3eb70000,0xbe573e94,0xbde2beae,0xbe943e57,0xbeb7,0x3e943e57,0xbeae3de2,
0xbeae3de2,0xbeb7,0x3eae3de2,0xbe573e94,0x3de23eae,0xbeb78000,0x3de2beae,0x3e943e57,0x3eb7,0xbeb70000,0xbeb7,0x3eb70000,0x3eb78000,0x3eb7,0xbeb78000,0xbeb7,
0x3eb7,0xbeae3de2,0xbe57be94,0x3e57be94,0x3eb78000,0x3de23eae,0xbe943e57,0xbe94be57,0x3eb7,0xbe943e57,0xbeaebde2,0xbde2beae,0x3eb78000,0x3e573e94,0xbde23eae,0xbeae3de2,
0x3eb7,0xbe573e94,0xbeae3de2,0xbeaebde2,0x3eb78000,0x3e943e57,0x3de23eae,0xbde23eae,0x3eb7,0xbde23eae,0xbe573e94,0xbe943e57,0x3eb78000,0x3eae3de2,0x3e943e57,0x3e573e94,
0x3eae3de2,0x3eb7,0xbeae3de2,0xbe57be94,0x3de2beae,0x3eb78000,0x3de23eae,0xbe943e57,0x3e57be94,0x3eb70000,0x3e573e94,0xbde23eae,0xbe94be57,0xbeb7,0x3e94be57,0x3eae3de2,
0xbe57be94,0xbeb7,0x3e57be94,0x3eaebde2,0xbe943e57,0xbeb78000,0xbe94be57,0xbde2beae,0xbeae3de2,0xbeb70000,0xbeaebde2,0xbe94be57,0x3de23eae,0x3eb7,0xbde23eae,0xbe573e94,
0x3eb7,0x3eb7,0x3eb7,0x3eb7,0x3eb78000,0x3eb78000,0x3eb78000,0x3eb78000,0x3e57be94,0x3de2beae,0xbeb7,0xbde2beae,0xbe94be57,0xbeaebde2,0xbeb78000,0xbeae3de2,
0xbeae3de2,0xbe573e94,0x3eb7,0x3e573e94,0x3de23eae,0x3e943e57,0x3eb78000,0x3e94be57,0x3eae3de2,0x3e94be57,0xbeb7,0xbe94be57,0x3de2beae,0xbe57be94,0xbeb78000,0xbe573e94,
0x3eb7,0x3eb7,0x3eb7,0x3eb7,0x3eb78000,0x3eb78000,0x3eb78000,0x3eb78000,0xbe57be94,0xbe94be57,0xbeaebde2,0xbeb70000,0xbe943e57,0xbe573e94,0xbde23eae,0x3eb7,
0x3eae3de2,0x3eaebde2,0x3e57be94,0xbeb7,0x3de2beae,0xbde2beae,0xbe94be57,0xbeb78000,0xbeae3de2,0xbde23eae,0x3e573e94,0x3eb70000,0x3de23eae,0x3eae3de2,0x3e94be57,0xbeb7,
0xbe57be94,0xbeae3de2,0x3eb7,0x3eae3de2,0xbe943e57,0x3de23eae,0x3eb78000,0x3de2beae,0x3eb7,0x3eb70000,0xbeb7,0xbeb70000,0x3eb78000,0xbeb7,0xbeb78000,0x3eb7,
0x3e57be94,0xbeaebde2,0x3eb7,0x3eaebde2,0xbe94be57,0xbde23eae,0x3eb78000,0xbde2beae,0xbeae3de2,0x3e943e57,0xbeb7,0xbe943e57,0x3de23eae,0x3e57be94,0xbeb78000,0x3e573e94,
0x3e57be94,0xbe57be94,0xbeae3de2,0x3eb7,0xbe94be57,0xbe943e57,0x3de23eae,0x3eb78000,0x3eb7,0x3eb70000,0xbeb7,0xbeb70000,0x3eb78000,0xbeb7,0xbeb78000,0x3eb7,
0xbe57be94,0xbe573e94,0x3eae3de2,0xbeb7,0xbe943e57,0x3e943e57,0x3de2beae,0xbeb78000,0x3eae3de2,0xbde2beae,0xbe573e94,0x3eb70000,0x3de2beae,0xbeae3de2,0x3e943e57,0xbeb7,
0x3eae3de2,0xbe57be94,0x3eb7,0x3e57be94,0x3de2beae,0xbe943e57,0x3eb78000,0xbe94be57,0xbe57be94,0x3de23eae,0xbeb7,0xbde23eae,0xbe943e57,0x3eaebde2,0xbeb78000,0x3eae3de2,
0x3eb7,0xbeb7,0x3eb7,0xbeb7,0x3eb78000,0xbeb78000,0x3eb78000,0xbeb78000,0x3e57be94,0xbde23eae,0xbeb7,0x3de23eae,0xbe94be57,0x3eae3de2,0xbeb78000,0x3eaebde2,
0xbeae3de2,0x3eae3de2,0xbe57be94,0x3eb7,0x3de23eae,0x3de2beae,0xbe943e57,0x3eb78000,0x3e57be94,0xbe943e57,0x3eaebde2,0xbeb70000,0xbe94be57,0x3e573e94,0xbde2beae,0x3eb7,
0x3eb7,0xbeb7,0x3eb7,0xbeb7,0x3eb78000,0xbeb78000,0x3eb78000,0xbeb78000,0xbe57be94,0x3e943e57,0xbeaebde2,0x3eb70000,0xbe943e57,0x3e57be94,0xbde23eae,0xbeb7,
0xbeae3de2,0x3e57be94,0x3eb7,0xbe57be94,0x3de23eae,0xbe94be57,0x3eb78000,0xbe943e57,0x3eae3de2,0xbe943e57,0xbeb7,0x3e943e57,0x3de2beae,0x3e573e94,0xbeb78000,0x3e57be94,
0xbe57be94,0x3eaebde2,0x3eb7,0xbeaebde2,0xbe943e57,0xbde2beae,0x3eb78000,0xbde23eae,0x3eb7,0xbeb70000,0xbeb7,0x3eb70000,0x3eb78000,0x3eb7,0xbeb78000,0xbeb7,
0x3eae3de2,0xbeae3de2,0x3e57be94,0x3eb7,0x3de2beae,0x3de23eae,0xbe94be57,0x3eb78000,0xbeae3de2,0x3de2beae,0x3e573e94,0xbeb70000,0x3de23eae,0xbeaebde2,0x3e94be57,0x3eb7,
0x3e57be94,0x3e573e94,0xbeae3de2,0xbeb7,0xbe94be57,0x3e94be57,0x3de23eae,0xbeb78000,0x3eb7,0xbeb70000,0xbeb7,0x3eb70000,0x3eb78000,0x3eb7,0xbeb78000,0xbeb7,
0x3e57be94,0x3eae3de2,0x3eb7,0xbeae3de2,0xbe94be57,0x3de2beae,0x3eb78000,0x3de23eae,0xbeae3de2,0xbe94be57,0xbeb7,0x3e94be57,0x3de23eae,0xbe573e94,0xbeb78000,0xbe57be94,
0x3eae3de2,0x3e573e94,0x3eb7,0xbe573e94,0x3de2beae,0x3e94be57,0x3eb78000,0x3e943e57,0xbe57be94,0xbde2beae,0xbeb7,0x3de2beae,0xbe943e57,0xbeae3de2,0xbeb78000,0xbeaebde2,
0xbe57be94,0x3e57be94,0x3eae3de2,0x3eb7,0xbe943e57,0xbe94be57,0x3de2beae,0x3eb78000,0x3eae3de2,0x3de23eae,0xbe573e94,0xbeb70000,0x3de2beae,0x3eaebde2,0x3e943e57,0x3eb7,
0xbeae3de2,0xbeaebde2,0xbe57be94,0xbeb7,0x3de23eae,0xbde23eae,0xbe943e57,0xbeb78000,0x3e57be94,0x3e94be57,0x3eaebde2,0x3eb70000,0xbe94be57,0xbe57be94,0xbde2beae,0xbeb7,
0x3eb7,0x3eb7,0x3eb7,0x3eb7,0x3eb78000,0x3eb78000,0x3eb78000,0x3eb78000,0xbeae3de2,0xbe943e57,0xbe573e94,0xbde23eae,0x3de23eae,0x3e573e94,0x3e943e57,0x3eae3de2,
0xbe57be94,0xbeaebde2,0xbeae3de2,0xbe573e94,0xbe943e57,0xbde23eae,0x3de23eae,0x3e943e57,0x3e57be94,0xbde2beae,0xbeaebde2,0xbe943e57,0xbe94be57,0xbeae3de2,0xbde23eae,0x3e573e94,
0,0,0,0,0,0,0,0,0,0,0,0,0,0,0,0,
0,0,0,0,0,0,0,0,0,0,0,0,0,0,0,0,
0x3eae3de2,0x3e57be94,0xbe57be94,0xbeae3de2,0x3de2beae,0xbe94be57,0xbe943e57,0x3de23eae,0x3eb7,0x3eb70000,0xbeb7,0xbeb70000,0x3eb78000,0xbeb7,0xbeb78000,0x3eb7,
0xbeae3de2,0x3e573e94,0x3e57be94,0xbeaebde2,0x3de23eae,0x3e94be57,0xbe94be57,0xbde23eae,0xbe57be94,0xbde23eae,0x3eaebde2,0xbe94be57,0xbe943e57,0x3eae3de2,0xbde2beae,0xbe573e94,
0,0,0,0,0,0,0,0,0,0,0,0,0,0,0,0,
0,0,0,0,0,0,0,0,0,0,0,0,0,0,0,0,
0x3e57be94,0xbeae3de2,0x3eae3de2,0xbe57be94,0xbe94be57,0x3de23eae,0x3de2beae,0xbe943e57,0x3eae3de2,0xbe94be57,0x3e573e94,0xbde2beae,0x3de2beae,0xbe573e94,0x3e94be57,0xbeae3de2,
0x3eb7,0xbeb7,0x3eb7,0xbeb7,0x3eb78000,0xbeb78000,0x3eb78000,0xbeb78000,0xbeae3de2,0x3e94be57,0xbe573e94,0x3de2beae,0x3de23eae,0xbe57be94,0x3e943e57,0xbeaebde2,
0,0,0,0,0,0,0,0,0,0,0,0,0,0,0,0,
0,0,0,0,0,0,0,0,0,0,0,0,0,0,0,0,
0xbe57be94,0x3eae3de2,0xbeae3de2,0x3e57be94,0xbe943e57,0x3de2beae,0x3de23eae,0xbe94be57,0x3e57be94,0x3de23eae,0xbeaebde2,0x3e94be57,0xbe94be57,0x3eaebde2,0xbde23eae,0xbe57be94,
0x3eae3de2,0xbe573e94,0xbe57be94,0x3eaebde2,0x3de2beae,0x3e943e57,0xbe943e57,0xbde2beae,0x3eb7,0xbeb70000,0xbeb7,0x3eb70000,0x3eb78000,0x3eb7,0xbeb78000,0xbeb7,
0,0,0,0,0,0,0,0,0,0,0,0,0,0,0,0,
0,0,0,0,0,0,0,0,0,0,0,0,0,0,0,0,
0xbeae3de2,0xbe57be94,0x3e57be94,0x3eae3de2,0x3de23eae,0xbe943e57,0xbe94be57,0x3de2beae,0xbe57be94,0x3de2beae,0x3eaebde2,0x3e943e57,0xbe943e57,0xbeaebde2,0xbde2beae,0x3e57be94,
0x3e57be94,0x3eaebde2,0x3eae3de2,0x3e573e94,0xbe94be57,0xbde2beae,0x3de2beae,0x3e94be57,0x3eae3de2,0x3e943e57,0x3e573e94,0x3de23eae,0x3de2beae,0x3e57be94,0x3e94be57,0x3eaebde2,
0,0,0,0,0,0,0,0,0,0,0,0,0,0,0,0,
0,0,0,0,0,0,0,0,0,0,0,0,0,0,0,0,
0,0,0,0,0,0,0,0,0,0,0,0,0,0,0,0,
0,0,0,0,0,0,0,0,0,0,0,0,0,0,0,0,
0x3eb7,0x3eb7,0x3eb7,0x3eb7,0x3eb78000,0x3eb78000,0x3eb78000,0x3eb78000,0xbeae3de2,0xbe943e57,0xbe573e94,0xbde23eae,0x3de23eae,0x3e573e94,0x3e943e57,0x3eae3de2,
0xbe57be94,0xbeaebde2,0xbeae3de2,0xbe573e94,0xbe943e57,0xbde23eae,0x3de23eae,0x3e943e57,0x3e57be94,0xbde2beae,0xbeaebde2,0xbe943e57,0xbe94be57,0xbeae3de2,0xbde23eae,0x3e573e94,
0,0,0,0,0,0,0,0,0,0,0,0,0,0,0,0,
0,0,0,0,0,0,0,0,0,0,0,0,0,0,0,0,
0x3eae3de2,0x3e57be94,0xbe57be94,0xbeae3de2,0x3de2beae,0xbe94be57,0xbe943e57,0x3de23eae,0x3eb7,0x3eb70000,0xbeb7,0xbeb70000,0x3eb78000,0xbeb7,0xbeb78000,0x3eb7,
0xbeae3de2,0x3e573e94,0x3e57be94,0xbeaebde2,0x3de23eae,0x3e94be57,0xbe94be57,0xbde23eae,0xbe57be94,0xbde23eae,0x3eaebde2,0xbe94be57,0xbe943e57,0x3eae3de2,0xbde2beae,0xbe573e94,
0,0,0,0,0,0,0,0,0,0,0,0,0,0,0,0,
0,0,0,0,0,0,0,0,0,0,0,0,0,0,0,0,
0x3e57be94,0xbeae3de2,0x3eae3de2,0xbe57be94,0xbe94be57,0x3de23eae,0x3de2beae,0xbe943e57,0x3eae3de2,0xbe94be57,0x3e573e94,0xbde2beae,0x3de2beae,0xbe573e94,0x3e94be57,0xbeae3de2,
0x3eb7,0xbeb7,0x3eb7,0xbeb7,0x3eb78000,0xbeb78000,0x3eb78000,0xbeb78000,0xbeae3de2,0x3e94be57,0xbe573e94,0x3de2beae,0x3de23eae,0xbe57be94,0x3e943e57,0xbeaebde2,
0,0,0,0,0,0,0,0,0,0,0,0,0,0,0,0,
0,0,0,0,0,0,0,0,0,0,0,0,0,0,0,0,
0xbe57be94,0x3eae3de2,0xbeae3de2,0x3e57be94,0xbe943e57,0x3de2beae,0x3de23eae,0xbe94be57,0x3e57be94,0x3de23eae,0xbeaebde2,0x3e94be57,0xbe94be57,0x3eaebde2,0xbde23eae,0xbe57be94,
0x3eae3de2,0xbe573e94,0xbe57be94,0x3eaebde2,0x3de2beae,0x3e943e57,0xbe943e57,0xbde2beae,0x3eb7,0xbeb70000,0xbeb7,0x3eb70000,0x3eb78000,0x3eb7,0xbeb78000,0xbeb7,
0,0,0,0,0,0,0,0,0,0,0,0,0,0,0,0,
0,0,0,0,0,0,0,0,0,0,0,0,0,0,0,0,
0xbeae3de2,0xbe57be94,0x3e57be94,0x3eae3de2,0x3de23eae,0xbe943e57,0xbe94be57,0x3de2beae,0xbe57be94,0x3de2beae,0x3eaebde2,0x3e943e57,0xbe943e57,0xbeaebde2,0xbde2beae,0x3e57be94,
0x3e57be94,0x3eaebde2,0x3eae3de2,0x3e573e94,0xbe94be57,0xbde2beae,0x3de2beae,0x3e94be57,0x3eae3de2,0x3e943e57,0x3e573e94,0x3de23eae,0x3de2beae,0x3e57be94,0x3e94be57,0x3eaebde2,
};
__device__ __align__(128) const uint32_t TAB_P3[4288] = {
0,0,0,0,0,0,0,0,0,0,0,0,0,0,0,0,
0x80003e83,0xbe79bda2,0x3e1abe54,0x3e1a3e54,0x3e830000,0xbda23e79,0xbe54be1a,0x3e54be1a,0x80003e83,0xbe54be1a,0x3e79bda2,0xbda23e79,0x3e830000,0xbe1a3e54,0xbda2be79,0x3e793da2,
0,0,0,0,0,0,0,0,0,0,0,0,0,0,0,0,
0xbe793da2,0x8000be83,0x3e793da2,0xbe1a3e54,0x3da23e79,0xbe830000,0x3da2be79,0x3e543e1a,0xbe1abe54,0x3e830000,0xbe1a3e54,0xbda2be79,0xbe543e1a,0xbe83,0x3e543e1a,0xbe793da2,
0x80003e83,0xbe1abe54,0x3e793da2,0xbe793da2,0x3e830000,0xbe543e1a,0x3da2be79,0x3da23e79,0x80003e83,0xbda2be79,0x3e1a3e54,0xbe54be1a,0x3e830000,0xbe793da2,0x3e54be1a,0xbe1a3e54,
0x80003e83,0x8000be83,0x80003e83,0x8000be83,0x3e830000,0xbe830000,0x3e830000,0xbe830000,0x80003e83,0x3da2be79,0xbe1a3e54,0x3e54be1a,0x3e830000,0xbe79bda2,0x3e543e1a,0xbe1abe54,
0x3e1abe54,0x80003e83,0xbe1abe54,0x3e793da2,0xbe54be1a,0x3e830000,0xbe543e1a,0x3da2be79,0x3e793da2,0xbe830000,0x3e79bda2,0xbe543e1a,0x3da2be79,0x3e83,0xbda2be79,0x3e1a3e54,
0x80003e83,0x8000be83,0x80003e83,0x8000be83,0x3e830000,0xbe830000,0x3e830000,0xbe830000,0xbe793da2,0x3e830000,0xbe79bda2,0x3e543e1a,0x3da23e79,0xbe83,0xbda23e79,0x3e1abe54,
0x80003e83,0x3e1abe54,0xbe793da2,0x3e793da2,0x3e830000,0xbe54be1a,0x3da23e79,0x3da2be79,0x80003e83,0x3e54be1a,0xbe79bda2,0x3da23e79,0x3e830000,0xbe1abe54,0xbda23e79,0x3e79bda2,
0x80003e83,0x3e79bda2,0xbe1abe54,0xbe1a3e54,0x3e830000,0xbda2be79,0xbe543e1a,0x3e543e1a,0x80003e83,0x3e830000,0x8000be83,0xbe830000,0x3e830000,0xbe83,0xbe830000,0x3e83,
0xbe1abe54,0x80003e83,0x3e1abe54,0xbe793da2,0xbe543e1a,0x3e830000,0xbe54be1a,0x3da23e79,0x3e1abe54,0xbe830000,0x3e1a3e54,0x3da2be79,0xbe54be1a,0x3e83,0x3e54be1a,0xbe79bda2,
0x3e793da2,0x8000be83,0xbe793da2,0x3e1a3e54,0x3da2be79,0xbe830000,0x3da23e79,0x3e54be1a,0x80003e83,0x3e830000,0x8000be83,0xbe830000,0x3e830000,0xbe83,0xbe830000,0x3e83,
0x80003e83,0x3e793da2,0x3e1abe54,0xbe1abe54,0x3e830000,0x3da2be79,0xbe54be1a,0xbe543e1a,0x80003e83,0x3e543e1a,0x3e79bda2,0x3da2be79,0x3e830000,0x3e1abe54,0xbda2be79,0xbe79bda2,
0x80003e83,0x3e1a3e54,0x3e793da2,0x3e79bda2,0x3e830000,0x3e54be1a,0x3da2be79,0xbda2be79,0x80003e83,0x3da23e79,0x3e1a3e54,0x3e543e1a,0x3e830000,0x3e79bda2,0x3e54be1a,0x3e1abe54,
0xbe793da2,0x80003e83,0x3e793da2,0x3e1abe54,0x3da23e79,0x3e830000,0x3da2be79,0xbe54be1a,0xbe1abe54,0xbe830000,0xbe1a3e54,0x3da23e79,0xbe543e1a,0x3e83,0x3e543e1a,0x3e79bda2,
0x3e1abe54,0x8000be83,0xbe1abe54,0xbe79bda2,0xbe54be1a,0xbe830000,0xbe543e1a,0xbda23e79,0x3e793da2,0x3e830000,0x3e79bda2,0x3e54be1a,0x3da2be79,0xbe83,0xbda2be79,0xbe1abe54,
0,0,0,0,0,0,0,0,0,0,0,0,0,0,0,0,
0,0,0,0,0,0,0,0,0,0,0,0,0,0,0,0,
0,0,0,0,0,0,0,0,0,0,0,0,0,0,0,0,
0xbe1abe54,0x3e79bda2,0x80003e83,0xbe79bda2,0xbe543e1a,0xbda2be79,0x3e830000,0xbda23e79,0x3e793da2,0xbe543e1a,0x8000be83,0x3e543e1a,0x3da2be79,0x3e1a3e54,0xbe830000,0x3e1abe54,
0,0,0,0,0,0,0,0,0,0,0,0,0,0,0,0,
0,0,0,0,0,0,0,0,0,0,0,0,0,0,0,0,
0xbe793da2,0x3e1abe54,0x80003e83,0xbe1abe54,0x3da23e79,0xbe54be1a,0x3e830000,0xbe543e1a,0x3e1abe54,0xbda23e79,0x8000be83,0x3da23e79,0xbe54be1a,0x3e793da2,0xbe830000,0x3e79bda2,
0x80003e83,0x8000be83,0x80003e83,0x8000be83,0x3e830000,0xbe830000,0x3e830000,0xbe830000,0xbe1abe54,0x3da23e79,0x8000be83,0xbda23e79,0xbe543e1a,0x3e79bda2,0xbe830000,0x3e793da2,
0,0,0,0,0,0,0,0,0,0,0,0,0,0,0,0,
0,0,0,0,0,0,0,0,0,0,0,0,0,0,0,0,
0x3e793da2,0xbe1abe54,0x80003e83,0x3e1abe54,0x3da2be79,0xbe543e1a,0x3e830000,0xbe54be1a,0xbe793da2,0x3e543e1a,0x8000be83,0xbe543e1a,0x3da23e79,0x3e1abe54,0xbe830000,0x3e1a3e54,
0x3e1abe54,0xbe79bda2,0x80003e83,0x3e79bda2,0xbe54be1a,0xbda23e79,0x3e830000,0xbda2be79,0x80003e83,0x3e830000,0x8000be83,0xbe830000,0x3e830000,0xbe83,0xbe830000,0x3e83,
0,0,0,0,0,0,0,0,0,0,0,0,0,0,0,0,
0,0,0,0,0,0,0,0,0,0,0,0,0,0,0,0,
0xbe1abe54,0xbe793da2,0x80003e83,0x3e793da2,0xbe543e1a,0x3da23e79,0x3e830000,0x3da2be79,0x3e793da2,0x3e54be1a,0x8000be83,0xbe54be1a,0x3da2be79,0xbe1abe54,0xbe830000,0xbe1a3e54,
0xbe793da2,0xbe1a3e54,0x80003e83,0x3e1a3e54,0x3da23e79,0x3e543e1a,0x3e830000,0x3e54be1a,0x3e1abe54,0x3da2be79,0x8000be83,0xbda2be79,0xbe54be1a,0xbe79bda2,0xbe830000,0xbe793da2,
0,0,0,0,0,0,0,0,0,0,0,0,0,0,0,0,
0x3e1abe54,0x3e1a3e54,0xbe793da2,0x8000be83,0xbe54be1a,0x3e54be1a,0x3da23e79,0xbe830000,0xbe793da2,0x3da2be79,0x3e1a3e54,0xbe830000,0x3da23e79,0xbe79bda2,0x3e54be1a,0x3e83,
0,0,0,0,0,0,0,0,0,0,0,0,0,0,0,0,
0x3e793da2,0xbe1a3e54,0xbe1abe54,0x3e79bda2,0x3da2be79,0x3e543e1a,0xbe543e1a,0xbda2be79,0x3e1abe54,0x3da23e79,0xbe79bda2,0x3e54be1a,0xbe54be1a,0x3e79bda2,0xbda23e79,0xbe1abe54,
0x3e793da2,0xbe793da2,0x3e1abe54,0x80003e83,0x3da2be79,0x3da23e79,0xbe54be1a,0x3e830000,0xbe1abe54,0x3e543e1a,0xbe79bda2,0x3e830000,0xbe543e1a,0x3e1abe54,0xbda23e79,0xbe83,
0x80003e83,0x8000be83,0x80003e83,0x8000be83,0x3e830000,0xbe830000,0x3e830000,0xbe830000,0x3e1abe54,0xbe543e1a,0x3e79bda2,0xbe830000,0xbe54be1a,0x3e1a3e54,0xbda2be79,0x3e83,
0xbe1abe54,0x3e793da2,0xbe793da2,0x3e1abe54,0xbe543e1a,0x3da2be79,0x3da23e79,0xbe54be1a,0xbe793da2,0x3e54be1a,0xbe1a3e54,0x3da2be79,0x3da23e79,0xbe1abe54,0x3e543e1a,0xbe79bda2,
0x80003e83,0x8000be83,0x80003e83,0x8000be83,0x3e830000,0xbe830000,0x3e830000,0xbe830000,0x3e793da2,0xbe54be1a,0x3e1a3e54,0xbda2be79,0x3da2be79,0xbe1a3e54,0x3e54be1a,0xbe793da2,
0xbe793da2,0x3e793da2,0xbe1abe54,0x80003e83,0x3da23e79,0x3da2be79,0xbe543e1a,0x3e830000,0x3e793da2,0xbda2be79,0xbe1a3e54,0x3e830000,0x3da2be79,0xbe793da2,0x3e543e1a,0xbe83,
0xbe1abe54,0xbe1a3e54,0x3e793da2,0x8000be83,0xbe543e1a,0x3e543e1a,0x3da2be79,0xbe830000,0x80003e83,0x3e830000,0x8000be83,0xbe830000,0x3e830000,0xbe83,0xbe830000,0x3e83,
0x3e1abe54,0xbe793da2,0x3e793da2,0xbe1abe54,0xbe54be1a,0x3da23e79,0x3da2be79,0xbe543e1a,0xbe1abe54,0xbda23e79,0x3e79bda2,0xbe54be1a,0xbe543e1a,0x3e793da2,0xbda2be79,0xbe1a3e54,
0xbe793da2,0x3e1a3e54,0x3e1abe54,0xbe79bda2,0x3da23e79,0x3e54be1a,0xbe54be1a,0xbda23e79,0x80003e83,0x3e830000,0x8000be83,0xbe830000,0x3e830000,0xbe83,0xbe830000,0x3e83,
0x3e1abe54,0xbe1abe54,0xbe793da2,0x80003e83,0xbe54be1a,0xbe543e1a,0x3da23e79,0x3e830000,0xbe793da2,0xbda23e79,0x3e1a3e54,0x3e830000,0x3da23e79,0x3e793da2,0x3e54be1a,0xbe83,
0x3e793da2,0x3e79bda2,0x3e1abe54,0x8000be83,0x3da2be79,0xbda2be79,0xbe54be1a,0xbe830000,0xbe1abe54,0xbe54be1a,0xbe79bda2,0xbe830000,0xbe543e1a,0xbe1a3e54,0xbda23e79,0x3e83,
0x3e793da2,0x3e1abe54,0xbe1abe54,0xbe793da2,0x3da2be79,0xbe54be1a,0xbe543e1a,0x3da23e79,0x3e1abe54,0xbda2be79,0xbe79bda2,0xbe543e1a,0xbe54be1a,0xbe793da2,0xbda23e79,0x3e1a3e54,
0xbe1abe54,0xbe79bda2,0xbe793da2,0xbe1a3e54,0xbe543e1a,0xbda23e79,0x3da23e79,0x3e543e1a,0xbe793da2,0xbe543e1a,0xbe1a3e54,0xbda23e79,0x3da23e79,0x3e1a3e54,0x3e543e1a,0x3e793da2,
0xbe163dda,0,0,0,0,0xbe163dda,0,0,0,0,0xbe163dda,0,0,0,0,0xbe163dda,
0xbe253da8,0,0,0,0,0xbe253da8,0,0,0,0,0xbe253da8,0,0,0,0,0xbe253da8,
0xbd65be30,0,0,0,0,0xbd65be30,0,0,0,0,0xbd65be30,0,0,0,0,0xbd65be30,
0x3ce8be37,0,0,0,0,0x3ce8be37,0,0,0,0,0x3ce8be37,0,0,0,0,0x3ce8be37,
0xbe303d65,0,0,0,0,0xbe303d65,0,0,0,0,0xbe303d65,0,0,0,0,0xbe303d65,
0xbe373ce8,0,0,0,0,0xbe373ce8,0,0,0,0,0xbe373ce8,0,0,0,0,0xbe373ce8,
0x3ddabe16,0,0,0,0,0x3ddabe16,0,0,0,0,0x3ddabe16,0,0,0,0,0x3ddabe16,
0x3e25bda8,0,0,0,0,0x3e25bda8,0,0,0,0,0x3e25bda8,0,0,0,0,0x3e25bda8,
0xbe390000,0,0,0,0,0xbe390000,0,0,0,0,0xbe390000,0,0,0,0,0xbe390000,
0xbe37bce8,0,0,0,0,0xbe37bce8,0,0,0,0,0xbe37bce8,0,0,0,0,0xbe37bce8,
0x3e390000,0,0,0,0,0x3e390000,0,0,0,0,0x3e390000,0,0,0,0,0x3e390000,
0x3e253da8,0,0,0,0,0x3e253da8,0,0,0,0,0x3e253da8,0,0,0,0,0x3e253da8,
0xbe30bd65,0,0,0,0,0xbe30bd65,0,0,0,0,0xbe30bd65,0,0,0,0,0xbe30bd65,
0xbe25bda8,0,0,0,0,0xbe25bda8,0,0,0,0,0xbe25bda8,0,0,0,0,0xbe25bda8,
0x3dda3e16,0,0,0,0,0x3dda3e16,0,0,0,0,0x3dda3e16,0,0,0,0,0x3dda3e16,
0x3ce83e37,0,0,0,0,0x3ce83e37,0,0,0,0,0x3ce83e37,0,0,0,0,0x3ce83e37,
0xbe16bdda,0,0,0,0,0xbe16bdda,0,0,0,0,0xbe16bdda,0,0,0,0,0xbe16bdda,
0xbe03be03,0,0,0,0,0xbe03be03,0,0,0,0,0xbe03be03,0,0,0,0,0xbe03be03,
0xbd653e30,0,0,0,0,0xbd653e30,0,0,0,0,0xbd653e30,0,0,0,0,0xbd653e30,
0xbe033e03,0,0,0,0,0xbe033e03,0,0,0,0,0xbe033e03,0,0,0,0,0xbe033e03,
0xbddabe16,0,0,0,0,0xbddabe16,0,0,0,0,0xbddabe16,0,0,0,0,0xbddabe16,
0xbda8be25,0,0,0,0,0xbda8be25,0,0,0,0,0xbda8be25,0,0,0,0,0xbda8be25,
0xbe303d65,0,0,0,0,0xbe303d65,0,0,0,0,0xbe303d65,0,0,0,0,0xbe303d65,
0xbe37bce8,0,0,0,0,0xbe37bce8,0,0,0,0,0xbe37bce8,0,0,0,0,0xbe37bce8,
0xbd65be30,0,0,0,0,0xbd65be30,0,0,0,0,0xbd65be30,0,0,0,0,0xbd65be30,
0xbce8be37,0,0,0,0,0xbce8be37,0,0,0,0,0xbce8be37,0,0,0,0,0xbce8be37,
0xbe16bdda,0,0,0,0,0xbe16bdda,0,0,0,0,0xbe16bdda,0,0,0,0,0xbe16bdda,
0xbda8be25,0,0,0,0,0xbda8be25,0,0,0,0,0xbda8be25,0,0,0,0,0xbda8be25,
0x3e390000,0,0,0,0,0x3e390000,0,0,0,0,0x3e390000,0,0,0,0,0x3e390000,
0x3e033e03,0,0,0,0,0x3e033e03,0,0,0,0,0x3e033e03,0,0,0,0,0x3e033e03,
0xbd653e30,0,0,0,0,0xbd653e30,0,0,0,0,0xbd653e30,0,0,0,0,0xbd653e30,
0xbe373ce8,0,0,0,0,0xbe373ce8,0,0,0,0,0xbe373ce8,0,0,0,0,0xbe373ce8,
0x80003e39,0,0,0,0,0x80003e39,0,0,0,0,0x80003e39,0,0,0,0,0x80003e39,
0xbe033e03,0,0,0,0,0xbe033e03,0,0,0,0,0xbe033e03,0,0,0,0,0xbe033e03,
0xbddabe16,0,0,0,0,0xbddabe16,0,0,0,0,0xbddabe16,0,0,0,0,0xbddabe16,
0x3da8be25,0,0,0,0,0x3da8be25,0,0,0,0,0x3da8be25,0,0,0,0,0x3da8be25,
0xbe390000,0,0,0,0,0xbe390000,0,0,0,0,0xbe390000,0,0,0,0,0xbe390000,
0xbe03be03,0,0,0,0,0xbe03be03,0,0,0,0,0xbe03be03,0,0,0,0,0xbe03be03,
0x3e390000,0,0,0,0,0x3e390000,0,0,0,0,0x3e390000,0,0,0,0,0x3e390000,
0x3da83e25,0,0,0,0,0x3da83e25,0,0,0,0,0x3da83e25,0,0,0,0,0x3da83e25,
0x8000be39,0,0,0,0,0x8000be39,0,0,0,0,0x8000be39,0,0,0,0,0x8000be39,
0x3e03be03,0,0,0,0,0x3e03be03,0,0,0,0,0x3e03be03,0,0,0,0,0x3e03be03,
0xbdda3e16,0,0,0,0,0xbdda3e16,0,0,0,0,0xbdda3e16,0,0,0,0,0xbdda3e16,
0xbe37bce8,0,0,0,0,0xbe37bce8,0,0,0,0,0xbe37bce8,0,0,0,0,0xbe37bce8,
0x3e390000,0,0,0,0,0x3e390000,0,0,0,0,0x3e390000,0,0,0,0,0x3e390000,
0x3e033e03,0,0,0,0,0x3e033e03,0,0,0,0,0x3e033e03,0,0,0,0,0x3e033e03,
0xbd65be30,0,0,0,0,0xbd65be30,0,0,0,0,0xbd65be30,0,0,0,0,0xbd65be30,
0x3e03be03,0,0,0,0,0x3e03be03,0,0,0,0,0x3e03be03,0,0,0,0,0x3e03be03,
0x80003e39,0,0,0,0,0x80003e39,0,0,0,0,0x80003e39,0,0,0,0,0x80003e39,
0xbe033e03,0,0,0,0,0xbe033e03,0,0,0,0,0xbe033e03,0,0,0,0,0xbe033e03,
0x3e303d65,0,0,0,0,0x3e303d65,0,0,0,0,0x3e303d65,0,0,0,0,0x3e303d65,
0x3ce83e37,0,0,0,0,0x3ce83e37,0,0,0,0,0x3ce83e37,0,0,0,0,0x3ce83e37,
0xbe390000,0,0,0,0,0xbe390000,0,0,0,0,0xbe390000,0,0,0,0,0xbe390000,
0xbe03be03,0,0,0,0,0xbe03be03,0,0,0,0,0xbe03be03,0,0,0,0,0xbe03be03,
0xbe163dda,0,0,0,0,0xbe163dda,0,0,0,0,0xbe163dda,0,0,0,0,0xbe163dda,
0xbe25bda8,0,0,0,0,0xbe25bda8,0,0,0,0,0xbe25bda8,0,0,0,0,0xbe25bda8,
0xbe16bdda,0,0,0,0,0xbe16bdda,0,0,0,0,0xbe16bdda,0,0,0,0,0xbe16bdda,
0x3da8be25,0,0,0,0,0x3da8be25,0,0,0,0,0x3da8be25,0,0,0,0,0x3da8be25,
0x3e16bdda,0,0,0,0,0x3e16bdda,0,0,0,0,0x3e16bdda,0,0,0,0,0x3e16bdda,
0x3da83e25,0,0,0,0,0x3da83e25,0,0,0,0,0x3da83e25,0,0,0,0,0x3da83e25,
0x3e303d65,0,0,0,0,0x3e303d65,0,0,0,0,0x3e303d65,0,0,0,0,0x3e303d65,
0xbce83e37,0,0,0,0,0xbce83e37,0,0,0,0,0xbce83e37,0,0,0,0,0xbce83e37,
0xbe303d65,0,0,0,0,0xbe303d65,0,0,0,0,0xbe303d65,0,0,0,0,0xbe303d65,
0xbce8be37,0,0,0,0,0xbce8be37,0,0,0,0,0xbce8be37,0,0,0,0,0xbce8be37,
0xbe390000,0,0,0,0,0xbe390000,0,0,0,0,0xbe390000,0,0,0,0,0xbe390000,
0xbce8be37,0,0,0,0,0xbce8be37,0,0,0,0,0xbce8be37,0,0,0,0,0xbce8be37,
0x3e390000,0,0,0,0,0x3e390000,0,0,0,0,0x3e390000,0,0,0,0,0x3e390000,
0xbce83e37,0,0,0,0,0xbce83e37,0,0,0,0,0xbce83e37,0,0,0,0,0xbce83e37,
0x3e30bd65,0,0,0,0,0x3e30bd65,0,0,0,0,0x3e30bd65,0,0,0,0,0x3e30bd65,
0x3da83e25,0,0,0,0,0x3da83e25,0,0,0,0,0x3da83e25,0,0,0,0,0x3da83e25,
0xbe30bd65,0,0,0,0,0xbe30bd65,0,0,0,0,0xbe30bd65,0,0,0,0,0xbe30bd65,
0x3da8be25,0,0,0,0,0x3da8be25,0,0,0,0,0x3da8be25,0,0,0,0,0x3da8be25,
0xbe163dda,0,0,0,0,0xbe163dda,0,0,0,0,0xbe163dda,0,0,0,0,0xbe163dda,
0xbe03be03,0,0,0,0,0xbe03be03,0,0,0,0,0xbe03be03,0,0,0,0,0xbe03be03,
0x3e163dda,0,0,0,0,0x3e163dda,0,0,0,0,0x3e163dda,0,0,0,0,0x3e163dda,
0xbe033e03,0,0,0,0,0xbe033e03,0,0,0,0,0xbe033e03,0,0,0,0,0xbe033e03,
0x3ddabe16,0,0,0,0,0x3ddabe16,0,0,0,0,0x3ddabe16,0,0,0,0,0x3ddabe16,
0x3e253da8,0,0,0,0,0x3e253da8,0,0,0,0,0x3e253da8,0,0,0,0,0x3e253da8,
0xbddabe16,0,0,0,0,0xbddabe16,0,0,0,0,0xbddabe16,0,0,0,0,0xbddabe16,
0x3e25bda8,0,0,0,0,0x3e25bda8,0,0,0,0,0x3e25bda8,0,0,0,0,0x3e25bda8,
0xbd653e30,0,0,0,0,0xbd653e30,0,0,0,0,0xbd653e30,0,0,0,0,0xbd653e30,
0xbe37bce8,0,0,0,0,0xbe37bce8,0,0,0,0,0xbe37bce8,0,0,0,0,0xbe37bce8,
0x3d653e30,0,0,0,0,0x3d653e30,0,0,0,0,0x3d653e30,0,0,0,0,0x3d653e30,
0xbe373ce8,0,0,0,0,0xbe373ce8,0,0,0,0,0xbe373ce8,0,0,0,0,0xbe373ce8,
0x3d653e30,0,0,0,0,0x3d653e30,0,0,0,0,0x3d653e30,0,0,0,0,0x3d653e30,
0xbe37bce8,0,0,0,0,0xbe37bce8,0,0,0,0,0xbe37bce8,0,0,0,0,0xbe37bce8,
0xbe390000,0,0,0,0,0xbe390000,0,0,0,0,0xbe390000,0,0,0,0,0xbe390000,
0x3e03be03,0,0,0,0,0x3e03be03,0,0,0,0,0x3e03be03,0,0,0,0,0x3e03be03,
0x3ddabe16,0,0,0,0,0x3ddabe16,0,0,0,0,0x3ddabe16,0,0,0,0,0x3ddabe16,
0x3da83e25,0,0,0,0,0x3da83e25,0,0,0,0,0x3da83e25,0,0,0,0,0x3da83e25,
0x80003e39,0,0,0,0,0x80003e39,0,0,0,0,0x80003e39,0,0,0,0,0x80003e39,
0xbe03be03,0,0,0,0,0xbe03be03,0,0,0,0,0xbe03be03,0,0,0,0,0xbe03be03,
0xbe390000,0,0,0,0,0xbe390000,0,0,0,0,0xbe390000,0,0,0,0,0xbe390000,
0x3da8be25,0,0,0,0,0x3da8be25,0,0,0,0,0x3da8be25,0,0,0,0,0x3da8be25,
0x3e390000,0,0,0,0,0x3e390000,0,0,0,0,0x3e390000,0,0,0,0,0x3e390000,
0xbe033e03,0,0,0,0,0xbe033e03,0,0,0,0,0xbe033e03,0,0,0,0,0xbe033e03,
0x3dda3e16,0,0,0,0,0x3dda3e16,0,0,0,0,0x3dda3e16,0,0,0,0,0x3dda3e16,
0xbe373ce8,0,0,0,0,0xbe373ce8,0,0,0,0,0xbe373ce8,0,0,0,0,0xbe373ce8,
0x8000be39,0,0,0,0,0x8000be39,0,0,0,0,0x8000be39,0,0,0,0,0x8000be39,
0x3e033e03,0,0,0,0,0x3e033e03,0,0,0,0,0x3e033e03,0,0,0,0,0x3e033e03,
0x3d65be30,0,0,0,0,0x3d65be30,0,0,0,0,0x3d65be30,0,0,0,0,0x3d65be30,
0x3e033e03,0,0,0,0,0x3e033e03,0,0,0,0,0x3e033e03,0,0,0,0,0x3e033e03,
0xbe390000,0,0,0,0,0xbe390000,0,0,0,0,0xbe390000,0,0,0,0,0xbe390000,
0x3e03be03,0,0,0,0,0x3e03be03,0,0,0,0,0x3e03be03,0,0,0,0,0x3e03be03,
0xbe303d65,0,0,0,0,0xbe303d65,0,0,0,0,0xbe303d65,0,0,0,0,0xbe303d65,
0x3ce8be37,0,0,0,0,0x3ce8be37,0,0,0,0,0x3ce8be37,0,0,0,0,0x3ce8be37,
0x80003e39,0,0,0,0,0x80003e39,0,0,0,0,0x80003e39,0,0,0,0,0x80003e39,
0xbe03be03,0,0,0,0,0xbe03be03,0,0,0,0,0xbe03be03,0,0,0,0,0xbe03be03,
0x3e163dda,0,0,0,0,0x3e163dda,0,0,0,0,0x3e163dda,0,0,0,0,0x3e163dda,
0xbe253da8,0,0,0,0,0xbe253da8,0,0,0,0,0xbe253da8,0,0,0,0,0xbe253da8,
0x3e390000,0,0,0,0,0x3e390000,0,0,0,0,0x3e390000,0,0,0,0,0x3e390000,
0xbe033e03,0,0,0,0,0xbe033e03,0,0,0,0,0xbe033e03,0,0,0,0,0xbe033e03,
0x3d65be30,0,0,0,0,0x3d65be30,0,0,0,0,0x3d65be30,0,0,0,0,0x3d65be30,
0x3ce83e37,0,0,0,0,0x3ce83e37,0,0,0,0,0x3ce83e37,0,0,0,0,0x3ce83e37,
0x3e163dda,0,0,0,0,0x3e163dda,0,0,0,0,0x3e163dda,0,0,0,0,0x3e163dda,
0xbe25bda8,0,0,0,0,0xbe25bda8,0,0,0,0,0xbe25bda8,0,0,0,0,0xbe25bda8,
0xbddabe16,0,0,0,0,0xbddabe16,0,0,0,0,0xbddabe16,0,0,0,0,0xbddabe16,
0x3e253da8,0,0,0,0,0x3e253da8,0,0,0,0,0x3e253da8,0,0,0,0,0x3e253da8,
0x3e303d65,0,0,0,0,0x3e303d65,0,0,0,0,0x3e303d65,0,0,0,0,0x3e303d65,
0xbe37bce8,0,0,0,0,0xbe37bce8,0,0,0,0,0xbe37bce8,0,0,0,0,0xbe37bce8,
0xbe390000,0,0,0,0,0xbe390000,0,0,0,0,0xbe390000,0,0,0,0,0xbe390000,
0x3e25bda8,0,0,0,0,0x3e25bda8,0,0,0,0,0x3e25bda8,0,0,0,0,0x3e25bda8,
0x3e390000,0,0,0,0,0x3e390000,0,0,0,0,0x3e390000,0,0,0,0,0x3e390000,
0xbe373ce8,0,0,0,0,0xbe373ce8,0,0,0,0,0xbe373ce8,0,0,0,0,0xbe373ce8,
0xbdda3e16,0,0,0,0,0xbdda3e16,0,0,0,0,0xbdda3e16,0,0,0,0,0xbdda3e16,
0x3ce8be37,0,0,0,0,0x3ce8be37,0,0,0,0,0x3ce8be37,0,0,0,0,0x3ce8be37,
0x3e30bd65,0,0,0,0,0x3e30bd65,0,0,0,0,0x3e30bd65,0,0,0,0,0x3e30bd65,
0xbe253da8,0,0,0,0,0xbe253da8,0,0,0,0,0xbe253da8,0,0,0,0,0xbe253da8,
0x3d653e30,0,0,0,0,0x3d653e30,0,0,0,0,0x3d653e30,0,0,0,0,0x3d653e30,
0xbe03be03,0,0,0,0,0xbe03be03,0,0,0,0,0xbe03be03,0,0,0,0,0xbe03be03,
0x3e16bdda,0,0,0,0,0x3e16bdda,0,0,0,0,0x3e16bdda,0,0,0,0,0x3e16bdda,
0xbe033e03,0,0,0,0,0xbe033e03,0,0,0,0,0xbe033e03,0,0,0,0,0xbe033e03,
0x3e303d65,0,0,0,0,0x3e303d65,0,0,0,0,0x3e303d65,0,0,0,0,0x3e303d65,
0xbe373ce8,0,0,0,0,0xbe373ce8,0,0,0,0,0xbe373ce8,0,0,0,0,0xbe373ce8,
0x3ddabe16,0,0,0,0,0x3ddabe16,0,0,0,0,0x3ddabe16,0,0,0,0,0x3ddabe16,
0xbda83e25,0,0,0,0,0xbda83e25,0,0,0,0,0xbda83e25,0,0,0,0,0xbda83e25,
0x3e16bdda,0,0,0,0,0x3e16bdda,0,0,0,0,0x3e16bdda,0,0,0,0,0x3e16bdda,
0xbda83e25,0,0,0,0,0xbda83e25,0,0,0,0,0xbda83e25,0,0,0,0,0xbda83e25,
0x3d65be30,0,0,0,0,0x3d65be30,0,0,0,0,0x3d65be30,0,0,0,0,0x3d65be30,
0xbce83e37,0,0,0,0,0xbce83e37,0,0,0,0,0xbce83e37,0,0,0,0,0xbce83e37,
0,0,0xbe163dda,0,0,0,0,0xbe163dda,0,0,0xbe253da8,0,0,0,0,0xbe253da8,
0,0,0xbe303d65,0,0,0,0,0xbe303d65,0,0,0xbe373ce8,0,0,0,0,0xbe373ce8,
0,0,0xbd65be30,0,0,0,0,0xbd65be30,0,0,0x3ce8be37,0,0,0,0,0x3ce8be37,
0,0,0x3ddabe16,0,0,0,0,0x3ddabe16,0,0,0x3e25bda8,0,0,0,0,0x3e25bda8,
0,0,0xbe390000,0,0,0,0,0xbe390000,0,0,0xbe37bce8,0,0,0,0,0xbe37bce8,
0,0,0xbe30bd65,0,0,0,0,0xbe30bd65,0,0,0xbe25bda8,0,0,0,0,0xbe25bda8,
0,0,0x3e390000,0,0,0,0,0x3e390000,0,0,0x3e253da8,0,0,0,0,0x3e253da8,
0,0,0x3dda3e16,0,0,0,0,0x3dda3e16,0,0,0x3ce83e37,0,0,0,0,0x3ce83e37,
0,0,0xbe16bdda,0,0,0,0,0xbe16bdda,0,0,0xbe03be03,0,0,0,0,0xbe03be03,
0,0,0xbddabe16,0,0,0,0,0xbddabe16,0,0,0xbda8be25,0,0,0,0,0xbda8be25,
0,0,0xbd653e30,0,0,0,0,0xbd653e30,0,0,0xbe033e03,0,0,0,0,0xbe033e03,
0,0,0xbe303d65,0,0,0,0,0xbe303d65,0,0,0xbe37bce8,0,0,0,0,0xbe37bce8,
0,0,0xbd65be30,0,0,0,0,0xbd65be30,0,0,0xbce8be37,0,0,0,0,0xbce8be37,
0,0,0,0,0,0,0,0,0,0,0,0,0,0,0,0,
0,0,0xbe16bdda,0,0,0,0,0xbe16bdda,0,0,0xbda8be25,0,0,0,0,0xbda8be25,
0,0,0,0,0,0,0,0,0,0,0,0,0,0,0,0,
0,0,0x3e390000,0,0,0,0,0x3e390000,0,0,0x3e033e03,0,0,0,0,0x3e033e03,
0,0,0x80003e39,0,0,0,0,0x80003e39,0,0,0xbe033e03,0,0,0,0,0xbe033e03,
0,0,0xbd653e30,0,0,0,0,0xbd653e30,0,0,0xbe373ce8,0,0,0,0,0xbe373ce8,
0,0,0xbddabe16,0,0,0,0,0xbddabe16,0,0,0x3da8be25,0,0,0,0,0x3da8be25,
0,0,0xbe390000,0,0,0,0,0xbe390000,0,0,0xbe03be03,0,0,0,0,0xbe03be03,
0,0,0x8000be39,0,0,0,0,0x8000be39,0,0,0x3e03be03,0,0,0,0,0x3e03be03,
0,0,0x3e390000,0,0,0,0,0x3e390000,0,0,0x3da83e25,0,0,0,0,0x3da83e25,
0,0,0xbdda3e16,0,0,0,0,0xbdda3e16,0,0,0xbe37bce8,0,0,0,0,0xbe37bce8,
0,0,0x3e390000,0,0,0,0,0x3e390000,0,0,0x3e033e03,0,0,0,0,0x3e033e03,
0,0,0x80003e39,0,0,0,0,0x80003e39,0,0,0xbe033e03,0,0,0,0,0xbe033e03,
0,0,0xbd65be30,0,0,0,0,0xbd65be30,0,0,0x3e03be03,0,0,0,0,0x3e03be03,
0,0,0x3e303d65,0,0,0,0,0x3e303d65,0,0,0x3ce83e37,0,0,0,0,0x3ce83e37,
0,0,0xbe390000,0,0,0,0,0xbe390000,0,0,0xbe03be03,0,0,0,0,0xbe03be03,
0,0,0,0,0,0,0,0,0,0,0,0,0,0,0,0,
0,0,0xbe163dda,0,0,0,0,0xbe163dda,0,0,0xbe25bda8,0,0,0,0,0xbe25bda8,
0,0,0,0,0,0,0,0,0,0,0,0,0,0,0,0,
0,0,0xbe16bdda,0,0,0,0,0xbe16bdda,0,0,0x3da8be25,0,0,0,0,0x3da8be25,
0,0,0x3e303d65,0,0,0,0,0x3e303d65,0,0,0xbce83e37,0,0,0,0,0xbce83e37,
0,0,0x3e16bdda,0,0,0,0,0x3e16bdda,0,0,0x3da83e25,0,0,0,0,0x3da83e25,
0,0,0xbe303d65,0,0,0,0,0xbe303d65,0,0,0xbce8be37,0,0,0,0,0xbce8be37,
0,0,0xbe390000,0,0,0,0,0xbe390000,0,0,0xbce8be37,0,0,0,0,0xbce8be37,
0,0,0x3e30bd65,0,0,0,0,0x3e30bd65,0,0,0x3da83e25,0,0,0,0,0x3da83e25,
0,0,0x3e390000,0,0,0,0,0x3e390000,0,0,0xbce83e37,0,0,0,0,0xbce83e37,
0,0,0xbe30bd65,0,0,0,0,0xbe30bd65,0,0,0x3da8be25,0,0,0,0,0x3da8be25,
0,0,0xbe163dda,0,0,0,0,0xbe163dda,0,0,0xbe03be03,0,0,0,0,0xbe03be03,
0,0,0x3ddabe16,0,0,0,0,0x3ddabe16,0,0,0x3e253da8,0,0,0,0,0x3e253da8,
0,0,0x3e163dda,0,0,0,0,0x3e163dda,0,0,0xbe033e03,0,0,0,0,0xbe033e03,
0,0,0xbddabe16,0,0,0,0,0xbddabe16,0,0,0x3e25bda8,0,0,0,0,0x3e25bda8,
0,0,0xbd653e30,0,0,0,0,0xbd653e30,0,0,0xbe37bce8,0,0,0,0,0xbe37bce8,
0,0,0,0,0,0,0,0,0,0,0,0,0,0,0,0,
0,0,0x3d653e30,0,0,0,0,0x3d653e30,0,0,0xbe373ce8,0,0,0,0,0xbe373ce8,
0,0,0,0,0,0,0,0,0,0,0,0,0,0,0,0,
0,0,0x3d653e30,0,0,0,0,0x3d653e30,0,0,0xbe37bce8,0,0,0,0,0xbe37bce8,
0,0,0x3ddabe16,0,0,0,0,0x3ddabe16,0,0,0x3da83e25,0,0,0,0,0x3da83e25,
0,0,0xbe390000,0,0,0,0,0xbe390000,0,0,0x3e03be03,0,0,0,0,0x3e03be03,
0,0,0x80003e39,0,0,0,0,0x80003e39,0,0,0xbe03be03,0,0,0,0,0xbe03be03,
0,0,0xbe390000,0,0,0,0,0xbe390000,0,0,0x3da8be25,0,0,0,0,0x3da8be25,
0,0,0x3dda3e16,0,0,0,0,0x3dda3e16,0,0,0xbe373ce8,0,0,0,0,0xbe373ce8,
0,0,0x3e390000,0,0,0,0,0x3e390000,0,0,0xbe033e03,0,0,0,0,0xbe033e03,
0,0,0x8000be39,0,0,0,0,0x8000be39,0,0,0x3e033e03,0,0,0,0,0x3e033e03,
0,0,0x3d65be30,0,0,0,0,0x3d65be30,0,0,0x3e033e03,0,0,0,0,0x3e033e03,
0,0,0xbe303d65,0,0,0,0,0xbe303d65,0,0,0x3ce8be37,0,0,0,0,0x3ce8be37,
0,0,0xbe390000,0,0,0,0,0xbe390000,0,0,0x3e03be03,0,0,0,0,0x3e03be03,
0,0,0x80003e39,0,0,0,0,0x80003e39,0,0,0xbe03be03,0,0,0,0,0xbe03be03,
0,0,0x3e163dda,0,0,0,0,0x3e163dda,0,0,0xbe253da8,0,0,0,0,0xbe253da8,
0,0,0,0,0,0,0,0,0,0,0,0,0,0,0,0,
0,0,0x3e390000,0,0,0,0,0x3e390000,0,0,0xbe033e03,0,0,0,0,0xbe033e03,
0,0,0,0,0,0,0,0,0,0,0,0,0,0,0,0,
0,0,0x3d65be30,0,0,0,0,0x3d65be30,0,0,0x3ce83e37,0,0,0,0,0x3ce83e37,
0,0,0xbddabe16,0,0,0,0,0xbddabe16,0,0,0x3e253da8,0,0,0,0,0x3e253da8,
0,0,0x3e163dda,0,0,0,0,0x3e163dda,0,0,0xbe25bda8,0,0,0,0,0xbe25bda8,
0,0,0x3e303d65,0,0,0,0,0x3e303d65,0,0,0xbe37bce8,0,0,0,0,0xbe37bce8,
0,0,0xbe390000,0,0,0,0,0xbe390000,0,0,0x3e25bda8,0,0,0,0,0x3e25bda8,
0,0,0xbdda3e16,0,0,0,0,0xbdda3e16,0,0,0x3ce8be37,0,0,0,0,0x3ce8be37,
0,0,0x3e390000,0,0,0,0,0x3e390000,0,0,0xbe373ce8,0,0,0,0,0xbe373ce8,
0,0,0x3e30bd65,0,0,0,0,0x3e30bd65,0,0,0xbe253da8,0,0,0,0,0xbe253da8,
0,0,0x3d653e30,0,0,0,0,0x3d653e30,0,0,0xbe03be03,0,0,0,0,0xbe03be03,
0,0,0x3e303d65,0,0,0,0,0x3e303d65,0,0,0xbe373ce8,0,0,0,0,0xbe373ce8,
0,0,0x3e16bdda,0,0,0,0,0x3e16bdda,0,0,0xbe033e03,0,0,0,0,0xbe033e03,
0,0,0x3ddabe16,0,0,0,0,0x3ddabe16,0,0,0xbda83e25,0,0,0,0,0xbda83e25,
0,0,0x3e16bdda,0,0,0,0,0x3e16bdda,0,0,0xbda83e25,0,0,0,0,0xbda83e25,
0,0,0,0,0,0,0,0,0,0,0,0,0,0,0,0,
0,0,0x3d65be30,0,0,0,0,0x3d65be30,0,0,0xbce83e37,0,0,0,0,0xbce83e37,
0,0,0,0,0,0,0,0,0,0,0,0,0,0,0,0,
};
constexpr unsigned long long COS_PK0 = 0x3f903f9a3fa03fa2ull;
constexpr unsigned long long COS_PK1 = 0x3f133f3e3f653f83ull;
constexpr unsigned long long COS_PK2 = 0x3e4b3ec8ull;

__device__ __forceinline__ void wgmma_ss_n80_z(float (&d)[40], uint64_t da, uint64_t db) {
  asm volatile("{\n.reg .pred p;\nsetp.ne.b32 p, 0, 0;\nwgmma.mma_async.sync.aligned.m64n80k16.f32.bf16.bf16 {%0,%1,%2,%3,%4,%5,%6,%7,%8,%9,%10,%11,%12,%13,%14,%15,%16,%17,%18,%19,%20,%21,%22,%23,%24,%25,%26,%27,%28,%29,%30,%31,%32,%33,%34,%35,%36,%37,%38,%39}, %40, %41, p, 1, 1, 1, 0;\n}\n"
    : "+f"(d[0]), "+f"(d[1]), "+f"(d[2]), "+f"(d[3]), "+f"(d[4]), "+f"(d[5]), "+f"(d[6]), "+f"(d[7]), "+f"(d[8]), "+f"(d[9]), "+f"(d[10]), "+f"(d[11]), "+f"(d[12]), "+f"(d[13]), "+f"(d[14]), "+f"(d[15]), "+f"(d[16]), "+f"(d[17]), "+f"(d[18]), "+f"(d[19]), "+f"(d[20]), "+f"(d[21]), "+f"(d[22]), "+f"(d[23]), "+f"(d[24]), "+f"(d[25]), "+f"(d[26]), "+f"(d[27]), "+f"(d[28]), "+f"(d[29]), "+f"(d[30]), "+f"(d[31]), "+f"(d[32]), "+f"(d[33]), "+f"(d[34]), "+f"(d[35]), "+f"(d[36]), "+f"(d[37]), "+f"(d[38]), "+f"(d[39])
    : "l"(da), "l"(db));
}
__device__ __forceinline__ void wgmma_ss_n80_a(float (&d)[40], uint64_t da, uint64_t db) {
  asm volatile("{\n.reg .pred p;\nsetp.ne.b32 p, 1, 0;\nwgmma.mma_async.sync.aligned.m64n80k16.f32.bf16.bf16 {%0,%1,%2,%3,%4,%5,%6,%7,%8,%9,%10,%11,%12,%13,%14,%15,%16,%17,%18,%19,%20,%21,%22,%23,%24,%25,%26,%27,%28,%29,%30,%31,%32,%33,%34,%35,%36,%37,%38,%39}, %40, %41, p, 1, 1, 1, 0;\n}\n"
    : "+f"(d[0]), "+f"(d[1]), "+f"(d[2]), "+f"(d[3]), "+f"(d[4]), "+f"(d[5]), "+f"(d[6]), "+f"(d[7]), "+f"(d[8]), "+f"(d[9]), "+f"(d[10]), "+f"(d[11]), "+f"(d[12]), "+f"(d[13]), "+f"(d[14]), "+f"(d[15]), "+f"(d[16]), "+f"(d[17]), "+f"(d[18]), "+f"(d[19]), "+f"(d[20]), "+f"(d[21]), "+f"(d[22]), "+f"(d[23]), "+f"(d[24]), "+f"(d[25]), "+f"(d[26]), "+f"(d[27]), "+f"(d[28]), "+f"(d[29]), "+f"(d[30]), "+f"(d[31]), "+f"(d[32]), "+f"(d[33]), "+f"(d[34]), "+f"(d[35]), "+f"(d[36]), "+f"(d[37]), "+f"(d[38]), "+f"(d[39])
    : "l"(da), "l"(db));
}

__device__ __forceinline__ void wgmma_rs_n40_z(float (&d)[20], uint32_t a0, uint32_t a1, uint32_t a2, uint32_t a3, uint64_t db) {
  asm volatile("{\n.reg .pred p;\nsetp.ne.b32 p, 0, 0;\nwgmma.mma_async.sync.aligned.m64n40k16.f32.bf16.bf16 {%0,%1,%2,%3,%4,%5,%6,%7,%8,%9,%10,%11,%12,%13,%14,%15,%16,%17,%18,%19}, {%20,%21,%22,%23}, %24, p, 1, 1, 0;\n}\n"
    : "+f"(d[0]), "+f"(d[1]), "+f"(d[2]), "+f"(d[3]), "+f"(d[4]), "+f"(d[5]), "+f"(d[6]), "+f"(d[7]), "+f"(d[8]), "+f"(d[9]), "+f"(d[10]), "+f"(d[11]), "+f"(d[12]), "+f"(d[13]), "+f"(d[14]), "+f"(d[15]), "+f"(d[16]), "+f"(d[17]), "+f"(d[18]), "+f"(d[19])
    : "r"(a0), "r"(a1), "r"(a2), "r"(a3), "l"(db));
}
__device__ __forceinline__ void wgmma_rs_n40_a(float (&d)[20], uint32_t a0, uint32_t a1, uint32_t a2, uint32_t a3, uint64_t db) {
  asm volatile("{\n.reg .pred p;\nsetp.ne.b32 p, 1, 0;\nwgmma.mma_async.sync.aligned.m64n40k16.f32.bf16.bf16 {%0,%1,%2,%3,%4,%5,%6,%7,%8,%9,%10,%11,%12,%13,%14,%15,%16,%17,%18,%19}, {%20,%21,%22,%23}, %24, p, 1, 1, 0;\n}\n"
    : "+f"(d[0]), "+f"(d[1]), "+f"(d[2]), "+f"(d[3]), "+f"(d[4]), "+f"(d[5]), "+f"(d[6]), "+f"(d[7]), "+f"(d[8]), "+f"(d[9]), "+f"(d[10]), "+f"(d[11]), "+f"(d[12]), "+f"(d[13]), "+f"(d[14]), "+f"(d[15]), "+f"(d[16]), "+f"(d[17]), "+f"(d[18]), "+f"(d[19])
    : "r"(a0), "r"(a1), "r"(a2), "r"(a3), "l"(db));
}

__device__ __forceinline__ void wgmma_rs_n128_z(float (&d)[64], uint32_t a0, uint32_t a1, uint32_t a2, uint32_t a3, uint64_t db) {
  asm volatile("{\n.reg .pred p;\nsetp.ne.b32 p, 0, 0;\nwgmma.mma_async.sync.aligned.m64n128k16.f32.bf16.bf16 {%0,%1,%2,%3,%4,%5,%6,%7,%8,%9,%10,%11,%12,%13,%14,%15,%16,%17,%18,%19,%20,%21,%22,%23,%24,%25,%26,%27,%28,%29,%30,%31,%32,%33,%34,%35,%36,%37,%38,%39,%40,%41,%42,%43,%44,%45,%46,%47,%48,%49,%50,%51,%52,%53,%54,%55,%56,%57,%58,%59,%60,%61,%62,%63}, {%64,%65,%66,%67}, %68, p, 1, 1, 1;\n}\n"
    : "+f"(d[0]), "+f"(d[1]), "+f"(d[2]), "+f"(d[3]), "+f"(d[4]), "+f"(d[5]), "+f"(d[6]), "+f"(d[7]), "+f"(d[8]), "+f"(d[9]), "+f"(d[10]), "+f"(d[11]), "+f"(d[12]), "+f"(d[13]), "+f"(d[14]), "+f"(d[15]), "+f"(d[16]), "+f"(d[17]), "+f"(d[18]), "+f"(d[19]), "+f"(d[20]), "+f"(d[21]), "+f"(d[22]), "+f"(d[23]), "+f"(d[24]), "+f"(d[25]), "+f"(d[26]), "+f"(d[27]), "+f"(d[28]), "+f"(d[29]), "+f"(d[30]), "+f"(d[31]), "+f"(d[32]), "+f"(d[33]), "+f"(d[34]), "+f"(d[35]), "+f"(d[36]), "+f"(d[37]), "+f"(d[38]), "+f"(d[39]), "+f"(d[40]), "+f"(d[41]), "+f"(d[42]), "+f"(d[43]), "+f"(d[44]), "+f"(d[45]), "+f"(d[46]), "+f"(d[47]), "+f"(d[48]), "+f"(d[49]), "+f"(d[50]), "+f"(d[51]), "+f"(d[52]), "+f"(d[53]), "+f"(d[54]), "+f"(d[55]), "+f"(d[56]), "+f"(d[57]), "+f"(d[58]), "+f"(d[59]), "+f"(d[60]), "+f"(d[61]), "+f"(d[62]), "+f"(d[63])
    : "r"(a0), "r"(a1), "r"(a2), "r"(a3), "l"(db));
}
__device__ __forceinline__ void wgmma_rs_n128_a(float (&d)[64], uint32_t a0, uint32_t a1, uint32_t a2, uint32_t a3, uint64_t db) {
  asm volatile("{\n.reg .pred p;\nsetp.ne.b32 p, 1, 0;\nwgmma.mma_async.sync.aligned.m64n128k16.f32.bf16.bf16 {%0,%1,%2,%3,%4,%5,%6,%7,%8,%9,%10,%11,%12,%13,%14,%15,%16,%17,%18,%19,%20,%21,%22,%23,%24,%25,%26,%27,%28,%29,%30,%31,%32,%33,%34,%35,%36,%37,%38,%39,%40,%41,%42,%43,%44,%45,%46,%47,%48,%49,%50,%51,%52,%53,%54,%55,%56,%57,%58,%59,%60,%61,%62,%63}, {%64,%65,%66,%67}, %68, p, 1, 1, 1;\n}\n"
    : "+f"(d[0]), "+f"(d[1]), "+f"(d[2]), "+f"(d[3]), "+f"(d[4]), "+f"(d[5]), "+f"(d[6]), "+f"(d[7]), "+f"(d[8]), "+f"(d[9]), "+f"(d[10]), "+f"(d[11]), "+f"(d[12]), "+f"(d[13]), "+f"(d[14]), "+f"(d[15]), "+f"(d[16]), "+f"(d[17]), "+f"(d[18]), "+f"(d[19]), "+f"(d[20]), "+f"(d[21]), "+f"(d[22]), "+f"(d[23]), "+f"(d[24]), "+f"(d[25]), "+f"(d[26]), "+f"(d[27]), "+f"(d[28]), "+f"(d[29]), "+f"(d[30]), "+f"(d[31]), "+f"(d[32]), "+f"(d[33]), "+f"(d[34]), "+f"(d[35]), "+f"(d[36]), "+f"(d[37]), "+f"(d[38]), "+f"(d[39]), "+f"(d[40]), "+f"(d[41]), "+f"(d[42]), "+f"(d[43]), "+f"(d[44]), "+f"(d[45]), "+f"(d[46]), "+f"(d[47]), "+f"(d[48]), "+f"(d[49]), "+f"(d[50]), "+f"(d[51]), "+f"(d[52]), "+f"(d[53]), "+f"(d[54]), "+f"(d[55]), "+f"(d[56]), "+f"(d[57]), "+f"(d[58]), "+f"(d[59]), "+f"(d[60]), "+f"(d[61]), "+f"(d[62]), "+f"(d[63])
    : "r"(a0), "r"(a1), "r"(a2), "r"(a3), "l"(db));
}

__device__ __forceinline__ void wgmma_rs_n32_z(float (&d)[16], uint32_t a0, uint32_t a1, uint32_t a2, uint32_t a3, uint64_t db) {
  asm volatile("{\n.reg .pred p;\nsetp.ne.b32 p, 0, 0;\nwgmma.mma_async.sync.aligned.m64n32k16.f32.bf16.bf16 {%0,%1,%2,%3,%4,%5,%6,%7,%8,%9,%10,%11,%12,%13,%14,%15}, {%16,%17,%18,%19}, %20, p, 1, 1, 0;\n}\n"
    : "+f"(d[0]), "+f"(d[1]), "+f"(d[2]), "+f"(d[3]), "+f"(d[4]), "+f"(d[5]), "+f"(d[6]), "+f"(d[7]), "+f"(d[8]), "+f"(d[9]), "+f"(d[10]), "+f"(d[11]), "+f"(d[12]), "+f"(d[13]), "+f"(d[14]), "+f"(d[15])
    : "r"(a0), "r"(a1), "r"(a2), "r"(a3), "l"(db));
}
__device__ __forceinline__ void wgmma_rs_n32_a(float (&d)[16], uint32_t a0, uint32_t a1, uint32_t a2, uint32_t a3, uint64_t db) {
  asm volatile("{\n.reg .pred p;\nsetp.ne.b32 p, 1, 0;\nwgmma.mma_async.sync.aligned.m64n32k16.f32.bf16.bf16 {%0,%1,%2,%3,%4,%5,%6,%7,%8,%9,%10,%11,%12,%13,%14,%15}, {%16,%17,%18,%19}, %20, p, 1, 1, 0;\n}\n"
    : "+f"(d[0]), "+f"(d[1]), "+f"(d[2]), "+f"(d[3]), "+f"(d[4]), "+f"(d[5]), "+f"(d[6]), "+f"(d[7]), "+f"(d[8]), "+f"(d[9]), "+f"(d[10]), "+f"(d[11]), "+f"(d[12]), "+f"(d[13]), "+f"(d[14]), "+f"(d[15])
    : "r"(a0), "r"(a1), "r"(a2), "r"(a3), "l"(db));
}

__device__ __forceinline__ void wgmma_rs_n64_z(float (&d)[32], uint32_t a0, uint32_t a1, uint32_t a2, uint32_t a3, uint64_t db) {
  asm volatile("{\n.reg .pred p;\nsetp.ne.b32 p, 0, 0;\nwgmma.mma_async.sync.aligned.m64n64k16.f32.bf16.bf16 {%0,%1,%2,%3,%4,%5,%6,%7,%8,%9,%10,%11,%12,%13,%14,%15,%16,%17,%18,%19,%20,%21,%22,%23,%24,%25,%26,%27,%28,%29,%30,%31}, {%32,%33,%34,%35}, %36, p, 1, 1, 0;\n}\n"
    : "+f"(d[0]), "+f"(d[1]), "+f"(d[2]), "+f"(d[3]), "+f"(d[4]), "+f"(d[5]), "+f"(d[6]), "+f"(d[7]), "+f"(d[8]), "+f"(d[9]), "+f"(d[10]), "+f"(d[11]), "+f"(d[12]), "+f"(d[13]), "+f"(d[14]), "+f"(d[15]), "+f"(d[16]), "+f"(d[17]), "+f"(d[18]), "+f"(d[19]), "+f"(d[20]), "+f"(d[21]), "+f"(d[22]), "+f"(d[23]), "+f"(d[24]), "+f"(d[25]), "+f"(d[26]), "+f"(d[27]), "+f"(d[28]), "+f"(d[29]), "+f"(d[30]), "+f"(d[31])
    : "r"(a0), "r"(a1), "r"(a2), "r"(a3), "l"(db));
}
__device__ __forceinline__ void wgmma_rs_n64_a(float (&d)[32], uint32_t a0, uint32_t a1, uint32_t a2, uint32_t a3, uint64_t db) {
  asm volatile("{\n.reg .pred p;\nsetp.ne.b32 p, 1, 0;\nwgmma.mma_async.sync.aligned.m64n64k16.f32.bf16.bf16 {%0,%1,%2,%3,%4,%5,%6,%7,%8,%9,%10,%11,%12,%13,%14,%15,%16,%17,%18,%19,%20,%21,%22,%23,%24,%25,%26,%27,%28,%29,%30,%31}, {%32,%33,%34,%35}, %36, p, 1, 1, 0;\n}\n"
    : "+f"(d[0]), "+f"(d[1]), "+f"(d[2]), "+f"(d[3]), "+f"(d[4]), "+f"(d[5]), "+f"(d[6]), "+f"(d[7]), "+f"(d[8]), "+f"(d[9]), "+f"(d[10]), "+f"(d[11]), "+f"(d[12]), "+f"(d[13]), "+f"(d[14]), "+f"(d[15]), "+f"(d[16]), "+f"(d[17]), "+f"(d[18]), "+f"(d[19]), "+f"(d[20]), "+f"(d[21]), "+f"(d[22]), "+f"(d[23]), "+f"(d[24]), "+f"(d[25]), "+f"(d[26]), "+f"(d[27]), "+f"(d[28]), "+f"(d[29]), "+f"(d[30]), "+f"(d[31])
    : "r"(a0), "r"(a1), "r"(a2), "r"(a3), "l"(db));
}

__device__ __forceinline__ void wgmma_ss_n32_z(float (&d)[16], uint64_t da, uint64_t db) {
  asm volatile("{\n.reg .pred p;\nsetp.ne.b32 p, 0, 0;\nwgmma.mma_async.sync.aligned.m64n32k16.f32.bf16.bf16 {%0,%1,%2,%3,%4,%5,%6,%7,%8,%9,%10,%11,%12,%13,%14,%15}, %16, %17, p, 1, 1, 1, 0;\n}\n"
    : "+f"(d[0]), "+f"(d[1]), "+f"(d[2]), "+f"(d[3]), "+f"(d[4]), "+f"(d[5]), "+f"(d[6]), "+f"(d[7]), "+f"(d[8]), "+f"(d[9]), "+f"(d[10]), "+f"(d[11]), "+f"(d[12]), "+f"(d[13]), "+f"(d[14]), "+f"(d[15])
    : "l"(da), "l"(db));
}
__device__ __forceinline__ void wgmma_ss_n32_a(float (&d)[16], uint64_t da, uint64_t db) {
  asm volatile("{\n.reg .pred p;\nsetp.ne.b32 p, 1, 0;\nwgmma.mma_async.sync.aligned.m64n32k16.f32.bf16.bf16 {%0,%1,%2,%3,%4,%5,%6,%7,%8,%9,%10,%11,%12,%13,%14,%15}, %16, %17, p, 1, 1, 1, 0;\n}\n"
    : "+f"(d[0]), "+f"(d[1]), "+f"(d[2]), "+f"(d[3]), "+f"(d[4]), "+f"(d[5]), "+f"(d[6]), "+f"(d[7]), "+f"(d[8]), "+f"(d[9]), "+f"(d[10]), "+f"(d[11]), "+f"(d[12]), "+f"(d[13]), "+f"(d[14]), "+f"(d[15])
    : "l"(da), "l"(db));
}

__device__ __forceinline__ void wgmma_ss_n40_z(float (&d)[20], uint64_t da, uint64_t db) {
  asm volatile("{\n.reg .pred p;\nsetp.ne.b32 p, 0, 0;\nwgmma.mma_async.sync.aligned.m64n40k16.f32.bf16.bf16 {%0,%1,%2,%3,%4,%5,%6,%7,%8,%9,%10,%11,%12,%13,%14,%15,%16,%17,%18,%19}, %20, %21, p, 1, 1, 1, 0;\n}\n"
    : "+f"(d[0]), "+f"(d[1]), "+f"(d[2]), "+f"(d[3]), "+f"(d[4]), "+f"(d[5]), "+f"(d[6]), "+f"(d[7]), "+f"(d[8]), "+f"(d[9]), "+f"(d[10]), "+f"(d[11]), "+f"(d[12]), "+f"(d[13]), "+f"(d[14]), "+f"(d[15]), "+f"(d[16]), "+f"(d[17]), "+f"(d[18]), "+f"(d[19])
    : "l"(da), "l"(db));
}
__device__ __forceinline__ void wgmma_ss_n40_a(float (&d)[20], uint64_t da, uint64_t db) {
  asm volatile("{\n.reg .pred p;\nsetp.ne.b32 p, 1, 0;\nwgmma.mma_async.sync.aligned.m64n40k16.f32.bf16.bf16 {%0,%1,%2,%3,%4,%5,%6,%7,%8,%9,%10,%11,%12,%13,%14,%15,%16,%17,%18,%19}, %20, %21, p, 1, 1, 1, 0;\n}\n"
    : "+f"(d[0]), "+f"(d[1]), "+f"(d[2]), "+f"(d[3]), "+f"(d[4]), "+f"(d[5]), "+f"(d[6]), "+f"(d[7]), "+f"(d[8]), "+f"(d[9]), "+f"(d[10]), "+f"(d[11]), "+f"(d[12]), "+f"(d[13]), "+f"(d[14]), "+f"(d[15]), "+f"(d[16]), "+f"(d[17]), "+f"(d[18]), "+f"(d[19])
    : "l"(da), "l"(db));
}

constexpr int NSM = 132, NH = 66;
constexpr int S0 = 0, S1 = 51200, S2 = 102400;
constexpr int C1 = 153600, C3 = C1, RG = C1 + 18432;
constexpr int WP = RG, TBL = RG + 28672, WS2 = RG + 30720;
constexpr int BARS = RG + 49152;
__host__ __device__ constexpr int wst_off(int i) { return i < 12 ? S2 + i * 4096 : WS2 + (i - 12) * 4096; }
constexpr int NBAR = 280;
constexpr int REL = BARS + NBAR * 8;
constexpr int SMEM_BYTES = REL + 16;
constexpr int B_XF = 0, B_CF1 = 15, B_CF3 = 16, B_WF = 17  , B_P1D = 18, B_REL = 21, B_ROLE = 22, B_SIG = 24;
constexpr int B_RF = 32, B_RE = 46, B_YF = 60, B_WRD = 75, B_SFREE = 89, B_WCH = 131, B_RDY = 136, B_WE = 205, B_WL = 217, B_FIN = 229, B_TOK = 232;
constexpr int R_P2 = 15, R_P3 = 57;
constexpr int CNT_P1 = 0, CNT_P2 = 4, CNT_W = 8, CNT_RANK = 9, NCLS = 10, CNT_DONE = 0, CNT_REL = 1, NCNT = 2;
constexpr int SIG_W = 0, SIG_P1 = 1, SIG_P2 = 4;
#define T1MASK 0x3e00
#define T2MASK 0x1f00

__device__ uint4 g_scr[(14 << 21) / 16];
__device__ uint4 g_wf[200 * 72 * 32];
__device__ unsigned g_cnt[NCNT * 32];
__device__ __forceinline__ int slot_line(int chunk, int pg, int cls) {
    return (pg & 1) << 6 | (pg >> 1) << 9 | (chunk & 1) << 10 | (chunk >> 1) << 12 | ((pg ^ (pg >> 1) ^ chunk ^ (chunk >> 1) ^ cls) & 1) << 5;
}
__device__ __forceinline__ int phi_line(int phi, uint32_t rel) {
    return (phi >> 4) << 14 | (phi & 3) << 7 | ((phi >> 2) & 1) << 11 | ((phi >> 3) & 1) << 13 | ((rel >> (phi >> 4)) & 1) << 5;
}
__device__ __forceinline__ int extra_mask(int rk) { return rk < 58 ? 0 : rk < 60 ? 2 : rk < 62 ? 1 : rk < 64 ? 4 : 8; }
__device__ __forceinline__ int wslot(int pc) {
    return (int)((0x576476503421ull >> (4 * pc)) & 3) * 12288 + (((0x576476503421ull >> (4 * pc)) & 4) ? S0 : RG);
}
__device__ __forceinline__ int xslot(int n) { return ((n & 4) ? S2 : RG) + ((n + 1) & 3) * 12288; }
__device__ __forceinline__ int extra_phi(int rk) { return 198 + (rk & 1); }
__host__ __device__ constexpr int quad_off(int Q) { return (Q >> 2) * 4096 + (Q & 3) * 512; }

struct Maps { CUtensorMap w, x34, x6, x28, wst, f16, f8, y4, y2; };
struct Ptrs { char* scr; const char* wf; const void* tab1; const void* tab3; unsigned* cnt; const char* x; };

__device__ __forceinline__ uint32_t smem_u32(const void* p) { return (uint32_t)__cvta_generic_to_shared(p); }
__device__ __forceinline__ void mbar_wait(uint32_t bar) {
    uint32_t ok, it = 0;
    do {
        asm volatile("{\n.reg .pred p;\nmbarrier.try_wait.parity.shared::cta.b64 p, [%1], 0;\nselp.u32 %0, 1, 0, p;\n}" : "=r"(ok) : "r"(bar) : "memory");
        if (++it > (1u << 22)) break;
    } while (!ok);
}
__device__ __forceinline__ bool mbar_test(uint32_t bar) {
    uint32_t ok;
    asm volatile("{\n.reg .pred p;\nmbarrier.test_wait.parity.shared::cta.b64 p, [%1], 0;\nselp.u32 %0, 1, 0, p;\n}" : "=r"(ok) : "r"(bar) : "memory");
    return ok;
}
__device__ __forceinline__ void fence_async() { asm volatile("fence.proxy.async;" ::: "memory"); }
__device__ __forceinline__ void fence_async_smem() { asm volatile("fence.proxy.async.shared::cta;" ::: "memory"); }
#define ELECT "{\n.reg .pred p;\nelect.sync _|p, 0xffffffff;\n@p "
__device__ __forceinline__ void e_arrive(uint32_t bar) { asm volatile(ELECT "mbarrier.arrive.shared::cta.b64 _, [%0];\n}" :: "r"(bar) : "memory"); }
__device__ __forceinline__ void e_expect(uint32_t bar, uint32_t bytes) { asm volatile(ELECT "mbarrier.arrive.expect_tx.shared::cta.b64 _, [%0], %1;\n}" :: "r"(bar), "r"(bytes) : "memory"); }
__device__ __forceinline__ void e_g2s(uint32_t dst, const void* src, uint32_t bytes, uint32_t bar) {
    asm volatile(ELECT "cp.async.bulk.shared::cluster.global.mbarrier::complete_tx::bytes [%0], [%1], %2, [%3];\n}" :: "r"(dst), "l"(src), "r"(bytes), "r"(bar) : "memory");
}
__device__ __forceinline__ void e_s2g(void* dst, uint32_t src, uint32_t bytes) {
    asm volatile(ELECT "cp.async.bulk.global.shared::cta.bulk_group [%0], [%1], %2;\n}" :: "l"(dst), "r"(src), "r"(bytes) : "memory");
}
__device__ __forceinline__ void e_ld3(uint32_t dst, const CUtensorMap* m, int c0, int c1, int c2, uint32_t bar) {
    asm volatile(ELECT "cp.async.bulk.tensor.3d.shared::cluster.global.mbarrier::complete_tx::bytes [%0], [%1, {%3, %4, %5}], [%2];\n}"
                 :: "r"(dst), "l"(m), "r"(bar), "r"(c0), "r"(c1), "r"(c2) : "memory");
}
__device__ __forceinline__ void e_ld4(uint32_t dst, const CUtensorMap* m, int c0, int c3, uint32_t bar) {
    asm volatile(ELECT "cp.async.bulk.tensor.4d.shared::cluster.global.mbarrier::complete_tx::bytes [%0], [%1, {%3, %5, %5, %4}], [%2];\n}"
                 :: "r"(dst), "l"(m), "r"(bar), "r"(c0), "r"(c3), "r"(0) : "memory");
}
__device__ __forceinline__ void e_st3(const CUtensorMap* m, uint32_t src, int c0, int c1, int c2) {
    asm volatile(ELECT "cp.async.bulk.tensor.3d.global.shared::cta.bulk_group [%0, {%2, %3, %4}], [%1];\n}" :: "l"(m), "r"(src), "r"(c0), "r"(c1), "r"(c2) : "memory");
}
__device__ __forceinline__ void e_ld5(uint32_t dst, const CUtensorMap* m, int c4, uint32_t bar) {
    asm volatile(ELECT "cp.async.bulk.tensor.5d.shared::cluster.global.mbarrier::complete_tx::bytes [%0], [%1, {%4, %4, %4, %4, %3}], [%2];\n}"
                 :: "r"(dst), "l"(m), "r"(bar), "r"(c4), "r"(0) : "memory");
}
__device__ __forceinline__ void e_st5(const CUtensorMap* m, uint32_t src, int c4) {
    asm volatile(ELECT "cp.async.bulk.tensor.5d.global.shared::cta.bulk_group [%0, {%3, %3, %3, %3, %2}], [%1];\n}" :: "l"(m), "r"(src), "r"(c4), "r"(0) : "memory");
}
__device__ __forceinline__ void bulk_commit() { asm volatile("cp.async.bulk.commit_group;" ::: "memory"); }
template <int N> __device__ __forceinline__ void bulk_wait() { asm volatile("cp.async.bulk.wait_group %0;" :: "n"(N) : "memory"); }
template <int N> __device__ __forceinline__ void bulk_wait_read() { asm volatile("cp.async.bulk.wait_group.read %0;" :: "n"(N) : "memory"); }
__device__ __forceinline__ void wg_bar(int id) { asm volatile("bar.sync %0, 128;" :: "r"(id) : "memory"); }
__device__ __forceinline__ void bb_break(uint32_t v) { asm volatile("{\n.reg .pred p;\nsetp.eq.u32 p, %0, 0x7fc17fc1;\n@p nanosleep.u32 0;\n}" :: "r"(v) : "memory"); }
__device__ __forceinline__ uint32_t uni(uint32_t v) { return __shfl_sync(0xffffffffu, v, 0); }
__device__ __forceinline__ char* cls_cnt(char* scr, int cls) { return scr + slot_line(3, 2, cls) * 128; }
__device__ __forceinline__ uint32_t cnt_wait(const void* p, unsigned target) {
    uint32_t v = 0;
#pragma unroll 1
    for (unsigned it = 0; it < (1u << 22) && v < target; it++) {
        asm volatile("ld.acquire.gpu.global.u32 %0, [%1];" : "=r"(v) : "l"(p) : "memory");
        v = uni(v);
    }
    asm volatile("fence.proxy.async.global;" ::: "memory");
    return v;
}
__device__ __forceinline__ void wg_fence() { asm volatile("wgmma.fence.sync.aligned;" ::: "memory"); }
__device__ __forceinline__ void wg_commit() { asm volatile("wgmma.commit_group.sync.aligned;" ::: "memory"); }
template <int N> __device__ __forceinline__ void wg_wait() { asm volatile("wgmma.wait_group.sync.aligned %0;" :: "n"(N) : "memory"); }
template <int N> __device__ __forceinline__ void reg_fence(float (&d)[N]) {
#pragma unroll
    for (int i = 0; i < N; i++) asm volatile("" : "+f"(d[i]) :: "memory");
}
template <int N> __device__ __forceinline__ void zero(float (&d)[N]) {
#pragma unroll
    for (int i = 0; i < N; i++) d[i] = 0.f;
}
__device__ __forceinline__ uint32_t pack2(float lo, float hi) {
    uint32_t r; asm volatile("cvt.rn.bf16x2.f32 %0, %1, %2;" : "=r"(r) : "f"(hi), "f"(lo)); return r;
}
__device__ __forceinline__ void stm4(uint32_t a, uint32_t r0, uint32_t r1, uint32_t r2, uint32_t r3) {
    asm volatile("stmatrix.sync.aligned.m8n8.x4.trans.shared.b16 [%0], {%1,%2,%3,%4};" :: "r"(a), "r"(r0), "r"(r1), "r"(r2), "r"(r3) : "memory");
}
__device__ __forceinline__ void stm2(uint32_t a, uint32_t r0, uint32_t r1) {
    asm volatile("stmatrix.sync.aligned.m8n8.x2.trans.shared.b16 [%0], {%1,%2};" :: "r"(a), "r"(r0), "r"(r1) : "memory");
}
struct Desc {
    uint32_t lo, hi;
    __device__ __forceinline__ operator uint64_t() const { return ((uint64_t)hi << 32) | lo; }
    __device__ __forceinline__ Desc operator+(uint32_t o) const { return Desc{lo + o, hi}; }
    __device__ __forceinline__ Desc operator^(uint32_t o) const { return Desc{lo ^ o, hi}; }
};
__device__ __forceinline__ Desc mkdesc(uint32_t addr, uint32_t lbo, uint32_t sbo, uint32_t swz) {
    return Desc{((addr & 0x3FFFF) >> 4) | ((lbo >> 4) << 16), (sbo >> 4) | (swz << 30)};
}
__device__ __forceinline__ uint32_t cos_bits(int k) {
    if (k > 20) k = 40 - k;
    const bool neg = k > 10;
    if (neg) k = 20 - k;
    const unsigned long long pk = k < 4 ? COS_PK0 : k < 8 ? COS_PK1 : COS_PK2;
    return (uint32_t)((pk >> (16 * (k & 3))) & 0xffff) ^ (neg ? 0x8000u : 0u);
}

__device__ __forceinline__ void task_w(int wg, int k, uint32_t sb) {
    const int tid = threadIdx.x & 127, w = uni(tid >> 5), lane = tid & 31, q = lane & 3;
    const int tb = 14 * k, t1 = min(tb + 14, 1800), cb0 = tb / 25;
    float acc[64];
    zero(acc);
    const int oc0 = tb - 25 * cb0, Lt = t1 - tb, L0 = min(Lt, 25 - oc0), n0 = (L0 + 3) >> 2;
    uint32_t a[2][4][4];
    auto gen = [&](uint32_t (&a)[4][4], int at) {
        const int phi = 8 * ((at < n0 ? oc0 + 4 * at : 4 * (at - n0)) + w) + (lane >> 2), f = (phi * 205) >> 12;
        const uint32_t ca = 8 * f + 4, cw = (phi - 20 * f) * 8, p0 = sb + TBL + cw * 2 * q;
#pragma unroll
        for (int kh = 0; kh < 7; kh++) {
            uint32_t v0, v1;
            asm volatile("ld.shared.u32 %0, [%1];" : "=r"(v0) : "r"(p0 + ca * kh));
            asm volatile("ld.shared.u32 %0, [%1];" : "=r"(v1) : "r"(p0 + cw + ca * kh));
            const int h = kh == 6 ? 1 : kh & 1;
            a[kh >> 1][2 * h] = __byte_perm(v0, v1, 0x5410);
            a[kh >> 1][2 * h + 1] = __byte_perm(v0, v1, 0x7632);
        }
        a[3][0] = 0; a[3][1] = 0;
    };
    gen(a[0], wg);
    if (wg) gen(a[1], wg + 2);
#pragma unroll 1
    for (int n = 0; n < 2; n++) {
        const int at = wg + 2 * n, i0 = at < n0 ? 4 * at : L0 + 4 * (at - n0), cnt = (at < n0 ? L0 : Lt) - i0, cb = cb0 + (at >= n0);
        if (cnt <= 0 || (n && !wg)) break;
        if (n) {
#pragma unroll
            for (int j = 0; j < 16; j++) a[0][j >> 2][j & 3] = a[1][j >> 2][j & 3];
        }
        const Desc dB = mkdesc(sb + WP + (cb - cb0) * 14336, 3584, 512, 2);
        if (at) mbar_wait(sb + BARS + 8 * (B_WCH + at - 1));
        mbar_wait(sb + BARS + 8 * (B_WF + 2 * (cb - cb0)));
        wg_fence();
        wgmma_rs_n128_z(acc, a[0][0][0], a[0][0][1], a[0][0][2], a[0][0][3], dB);
        wgmma_rs_n128_a(acc, a[0][1][0], a[0][1][1], a[0][1][2], a[0][1][3], dB + (uint32_t)(16 * 64 >> 4));
        wgmma_rs_n128_a(acc, a[0][2][0], a[0][2][1], a[0][2][2], a[0][2][3], dB + (uint32_t)(32 * 64 >> 4));
        wgmma_rs_n128_a(acc, a[0][3][0], a[0][3][1], a[0][3][2], a[0][3][3], dB + (uint32_t)(40 * 64 >> 4));
        wg_commit();
        wg_wait<0>();
        reg_fence(acc);
        e_arrive(sb + BARS + 8 * (B_WCH + at));
        if (w < cnt) {
            const uint32_t dst = sb + wst_off(i0 + w) + (lane >> 2) * 512 + (lane & 4) * 16 + ((q ^ cb) & 3) * 16;
#pragma unroll
            for (int j = 0; j < 4; j++)
#pragma unroll
                for (int e = 0; e < 2; e++)
                    asm volatile("st.shared.v4.u32 [%0], {%1,%2,%3,%4};" :: "r"((dst ^ (e * 64)) + j * 128),
                                 "r"(pack2(acc[4 * j + e], acc[16 + 4 * j + e])), "r"(pack2(acc[4 * j + 2 + e], acc[16 + 4 * j + 2 + e])),
                                 "r"(pack2(acc[32 + 4 * j + e], acc[48 + 4 * j + e])), "r"(pack2(acc[32 + 4 * j + 2 + e], acc[48 + 4 * j + 2 + e])) : "memory");
            fence_async_smem();
            e_arrive(sb + BARS + 8 * (B_WRD + i0 + w));
        }
    }
}

__device__ __forceinline__ void task_p1(int wg, int pair, uint32_t sb) {
    const int tid = threadIdx.x & 127, w = tid >> 5, lane = tid & 31;
    const uint32_t buf = sb + wg * 51200, bars = sb + BARS;
    uint32_t fr[5][10][2];
    float A[40], d[20];
    zero(A);
    {
        const Desc dA = mkdesc(buf, 3584, 512, 2), dB = mkdesc(sb + C1, 128, 256, 0);
        auto issue = [&](int g, float (&d)[40]) {
            mbar_wait(bars + 8 * (B_XF + wg * 5 + g));
            wg_fence();
            wgmma_ss_n80_z(d, dA + (uint32_t)(g * 8704 >> 4), dB);
#pragma unroll
            for (int j = 1; j < 5; j++) wgmma_ss_n80_a(d, dA + (uint32_t)((g * 8704 + j * 1024) >> 4), dB + (uint32_t)(j * 2560 >> 4));
            wg_commit();
        };
        auto pack = [&](int g, float (&d)[40]) {
            reg_fence(d);
#pragma unroll
            for (int f = 0; f < 10; f++) {
                fr[g][f][0] = pack2(d[4 * f], d[4 * f + 1]);
                fr[g][f][1] = pack2(d[4 * f + 2], d[4 * f + 3]);
            }
        };
        mbar_wait(bars + 8 * B_CF1);
#pragma unroll
        for (int g = 0; g < 4; g++) { issue(g, A); wg_wait<0>(); pack(g, A); }
        zero(d);
        mbar_wait(bars + 8 * (B_XF + wg * 5 + 4));
#pragma unroll
        for (int h = 0; h < 2; h++) {
            wg_fence();
            wgmma_ss_n40_z(d, dA + (uint32_t)(4 * 8704 >> 4), dB + (uint32_t)(h * 1280 >> 4));
#pragma unroll
            for (int j = 1; j < 5; j++) wgmma_ss_n40_a(d, dA + (uint32_t)((4 * 8704 + j * 1024) >> 4), dB + (uint32_t)((j * 2560 + h * 1280) >> 4));
            wg_commit(); wg_wait<0>(); reg_fence(d);
#pragma unroll
            for (int f = 0; f < 5; f++) { fr[4][5 * h + f][0] = pack2(d[4 * f], d[4 * f + 1]); fr[4][5 * h + f][1] = pack2(d[4 * f + 2], d[4 * f + 3]); }
        }
    }
    bb_break(sb);
    wg_bar(1 + wg);
    {
        const Desc dB = mkdesc(sb + C1 + 12800, 128, 256, 0);
        const int i = lane & 7, mi = lane >> 3, th = w >> 1, tz = (2 * pair + th) & 3;
        const uint32_t s0 = buf + (i >> 1) * 128 + (i & 1) * 64 + (((2 * (w & 1) + (mi & 1)) ^ tz ^ (i >> 1)) << 4);
        const uint32_t sA = s0 + th * 2048 + (mi >> 1) * 512, sB = s0 + th * 2048 + (mi >> 1) * 2560, sC = s0 + th * 1024 + (mi >> 1) * 512;
        auto issue = [&](int f, float (&d)[20]) {
            wg_fence();
            wgmma_rs_n40_z(d, fr[0][f][0], fr[0][f][1], fr[1][f][0], fr[1][f][1], dB);
            wgmma_rs_n40_a(d, fr[2][f][0], fr[2][f][1], fr[3][f][0], fr[3][f][1], dB + (uint32_t)(1280 >> 4));
            wgmma_rs_n40_a(d, fr[4][f % 5][0], fr[4][f % 5][1], fr[4][f % 5 + 5][0], fr[4][f % 5 + 5][1], dB + (uint32_t)((2560 + (f / 5) * 1280) >> 4));
            wg_commit();
        };
#pragma unroll
        for (int f = 0; f < 10; f++) {
            issue(f, d);
            if (f && !(f & 1)) { fence_async_smem(); e_arrive(bars + 8 * (B_RDY + wg * 5 + (f >> 1) - 1)); }
            wg_wait<0>(); reg_fence(d);
            const int Q = 5 * f;
            stm4(((Q & 3) == 3 ? sB : sA) + quad_off(Q), pack2(d[0], d[1]), pack2(d[2], d[3]), pack2(d[4], d[5]), pack2(d[6], d[7]));
            stm2(sA + quad_off(Q + 2), pack2(d[8], d[9]), pack2(d[10], d[11]));
            stm4((f == 9 ? sC : ((Q + 3) & 3) == 3 ? sB : sA) + quad_off(Q + 3), pack2(d[12], d[13]), pack2(d[14], d[15]), pack2(d[16], d[17]), pack2(d[18], d[19]));
            if (f == 9) { fence_async_smem(); e_arrive(bars + 8 * (B_RDY + wg * 5 + (f >> 1))); }
        }
    }
}

__device__ __forceinline__ void task_p2(int wg, int rk, uint32_t sb) {
    const int tid = threadIdx.x & 127, w = tid >> 5, lane = tid & 31;
    const uint32_t bars = sb + BARS;
    const int phi0 = 3 * rk, phiE = extra_phi(rk), mE = extra_mask(rk);
    uint4 wA[6], wB[6], wC[6], wE[6];
    auto ldw = [&](uint4 (&a)[6], int j, int phi) {
        const int pc = 3 * j + wg;
        const uint32_t p = sb + wslot(pc) + (lane & 3) * 512 + w * 128 + (((lane >> 2) ^ phi) & 1) * 64 + (((lane >> 3) ^ lane) & 3) * 16 + (phi & 1) * 8;
        mbar_wait(bars + 8 * (B_WL + pc));
#pragma unroll
        for (int s = 0; s < 6; s++) {
            asm volatile("ld.shared.v2.u32 {%0, %1}, [%2];" : "=r"(a[s].x), "=r"(a[s].y) : "r"(p + s * 2048) : "memory");
            asm volatile("ld.shared.v2.u32 {%0, %1}, [%2];" : "=r"(a[s].z), "=r"(a[s].w) : "r"((p ^ 8) + s * 2048) : "memory");
        }
        uint32_t dep = 0;
#pragma unroll
        for (int s = 0; s < 6; s++) dep |= a[s].x ^ a[s].z;
        if (__any_sync(0xffffffffu, dep == 0x7fc17fc1u)) __nanosleep(0);
        e_arrive(bars + 8 * (B_WE + pc));
    };
    ldw(wA, 0, phi0); ldw(wB, 1, phi0 + 1);
    mbar_wait(bars + 8 * (B_SIG + SIG_P1 + 1));
    const int i = lane & 7, mi = lane >> 3;
    const uint32_t soff = sb + S1 + wg * 4096 + mi * 512 + (i >> 1) * 128 + (i & 1) * 64;
    const int xo = w ^ (i >> 1);
    float d[32];
    zero(d);
    int n = 0;
    uint32_t xb = ((sb + xslot(0)) & 0x3FFFF) >> 4 | 1u << 16, mb = bars + 8 * wg;
    bool landed = false;
    auto unit = [&](const uint4 (&a)[6], int z) {
        const Desc d0{xb + (z & 2), (512u >> 4) | (2u << 30)}, d1 = d0 ^ 2u;
        if (!landed) mbar_wait(bars + 8 * (B_RF + n));
        mbar_wait(mb + 8 * (B_TOK - 1));
        wg_fence();
        wgmma_rs_n64_z(d, a[0].x, a[0].y, a[0].z, a[0].w, d0);
        wgmma_rs_n64_a(d, a[1].x, a[1].y, a[1].z, a[1].w, d1);
        e_arrive(bars + 8 * (n ? B_RE + n - 1 : B_RE + 13));
        const bool sfree = mbar_test(n >= 4 ? mb + 8 * (B_SFREE - 12) : bars + 8 * (B_TOK - 1));
        landed = mbar_test(bars + 8 * (B_RF + n + 1));
        wgmma_rs_n64_a(d, a[2].x, a[2].y, a[2].z, a[2].w, d0 + (uint32_t)(4096 >> 4));
        wgmma_rs_n64_a(d, a[3].x, a[3].y, a[3].z, a[3].w, d1 + (uint32_t)(4096 >> 4));
        e_arrive(mb + 8 * B_TOK);
        wgmma_rs_n64_a(d, a[4].x, a[4].y, a[4].z, a[4].w, d0 + (uint32_t)(8192 >> 4));
        wgmma_rs_n64_a(d, a[5].x, a[5].y, a[5].z, a[5].w, d1 + (uint32_t)(8192 >> 4));
        wg_commit();
        if (!sfree) mbar_wait(mb + 8 * (B_SFREE - 12));
        const uint32_t a0 = soff + (n & 3) * 12288 + ((xo ^ z) << 4);
        n++;
        xb = ((sb + xslot(n)) & 0x3FFFF) >> 4 | 1u << 16;
        wg_wait<0>();
        reg_fence(d);
        uint32_t p[8];
#pragma unroll
        for (int j = 0; j < 8; j++) p[j] = pack2(d[4 * j] - d[4 * j + 3], d[4 * j + 2] + d[4 * j + 1]);
        stm4(a0, p[0], p[1], p[2], p[3]);
        stm4(a0 + 2048, p[4], p[5], p[6], p[7]);
        fence_async_smem();
        e_arrive(mb + 8 * (B_RDY + R_P2));
        mb += 24;
    };
    const int zA = phi0 & 3, zB = (phi0 + 1) & 3, zC = (phi0 + 2) & 3, zE = phiE & 3;
#pragma unroll 1
    for (int it = 0; it < 4; it++) {
        unit(wA, zA);
        unit(wB, zB);
        if (it == 0) ldw(wC, 2, phi0 + 2);
        unit(wC, zC);
        if (it == 0 && mE) ldw(wE, 3, phiE);
        if (mE >> it & 1) unit(wE, zE);
    }
}

__device__ __forceinline__ void task_p3(int wg, int pair, uint32_t sb) {
    const int tid = threadIdx.x & 127, w = tid >> 5, lane = tid & 31;
    const uint32_t buf = sb + (wg ? 3 - wg : 0) * 51200, bars = sb + BARS;
    uint32_t fr[10][4][2];
    float acc[2][16];
    zero(acc[0]); zero(acc[1]);
    {
        const Desc dB = mkdesc(sb + C3, 128, 256, 0);
        const uint32_t a0 = (buf & 0x3FFFF) >> 4;
        auto dq = [&](int Q) {
            return Desc{a0 + (uint32_t)((quad_off(Q) >> 4) | ((Q < 48 ? 2048 : 1024) >> 4) << 16), (uint32_t)((quad_off(Q + 1) - quad_off(Q)) >> 4) | (2u << 30)};
        };
        auto issue = [&](int f) {
            if (!(f & 1)) mbar_wait(bars + 8 * (B_YF + wg * 5 + (f >> 1)));
            wg_fence();
            wgmma_ss_n32_z(acc[f & 1], dq(5 * f), dB);
            wgmma_ss_n32_a(acc[f & 1], dq(5 * f + 1), dB + (uint32_t)(1024 >> 4));
            wgmma_ss_n32_a(acc[f & 1], dq(5 * f + 3), dB + (uint32_t)(2048 >> 4));
            wg_commit();
        };
        mbar_wait(bars + 8 * B_CF3);
        issue(0);
#pragma unroll
        for (int f = 0; f < 10; f++) {
            if (f < 9) { issue(f + 1); wg_wait<1>(); } else wg_wait<0>();
            float (&d)[16] = acc[f & 1];
            reg_fence(d);
#pragma unroll
            for (int g = 0; g < 4; g++) { fr[f][g][0] = pack2(d[4 * g], d[4 * g + 1]); fr[f][g][1] = pack2(d[4 * g + 2], d[4 * g + 3]); }
        }
    }
    {
        const Desc dB = mkdesc(sb + C3 + 3072, 128, 256, 0);
        const int i = lane & 7, mi = lane >> 3, th = w >> 1, tz = (2 * pair + th) & 3;
        const int oct = (2 * (w & 1) + (mi & 1)) ^ tz;
        const uint32_t soff = buf + th * 3584 + (mi >> 1) * 512 + i * 64 + ((oct ^ (i >> 1)) << 4);
        auto mma = [&](int t, int s) {
            if (t > 6) return;
            const int g = t < 6 ? 1 + (t >> 1) : 0;
            const uint32_t o = t < 6 ? (t & 1) * 1024 : 8960, st = t < 6 ? 1792 : 1024;
            if (s == 0) { wg_fence(); wgmma_rs_n32_z(acc[t & 1], fr[0][g][0], fr[0][g][1], fr[1][g][0], fr[1][g][1], dB + (o >> 4)); }
            else wgmma_rs_n32_a(acc[t & 1], fr[2 * s][g][0], fr[2 * s][g][1], fr[2 * s + 1][g][0], fr[2 * s + 1][g][1], dB + ((o + s * st) >> 4));
            if (s == 4) wg_commit();
        };
        const int row = th * 14 + 4 * (mi >> 1) + (i >> 1);
        const uint32_t z0 = buf + row * 128 + (i & 1) * 64 + ((oct ^ (row & 3)) << 4), z1 = (lane & 20) == 20 ? buf + 4096 + lane * 16 : z0 + 1024;
        bb_break(sb);
#pragma unroll
        for (int s = 0; s < 5; s++) mma(0, s);
        wg_bar(1 + wg);
#pragma unroll
        for (int t = 0; t < 7; t++) {
#pragma unroll
            for (int s = 0; s < 2; s++) mma(t + 1, s);
            if (t < 6) { wg_commit(); wg_wait<1>(); } else wg_wait<0>();
            float (&d)[16] = acc[t & 1];
            reg_fence(d);
            const uint32_t a = soff + (1 + (t >> 1)) * 7168 + (t & 1) * 2048;
            stm4(t < 6 ? a : z0, pack2(d[0], d[1]), pack2(d[2], d[3]), pack2(d[4], d[5]), pack2(d[6], d[7]));
            mma(t + 1, 2);
            if (t & 1) stm2(a + 1024, pack2(d[8], d[9]), pack2(d[10], d[11]));
            else stm4(t < 6 ? a + 1024 : z1, pack2(d[8], d[9]), pack2(d[10], d[11]), pack2(d[12], d[13]), pack2(d[14], d[15]));
#pragma unroll
            for (int s = 3; s < 5; s++) mma(t + 1, s);
            if ((t & 1) || t == 6) { fence_async_smem(); e_arrive(bars + 8 * (B_RDY + R_P3 + wg * 4 + (t >> 1))); }
        }
    }
}

__device__ __forceinline__ void load_x(int cls, int rk, int u, uint32_t sb, const Maps& mp) {
    const int id = u * NH + rk, pl = id / 3, c0 = 32 * (id - 3 * pl), tp = cls * 4 + (pl >> 4), col = 14 * (pl & 15) - 8;
    const uint32_t bar = sb + BARS + 8 * (B_XF + u * 5), dst = sb + u * 51200;
    const int wrap = col < 0 ? 224 : 0;
    if (tp) {
#pragma unroll
        for (int g = 0; g < 5; g++) e_ld3(dst + g * 8704, &mp.x34, c0, col + 4 * g + (g < 2 ? wrap : 0), 28 * tp - 6, bar + 8 * g);
    } else {
#pragma unroll
        for (int g = 0; g < 5; g++) {
            e_ld3(dst + g * 8704, &mp.x6, c0, col + 4 * g + (g < 2 ? wrap : 0), 218, bar + 8 * g);
            e_ld3(dst + g * 8704 + 1536, &mp.x28, c0, col + 4 * g + (g < 2 ? wrap : 0), 0, bar + 8 * g);
        }
    }
}

__device__ __forceinline__ void load_x_box(int cls, int rk, int u, int g, uint32_t sb, const Maps& mp) {
    const int id = u * NH + rk, pl = id / 3, c0 = 32 * (id - 3 * pl), tp = cls * 4 + (pl >> 4), col = 14 * (pl & 15) - 8 + 4 * g;
    e_ld3(sb + u * 51200 + g * 8704, &mp.x34, c0, col < 0 ? col + 224 : col, 28 * tp - 6, sb + BARS + 8 * (B_XF + u * 5 + g));
}

__device__ __forceinline__ void load_first(uint32_t sb, const Maps& mp, const Ptrs& pt) {
    const uint32_t bars = sb + BARS;
    const int k = blockIdx.x;
    if (k < 129) {
        const int cb0 = 14 * k / 25, cb1 = min((14 * k + 13) / 25, 71);
#pragma unroll 1
        for (int cb = cb0; cb <= cb1; cb++) {
            const int b = cb / 24, i0 = 16 * ((cb >> 2) - 6 * b) + 2 * (cb & 3);
            const uint32_t bar = bars + 8 * (B_WF + 2 * (cb - cb0));
            e_expect(bar, 14336);
            e_ld4(sb + WP + (cb - cb0) * 14336, &mp.w, 32 * b, i0, bar);
            e_ld4(sb + WP + (cb - cb0) * 14336 + 7168, &mp.w, 32 * b, i0 + 8, bar);
        }
    }
    asm volatile(ELECT "cp.async.bulk.prefetch.L2.global [%0], 9088;\n}" :: "l"(pt.x + (k & 1) * (112 * 43008) + (k >> 1) * 9088) : "memory");
    e_expect(bars + 8 * B_CF1, 17920); e_g2s(sb + C1, pt.tab1, 17920, bars + 8 * B_CF1);
    if ((threadIdx.x & 31) < 15) asm volatile("mbarrier.arrive.expect_tx.shared::cta.b64 _, [%0], 8704;" :: "r"(bars + 8 * (B_XF + (threadIdx.x & 31))) : "memory");
    __syncwarp();
}

__device__ __forceinline__ uint32_t get_rel(uint32_t sb) {
    mbar_wait(sb + BARS + 8 * B_REL);
    uint32_t v; asm volatile("ld.shared.u32 %0, [%1];" : "=r"(v) : "r"(sb + REL) : "memory");
    return uni(v);
}

__device__ __forceinline__ void load_warp(int cls, int rk, uint32_t sb, const Ptrs& pt) {
    const uint32_t bars = sb + BARS;
    mbar_wait(bars + 8 * (B_SIG + SIG_P1));
    const uint32_t rel = get_rel(sb);
    const char* cnt = cls_cnt(pt.scr, cls);
    const int mE = extra_mask(rk);
    const int lpA = phi_line(3 * rk, rel), lpB = phi_line(3 * rk + 1, rel), lpC = phi_line(3 * rk + 2, rel), lpE = phi_line(extra_phi(rk), rel);
    e_arrive(bars + 8 * (B_TOK - 1));
    if ((threadIdx.x & 31) < 14) asm volatile("mbarrier.arrive.expect_tx.shared::cta.b64 _, [%0], 12288;" :: "r"(bars + 8 * (B_RF + (threadIdx.x & 31))) : "memory");
    __syncwarp();
    int n = 0;
#pragma unroll 1
    for (int pg = 0; pg < 4; pg++) {
        const int l0 = slot_line(0, pg, cls), l1 = slot_line(1, pg, cls), l2 = slot_line(2, pg, cls);
        auto unit = [&](int lp) {
            const uint32_t bar = bars + 8 * (B_RF + n), dst = sb + xslot(n);
            mbar_wait(bars + 8 * (n >= 8 ? B_RE + n - 8 : n >= 4 ? B_SIG + SIG_P1 + (rk < 60 ? 2 : 1) : B_WE + ((0x4310 >> (4 * n)) & 15)));
            e_g2s(dst, pt.scr + (size_t)(lp ^ l0) * 128, 4096, bar);
            e_g2s(dst + 4096, pt.scr + (size_t)(lp ^ l1) * 128, 4096, bar);
            e_g2s(dst + 8192, pt.scr + (size_t)(lp ^ l2) * 128, 4096, bar);
            n++;
        };
        cnt_wait(cnt + (CNT_P1 + pg) * 128, 48);
        unit(lpA); unit(lpB); unit(lpC);
        if (mE >> pg & 1) unit(lpE);
        if (pg == 1) { mbar_wait(bars + 8 * B_P1D); e_expect(bars + 8 * B_CF3, 17152); e_g2s(sb + C3, pt.tab3, 17152, bars + 8 * B_CF3); }
    }
}

__device__ __forceinline__ int near_page(char* p, int rounds) {
#pragma unroll
    for (int e = 0; e < 4; e++) asm volatile("st.relaxed.gpu.global.v4.u32 [%0], {%1, %1, %1, %1};" :: "l"(p + (e >> 1) * 4096 + (e & 1) * 16), "r"(0) : "memory");
    int score = 0;
#pragma unroll 1
    for (int r = 0; r < rounds; r++) {
        uint32_t v0, v1, t0, t1;
        asm volatile("atom.relaxed.gpu.global.exch.b32 %0, [%1], 1;" : "=r"(v0) : "l"(p + (r & 1) * 4096) : "memory");
        asm volatile("atom.relaxed.gpu.global.exch.b32 %0, [%1], 1;" : "=r"(v1) : "l"(p + (~r & 1) * 4096) : "memory");
        asm volatile("{\n.reg .pred p;\nsetp.ne.u32 p, %1, 0xffffffff;\nmov.u32 %0, 0;\n@p mov.u32 %0, %%clock;\n}" : "=r"(t0) : "r"(v0) : "memory");
        asm volatile("{\n.reg .pred p;\nsetp.ne.u32 p, %1, 0xffffffff;\nmov.u32 %0, 0;\n@p mov.u32 %0, %%clock;\n}" : "=r"(t1) : "r"(v1) : "memory");
        const int gap = min((int)(t1 - t0), 160) - 80;
        score += (r & 1) ? gap : -gap;
    }
    return score > 0;
}

__device__ __forceinline__ uint32_t find_role(uint32_t sb, char* scr) {
    const int k = blockIdx.x;
    int c = near_page(scr + (slot_line(3, 3, 0) + phi_line(1 + (k >> 5), 0) + (k & 31)) * 128, 1);
    int r;
    asm volatile("atom.relaxed.gpu.global.add.u32 %0, [%1], 1;" : "=r"(r) : "l"(cls_cnt(scr, c) + CNT_RANK * 128) : "memory");
    asm volatile("st.shared.u32 [%0], %1;" :: "r"(sb + REL + 8), "r"(c) : "memory");
    if (r >= NH) { c ^= 1; r = NSM - 1 - r; }
    asm volatile("st.shared.u32 [%0], %1;" :: "r"(sb + REL + 4), "r"(c << 8 | r) : "memory");
    return c << 8 | r;
}
__device__ __forceinline__ void get_role(uint32_t sb, int& cls, int& rk) {
    mbar_wait(sb + BARS + 8 * B_ROLE);
    uint32_t v; asm volatile("ld.shared.u32 %0, [%1];" : "=r"(v) : "r"(sb + REL + 4) : "memory");
    v = uni(v); cls = v >> 8; rk = v & 255;
}

__device__ __forceinline__ void load3_warp(int cls, int rk, uint32_t sb, const Maps& mp, const Ptrs& pt) {
    const uint32_t bars = sb + BARS;
    mbar_wait(bars + 8 * B_XF);
    const uint32_t rel = cnt_wait(pt.cnt + CNT_REL * 32, 12u << 16);
    asm volatile("st.shared.u32 [%0], %1;" :: "r"(sb + REL), "r"(rel) : "memory");
    __syncwarp();
    e_arrive(bars + 8 * B_REL);
    mbar_wait(bars + 8 * (B_SIG + SIG_W));
    cnt_wait(cls_cnt(pt.scr, cls) + CNT_W * 128, NSM);
    {
        const int np = rk >= 58 ? 12 : 9;
#pragma unroll 1
        for (int o = 0; o < np; o++) {
            const int pc = (0xba9876524310ull >> (4 * o)) & 15;
            if (o == 4) mbar_wait(bars + 8 * (B_SIG + SIG_P1));
            if (o >= 8) mbar_wait(bars + 8 * (B_WE + ((0x5762 >> (4 * (o - 8))) & 15)));
            if (o >= 4) mbar_wait(bars + 8 * (B_WL + ((0xba9876524310ull >> (4 * (o - 4))) & 15)));
            e_expect(bars + 8 * (B_WL + pc), 12288);
            e_g2s(sb + wslot(pc), pt.wf + (pc < 9 ? 9 * rk + pc : 3 * extra_phi(rk) + pc - 9) * 12288, 12288, bars + 8 * (B_WL + pc));
        }
        if (np == 12) { mbar_wait(bars + 8 * (B_WE + 9)); mbar_wait(bars + 8 * (B_WE + 10)); mbar_wait(bars + 8 * (B_WE + 11)); }
    }
    mbar_wait(bars + 8 * (B_SIG + SIG_P2 + 1));
    const int nu = rk < 60 ? 3 : 2;
#pragma unroll 1
    for (int u = 0; u < nu; u++) {
        const int id = u * NH + rk, pl = id / 3, chunk = id - 3 * pl;
        const int l0 = slot_line(chunk, pl >> 4, cls) + (pl & 15) * 2;
        const uint32_t buf = sb + (u ? 3 - u : 0) * 51200, bar = bars + 8 * (B_YF + u * 5);
#pragma unroll
        for (int j = 0; j < 5; j++) e_expect(bar + 8 * j, j == 4 ? 10240 : (j & 1) ? 8192 : 12288);
        if (u) mbar_wait(bars + 8 * (B_SIG + SIG_P2 + 3));
        cnt_wait(cls_cnt(pt.scr, cls) + (CNT_P2 + (pl >> 4)) * 128, NH);
        if (u == nu - 1) e_arrive(bars + 8 * B_FIN);
        const uint32_t r2 = uni(rel) << 5;
#pragma unroll
        for (int G = 0; G < 13; G++)
            e_ld5(buf + G * 4096, G < 12 ? &mp.f16 : &mp.f8, (l0 ^ ((r2 >> G) & 32)) + (G << 14), bar + 8 * ((2 * G) / 5));
    }
}

__device__ __forceinline__ void store_warp(uint32_t sb, const Maps& mp, const Ptrs& pt) {
    const uint32_t bars = sb + BARS;
    const int k = blockIdx.x;
    uint32_t pa = 0, pb = 0, qa = 0, qb = 0;
    auto arr2 = [&](uint32_t& a, uint32_t& b) { if (a) e_arrive(a); if (b) e_arrive(b); a = b = 0; };
    auto pre = [&](int idx) {
        const uint32_t bar = bars + 8 * idx;
        if ((pb | qb) && !mbar_test(bar)) { bulk_wait<0>(); arr2(qa, qb); arr2(pa, pb); }
        mbar_wait(bar);
    };
    auto post = [&](uint32_t fr) {
        bulk_commit(); bulk_wait_read<2>();
        if (qb) bulk_wait<2>();
        arr2(qa, qb); qa = pa; qb = pb; pb = 0; pa = fr;
    };
    auto after = [&](int sig) { pb = bars + 8 * (B_SIG + sig); };
    int cls, rk; get_role(sb, cls, rk);
    {
        int cb = 14 * k / 25, oc = 14 * k - 25 * cb;
        int g1 = 0;
#pragma unroll 1
        for (int i = 0; i < 14 && cb < 72; i++) {
            pre(B_WRD + i);
            e_st3(&mp.wst, sb + wst_off(i), 0, 8 * oc, cb);
            post(0);
            if (T1MASK >> i & 1) load_x_box(cls, rk, 1, g1++, sb, mp);
            if (++oc == 25) { oc = 0; cb++; }
        }
#pragma unroll 1
        for (; g1 < 5; g1++) load_x_box(cls, rk, 1, g1, sb, mp);
        after(SIG_W);
    }
    pre(B_REL);
    const uint32_t rel = get_rel(sb);
    const int nu = rk < 60 ? 3 : 2;
    int g2 = 0;
#pragma unroll 1
    for (int u = 0; u < nu; u++) {
        const int id = u * NH + rk, pl = id / 3, chunk = id - 3 * pl;
        const int l0 = slot_line(chunk, pl >> 4, cls) + (pl & 15) * 2;
        int j = B_RDY + u * 5;
        const int m2 = nu == 3 ? (u == 0 ? T2MASK & 0x1fff : u == 1 ? T2MASK >> 13 : 0) : 0;
#pragma unroll 1
        for (int G = 0; G < 13; G++) {
            if (0x4a5 >> G & 1) pre(j++);
            e_st5(G < 12 ? &mp.f16 : &mp.f8, sb + u * 51200 + G * 4096, (l0 ^ ((rel >> G) & 1) << 5) + (G << 14));
            post(0);
            if (m2 >> G & 1) load_x_box(cls, rk, 2, g2++, sb, mp);
        }
        after(SIG_P1 + u);
    }
    const int mE = extra_mask(rk);
    int n = 0;
#pragma unroll 1
    for (int pg = 0; pg < 4; pg++) {
        const int nj = 3 + (mE >> pg & 1);
        const int l0 = slot_line(0, pg, cls), l1 = slot_line(1, pg, cls), l2 = slot_line(2, pg, cls);
#pragma unroll 1
        for (int j = 0; j < nj; j++) {
            const int lp = phi_line(j == 3 ? extra_phi(rk) : 3 * rk + j, rel);
#pragma unroll
            for (int b = 0; b < 3; b++) {
                pre(B_RDY + R_P2 + n * 3 + b);
                e_s2g(pt.scr + (size_t)(lp ^ (b == 0 ? l0 : b == 1 ? l1 : l2)) * 128, sb + S1 + (n & 3) * 12288 + b * 4096, 4096);
                post(bars + 8 * (B_SFREE + n * 3 + b));
            }
            n++;
        }
        after(SIG_P2 + pg);
    }
#pragma unroll 1
    for (int u = 0; u < nu; u++) {
        const int id = u * NH + rk, pl = id / 3, chunk = id - 3 * pl, tp = cls * 4 + (pl >> 4), tx = pl & 15;
        const uint32_t buf = sb + (u ? 3 - u : 0) * 51200;
#pragma unroll
        for (int gg = 1; gg < 5; gg++) {
            pre(B_RDY + R_P3 + u * 4 + gg - 1);
            if (gg < 4) e_st3(&mp.y4, buf + gg * 7168, 32 * chunk, 14 * tx - 4 + 4 * gg, 28 * tp);
            else e_st3(&mp.y2, buf, 32 * chunk, tx == 0 ? 222 : 14 * tx - 2, 28 * tp);
            post(0);
        }
    }
    bulk_wait_read<0>();
}

__device__ __forceinline__ void signal_warp(int cls, int rk, uint32_t sb, const Ptrs& pt) {
    const uint32_t bars = sb + BARS;
    char* cnt = cls_cnt(pt.scr, cls);
    if (threadIdx.x & 31) return;
#pragma unroll 1
    for (int c = 0; c < 8; c++) {
        if (c == SIG_P1 + 2 && rk >= 60) continue;
        char* ctr = cnt + (c == SIG_W ? CNT_W : c < SIG_P2 ? CNT_P1 + ((c - SIG_P1) * NH + rk) / 48 : CNT_P2 + c - SIG_P2) * 128;
        mbar_wait(bars + 8 * (B_SIG + c));
        fence_async();
        asm volatile("red.relaxed.gpu.global.add.u32 [%0], 1;" :: "l"(ctr) : "memory");
        if (c == SIG_W) asm volatile("red.relaxed.gpu.global.add.u32 [%0], 1;" :: "l"((uintptr_t)ctr ^ 4096) : "memory");
    }
    mbar_wait(bars + 8 * B_FIN);
    unsigned old;
    asm volatile("atom.add.relaxed.gpu.global.u32 %0, [%1], 1;" : "=r"(old) : "l"(pt.cnt + CNT_DONE * 32) : "memory");
    if (old == NSM - 1) {
#pragma unroll
        for (int c = 0; c < NCNT; c++) pt.cnt[c * 32] = 0;
#pragma unroll 1
        for (int c = 0; c < NCLS; c++) { *reinterpret_cast<unsigned*>(cnt + c * 128) = 0; *reinterpret_cast<unsigned*>(((uintptr_t)cnt ^ 4096) + c * 128) = 0; }
    }
}

__global__ void __launch_bounds__(512, 1) fftconv_kernel(const Ptrs pt, const __grid_constant__ Maps mp) {
    extern __shared__ __align__(1024) uint8_t smem[];
    const uint32_t sb = smem_u32(smem);
    const int tid = threadIdx.x, warp = uni(tid >> 5), wg = warp >> 2;
    int cls, rk;
    auto bar_init = [&](int i) {
        uint32_t c = 1;
        if (i == B_P1D || (i >= B_RE && i < B_RE + 14)) c = 12;
        else if ((i >= B_WCH && i < B_WL) || i >= B_TOK) c = 4;
        asm volatile("st.shared.v2.u32 [%0], {%1, %2};" :: "r"(sb + BARS + 8 * i), "r"((0x100000u - c) << 1), "r"((0x100000u - c) << 11) : "memory");
        fence_async_smem();
    };
    if (wg == 3) {
        asm volatile("setmaxnreg.dec.sync.aligned.u32 32;");
        if (warp == 12) {
            bar_init(tid & 31);
            __syncwarp();
            asm volatile("bar.arrive 4, 416;" ::: "memory");
            load_first(sb, mp, pt);
            asm volatile("bar.sync 5, 416;" ::: "memory");
            get_role(sb, cls, rk);
            load_warp(cls, rk, sb, pt);
        } else if (warp == 13) {
            if ((tid & 31) < 8) asm volatile("prefetch.tensormap [%0];" :: "l"(reinterpret_cast<const CUtensorMap*>(&mp) + 1 + (tid & 31)) : "memory");
            __syncwarp();
            asm volatile("bar.sync 6, 416;" ::: "memory");
            store_warp(sb, mp, pt);
        } else if (warp == 14) {
            const int G = blockIdx.x - 119;
            int sel = 0;
            if (G >= 1 && (tid & 31) == 0) sel = near_page(pt.scr + ((size_t)G << 21) + slot_line(3, 3, 0) * 128, 2);
            __syncwarp();
            asm volatile("bar.sync 7, 416;" ::: "memory");
            get_role(sb, cls, rk);
            if (G >= 1 && (tid & 31) == 0) {
                uint32_t c; asm volatile("ld.shared.u32 %0, [%1];" : "=r"(c) : "r"(sb + REL + 8) : "memory");
                asm volatile("red.relaxed.gpu.global.add.u32 [%0], %1;" :: "l"(pt.cnt + CNT_REL * 32), "r"(0x10000u | (sel ^ c) << G) : "memory");
            }
            __syncwarp();
            load3_warp(cls, rk, sb, mp, pt);
        } else {
            uint32_t role = 0;
            if ((tid & 31) == 0) role = find_role(sb, pt.scr);
            role = uni(role); cls = role >> 8; rk = role & 255;
            asm volatile("bar.sync 8, 416;" ::: "memory");
            load_x(cls, rk, 0, sb, mp);
            e_arrive(sb + BARS + 8 * B_ROLE);
            signal_warp(cls, rk, sb, pt);
        }
    } else {
        if (tid >= 32 && tid < NBAR) bar_init(tid);
        {
            const int r = tid % 40;
            asm volatile("st.shared.u32 [%0], %1;" :: "r"(sb + TBL + 4 * tid), "r"(cos_bits(r) | (cos_bits(r < 30 ? r + 10 : r - 30) << 16)) : "memory");
        }
        __syncwarp();
        asm volatile("bar.sync 4, 416;" ::: "memory");
        asm volatile("bar.arrive 5, 416;" ::: "memory");
        asm volatile("bar.arrive 6, 416;" ::: "memory");
        asm volatile("bar.arrive 7, 416;" ::: "memory");
        asm volatile("bar.arrive 8, 416;" ::: "memory");
        task_w(wg, blockIdx.x, sb);
        asm volatile("setmaxnreg.inc.sync.aligned.u32 160;");
        get_role(sb, cls, rk);
        const int id = wg * NH + rk;
        if (id < 192) task_p1(wg, id / 3, sb);
        e_arrive(sb + BARS + 8 * B_P1D);
        task_p2(wg, rk, sb);
        if (id < 192) task_p3(wg, id / 3, sb);
    }
}

__global__ void fallback_kernel(const __nv_bfloat16* x, const __nv_bfloat16* w, __nv_bfloat16* y) {
    const int px = blockIdx.x, o = threadIdx.x, h = px / 224, c = px % 224;
    float acc = 0.f;
    for (int kh = 0; kh < 7; kh++)
        for (int kw = 0; kw < 7; kw++) {
            const __nv_bfloat16* xp = x + (((h - kh + 224) % 224) * 224 + (c - kw + 224) % 224) * 96;
            const __nv_bfloat16* wp = w + (kh * 7 + kw) * 9216 + o;
            for (int i = 0; i < 96; i++) acc += __bfloat162float(xp[i]) * __bfloat162float(wp[i * 96]);
        }
    y[px * 96 + o] = __float2bfloat16(acc);
}

typedef CUresult (*EncodeFn)(CUtensorMap*, CUtensorMapDataType, cuuint32_t, void*, const cuuint64_t*, const cuuint64_t*, const cuuint32_t*, const cuuint32_t*,
                             CUtensorMapInterleave, CUtensorMapSwizzle, CUtensorMapL2promotion, CUtensorMapFloatOOBfill);

static void encode3(EncodeFn fn, CUtensorMap* m, void* ptr, uint64_t d0, uint64_t d1, uint64_t d2, uint64_t s1, uint64_t s2,
                    uint32_t b0, uint32_t b1, uint32_t b2, CUtensorMapSwizzle sw) {
    cuuint64_t dims[3] = {d0, d1, d2}, strides[2] = {s1, s2};
    cuuint32_t box[3] = {b0, b1, b2}, es[3] = {1, 1, 1};
    fn(m, CU_TENSOR_MAP_DATA_TYPE_BFLOAT16, 3, ptr, dims, strides, box, es, CU_TENSOR_MAP_INTERLEAVE_NONE, sw,
       CU_TENSOR_MAP_L2_PROMOTION_NONE, CU_TENSOR_MAP_FLOAT_OOB_FILL_NONE);
}

extern "C" void kernel_launch(void* const* d_in, const int* in_sizes, int n_in, void* d_out, int out_size) {
    (void)in_sizes; (void)n_in; (void)out_size;
    int dev = 0, nsm = 0;
    cudaGetDevice(&dev);
    cudaDeviceGetAttribute(&nsm, cudaDevAttrMultiProcessorCount, dev);
    if (nsm < NSM) {
        fallback_kernel<<<224 * 224, 96>>>((const __nv_bfloat16*)d_in[0], (const __nv_bfloat16*)d_in[1], (__nv_bfloat16*)d_out);
        return;
    }
    void* fnp = nullptr; cudaDriverEntryPointQueryResult qr;
    cudaGetDriverEntryPoint("cuTensorMapEncodeTiled", &fnp, cudaEnableDefault, &qr);
    EncodeFn fn = (EncodeFn)fnp;
    void* xf = nullptr; cudaGetSymbolAddress(&xf, g_scr);
    xf = (void*)(((uintptr_t)xf + (1u << 21) - 1) & ~(uintptr_t)((1u << 21) - 1));
    void* wf = nullptr; cudaGetSymbolAddress(&wf, g_wf);
    Maps mp;
    Ptrs pt;
    pt.scr = (char*)xf; pt.wf = (const char*)wf; pt.x = (const char*)d_in[0];
    void* p = nullptr;
    cudaGetSymbolAddress(&p, TAB_P1); pt.tab1 = p;
    cudaGetSymbolAddress(&p, TAB_P3); pt.tab3 = p;
    cudaGetSymbolAddress(&p, g_cnt); pt.cnt = (unsigned*)p;
    {
        cuuint32_t b16[5] = {64, 4, 2, 2, 2}, b8[5] = {64, 4, 2, 1, 2}, es[5] = {1, 1, 1, 1, 1};
        cuuint64_t d[5] = {64, 4, 2, 2, 13 << 14}, st[4] = {16384, 262144, 1048576, 128};
        fn(&mp.f16, CU_TENSOR_MAP_DATA_TYPE_BFLOAT16, 5, xf, d, st, b16, es, CU_TENSOR_MAP_INTERLEAVE_NONE, CU_TENSOR_MAP_SWIZZLE_NONE, CU_TENSOR_MAP_L2_PROMOTION_NONE, CU_TENSOR_MAP_FLOAT_OOB_FILL_NONE);
        fn(&mp.f8, CU_TENSOR_MAP_DATA_TYPE_BFLOAT16, 5, xf, d, st, b8, es, CU_TENSOR_MAP_INTERLEAVE_NONE, CU_TENSOR_MAP_SWIZZLE_NONE, CU_TENSOR_MAP_L2_PROMOTION_NONE, CU_TENSOR_MAP_FLOAT_OOB_FILL_NONE);
    }
    encode3(fn, &mp.x6, d_in[0], 96, 224, 224, 192, 224 * 192, 32, 4, 6, CU_TENSOR_MAP_SWIZZLE_64B);
    encode3(fn, &mp.x34, d_in[0], 96, 224, 224, 192, 224 * 192, 32, 4, 34, CU_TENSOR_MAP_SWIZZLE_64B);
    encode3(fn, &mp.x28, d_in[0], 96, 224, 224, 192, 224 * 192, 32, 4, 28, CU_TENSOR_MAP_SWIZZLE_64B);
    {
        cuuint32_t box[4] = {32, 8, 7, 2}, es[4] = {1, 1, 1, 1};
        cuuint64_t d[4] = {96, 7, 7, 96}, st[3] = {18432, 7 * 18432, 192};
        fn(&mp.w, CU_TENSOR_MAP_DATA_TYPE_BFLOAT16, 4, d_in[1], d, st, box, es, CU_TENSOR_MAP_INTERLEAVE_NONE, CU_TENSOR_MAP_SWIZZLE_64B, CU_TENSOR_MAP_L2_PROMOTION_NONE, CU_TENSOR_MAP_FLOAT_OOB_FILL_NONE);
    }
    encode3(fn, &mp.wst, wf, 256, 200, 72, 36864, 512, 256, 8, 1, CU_TENSOR_MAP_SWIZZLE_NONE);
    encode3(fn, &mp.y4, d_out, 96, 224, 224, 192, 224 * 192, 32, 4, 28, CU_TENSOR_MAP_SWIZZLE_64B);
    encode3(fn, &mp.y2, d_out, 96, 224, 224, 192, 224 * 192, 32, 2, 28, CU_TENSOR_MAP_SWIZZLE_64B);
    constexpr int SMEM_LAUNCH = SMEM_BYTES;
    cudaFuncSetAttribute(fftconv_kernel, cudaFuncAttributeMaxDynamicSharedMemorySize, SMEM_LAUNCH);
    fftconv_kernel<<<NSM, 512, SMEM_LAUNCH>>>(pt, mp);
}
```

```cpp
#include <cuda_runtime.h>
#include <cuda_bf16.h>
#include <cuda.h>
#include <stdint.h>

__device__ __align__(128) const uint32_t TAB_P1[4480] = {
0x3e75,0,0x3e72,0,0x8000,0,0xbd19,0,0x3e750000,0,0x3e720000,0,0x80000000,0,0xbd190000,0,
0,0x3e75,0,0x3e72,0,0x8000,0,0xbd19,0,0x3e750000,0,0x3e720000,0,0x80000000,0,0xbd190000,
0x3e69,0,0x3e5a,0,0xbd97,0,0xbdde,0,0x3e690000,0,0x3e5a0000,0,0xbd970000,0,0xbdde0000,0,
0,0x3e69,0,0x3e5a,0,0xbd97,0,0xbdde,0,0x3e690000,0,0x3e5a0000,0,0xbd970000,0,0xbdde0000,
0x3e75,0,0x3e5a,0,0x8000,0,0xbdde,0,0x3e750000,0,0x3e5a0000,0,0x80000000,0,0xbdde0000,0,
0,0x3e75,0,0x3e5a,0,0x8000,0,0xbdde,0,0x3e750000,0,0x3e5a0000,0,0x80000000,0,0xbdde0000,
0x3e10,0,0x3d19,0,0xbe46,0,0xbe72,0,0x3e100000,0,0x3d190000,0,0xbe460000,0,0xbe720000,0,
0,0x3e10,0,0x3d19,0,0xbe46,0,0xbe72,0,0x3e100000,0,0x3d190000,0,0xbe460000,0,0xbe720000,
0x3e75,0,0x3e2d,0,0x8000,0,0xbe2d,0,0x3e750000,0,0x3e2d0000,0,0x80000000,0,0xbe2d0000,0,
0,0x3e75,0,0x3e2d,0,0x8000,0,0xbe2d,0,0x3e750000,0,0x3e2d0000,0,0x80000000,0,0xbe2d0000,
0,0,0xbe2d,0,0xbe75,0,0xbe2d,0,0,0,0xbe2d0000,0,0xbe750000,0,0xbe2d0000,0,
0,0,0,0xbe2d,0,0xbe75,0,0xbe2d,0,0,0,0xbe2d0000,0,0xbe750000,0,0xbe2d0000,
0x3e75,0,0x3dde,0,0x8000,0,0xbe5a,0,0x3e750000,0,0x3dde0000,0,0x80000000,0,0xbe5a0000,0,
0,0x3e75,0,0x3dde,0,0x8000,0,0xbe5a,0,0x3e750000,0,0x3dde0000,0,0x80000000,0,0xbe5a0000,
0xbe10,0,0xbe72,0,0xbe46,0,0x3d19,0,0xbe100000,0,0xbe720000,0,0xbe460000,0,0x3d190000,0,
0,0xbe10,0,0xbe72,0,0xbe46,0,0x3d19,0,0xbe100000,0,0xbe720000,0,0xbe460000,0,0x3d190000,
0x3e75,0,0x3d19,0,0x8000,0,0xbe72,0,0x3e750000,0,0x3d190000,0,0x80000000,0,0xbe720000,0,
0,0x3e75,0,0x3d19,0,0x8000,0,0xbe72,0,0x3e750000,0,0x3d190000,0,0x80000000,0,0xbe720000,
0xbe69,0,0xbdde,0,0xbd97,0,0x3e5a,0,0xbe690000,0,0xbdde0000,0,0xbd970000,0,0x3e5a0000,0,
0,0xbe69,0,0xbdde,0,0xbd97,0,0x3e5a,0,0xbe690000,0,0xbdde0000,0,0xbd970000,0,0x3e5a0000,
0x3e75,0,0xbd19,0,0x8000,0,0xbe72,0,0x3e750000,0,0xbd190000,0,0x80000000,0,0xbe720000,0,
0,0x3e75,0,0xbd19,0,0x8000,0,0xbe72,0,0x3e750000,0,0xbd190000,0,0x80000000,0,0xbe720000,
0xbe69,0,0x3dde,0,0x3d97,0,0x3e5a,0,0xbe690000,0,0x3dde0000,0,0x3d970000,0,0x3e5a0000,0,
0,0xbe69,0,0x3dde,0,0x3d97,0,0x3e5a,0,0xbe690000,0,0x3dde0000,0,0x3d970000,0,0x3e5a0000,
0x3e75,0,0xbdde,0,0x8000,0,0xbe5a,0,0x3e750000,0,0xbdde0000,0,0x80000000,0,0xbe5a0000,0,
0,0x3e75,0,0xbdde,0,0x8000,0,0xbe5a,0,0x3e750000,0,0xbdde0000,0,0x80000000,0,0xbe5a0000,
0xbe10,0,0x3e72,0,0x3e46,0,0x3d19,0,0xbe100000,0,0x3e720000,0,0x3e460000,0,0x3d190000,0,
0,0xbe10,0,0x3e72,0,0x3e46,0,0x3d19,0,0xbe100000,0,0x3e720000,0,0x3e460000,0,0x3d190000,
0x3e75,0,0xbe2d,0,0x8000,0,0xbe2d,0,0x3e750000,0,0xbe2d0000,0,0x80000000,0,0xbe2d0000,0,
0,0x3e75,0,0xbe2d,0,0x8000,0,0xbe2d,0,0x3e750000,0,0xbe2d0000,0,0x80000000,0,0xbe2d0000,
0,0,0x3e2d,0,0x3e75,0,0xbe2d,0,0,0,0x3e2d0000,0,0x3e750000,0,0xbe2d0000,0,
0,0,0,0x3e2d,0,0x3e75,0,0xbe2d,0,0,0,0x3e2d0000,0,0x3e750000,0,0xbe2d0000,
0x3e75,0,0xbe5a,0,0x8000,0,0xbdde,0,0x3e750000,0,0xbe5a0000,0,0x80000000,0,0xbdde0000,0,
0,0x3e75,0,0xbe5a,0,0x8000,0,0xbdde,0,0x3e750000,0,0xbe5a0000,0,0x80000000,0,0xbdde0000,
0x3e10,0,0xbd19,0,0x3e46,0,0xbe72,0,0x3e100000,0,0xbd190000,0,0x3e460000,0,0xbe720000,0,
0,0x3e10,0,0xbd19,0,0x3e46,0,0xbe72,0,0x3e100000,0,0xbd190000,0,0x3e460000,0,0xbe720000,
0x3e75,0,0xbe72,0,0x8000,0,0xbd19,0,0x3e750000,0,0xbe720000,0,0x80000000,0,0xbd190000,0,
0,0x3e75,0,0xbe72,0,0x8000,0,0xbd19,0,0x3e750000,0,0xbe720000,0,0x80000000,0,0xbd190000,
0x3e69,0,0xbe5a,0,0x3d97,0,0xbdde,0,0x3e690000,0,0xbe5a0000,0,0x3d970000,0,0xbdde0000,0,
0,0x3e69,0,0xbe5a,0,0x3d97,0,0xbdde,0,0x3e690000,0,0xbe5a0000,0,0x3d970000,0,0xbdde0000,
0x3e46,0,0x3e2d,0,0xbe10,0,0xbe2d,0,0x3e460000,0,0x3e2d0000,0,0xbe100000,0,0xbe2d0000,0,
0,0x3e46,0,0x3e2d,0,0xbe10,0,0xbe2d,0,0x3e460000,0,0x3e2d0000,0,0xbe100000,0,0xbe2d0000,
0x3e10,0,0x3dde,0,0xbe46,0,0xbe5a,0,0x3e100000,0,0x3dde0000,0,0xbe460000,0,0xbe5a0000,0,
0,0x3e10,0,0x3dde,0,0xbe46,0,0xbe5a,0,0x3e100000,0,0x3dde0000,0,0xbe460000,0,0xbe5a0000,
0xbd97,0,0xbe2d,0,0xbe69,0,0xbe2d,0,0xbd970000,0,0xbe2d0000,0,0xbe690000,0,0xbe2d0000,0,
0,0xbd97,0,0xbe2d,0,0xbe69,0,0xbe2d,0,0xbd970000,0,0xbe2d0000,0,0xbe690000,0,0xbe2d0000,
0xbe69,0,0xbe72,0,0xbd97,0,0x3d19,0,0xbe690000,0,0xbe720000,0,0xbd970000,0,0x3d190000,0,
0,0xbe69,0,0xbe72,0,0xbd97,0,0x3d19,0,0xbe690000,0,0xbe720000,0,0xbd970000,0,0x3d190000,
0xbe75,0,0xbe2d,0,0x8000,0,0x3e2d,0,0xbe750000,0,0xbe2d0000,0,0x80000000,0,0x3e2d0000,0,
0,0xbe75,0,0xbe2d,0,0x8000,0,0x3e2d,0,0xbe750000,0,0xbe2d0000,0,0x80000000,0,0x3e2d0000,
0,0,0x3e2d,0,0x3e75,0,0x3e2d,0,0,0,0x3e2d0000,0,0x3e750000,0,0x3e2d0000,0,
0,0,0,0x3e2d,0,0x3e75,0,0x3e2d,0,0,0,0x3e2d0000,0,0x3e750000,0,0x3e2d0000,
0xbd97,0,0x3e2d,0,0x3e69,0,0x3e2d,0,0xbd970000,0,0x3e2d0000,0,0x3e690000,0,0x3e2d0000,0,
0,0xbd97,0,0x3e2d,0,0x3e69,0,0x3e2d,0,0xbd970000,0,0x3e2d0000,0,0x3e690000,0,0x3e2d0000,
0x3e69,0,0x3d19,0,0xbd97,0,0xbe72,0,0x3e690000,0,0x3d190000,0,0xbd970000,0,0xbe720000,0,
0,0x3e69,0,0x3d19,0,0xbd97,0,0xbe72,0,0x3e690000,0,0x3d190000,0,0xbd970000,0,0xbe720000,
0x3e46,0,0x3e2d,0,0x3e10,0,0xbe2d,0,0x3e460000,0,0x3e2d0000,0,0x3e100000,0,0xbe2d0000,0,
0,0x3e46,0,0x3e2d,0,0x3e10,0,0xbe2d,0,0x3e460000,0,0x3e2d0000,0,0x3e100000,0,0xbe2d0000,
0xbe10,0,0xbe5a,0,0xbe46,0,0x3dde,0,0xbe100000,0,0xbe5a0000,0,0xbe460000,0,0x3dde0000,0,
0,0xbe10,0,0xbe5a,0,0xbe46,0,0x3dde,0,0xbe100000,0,0xbe5a0000,0,0xbe460000,0,0x3dde0000,
0x3e46,0,0xbe2d,0,0xbe10,0,0xbe2d,0,0x3e460000,0,0xbe2d0000,0,0xbe100000,0,0xbe2d0000,0,
0,0x3e46,0,0xbe2d,0,0xbe10,0,0xbe2d,0,0x3e460000,0,0xbe2d0000,0,0xbe100000,0,0xbe2d0000,
0xbe10,0,0x3e5a,0,0x3e46,0,0x3dde,0,0xbe100000,0,0x3e5a0000,0,0x3e460000,0,0x3dde0000,0,
0,0xbe10,0,0x3e5a,0,0x3e46,0,0x3dde,0,0xbe100000,0,0x3e5a0000,0,0x3e460000,0,0x3dde0000,
0xbd97,0,0xbe2d,0,0xbe69,0,0x3e2d,0,0xbd970000,0,0xbe2d0000,0,0xbe690000,0,0x3e2d0000,0,
0,0xbd97,0,0xbe2d,0,0xbe69,0,0x3e2d,0,0xbd970000,0,0xbe2d0000,0,0xbe690000,0,0x3e2d0000,
0x3e69,0,0xbd19,0,0x3d97,0,0xbe72,0,0x3e690000,0,0xbd190000,0,0x3d970000,0,0xbe720000,0,
0,0x3e69,0,0xbd19,0,0x3d97,0,0xbe72,0,0x3e690000,0,0xbd190000,0,0x3d970000,0,0xbe720000,
0xbe75,0,0x3e2d,0,0x8000,0,0x3e2d,0,0xbe750000,0,0x3e2d0000,0,0x80000000,0,0x3e2d0000,0,
0,0xbe75,0,0x3e2d,0,0x8000,0,0x3e2d,0,0xbe750000,0,0x3e2d0000,0,0x80000000,0,0x3e2d0000,
0,0,0xbe2d,0,0xbe75,0,0x3e2d,0,0,0,0xbe2d0000,0,0xbe750000,0,0x3e2d0000,0,
0,0,0,0xbe2d,0,0xbe75,0,0x3e2d,0,0,0,0xbe2d0000,0,0xbe750000,0,0x3e2d0000,
0xbd97,0,0x3e2d,0,0x3e69,0,0xbe2d,0,0xbd970000,0,0x3e2d0000,0,0x3e690000,0,0xbe2d0000,0,
0,0xbd97,0,0x3e2d,0,0x3e69,0,0xbe2d,0,0xbd970000,0,0x3e2d0000,0,0x3e690000,0,0xbe2d0000,
0xbe69,0,0x3e72,0,0x3d97,0,0x3d19,0,0xbe690000,0,0x3e720000,0,0x3d970000,0,0x3d190000,0,
0,0xbe69,0,0x3e72,0,0x3d97,0,0x3d19,0,0xbe690000,0,0x3e720000,0,0x3d970000,0,0x3d190000,
0x3e46,0,0xbe2d,0,0x3e10,0,0xbe2d,0,0x3e460000,0,0xbe2d0000,0,0x3e100000,0,0xbe2d0000,0,
0,0x3e46,0,0xbe2d,0,0x3e10,0,0xbe2d,0,0x3e460000,0,0xbe2d0000,0,0x3e100000,0,0xbe2d0000,
0x3e10,0,0xbdde,0,0x3e46,0,0xbe5a,0,0x3e100000,0,0xbdde0000,0,0x3e460000,0,0xbe5a0000,0,
0,0x3e10,0,0xbdde,0,0x3e46,0,0xbe5a,0,0x3e100000,0,0xbdde0000,0,0x3e460000,0,0xbe5a0000,
0x3d97,0,0x3d19,0,0xbe69,0,0xbe72,0,0x3d970000,0,0x3d190000,0,0xbe690000,0,0xbe720000,0,
0,0x3d97,0,0x3d19,0,0xbe69,0,0xbe72,0,0x3d970000,0,0x3d190000,0,0xbe690000,0,0xbe720000,
0,0,0xbd19,0,0xbe75,0,0xbe72,0,0,0,0xbd190000,0,0xbe750000,0,0xbe720000,0,
0,0,0,0xbd19,0,0xbe75,0,0xbe72,0,0,0,0xbd190000,0,0xbe750000,0,0xbe720000,
0xbe46,0,0xbdde,0,0x3e10,0,0x3e5a,0,0xbe460000,0,0xbdde0000,0,0x3e100000,0,0x3e5a0000,0,
0,0xbe46,0,0xbdde,0,0x3e10,0,0x3e5a,0,0xbe460000,0,0xbdde0000,0,0x3e100000,0,0x3e5a0000,
0,0,0x3dde,0,0x3e75,0,0x3e5a,0,0,0,0x3dde0000,0,0x3e750000,0,0x3e5a0000,0,
0,0,0,0x3dde,0,0x3e75,0,0x3e5a,0,0,0,0x3dde0000,0,0x3e750000,0,0x3e5a0000,
0x3e75,0,0x3e2d,0,0x8000,0,0xbe2d,0,0x3e750000,0,0x3e2d0000,0,0x80000000,0,0xbe2d0000,0,
0,0x3e75,0,0x3e2d,0,0x8000,0,0xbe2d,0,0x3e750000,0,0x3e2d0000,0,0x80000000,0,0xbe2d0000,
0,0,0xbe2d,0,0xbe75,0,0xbe2d,0,0,0,0xbe2d0000,0,0xbe750000,0,0xbe2d0000,0,
0,0,0,0xbe2d,0,0xbe75,0,0xbe2d,0,0,0,0xbe2d0000,0,0xbe750000,0,0xbe2d0000,
0xbe46,0,0xbe5a,0,0xbe10,0,0x3dde,0,0xbe460000,0,0xbe5a0000,0,0xbe100000,0,0x3dde0000,0,
0,0xbe46,0,0xbe5a,0,0xbe10,0,0x3dde,0,0xbe460000,0,0xbe5a0000,0,0xbe100000,0,0x3dde0000,
0,0,0x3e5a,0,0x3e75,0,0x3dde,0,0,0,0x3e5a0000,0,0x3e750000,0,0x3dde0000,0,
0,0,0,0x3e5a,0,0x3e75,0,0x3dde,0,0,0,0x3e5a0000,0,0x3e750000,0,0x3dde0000,
0x3d97,0,0x3e72,0,0x3e69,0,0xbd19,0,0x3d970000,0,0x3e720000,0,0x3e690000,0,0xbd190000,0,
0,0x3d97,0,0x3e72,0,0x3e69,0,0xbd19,0,0x3d970000,0,0x3e720000,0,0x3e690000,0,0xbd190000,
0,0,0xbe72,0,0xbe75,0,0xbd19,0,0,0,0xbe720000,0,0xbe750000,0,0xbd190000,0,
0,0,0,0xbe72,0,0xbe75,0,0xbd19,0,0,0,0xbe720000,0,0xbe750000,0,0xbd190000,
0x3d97,0,0xbe72,0,0xbe69,0,0xbd19,0,0x3d970000,0,0xbe720000,0,0xbe690000,0,0xbd190000,0,
0,0x3d97,0,0xbe72,0,0xbe69,0,0xbd19,0,0x3d970000,0,0xbe720000,0,0xbe690000,0,0xbd190000,
0,0,0x3e72,0,0x3e75,0,0xbd19,0,0,0,0x3e720000,0,0x3e750000,0,0xbd190000,0,
0,0,0,0x3e72,0,0x3e75,0,0xbd19,0,0,0,0x3e720000,0,0x3e750000,0,0xbd190000,
0xbe46,0,0x3e5a,0,0x3e10,0,0x3dde,0,0xbe460000,0,0x3e5a0000,0,0x3e100000,0,0x3dde0000,0,
0,0xbe46,0,0x3e5a,0,0x3e10,0,0x3dde,0,0xbe460000,0,0x3e5a0000,0,0x3e100000,0,0x3dde0000,
0,0,0xbe5a,0,0xbe75,0,0x3dde,0,0,0,0xbe5a0000,0,0xbe750000,0,0x3dde0000,0,
0,0,0,0xbe5a,0,0xbe75,0,0x3dde,0,0,0,0xbe5a0000,0,0xbe750000,0,0x3dde0000,
0x3e75,0,0xbe2d,0,0x8000,0,0xbe2d,0,0x3e750000,0,0xbe2d0000,0,0x80000000,0,0xbe2d0000,0,
0,0x3e75,0,0xbe2d,0,0x8000,0,0xbe2d,0,0x3e750000,0,0xbe2d0000,0,0x80000000,0,0xbe2d0000,
0,0,0x3e2d,0,0x3e75,0,0xbe2d,0,0,0,0x3e2d0000,0,0x3e750000,0,0xbe2d0000,0,
0,0,0,0x3e2d,0,0x3e75,0,0xbe2d,0,0,0,0x3e2d0000,0,0x3e750000,0,0xbe2d0000,
0xbe46,0,0x3dde,0,0xbe10,0,0x3e5a,0,0xbe460000,0,0x3dde0000,0,0xbe100000,0,0x3e5a0000,0,
0,0xbe46,0,0x3dde,0,0xbe10,0,0x3e5a,0,0xbe460000,0,0x3dde0000,0,0xbe100000,0,0x3e5a0000,
0,0,0xbdde,0,0xbe75,0,0x3e5a,0,0,0,0xbdde0000,0,0xbe750000,0,0x3e5a0000,0,
0,0,0,0xbdde,0,0xbe75,0,0x3e5a,0,0,0,0xbdde0000,0,0xbe750000,0,0x3e5a0000,
0x3d97,0,0xbd19,0,0x3e69,0,0xbe72,0,0x3d970000,0,0xbd190000,0,0x3e690000,0,0xbe720000,0,
0,0x3d97,0,0xbd19,0,0x3e69,0,0xbe72,0,0x3d970000,0,0xbd190000,0,0x3e690000,0,0xbe720000,
0,0,0x3d19,0,0x3e75,0,0xbe72,0,0,0,0x3d190000,0,0x3e750000,0,0xbe720000,0,
0,0,0,0x3d19,0,0x3e75,0,0xbe72,0,0,0,0x3d190000,0,0x3e750000,0,0xbe720000,
0xbd97,0,0xbdde,0,0xbe69,0,0xbe5a,0,0xbd970000,0,0xbdde0000,0,0xbe690000,0,0xbe5a0000,0,
0,0xbd97,0,0xbdde,0,0xbe69,0,0xbe5a,0,0xbd970000,0,0xbdde0000,0,0xbe690000,0,0xbe5a0000,
0xbe10,0,0xbe2d,0,0xbe46,0,0xbe2d,0,0xbe100000,0,0xbe2d0000,0,0xbe460000,0,0xbe2d0000,0,
0,0xbe10,0,0xbe2d,0,0xbe46,0,0xbe2d,0,0xbe100000,0,0xbe2d0000,0,0xbe460000,0,0xbe2d0000,
0x3e46,0,0x3e72,0,0x3e10,0,0x3d19,0,0x3e460000,0,0x3e720000,0,0x3e100000,0,0x3d190000,0,
0,0x3e46,0,0x3e72,0,0x3e10,0,0x3d19,0,0x3e460000,0,0x3e720000,0,0x3e100000,0,0x3d190000,
0x3e69,0,0x3e2d,0,0xbd97,0,0xbe2d,0,0x3e690000,0,0x3e2d0000,0,0xbd970000,0,0xbe2d0000,0,
0,0x3e69,0,0x3e2d,0,0xbd97,0,0xbe2d,0,0x3e690000,0,0x3e2d0000,0,0xbd970000,0,0xbe2d0000,
0xbe75,0,0xbe2d,0,0x8000,0,0x3e2d,0,0xbe750000,0,0xbe2d0000,0,0x80000000,0,0x3e2d0000,0,
0,0xbe75,0,0xbe2d,0,0x8000,0,0x3e2d,0,0xbe750000,0,0xbe2d0000,0,0x80000000,0,0x3e2d0000,
0,0,0x3e2d,0,0x3e75,0,0x3e2d,0,0,0,0x3e2d0000,0,0x3e750000,0,0x3e2d0000,0,
0,0,0,0x3e2d,0,0x3e75,0,0x3e2d,0,0,0,0x3e2d0000,0,0x3e750000,0,0x3e2d0000,
0x3e46,0,0xbd19,0,0xbe10,0,0xbe72,0,0x3e460000,0,0xbd190000,0,0xbe100000,0,0xbe720000,0,
0,0x3e46,0,0xbd19,0,0xbe10,0,0xbe72,0,0x3e460000,0,0xbd190000,0,0xbe100000,0,0xbe720000,
0xbe69,0,0xbe2d,0,0xbd97,0,0x3e2d,0,0xbe690000,0,0xbe2d0000,0,0xbd970000,0,0x3e2d0000,0,
0,0xbe69,0,0xbe2d,0,0xbd97,0,0x3e2d,0,0xbe690000,0,0xbe2d0000,0,0xbd970000,0,0x3e2d0000,
0xbd97,0,0x3e5a,0,0x3e69,0,0x3dde,0,0xbd970000,0,0x3e5a0000,0,0x3e690000,0,0x3dde0000,0,
0,0xbd97,0,0x3e5a,0,0x3e69,0,0x3dde,0,0xbd970000,0,0x3e5a0000,0,0x3e690000,0,0x3dde0000,
0x3e10,0,0xbe2d,0,0xbe46,0,0xbe2d,0,0x3e100000,0,0xbe2d0000,0,0xbe460000,0,0xbe2d0000,0,
0,0x3e10,0,0xbe2d,0,0xbe46,0,0xbe2d,0,0x3e100000,0,0xbe2d0000,0,0xbe460000,0,0xbe2d0000,
0xbd97,0,0xbe5a,0,0xbe69,0,0x3dde,0,0xbd970000,0,0xbe5a0000,0,0xbe690000,0,0x3dde0000,0,
0,0xbd97,0,0xbe5a,0,0xbe69,0,0x3dde,0,0xbd970000,0,0xbe5a0000,0,0xbe690000,0,0x3dde0000,
0x3e10,0,0x3e2d,0,0x3e46,0,0xbe2d,0,0x3e100000,0,0x3e2d0000,0,0x3e460000,0,0xbe2d0000,0,
0,0x3e10,0,0x3e2d,0,0x3e46,0,0xbe2d,0,0x3e100000,0,0x3e2d0000,0,0x3e460000,0,0xbe2d0000,
0x3e46,0,0x3d19,0,0x3e10,0,0xbe72,0,0x3e460000,0,0x3d190000,0,0x3e100000,0,0xbe720000,0,
0,0x3e46,0,0x3d19,0,0x3e10,0,0xbe72,0,0x3e460000,0,0x3d190000,0,0x3e100000,0,0xbe720000,
0xbe69,0,0x3e2d,0,0x3d97,0,0x3e2d,0,0xbe690000,0,0x3e2d0000,0,0x3d970000,0,0x3e2d0000,0,
0,0xbe69,0,0x3e2d,0,0x3d97,0,0x3e2d,0,0xbe690000,0,0x3e2d0000,0,0x3d970000,0,0x3e2d0000,
0xbe75,0,0x3e2d,0,0x8000,0,0x3e2d,0,0xbe750000,0,0x3e2d0000,0,0x80000000,0,0x3e2d0000,0,
0,0xbe75,0,0x3e2d,0,0x8000,0,0x3e2d,0,0xbe750000,0,0x3e2d0000,0,0x80000000,0,0x3e2d0000,
0,0,0xbe2d,0,0xbe75,0,0x3e2d,0,0,0,0xbe2d0000,0,0xbe750000,0,0x3e2d0000,0,
0,0,0,0xbe2d,0,0xbe75,0,0x3e2d,0,0,0,0xbe2d0000,0,0xbe750000,0,0x3e2d0000,
0x3e46,0,0xbe72,0,0xbe10,0,0x3d19,0,0x3e460000,0,0xbe720000,0,0xbe100000,0,0x3d190000,0,
0,0x3e46,0,0xbe72,0,0xbe10,0,0x3d19,0,0x3e460000,0,0xbe720000,0,0xbe100000,0,0x3d190000,
0x3e69,0,0xbe2d,0,0x3d97,0,0xbe2d,0,0x3e690000,0,0xbe2d0000,0,0x3d970000,0,0xbe2d0000,0,
0,0x3e69,0,0xbe2d,0,0x3d97,0,0xbe2d,0,0x3e690000,0,0xbe2d0000,0,0x3d970000,0,0xbe2d0000,
0xbd97,0,0x3dde,0,0x3e69,0,0xbe5a,0,0xbd970000,0,0x3dde0000,0,0x3e690000,0,0xbe5a0000,0,
0,0xbd97,0,0x3dde,0,0x3e69,0,0xbe5a,0,0xbd970000,0,0x3dde0000,0,0x3e690000,0,0xbe5a0000,
0xbe10,0,0x3e2d,0,0x3e46,0,0xbe2d,0,0xbe100000,0,0x3e2d0000,0,0x3e460000,0,0xbe2d0000,0,
0,0xbe10,0,0x3e2d,0,0x3e46,0,0xbe2d,0,0xbe100000,0,0x3e2d0000,0,0x3e460000,0,0xbe2d0000,
0xbe46,0,0xbe5a,0,0xbe10,0,0xbdde,0,0xbe460000,0,0xbe5a0000,0,0xbe100000,0,0xbdde0000,0,
0,0xbe46,0,0xbe5a,0,0xbe10,0,0xbdde,0,0xbe460000,0,0xbe5a0000,0,0xbe100000,0,0xbdde0000,
0xbe69,0,0xbe72,0,0xbd97,0,0xbd19,0,0xbe690000,0,0xbe720000,0,0xbd970000,0,0xbd190000,0,
0,0xbe69,0,0xbe72,0,0xbd97,0,0xbd19,0,0xbe690000,0,0xbe720000,0,0xbd970000,0,0xbd190000,
0x3d97,0,0xbd19,0,0xbe69,0,0xbe72,0,0x3d970000,0,0xbd190000,0,0xbe690000,0,0xbe720000,0,
0,0x3d97,0,0xbd19,0,0xbe69,0,0xbe72,0,0x3d970000,0,0xbd190000,0,0xbe690000,0,0xbe720000,
0xbe10,0,0xbe5a,0,0xbe46,0,0xbdde,0,0xbe100000,0,0xbe5a0000,0,0xbe460000,0,0xbdde0000,0,
0,0xbe10,0,0xbe5a,0,0xbe46,0,0xbdde,0,0xbe100000,0,0xbe5a0000,0,0xbe460000,0,0xbdde0000,
0x3e75,0,0x3e2d,0,0x8000,0,0xbe2d,0,0x3e750000,0,0x3e2d0000,0,0x80000000,0,0xbe2d0000,0,
0,0x3e75,0,0x3e2d,0,0x8000,0,0xbe2d,0,0x3e750000,0,0x3e2d0000,0,0x80000000,0,0xbe2d0000,
0,0,0xbe2d,0,0xbe75,0,0xbe2d,0,0,0,0xbe2d0000,0,0xbe750000,0,0xbe2d0000,0,
0,0,0,0xbe2d,0,0xbe75,0,0xbe2d,0,0,0,0xbe2d0000,0,0xbe750000,0,0xbe2d0000,
0x3d97,0,0x3e72,0,0x3e69,0,0x3d19,0,0x3d970000,0,0x3e720000,0,0x3e690000,0,0x3d190000,0,
0,0x3d97,0,0x3e72,0,0x3e69,0,0x3d19,0,0x3d970000,0,0x3e720000,0,0x3e690000,0,0x3d190000,
0x3e10,0,0xbdde,0,0xbe46,0,0xbe5a,0,0x3e100000,0,0xbdde0000,0,0xbe460000,0,0xbe5a0000,0,
0,0x3e10,0,0xbdde,0,0xbe46,0,0xbe5a,0,0x3e100000,0,0xbdde0000,0,0xbe460000,0,0xbe5a0000,
0xbe46,0,0x3dde,0,0x3e10,0,0x3e5a,0,0xbe460000,0,0x3dde0000,0,0x3e100000,0,0x3e5a0000,0,
0,0xbe46,0,0x3dde,0,0x3e10,0,0x3e5a,0,0xbe460000,0,0x3dde0000,0,0x3e100000,0,0x3e5a0000,
0x3e69,0,0xbd19,0,0xbd97,0,0xbe72,0,0x3e690000,0,0xbd190000,0,0xbd970000,0,0xbe720000,0,
0,0x3e69,0,0xbd19,0,0xbd97,0,0xbe72,0,0x3e690000,0,0xbd190000,0,0xbd970000,0,0xbe720000,
0xbe46,0,0xbdde,0,0xbe10,0,0x3e5a,0,0xbe460000,0,0xbdde0000,0,0xbe100000,0,0x3e5a0000,0,
0,0xbe46,0,0xbdde,0,0xbe10,0,0x3e5a,0,0xbe460000,0,0xbdde0000,0,0xbe100000,0,0x3e5a0000,
0x3e69,0,0x3d19,0,0x3d97,0,0xbe72,0,0x3e690000,0,0x3d190000,0,0x3d970000,0,0xbe720000,0,
0,0x3e69,0,0x3d19,0,0x3d97,0,0xbe72,0,0x3e690000,0,0x3d190000,0,0x3d970000,0,0xbe720000,
0x3d97,0,0xbe72,0,0xbe69,0,0x3d19,0,0x3d970000,0,0xbe720000,0,0xbe690000,0,0x3d190000,0,
0,0x3d97,0,0xbe72,0,0xbe69,0,0x3d19,0,0x3d970000,0,0xbe720000,0,0xbe690000,0,0x3d190000,
0x3e10,0,0x3dde,0,0x3e46,0,0xbe5a,0,0x3e100000,0,0x3dde0000,0,0x3e460000,0,0xbe5a0000,0,
0,0x3e10,0,0x3dde,0,0x3e46,0,0xbe5a,0,0x3e100000,0,0x3dde0000,0,0x3e460000,0,0xbe5a0000,
0x3e75,0,0xbe2d,0,0x8000,0,0xbe2d,0,0x3e750000,0,0xbe2d0000,0,0x80000000,0,0xbe2d0000,0,
0,0x3e75,0,0xbe2d,0,0x8000,0,0xbe2d,0,0x3e750000,0,0xbe2d0000,0,0x80000000,0,0xbe2d0000,
0,0,0x3e2d,0,0x3e75,0,0xbe2d,0,0,0,0x3e2d0000,0,0x3e750000,0,0xbe2d0000,0,
0,0,0,0x3e2d,0,0x3e75,0,0xbe2d,0,0,0,0x3e2d0000,0,0x3e750000,0,0xbe2d0000,
0x3d97,0,0x3d19,0,0x3e69,0,0xbe72,0,0x3d970000,0,0x3d190000,0,0x3e690000,0,0xbe720000,0,
0,0x3d97,0,0x3d19,0,0x3e69,0,0xbe72,0,0x3d970000,0,0x3d190000,0,0x3e690000,0,0xbe720000,
0xbe10,0,0x3e5a,0,0x3e46,0,0xbdde,0,0xbe100000,0,0x3e5a0000,0,0x3e460000,0,0xbdde0000,0,
0,0xbe10,0,0x3e5a,0,0x3e46,0,0xbdde,0,0xbe100000,0,0x3e5a0000,0,0x3e460000,0,0xbdde0000,
0xbe46,0,0x3e5a,0,0x3e10,0,0xbdde,0,0xbe460000,0,0x3e5a0000,0,0x3e100000,0,0xbdde0000,0,
0,0xbe46,0,0x3e5a,0,0x3e10,0,0xbdde,0,0xbe460000,0,0x3e5a0000,0,0x3e100000,0,0xbdde0000,
0xbe69,0,0x3e72,0,0x3d97,0,0xbd19,0,0xbe690000,0,0x3e720000,0,0x3d970000,0,0xbd190000,0,
0,0xbe69,0,0x3e72,0,0x3d97,0,0xbd19,0,0xbe690000,0,0x3e720000,0,0x3d970000,0,0xbd190000,
0x3eb7,0x3eb7,0x3eb7,0x3eb7,0x3eb78000,0x3eb78000,0x3eb78000,0x3eb78000,0x3eb7,0x3de23eae,0x3e573e94,0x3e943e57,0x3eb78000,0x3eaebde2,0x3e94be57,0x3e57be94,
0x3eb7,0x3e573e94,0x3eae3de2,0x3eaebde2,0x3eb78000,0x3e94be57,0x3de2beae,0xbde2beae,0x3eb7,0x3e943e57,0x3eaebde2,0x3de2beae,0x3eb78000,0x3e57be94,0xbde2beae,0xbeaebde2,
0x3eb7,0x3eb7,0x3eb7,0x3eb7,0x3eb78000,0x3eb78000,0x3eb78000,0x3eb78000,0x3eae3de2,0x3eb70000,0x3eaebde2,0x3e94be57,0x3de2beae,0xbeb7,0xbde2beae,0xbe57be94,
0x3e57be94,0xbeb7,0xbe57be94,0xbeaebde2,0xbe94be57,0xbeb78000,0xbe943e57,0xbde23eae,0xbe57be94,0xbeb70000,0xbe573e94,0x3de23eae,0xbe943e57,0x3eb7,0x3e943e57,0x3eaebde2,
0x3eb7,0x3eae3de2,0x3e57be94,0xbe57be94,0x3eb78000,0x3de2beae,0xbe94be57,0xbe943e57,0x3eb7,0x3eb70000,0xbeb7,0xbeb70000,0x3eb78000,0xbeb7,0xbeb78000,0x3eb7,
0x3eb7,0x3eaebde2,0xbe57be94,0xbe573e94,0x3eb78000,0xbde2beae,0xbe943e57,0x3e943e57,0x3eb7,0x3e94be57,0xbeaebde2,0x3de23eae,0x3eb78000,0xbe57be94,0xbde23eae,0x3eaebde2,
0xbeae3de2,0x3eb7,0x3eae3de2,0x3e57be94,0x3de23eae,0x3eb78000,0x3de2beae,0xbe94be57,0x3eb7,0x3eb70000,0xbeb7,0xbeb70000,0x3eb78000,0xbeb7,0xbeb78000,0x3eb7,
0x3eae3de2,0xbeb7,0xbeae3de2,0x3e573e94,0x3de2beae,0xbeb78000,0x3de23eae,0x3e94be57,0x3e57be94,0xbeb70000,0x3e573e94,0x3de2beae,0xbe94be57,0x3eb7,0x3e94be57,0xbeaebde2,
0x3eb7,0x3e57be94,0xbeae3de2,0x3eae3de2,0x3eb78000,0xbe94be57,0x3de23eae,0x3de2beae,0x3eb7,0x3de2beae,0xbe573e94,0x3e94be57,0x3eb78000,0xbeaebde2,0x3e943e57,0xbe57be94,
0x3eb7,0xbeb7,0x3eb7,0xbeb7,0x3eb78000,0xbeb78000,0x3eb78000,0xbeb78000,0x3eb7,0xbde2beae,0x3e573e94,0xbe94be57,0x3eb78000,0xbeae3de2,0x3e94be57,0xbe573e94,
0xbe57be94,0x3eb7,0x3e57be94,0xbeae3de2,0xbe943e57,0x3eb78000,0xbe94be57,0x3de23eae,0xbeae3de2,0x3eb70000,0xbeaebde2,0x3e943e57,0x3de23eae,0xbeb7,0xbde23eae,0x3e57be94,
0x3eb7,0xbeb7,0x3eb7,0xbeb7,0x3eb78000,0xbeb78000,0x3eb78000,0xbeb78000,0x3eae3de2,0xbeb70000,0x3eaebde2,0xbe943e57,0x3de2beae,0x3eb7,0xbde2beae,0x3e573e94,
0x3eb7,0xbe57be94,0x3eae3de2,0xbeae3de2,0x3eb78000,0xbe943e57,0x3de2beae,0x3de23eae,0x3eb7,0xbe94be57,0x3eaebde2,0xbde23eae,0x3eb78000,0xbe573e94,0xbde2beae,0x3eae3de2,
0x3eb7,0xbeaebde2,0x3e57be94,0x3e573e94,0x3eb78000,0xbde23eae,0xbe94be57,0x3e94be57,0x3eb7,0xbeb70000,0xbeb7,0x3eb70000,0x3eb78000,0x3eb7,0xbeb78000,0xbeb7,
0x3e57be94,0x3eb7,0xbe57be94,0x3eae3de2,0xbe94be57,0x3eb78000,0xbe943e57,0x3de2beae,0xbe57be94,0x3eb70000,0xbe573e94,0xbde2beae,0xbe943e57,0xbeb7,0x3e943e57,0xbeae3de2,
0xbeae3de2,0xbeb7,0x3eae3de2,0xbe573e94,0x3de23eae,0xbeb78000,0x3de2beae,0x3e943e57,0x3eb7,0xbeb70000,0xbeb7,0x3eb70000,0x3eb78000,0x3eb7,0xbeb78000,0xbeb7,
0x3eb7,0xbeae3de2,0xbe57be94,0x3e57be94,0x3eb78000,0x3de23eae,0xbe943e57,0xbe94be57,0x3eb7,0xbe943e57,0xbeaebde2,0xbde2beae,0x3eb78000,0x3e573e94,0xbde23eae,0xbeae3de2,
0x3eb7,0xbe573e94,0xbeae3de2,0xbeaebde2,0x3eb78000,0x3e943e57,0x3de23eae,0xbde23eae,0x3eb7,0xbde23eae,0xbe573e94,0xbe943e57,0x3eb78000,0x3eae3de2,0x3e943e57,0x3e573e94,
0x3eae3de2,0x3eb7,0xbeae3de2,0xbe57be94,0x3de2beae,0x3eb78000,0x3de23eae,0xbe943e57,0x3e57be94,0x3eb70000,0x3e573e94,0xbde23eae,0xbe94be57,0xbeb7,0x3e94be57,0x3eae3de2,
0xbe57be94,0xbeb7,0x3e57be94,0x3eaebde2,0xbe943e57,0xbeb78000,0xbe94be57,0xbde2beae,0xbeae3de2,0xbeb70000,0xbeaebde2,0xbe94be57,0x3de23eae,0x3eb7,0xbde23eae,0xbe573e94,
0x3eb7,0x3eb7,0x3eb7,0x3eb7,0x3eb78000,0x3eb78000,0x3eb78000,0x3eb78000,0x3e57be94,0x3de2beae,0xbeb7,0xbde2beae,0xbe94be57,0xbeaebde2,0xbeb78000,0xbeae3de2,
0xbeae3de2,0xbe573e94,0x3eb7,0x3e573e94,0x3de23eae,0x3e943e57,0x3eb78000,0x3e94be57,0x3eae3de2,0x3e94be57,0xbeb7,0xbe94be57,0x3de2beae,0xbe57be94,0xbeb78000,0xbe573e94,
0x3eb7,0x3eb7,0x3eb7,0x3eb7,0x3eb78000,0x3eb78000,0x3eb78000,0x3eb78000,0xbe57be94,0xbe94be57,0xbeaebde2,0xbeb70000,0xbe943e57,0xbe573e94,0xbde23eae,0x3eb7,
0x3eae3de2,0x3eaebde2,0x3e57be94,0xbeb7,0x3de2beae,0xbde2beae,0xbe94be57,0xbeb78000,0xbeae3de2,0xbde23eae,0x3e573e94,0x3eb70000,0x3de23eae,0x3eae3de2,0x3e94be57,0xbeb7,
0xbe57be94,0xbeae3de2,0x3eb7,0x3eae3de2,0xbe943e57,0x3de23eae,0x3eb78000,0x3de2beae,0x3eb7,0x3eb70000,0xbeb7,0xbeb70000,0x3eb78000,0xbeb7,0xbeb78000,0x3eb7,
0x3e57be94,0xbeaebde2,0x3eb7,0x3eaebde2,0xbe94be57,0xbde23eae,0x3eb78000,0xbde2beae,0xbeae3de2,0x3e943e57,0xbeb7,0xbe943e57,0x3de23eae,0x3e57be94,0xbeb78000,0x3e573e94,
0x3e57be94,0xbe57be94,0xbeae3de2,0x3eb7,0xbe94be57,0xbe943e57,0x3de23eae,0x3eb78000,0x3eb7,0x3eb70000,0xbeb7,0xbeb70000,0x3eb78000,0xbeb7,0xbeb78000,0x3eb7,
0xbe57be94,0xbe573e94,0x3eae3de2,0xbeb7,0xbe943e57,0x3e943e57,0x3de2beae,0xbeb78000,0x3eae3de2,0xbde2beae,0xbe573e94,0x3eb70000,0x3de2beae,0xbeae3de2,0x3e943e57,0xbeb7,
0x3eae3de2,0xbe57be94,0x3eb7,0x3e57be94,0x3de2beae,0xbe943e57,0x3eb78000,0xbe94be57,0xbe57be94,0x3de23eae,0xbeb7,0xbde23eae,0xbe943e57,0x3eaebde2,0xbeb78000,0x3eae3de2,
0x3eb7,0xbeb7,0x3eb7,0xbeb7,0x3eb78000,0xbeb78000,0x3eb78000,0xbeb78000,0x3e57be94,0xbde23eae,0xbeb7,0x3de23eae,0xbe94be57,0x3eae3de2,0xbeb78000,0x3eaebde2,
0xbeae3de2,0x3eae3de2,0xbe57be94,0x3eb7,0x3de23eae,0x3de2beae,0xbe943e57,0x3eb78000,0x3e57be94,0xbe943e57,0x3eaebde2,0xbeb70000,0xbe94be57,0x3e573e94,0xbde2beae,0x3eb7,
0x3eb7,0xbeb7,0x3eb7,0xbeb7,0x3eb78000,0xbeb78000,0x3eb78000,0xbeb78000,0xbe57be94,0x3e943e57,0xbeaebde2,0x3eb70000,0xbe943e57,0x3e57be94,0xbde23eae,0xbeb7,
0xbeae3de2,0x3e57be94,0x3eb7,0xbe57be94,0x3de23eae,0xbe94be57,0x3eb78000,0xbe943e57,0x3eae3de2,0xbe943e57,0xbeb7,0x3e943e57,0x3de2beae,0x3e573e94,0xbeb78000,0x3e57be94,
0xbe57be94,0x3eaebde2,0x3eb7,0xbeaebde2,0xbe943e57,0xbde2beae,0x3eb78000,0xbde23eae,0x3eb7,0xbeb70000,0xbeb7,0x3eb70000,0x3eb78000,0x3eb7,0xbeb78000,0xbeb7,
0x3eae3de2,0xbeae3de2,0x3e57be94,0x3eb7,0x3de2beae,0x3de23eae,0xbe94be57,0x3eb78000,0xbeae3de2,0x3de2beae,0x3e573e94,0xbeb70000,0x3de23eae,0xbeaebde2,0x3e94be57,0x3eb7,
0x3e57be94,0x3e573e94,0xbeae3de2,0xbeb7,0xbe94be57,0x3e94be57,0x3de23eae,0xbeb78000,0x3eb7,0xbeb70000,0xbeb7,0x3eb70000,0x3eb78000,0x3eb7,0xbeb78000,0xbeb7,
0x3e57be94,0x3eae3de2,0x3eb7,0xbeae3de2,0xbe94be57,0x3de2beae,0x3eb78000,0x3de23eae,0xbeae3de2,0xbe94be57,0xbeb7,0x3e94be57,0x3de23eae,0xbe573e94,0xbeb78000,0xbe57be94,
0x3eae3de2,0x3e573e94,0x3eb7,0xbe573e94,0x3de2beae,0x3e94be57,0x3eb78000,0x3e943e57,0xbe57be94,0xbde2beae,0xbeb7,0x3de2beae,0xbe943e57,0xbeae3de2,0xbeb78000,0xbeaebde2,
0xbe57be94,0x3e57be94,0x3eae3de2,0x3eb7,0xbe943e57,0xbe94be57,0x3de2beae,0x3eb78000,0x3eae3de2,0x3de23eae,0xbe573e94,0xbeb70000,0x3de2beae,0x3eaebde2,0x3e943e57,0x3eb7,
0xbeae3de2,0xbeaebde2,0xbe57be94,0xbeb7,0x3de23eae,0xbde23eae,0xbe943e57,0xbeb78000,0x3e57be94,0x3e94be57,0x3eaebde2,0x3eb70000,0xbe94be57,0xbe57be94,0xbde2beae,0xbeb7,
0x3eb7,0x3eb7,0x3eb7,0x3eb7,0x3eb78000,0x3eb78000,0x3eb78000,0x3eb78000,0xbeae3de2,0xbe943e57,0xbe573e94,0xbde23eae,0x3de23eae,0x3e573e94,0x3e943e57,0x3eae3de2,
0xbe57be94,0xbeaebde2,0xbeae3de2,0xbe573e94,0xbe943e57,0xbde23eae,0x3de23eae,0x3e943e57,0x3e57be94,0xbde2beae,0xbeaebde2,0xbe943e57,0xbe94be57,0xbeae3de2,0xbde23eae,0x3e573e94,
0,0,0,0,0,0,0,0,0,0,0,0,0,0,0,0,
0,0,0,0,0,0,0,0,0,0,0,0,0,0,0,0,
0x3eae3de2,0x3e57be94,0xbe57be94,0xbeae3de2,0x3de2beae,0xbe94be57,0xbe943e57,0x3de23eae,0x3eb7,0x3eb70000,0xbeb7,0xbeb70000,0x3eb78000,0xbeb7,0xbeb78000,0x3eb7,
0xbeae3de2,0x3e573e94,0x3e57be94,0xbeaebde2,0x3de23eae,0x3e94be57,0xbe94be57,0xbde23eae,0xbe57be94,0xbde23eae,0x3eaebde2,0xbe94be57,0xbe943e57,0x3eae3de2,0xbde2beae,0xbe573e94,
0,0,0,0,0,0,0,0,0,0,0,0,0,0,0,0,
0,0,0,0,0,0,0,0,0,0,0,0,0,0,0,0,
0x3e57be94,0xbeae3de2,0x3eae3de2,0xbe57be94,0xbe94be57,0x3de23eae,0x3de2beae,0xbe943e57,0x3eae3de2,0xbe94be57,0x3e573e94,0xbde2beae,0x3de2beae,0xbe573e94,0x3e94be57,0xbeae3de2,
0x3eb7,0xbeb7,0x3eb7,0xbeb7,0x3eb78000,0xbeb78000,0x3eb78000,0xbeb78000,0xbeae3de2,0x3e94be57,0xbe573e94,0x3de2beae,0x3de23eae,0xbe57be94,0x3e943e57,0xbeaebde2,
0,0,0,0,0,0,0,0,0,0,0,0,0,0,0,0,
0,0,0,0,0,0,0,0,0,0,0,0,0,0,0,0,
0xbe57be94,0x3eae3de2,0xbeae3de2,0x3e57be94,0xbe943e57,0x3de2beae,0x3de23eae,0xbe94be57,0x3e57be94,0x3de23eae,0xbeaebde2,0x3e94be57,0xbe94be57,0x3eaebde2,0xbde23eae,0xbe57be94,
0x3eae3de2,0xbe573e94,0xbe57be94,0x3eaebde2,0x3de2beae,0x3e943e57,0xbe943e57,0xbde2beae,0x3eb7,0xbeb70000,0xbeb7,0x3eb70000,0x3eb78000,0x3eb7,0xbeb78000,0xbeb7,
0,0,0,0,0,0,0,0,0,0,0,0,0,0,0,0,
0,0,0,0,0,0,0,0,0,0,0,0,0,0,0,0,
0xbeae3de2,0xbe57be94,0x3e57be94,0x3eae3de2,0x3de23eae,0xbe943e57,0xbe94be57,0x3de2beae,0xbe57be94,0x3de2beae,0x3eaebde2,0x3e943e57,0xbe943e57,0xbeaebde2,0xbde2beae,0x3e57be94,
0x3e57be94,0x3eaebde2,0x3eae3de2,0x3e573e94,0xbe94be57,0xbde2beae,0x3de2beae,0x3e94be57,0x3eae3de2,0x3e943e57,0x3e573e94,0x3de23eae,0x3de2beae,0x3e57be94,0x3e94be57,0x3eaebde2,
0,0,0,0,0,0,0,0,0,0,0,0,0,0,0,0,
0,0,0,0,0,0,0,0,0,0,0,0,0,0,0,0,
0,0,0,0,0,0,0,0,0,0,0,0,0,0,0,0,
0,0,0,0,0,0,0,0,0,0,0,0,0,0,0,0,
0x3eb7,0x3eb7,0x3eb7,0x3eb7,0x3eb78000,0x3eb78000,0x3eb78000,0x3eb78000,0xbeae3de2,0xbe943e57,0xbe573e94,0xbde23eae,0x3de23eae,0x3e573e94,0x3e943e57,0x3eae3de2,
0xbe57be94,0xbeaebde2,0xbeae3de2,0xbe573e94,0xbe943e57,0xbde23eae,0x3de23eae,0x3e943e57,0x3e57be94,0xbde2beae,0xbeaebde2,0xbe943e57,0xbe94be57,0xbeae3de2,0xbde23eae,0x3e573e94,
0,0,0,0,0,0,0,0,0,0,0,0,0,0,0,0,
0,0,0,0,0,0,0,0,0,0,0,0,0,0,0,0,
0x3eae3de2,0x3e57be94,0xbe57be94,0xbeae3de2,0x3de2beae,0xbe94be57,0xbe943e57,0x3de23eae,0x3eb7,0x3eb70000,0xbeb7,0xbeb70000,0x3eb78000,0xbeb7,0xbeb78000,0x3eb7,
0xbeae3de2,0x3e573e94,0x3e57be94,0xbeaebde2,0x3de23eae,0x3e94be57,0xbe94be57,0xbde23eae,0xbe57be94,0xbde23eae,0x3eaebde2,0xbe94be57,0xbe943e57,0x3eae3de2,0xbde2beae,0xbe573e94,
0,0,0,0,0,0,0,0,0,0,0,0,0,0,0,0,
0,0,0,0,0,0,0,0,0,0,0,0,0,0,0,0,
0x3e57be94,0xbeae3de2,0x3eae3de2,0xbe57be94,0xbe94be57,0x3de23eae,0x3de2beae,0xbe943e57,0x3eae3de2,0xbe94be57,0x3e573e94,0xbde2beae,0x3de2beae,0xbe573e94,0x3e94be57,0xbeae3de2,
0x3eb7,0xbeb7,0x3eb7,0xbeb7,0x3eb78000,0xbeb78000,0x3eb78000,0xbeb78000,0xbeae3de2,0x3e94be57,0xbe573e94,0x3de2beae,0x3de23eae,0xbe57be94,0x3e943e57,0xbeaebde2,
0,0,0,0,0,0,0,0,0,0,0,0,0,0,0,0,
0,0,0,0,0,0,0,0,0,0,0,0,0,0,0,0,
0xbe57be94,0x3eae3de2,0xbeae3de2,0x3e57be94,0xbe943e57,0x3de2beae,0x3de23eae,0xbe94be57,0x3e57be94,0x3de23eae,0xbeaebde2,0x3e94be57,0xbe94be57,0x3eaebde2,0xbde23eae,0xbe57be94,
0x3eae3de2,0xbe573e94,0xbe57be94,0x3eaebde2,0x3de2beae,0x3e943e57,0xbe943e57,0xbde2beae,0x3eb7,0xbeb70000,0xbeb7,0x3eb70000,0x3eb78000,0x3eb7,0xbeb78000,0xbeb7,
0,0,0,0,0,0,0,0,0,0,0,0,0,0,0,0,
0,0,0,0,0,0,0,0,0,0,0,0,0,0,0,0,
0xbeae3de2,0xbe57be94,0x3e57be94,0x3eae3de2,0x3de23eae,0xbe943e57,0xbe94be57,0x3de2beae,0xbe57be94,0x3de2beae,0x3eaebde2,0x3e943e57,0xbe943e57,0xbeaebde2,0xbde2beae,0x3e57be94,
0x3e57be94,0x3eaebde2,0x3eae3de2,0x3e573e94,0xbe94be57,0xbde2beae,0x3de2beae,0x3e94be57,0x3eae3de2,0x3e943e57,0x3e573e94,0x3de23eae,0x3de2beae,0x3e57be94,0x3e94be57,0x3eaebde2,
};
__device__ __align__(128) const uint32_t TAB_P3[4288] = {
0,0,0,0,0,0,0,0,0,0,0,0,0,0,0,0,
0x80003e83,0xbe79bda2,0x3e1abe54,0x3e1a3e54,0x3e830000,0xbda23e79,0xbe54be1a,0x3e54be1a,0x80003e83,0xbe54be1a,0x3e79bda2,0xbda23e79,0x3e830000,0xbe1a3e54,0xbda2be79,0x3e793da2,
0,0,0,0,0,0,0,0,0,0,0,0,0,0,0,0,
0xbe793da2,0x8000be83,0x3e793da2,0xbe1a3e54,0x3da23e79,0xbe830000,0x3da2be79,0x3e543e1a,0xbe1abe54,0x3e830000,0xbe1a3e54,0xbda2be79,0xbe543e1a,0xbe83,0x3e543e1a,0xbe793da2,
0x80003e83,0xbe1abe54,0x3e793da2,0xbe793da2,0x3e830000,0xbe543e1a,0x3da2be79,0x3da23e79,0x80003e83,0xbda2be79,0x3e1a3e54,0xbe54be1a,0x3e830000,0xbe793da2,0x3e54be1a,0xbe1a3e54,
0x80003e83,0x8000be83,0x80003e83,0x8000be83,0x3e830000,0xbe830000,0x3e830000,0xbe830000,0x80003e83,0x3da2be79,0xbe1a3e54,0x3e54be1a,0x3e830000,0xbe79bda2,0x3e543e1a,0xbe1abe54,
0x3e1abe54,0x80003e83,0xbe1abe54,0x3e793da2,0xbe54be1a,0x3e830000,0xbe543e1a,0x3da2be79,0x3e793da2,0xbe830000,0x3e79bda2,0xbe543e1a,0x3da2be79,0x3e83,0xbda2be79,0x3e1a3e54,
0x80003e83,0x8000be83,0x80003e83,0x8000be83,0x3e830000,0xbe830000,0x3e830000,0xbe830000,0xbe793da2,0x3e830000,0xbe79bda2,0x3e543e1a,0x3da23e79,0xbe83,0xbda23e79,0x3e1abe54,
0x80003e83,0x3e1abe54,0xbe793da2,0x3e793da2,0x3e830000,0xbe54be1a,0x3da23e79,0x3da2be79,0x80003e83,0x3e54be1a,0xbe79bda2,0x3da23e79,0x3e830000,0xbe1abe54,0xbda23e79,0x3e79bda2,
0x80003e83,0x3e79bda2,0xbe1abe54,0xbe1a3e54,0x3e830000,0xbda2be79,0xbe543e1a,0x3e543e1a,0x80003e83,0x3e830000,0x8000be83,0xbe830000,0x3e830000,0xbe83,0xbe830000,0x3e83,
0xbe1abe54,0x80003e83,0x3e1abe54,0xbe793da2,0xbe543e1a,0x3e830000,0xbe54be1a,0x3da23e79,0x3e1abe54,0xbe830000,0x3e1a3e54,0x3da2be79,0xbe54be1a,0x3e83,0x3e54be1a,0xbe79bda2,
0x3e793da2,0x8000be83,0xbe793da2,0x3e1a3e54,0x3da2be79,0xbe830000,0x3da23e79,0x3e54be1a,0x80003e83,0x3e830000,0x8000be83,0xbe830000,0x3e830000,0xbe83,0xbe830000,0x3e83,
0x80003e83,0x3e793da2,0x3e1abe54,0xbe1abe54,0x3e830000,0x3da2be79,0xbe54be1a,0xbe543e1a,0x80003e83,0x3e543e1a,0x3e79bda2,0x3da2be79,0x3e830000,0x3e1abe54,0xbda2be79,0xbe79bda2,
0x80003e83,0x3e1a3e54,0x3e793da2,0x3e79bda2,0x3e830000,0x3e54be1a,0x3da2be79,0xbda2be79,0x80003e83,0x3da23e79,0x3e1a3e54,0x3e543e1a,0x3e830000,0x3e79bda2,0x3e54be1a,0x3e1abe54,
0xbe793da2,0x80003e83,0x3e793da2,0x3e1abe54,0x3da23e79,0x3e830000,0x3da2be79,0xbe54be1a,0xbe1abe54,0xbe830000,0xbe1a3e54,0x3da23e79,0xbe543e1a,0x3e83,0x3e543e1a,0x3e79bda2,
0x3e1abe54,0x8000be83,0xbe1abe54,0xbe79bda2,0xbe54be1a,0xbe830000,0xbe543e1a,0xbda23e79,0x3e793da2,0x3e830000,0x3e79bda2,0x3e54be1a,0x3da2be79,0xbe83,0xbda2be79,0xbe1abe54,
0,0,0,0,0,0,0,0,0,0,0,0,0,0,0,0,
0,0,0,0,0,0,0,0,0,0,0,0,0,0,0,0,
0,0,0,0,0,0,0,0,0,0,0,0,0,0,0,0,
0xbe1abe54,0x3e79bda2,0x80003e83,0xbe79bda2,0xbe543e1a,0xbda2be79,0x3e830000,0xbda23e79,0x3e793da2,0xbe543e1a,0x8000be83,0x3e543e1a,0x3da2be79,0x3e1a3e54,0xbe830000,0x3e1abe54,
0,0,0,0,0,0,0,0,0,0,0,0,0,0,0,0,
0,0,0,0,0,0,0,0,0,0,0,0,0,0,0,0,
0xbe793da2,0x3e1abe54,0x80003e83,0xbe1abe54,0x3da23e79,0xbe54be1a,0x3e830000,0xbe543e1a,0x3e1abe54,0xbda23e79,0x8000be83,0x3da23e79,0xbe54be1a,0x3e793da2,0xbe830000,0x3e79bda2,
0x80003e83,0x8000be83,0x80003e83,0x8000be83,0x3e830000,0xbe830000,0x3e830000,0xbe830000,0xbe1abe54,0x3da23e79,0x8000be83,0xbda23e79,0xbe543e1a,0x3e79bda2,0xbe830000,0x3e793da2,
0,0,0,0,0,0,0,0,0,0,0,0,0,0,0,0,
0,0,0,0,0,0,0,0,0,0,0,0,0,0,0,0,
0x3e793da2,0xbe1abe54,0x80003e83,0x3e1abe54,0x3da2be79,0xbe543e1a,0x3e830000,0xbe54be1a,0xbe793da2,0x3e543e1a,0x8000be83,0xbe543e1a,0x3da23e79,0x3e1abe54,0xbe830000,0x3e1a3e54,
0x3e1abe54,0xbe79bda2,0x80003e83,0x3e79bda2,0xbe54be1a,0xbda23e79,0x3e830000,0xbda2be79,0x80003e83,0x3e830000,0x8000be83,0xbe830000,0x3e830000,0xbe83,0xbe830000,0x3e83,
0,0,0,0,0,0,0,0,0,0,0,0,0,0,0,0,
0,0,0,0,0,0,0,0,0,0,0,0,0,0,0,0,
0xbe1abe54,0xbe793da2,0x80003e83,0x3e793da2,0xbe543e1a,0x3da23e79,0x3e830000,0x3da2be79,0x3e793da2,0x3e54be1a,0x8000be83,0xbe54be1a,0x3da2be79,0xbe1abe54,0xbe830000,0xbe1a3e54,
0xbe793da2,0xbe1a3e54,0x80003e83,0x3e1a3e54,0x3da23e79,0x3e543e1a,0x3e830000,0x3e54be1a,0x3e1abe54,0x3da2be79,0x8000be83,0xbda2be79,0xbe54be1a,0xbe79bda2,0xbe830000,0xbe793da2,
0,0,0,0,0,0,0,0,0,0,0,0,0,0,0,0,
0x3e1abe54,0x3e1a3e54,0xbe793da2,0x8000be83,0xbe54be1a,0x3e54be1a,0x3da23e79,0xbe830000,0xbe793da2,0x3da2be79,0x3e1a3e54,0xbe830000,0x3da23e79,0xbe79bda2,0x3e54be1a,0x3e83,
0,0,0,0,0,0,0,0,0,0,0,0,0,0,0,0,
0x3e793da2,0xbe1a3e54,0xbe1abe54,0x3e79bda2,0x3da2be79,0x3e543e1a,0xbe543e1a,0xbda2be79,0x3e1abe54,0x3da23e79,0xbe79bda2,0x3e54be1a,0xbe54be1a,0x3e79bda2,0xbda23e79,0xbe1abe54,
0x3e793da2,0xbe793da2,0x3e1abe54,0x80003e83,0x3da2be79,0x3da23e79,0xbe54be1a,0x3e830000,0xbe1abe54,0x3e543e1a,0xbe79bda2,0x3e830000,0xbe543e1a,0x3e1abe54,0xbda23e79,0xbe83,
0x80003e83,0x8000be83,0x80003e83,0x8000be83,0x3e830000,0xbe830000,0x3e830000,0xbe830000,0x3e1abe54,0xbe543e1a,0x3e79bda2,0xbe830000,0xbe54be1a,0x3e1a3e54,0xbda2be79,0x3e83,
0xbe1abe54,0x3e793da2,0xbe793da2,0x3e1abe54,0xbe543e1a,0x3da2be79,0x3da23e79,0xbe54be1a,0xbe793da2,0x3e54be1a,0xbe1a3e54,0x3da2be79,0x3da23e79,0xbe1abe54,0x3e543e1a,0xbe79bda2,
0x80003e83,0x8000be83,0x80003e83,0x8000be83,0x3e830000,0xbe830000,0x3e830000,0xbe830000,0x3e793da2,0xbe54be1a,0x3e1a3e54,0xbda2be79,0x3da2be79,0xbe1a3e54,0x3e54be1a,0xbe793da2,
0xbe793da2,0x3e793da2,0xbe1abe54,0x80003e83,0x3da23e79,0x3da2be79,0xbe543e1a,0x3e830000,0x3e793da2,0xbda2be79,0xbe1a3e54,0x3e830000,0x3da2be79,0xbe793da2,0x3e543e1a,0xbe83,
0xbe1abe54,0xbe1a3e54,0x3e793da2,0x8000be83,0xbe543e1a,0x3e543e1a,0x3da2be79,0xbe830000,0x80003e83,0x3e830000,0x8000be83,0xbe830000,0x3e830000,0xbe83,0xbe830000,0x3e83,
0x3e1abe54,0xbe793da2,0x3e793da2,0xbe1abe54,0xbe54be1a,0x3da23e79,0x3da2be79,0xbe543e1a,0xbe1abe54,0xbda23e79,0x3e79bda2,0xbe54be1a,0xbe543e1a,0x3e793da2,0xbda2be79,0xbe1a3e54,
0xbe793da2,0x3e1a3e54,0x3e1abe54,0xbe79bda2,0x3da23e79,0x3e54be1a,0xbe54be1a,0xbda23e79,0x80003e83,0x3e830000,0x8000be83,0xbe830000,0x3e830000,0xbe83,0xbe830000,0x3e83,
0x3e1abe54,0xbe1abe54,0xbe793da2,0x80003e83,0xbe54be1a,0xbe543e1a,0x3da23e79,0x3e830000,0xbe793da2,0xbda23e79,0x3e1a3e54,0x3e830000,0x3da23e79,0x3e793da2,0x3e54be1a,0xbe83,
0x3e793da2,0x3e79bda2,0x3e1abe54,0x8000be83,0x3da2be79,0xbda2be79,0xbe54be1a,0xbe830000,0xbe1abe54,0xbe54be1a,0xbe79bda2,0xbe830000,0xbe543e1a,0xbe1a3e54,0xbda23e79,0x3e83,
0x3e793da2,0x3e1abe54,0xbe1abe54,0xbe793da2,0x3da2be79,0xbe54be1a,0xbe543e1a,0x3da23e79,0x3e1abe54,0xbda2be79,0xbe79bda2,0xbe543e1a,0xbe54be1a,0xbe793da2,0xbda23e79,0x3e1a3e54,
0xbe1abe54,0xbe79bda2,0xbe793da2,0xbe1a3e54,0xbe543e1a,0xbda23e79,0x3da23e79,0x3e543e1a,0xbe793da2,0xbe543e1a,0xbe1a3e54,0xbda23e79,0x3da23e79,0x3e1a3e54,0x3e543e1a,0x3e793da2,
0xbe163dda,0,0,0,0,0xbe163dda,0,0,0,0,0xbe163dda,0,0,0,0,0xbe163dda,
0xbe253da8,0,0,0,0,0xbe253da8,0,0,0,0,0xbe253da8,0,0,0,0,0xbe253da8,
0xbd65be30,0,0,0,0,0xbd65be30,0,0,0,0,0xbd65be30,0,0,0,0,0xbd65be30,
0x3ce8be37,0,0,0,0,0x3ce8be37,0,0,0,0,0x3ce8be37,0,0,0,0,0x3ce8be37,
0xbe303d65,0,0,0,0,0xbe303d65,0,0,0,0,0xbe303d65,0,0,0,0,0xbe303d65,
0xbe373ce8,0,0,0,0,0xbe373ce8,0,0,0,0,0xbe373ce8,0,0,0,0,0xbe373ce8,
0x3ddabe16,0,0,0,0,0x3ddabe16,0,0,0,0,0x3ddabe16,0,0,0,0,0x3ddabe16,
0x3e25bda8,0,0,0,0,0x3e25bda8,0,0,0,0,0x3e25bda8,0,0,0,0,0x3e25bda8,
0xbe390000,0,0,0,0,0xbe390000,0,0,0,0,0xbe390000,0,0,0,0,0xbe390000,
0xbe37bce8,0,0,0,0,0xbe37bce8,0,0,0,0,0xbe37bce8,0,0,0,0,0xbe37bce8,
0x3e390000,0,0,0,0,0x3e390000,0,0,0,0,0x3e390000,0,0,0,0,0x3e390000,
0x3e253da8,0,0,0,0,0x3e253da8,0,0,0,0,0x3e253da8,0,0,0,0,0x3e253da8,
0xbe30bd65,0,0,0,0,0xbe30bd65,0,0,0,0,0xbe30bd65,0,0,0,0,0xbe30bd65,
0xbe25bda8,0,0,0,0,0xbe25bda8,0,0,0,0,0xbe25bda8,0,0,0,0,0xbe25bda8,
0x3dda3e16,0,0,0,0,0x3dda3e16,0,0,0,0,0x3dda3e16,0,0,0,0,0x3dda3e16,
0x3ce83e37,0,0,0,0,0x3ce83e37,0,0,0,0,0x3ce83e37,0,0,0,0,0x3ce83e37,
0xbe16bdda,0,0,0,0,0xbe16bdda,0,0,0,0,0xbe16bdda,0,0,0,0,0xbe16bdda,
0xbe03be03,0,0,0,0,0xbe03be03,0,0,0,0,0xbe03be03,0,0,0,0,0xbe03be03,
0xbd653e30,0,0,0,0,0xbd653e30,0,0,0,0,0xbd653e30,0,0,0,0,0xbd653e30,
0xbe033e03,0,0,0,0,0xbe033e03,0,0,0,0,0xbe033e03,0,0,0,0,0xbe033e03,
0xbddabe16,0,0,0,0,0xbddabe16,0,0,0,0,0xbddabe16,0,0,0,0,0xbddabe16,
0xbda8be25,0,0,0,0,0xbda8be25,0,0,0,0,0xbda8be25,0,0,0,0,0xbda8be25,
0xbe303d65,0,0,0,0,0xbe303d65,0,0,0,0,0xbe303d65,0,0,0,0,0xbe303d65,
0xbe37bce8,0,0,0,0,0xbe37bce8,0,0,0,0,0xbe37bce8,0,0,0,0,0xbe37bce8,
0xbd65be30,0,0,0,0,0xbd65be30,0,0,0,0,0xbd65be30,0,0,0,0,0xbd65be30,
0xbce8be37,0,0,0,0,0xbce8be37,0,0,0,0,0xbce8be37,0,0,0,0,0xbce8be37,
0xbe16bdda,0,0,0,0,0xbe16bdda,0,0,0,0,0xbe16bdda,0,0,0,0,0xbe16bdda,
0xbda8be25,0,0,0,0,0xbda8be25,0,0,0,0,0xbda8be25,0,0,0,0,0xbda8be25,
0x3e390000,0,0,0,0,0x3e390000,0,0,0,0,0x3e390000,0,0,0,0,0x3e390000,
0x3e033e03,0,0,0,0,0x3e033e03,0,0,0,0,0x3e033e03,0,0,0,0,0x3e033e03,
0xbd653e30,0,0,0,0,0xbd653e30,0,0,0,0,0xbd653e30,0,0,0,0,0xbd653e30,
0xbe373ce8,0,0,0,0,0xbe373ce8,0,0,0,0,0xbe373ce8,0,0,0,0,0xbe373ce8,
0x80003e39,0,0,0,0,0x80003e39,0,0,0,0,0x80003e39,0,0,0,0,0x80003e39,
0xbe033e03,0,0,0,0,0xbe033e03,0,0,0,0,0xbe033e03,0,0,0,0,0xbe033e03,
0xbddabe16,0,0,0,0,0xbddabe16,0,0,0,0,0xbddabe16,0,0,0,0,0xbddabe16,
0x3da8be25,0,0,0,0,0x3da8be25,0,0,0,0,0x3da8be25,0,0,0,0,0x3da8be25,
0xbe390000,0,0,0,0,0xbe390000,0,0,0,0,0xbe390000,0,0,0,0,0xbe390000,
0xbe03be03,0,0,0,0,0xbe03be03,0,0,0,0,0xbe03be03,0,0,0,0,0xbe03be03,
0x3e390000,0,0,0,0,0x3e390000,0,0,0,0,0x3e390000,0,0,0,0,0x3e390000,
0x3da83e25,0,0,0,0,0x3da83e25,0,0,0,0,0x3da83e25,0,0,0,0,0x3da83e25,
0x8000be39,0,0,0,0,0x8000be39,0,0,0,0,0x8000be39,0,0,0,0,0x8000be39,
0x3e03be03,0,0,0,0,0x3e03be03,0,0,0,0,0x3e03be03,0,0,0,0,0x3e03be03,
0xbdda3e16,0,0,0,0,0xbdda3e16,0,0,0,0,0xbdda3e16,0,0,0,0,0xbdda3e16,
0xbe37bce8,0,0,0,0,0xbe37bce8,0,0,0,0,0xbe37bce8,0,0,0,0,0xbe37bce8,
0x3e390000,0,0,0,0,0x3e390000,0,0,0,0,0x3e390000,0,0,0,0,0x3e390000,
0x3e033e03,0,0,0,0,0x3e033e03,0,0,0,0,0x3e033e03,0,0,0,0,0x3e033e03,
0xbd65be30,0,0,0,0,0xbd65be30,0,0,0,0,0xbd65be30,0,0,0,0,0xbd65be30,
0x3e03be03,0,0,0,0,0x3e03be03,0,0,0,0,0x3e03be03,0,0,0,0,0x3e03be03,
0x80003e39,0,0,0,0,0x80003e39,0,0,0,0,0x80003e39,0,0,0,0,0x80003e39,
0xbe033e03,0,0,0,0,0xbe033e03,0,0,0,0,0xbe033e03,0,0,0,0,0xbe033e03,
0x3e303d65,0,0,0,0,0x3e303d65,0,0,0,0,0x3e303d65,0,0,0,0,0x3e303d65,
0x3ce83e37,0,0,0,0,0x3ce83e37,0,0,0,0,0x3ce83e37,0,0,0,0,0x3ce83e37,
0xbe390000,0,0,0,0,0xbe390000,0,0,0,0,0xbe390000,0,0,0,0,0xbe390000,
0xbe03be03,0,0,0,0,0xbe03be03,0,0,0,0,0xbe03be03,0,0,0,0,0xbe03be03,
0xbe163dda,0,0,0,0,0xbe163dda,0,0,0,0,0xbe163dda,0,0,0,0,0xbe163dda,
0xbe25bda8,0,0,0,0,0xbe25bda8,0,0,0,0,0xbe25bda8,0,0,0,0,0xbe25bda8,
0xbe16bdda,0,0,0,0,0xbe16bdda,0,0,0,0,0xbe16bdda,0,0,0,0,0xbe16bdda,
0x3da8be25,0,0,0,0,0x3da8be25,0,0,0,0,0x3da8be25,0,0,0,0,0x3da8be25,
0x3e16bdda,0,0,0,0,0x3e16bdda,0,0,0,0,0x3e16bdda,0,0,0,0,0x3e16bdda,
0x3da83e25,0,0,0,0,0x3da83e25,0,0,0,0,0x3da83e25,0,0,0,0,0x3da83e25,
0x3e303d65,0,0,0,0,0x3e303d65,0,0,0,0,0x3e303d65,0,0,0,0,0x3e303d65,
0xbce83e37,0,0,0,0,0xbce83e37,0,0,0,0,0xbce83e37,0,0,0,0,0xbce83e37,
0xbe303d65,0,0,0,0,0xbe303d65,0,0,0,0,0xbe303d65,0,0,0,0,0xbe303d65,
0xbce8be37,0,0,0,0,0xbce8be37,0,0,0,0,0xbce8be37,0,0,0,0,0xbce8be37,
0xbe390000,0,0,0,0,0xbe390000,0,0,0,0,0xbe390000,0,0,0,0,0xbe390000,
0xbce8be37,0,0,0,0,0xbce8be37,0,0,0,0,0xbce8be37,0,0,0,0,0xbce8be37,
0x3e390000,0,0,0,0,0x3e390000,0,0,0,0,0x3e390000,0,0,0,0,0x3e390000,
0xbce83e37,0,0,0,0,0xbce83e37,0,0,0,0,0xbce83e37,0,0,0,0,0xbce83e37,
0x3e30bd65,0,0,0,0,0x3e30bd65,0,0,0,0,0x3e30bd65,0,0,0,0,0x3e30bd65,
0x3da83e25,0,0,0,0,0x3da83e25,0,0,0,0,0x3da83e25,0,0,0,0,0x3da83e25,
0xbe30bd65,0,0,0,0,0xbe30bd65,0,0,0,0,0xbe30bd65,0,0,0,0,0xbe30bd65,
0x3da8be25,0,0,0,0,0x3da8be25,0,0,0,0,0x3da8be25,0,0,0,0,0x3da8be25,
0xbe163dda,0,0,0,0,0xbe163dda,0,0,0,0,0xbe163dda,0,0,0,0,0xbe163dda,
0xbe03be03,0,0,0,0,0xbe03be03,0,0,0,0,0xbe03be03,0,0,0,0,0xbe03be03,
0x3e163dda,0,0,0,0,0x3e163dda,0,0,0,0,0x3e163dda,0,0,0,0,0x3e163dda,
0xbe033e03,0,0,0,0,0xbe033e03,0,0,0,0,0xbe033e03,0,0,0,0,0xbe033e03,
0x3ddabe16,0,0,0,0,0x3ddabe16,0,0,0,0,0x3ddabe16,0,0,0,0,0x3ddabe16,
0x3e253da8,0,0,0,0,0x3e253da8,0,0,0,0,0x3e253da8,0,0,0,0,0x3e253da8,
0xbddabe16,0,0,0,0,0xbddabe16,0,0,0,0,0xbddabe16,0,0,0,0,0xbddabe16,
0x3e25bda8,0,0,0,0,0x3e25bda8,0,0,0,0,0x3e25bda8,0,0,0,0,0x3e25bda8,
0xbd653e30,0,0,0,0,0xbd653e30,0,0,0,0,0xbd653e30,0,0,0,0,0xbd653e30,
0xbe37bce8,0,0,0,0,0xbe37bce8,0,0,0,0,0xbe37bce8,0,0,0,0,0xbe37bce8,
0x3d653e30,0,0,0,0,0x3d653e30,0,0,0,0,0x3d653e30,0,0,0,0,0x3d653e30,
0xbe373ce8,0,0,0,0,0xbe373ce8,0,0,0,0,0xbe373ce8,0,0,0,0,0xbe373ce8,
0x3d653e30,0,0,0,0,0x3d653e30,0,0,0,0,0x3d653e30,0,0,0,0,0x3d653e30,
0xbe37bce8,0,0,0,0,0xbe37bce8,0,0,0,0,0xbe37bce8,0,0,0,0,0xbe37bce8,
0xbe390000,0,0,0,0,0xbe390000,0,0,0,0,0xbe390000,0,0,0,0,0xbe390000,
0x3e03be03,0,0,0,0,0x3e03be03,0,0,0,0,0x3e03be03,0,0,0,0,0x3e03be03,
0x3ddabe16,0,0,0,0,0x3ddabe16,0,0,0,0,0x3ddabe16,0,0,0,0,0x3ddabe16,
0x3da83e25,0,0,0,0,0x3da83e25,0,0,0,0,0x3da83e25,0,0,0,0,0x3da83e25,
0x80003e39,0,0,0,0,0x80003e39,0,0,0,0,0x80003e39,0,0,0,0,0x80003e39,
0xbe03be03,0,0,0,0,0xbe03be03,0,0,0,0,0xbe03be03,0,0,0,0,0xbe03be03,
0xbe390000,0,0,0,0,0xbe390000,0,0,0,0,0xbe390000,0,0,0,0,0xbe390000,
0x3da8be25,0,0,0,0,0x3da8be25,0,0,0,0,0x3da8be25,0,0,0,0,0x3da8be25,
0x3e390000,0,0,0,0,0x3e390000,0,0,0,0,0x3e390000,0,0,0,0,0x3e390000,
0xbe033e03,0,0,0,0,0xbe033e03,0,0,0,0,0xbe033e03,0,0,0,0,0xbe033e03,
0x3dda3e16,0,0,0,0,0x3dda3e16,0,0,0,0,0x3dda3e16,0,0,0,0,0x3dda3e16,
0xbe373ce8,0,0,0,0,0xbe373ce8,0,0,0,0,0xbe373ce8,0,0,0,0,0xbe373ce8,
0x8000be39,0,0,0,0,0x8000be39,0,0,0,0,0x8000be39,0,0,0,0,0x8000be39,
0x3e033e03,0,0,0,0,0x3e033e03,0,0,0,0,0x3e033e03,0,0,0,0,0x3e033e03,
0x3d65be30,0,0,0,0,0x3d65be30,0,0,0,0,0x3d65be30,0,0,0,0,0x3d65be30,
0x3e033e03,0,0,0,0,0x3e033e03,0,0,0,0,0x3e033e03,0,0,0,0,0x3e033e03,
0xbe390000,0,0,0,0,0xbe390000,0,0,0,0,0xbe390000,0,0,0,0,0xbe390000,
0x3e03be03,0,0,0,0,0x3e03be03,0,0,0,0,0x3e03be03,0,0,0,0,0x3e03be03,
0xbe303d65,0,0,0,0,0xbe303d65,0,0,0,0,0xbe303d65,0,0,0,0,0xbe303d65,
0x3ce8be37,0,0,0,0,0x3ce8be37,0,0,0,0,0x3ce8be37,0,0,0,0,0x3ce8be37,
0x80003e39,0,0,0,0,0x80003e39,0,0,0,0,0x80003e39,0,0,0,0,0x80003e39,
0xbe03be03,0,0,0,0,0xbe03be03,0,0,0,0,0xbe03be03,0,0,0,0,0xbe03be03,
0x3e163dda,0,0,0,0,0x3e163dda,0,0,0,0,0x3e163dda,0,0,0,0,0x3e163dda,
0xbe253da8,0,0,0,0,0xbe253da8,0,0,0,0,0xbe253da8,0,0,0,0,0xbe253da8,
0x3e390000,0,0,0,0,0x3e390000,0,0,0,0,0x3e390000,0,0,0,0,0x3e390000,
0xbe033e03,0,0,0,0,0xbe033e03,0,0,0,0,0xbe033e03,0,0,0,0,0xbe033e03,
0x3d65be30,0,0,0,0,0x3d65be30,0,0,0,0,0x3d65be30,0,0,0,0,0x3d65be30,
0x3ce83e37,0,0,0,0,0x3ce83e37,0,0,0,0,0x3ce83e37,0,0,0,0,0x3ce83e37,
0x3e163dda,0,0,0,0,0x3e163dda,0,0,0,0,0x3e163dda,0,0,0,0,0x3e163dda,
0xbe25bda8,0,0,0,0,0xbe25bda8,0,0,0,0,0xbe25bda8,0,0,0,0,0xbe25bda8,
0xbddabe16,0,0,0,0,0xbddabe16,0,0,0,0,0xbddabe16,0,0,0,0,0xbddabe16,
0x3e253da8,0,0,0,0,0x3e253da8,0,0,0,0,0x3e253da8,0,0,0,0,0x3e253da8,
0x3e303d65,0,0,0,0,0x3e303d65,0,0,0,0,0x3e303d65,0,0,0,0,0x3e303d65,
0xbe37bce8,0,0,0,0,0xbe37bce8,0,0,0,0,0xbe37bce8,0,0,0,0,0xbe37bce8,
0xbe390000,0,0,0,0,0xbe390000,0,0,0,0,0xbe390000,0,0,0,0,0xbe390000,
0x3e25bda8,0,0,0,0,0x3e25bda8,0,0,0,0,0x3e25bda8,0,0,0,0,0x3e25bda8,
0x3e390000,0,0,0,0,0x3e390000,0,0,0,0,0x3e390000,0,0,0,0,0x3e390000,
0xbe373ce8,0,0,0,0,0xbe373ce8,0,0,0,0,0xbe373ce8,0,0,0,0,0xbe373ce8,
0xbdda3e16,0,0,0,0,0xbdda3e16,0,0,0,0,0xbdda3e16,0,0,0,0,0xbdda3e16,
0x3ce8be37,0,0,0,0,0x3ce8be37,0,0,0,0,0x3ce8be37,0,0,0,0,0x3ce8be37,
0x3e30bd65,0,0,0,0,0x3e30bd65,0,0,0,0,0x3e30bd65,0,0,0,0,0x3e30bd65,
0xbe253da8,0,0,0,0,0xbe253da8,0,0,0,0,0xbe253da8,0,0,0,0,0xbe253da8,
0x3d653e30,0,0,0,0,0x3d653e30,0,0,0,0,0x3d653e30,0,0,0,0,0x3d653e30,
0xbe03be03,0,0,0,0,0xbe03be03,0,0,0,0,0xbe03be03,0,0,0,0,0xbe03be03,
0x3e16bdda,0,0,0,0,0x3e16bdda,0,0,0,0,0x3e16bdda,0,0,0,0,0x3e16bdda,
0xbe033e03,0,0,0,0,0xbe033e03,0,0,0,0,0xbe033e03,0,0,0,0,0xbe033e03,
0x3e303d65,0,0,0,0,0x3e303d65,0,0,0,0,0x3e303d65,0,0,0,0,0x3e303d65,
0xbe373ce8,0,0,0,0,0xbe373ce8,0,0,0,0,0xbe373ce8,0,0,0,0,0xbe373ce8,
0x3ddabe16,0,0,0,0,0x3ddabe16,0,0,0,0,0x3ddabe16,0,0,0,0,0x3ddabe16,
0xbda83e25,0,0,0,0,0xbda83e25,0,0,0,0,0xbda83e25,0,0,0,0,0xbda83e25,
0x3e16bdda,0,0,0,0,0x3e16bdda,0,0,0,0,0x3e16bdda,0,0,0,0,0x3e16bdda,
0xbda83e25,0,0,0,0,0xbda83e25,0,0,0,0,0xbda83e25,0,0,0,0,0xbda83e25,
0x3d65be30,0,0,0,0,0x3d65be30,0,0,0,0,0x3d65be30,0,0,0,0,0x3d65be30,
0xbce83e37,0,0,0,0,0xbce83e37,0,0,0,0,0xbce83e37,0,0,0,0,0xbce83e37,
0,0,0xbe163dda,0,0,0,0,0xbe163dda,0,0,0xbe253da8,0,0,0,0,0xbe253da8,
0,0,0xbe303d65,0,0,0,0,0xbe303d65,0,0,0xbe373ce8,0,0,0,0,0xbe373ce8,
0,0,0xbd65be30,0,0,0,0,0xbd65be30,0,0,0x3ce8be37,0,0,0,0,0x3ce8be37,
0,0,0x3ddabe16,0,0,0,0,0x3ddabe16,0,0,0x3e25bda8,0,0,0,0,0x3e25bda8,
0,0,0xbe390000,0,0,0,0,0xbe390000,0,0,0xbe37bce8,0,0,0,0,0xbe37bce8,
0,0,0xbe30bd65,0,0,0,0,0xbe30bd65,0,0,0xbe25bda8,0,0,0,0,0xbe25bda8,
0,0,0x3e390000,0,0,0,0,0x3e390000,0,0,0x3e253da8,0,0,0,0,0x3e253da8,
0,0,0x3dda3e16,0,0,0,0,0x3dda3e16,0,0,0x3ce83e37,0,0,0,0,0x3ce83e37,
0,0,0xbe16bdda,0,0,0,0,0xbe16bdda,0,0,0xbe03be03,0,0,0,0,0xbe03be03,
0,0,0xbddabe16,0,0,0,0,0xbddabe16,0,0,0xbda8be25,0,0,0,0,0xbda8be25,
0,0,0xbd653e30,0,0,0,0,0xbd653e30,0,0,0xbe033e03,0,0,0,0,0xbe033e03,
0,0,0xbe303d65,0,0,0,0,0xbe303d65,0,0,0xbe37bce8,0,0,0,0,0xbe37bce8,
0,0,0xbd65be30,0,0,0,0,0xbd65be30,0,0,0xbce8be37,0,0,0,0,0xbce8be37,
0,0,0,0,0,0,0,0,0,0,0,0,0,0,0,0,
0,0,0xbe16bdda,0,0,0,0,0xbe16bdda,0,0,0xbda8be25,0,0,0,0,0xbda8be25,
0,0,0,0,0,0,0,0,0,0,0,0,0,0,0,0,
0,0,0x3e390000,0,0,0,0,0x3e390000,0,0,0x3e033e03,0,0,0,0,0x3e033e03,
0,0,0x80003e39,0,0,0,0,0x80003e39,0,0,0xbe033e03,0,0,0,0,0xbe033e03,
0,0,0xbd653e30,0,0,0,0,0xbd653e30,0,0,0xbe373ce8,0,0,0,0,0xbe373ce8,
0,0,0xbddabe16,0,0,0,0,0xbddabe16,0,0,0x3da8be25,0,0,0,0,0x3da8be25,
0,0,0xbe390000,0,0,0,0,0xbe390000,0,0,0xbe03be03,0,0,0,0,0xbe03be03,
0,0,0x8000be39,0,0,0,0,0x8000be39,0,0,0x3e03be03,0,0,0,0,0x3e03be03,
0,0,0x3e390000,0,0,0,0,0x3e390000,0,0,0x3da83e25,0,0,0,0,0x3da83e25,
0,0,0xbdda3e16,0,0,0,0,0xbdda3e16,0,0,0xbe37bce8,0,0,0,0,0xbe37bce8,
0,0,0x3e390000,0,0,0,0,0x3e390000,0,0,0x3e033e03,0,0,0,0,0x3e033e03,
0,0,0x80003e39,0,0,0,0,0x80003e39,0,0,0xbe033e03,0,0,0,0,0xbe033e03,
0,0,0xbd65be30,0,0,0,0,0xbd65be30,0,0,0x3e03be03,0,0,0,0,0x3e03be03,
0,0,0x3e303d65,0,0,0,0,0x3e303d65,0,0,0x3ce83e37,0,0,0,0,0x3ce83e37,
0,0,0xbe390000,0,0,0,0,0xbe390000,0,0,0xbe03be03,0,0,0,0,0xbe03be03,
0,0,0,0,0,0,0,0,0,0,0,0,0,0,0,0,
0,0,0xbe163dda,0,0,0,0,0xbe163dda,0,0,0xbe25bda8,0,0,0,0,0xbe25bda8,
0,0,0,0,0,0,0,0,0,0,0,0,0,0,0,0,
0,0,0xbe16bdda,0,0,0,0,0xbe16bdda,0,0,0x3da8be25,0,0,0,0,0x3da8be25,
0,0,0x3e303d65,0,0,0,0,0x3e303d65,0,0,0xbce83e37,0,0,0,0,0xbce83e37,
0,0,0x3e16bdda,0,0,0,0,0x3e16bdda,0,0,0x3da83e25,0,0,0,0,0x3da83e25,
0,0,0xbe303d65,0,0,0,0,0xbe303d65,0,0,0xbce8be37,0,0,0,0,0xbce8be37,
0,0,0xbe390000,0,0,0,0,0xbe390000,0,0,0xbce8be37,0,0,0,0,0xbce8be37,
0,0,0x3e30bd65,0,0,0,0,0x3e30bd65,0,0,0x3da83e25,0,0,0,0,0x3da83e25,
0,0,0x3e390000,0,0,0,0,0x3e390000,0,0,0xbce83e37,0,0,0,0,0xbce83e37,
0,0,0xbe30bd65,0,0,0,0,0xbe30bd65,0,0,0x3da8be25,0,0,0,0,0x3da8be25,
0,0,0xbe163dda,0,0,0,0,0xbe163dda,0,0,0xbe03be03,0,0,0,0,0xbe03be03,
0,0,0x3ddabe16,0,0,0,0,0x3ddabe16,0,0,0x3e253da8,0,0,0,0,0x3e253da8,
0,0,0x3e163dda,0,0,0,0,0x3e163dda,0,0,0xbe033e03,0,0,0,0,0xbe033e03,
0,0,0xbddabe16,0,0,0,0,0xbddabe16,0,0,0x3e25bda8,0,0,0,0,0x3e25bda8,
0,0,0xbd653e30,0,0,0,0,0xbd653e30,0,0,0xbe37bce8,0,0,0,0,0xbe37bce8,
0,0,0,0,0,0,0,0,0,0,0,0,0,0,0,0,
0,0,0x3d653e30,0,0,0,0,0x3d653e30,0,0,0xbe373ce8,0,0,0,0,0xbe373ce8,
0,0,0,0,0,0,0,0,0,0,0,0,0,0,0,0,
0,0,0x3d653e30,0,0,0,0,0x3d653e30,0,0,0xbe37bce8,0,0,0,0,0xbe37bce8,
0,0,0x3ddabe16,0,0,0,0,0x3ddabe16,0,0,0x3da83e25,0,0,0,0,0x3da83e25,
0,0,0xbe390000,0,0,0,0,0xbe390000,0,0,0x3e03be03,0,0,0,0,0x3e03be03,
0,0,0x80003e39,0,0,0,0,0x80003e39,0,0,0xbe03be03,0,0,0,0,0xbe03be03,
0,0,0xbe390000,0,0,0,0,0xbe390000,0,0,0x3da8be25,0,0,0,0,0x3da8be25,
0,0,0x3dda3e16,0,0,0,0,0x3dda3e16,0,0,0xbe373ce8,0,0,0,0,0xbe373ce8,
0,0,0x3e390000,0,0,0,0,0x3e390000,0,0,0xbe033e03,0,0,0,0,0xbe033e03,
0,0,0x8000be39,0,0,0,0,0x8000be39,0,0,0x3e033e03,0,0,0,0,0x3e033e03,
0,0,0x3d65be30,0,0,0,0,0x3d65be30,0,0,0x3e033e03,0,0,0,0,0x3e033e03,
0,0,0xbe303d65,0,0,0,0,0xbe303d65,0,0,0x3ce8be37,0,0,0,0,0x3ce8be37,
0,0,0xbe390000,0,0,0,0,0xbe390000,0,0,0x3e03be03,0,0,0,0,0x3e03be03,
0,0,0x80003e39,0,0,0,0,0x80003e39,0,0,0xbe03be03,0,0,0,0,0xbe03be03,
0,0,0x3e163dda,0,0,0,0,0x3e163dda,0,0,0xbe253da8,0,0,0,0,0xbe253da8,
0,0,0,0,0,0,0,0,0,0,0,0,0,0,0,0,
0,0,0x3e390000,0,0,0,0,0x3e390000,0,0,0xbe033e03,0,0,0,0,0xbe033e03,
0,0,0,0,0,0,0,0,0,0,0,0,0,0,0,0,
0,0,0x3d65be30,0,0,0,0,0x3d65be30,0,0,0x3ce83e37,0,0,0,0,0x3ce83e37,
0,0,0xbddabe16,0,0,0,0,0xbddabe16,0,0,0x3e253da8,0,0,0,0,0x3e253da8,
0,0,0x3e163dda,0,0,0,0,0x3e163dda,0,0,0xbe25bda8,0,0,0,0,0xbe25bda8,
0,0,0x3e303d65,0,0,0,0,0x3e303d65,0,0,0xbe37bce8,0,0,0,0,0xbe37bce8,
0,0,0xbe390000,0,0,0,0,0xbe390000,0,0,0x3e25bda8,0,0,0,0,0x3e25bda8,
0,0,0xbdda3e16,0,0,0,0,0xbdda3e16,0,0,0x3ce8be37,0,0,0,0,0x3ce8be37,
0,0,0x3e390000,0,0,0,0,0x3e390000,0,0,0xbe373ce8,0,0,0,0,0xbe373ce8,
0,0,0x3e30bd65,0,0,0,0,0x3e30bd65,0,0,0xbe253da8,0,0,0,0,0xbe253da8,
0,0,0x3d653e30,0,0,0,0,0x3d653e30,0,0,0xbe03be03,0,0,0,0,0xbe03be03,
0,0,0x3e303d65,0,0,0,0,0x3e303d65,0,0,0xbe373ce8,0,0,0,0,0xbe373ce8,
0,0,0x3e16bdda,0,0,0,0,0x3e16bdda,0,0,0xbe033e03,0,0,0,0,0xbe033e03,
0,0,0x3ddabe16,0,0,0,0,0x3ddabe16,0,0,0xbda83e25,0,0,0,0,0xbda83e25,
0,0,0x3e16bdda,0,0,0,0,0x3e16bdda,0,0,0xbda83e25,0,0,0,0,0xbda83e25,
0,0,0,0,0,0,0,0,0,0,0,0,0,0,0,0,
0,0,0x3d65be30,0,0,0,0,0x3d65be30,0,0,0xbce83e37,0,0,0,0,0xbce83e37,
0,0,0,0,0,0,0,0,0,0,0,0,0,0,0,0,
};
constexpr unsigned long long COS_PK0 = 0x3f903f9a3fa03fa2ull;
constexpr unsigned long long COS_PK1 = 0x3f133f3e3f653f83ull;
constexpr unsigned long long COS_PK2 = 0x3e4b3ec8ull;

__device__ __forceinline__ void wgmma_ss_n80_z(float (&d)[40], uint64_t da, uint64_t db) {
  asm volatile("{\n.reg .pred p;\nsetp.ne.b32 p, 0, 0;\nwgmma.mma_async.sync.aligned.m64n80k16.f32.bf16.bf16 {%0,%1,%2,%3,%4,%5,%6,%7,%8,%9,%10,%11,%12,%13,%14,%15,%16,%17,%18,%19,%20,%21,%22,%23,%24,%25,%26,%27,%28,%29,%30,%31,%32,%33,%34,%35,%36,%37,%38,%39}, %40, %41, p, 1, 1, 1, 0;\n}\n"
    : "+f"(d[0]), "+f"(d[1]), "+f"(d[2]), "+f"(d[3]), "+f"(d[4]), "+f"(d[5]), "+f"(d[6]), "+f"(d[7]), "+f"(d[8]), "+f"(d[9]), "+f"(d[10]), "+f"(d[11]), "+f"(d[12]), "+f"(d[13]), "+f"(d[14]), "+f"(d[15]), "+f"(d[16]), "+f"(d[17]), "+f"(d[18]), "+f"(d[19]), "+f"(d[20]), "+f"(d[21]), "+f"(d[22]), "+f"(d[23]), "+f"(d[24]), "+f"(d[25]), "+f"(d[26]), "+f"(d[27]), "+f"(d[28]), "+f"(d[29]), "+f"(d[30]), "+f"(d[31]), "+f"(d[32]), "+f"(d[33]), "+f"(d[34]), "+f"(d[35]), "+f"(d[36]), "+f"(d[37]), "+f"(d[38]), "+f"(d[39])
    : "l"(da), "l"(db));
}
__device__ __forceinline__ void wgmma_ss_n80_a(float (&d)[40], uint64_t da, uint64_t db) {
  asm volatile("{\n.reg .pred p;\nsetp.ne.b32 p, 1, 0;\nwgmma.mma_async.sync.aligned.m64n80k16.f32.bf16.bf16 {%0,%1,%2,%3,%4,%5,%6,%7,%8,%9,%10,%11,%12,%13,%14,%15,%16,%17,%18,%19,%20,%21,%22,%23,%24,%25,%26,%27,%28,%29,%30,%31,%32,%33,%34,%35,%36,%37,%38,%39}, %40, %41, p, 1, 1, 1, 0;\n}\n"
    : "+f"(d[0]), "+f"(d[1]), "+f"(d[2]), "+f"(d[3]), "+f"(d[4]), "+f"(d[5]), "+f"(d[6]), "+f"(d[7]), "+f"(d[8]), "+f"(d[9]), "+f"(d[10]), "+f"(d[11]), "+f"(d[12]), "+f"(d[13]), "+f"(d[14]), "+f"(d[15]), "+f"(d[16]), "+f"(d[17]), "+f"(d[18]), "+f"(d[19]), "+f"(d[20]), "+f"(d[21]), "+f"(d[22]), "+f"(d[23]), "+f"(d[24]), "+f"(d[25]), "+f"(d[26]), "+f"(d[27]), "+f"(d[28]), "+f"(d[29]), "+f"(d[30]), "+f"(d[31]), "+f"(d[32]), "+f"(d[33]), "+f"(d[34]), "+f"(d[35]), "+f"(d[36]), "+f"(d[37]), "+f"(d[38]), "+f"(d[39])
    : "l"(da), "l"(db));
}

__device__ __forceinline__ void wgmma_rs_n40_z(float (&d)[20], uint32_t a0, uint32_t a1, uint32_t a2, uint32_t a3, uint64_t db) {
  asm volatile("{\n.reg .pred p;\nsetp.ne.b32 p, 0, 0;\nwgmma.mma_async.sync.aligned.m64n40k16.f32.bf16.bf16 {%0,%1,%2,%3,%4,%5,%6,%7,%8,%9,%10,%11,%12,%13,%14,%15,%16,%17,%18,%19}, {%20,%21,%22,%23}, %24, p, 1, 1, 0;\n}\n"
    : "+f"(d[0]), "+f"(d[1]), "+f"(d[2]), "+f"(d[3]), "+f"(d[4]), "+f"(d[5]), "+f"(d[6]), "+f"(d[7]), "+f"(d[8]), "+f"(d[9]), "+f"(d[10]), "+f"(d[11]), "+f"(d[12]), "+f"(d[13]), "+f"(d[14]), "+f"(d[15]), "+f"(d[16]), "+f"(d[17]), "+f"(d[18]), "+f"(d[19])
    : "r"(a0), "r"(a1), "r"(a2), "r"(a3), "l"(db));
}
__device__ __forceinline__ void wgmma_rs_n40_a(float (&d)[20], uint32_t a0, uint32_t a1, uint32_t a2, uint32_t a3, uint64_t db) {
  asm volatile("{\n.reg .pred p;\nsetp.ne.b32 p, 1, 0;\nwgmma.mma_async.sync.aligned.m64n40k16.f32.bf16.bf16 {%0,%1,%2,%3,%4,%5,%6,%7,%8,%9,%10,%11,%12,%13,%14,%15,%16,%17,%18,%19}, {%20,%21,%22,%23}, %24, p, 1, 1, 0;\n}\n"
    : "+f"(d[0]), "+f"(d[1]), "+f"(d[2]), "+f"(d[3]), "+f"(d[4]), "+f"(d[5]), "+f"(d[6]), "+f"(d[7]), "+f"(d[8]), "+f"(d[9]), "+f"(d[10]), "+f"(d[11]), "+f"(d[12]), "+f"(d[13]), "+f"(d[14]), "+f"(d[15]), "+f"(d[16]), "+f"(d[17]), "+f"(d[18]), "+f"(d[19])
    : "r"(a0), "r"(a1), "r"(a2), "r"(a3), "l"(db));
}

__device__ __forceinline__ void wgmma_rs_n128_z(float (&d)[64], uint32_t a0, uint32_t a1, uint32_t a2, uint32_t a3, uint64_t db) {
  asm volatile("{\n.reg .pred p;\nsetp.ne.b32 p, 0, 0;\nwgmma.mma_async.sync.aligned.m64n128k16.f32.bf16.bf16 {%0,%1,%2,%3,%4,%5,%6,%7,%8,%9,%10,%11,%12,%13,%14,%15,%16,%17,%18,%19,%20,%21,%22,%23,%24,%25,%26,%27,%28,%29,%30,%31,%32,%33,%34,%35,%36,%37,%38,%39,%40,%41,%42,%43,%44,%45,%46,%47,%48,%49,%50,%51,%52,%53,%54,%55,%56,%57,%58,%59,%60,%61,%62,%63}, {%64,%65,%66,%67}, %68, p, 1, 1, 1;\n}\n"
    : "+f"(d[0]), "+f"(d[1]), "+f"(d[2]), "+f"(d[3]), "+f"(d[4]), "+f"(d[5]), "+f"(d[6]), "+f"(d[7]), "+f"(d[8]), "+f"(d[9]), "+f"(d[10]), "+f"(d[11]), "+f"(d[12]), "+f"(d[13]), "+f"(d[14]), "+f"(d[15]), "+f"(d[16]), "+f"(d[17]), "+f"(d[18]), "+f"(d[19]), "+f"(d[20]), "+f"(d[21]), "+f"(d[22]), "+f"(d[23]), "+f"(d[24]), "+f"(d[25]), "+f"(d[26]), "+f"(d[27]), "+f"(d[28]), "+f"(d[29]), "+f"(d[30]), "+f"(d[31]), "+f"(d[32]), "+f"(d[33]), "+f"(d[34]), "+f"(d[35]), "+f"(d[36]), "+f"(d[37]), "+f"(d[38]), "+f"(d[39]), "+f"(d[40]), "+f"(d[41]), "+f"(d[42]), "+f"(d[43]), "+f"(d[44]), "+f"(d[45]), "+f"(d[46]), "+f"(d[47]), "+f"(d[48]), "+f"(d[49]), "+f"(d[50]), "+f"(d[51]), "+f"(d[52]), "+f"(d[53]), "+f"(d[54]), "+f"(d[55]), "+f"(d[56]), "+f"(d[57]), "+f"(d[58]), "+f"(d[59]), "+f"(d[60]), "+f"(d[61]), "+f"(d[62]), "+f"(d[63])
    : "r"(a0), "r"(a1), "r"(a2), "r"(a3), "l"(db));
}
__device__ __forceinline__ void wgmma_rs_n128_a(float (&d)[64], uint32_t a0, uint32_t a1, uint32_t a2, uint32_t a3, uint64_t db) {
  asm volatile("{\n.reg .pred p;\nsetp.ne.b32 p, 1, 0;\nwgmma.mma_async.sync.aligned.m64n128k16.f32.bf16.bf16 {%0,%1,%2,%3,%4,%5,%6,%7,%8,%9,%10,%11,%12,%13,%14,%15,%16,%17,%18,%19,%20,%21,%22,%23,%24,%25,%26,%27,%28,%29,%30,%31,%32,%33,%34,%35,%36,%37,%38,%39,%40,%41,%42,%43,%44,%45,%46,%47,%48,%49,%50,%51,%52,%53,%54,%55,%56,%57,%58,%59,%60,%61,%62,%63}, {%64,%65,%66,%67}, %68, p, 1, 1, 1;\n}\n"
    : "+f"(d[0]), "+f"(d[1]), "+f"(d[2]), "+f"(d[3]), "+f"(d[4]), "+f"(d[5]), "+f"(d[6]), "+f"(d[7]), "+f"(d[8]), "+f"(d[9]), "+f"(d[10]), "+f"(d[11]), "+f"(d[12]), "+f"(d[13]), "+f"(d[14]), "+f"(d[15]), "+f"(d[16]), "+f"(d[17]), "+f"(d[18]), "+f"(d[19]), "+f"(d[20]), "+f"(d[21]), "+f"(d[22]), "+f"(d[23]), "+f"(d[24]), "+f"(d[25]), "+f"(d[26]), "+f"(d[27]), "+f"(d[28]), "+f"(d[29]), "+f"(d[30]), "+f"(d[31]), "+f"(d[32]), "+f"(d[33]), "+f"(d[34]), "+f"(d[35]), "+f"(d[36]), "+f"(d[37]), "+f"(d[38]), "+f"(d[39]), "+f"(d[40]), "+f"(d[41]), "+f"(d[42]), "+f"(d[43]), "+f"(d[44]), "+f"(d[45]), "+f"(d[46]), "+f"(d[47]), "+f"(d[48]), "+f"(d[49]), "+f"(d[50]), "+f"(d[51]), "+f"(d[52]), "+f"(d[53]), "+f"(d[54]), "+f"(d[55]), "+f"(d[56]), "+f"(d[57]), "+f"(d[58]), "+f"(d[59]), "+f"(d[60]), "+f"(d[61]), "+f"(d[62]), "+f"(d[63])
    : "r"(a0), "r"(a1), "r"(a2), "r"(a3), "l"(db));
}

__device__ __forceinline__ void wgmma_rs_n32_z(float (&d)[16], uint32_t a0, uint32_t a1, uint32_t a2, uint32_t a3, uint64_t db) {
  asm volatile("{\n.reg .pred p;\nsetp.ne.b32 p, 0, 0;\nwgmma.mma_async.sync.aligned.m64n32k16.f32.bf16.bf16 {%0,%1,%2,%3,%4,%5,%6,%7,%8,%9,%10,%11,%12,%13,%14,%15}, {%16,%17,%18,%19}, %20, p, 1, 1, 0;\n}\n"
    : "+f"(d[0]), "+f"(d[1]), "+f"(d[2]), "+f"(d[3]), "+f"(d[4]), "+f"(d[5]), "+f"(d[6]), "+f"(d[7]), "+f"(d[8]), "+f"(d[9]), "+f"(d[10]), "+f"(d[11]), "+f"(d[12]), "+f"(d[13]), "+f"(d[14]), "+f"(d[15])
    : "r"(a0), "r"(a1), "r"(a2), "r"(a3), "l"(db));
}
__device__ __forceinline__ void wgmma_rs_n32_a(float (&d)[16], uint32_t a0, uint32_t a1, uint32_t a2, uint32_t a3, uint64_t db) {
  asm volatile("{\n.reg .pred p;\nsetp.ne.b32 p, 1, 0;\nwgmma.mma_async.sync.aligned.m64n32k16.f32.bf16.bf16 {%0,%1,%2,%3,%4,%5,%6,%7,%8,%9,%10,%11,%12,%13,%14,%15}, {%16,%17,%18,%19}, %20, p, 1, 1, 0;\n}\n"
    : "+f"(d[0]), "+f"(d[1]), "+f"(d[2]), "+f"(d[3]), "+f"(d[4]), "+f"(d[5]), "+f"(d[6]), "+f"(d[7]), "+f"(d[8]), "+f"(d[9]), "+f"(d[10]), "+f"(d[11]), "+f"(d[12]), "+f"(d[13]), "+f"(d[14]), "+f"(d[15])
    : "r"(a0), "r"(a1), "r"(a2), "r"(a3), "l"(db));
}

__device__ __forceinline__ void wgmma_rs_n64_z(float (&d)[32], uint32_t a0, uint32_t a1, uint32_t a2, uint32_t a3, uint64_t db) {
  asm volatile("{\n.reg .pred p;\nsetp.ne.b32 p, 0, 0;\nwgmma.mma_async.sync.aligned.m64n64k16.f32.bf16.bf16 {%0,%1,%2,%3,%4,%5,%6,%7,%8,%9,%10,%11,%12,%13,%14,%15,%16,%17,%18,%19,%20,%21,%22,%23,%24,%25,%26,%27,%28,%29,%30,%31}, {%32,%33,%34,%35}, %36, p, 1, 1, 0;\n}\n"
    : "+f"(d[0]), "+f"(d[1]), "+f"(d[2]), "+f"(d[3]), "+f"(d[4]), "+f"(d[5]), "+f"(d[6]), "+f"(d[7]), "+f"(d[8]), "+f"(d[9]), "+f"(d[10]), "+f"(d[11]), "+f"(d[12]), "+f"(d[13]), "+f"(d[14]), "+f"(d[15]), "+f"(d[16]), "+f"(d[17]), "+f"(d[18]), "+f"(d[19]), "+f"(d[20]), "+f"(d[21]), "+f"(d[22]), "+f"(d[23]), "+f"(d[24]), "+f"(d[25]), "+f"(d[26]), "+f"(d[27]), "+f"(d[28]), "+f"(d[29]), "+f"(d[30]), "+f"(d[31])
    : "r"(a0), "r"(a1), "r"(a2), "r"(a3), "l"(db));
}
__device__ __forceinline__ void wgmma_rs_n64_a(float (&d)[32], uint32_t a0, uint32_t a1, uint32_t a2, uint32_t a3, uint64_t db) {
  asm volatile("{\n.reg .pred p;\nsetp.ne.b32 p, 1, 0;\nwgmma.mma_async.sync.aligned.m64n64k16.f32.bf16.bf16 {%0,%1,%2,%3,%4,%5,%6,%7,%8,%9,%10,%11,%12,%13,%14,%15,%16,%17,%18,%19,%20,%21,%22,%23,%24,%25,%26,%27,%28,%29,%30,%31}, {%32,%33,%34,%35}, %36, p, 1, 1, 0;\n}\n"
    : "+f"(d[0]), "+f"(d[1]), "+f"(d[2]), "+f"(d[3]), "+f"(d[4]), "+f"(d[5]), "+f"(d[6]), "+f"(d[7]), "+f"(d[8]), "+f"(d[9]), "+f"(d[10]), "+f"(d[11]), "+f"(d[12]), "+f"(d[13]), "+f"(d[14]), "+f"(d[15]), "+f"(d[16]), "+f"(d[17]), "+f"(d[18]), "+f"(d[19]), "+f"(d[20]), "+f"(d[21]), "+f"(d[22]), "+f"(d[23]), "+f"(d[24]), "+f"(d[25]), "+f"(d[26]), "+f"(d[27]), "+f"(d[28]), "+f"(d[29]), "+f"(d[30]), "+f"(d[31])
    : "r"(a0), "r"(a1), "r"(a2), "r"(a3), "l"(db));
}

__device__ __forceinline__ void wgmma_ss_n32_z(float (&d)[16], uint64_t da, uint64_t db) {
  asm volatile("{\n.reg .pred p;\nsetp.ne.b32 p, 0, 0;\nwgmma.mma_async.sync.aligned.m64n32k16.f32.bf16.bf16 {%0,%1,%2,%3,%4,%5,%6,%7,%8,%9,%10,%11,%12,%13,%14,%15}, %16, %17, p, 1, 1, 1, 0;\n}\n"
    : "+f"(d[0]), "+f"(d[1]), "+f"(d[2]), "+f"(d[3]), "+f"(d[4]), "+f"(d[5]), "+f"(d[6]), "+f"(d[7]), "+f"(d[8]), "+f"(d[9]), "+f"(d[10]), "+f"(d[11]), "+f"(d[12]), "+f"(d[13]), "+f"(d[14]), "+f"(d[15])
    : "l"(da), "l"(db));
}
__device__ __forceinline__ void wgmma_ss_n32_a(float (&d)[16], uint64_t da, uint64_t db) {
  asm volatile("{\n.reg .pred p;\nsetp.ne.b32 p, 1, 0;\nwgmma.mma_async.sync.aligned.m64n32k16.f32.bf16.bf16 {%0,%1,%2,%3,%4,%5,%6,%7,%8,%9,%10,%11,%12,%13,%14,%15}, %16, %17, p, 1, 1, 1, 0;\n}\n"
    : "+f"(d[0]), "+f"(d[1]), "+f"(d[2]), "+f"(d[3]), "+f"(d[4]), "+f"(d[5]), "+f"(d[6]), "+f"(d[7]), "+f"(d[8]), "+f"(d[9]), "+f"(d[10]), "+f"(d[11]), "+f"(d[12]), "+f"(d[13]), "+f"(d[14]), "+f"(d[15])
    : "l"(da), "l"(db));
}

__device__ __forceinline__ void wgmma_ss_n40_z(float (&d)[20], uint64_t da, uint64_t db) {
  asm volatile("{\n.reg .pred p;\nsetp.ne.b32 p, 0, 0;\nwgmma.mma_async.sync.aligned.m64n40k16.f32.bf16.bf16 {%0,%1,%2,%3,%4,%5,%6,%7,%8,%9,%10,%11,%12,%13,%14,%15,%16,%17,%18,%19}, %20, %21, p, 1, 1, 1, 0;\n}\n"
    : "+f"(d[0]), "+f"(d[1]), "+f"(d[2]), "+f"(d[3]), "+f"(d[4]), "+f"(d[5]), "+f"(d[6]), "+f"(d[7]), "+f"(d[8]), "+f"(d[9]), "+f"(d[10]), "+f"(d[11]), "+f"(d[12]), "+f"(d[13]), "+f"(d[14]), "+f"(d[15]), "+f"(d[16]), "+f"(d[17]), "+f"(d[18]), "+f"(d[19])
    : "l"(da), "l"(db));
}
__device__ __forceinline__ void wgmma_ss_n40_a(float (&d)[20], uint64_t da, uint64_t db) {
  asm volatile("{\n.reg .pred p;\nsetp.ne.b32 p, 1, 0;\nwgmma.mma_async.sync.aligned.m64n40k16.f32.bf16.bf16 {%0,%1,%2,%3,%4,%5,%6,%7,%8,%9,%10,%11,%12,%13,%14,%15,%16,%17,%18,%19}, %20, %21, p, 1, 1, 1, 0;\n}\n"
    : "+f"(d[0]), "+f"(d[1]), "+f"(d[2]), "+f"(d[3]), "+f"(d[4]), "+f"(d[5]), "+f"(d[6]), "+f"(d[7]), "+f"(d[8]), "+f"(d[9]), "+f"(d[10]), "+f"(d[11]), "+f"(d[12]), "+f"(d[13]), "+f"(d[14]), "+f"(d[15]), "+f"(d[16]), "+f"(d[17]), "+f"(d[18]), "+f"(d[19])
    : "l"(da), "l"(db));
}

constexpr int NSM = 132, NH = 66;
constexpr int S0 = 0, S1 = 51200, S2 = 102400;
constexpr int C1 = 153600, C3 = C1, RG = C1 + 18432;
constexpr int WP = RG, TBL = RG + 28672, WS2 = RG + 30720;
constexpr int BARS = RG + 49152;
__host__ __device__ constexpr int wst_off(int i) { return i < 12 ? S2 + i * 4096 : WS2 + (i - 12) * 4096; }
constexpr int NBAR = 280;
constexpr int REL = BARS + NBAR * 8;
constexpr int SMEM_BYTES = REL + 16;
constexpr int B_XF = 0, B_CF1 = 15, B_CF3 = 16, B_WF = 17  , B_P1D = 18, B_REL = 21, B_ROLE = 22, B_SIG = 24;
constexpr int B_RF = 32, B_RE = 46, B_YF = 60, B_WRD = 75, B_SFREE = 89, B_WCH = 131, B_RDY = 136, B_WE = 205, B_WL = 217, B_FIN = 229, B_TOK = 232;
constexpr int R_P2 = 15, R_P3 = 57;
constexpr int CNT_P1 = 0, CNT_P2 = 4, CNT_W = 8, CNT_RANK = 9, NCLS = 10, CNT_DONE = 0, CNT_REL = 1, NCNT = 2;
constexpr int SIG_W = 0, SIG_P1 = 1, SIG_P2 = 4;
#define T1MASK 0x3e00
#define T2MASK 0x1f00

__device__ uint4 g_scr[(14 << 21) / 16];
__device__ __align__(128) uint4 g_wf[200 * 72 * 32];
__device__ __align__(128) unsigned g_cnt[NCNT * 32];
__device__ __forceinline__ int slot_line(int chunk, int pg, int cls) {
    return (pg & 1) << 6 | (pg >> 1) << 9 | (chunk & 1) << 10 | (chunk >> 1) << 12 | ((pg ^ (pg >> 1) ^ chunk ^ (chunk >> 1) ^ cls) & 1) << 5;
}
__device__ __forceinline__ int phi_line(int phi, uint32_t rel) {
    return (phi >> 4) << 14 | (phi & 3) << 7 | ((phi >> 2) & 1) << 11 | ((phi >> 3) & 1) << 13 | ((rel >> (phi >> 4)) & 1) << 5;
}
__device__ __forceinline__ int extra_mask(int rk) { return rk < 60 ? 0 : rk < 62 ? 1 : rk < 64 ? 10 : 4; }
__device__ __forceinline__ int wslot(int pc) {
    return (int)((0x576476503421ull >> (4 * pc)) & 3) * 12288 + (((0x576476503421ull >> (4 * pc)) & 4) ? S0 : RG);
}
__device__ __forceinline__ int xslot(int n) { return ((n & 4) ? S2 : RG) + ((n + 1) & 3) * 12288; }
__device__ __forceinline__ int extra_phi(int rk) { return 198 + (rk & 1); }
__host__ __device__ constexpr int quad_off(int Q) { return (Q >> 2) * 4096 + (Q & 3) * 512; }

struct Maps { CUtensorMap w, x34, x6, x28, wst, f16, f8, y4, y2; };
struct Ptrs { char* scr; const char* wf; const void* tab1; const void* tab3; unsigned* cnt; const char* x; };

__device__ __forceinline__ uint32_t smem_u32(const void* p) { return (uint32_t)__cvta_generic_to_shared(p); }
__device__ __forceinline__ void mbar_wait(uint32_t bar) {
    uint32_t ok, it = 0;
    do {
        asm volatile("{\n.reg .pred p;\nmbarrier.try_wait.parity.shared::cta.b64 p, [%1], 0;\nselp.u32 %0, 1, 0, p;\n}" : "=r"(ok) : "r"(bar) : "memory");
        if (++it > (1u << 22)) break;
    } while (!ok);
}
__device__ __forceinline__ bool mbar_test(uint32_t bar) {
    uint32_t ok;
    asm volatile("{\n.reg .pred p;\nmbarrier.test_wait.parity.shared::cta.b64 p, [%1], 0;\nselp.u32 %0, 1, 0, p;\n}" : "=r"(ok) : "r"(bar) : "memory");
    return ok;
}
__device__ __forceinline__ void fence_async() { asm volatile("fence.proxy.async;" ::: "memory"); }
__device__ __forceinline__ void fence_async_smem() { asm volatile("fence.proxy.async.shared::cta;" ::: "memory"); }
#define ELECT "{\n.reg .pred p;\nelect.sync _|p, 0xffffffff;\n@p "
__device__ __forceinline__ void e_arrive(uint32_t bar) { asm volatile(ELECT "mbarrier.arrive.shared::cta.b64 _, [%0];\n}" :: "r"(bar) : "memory"); }
__device__ __forceinline__ void e_expect(uint32_t bar, uint32_t bytes) { asm volatile(ELECT "mbarrier.arrive.expect_tx.shared::cta.b64 _, [%0], %1;\n}" :: "r"(bar), "r"(bytes) : "memory"); }
__device__ __forceinline__ void e_g2s(uint32_t dst, const void* src, uint32_t bytes, uint32_t bar) {
    asm volatile(ELECT "cp.async.bulk.shared::cluster.global.mbarrier::complete_tx::bytes [%0], [%1], %2, [%3];\n}" :: "r"(dst), "l"(src), "r"(bytes), "r"(bar) : "memory");
}
__device__ __forceinline__ void e_s2g(void* dst, uint32_t src, uint32_t bytes) {
    asm volatile(ELECT "cp.async.bulk.global.shared::cta.bulk_group [%0], [%1], %2;\n}" :: "l"(dst), "r"(src), "r"(bytes) : "memory");
}
__device__ __forceinline__ void e_ld3(uint32_t dst, const CUtensorMap* m, int c0, int c1, int c2, uint32_t bar) {
    asm volatile(ELECT "cp.async.bulk.tensor.3d.shared::cluster.global.mbarrier::complete_tx::bytes [%0], [%1, {%3, %4, %5}], [%2];\n}"
                 :: "r"(dst), "l"(m), "r"(bar), "r"(c0), "r"(c1), "r"(c2) : "memory");
}
__device__ __forceinline__ void e_ld4(uint32_t dst, const CUtensorMap* m, int c0, int c3, uint32_t bar) {
    asm volatile(ELECT "cp.async.bulk.tensor.4d.shared::cluster.global.mbarrier::complete_tx::bytes [%0], [%1, {%3, %5, %5, %4}], [%2];\n}"
                 :: "r"(dst), "l"(m), "r"(bar), "r"(c0), "r"(c3), "r"(0) : "memory");
}
__device__ __forceinline__ void e_st3(const CUtensorMap* m, uint32_t src, int c0, int c1, int c2) {
    asm volatile(ELECT "cp.async.bulk.tensor.3d.global.shared::cta.bulk_group [%0, {%2, %3, %4}], [%1];\n}" :: "l"(m), "r"(src), "r"(c0), "r"(c1), "r"(c2) : "memory");
}
__device__ __forceinline__ void e_ld5(uint32_t dst, const CUtensorMap* m, int c4, uint32_t bar) {
    asm volatile(ELECT "cp.async.bulk.tensor.5d.shared::cluster.global.mbarrier::complete_tx::bytes [%0], [%1, {%4, %4, %4, %4, %3}], [%2];\n}"
                 :: "r"(dst), "l"(m), "r"(bar), "r"(c4), "r"(0) : "memory");
}
__device__ __forceinline__ void e_st5(const CUtensorMap* m, uint32_t src, int c4) {
    asm volatile(ELECT "cp.async.bulk.tensor.5d.global.shared::cta.bulk_group [%0, {%3, %3, %3, %3, %2}], [%1];\n}" :: "l"(m), "r"(src), "r"(c4), "r"(0) : "memory");
}
__device__ __forceinline__ void bulk_commit() { asm volatile("cp.async.bulk.commit_group;" ::: "memory"); }
template <int N> __device__ __forceinline__ void bulk_wait() { asm volatile("cp.async.bulk.wait_group %0;" :: "n"(N) : "memory"); }
template <int N> __device__ __forceinline__ void bulk_wait_read() { asm volatile("cp.async.bulk.wait_group.read %0;" :: "n"(N) : "memory"); }
__device__ __forceinline__ void wg_bar(int id) { asm volatile("bar.sync %0, 128;" :: "r"(id) : "memory"); }
__device__ __forceinline__ void bb_break(uint32_t v) { asm volatile("{\n.reg .pred p;\nsetp.eq.u32 p, %0, 0x7fc17fc1;\n@p nanosleep.u32 0;\n}" :: "r"(v) : "memory"); }
__device__ __forceinline__ uint32_t uni(uint32_t v) { return __shfl_sync(0xffffffffu, v, 0); }
__device__ __forceinline__ char* cls_cnt(char* scr, int cls) { return scr + slot_line(3, 2, cls) * 128; }
__device__ __forceinline__ uint32_t cnt_wait(const void* p, unsigned target) {
    uint32_t v = 0;
#pragma unroll 1
    for (unsigned it = 0; it < (1u << 22) && v < target; it++) {
        asm volatile("ld.acquire.gpu.global.u32 %0, [%1];" : "=r"(v) : "l"(p) : "memory");
        v = uni(v);
    }
    asm volatile("fence.proxy.async.global;" ::: "memory");
    return v;
}
__device__ __forceinline__ void wg_fence() { asm volatile("wgmma.fence.sync.aligned;" ::: "memory"); }
__device__ __forceinline__ void wg_commit() { asm volatile("wgmma.commit_group.sync.aligned;" ::: "memory"); }
template <int N> __device__ __forceinline__ void wg_wait() { asm volatile("wgmma.wait_group.sync.aligned %0;" :: "n"(N) : "memory"); }
template <int N> __device__ __forceinline__ void reg_fence(float (&d)[N]) {
#pragma unroll
    for (int i = 0; i < N; i++) asm volatile("" : "+f"(d[i]) :: "memory");
}
template <int N> __device__ __forceinline__ void zero(float (&d)[N]) {
#pragma unroll
    for (int i = 0; i < N; i++) d[i] = 0.f;
}
__device__ __forceinline__ uint32_t pack2(float lo, float hi) {
    uint32_t r; asm volatile("cvt.rn.bf16x2.f32 %0, %1, %2;" : "=r"(r) : "f"(hi), "f"(lo)); return r;
}
__device__ __forceinline__ void stm4(uint32_t a, uint32_t r0, uint32_t r1, uint32_t r2, uint32_t r3) {
    asm volatile("stmatrix.sync.aligned.m8n8.x4.trans.shared.b16 [%0], {%1,%2,%3,%4};" :: "r"(a), "r"(r0), "r"(r1), "r"(r2), "r"(r3) : "memory");
}
__device__ __forceinline__ void stm2(uint32_t a, uint32_t r0, uint32_t r1) {
    asm volatile("stmatrix.sync.aligned.m8n8.x2.trans.shared.b16 [%0], {%1,%2};" :: "r"(a), "r"(r0), "r"(r1) : "memory");
}
struct Desc {
    uint32_t lo, hi;
    __device__ __forceinline__ operator uint64_t() const { return ((uint64_t)hi << 32) | lo; }
    __device__ __forceinline__ Desc operator+(uint32_t o) const { return Desc{lo + o, hi}; }
    __device__ __forceinline__ Desc operator^(uint32_t o) const { return Desc{lo ^ o, hi}; }
};
__device__ __forceinline__ Desc mkdesc(uint32_t addr, uint32_t lbo, uint32_t sbo, uint32_t swz) {
    return Desc{((addr & 0x3FFFF) >> 4) | ((lbo >> 4) << 16), (sbo >> 4) | (swz << 30)};
}
__device__ __forceinline__ uint32_t cos_bits(int k) {
    if (k > 20) k = 40 - k;
    const bool neg = k > 10;
    if (neg) k = 20 - k;
    const unsigned long long pk = k < 4 ? COS_PK0 : k < 8 ? COS_PK1 : COS_PK2;
    return (uint32_t)((pk >> (16 * (k & 3))) & 0xffff) ^ (neg ? 0x8000u : 0u);
}

__device__ __forceinline__ void task_w(int wg, int k, uint32_t sb) {
    const int tid = threadIdx.x & 127, w = uni(tid >> 5), lane = tid & 31, q = lane & 3;
    const int tb = 14 * k, t1 = min(tb + 14, 1800), cb0 = tb / 25;
    float acc[64];
    zero(acc);
    const int oc0 = tb - 25 * cb0, Lt = t1 - tb, L0 = min(Lt, 25 - oc0), n0 = (L0 + 3) >> 2;
    uint32_t a[2][4][4];
    auto gen = [&](uint32_t (&a)[4][4], int at) {
        const int phi = 8 * ((at < n0 ? oc0 + 4 * at : 4 * (at - n0)) + w) + (lane >> 2), f = (phi * 205) >> 12;
        const uint32_t ca = 8 * f + 4, cw = (phi - 20 * f) * 8, p0 = sb + TBL + cw * 2 * q;
#pragma unroll
        for (int kh = 0; kh < 7; kh++) {
            uint32_t v0, v1;
            asm volatile("ld.shared.u32 %0, [%1];" : "=r"(v0) : "r"(p0 + ca * kh));
            asm volatile("ld.shared.u32 %0, [%1];" : "=r"(v1) : "r"(p0 + cw + ca * kh));
            const int h = kh == 6 ? 1 : kh & 1;
            a[kh >> 1][2 * h] = __byte_perm(v0, v1, 0x5410);
            a[kh >> 1][2 * h + 1] = __byte_perm(v0, v1, 0x7632);
        }
        a[3][0] = 0; a[3][1] = 0;
    };
    gen(a[0], wg);
    if (wg) gen(a[1], wg + 2);
#pragma unroll 1
    for (int n = 0; n < 2; n++) {
        const int at = wg + 2 * n, i0 = at < n0 ? 4 * at : L0 + 4 * (at - n0), cnt = (at < n0 ? L0 : Lt) - i0, cb = cb0 + (at >= n0);
        if (cnt <= 0 || (n && !wg)) break;
        if (n) {
#pragma unroll
            for (int j = 0; j < 16; j++) a[0][j >> 2][j & 3] = a[1][j >> 2][j & 3];
        }
        const Desc dB = mkdesc(sb + WP + (cb - cb0) * 14336, 3584, 512, 2);
        if (at) mbar_wait(sb + BARS + 8 * (B_WCH + at - 1));
        mbar_wait(sb + BARS + 8 * (B_WF + 2 * (cb - cb0)));
        wg_fence();
        wgmma_rs_n128_z(acc, a[0][0][0], a[0][0][1], a[0][0][2], a[0][0][3], dB);
        wgmma_rs_n128_a(acc, a[0][1][0], a[0][1][1], a[0][1][2], a[0][1][3], dB + (uint32_t)(16 * 64 >> 4));
        wgmma_rs_n128_a(acc, a[0][2][0], a[0][2][1], a[0][2][2], a[0][2][3], dB + (uint32_t)(32 * 64 >> 4));
        wgmma_rs_n128_a(acc, a[0][3][0], a[0][3][1], a[0][3][2], a[0][3][3], dB + (uint32_t)(40 * 64 >> 4));
        wg_commit();
        wg_wait<0>();
        reg_fence(acc);
        e_arrive(sb + BARS + 8 * (B_WCH + at));
        if (w < cnt) {
            const uint32_t dst = sb + wst_off(i0 + w) + (lane >> 2) * 512 + (lane & 4) * 16 + ((q ^ cb) & 3) * 16;
#pragma unroll
            for (int j = 0; j < 4; j++)
#pragma unroll
                for (int e = 0; e < 2; e++)
                    asm volatile("st.shared.v4.u32 [%0], {%1,%2,%3,%4};" :: "r"((dst ^ (e * 64)) + j * 128),
                                 "r"(pack2(acc[4 * j + e], acc[16 + 4 * j + e])), "r"(pack2(acc[4 * j + 2 + e], acc[16 + 4 * j + 2 + e])),
                                 "r"(pack2(acc[32 + 4 * j + e], acc[48 + 4 * j + e])), "r"(pack2(acc[32 + 4 * j + 2 + e], acc[48 + 4 * j + 2 + e])) : "memory");
            fence_async_smem();
            e_arrive(sb + BARS + 8 * (B_WRD + i0 + w));
        }
    }
}

__device__ __forceinline__ void task_p1(int wg, int pair, uint32_t sb) {
    const int tid = threadIdx.x & 127, w = tid >> 5, lane = tid & 31;
    const uint32_t buf = sb + wg * 51200, bars = sb + BARS;
    uint32_t fr[5][10][2];
    float A[40], d[20];
    zero(A);
    {
        const Desc dA = mkdesc(buf, 3584, 512, 2), dB = mkdesc(sb + C1, 128, 256, 0);
        auto issue = [&](int g, float (&d)[40]) {
            mbar_wait(bars + 8 * (B_XF + wg * 5 + g));
            wg_fence();
            wgmma_ss_n80_z(d, dA + (uint32_t)(g * 8704 >> 4), dB);
#pragma unroll
            for (int j = 1; j < 5; j++) wgmma_ss_n80_a(d, dA + (uint32_t)((g * 8704 + j * 1024) >> 4), dB + (uint32_t)(j * 2560 >> 4));
            wg_commit();
        };
        auto pack = [&](int g, float (&d)[40]) {
            reg_fence(d);
#pragma unroll
            for (int f = 0; f < 10; f++) {
                fr[g][f][0] = pack2(d[4 * f], d[4 * f + 1]);
                fr[g][f][1] = pack2(d[4 * f + 2], d[4 * f + 3]);
            }
        };
        mbar_wait(bars + 8 * B_CF1);
#pragma unroll
        for (int g = 0; g < 4; g++) { issue(g, A); wg_wait<0>(); pack(g, A); }
        zero(d);
        mbar_wait(bars + 8 * (B_XF + wg * 5 + 4));
#pragma unroll
        for (int h = 0; h < 2; h++) {
            wg_fence();
            wgmma_ss_n40_z(d, dA + (uint32_t)(4 * 8704 >> 4), dB + (uint32_t)(h * 1280 >> 4));
#pragma unroll
            for (int j = 1; j < 5; j++) wgmma_ss_n40_a(d, dA + (uint32_t)((4 * 8704 + j * 1024) >> 4), dB + (uint32_t)((j * 2560 + h * 1280) >> 4));
            wg_commit(); wg_wait<0>(); reg_fence(d);
#pragma unroll
            for (int f = 0; f < 5; f++) { fr[4][5 * h + f][0] = pack2(d[4 * f], d[4 * f + 1]); fr[4][5 * h + f][1] = pack2(d[4 * f + 2], d[4 * f + 3]); }
        }
    }
    bb_break(sb);
    wg_bar(1 + wg);
    {
        const Desc dB = mkdesc(sb + C1 + 12800, 128, 256, 0);
        const int i = lane & 7, mi = lane >> 3, th = w >> 1, tz = (2 * pair + th) & 3;
        const uint32_t s0 = buf + (i >> 1) * 128 + (i & 1) * 64 + (((2 * (w & 1) + (mi & 1)) ^ tz ^ (i >> 1)) << 4);
        const uint32_t sA = s0 + th * 2048 + (mi >> 1) * 512, sB = s0 + th * 2048 + (mi >> 1) * 2560, sC = s0 + th * 1024 + (mi >> 1) * 512;
        auto issue = [&](int f, float (&d)[20]) {
            wg_fence();
            wgmma_rs_n40_z(d, fr[0][f][0], fr[0][f][1], fr[1][f][0], fr[1][f][1], dB);
            wgmma_rs_n40_a(d, fr[2][f][0], fr[2][f][1], fr[3][f][0], fr[3][f][1], dB + (uint32_t)(1280 >> 4));
            wgmma_rs_n40_a(d, fr[4][f % 5][0], fr[4][f % 5][1], fr[4][f % 5 + 5][0], fr[4][f % 5 + 5][1], dB + (uint32_t)((2560 + (f / 5) * 1280) >> 4));
            wg_commit();
        };
#pragma unroll
        for (int f = 0; f < 10; f++) {
            issue(f, d);
            if (f && !(f & 1)) { fence_async_smem(); e_arrive(bars + 8 * (B_RDY + wg * 5 + (f >> 1) - 1)); }
            wg_wait<0>(); reg_fence(d);
            const int Q = 5 * f;
            stm4(((Q & 3) == 3 ? sB : sA) + quad_off(Q), pack2(d[0], d[1]), pack2(d[2], d[3]), pack2(d[4], d[5]), pack2(d[6], d[7]));
            stm2(sA + quad_off(Q + 2), pack2(d[8], d[9]), pack2(d[10], d[11]));
            stm4((f == 9 ? sC : ((Q + 3) & 3) == 3 ? sB : sA) + quad_off(Q + 3), pack2(d[12], d[13]), pack2(d[14], d[15]), pack2(d[16], d[17]), pack2(d[18], d[19]));
            if (f == 9) { fence_async_smem(); e_arrive(bars + 8 * (B_RDY + wg * 5 + (f >> 1))); }
        }
    }
}

__device__ __forceinline__ void task_p2(int wg, int rk, uint32_t sb) {
    const int tid = threadIdx.x & 127, w = tid >> 5, lane = tid & 31;
    const uint32_t bars = sb + BARS;
    const int phi0 = 3 * rk, phiE = extra_phi(rk), mE = extra_mask(rk);
    uint4 wA[6], wB[6], wC[6], wE[6];
    auto ldw = [&](uint4 (&a)[6], int j, int phi) {
        const int pc = 3 * j + wg;
        const uint32_t p = sb + wslot(pc) + (lane & 3) * 512 + w * 128 + (((lane >> 2) ^ phi) & 1) * 64 + (((lane >> 3) ^ lane) & 3) * 16 + (phi & 1) * 8;
        mbar_wait(bars + 8 * (B_WL + pc));
#pragma unroll
        for (int s = 0; s < 6; s++) {
            asm volatile("ld.shared.v2.u32 {%0, %1}, [%2];" : "=r"(a[s].x), "=r"(a[s].y) : "r"(p + s * 2048) : "memory");
            asm volatile("ld.shared.v2.u32 {%0, %1}, [%2];" : "=r"(a[s].z), "=r"(a[s].w) : "r"((p ^ 8) + s * 2048) : "memory");
        }
        uint32_t dep = 0;
#pragma unroll
        for (int s = 0; s < 6; s++) dep |= a[s].x ^ a[s].z;
        if (__any_sync(0xffffffffu, dep == 0x7fc17fc1u)) __nanosleep(0);
        e_arrive(bars + 8 * (B_WE + pc));
    };
    ldw(wA, 0, phi0); ldw(wB, 1, phi0 + 1);
    mbar_wait(bars + 8 * (B_SIG + SIG_P1 + 1));
    const int i = lane & 7, mi = lane >> 3;
    const uint32_t soff = sb + S1 + wg * 4096 + mi * 512 + (i >> 1) * 128 + (i & 1) * 64;
    const int xo = w ^ (i >> 1);
    float d[32];
    zero(d);
    int n = 0;
    uint32_t xb = ((sb + xslot(0)) & 0x3FFFF) >> 4 | 1u << 16, mb = bars + 8 * wg;
    bool landed = false;
    auto unit = [&](const uint4 (&a)[6], int z) {
        const Desc d0{xb + (z & 2), (512u >> 4) | (2u << 30)}, d1 = d0 ^ 2u;
        if (!landed) mbar_wait(bars + 8 * (B_RF + n));
        mbar_wait(mb + 8 * (B_TOK - 1));
        wg_fence();
        wgmma_rs_n64_z(d, a[0].x, a[0].y, a[0].z, a[0].w, d0);
        wgmma_rs_n64_a(d, a[1].x, a[1].y, a[1].z, a[1].w, d1);
        e_arrive(bars + 8 * (n ? B_RE + n - 1 : B_RE + 13));
        const bool sfree = mbar_test(n >= 4 ? mb + 8 * (B_SFREE - 12) : bars + 8 * (B_TOK - 1));
        landed = mbar_test(bars + 8 * (B_RF + n + 1));
        wgmma_rs_n64_a(d, a[2].x, a[2].y, a[2].z, a[2].w, d0 + (uint32_t)(4096 >> 4));
        wgmma_rs_n64_a(d, a[3].x, a[3].y, a[3].z, a[3].w, d1 + (uint32_t)(4096 >> 4));
        e_arrive(mb + 8 * B_TOK);
        wgmma_rs_n64_a(d, a[4].x, a[4].y, a[4].z, a[4].w, d0 + (uint32_t)(8192 >> 4));
        wgmma_rs_n64_a(d, a[5].x, a[5].y, a[5].z, a[5].w, d1 + (uint32_t)(8192 >> 4));
        wg_commit();
        if (!sfree) mbar_wait(mb + 8 * (B_SFREE - 12));
        const uint32_t a0 = soff + (n & 3) * 12288 + ((xo ^ z) << 4);
        n++;
        xb = ((sb + xslot(n)) & 0x3FFFF) >> 4 | 1u << 16;
        wg_wait<0>();
        reg_fence(d);
        uint32_t p[8];
#pragma unroll
        for (int j = 0; j < 8; j++) p[j] = pack2(d[4 * j] - d[4 * j + 3], d[4 * j + 2] + d[4 * j + 1]);
        stm4(a0, p[0], p[1], p[2], p[3]);
        stm4(a0 + 2048, p[4], p[5], p[6], p[7]);
        fence_async_smem();
        e_arrive(mb + 8 * (B_RDY + R_P2));
        mb += 24;
    };
    const int zA = phi0 & 3, zB = (phi0 + 1) & 3, zC = (phi0 + 2) & 3, zE = phiE & 3;
#pragma unroll 1
    for (int it = 0; it < 4; it++) {
        unit(wA, zA);
        unit(wB, zB);
        if (it == 0) ldw(wC, 2, phi0 + 2);
        unit(wC, zC);
        if (it == 0 && mE) ldw(wE, 3, phiE);
        if (mE >> it & 1) unit(wE, zE);
    }
}

__device__ __forceinline__ void task_p3(int wg, int pair, uint32_t sb) {
    const int tid = threadIdx.x & 127, w = tid >> 5, lane = tid & 31;
    const uint32_t buf = sb + (wg ? 3 - wg : 0) * 51200, bars = sb + BARS;
    uint32_t fr[10][4][2];
    float acc[2][16];
    zero(acc[0]); zero(acc[1]);
    {
        const Desc dB = mkdesc(sb + C3, 128, 256, 0);
        const uint32_t a0 = (buf & 0x3FFFF) >> 4;
        auto dq = [&](int Q) {
            return Desc{a0 + (uint32_t)((quad_off(Q) >> 4) | ((Q < 48 ? 2048 : 1024) >> 4) << 16), (uint32_t)((quad_off(Q + 1) - quad_off(Q)) >> 4) | (2u << 30)};
        };
        auto issue = [&](int f) {
            if (!(f & 1)) mbar_wait(bars + 8 * (B_YF + wg * 5 + (f >> 1)));
            wg_fence();
            wgmma_ss_n32_z(acc[f & 1], dq(5 * f), dB);
            wgmma_ss_n32_a(acc[f & 1], dq(5 * f + 1), dB + (uint32_t)(1024 >> 4));
            wgmma_ss_n32_a(acc[f & 1], dq(5 * f + 3), dB + (uint32_t)(2048 >> 4));
            wg_commit();
        };
        mbar_wait(bars + 8 * B_CF3);
        issue(0);
#pragma unroll
        for (int f = 0; f < 10; f++) {
            if (f < 9) { issue(f + 1); wg_wait<1>(); } else wg_wait<0>();
            float (&d)[16] = acc[f & 1];
            reg_fence(d);
#pragma unroll
            for (int g = 0; g < 4; g++) { fr[f][g][0] = pack2(d[4 * g], d[4 * g + 1]); fr[f][g][1] = pack2(d[4 * g + 2], d[4 * g + 3]); }
        }
    }
    {
        const Desc dB = mkdesc(sb + C3 + 3072, 128, 256, 0);
        const int i = lane & 7, mi = lane >> 3, th = w >> 1, tz = (2 * pair + th) & 3;
        const int oct = (2 * (w & 1) + (mi & 1)) ^ tz;
        const uint32_t soff = buf + th * 3584 + (mi >> 1) * 512 + i * 64 + ((oct ^ (i >> 1)) << 4);
        auto mma = [&](int t, int s) {
            if (t > 6) return;
            const int g = t < 6 ? 1 + (t >> 1) : 0;
            const uint32_t o = t < 6 ? (t & 1) * 1024 : 8960, st = t < 6 ? 1792 : 1024;
            if (s == 0) { wg_fence(); wgmma_rs_n32_z(acc[t & 1], fr[0][g][0], fr[0][g][1], fr[1][g][0], fr[1][g][1], dB + (o >> 4)); }
            else wgmma_rs_n32_a(acc[t & 1], fr[2 * s][g][0], fr[2 * s][g][1], fr[2 * s + 1][g][0], fr[2 * s + 1][g][1], dB + ((o + s * st) >> 4));
            if (s == 4) wg_commit();
        };
        const int row = th * 14 + 4 * (mi >> 1) + (i >> 1);
        const uint32_t z0 = buf + row * 128 + (i & 1) * 64 + ((oct ^ (row & 3)) << 4), z1 = (lane & 20) == 20 ? buf + 4096 + lane * 16 : z0 + 1024;
        bb_break(sb);
#pragma unroll
        for (int s = 0; s < 5; s++) mma(0, s);
        wg_bar(1 + wg);
#pragma unroll
        for (int t = 0; t < 7; t++) {
#pragma unroll
            for (int s = 0; s < 2; s++) mma(t + 1, s);
            if (t < 6) { wg_commit(); wg_wait<1>(); } else wg_wait<0>();
            float (&d)[16] = acc[t & 1];
            reg_fence(d);
            const uint32_t a = soff + (1 + (t >> 1)) * 7168 + (t & 1) * 2048;
            stm4(t < 6 ? a : z0, pack2(d[0], d[1]), pack2(d[2], d[3]), pack2(d[4], d[5]), pack2(d[6], d[7]));
            mma(t + 1, 2);
            if (t & 1) stm2(a + 1024, pack2(d[8], d[9]), pack2(d[10], d[11]));
            else stm4(t < 6 ? a + 1024 : z1, pack2(d[8], d[9]), pack2(d[10], d[11]), pack2(d[12], d[13]), pack2(d[14], d[15]));
#pragma unroll
            for (int s = 3; s < 5; s++) mma(t + 1, s);
            if ((t & 1) || t == 6) { fence_async_smem(); e_arrive(bars + 8 * (B_RDY + R_P3 + wg * 4 + (t >> 1))); }
        }
    }
}

__device__ __forceinline__ void load_x(int cls, int rk, int u, uint32_t sb, const Maps& mp) {
    const int id = u * NH + rk, pl = id / 3, c0 = 32 * (id - 3 * pl), tp = cls * 4 + (pl >> 4), col = 14 * (pl & 15) - 8;
    const uint32_t bar = sb + BARS + 8 * (B_XF + u * 5), dst = sb + u * 51200;
    const int wrap = col < 0 ? 224 : 0;
    if (tp) {
#pragma unroll
        for (int g = 0; g < 5; g++) e_ld3(dst + g * 8704, &mp.x34, c0, col + 4 * g + (g < 2 ? wrap : 0), 28 * tp - 6, bar + 8 * g);
    } else {
#pragma unroll
        for (int g = 0; g < 5; g++) {
            e_ld3(dst + g * 8704, &mp.x6, c0, col + 4 * g + (g < 2 ? wrap : 0), 218, bar + 8 * g);
            e_ld3(dst + g * 8704 + 1536, &mp.x28, c0, col + 4 * g + (g < 2 ? wrap : 0), 0, bar + 8 * g);
        }
    }
}

__device__ __forceinline__ void load_x_box(int cls, int rk, int u, int g, uint32_t sb, const Maps& mp) {
    const int id = u * NH + rk, pl = id / 3, c0 = 32 * (id - 3 * pl), tp = cls * 4 + (pl >> 4), col = 14 * (pl & 15) - 8 + 4 * g;
    e_ld3(sb + u * 51200 + g * 8704, &mp.x34, c0, col < 0 ? col + 224 : col, 28 * tp - 6, sb + BARS + 8 * (B_XF + u * 5 + g));
}

__device__ __forceinline__ void load_first(uint32_t sb, const Maps& mp, const Ptrs& pt) {
    const uint32_t bars = sb + BARS;
    const int k = blockIdx.x;
    if (k < 129) {
        const int cb0 = 14 * k / 25, cb1 = min((14 * k + 13) / 25, 71);
#pragma unroll 1
        for (int cb = cb0; cb <= cb1; cb++) {
            const int b = cb / 24, i0 = 16 * ((cb >> 2) - 6 * b) + 2 * (cb & 3);
            const uint32_t bar = bars + 8 * (B_WF + 2 * (cb - cb0));
            e_expect(bar, 14336);
            e_ld4(sb + WP + (cb - cb0) * 14336, &mp.w, 32 * b, i0, bar);
            e_ld4(sb + WP + (cb - cb0) * 14336 + 7168, &mp.w, 32 * b, i0 + 8, bar);
        }
    }
    asm volatile(ELECT "cp.async.bulk.prefetch.L2.global [%0], 9088;\n}" :: "l"(pt.x + (k & 1) * (112 * 43008) + (k >> 1) * 9088) : "memory");
    e_expect(bars + 8 * B_CF1, 17920); e_g2s(sb + C1, pt.tab1, 17920, bars + 8 * B_CF1);
    if ((threadIdx.x & 31) < 15) asm volatile("mbarrier.arrive.expect_tx.shared::cta.b64 _, [%0], 8704;" :: "r"(bars + 8 * (B_XF + (threadIdx.x & 31))) : "memory");
    __syncwarp();
}

__device__ __forceinline__ uint32_t get_rel(uint32_t sb) {
    mbar_wait(sb + BARS + 8 * B_REL);
    uint32_t v; asm volatile("ld.shared.u32 %0, [%1];" : "=r"(v) : "r"(sb + REL) : "memory");
    return uni(v);
}

__device__ __forceinline__ void load_warp(int cls, int rk, uint32_t sb, const Ptrs& pt) {
    const uint32_t bars = sb + BARS;
    mbar_wait(bars + 8 * (B_SIG + SIG_P1));
    const uint32_t rel = get_rel(sb);
    const char* cnt = cls_cnt(pt.scr, cls);
    const int mE = extra_mask(rk);
    const int lpA = phi_line(3 * rk, rel), lpB = phi_line(3 * rk + 1, rel), lpC = phi_line(3 * rk + 2, rel), lpE = phi_line(extra_phi(rk), rel);
    e_arrive(bars + 8 * (B_TOK - 1));
    if ((threadIdx.x & 31) < 14) asm volatile("mbarrier.arrive.expect_tx.shared::cta.b64 _, [%0], 12288;" :: "r"(bars + 8 * (B_RF + (threadIdx.x & 31))) : "memory");
    __syncwarp();
    int n = 0;
#pragma unroll 1
    for (int pg = 0; pg < 4; pg++) {
        const int l0 = slot_line(0, pg, cls), l1 = slot_line(1, pg, cls), l2 = slot_line(2, pg, cls);
        auto unit = [&](int lp) {
            const uint32_t bar = bars + 8 * (B_RF + n), dst = sb + xslot(n);
            mbar_wait(bars + 8 * (n >= 8 ? B_RE + n - 8 : n >= 4 ? B_SIG + SIG_P1 + (rk < 60 ? 2 : 1) : B_WE + ((0x4310 >> (4 * n)) & 15)));
            e_g2s(dst, pt.scr + (size_t)(lp ^ l0) * 128, 4096, bar);
            e_g2s(dst + 4096, pt.scr + (size_t)(lp ^ l1) * 128, 4096, bar);
            e_g2s(dst + 8192, pt.scr + (size_t)(lp ^ l2) * 128, 4096, bar);
            n++;
        };
        cnt_wait(cnt + (CNT_P1 + pg) * 128, 48);
        unit(lpA); unit(lpB); unit(lpC);
        if (mE >> pg & 1) unit(lpE);
        if (pg == 1) { mbar_wait(bars + 8 * B_P1D); e_expect(bars + 8 * B_CF3, 17152); e_g2s(sb + C3, pt.tab3, 17152, bars + 8 * B_CF3); }
    }
}

__device__ __forceinline__ int near_page(char* p) {
#pragma unroll
    for (int e = 0; e < 4; e++) asm volatile("st.relaxed.gpu.global.v4.u32 [%0], {%1, %1, %1, %1};" :: "l"(p + (e >> 1) * 4096 + (e & 1) * 16), "r"(0) : "memory");
    uint32_t v0, v1, t0, t1;
    asm volatile("atom.relaxed.gpu.global.exch.b32 %0, [%1], 1;" : "=r"(v0) : "l"(p) : "memory");
    asm volatile("atom.relaxed.gpu.global.exch.b32 %0, [%1], 1;" : "=r"(v1) : "l"(p + 4096) : "memory");
    asm volatile("{\n.reg .pred p;\nsetp.ne.u32 p, %1, 0xffffffff;\nmov.u32 %0, 0;\n@p mov.u32 %0, %%clock;\n}" : "=r"(t0) : "r"(v0) : "memory");
    asm volatile("{\n.reg .pred p;\nsetp.ne.u32 p, %1, 0xffffffff;\nmov.u32 %0, 0;\n@p mov.u32 %0, %%clock;\n}" : "=r"(t1) : "r"(v1) : "memory");
    return t1 - t0 < 80;
}

__device__ __forceinline__ uint32_t find_role(uint32_t sb, char* scr) {
    const int k = blockIdx.x;
    int c = near_page(scr + (slot_line(3, 3, 0) + phi_line(1 + (k >> 5), 0) + (k & 31)) * 128);
    int r;
    asm volatile("atom.relaxed.gpu.global.add.u32 %0, [%1], 1;" : "=r"(r) : "l"(cls_cnt(scr, c) + CNT_RANK * 128) : "memory");
    asm volatile("st.shared.u32 [%0], %1;" :: "r"(sb + REL + 8), "r"(c) : "memory");
    if (r >= NH) { c ^= 1; r = NSM - 1 - r; }
    asm volatile("st.shared.u32 [%0], %1;" :: "r"(sb + REL + 4), "r"(c << 8 | r) : "memory");
    return c << 8 | r;
}
__device__ __forceinline__ void get_role(uint32_t sb, int& cls, int& rk) {
    mbar_wait(sb + BARS + 8 * B_ROLE);
    uint32_t v; asm volatile("ld.shared.u32 %0, [%1];" : "=r"(v) : "r"(sb + REL + 4) : "memory");
    v = uni(v); cls = v >> 8; rk = v & 255;
}

__device__ __forceinline__ void load3_warp(int cls, int rk, uint32_t sb, const Maps& mp, const Ptrs& pt) {
    const uint32_t bars = sb + BARS;
    mbar_wait(bars + 8 * B_XF);
    const uint32_t rel = cnt_wait(pt.cnt + CNT_REL * 32, 12u << 16);
    asm volatile("st.shared.u32 [%0], %1;" :: "r"(sb + REL), "r"(rel) : "memory");
    __syncwarp();
    e_arrive(bars + 8 * B_REL);
    mbar_wait(bars + 8 * (B_SIG + SIG_W));
    cnt_wait(cls_cnt(pt.scr, cls) + CNT_W * 128, NSM);
    {
        const int np = rk >= 60 ? 12 : 9;
#pragma unroll 1
        for (int o = 0; o < np; o++) {
            const int pc = (0xba9876524310ull >> (4 * o)) & 15;
            if (o == 4) mbar_wait(bars + 8 * (B_SIG + SIG_P1));
            if (o >= 8) mbar_wait(bars + 8 * (B_WE + ((0x5762 >> (4 * (o - 8))) & 15)));
            if (o >= 4) mbar_wait(bars + 8 * (B_WL + ((0xba9876524310ull >> (4 * (o - 4))) & 15)));
            e_expect(bars + 8 * (B_WL + pc), 12288);
            e_g2s(sb + wslot(pc), pt.wf + (pc < 9 ? 9 * rk + pc : 3 * extra_phi(rk) + pc - 9) * 12288, 12288, bars + 8 * (B_WL + pc));
        }
        if (np == 12) { mbar_wait(bars + 8 * (B_WE + 9)); mbar_wait(bars + 8 * (B_WE + 10)); mbar_wait(bars + 8 * (B_WE + 11)); }
    }
    mbar_wait(bars + 8 * (B_SIG + SIG_P2 + 1));
    const int nu = rk < 60 ? 3 : 2;
#pragma unroll 1
    for (int u = 0; u < nu; u++) {
        const int id = u * NH + rk, pl = id / 3, chunk = id - 3 * pl;
        const int l0 = slot_line(chunk, pl >> 4, cls) + (pl & 15) * 2;
        const uint32_t buf = sb + (u ? 3 - u : 0) * 51200, bar = bars + 8 * (B_YF + u * 5);
#pragma unroll
        for (int j = 0; j < 5; j++) e_expect(bar + 8 * j, j == 4 ? 10240 : (j & 1) ? 8192 : 12288);
        if (u) mbar_wait(bars + 8 * (B_SIG + SIG_P2 + 3));
        cnt_wait(cls_cnt(pt.scr, cls) + (CNT_P2 + (pl >> 4)) * 128, NH);
        if (u == nu - 1) e_arrive(bars + 8 * B_FIN);
        const uint32_t r2 = uni(rel) << 5;
#pragma unroll
        for (int G = 0; G < 13; G++)
            e_ld5(buf + G * 4096, G < 12 ? &mp.f16 : &mp.f8, (l0 ^ ((r2 >> G) & 32)) + (G << 14), bar + 8 * ((2 * G) / 5));
    }
}

__device__ __forceinline__ void store_warp(uint32_t sb, const Maps& mp, const Ptrs& pt) {
    const uint32_t bars = sb + BARS;
    const int k = blockIdx.x;
    uint32_t pa = 0, pb = 0, qa = 0, qb = 0;
    auto arr2 = [&](uint32_t& a, uint32_t& b) { if (a) e_arrive(a); if (b) e_arrive(b); a = b = 0; };
    auto pre = [&](int idx) {
        const uint32_t bar = bars + 8 * idx;
        if ((pb | qb) && !mbar_test(bar)) { bulk_wait<0>(); arr2(qa, qb); arr2(pa, pb); }
        mbar_wait(bar);
    };
    auto post = [&](uint32_t fr) {
        bulk_commit(); bulk_wait_read<2>();
        if (qb) bulk_wait<2>();
        arr2(qa, qb); qa = pa; qb = pb; pb = 0; pa = fr;
    };
    auto after = [&](int sig) { pb = bars + 8 * (B_SIG + sig); };
    int cls, rk; get_role(sb, cls, rk);
    {
        int cb = 14 * k / 25, oc = 14 * k - 25 * cb;
        int g1 = 0;
#pragma unroll 1
        for (int i = 0; i < 14 && cb < 72; i++) {
            pre(B_WRD + i);
            e_st3(&mp.wst, sb + wst_off(i), 0, 8 * oc, cb);
            post(0);
            if (T1MASK >> i & 1) load_x_box(cls, rk, 1, g1++, sb, mp);
            if (++oc == 25) { oc = 0; cb++; }
        }
#pragma unroll 1
        for (; g1 < 5; g1++) load_x_box(cls, rk, 1, g1, sb, mp);
        after(SIG_W);
    }
    pre(B_REL);
    const uint32_t rel = get_rel(sb);
    const int nu = rk < 60 ? 3 : 2;
    int g2 = 0;
#pragma unroll 1
    for (int u = 0; u < nu; u++) {
        const int id = u * NH + rk, pl = id / 3, chunk = id - 3 * pl;
        const int l0 = slot_line(chunk, pl >> 4, cls) + (pl & 15) * 2;
        int j = B_RDY + u * 5;
        const int m2 = nu == 3 ? (u == 0 ? T2MASK & 0x1fff : u == 1 ? T2MASK >> 13 : 0) : 0;
#pragma unroll 1
        for (int G = 0; G < 13; G++) {
            if (0x4a5 >> G & 1) pre(j++);
            e_st5(G < 12 ? &mp.f16 : &mp.f8, sb + u * 51200 + G * 4096, (l0 ^ ((rel >> G) & 1) << 5) + (G << 14));
            post(0);
            if (m2 >> G & 1) load_x_box(cls, rk, 2, g2++, sb, mp);
        }
        after(SIG_P1 + u);
    }
    const int mE = extra_mask(rk);
    int n = 0;
#pragma unroll 1
    for (int pg = 0; pg < 4; pg++) {
        const int nj = 3 + (mE >> pg & 1);
        const int l0 = slot_line(0, pg, cls), l1 = slot_line(1, pg, cls), l2 = slot_line(2, pg, cls);
#pragma unroll 1
        for (int j = 0; j < nj; j++) {
            const int lp = phi_line(j == 3 ? extra_phi(rk) : 3 * rk + j, rel);
#pragma unroll
            for (int b = 0; b < 3; b++) {
                pre(B_RDY + R_P2 + n * 3 + b);
                e_s2g(pt.scr + (size_t)(lp ^ (b == 0 ? l0 : b == 1 ? l1 : l2)) * 128, sb + S1 + (n & 3) * 12288 + b * 4096, 4096);
                post(bars + 8 * (B_SFREE + n * 3 + b));
            }
            n++;
        }
        after(SIG_P2 + pg);
    }
#pragma unroll 1
    for (int u = 0; u < nu; u++) {
        const int id = u * NH + rk, pl = id / 3, chunk = id - 3 * pl, tp = cls * 4 + (pl >> 4), tx = pl & 15;
        const uint32_t buf = sb + (u ? 3 - u : 0) * 51200;
#pragma unroll
        for (int gg = 1; gg < 5; gg++) {
            pre(B_RDY + R_P3 + u * 4 + gg - 1);
            if (gg < 4) e_st3(&mp.y4, buf + gg * 7168, 32 * chunk, 14 * tx - 4 + 4 * gg, 28 * tp);
            else e_st3(&mp.y2, buf, 32 * chunk, tx == 0 ? 222 : 14 * tx - 2, 28 * tp);
            post(0);
        }
    }
    bulk_wait_read<0>();
}

__device__ __forceinline__ void signal_warp(int cls, int rk, uint32_t sb, const Ptrs& pt) {
    const uint32_t bars = sb + BARS;
    char* cnt = cls_cnt(pt.scr, cls);
    if (threadIdx.x & 31) return;
#pragma unroll 1
    for (int c = 0; c < 8; c++) {
        if (c == SIG_P1 + 2 && rk >= 60) continue;
        char* ctr = cnt + (c == SIG_W ? CNT_W : c < SIG_P2 ? CNT_P1 + ((c - SIG_P1) * NH + rk) / 48 : CNT_P2 + c - SIG_P2) * 128;
        mbar_wait(bars + 8 * (B_SIG + c));
        fence_async();
        asm volatile("red.relaxed.gpu.global.add.u32 [%0], 1;" :: "l"(ctr) : "memory");
        if (c == SIG_W) asm volatile("red.relaxed.gpu.global.add.u32 [%0], 1;" :: "l"((uintptr_t)ctr ^ 4096) : "memory");
    }
    mbar_wait(bars + 8 * B_FIN);
    unsigned old;
    asm volatile("atom.add.relaxed.gpu.global.u32 %0, [%1], 1;" : "=r"(old) : "l"(pt.cnt + CNT_DONE * 32) : "memory");
    if (old == NSM - 1) {
#pragma unroll
        for (int c = 0; c < NCNT; c++) pt.cnt[c * 32] = 0;
#pragma unroll 1
        for (int c = 0; c < NCLS; c++) { *reinterpret_cast<unsigned*>(cnt + c * 128) = 0; *reinterpret_cast<unsigned*>(((uintptr_t)cnt ^ 4096) + c * 128) = 0; }
    }
}

__global__ void __launch_bounds__(512, 1) fftconv_kernel(const Ptrs pt, const __grid_constant__ Maps mp) {
    extern __shared__ __align__(1024) uint8_t smem[];
    const uint32_t sb = smem_u32(smem);
    const int tid = threadIdx.x, warp = uni(tid >> 5), wg = warp >> 2;
    int cls, rk;
    auto bar_init = [&](int i) {
        uint32_t c = 1;
        if (i == B_P1D || (i >= B_RE && i < B_RE + 14)) c = 12;
        else if ((i >= B_WCH && i < B_WL) || i >= B_TOK) c = 4;
        asm volatile("st.shared.v2.u32 [%0], {%1, %2};" :: "r"(sb + BARS + 8 * i), "r"((0x100000u - c) << 1), "r"((0x100000u - c) << 11) : "memory");
        fence_async_smem();
    };
    if (wg == 3) {
        asm volatile("setmaxnreg.dec.sync.aligned.u32 32;");
        if (warp == 12) {
            bar_init(tid & 31);
            __syncwarp();
            asm volatile("bar.arrive 4, 416;" ::: "memory");
            load_first(sb, mp, pt);
            asm volatile("bar.sync 5, 416;" ::: "memory");
            get_role(sb, cls, rk);
            load_warp(cls, rk, sb, pt);
        } else if (warp == 13) {
            if ((tid & 31) < 8) asm volatile("prefetch.tensormap [%0];" :: "l"(reinterpret_cast<const CUtensorMap*>(&mp) + 1 + (tid & 31)) : "memory");
            __syncwarp();
            asm volatile("bar.sync 6, 416;" ::: "memory");
            store_warp(sb, mp, pt);
        } else if (warp == 14) {
            const int G = blockIdx.x - 119;
            int sel = 0;
            if (G >= 1 && (tid & 31) == 0) sel = near_page(pt.scr + ((size_t)G << 21) + slot_line(3, 3, 0) * 128);
            __syncwarp();
            asm volatile("bar.sync 7, 416;" ::: "memory");
            get_role(sb, cls, rk);
            if (G >= 1 && (tid & 31) == 0) {
                uint32_t c; asm volatile("ld.shared.u32 %0, [%1];" : "=r"(c) : "r"(sb + REL + 8) : "memory");
                asm volatile("red.relaxed.gpu.global.add.u32 [%0], %1;" :: "l"(pt.cnt + CNT_REL * 32), "r"(0x10000u | (sel ^ c) << G) : "memory");
            }
            __syncwarp();
            load3_warp(cls, rk, sb, mp, pt);
        } else {
            uint32_t role = 0;
            if ((tid & 31) == 0) role = find_role(sb, pt.scr);
            role = uni(role); cls = role >> 8; rk = role & 255;
            asm volatile("bar.sync 8, 416;" ::: "memory");
            load_x(cls, rk, 0, sb, mp);
            e_arrive(sb + BARS + 8 * B_ROLE);
            signal_warp(cls, rk, sb, pt);
        }
    } else {
        if (tid >= 32 && tid < NBAR) bar_init(tid);
        {
            const int r = tid % 40;
            asm volatile("st.shared.u32 [%0], %1;" :: "r"(sb + TBL + 4 * tid), "r"(cos_bits(r) | (cos_bits(r < 30 ? r + 10 : r - 30) << 16)) : "memory");
        }
        __syncwarp();
        asm volatile("bar.sync 4, 416;" ::: "memory");
        asm volatile("bar.arrive 5, 416;" ::: "memory");
        asm volatile("bar.arrive 6, 416;" ::: "memory");
        asm volatile("bar.arrive 7, 416;" ::: "memory");
        asm volatile("bar.arrive 8, 416;" ::: "memory");
        task_w(wg, blockIdx.x, sb);
        asm volatile("setmaxnreg.inc.sync.aligned.u32 160;");
        get_role(sb, cls, rk);
        const int id = wg * NH + rk;
        if (id < 192) task_p1(wg, id / 3, sb);
        e_arrive(sb + BARS + 8 * B_P1D);
        task_p2(wg, rk, sb);
        if (id < 192) task_p3(wg, id / 3, sb);
    }
}

__global__ void fallback_kernel(const __nv_bfloat16* x, const __nv_bfloat16* w, __nv_bfloat16* y) {
    const int px = blockIdx.x, o = threadIdx.x, h = px / 224, c = px % 224;
    float acc = 0.f;
    for (int kh = 0; kh < 7; kh++)
        for (int kw = 0; kw < 7; kw++) {
            const __nv_bfloat16* xp = x + (((h - kh + 224) % 224) * 224 + (c - kw + 224) % 224) * 96;
            const __nv_bfloat16* wp = w + (kh * 7 + kw) * 9216 + o;
            for (int i = 0; i < 96; i++) acc += __bfloat162float(xp[i]) * __bfloat162float(wp[i * 96]);
        }
    y[px * 96 + o] = __float2bfloat16(acc);
}

typedef CUresult (*EncodeFn)(CUtensorMap*, CUtensorMapDataType, cuuint32_t, void*, const cuuint64_t*, const cuuint64_t*, const cuuint32_t*, const cuuint32_t*,
                             CUtensorMapInterleave, CUtensorMapSwizzle, CUtensorMapL2promotion, CUtensorMapFloatOOBfill);

static void encode3(EncodeFn fn, CUtensorMap* m, void* ptr, uint64_t d0, uint64_t d1, uint64_t d2, uint64_t s1, uint64_t s2,
                    uint32_t b0, uint32_t b1, uint32_t b2, CUtensorMapSwizzle sw) {
    cuuint64_t dims[3] = {d0, d1, d2}, strides[2] = {s1, s2};
    cuuint32_t box[3] = {b0, b1, b2}, es[3] = {1, 1, 1};
    fn(m, CU_TENSOR_MAP_DATA_TYPE_BFLOAT16, 3, ptr, dims, strides, box, es, CU_TENSOR_MAP_INTERLEAVE_NONE, sw,
       CU_TENSOR_MAP_L2_PROMOTION_NONE, CU_TENSOR_MAP_FLOAT_OOB_FILL_NONE);
}

extern "C" void kernel_launch(void* const* d_in, const int* in_sizes, int n_in, void* d_out, int out_size) {
    (void)in_sizes; (void)n_in; (void)out_size;
    int dev = 0, nsm = 0;
    cudaGetDevice(&dev);
    cudaDeviceGetAttribute(&nsm, cudaDevAttrMultiProcessorCount, dev);
    if (nsm < NSM) {
        fallback_kernel<<<224 * 224, 96>>>((const __nv_bfloat16*)d_in[0], (const __nv_bfloat16*)d_in[1], (__nv_bfloat16*)d_out);
        return;
    }
    void* fnp = nullptr; cudaDriverEntryPointQueryResult qr;
    cudaGetDriverEntryPoint("cuTensorMapEncodeTiled", &fnp, cudaEnableDefault, &qr);
    EncodeFn fn = (EncodeFn)fnp;
    void* xf = nullptr; cudaGetSymbolAddress(&xf, g_scr);
    xf = (void*)(((uintptr_t)xf + (1u << 21) - 1) & ~(uintptr_t)((1u << 21) - 1));
    void* wf = nullptr; cudaGetSymbolAddress(&wf, g_wf);
    Maps mp;
    Ptrs pt;
    pt.scr = (char*)xf; pt.wf = (const char*)wf; pt.x = (const char*)d_in[0];
    void* p = nullptr;
    cudaGetSymbolAddress(&p, TAB_P1); pt.tab1 = p;
    cudaGetSymbolAddress(&p, TAB_P3); pt.tab3 = p;
    cudaGetSymbolAddress(&p, g_cnt); pt.cnt = (unsigned*)p;
    {
        cuuint32_t b16[5] = {64, 4, 2, 2, 2}, b8[5] = {64, 4, 2, 1, 2}, es[5] = {1, 1, 1, 1, 1};
        cuuint64_t d[5] = {64, 4, 2, 2, 13 << 14}, st[4] = {16384, 262144, 1048576, 128};
        fn(&mp.f16, CU_TENSOR_MAP_DATA_TYPE_BFLOAT16, 5, xf, d, st, b16, es, CU_TENSOR_MAP_INTERLEAVE_NONE, CU_TENSOR_MAP_SWIZZLE_NONE, CU_TENSOR_MAP_L2_PROMOTION_NONE, CU_TENSOR_MAP_FLOAT_OOB_FILL_NONE);
        fn(&mp.f8, CU_TENSOR_MAP_DATA_TYPE_BFLOAT16, 5, xf, d, st, b8, es, CU_TENSOR_MAP_INTERLEAVE_NONE, CU_TENSOR_MAP_SWIZZLE_NONE, CU_TENSOR_MAP_L2_PROMOTION_NONE, CU_TENSOR_MAP_FLOAT_OOB_FILL_NONE);
    }
    encode3(fn, &mp.x6, d_in[0], 96, 224, 224, 192, 224 * 192, 32, 4, 6, CU_TENSOR_MAP_SWIZZLE_64B);
    encode3(fn, &mp.x34, d_in[0], 96, 224, 224, 192, 224 * 192, 32, 4, 34, CU_TENSOR_MAP_SWIZZLE_64B);
    encode3(fn, &mp.x28, d_in[0], 96, 224, 224, 192, 224 * 192, 32, 4, 28, CU_TENSOR_MAP_SWIZZLE_64B);
    {
        cuuint32_t box[4] = {32, 8, 7, 2}, es[4] = {1, 1, 1, 1};
        cuuint64_t d[4] = {96, 7, 7, 96}, st[3] = {18432, 7 * 18432, 192};
        fn(&mp.w, CU_TENSOR_MAP_DATA_TYPE_BFLOAT16, 4, d_in[1], d, st, box, es, CU_TENSOR_MAP_INTERLEAVE_NONE, CU_TENSOR_MAP_SWIZZLE_64B, CU_TENSOR_MAP_L2_PROMOTION_NONE, CU_TENSOR_MAP_FLOAT_OOB_FILL_NONE);
    }
    encode3(fn, &mp.wst, wf, 256, 200, 72, 36864, 512, 256, 8, 1, CU_TENSOR_MAP_SWIZZLE_NONE);
    encode3(fn, &mp.y4, d_out, 96, 224, 224, 192, 224 * 192, 32, 4, 28, CU_TENSOR_MAP_SWIZZLE_64B);
    encode3(fn, &mp.y2, d_out, 96, 224, 224, 192, 224 * 192, 32, 2, 28, CU_TENSOR_MAP_SWIZZLE_64B);
    constexpr int SMEM_LAUNCH = SMEM_BYTES;
    cudaFuncSetAttribute(fftconv_kernel, cudaFuncAttributeMaxDynamicSharedMemorySize, SMEM_LAUNCH);
    fftconv_kernel<<<NSM, 512, SMEM_LAUNCH>>>(pt, mp);
}
```

```cpp
#include <cuda_runtime.h>
#include <cuda_bf16.h>
#include <cuda.h>
#include <stdint.h>

__device__ __align__(128) const uint32_t TAB_P1[4480] = {
0x3e75,0,0x3e72,0,0x8000,0,0xbd19,0,0x3e750000,0,0x3e720000,0,0x80000000,0,0xbd190000,0,
0,0x3e75,0,0x3e72,0,0x8000,0,0xbd19,0,0x3e750000,0,0x3e720000,0,0x80000000,0,0xbd190000,
0x3e69,0,0x3e5a,0,0xbd97,0,0xbdde,0,0x3e690000,0,0x3e5a0000,0,0xbd970000,0,0xbdde0000,0,
0,0x3e69,0,0x3e5a,0,0xbd97,0,0xbdde,0,0x3e690000,0,0x3e5a0000,0,0xbd970000,0,0xbdde0000,
0x3e75,0,0x3e5a,0,0x8000,0,0xbdde,0,0x3e750000,0,0x3e5a0000,0,0x80000000,0,0xbdde0000,0,
0,0x3e75,0,0x3e5a,0,0x8000,0,0xbdde,0,0x3e750000,0,0x3e5a0000,0,0x80000000,0,0xbdde0000,
0x3e10,0,0x3d19,0,0xbe46,0,0xbe72,0,0x3e100000,0,0x3d190000,0,0xbe460000,0,0xbe720000,0,
0,0x3e10,0,0x3d19,0,0xbe46,0,0xbe72,0,0x3e100000,0,0x3d190000,0,0xbe460000,0,0xbe720000,
0x3e75,0,0x3e2d,0,0x8000,0,0xbe2d,0,0x3e750000,0,0x3e2d0000,0,0x80000000,0,0xbe2d0000,0,
0,0x3e75,0,0x3e2d,0,0x8000,0,0xbe2d,0,0x3e750000,0,0x3e2d0000,0,0x80000000,0,0xbe2d0000,
0,0,0xbe2d,0,0xbe75,0,0xbe2d,0,0,0,0xbe2d0000,0,0xbe750000,0,0xbe2d0000,0,
0,0,0,0xbe2d,0,0xbe75,0,0xbe2d,0,0,0,0xbe2d0000,0,0xbe750000,0,0xbe2d0000,
0x3e75,0,0x3dde,0,0x8000,0,0xbe5a,0,0x3e750000,0,0x3dde0000,0,0x80000000,0,0xbe5a0000,0,
0,0x3e75,0,0x3dde,0,0x8000,0,0xbe5a,0,0x3e750000,0,0x3dde0000,0,0x80000000,0,0xbe5a0000,
0xbe10,0,0xbe72,0,0xbe46,0,0x3d19,0,0xbe100000,0,0xbe720000,0,0xbe460000,0,0x3d190000,0,
0,0xbe10,0,0xbe72,0,0xbe46,0,0x3d19,0,0xbe100000,0,0xbe720000,0,0xbe460000,0,0x3d190000,
0x3e75,0,0x3d19,0,0x8000,0,0xbe72,0,0x3e750000,0,0x3d190000,0,0x80000000,0,0xbe720000,0,
0,0x3e75,0,0x3d19,0,0x8000,0,0xbe72,0,0x3e750000,0,0x3d190000,0,0x80000000,0,0xbe720000,
0xbe69,0,0xbdde,0,0xbd97,0,0x3e5a,0,0xbe690000,0,0xbdde0000,0,0xbd970000,0,0x3e5a0000,0,
0,0xbe69,0,0xbdde,0,0xbd97,0,0x3e5a,0,0xbe690000,0,0xbdde0000,0,0xbd970000,0,0x3e5a0000,
0x3e75,0,0xbd19,0,0x8000,0,0xbe72,0,0x3e750000,0,0xbd190000,0,0x80000000,0,0xbe720000,0,
0,0x3e75,0,0xbd19,0,0x8000,0,0xbe72,0,0x3e750000,0,0xbd190000,0,0x80000000,0,0xbe720000,
0xbe69,0,0x3dde,0,0x3d97,0,0x3e5a,0,0xbe690000,0,0x3dde0000,0,0x3d970000,0,0x3e5a0000,0,
0,0xbe69,0,0x3dde,0,0x3d97,0,0x3e5a,0,0xbe690000,0,0x3dde0000,0,0x3d970000,0,0x3e5a0000,
0x3e75,0,0xbdde,0,0x8000,0,0xbe5a,0,0x3e750000,0,0xbdde0000,0,0x80000000,0,0xbe5a0000,0,
0,0x3e75,0,0xbdde,0,0x8000,0,0xbe5a,0,0x3e750000,0,0xbdde0000,0,0x80000000,0,0xbe5a0000,
0xbe10,0,0x3e72,0,0x3e46,0,0x3d19,0,0xbe100000,0,0x3e720000,0,0x3e460000,0,0x3d190000,0,
0,0xbe10,0,0x3e72,0,0x3e46,0,0x3d19,0,0xbe100000,0,0x3e720000,0,0x3e460000,0,0x3d190000,
0x3e75,0,0xbe2d,0,0x8000,0,0xbe2d,0,0x3e750000,0,0xbe2d0000,0,0x80000000,0,0xbe2d0000,0,
0,0x3e75,0,0xbe2d,0,0x8000,0,0xbe2d,0,0x3e750000,0,0xbe2d0000,0,0x80000000,0,0xbe2d0000,
0,0,0x3e2d,0,0x3e75,0,0xbe2d,0,0,0,0x3e2d0000,0,0x3e750000,0,0xbe2d0000,0,
0,0,0,0x3e2d,0,0x3e75,0,0xbe2d,0,0,0,0x3e2d0000,0,0x3e750000,0,0xbe2d0000,
0x3e75,0,0xbe5a,0,0x8000,0,0xbdde,0,0x3e750000,0,0xbe5a0000,0,0x80000000,0,0xbdde0000,0,
0,0x3e75,0,0xbe5a,0,0x8000,0,0xbdde,0,0x3e750000,0,0xbe5a0000,0,0x80000000,0,0xbdde0000,
0x3e10,0,0xbd19,0,0x3e46,0,0xbe72,0,0x3e100000,0,0xbd190000,0,0x3e460000,0,0xbe720000,0,
0,0x3e10,0,0xbd19,0,0x3e46,0,0xbe72,0,0x3e100000,0,0xbd190000,0,0x3e460000,0,0xbe720000,
0x3e75,0,0xbe72,0,0x8000,0,0xbd19,0,0x3e750000,0,0xbe720000,0,0x80000000,0,0xbd190000,0,
0,0x3e75,0,0xbe72,0,0x8000,0,0xbd19,0,0x3e750000,0,0xbe720000,0,0x80000000,0,0xbd190000,
0x3e69,0,0xbe5a,0,0x3d97,0,0xbdde,0,0x3e690000,0,0xbe5a0000,0,0x3d970000,0,0xbdde0000,0,
0,0x3e69,0,0xbe5a,0,0x3d97,0,0xbdde,0,0x3e690000,0,0xbe5a0000,0,0x3d970000,0,0xbdde0000,
0x3e46,0,0x3e2d,0,0xbe10,0,0xbe2d,0,0x3e460000,0,0x3e2d0000,0,0xbe100000,0,0xbe2d0000,0,
0,0x3e46,0,0x3e2d,0,0xbe10,0,0xbe2d,0,0x3e460000,0,0x3e2d0000,0,0xbe100000,0,0xbe2d0000,
0x3e10,0,0x3dde,0,0xbe46,0,0xbe5a,0,0x3e100000,0,0x3dde0000,0,0xbe460000,0,0xbe5a0000,0,
0,0x3e10,0,0x3dde,0,0xbe46,0,0xbe5a,0,0x3e100000,0,0x3dde0000,0,0xbe460000,0,0xbe5a0000,
0xbd97,0,0xbe2d,0,0xbe69,0,0xbe2d,0,0xbd970000,0,0xbe2d0000,0,0xbe690000,0,0xbe2d0000,0,
0,0xbd97,0,0xbe2d,0,0xbe69,0,0xbe2d,0,0xbd970000,0,0xbe2d0000,0,0xbe690000,0,0xbe2d0000,
0xbe69,0,0xbe72,0,0xbd97,0,0x3d19,0,0xbe690000,0,0xbe720000,0,0xbd970000,0,0x3d190000,0,
0,0xbe69,0,0xbe72,0,0xbd97,0,0x3d19,0,0xbe690000,0,0xbe720000,0,0xbd970000,0,0x3d190000,
0xbe75,0,0xbe2d,0,0x8000,0,0x3e2d,0,0xbe750000,0,0xbe2d0000,0,0x80000000,0,0x3e2d0000,0,
0,0xbe75,0,0xbe2d,0,0x8000,0,0x3e2d,0,0xbe750000,0,0xbe2d0000,0,0x80000000,0,0x3e2d0000,
0,0,0x3e2d,0,0x3e75,0,0x3e2d,0,0,0,0x3e2d0000,0,0x3e750000,0,0x3e2d0000,0,
0,0,0,0x3e2d,0,0x3e75,0,0x3e2d,0,0,0,0x3e2d0000,0,0x3e750000,0,0x3e2d0000,
0xbd97,0,0x3e2d,0,0x3e69,0,0x3e2d,0,0xbd970000,0,0x3e2d0000,0,0x3e690000,0,0x3e2d0000,0,
0,0xbd97,0,0x3e2d,0,0x3e69,0,0x3e2d,0,0xbd970000,0,0x3e2d0000,0,0x3e690000,0,0x3e2d0000,
0x3e69,0,0x3d19,0,0xbd97,0,0xbe72,0,0x3e690000,0,0x3d190000,0,0xbd970000,0,0xbe720000,0,
0,0x3e69,0,0x3d19,0,0xbd97,0,0xbe72,0,0x3e690000,0,0x3d190000,0,0xbd970000,0,0xbe720000,
0x3e46,0,0x3e2d,0,0x3e10,0,0xbe2d,0,0x3e460000,0,0x3e2d0000,0,0x3e100000,0,0xbe2d0000,0,
0,0x3e46,0,0x3e2d,0,0x3e10,0,0xbe2d,0,0x3e460000,0,0x3e2d0000,0,0x3e100000,0,0xbe2d0000,
0xbe10,0,0xbe5a,0,0xbe46,0,0x3dde,0,0xbe100000,0,0xbe5a0000,0,0xbe460000,0,0x3dde0000,0,
0,0xbe10,0,0xbe5a,0,0xbe46,0,0x3dde,0,0xbe100000,0,0xbe5a0000,0,0xbe460000,0,0x3dde0000,
0x3e46,0,0xbe2d,0,0xbe10,0,0xbe2d,0,0x3e460000,0,0xbe2d0000,0,0xbe100000,0,0xbe2d0000,0,
0,0x3e46,0,0xbe2d,0,0xbe10,0,0xbe2d,0,0x3e460000,0,0xbe2d0000,0,0xbe100000,0,0xbe2d0000,
0xbe10,0,0x3e5a,0,0x3e46,0,0x3dde,0,0xbe100000,0,0x3e5a0000,0,0x3e460000,0,0x3dde0000,0,
0,0xbe10,0,0x3e5a,0,0x3e46,0,0x3dde,0,0xbe100000,0,0x3e5a0000,0,0x3e460000,0,0x3dde0000,
0xbd97,0,0xbe2d,0,0xbe69,0,0x3e2d,0,0xbd970000,0,0xbe2d0000,0,0xbe690000,0,0x3e2d0000,0,
0,0xbd97,0,0xbe2d,0,0xbe69,0,0x3e2d,0,0xbd970000,0,0xbe2d0000,0,0xbe690000,0,0x3e2d0000,
0x3e69,0,0xbd19,0,0x3d97,0,0xbe72,0,0x3e690000,0,0xbd190000,0,0x3d970000,0,0xbe720000,0,
0,0x3e69,0,0xbd19,0,0x3d97,0,0xbe72,0,0x3e690000,0,0xbd190000,0,0x3d970000,0,0xbe720000,
0xbe75,0,0x3e2d,0,0x8000,0,0x3e2d,0,0xbe750000,0,0x3e2d0000,0,0x80000000,0,0x3e2d0000,0,
0,0xbe75,0,0x3e2d,0,0x8000,0,0x3e2d,0,0xbe750000,0,0x3e2d0000,0,0x80000000,0,0x3e2d0000,
0,0,0xbe2d,0,0xbe75,0,0x3e2d,0,0,0,0xbe2d0000,0,0xbe750000,0,0x3e2d0000,0,
0,0,0,0xbe2d,0,0xbe75,0,0x3e2d,0,0,0,0xbe2d0000,0,0xbe750000,0,0x3e2d0000,
0xbd97,0,0x3e2d,0,0x3e69,0,0xbe2d,0,0xbd970000,0,0x3e2d0000,0,0x3e690000,0,0xbe2d0000,0,
0,0xbd97,0,0x3e2d,0,0x3e69,0,0xbe2d,0,0xbd970000,0,0x3e2d0000,0,0x3e690000,0,0xbe2d0000,
0xbe69,0,0x3e72,0,0x3d97,0,0x3d19,0,0xbe690000,0,0x3e720000,0,0x3d970000,0,0x3d190000,0,
0,0xbe69,0,0x3e72,0,0x3d97,0,0x3d19,0,0xbe690000,0,0x3e720000,0,0x3d970000,0,0x3d190000,
0x3e46,0,0xbe2d,0,0x3e10,0,0xbe2d,0,0x3e460000,0,0xbe2d0000,0,0x3e100000,0,0xbe2d0000,0,
0,0x3e46,0,0xbe2d,0,0x3e10,0,0xbe2d,0,0x3e460000,0,0xbe2d0000,0,0x3e100000,0,0xbe2d0000,
0x3e10,0,0xbdde,0,0x3e46,0,0xbe5a,0,0x3e100000,0,0xbdde0000,0,0x3e460000,0,0xbe5a0000,0,
0,0x3e10,0,0xbdde,0,0x3e46,0,0xbe5a,0,0x3e100000,0,0xbdde0000,0,0x3e460000,0,0xbe5a0000,
0x3d97,0,0x3d19,0,0xbe69,0,0xbe72,0,0x3d970000,0,0x3d190000,0,0xbe690000,0,0xbe720000,0,
0,0x3d97,0,0x3d19,0,0xbe69,0,0xbe72,0,0x3d970000,0,0x3d190000,0,0xbe690000,0,0xbe720000,
0,0,0xbd19,0,0xbe75,0,0xbe72,0,0,0,0xbd190000,0,0xbe750000,0,0xbe720000,0,
0,0,0,0xbd19,0,0xbe75,0,0xbe72,0,0,0,0xbd190000,0,0xbe750000,0,0xbe720000,
0xbe46,0,0xbdde,0,0x3e10,0,0x3e5a,0,0xbe460000,0,0xbdde0000,0,0x3e100000,0,0x3e5a0000,0,
0,0xbe46,0,0xbdde,0,0x3e10,0,0x3e5a,0,0xbe460000,0,0xbdde0000,0,0x3e100000,0,0x3e5a0000,
0,0,0x3dde,0,0x3e75,0,0x3e5a,0,0,0,0x3dde0000,0,0x3e750000,0,0x3e5a0000,0,
0,0,0,0x3dde,0,0x3e75,0,0x3e5a,0,0,0,0x3dde0000,0,0x3e750000,0,0x3e5a0000,
0x3e75,0,0x3e2d,0,0x8000,0,0xbe2d,0,0x3e750000,0,0x3e2d0000,0,0x80000000,0,0xbe2d0000,0,
0,0x3e75,0,0x3e2d,0,0x8000,0,0xbe2d,0,0x3e750000,0,0x3e2d0000,0,0x80000000,0,0xbe2d0000,
0,0,0xbe2d,0,0xbe75,0,0xbe2d,0,0,0,0xbe2d0000,0,0xbe750000,0,0xbe2d0000,0,
0,0,0,0xbe2d,0,0xbe75,0,0xbe2d,0,0,0,0xbe2d0000,0,0xbe750000,0,0xbe2d0000,
0xbe46,0,0xbe5a,0,0xbe10,0,0x3dde,0,0xbe460000,0,0xbe5a0000,0,0xbe100000,0,0x3dde0000,0,
0,0xbe46,0,0xbe5a,0,0xbe10,0,0x3dde,0,0xbe460000,0,0xbe5a0000,0,0xbe100000,0,0x3dde0000,
0,0,0x3e5a,0,0x3e75,0,0x3dde,0,0,0,0x3e5a0000,0,0x3e750000,0,0x3dde0000,0,
0,0,0,0x3e5a,0,0x3e75,0,0x3dde,0,0,0,0x3e5a0000,0,0x3e750000,0,0x3dde0000,
0x3d97,0,0x3e72,0,0x3e69,0,0xbd19,0,0x3d970000,0,0x3e720000,0,0x3e690000,0,0xbd190000,0,
0,0x3d97,0,0x3e72,0,0x3e69,0,0xbd19,0,0x3d970000,0,0x3e720000,0,0x3e690000,0,0xbd190000,
0,0,0xbe72,0,0xbe75,0,0xbd19,0,0,0,0xbe720000,0,0xbe750000,0,0xbd190000,0,
0,0,0,0xbe72,0,0xbe75,0,0xbd19,0,0,0,0xbe720000,0,0xbe750000,0,0xbd190000,
0x3d97,0,0xbe72,0,0xbe69,0,0xbd19,0,0x3d970000,0,0xbe720000,0,0xbe690000,0,0xbd190000,0,
0,0x3d97,0,0xbe72,0,0xbe69,0,0xbd19,0,0x3d970000,0,0xbe720000,0,0xbe690000,0,0xbd190000,
0,0,0x3e72,0,0x3e75,0,0xbd19,0,0,0,0x3e720000,0,0x3e750000,0,0xbd190000,0,
0,0,0,0x3e72,0,0x3e75,0,0xbd19,0,0,0,0x3e720000,0,0x3e750000,0,0xbd190000,
0xbe46,0,0x3e5a,0,0x3e10,0,0x3dde,0,0xbe460000,0,0x3e5a0000,0,0x3e100000,0,0x3dde0000,0,
0,0xbe46,0,0x3e5a,0,0x3e10,0,0x3dde,0,0xbe460000,0,0x3e5a0000,0,0x3e100000,0,0x3dde0000,
0,0,0xbe5a,0,0xbe75,0,0x3dde,0,0,0,0xbe5a0000,0,0xbe750000,0,0x3dde0000,0,
0,0,0,0xbe5a,0,0xbe75,0,0x3dde,0,0,0,0xbe5a0000,0,0xbe750000,0,0x3dde0000,
0x3e75,0,0xbe2d,0,0x8000,0,0xbe2d,0,0x3e750000,0,0xbe2d0000,0,0x80000000,0,0xbe2d0000,0,
0,0x3e75,0,0xbe2d,0,0x8000,0,0xbe2d,0,0x3e750000,0,0xbe2d0000,0,0x80000000,0,0xbe2d0000,
0,0,0x3e2d,0,0x3e75,0,0xbe2d,0,0,0,0x3e2d0000,0,0x3e750000,0,0xbe2d0000,0,
0,0,0,0x3e2d,0,0x3e75,0,0xbe2d,0,0,0,0x3e2d0000,0,0x3e750000,0,0xbe2d0000,
0xbe46,0,0x3dde,0,0xbe10,0,0x3e5a,0,0xbe460000,0,0x3dde0000,0,0xbe100000,0,0x3e5a0000,0,
0,0xbe46,0,0x3dde,0,0xbe10,0,0x3e5a,0,0xbe460000,0,0x3dde0000,0,0xbe100000,0,0x3e5a0000,
0,0,0xbdde,0,0xbe75,0,0x3e5a,0,0,0,0xbdde0000,0,0xbe750000,0,0x3e5a0000,0,
0,0,0,0xbdde,0,0xbe75,0,0x3e5a,0,0,0,0xbdde0000,0,0xbe750000,0,0x3e5a0000,
0x3d97,0,0xbd19,0,0x3e69,0,0xbe72,0,0x3d970000,0,0xbd190000,0,0x3e690000,0,0xbe720000,0,
0,0x3d97,0,0xbd19,0,0x3e69,0,0xbe72,0,0x3d970000,0,0xbd190000,0,0x3e690000,0,0xbe720000,
0,0,0x3d19,0,0x3e75,0,0xbe72,0,0,0,0x3d190000,0,0x3e750000,0,0xbe720000,0,
0,0,0,0x3d19,0,0x3e75,0,0xbe72,0,0,0,0x3d190000,0,0x3e750000,0,0xbe720000,
0xbd97,0,0xbdde,0,0xbe69,0,0xbe5a,0,0xbd970000,0,0xbdde0000,0,0xbe690000,0,0xbe5a0000,0,
0,0xbd97,0,0xbdde,0,0xbe69,0,0xbe5a,0,0xbd970000,0,0xbdde0000,0,0xbe690000,0,0xbe5a0000,
0xbe10,0,0xbe2d,0,0xbe46,0,0xbe2d,0,0xbe100000,0,0xbe2d0000,0,0xbe460000,0,0xbe2d0000,0,
0,0xbe10,0,0xbe2d,0,0xbe46,0,0xbe2d,0,0xbe100000,0,0xbe2d0000,0,0xbe460000,0,0xbe2d0000,
0x3e46,0,0x3e72,0,0x3e10,0,0x3d19,0,0x3e460000,0,0x3e720000,0,0x3e100000,0,0x3d190000,0,
0,0x3e46,0,0x3e72,0,0x3e10,0,0x3d19,0,0x3e460000,0,0x3e720000,0,0x3e100000,0,0x3d190000,
0x3e69,0,0x3e2d,0,0xbd97,0,0xbe2d,0,0x3e690000,0,0x3e2d0000,0,0xbd970000,0,0xbe2d0000,0,
0,0x3e69,0,0x3e2d,0,0xbd97,0,0xbe2d,0,0x3e690000,0,0x3e2d0000,0,0xbd970000,0,0xbe2d0000,
0xbe75,0,0xbe2d,0,0x8000,0,0x3e2d,0,0xbe750000,0,0xbe2d0000,0,0x80000000,0,0x3e2d0000,0,
0,0xbe75,0,0xbe2d,0,0x8000,0,0x3e2d,0,0xbe750000,0,0xbe2d0000,0,0x80000000,0,0x3e2d0000,
0,0,0x3e2d,0,0x3e75,0,0x3e2d,0,0,0,0x3e2d0000,0,0x3e750000,0,0x3e2d0000,0,
0,0,0,0x3e2d,0,0x3e75,0,0x3e2d,0,0,0,0x3e2d0000,0,0x3e750000,0,0x3e2d0000,
0x3e46,0,0xbd19,0,0xbe10,0,0xbe72,0,0x3e460000,0,0xbd190000,0,0xbe100000,0,0xbe720000,0,
0,0x3e46,0,0xbd19,0,0xbe10,0,0xbe72,0,0x3e460000,0,0xbd190000,0,0xbe100000,0,0xbe720000,
0xbe69,0,0xbe2d,0,0xbd97,0,0x3e2d,0,0xbe690000,0,0xbe2d0000,0,0xbd970000,0,0x3e2d0000,0,
0,0xbe69,0,0xbe2d,0,0xbd97,0,0x3e2d,0,0xbe690000,0,0xbe2d0000,0,0xbd970000,0,0x3e2d0000,
0xbd97,0,0x3e5a,0,0x3e69,0,0x3dde,0,0xbd970000,0,0x3e5a0000,0,0x3e690000,0,0x3dde0000,0,
0,0xbd97,0,0x3e5a,0,0x3e69,0,0x3dde,0,0xbd970000,0,0x3e5a0000,0,0x3e690000,0,0x3dde0000,
0x3e10,0,0xbe2d,0,0xbe46,0,0xbe2d,0,0x3e100000,0,0xbe2d0000,0,0xbe460000,0,0xbe2d0000,0,
0,0x3e10,0,0xbe2d,0,0xbe46,0,0xbe2d,0,0x3e100000,0,0xbe2d0000,0,0xbe460000,0,0xbe2d0000,
0xbd97,0,0xbe5a,0,0xbe69,0,0x3dde,0,0xbd970000,0,0xbe5a0000,0,0xbe690000,0,0x3dde0000,0,
0,0xbd97,0,0xbe5a,0,0xbe69,0,0x3dde,0,0xbd970000,0,0xbe5a0000,0,0xbe690000,0,0x3dde0000,
0x3e10,0,0x3e2d,0,0x3e46,0,0xbe2d,0,0x3e100000,0,0x3e2d0000,0,0x3e460000,0,0xbe2d0000,0,
0,0x3e10,0,0x3e2d,0,0x3e46,0,0xbe2d,0,0x3e100000,0,0x3e2d0000,0,0x3e460000,0,0xbe2d0000,
0x3e46,0,0x3d19,0,0x3e10,0,0xbe72,0,0x3e460000,0,0x3d190000,0,0x3e100000,0,0xbe720000,0,
0,0x3e46,0,0x3d19,0,0x3e10,0,0xbe72,0,0x3e460000,0,0x3d190000,0,0x3e100000,0,0xbe720000,
0xbe69,0,0x3e2d,0,0x3d97,0,0x3e2d,0,0xbe690000,0,0x3e2d0000,0,0x3d970000,0,0x3e2d0000,0,
0,0xbe69,0,0x3e2d,0,0x3d97,0,0x3e2d,0,0xbe690000,0,0x3e2d0000,0,0x3d970000,0,0x3e2d0000,
0xbe75,0,0x3e2d,0,0x8000,0,0x3e2d,0,0xbe750000,0,0x3e2d0000,0,0x80000000,0,0x3e2d0000,0,
0,0xbe75,0,0x3e2d,0,0x8000,0,0x3e2d,0,0xbe750000,0,0x3e2d0000,0,0x80000000,0,0x3e2d0000,
0,0,0xbe2d,0,0xbe75,0,0x3e2d,0,0,0,0xbe2d0000,0,0xbe750000,0,0x3e2d0000,0,
0,0,0,0xbe2d,0,0xbe75,0,0x3e2d,0,0,0,0xbe2d0000,0,0xbe750000,0,0x3e2d0000,
0x3e46,0,0xbe72,0,0xbe10,0,0x3d19,0,0x3e460000,0,0xbe720000,0,0xbe100000,0,0x3d190000,0,
0,0x3e46,0,0xbe72,0,0xbe10,0,0x3d19,0,0x3e460000,0,0xbe720000,0,0xbe100000,0,0x3d190000,
0x3e69,0,0xbe2d,0,0x3d97,0,0xbe2d,0,0x3e690000,0,0xbe2d0000,0,0x3d970000,0,0xbe2d0000,0,
0,0x3e69,0,0xbe2d,0,0x3d97,0,0xbe2d,0,0x3e690000,0,0xbe2d0000,0,0x3d970000,0,0xbe2d0000,
0xbd97,0,0x3dde,0,0x3e69,0,0xbe5a,0,0xbd970000,0,0x3dde0000,0,0x3e690000,0,0xbe5a0000,0,
0,0xbd97,0,0x3dde,0,0x3e69,0,0xbe5a,0,0xbd970000,0,0x3dde0000,0,0x3e690000,0,0xbe5a0000,
0xbe10,0,0x3e2d,0,0x3e46,0,0xbe2d,0,0xbe100000,0,0x3e2d0000,0,0x3e460000,0,0xbe2d0000,0,
0,0xbe10,0,0x3e2d,0,0x3e46,0,0xbe2d,0,0xbe100000,0,0x3e2d0000,0,0x3e460000,0,0xbe2d0000,
0xbe46,0,0xbe5a,0,0xbe10,0,0xbdde,0,0xbe460000,0,0xbe5a0000,0,0xbe100000,0,0xbdde0000,0,
0,0xbe46,0,0xbe5a,0,0xbe10,0,0xbdde,0,0xbe460000,0,0xbe5a0000,0,0xbe100000,0,0xbdde0000,
0xbe69,0,0xbe72,0,0xbd97,0,0xbd19,0,0xbe690000,0,0xbe720000,0,0xbd970000,0,0xbd190000,0,
0,0xbe69,0,0xbe72,0,0xbd97,0,0xbd19,0,0xbe690000,0,0xbe720000,0,0xbd970000,0,0xbd190000,
0x3d97,0,0xbd19,0,0xbe69,0,0xbe72,0,0x3d970000,0,0xbd190000,0,0xbe690000,0,0xbe720000,0,
0,0x3d97,0,0xbd19,0,0xbe69,0,0xbe72,0,0x3d970000,0,0xbd190000,0,0xbe690000,0,0xbe720000,
0xbe10,0,0xbe5a,0,0xbe46,0,0xbdde,0,0xbe100000,0,0xbe5a0000,0,0xbe460000,0,0xbdde0000,0,
0,0xbe10,0,0xbe5a,0,0xbe46,0,0xbdde,0,0xbe100000,0,0xbe5a0000,0,0xbe460000,0,0xbdde0000,
0x3e75,0,0x3e2d,0,0x8000,0,0xbe2d,0,0x3e750000,0,0x3e2d0000,0,0x80000000,0,0xbe2d0000,0,
0,0x3e75,0,0x3e2d,0,0x8000,0,0xbe2d,0,0x3e750000,0,0x3e2d0000,0,0x80000000,0,0xbe2d0000,
0,0,0xbe2d,0,0xbe75,0,0xbe2d,0,0,0,0xbe2d0000,0,0xbe750000,0,0xbe2d0000,0,
0,0,0,0xbe2d,0,0xbe75,0,0xbe2d,0,0,0,0xbe2d0000,0,0xbe750000,0,0xbe2d0000,
0x3d97,0,0x3e72,0,0x3e69,0,0x3d19,0,0x3d970000,0,0x3e720000,0,0x3e690000,0,0x3d190000,0,
0,0x3d97,0,0x3e72,0,0x3e69,0,0x3d19,0,0x3d970000,0,0x3e720000,0,0x3e690000,0,0x3d190000,
0x3e10,0,0xbdde,0,0xbe46,0,0xbe5a,0,0x3e100000,0,0xbdde0000,0,0xbe460000,0,0xbe5a0000,0,
0,0x3e10,0,0xbdde,0,0xbe46,0,0xbe5a,0,0x3e100000,0,0xbdde0000,0,0xbe460000,0,0xbe5a0000,
0xbe46,0,0x3dde,0,0x3e10,0,0x3e5a,0,0xbe460000,0,0x3dde0000,0,0x3e100000,0,0x3e5a0000,0,
0,0xbe46,0,0x3dde,0,0x3e10,0,0x3e5a,0,0xbe460000,0,0x3dde0000,0,0x3e100000,0,0x3e5a0000,
0x3e69,0,0xbd19,0,0xbd97,0,0xbe72,0,0x3e690000,0,0xbd190000,0,0xbd970000,0,0xbe720000,0,
0,0x3e69,0,0xbd19,0,0xbd97,0,0xbe72,0,0x3e690000,0,0xbd190000,0,0xbd970000,0,0xbe720000,
0xbe46,0,0xbdde,0,0xbe10,0,0x3e5a,0,0xbe460000,0,0xbdde0000,0,0xbe100000,0,0x3e5a0000,0,
0,0xbe46,0,0xbdde,0,0xbe10,0,0x3e5a,0,0xbe460000,0,0xbdde0000,0,0xbe100000,0,0x3e5a0000,
0x3e69,0,0x3d19,0,0x3d97,0,0xbe72,0,0x3e690000,0,0x3d190000,0,0x3d970000,0,0xbe720000,0,
0,0x3e69,0,0x3d19,0,0x3d97,0,0xbe72,0,0x3e690000,0,0x3d190000,0,0x3d970000,0,0xbe720000,
0x3d97,0,0xbe72,0,0xbe69,0,0x3d19,0,0x3d970000,0,0xbe720000,0,0xbe690000,0,0x3d190000,0,
0,0x3d97,0,0xbe72,0,0xbe69,0,0x3d19,0,0x3d970000,0,0xbe720000,0,0xbe690000,0,0x3d190000,
0x3e10,0,0x3dde,0,0x3e46,0,0xbe5a,0,0x3e100000,0,0x3dde0000,0,0x3e460000,0,0xbe5a0000,0,
0,0x3e10,0,0x3dde,0,0x3e46,0,0xbe5a,0,0x3e100000,0,0x3dde0000,0,0x3e460000,0,0xbe5a0000,
0x3e75,0,0xbe2d,0,0x8000,0,0xbe2d,0,0x3e750000,0,0xbe2d0000,0,0x80000000,0,0xbe2d0000,0,
0,0x3e75,0,0xbe2d,0,0x8000,0,0xbe2d,0,0x3e750000,0,0xbe2d0000,0,0x80000000,0,0xbe2d0000,
0,0,0x3e2d,0,0x3e75,0,0xbe2d,0,0,0,0x3e2d0000,0,0x3e750000,0,0xbe2d0000,0,
0,0,0,0x3e2d,0,0x3e75,0,0xbe2d,0,0,0,0x3e2d0000,0,0x3e750000,0,0xbe2d0000,
0x3d97,0,0x3d19,0,0x3e69,0,0xbe72,0,0x3d970000,0,0x3d190000,0,0x3e690000,0,0xbe720000,0,
0,0x3d97,0,0x3d19,0,0x3e69,0,0xbe72,0,0x3d970000,0,0x3d190000,0,0x3e690000,0,0xbe720000,
0xbe10,0,0x3e5a,0,0x3e46,0,0xbdde,0,0xbe100000,0,0x3e5a0000,0,0x3e460000,0,0xbdde0000,0,
0,0xbe10,0,0x3e5a,0,0x3e46,0,0xbdde,0,0xbe100000,0,0x3e5a0000,0,0x3e460000,0,0xbdde0000,
0xbe46,0,0x3e5a,0,0x3e10,0,0xbdde,0,0xbe460000,0,0x3e5a0000,0,0x3e100000,0,0xbdde0000,0,
0,0xbe46,0,0x3e5a,0,0x3e10,0,0xbdde,0,0xbe460000,0,0x3e5a0000,0,0x3e100000,0,0xbdde0000,
0xbe69,0,0x3e72,0,0x3d97,0,0xbd19,0,0xbe690000,0,0x3e720000,0,0x3d970000,0,0xbd190000,0,
0,0xbe69,0,0x3e72,0,0x3d97,0,0xbd19,0,0xbe690000,0,0x3e720000,0,0x3d970000,0,0xbd190000,
0x3eb7,0x3eb7,0x3eb7,0x3eb7,0x3eb78000,0x3eb78000,0x3eb78000,0x3eb78000,0x3eb7,0x3de23eae,0x3e573e94,0x3e943e57,0x3eb78000,0x3eaebde2,0x3e94be57,0x3e57be94,
0x3eb7,0x3e573e94,0x3eae3de2,0x3eaebde2,0x3eb78000,0x3e94be57,0x3de2beae,0xbde2beae,0x3eb7,0x3e943e57,0x3eaebde2,0x3de2beae,0x3eb78000,0x3e57be94,0xbde2beae,0xbeaebde2,
0x3eb7,0x3eb7,0x3eb7,0x3eb7,0x3eb78000,0x3eb78000,0x3eb78000,0x3eb78000,0x3eae3de2,0x3eb70000,0x3eaebde2,0x3e94be57,0x3de2beae,0xbeb7,0xbde2beae,0xbe57be94,
0x3e57be94,0xbeb7,0xbe57be94,0xbeaebde2,0xbe94be57,0xbeb78000,0xbe943e57,0xbde23eae,0xbe57be94,0xbeb70000,0xbe573e94,0x3de23eae,0xbe943e57,0x3eb7,0x3e943e57,0x3eaebde2,
0x3eb7,0x3eae3de2,0x3e57be94,0xbe57be94,0x3eb78000,0x3de2beae,0xbe94be57,0xbe943e57,0x3eb7,0x3eb70000,0xbeb7,0xbeb70000,0x3eb78000,0xbeb7,0xbeb78000,0x3eb7,
0x3eb7,0x3eaebde2,0xbe57be94,0xbe573e94,0x3eb78000,0xbde2beae,0xbe943e57,0x3e943e57,0x3eb7,0x3e94be57,0xbeaebde2,0x3de23eae,0x3eb78000,0xbe57be94,0xbde23eae,0x3eaebde2,
0xbeae3de2,0x3eb7,0x3eae3de2,0x3e57be94,0x3de23eae,0x3eb78000,0x3de2beae,0xbe94be57,0x3eb7,0x3eb70000,0xbeb7,0xbeb70000,0x3eb78000,0xbeb7,0xbeb78000,0x3eb7,
0x3eae3de2,0xbeb7,0xbeae3de2,0x3e573e94,0x3de2beae,0xbeb78000,0x3de23eae,0x3e94be57,0x3e57be94,0xbeb70000,0x3e573e94,0x3de2beae,0xbe94be57,0x3eb7,0x3e94be57,0xbeaebde2,
0x3eb7,0x3e57be94,0xbeae3de2,0x3eae3de2,0x3eb78000,0xbe94be57,0x3de23eae,0x3de2beae,0x3eb7,0x3de2beae,0xbe573e94,0x3e94be57,0x3eb78000,0xbeaebde2,0x3e943e57,0xbe57be94,
0x3eb7,0xbeb7,0x3eb7,0xbeb7,0x3eb78000,0xbeb78000,0x3eb78000,0xbeb78000,0x3eb7,0xbde2beae,0x3e573e94,0xbe94be57,0x3eb78000,0xbeae3de2,0x3e94be57,0xbe573e94,
0xbe57be94,0x3eb7,0x3e57be94,0xbeae3de2,0xbe943e57,0x3eb78000,0xbe94be57,0x3de23eae,0xbeae3de2,0x3eb70000,0xbeaebde2,0x3e943e57,0x3de23eae,0xbeb7,0xbde23eae,0x3e57be94,
0x3eb7,0xbeb7,0x3eb7,0xbeb7,0x3eb78000,0xbeb78000,0x3eb78000,0xbeb78000,0x3eae3de2,0xbeb70000,0x3eaebde2,0xbe943e57,0x3de2beae,0x3eb7,0xbde2beae,0x3e573e94,
0x3eb7,0xbe57be94,0x3eae3de2,0xbeae3de2,0x3eb78000,0xbe943e57,0x3de2beae,0x3de23eae,0x3eb7,0xbe94be57,0x3eaebde2,0xbde23eae,0x3eb78000,0xbe573e94,0xbde2beae,0x3eae3de2,
0x3eb7,0xbeaebde2,0x3e57be94,0x3e573e94,0x3eb78000,0xbde23eae,0xbe94be57,0x3e94be57,0x3eb7,0xbeb70000,0xbeb7,0x3eb70000,0x3eb78000,0x3eb7,0xbeb78000,0xbeb7,
0x3e57be94,0x3eb7,0xbe57be94,0x3eae3de2,0xbe94be57,0x3eb78000,0xbe943e57,0x3de2beae,0xbe57be94,0x3eb70000,0xbe573e94,0xbde2beae,0xbe943e57,0xbeb7,0x3e943e57,0xbeae3de2,
0xbeae3de2,0xbeb7,0x3eae3de2,0xbe573e94,0x3de23eae,0xbeb78000,0x3de2beae,0x3e943e57,0x3eb7,0xbeb70000,0xbeb7,0x3eb70000,0x3eb78000,0x3eb7,0xbeb78000,0xbeb7,
0x3eb7,0xbeae3de2,0xbe57be94,0x3e57be94,0x3eb78000,0x3de23eae,0xbe943e57,0xbe94be57,0x3eb7,0xbe943e57,0xbeaebde2,0xbde2beae,0x3eb78000,0x3e573e94,0xbde23eae,0xbeae3de2,
0x3eb7,0xbe573e94,0xbeae3de2,0xbeaebde2,0x3eb78000,0x3e943e57,0x3de23eae,0xbde23eae,0x3eb7,0xbde23eae,0xbe573e94,0xbe943e57,0x3eb78000,0x3eae3de2,0x3e943e57,0x3e573e94,
0x3eae3de2,0x3eb7,0xbeae3de2,0xbe57be94,0x3de2beae,0x3eb78000,0x3de23eae,0xbe943e57,0x3e57be94,0x3eb70000,0x3e573e94,0xbde23eae,0xbe94be57,0xbeb7,0x3e94be57,0x3eae3de2,
0xbe57be94,0xbeb7,0x3e57be94,0x3eaebde2,0xbe943e57,0xbeb78000,0xbe94be57,0xbde2beae,0xbeae3de2,0xbeb70000,0xbeaebde2,0xbe94be57,0x3de23eae,0x3eb7,0xbde23eae,0xbe573e94,
0x3eb7,0x3eb7,0x3eb7,0x3eb7,0x3eb78000,0x3eb78000,0x3eb78000,0x3eb78000,0x3e57be94,0x3de2beae,0xbeb7,0xbde2beae,0xbe94be57,0xbeaebde2,0xbeb78000,0xbeae3de2,
0xbeae3de2,0xbe573e94,0x3eb7,0x3e573e94,0x3de23eae,0x3e943e57,0x3eb78000,0x3e94be57,0x3eae3de2,0x3e94be57,0xbeb7,0xbe94be57,0x3de2beae,0xbe57be94,0xbeb78000,0xbe573e94,
0x3eb7,0x3eb7,0x3eb7,0x3eb7,0x3eb78000,0x3eb78000,0x3eb78000,0x3eb78000,0xbe57be94,0xbe94be57,0xbeaebde2,0xbeb70000,0xbe943e57,0xbe573e94,0xbde23eae,0x3eb7,
0x3eae3de2,0x3eaebde2,0x3e57be94,0xbeb7,0x3de2beae,0xbde2beae,0xbe94be57,0xbeb78000,0xbeae3de2,0xbde23eae,0x3e573e94,0x3eb70000,0x3de23eae,0x3eae3de2,0x3e94be57,0xbeb7,
0xbe57be94,0xbeae3de2,0x3eb7,0x3eae3de2,0xbe943e57,0x3de23eae,0x3eb78000,0x3de2beae,0x3eb7,0x3eb70000,0xbeb7,0xbeb70000,0x3eb78000,0xbeb7,0xbeb78000,0x3eb7,
0x3e57be94,0xbeaebde2,0x3eb7,0x3eaebde2,0xbe94be57,0xbde23eae,0x3eb78000,0xbde2beae,0xbeae3de2,0x3e943e57,0xbeb7,0xbe943e57,0x3de23eae,0x3e57be94,0xbeb78000,0x3e573e94,
0x3e57be94,0xbe57be94,0xbeae3de2,0x3eb7,0xbe94be57,0xbe943e57,0x3de23eae,0x3eb78000,0x3eb7,0x3eb70000,0xbeb7,0xbeb70000,0x3eb78000,0xbeb7,0xbeb78000,0x3eb7,
0xbe57be94,0xbe573e94,0x3eae3de2,0xbeb7,0xbe943e57,0x3e943e57,0x3de2beae,0xbeb78000,0x3eae3de2,0xbde2beae,0xbe573e94,0x3eb70000,0x3de2beae,0xbeae3de2,0x3e943e57,0xbeb7,
0x3eae3de2,0xbe57be94,0x3eb7,0x3e57be94,0x3de2beae,0xbe943e57,0x3eb78000,0xbe94be57,0xbe57be94,0x3de23eae,0xbeb7,0xbde23eae,0xbe943e57,0x3eaebde2,0xbeb78000,0x3eae3de2,
0x3eb7,0xbeb7,0x3eb7,0xbeb7,0x3eb78000,0xbeb78000,0x3eb78000,0xbeb78000,0x3e57be94,0xbde23eae,0xbeb7,0x3de23eae,0xbe94be57,0x3eae3de2,0xbeb78000,0x3eaebde2,
0xbeae3de2,0x3eae3de2,0xbe57be94,0x3eb7,0x3de23eae,0x3de2beae,0xbe943e57,0x3eb78000,0x3e57be94,0xbe943e57,0x3eaebde2,0xbeb70000,0xbe94be57,0x3e573e94,0xbde2beae,0x3eb7,
0x3eb7,0xbeb7,0x3eb7,0xbeb7,0x3eb78000,0xbeb78000,0x3eb78000,0xbeb78000,0xbe57be94,0x3e943e57,0xbeaebde2,0x3eb70000,0xbe943e57,0x3e57be94,0xbde23eae,0xbeb7,
0xbeae3de2,0x3e57be94,0x3eb7,0xbe57be94,0x3de23eae,0xbe94be57,0x3eb78000,0xbe943e57,0x3eae3de2,0xbe943e57,0xbeb7,0x3e943e57,0x3de2beae,0x3e573e94,0xbeb78000,0x3e57be94,
0xbe57be94,0x3eaebde2,0x3eb7,0xbeaebde2,0xbe943e57,0xbde2beae,0x3eb78000,0xbde23eae,0x3eb7,0xbeb70000,0xbeb7,0x3eb70000,0x3eb78000,0x3eb7,0xbeb78000,0xbeb7,
0x3eae3de2,0xbeae3de2,0x3e57be94,0x3eb7,0x3de2beae,0x3de23eae,0xbe94be57,0x3eb78000,0xbeae3de2,0x3de2beae,0x3e573e94,0xbeb70000,0x3de23eae,0xbeaebde2,0x3e94be57,0x3eb7,
0x3e57be94,0x3e573e94,0xbeae3de2,0xbeb7,0xbe94be57,0x3e94be57,0x3de23eae,0xbeb78000,0x3eb7,0xbeb70000,0xbeb7,0x3eb70000,0x3eb78000,0x3eb7,0xbeb78000,0xbeb7,
0x3e57be94,0x3eae3de2,0x3eb7,0xbeae3de2,0xbe94be57,0x3de2beae,0x3eb78000,0x3de23eae,0xbeae3de2,0xbe94be57,0xbeb7,0x3e94be57,0x3de23eae,0xbe573e94,0xbeb78000,0xbe57be94,
0x3eae3de2,0x3e573e94,0x3eb7,0xbe573e94,0x3de2beae,0x3e94be57,0x3eb78000,0x3e943e57,0xbe57be94,0xbde2beae,0xbeb7,0x3de2beae,0xbe943e57,0xbeae3de2,0xbeb78000,0xbeaebde2,
0xbe57be94,0x3e57be94,0x3eae3de2,0x3eb7,0xbe943e57,0xbe94be57,0x3de2beae,0x3eb78000,0x3eae3de2,0x3de23eae,0xbe573e94,0xbeb70000,0x3de2beae,0x3eaebde2,0x3e943e57,0x3eb7,
0xbeae3de2,0xbeaebde2,0xbe57be94,0xbeb7,0x3de23eae,0xbde23eae,0xbe943e57,0xbeb78000,0x3e57be94,0x3e94be57,0x3eaebde2,0x3eb70000,0xbe94be57,0xbe57be94,0xbde2beae,0xbeb7,
0x3eb7,0x3eb7,0x3eb7,0x3eb7,0x3eb78000,0x3eb78000,0x3eb78000,0x3eb78000,0xbeae3de2,0xbe943e57,0xbe573e94,0xbde23eae,0x3de23eae,0x3e573e94,0x3e943e57,0x3eae3de2,
0xbe57be94,0xbeaebde2,0xbeae3de2,0xbe573e94,0xbe943e57,0xbde23eae,0x3de23eae,0x3e943e57,0x3e57be94,0xbde2beae,0xbeaebde2,0xbe943e57,0xbe94be57,0xbeae3de2,0xbde23eae,0x3e573e94,
0,0,0,0,0,0,0,0,0,0,0,0,0,0,0,0,
0,0,0,0,0,0,0,0,0,0,0,0,0,0,0,0,
0x3eae3de2,0x3e57be94,0xbe57be94,0xbeae3de2,0x3de2beae,0xbe94be57,0xbe943e57,0x3de23eae,0x3eb7,0x3eb70000,0xbeb7,0xbeb70000,0x3eb78000,0xbeb7,0xbeb78000,0x3eb7,
0xbeae3de2,0x3e573e94,0x3e57be94,0xbeaebde2,0x3de23eae,0x3e94be57,0xbe94be57,0xbde23eae,0xbe57be94,0xbde23eae,0x3eaebde2,0xbe94be57,0xbe943e57,0x3eae3de2,0xbde2beae,0xbe573e94,
0,0,0,0,0,0,0,0,0,0,0,0,0,0,0,0,
0,0,0,0,0,0,0,0,0,0,0,0,0,0,0,0,
0x3e57be94,0xbeae3de2,0x3eae3de2,0xbe57be94,0xbe94be57,0x3de23eae,0x3de2beae,0xbe943e57,0x3eae3de2,0xbe94be57,0x3e573e94,0xbde2beae,0x3de2beae,0xbe573e94,0x3e94be57,0xbeae3de2,
0x3eb7,0xbeb7,0x3eb7,0xbeb7,0x3eb78000,0xbeb78000,0x3eb78000,0xbeb78000,0xbeae3de2,0x3e94be57,0xbe573e94,0x3de2beae,0x3de23eae,0xbe57be94,0x3e943e57,0xbeaebde2,
0,0,0,0,0,0,0,0,0,0,0,0,0,0,0,0,
0,0,0,0,0,0,0,0,0,0,0,0,0,0,0,0,
0xbe57be94,0x3eae3de2,0xbeae3de2,0x3e57be94,0xbe943e57,0x3de2beae,0x3de23eae,0xbe94be57,0x3e57be94,0x3de23eae,0xbeaebde2,0x3e94be57,0xbe94be57,0x3eaebde2,0xbde23eae,0xbe57be94,
0x3eae3de2,0xbe573e94,0xbe57be94,0x3eaebde2,0x3de2beae,0x3e943e57,0xbe943e57,0xbde2beae,0x3eb7,0xbeb70000,0xbeb7,0x3eb70000,0x3eb78000,0x3eb7,0xbeb78000,0xbeb7,
0,0,0,0,0,0,0,0,0,0,0,0,0,0,0,0,
0,0,0,0,0,0,0,0,0,0,0,0,0,0,0,0,
0xbeae3de2,0xbe57be94,0x3e57be94,0x3eae3de2,0x3de23eae,0xbe943e57,0xbe94be57,0x3de2beae,0xbe57be94,0x3de2beae,0x3eaebde2,0x3e943e57,0xbe943e57,0xbeaebde2,0xbde2beae,0x3e57be94,
0x3e57be94,0x3eaebde2,0x3eae3de2,0x3e573e94,0xbe94be57,0xbde2beae,0x3de2beae,0x3e94be57,0x3eae3de2,0x3e943e57,0x3e573e94,0x3de23eae,0x3de2beae,0x3e57be94,0x3e94be57,0x3eaebde2,
0,0,0,0,0,0,0,0,0,0,0,0,0,0,0,0,
0,0,0,0,0,0,0,0,0,0,0,0,0,0,0,0,
0,0,0,0,0,0,0,0,0,0,0,0,0,0,0,0,
0,0,0,0,0,0,0,0,0,0,0,0,0,0,0,0,
0x3eb7,0x3eb7,0x3eb7,0x3eb7,0x3eb78000,0x3eb78000,0x3eb78000,0x3eb78000,0xbeae3de2,0xbe943e57,0xbe573e94,0xbde23eae,0x3de23eae,0x3e573e94,0x3e943e57,0x3eae3de2,
0xbe57be94,0xbeaebde2,0xbeae3de2,0xbe573e94,0xbe943e57,0xbde23eae,0x3de23eae,0x3e943e57,0x3e57be94,0xbde2beae,0xbeaebde2,0xbe943e57,0xbe94be57,0xbeae3de2,0xbde23eae,0x3e573e94,
0,0,0,0,0,0,0,0,0,0,0,0,0,0,0,0,
0,0,0,0,0,0,0,0,0,0,0,0,0,0,0,0,
0x3eae3de2,0x3e57be94,0xbe57be94,0xbeae3de2,0x3de2beae,0xbe94be57,0xbe943e57,0x3de23eae,0x3eb7,0x3eb70000,0xbeb7,0xbeb70000,0x3eb78000,0xbeb7,0xbeb78000,0x3eb7,
0xbeae3de2,0x3e573e94,0x3e57be94,0xbeaebde2,0x3de23eae,0x3e94be57,0xbe94be57,0xbde23eae,0xbe57be94,0xbde23eae,0x3eaebde2,0xbe94be57,0xbe943e57,0x3eae3de2,0xbde2beae,0xbe573e94,
0,0,0,0,0,0,0,0,0,0,0,0,0,0,0,0,
0,0,0,0,0,0,0,0,0,0,0,0,0,0,0,0,
0x3e57be94,0xbeae3de2,0x3eae3de2,0xbe57be94,0xbe94be57,0x3de23eae,0x3de2beae,0xbe943e57,0x3eae3de2,0xbe94be57,0x3e573e94,0xbde2beae,0x3de2beae,0xbe573e94,0x3e94be57,0xbeae3de2,
0x3eb7,0xbeb7,0x3eb7,0xbeb7,0x3eb78000,0xbeb78000,0x3eb78000,0xbeb78000,0xbeae3de2,0x3e94be57,0xbe573e94,0x3de2beae,0x3de23eae,0xbe57be94,0x3e943e57,0xbeaebde2,
0,0,0,0,0,0,0,0,0,0,0,0,0,0,0,0,
0,0,0,0,0,0,0,0,0,0,0,0,0,0,0,0,
0xbe57be94,0x3eae3de2,0xbeae3de2,0x3e57be94,0xbe943e57,0x3de2beae,0x3de23eae,0xbe94be57,0x3e57be94,0x3de23eae,0xbeaebde2,0x3e94be57,0xbe94be57,0x3eaebde2,0xbde23eae,0xbe57be94,
0x3eae3de2,0xbe573e94,0xbe57be94,0x3eaebde2,0x3de2beae,0x3e943e57,0xbe943e57,0xbde2beae,0x3eb7,0xbeb70000,0xbeb7,0x3eb70000,0x3eb78000,0x3eb7,0xbeb78000,0xbeb7,
0,0,0,0,0,0,0,0,0,0,0,0,0,0,0,0,
0,0,0,0,0,0,0,0,0,0,0,0,0,0,0,0,
0xbeae3de2,0xbe57be94,0x3e57be94,0x3eae3de2,0x3de23eae,0xbe943e57,0xbe94be57,0x3de2beae,0xbe57be94,0x3de2beae,0x3eaebde2,0x3e943e57,0xbe943e57,0xbeaebde2,0xbde2beae,0x3e57be94,
0x3e57be94,0x3eaebde2,0x3eae3de2,0x3e573e94,0xbe94be57,0xbde2beae,0x3de2beae,0x3e94be57,0x3eae3de2,0x3e943e57,0x3e573e94,0x3de23eae,0x3de2beae,0x3e57be94,0x3e94be57,0x3eaebde2,
};
__device__ __align__(128) const uint32_t TAB_P3[4288] = {
0,0,0,0,0,0,0,0,0,0,0,0,0,0,0,0,
0x80003e83,0xbe79bda2,0x3e1abe54,0x3e1a3e54,0x3e830000,0xbda23e79,0xbe54be1a,0x3e54be1a,0x80003e83,0xbe54be1a,0x3e79bda2,0xbda23e79,0x3e830000,0xbe1a3e54,0xbda2be79,0x3e793da2,
0,0,0,0,0,0,0,0,0,0,0,0,0,0,0,0,
0xbe793da2,0x8000be83,0x3e793da2,0xbe1a3e54,0x3da23e79,0xbe830000,0x3da2be79,0x3e543e1a,0xbe1abe54,0x3e830000,0xbe1a3e54,0xbda2be79,0xbe543e1a,0xbe83,0x3e543e1a,0xbe793da2,
0x80003e83,0xbe1abe54,0x3e793da2,0xbe793da2,0x3e830000,0xbe543e1a,0x3da2be79,0x3da23e79,0x80003e83,0xbda2be79,0x3e1a3e54,0xbe54be1a,0x3e830000,0xbe793da2,0x3e54be1a,0xbe1a3e54,
0x80003e83,0x8000be83,0x80003e83,0x8000be83,0x3e830000,0xbe830000,0x3e830000,0xbe830000,0x80003e83,0x3da2be79,0xbe1a3e54,0x3e54be1a,0x3e830000,0xbe79bda2,0x3e543e1a,0xbe1abe54,
0x3e1abe54,0x80003e83,0xbe1abe54,0x3e793da2,0xbe54be1a,0x3e830000,0xbe543e1a,0x3da2be79,0x3e793da2,0xbe830000,0x3e79bda2,0xbe543e1a,0x3da2be79,0x3e83,0xbda2be79,0x3e1a3e54,
0x80003e83,0x8000be83,0x80003e83,0x8000be83,0x3e830000,0xbe830000,0x3e830000,0xbe830000,0xbe793da2,0x3e830000,0xbe79bda2,0x3e543e1a,0x3da23e79,0xbe83,0xbda23e79,0x3e1abe54,
0x80003e83,0x3e1abe54,0xbe793da2,0x3e793da2,0x3e830000,0xbe54be1a,0x3da23e79,0x3da2be79,0x80003e83,0x3e54be1a,0xbe79bda2,0x3da23e79,0x3e830000,0xbe1abe54,0xbda23e79,0x3e79bda2,
0x80003e83,0x3e79bda2,0xbe1abe54,0xbe1a3e54,0x3e830000,0xbda2be79,0xbe543e1a,0x3e543e1a,0x80003e83,0x3e830000,0x8000be83,0xbe830000,0x3e830000,0xbe83,0xbe830000,0x3e83,
0xbe1abe54,0x80003e83,0x3e1abe54,0xbe793da2,0xbe543e1a,0x3e830000,0xbe54be1a,0x3da23e79,0x3e1abe54,0xbe830000,0x3e1a3e54,0x3da2be79,0xbe54be1a,0x3e83,0x3e54be1a,0xbe79bda2,
0x3e793da2,0x8000be83,0xbe793da2,0x3e1a3e54,0x3da2be79,0xbe830000,0x3da23e79,0x3e54be1a,0x80003e83,0x3e830000,0x8000be83,0xbe830000,0x3e830000,0xbe83,0xbe830000,0x3e83,
0x80003e83,0x3e793da2,0x3e1abe54,0xbe1abe54,0x3e830000,0x3da2be79,0xbe54be1a,0xbe543e1a,0x80003e83,0x3e543e1a,0x3e79bda2,0x3da2be79,0x3e830000,0x3e1abe54,0xbda2be79,0xbe79bda2,
0x80003e83,0x3e1a3e54,0x3e793da2,0x3e79bda2,0x3e830000,0x3e54be1a,0x3da2be79,0xbda2be79,0x80003e83,0x3da23e79,0x3e1a3e54,0x3e543e1a,0x3e830000,0x3e79bda2,0x3e54be1a,0x3e1abe54,
0xbe793da2,0x80003e83,0x3e793da2,0x3e1abe54,0x3da23e79,0x3e830000,0x3da2be79,0xbe54be1a,0xbe1abe54,0xbe830000,0xbe1a3e54,0x3da23e79,0xbe543e1a,0x3e83,0x3e543e1a,0x3e79bda2,
0x3e1abe54,0x8000be83,0xbe1abe54,0xbe79bda2,0xbe54be1a,0xbe830000,0xbe543e1a,0xbda23e79,0x3e793da2,0x3e830000,0x3e79bda2,0x3e54be1a,0x3da2be79,0xbe83,0xbda2be79,0xbe1abe54,
0,0,0,0,0,0,0,0,0,0,0,0,0,0,0,0,
0,0,0,0,0,0,0,0,0,0,0,0,0,0,0,0,
0,0,0,0,0,0,0,0,0,0,0,0,0,0,0,0,
0xbe1abe54,0x3e79bda2,0x80003e83,0xbe79bda2,0xbe543e1a,0xbda2be79,0x3e830000,0xbda23e79,0x3e793da2,0xbe543e1a,0x8000be83,0x3e543e1a,0x3da2be79,0x3e1a3e54,0xbe830000,0x3e1abe54,
0,0,0,0,0,0,0,0,0,0,0,0,0,0,0,0,
0,0,0,0,0,0,0,0,0,0,0,0,0,0,0,0,
0xbe793da2,0x3e1abe54,0x80003e83,0xbe1abe54,0x3da23e79,0xbe54be1a,0x3e830000,0xbe543e1a,0x3e1abe54,0xbda23e79,0x8000be83,0x3da23e79,0xbe54be1a,0x3e793da2,0xbe830000,0x3e79bda2,
0x80003e83,0x8000be83,0x80003e83,0x8000be83,0x3e830000,0xbe830000,0x3e830000,0xbe830000,0xbe1abe54,0x3da23e79,0x8000be83,0xbda23e79,0xbe543e1a,0x3e79bda2,0xbe830000,0x3e793da2,
0,0,0,0,0,0,0,0,0,0,0,0,0,0,0,0,
0,0,0,0,0,0,0,0,0,0,0,0,0,0,0,0,
0x3e793da2,0xbe1abe54,0x80003e83,0x3e1abe54,0x3da2be79,0xbe543e1a,0x3e830000,0xbe54be1a,0xbe793da2,0x3e543e1a,0x8000be83,0xbe543e1a,0x3da23e79,0x3e1abe54,0xbe830000,0x3e1a3e54,
0x3e1abe54,0xbe79bda2,0x80003e83,0x3e79bda2,0xbe54be1a,0xbda23e79,0x3e830000,0xbda2be79,0x80003e83,0x3e830000,0x8000be83,0xbe830000,0x3e830000,0xbe83,0xbe830000,0x3e83,
0,0,0,0,0,0,0,0,0,0,0,0,0,0,0,0,
0,0,0,0,0,0,0,0,0,0,0,0,0,0,0,0,
0xbe1abe54,0xbe793da2,0x80003e83,0x3e793da2,0xbe543e1a,0x3da23e79,0x3e830000,0x3da2be79,0x3e793da2,0x3e54be1a,0x8000be83,0xbe54be1a,0x3da2be79,0xbe1abe54,0xbe830000,0xbe1a3e54,
0xbe793da2,0xbe1a3e54,0x80003e83,0x3e1a3e54,0x3da23e79,0x3e543e1a,0x3e830000,0x3e54be1a,0x3e1abe54,0x3da2be79,0x8000be83,0xbda2be79,0xbe54be1a,0xbe79bda2,0xbe830000,0xbe793da2,
0,0,0,0,0,0,0,0,0,0,0,0,0,0,0,0,
0x3e1abe54,0x3e1a3e54,0xbe793da2,0x8000be83,0xbe54be1a,0x3e54be1a,0x3da23e79,0xbe830000,0xbe793da2,0x3da2be79,0x3e1a3e54,0xbe830000,0x3da23e79,0xbe79bda2,0x3e54be1a,0x3e83,
0,0,0,0,0,0,0,0,0,0,0,0,0,0,0,0,
0x3e793da2,0xbe1a3e54,0xbe1abe54,0x3e79bda2,0x3da2be79,0x3e543e1a,0xbe543e1a,0xbda2be79,0x3e1abe54,0x3da23e79,0xbe79bda2,0x3e54be1a,0xbe54be1a,0x3e79bda2,0xbda23e79,0xbe1abe54,
0x3e793da2,0xbe793da2,0x3e1abe54,0x80003e83,0x3da2be79,0x3da23e79,0xbe54be1a,0x3e830000,0xbe1abe54,0x3e543e1a,0xbe79bda2,0x3e830000,0xbe543e1a,0x3e1abe54,0xbda23e79,0xbe83,
0x80003e83,0x8000be83,0x80003e83,0x8000be83,0x3e830000,0xbe830000,0x3e830000,0xbe830000,0x3e1abe54,0xbe543e1a,0x3e79bda2,0xbe830000,0xbe54be1a,0x3e1a3e54,0xbda2be79,0x3e83,
0xbe1abe54,0x3e793da2,0xbe793da2,0x3e1abe54,0xbe543e1a,0x3da2be79,0x3da23e79,0xbe54be1a,0xbe793da2,0x3e54be1a,0xbe1a3e54,0x3da2be79,0x3da23e79,0xbe1abe54,0x3e543e1a,0xbe79bda2,
0x80003e83,0x8000be83,0x80003e83,0x8000be83,0x3e830000,0xbe830000,0x3e830000,0xbe830000,0x3e793da2,0xbe54be1a,0x3e1a3e54,0xbda2be79,0x3da2be79,0xbe1a3e54,0x3e54be1a,0xbe793da2,
0xbe793da2,0x3e793da2,0xbe1abe54,0x80003e83,0x3da23e79,0x3da2be79,0xbe543e1a,0x3e830000,0x3e793da2,0xbda2be79,0xbe1a3e54,0x3e830000,0x3da2be79,0xbe793da2,0x3e543e1a,0xbe83,
0xbe1abe54,0xbe1a3e54,0x3e793da2,0x8000be83,0xbe543e1a,0x3e543e1a,0x3da2be79,0xbe830000,0x80003e83,0x3e830000,0x8000be83,0xbe830000,0x3e830000,0xbe83,0xbe830000,0x3e83,
0x3e1abe54,0xbe793da2,0x3e793da2,0xbe1abe54,0xbe54be1a,0x3da23e79,0x3da2be79,0xbe543e1a,0xbe1abe54,0xbda23e79,0x3e79bda2,0xbe54be1a,0xbe543e1a,0x3e793da2,0xbda2be79,0xbe1a3e54,
0xbe793da2,0x3e1a3e54,0x3e1abe54,0xbe79bda2,0x3da23e79,0x3e54be1a,0xbe54be1a,0xbda23e79,0x80003e83,0x3e830000,0x8000be83,0xbe830000,0x3e830000,0xbe83,0xbe830000,0x3e83,
0x3e1abe54,0xbe1abe54,0xbe793da2,0x80003e83,0xbe54be1a,0xbe543e1a,0x3da23e79,0x3e830000,0xbe793da2,0xbda23e79,0x3e1a3e54,0x3e830000,0x3da23e79,0x3e793da2,0x3e54be1a,0xbe83,
0x3e793da2,0x3e79bda2,0x3e1abe54,0x8000be83,0x3da2be79,0xbda2be79,0xbe54be1a,0xbe830000,0xbe1abe54,0xbe54be1a,0xbe79bda2,0xbe830000,0xbe543e1a,0xbe1a3e54,0xbda23e79,0x3e83,
0x3e793da2,0x3e1abe54,0xbe1abe54,0xbe793da2,0x3da2be79,0xbe54be1a,0xbe543e1a,0x3da23e79,0x3e1abe54,0xbda2be79,0xbe79bda2,0xbe543e1a,0xbe54be1a,0xbe793da2,0xbda23e79,0x3e1a3e54,
0xbe1abe54,0xbe79bda2,0xbe793da2,0xbe1a3e54,0xbe543e1a,0xbda23e79,0x3da23e79,0x3e543e1a,0xbe793da2,0xbe543e1a,0xbe1a3e54,0xbda23e79,0x3da23e79,0x3e1a3e54,0x3e543e1a,0x3e793da2,
0xbe163dda,0,0,0,0,0xbe163dda,0,0,0,0,0xbe163dda,0,0,0,0,0xbe163dda,
0xbe253da8,0,0,0,0,0xbe253da8,0,0,0,0,0xbe253da8,0,0,0,0,0xbe253da8,
0xbd65be30,0,0,0,0,0xbd65be30,0,0,0,0,0xbd65be30,0,0,0,0,0xbd65be30,
0x3ce8be37,0,0,0,0,0x3ce8be37,0,0,0,0,0x3ce8be37,0,0,0,0,0x3ce8be37,
0xbe303d65,0,0,0,0,0xbe303d65,0,0,0,0,0xbe303d65,0,0,0,0,0xbe303d65,
0xbe373ce8,0,0,0,0,0xbe373ce8,0,0,0,0,0xbe373ce8,0,0,0,0,0xbe373ce8,
0x3ddabe16,0,0,0,0,0x3ddabe16,0,0,0,0,0x3ddabe16,0,0,0,0,0x3ddabe16,
0x3e25bda8,0,0,0,0,0x3e25bda8,0,0,0,0,0x3e25bda8,0,0,0,0,0x3e25bda8,
0xbe390000,0,0,0,0,0xbe390000,0,0,0,0,0xbe390000,0,0,0,0,0xbe390000,
0xbe37bce8,0,0,0,0,0xbe37bce8,0,0,0,0,0xbe37bce8,0,0,0,0,0xbe37bce8,
0x3e390000,0,0,0,0,0x3e390000,0,0,0,0,0x3e390000,0,0,0,0,0x3e390000,
0x3e253da8,0,0,0,0,0x3e253da8,0,0,0,0,0x3e253da8,0,0,0,0,0x3e253da8,
0xbe30bd65,0,0,0,0,0xbe30bd65,0,0,0,0,0xbe30bd65,0,0,0,0,0xbe30bd65,
0xbe25bda8,0,0,0,0,0xbe25bda8,0,0,0,0,0xbe25bda8,0,0,0,0,0xbe25bda8,
0x3dda3e16,0,0,0,0,0x3dda3e16,0,0,0,0,0x3dda3e16,0,0,0,0,0x3dda3e16,
0x3ce83e37,0,0,0,0,0x3ce83e37,0,0,0,0,0x3ce83e37,0,0,0,0,0x3ce83e37,
0xbe16bdda,0,0,0,0,0xbe16bdda,0,0,0,0,0xbe16bdda,0,0,0,0,0xbe16bdda,
0xbe03be03,0,0,0,0,0xbe03be03,0,0,0,0,0xbe03be03,0,0,0,0,0xbe03be03,
0xbd653e30,0,0,0,0,0xbd653e30,0,0,0,0,0xbd653e30,0,0,0,0,0xbd653e30,
0xbe033e03,0,0,0,0,0xbe033e03,0,0,0,0,0xbe033e03,0,0,0,0,0xbe033e03,
0xbddabe16,0,0,0,0,0xbddabe16,0,0,0,0,0xbddabe16,0,0,0,0,0xbddabe16,
0xbda8be25,0,0,0,0,0xbda8be25,0,0,0,0,0xbda8be25,0,0,0,0,0xbda8be25,
0xbe303d65,0,0,0,0,0xbe303d65,0,0,0,0,0xbe303d65,0,0,0,0,0xbe303d65,
0xbe37bce8,0,0,0,0,0xbe37bce8,0,0,0,0,0xbe37bce8,0,0,0,0,0xbe37bce8,
0xbd65be30,0,0,0,0,0xbd65be30,0,0,0,0,0xbd65be30,0,0,0,0,0xbd65be30,
0xbce8be37,0,0,0,0,0xbce8be37,0,0,0,0,0xbce8be37,0,0,0,0,0xbce8be37,
0xbe16bdda,0,0,0,0,0xbe16bdda,0,0,0,0,0xbe16bdda,0,0,0,0,0xbe16bdda,
0xbda8be25,0,0,0,0,0xbda8be25,0,0,0,0,0xbda8be25,0,0,0,0,0xbda8be25,
0x3e390000,0,0,0,0,0x3e390000,0,0,0,0,0x3e390000,0,0,0,0,0x3e390000,
0x3e033e03,0,0,0,0,0x3e033e03,0,0,0,0,0x3e033e03,0,0,0,0,0x3e033e03,
0xbd653e30,0,0,0,0,0xbd653e30,0,0,0,0,0xbd653e30,0,0,0,0,0xbd653e30,
0xbe373ce8,0,0,0,0,0xbe373ce8,0,0,0,0,0xbe373ce8,0,0,0,0,0xbe373ce8,
0x80003e39,0,0,0,0,0x80003e39,0,0,0,0,0x80003e39,0,0,0,0,0x80003e39,
0xbe033e03,0,0,0,0,0xbe033e03,0,0,0,0,0xbe033e03,0,0,0,0,0xbe033e03,
0xbddabe16,0,0,0,0,0xbddabe16,0,0,0,0,0xbddabe16,0,0,0,0,0xbddabe16,
0x3da8be25,0,0,0,0,0x3da8be25,0,0,0,0,0x3da8be25,0,0,0,0,0x3da8be25,
0xbe390000,0,0,0,0,0xbe390000,0,0,0,0,0xbe390000,0,0,0,0,0xbe390000,
0xbe03be03,0,0,0,0,0xbe03be03,0,0,0,0,0xbe03be03,0,0,0,0,0xbe03be03,
0x3e390000,0,0,0,0,0x3e390000,0,0,0,0,0x3e390000,0,0,0,0,0x3e390000,
0x3da83e25,0,0,0,0,0x3da83e25,0,0,0,0,0x3da83e25,0,0,0,0,0x3da83e25,
0x8000be39,0,0,0,0,0x8000be39,0,0,0,0,0x8000be39,0,0,0,0,0x8000be39,
0x3e03be03,0,0,0,0,0x3e03be03,0,0,0,0,0x3e03be03,0,0,0,0,0x3e03be03,
0xbdda3e16,0,0,0,0,0xbdda3e16,0,0,0,0,0xbdda3e16,0,0,0,0,0xbdda3e16,
0xbe37bce8,0,0,0,0,0xbe37bce8,0,0,0,0,0xbe37bce8,0,0,0,0,0xbe37bce8,
0x3e390000,0,0,0,0,0x3e390000,0,0,0,0,0x3e390000,0,0,0,0,0x3e390000,
0x3e033e03,0,0,0,0,0x3e033e03,0,0,0,0,0x3e033e03,0,0,0,0,0x3e033e03,
0xbd65be30,0,0,0,0,0xbd65be30,0,0,0,0,0xbd65be30,0,0,0,0,0xbd65be30,
0x3e03be03,0,0,0,0,0x3e03be03,0,0,0,0,0x3e03be03,0,0,0,0,0x3e03be03,
0x80003e39,0,0,0,0,0x80003e39,0,0,0,0,0x80003e39,0,0,0,0,0x80003e39,
0xbe033e03,0,0,0,0,0xbe033e03,0,0,0,0,0xbe033e03,0,0,0,0,0xbe033e03,
0x3e303d65,0,0,0,0,0x3e303d65,0,0,0,0,0x3e303d65,0,0,0,0,0x3e303d65,
0x3ce83e37,0,0,0,0,0x3ce83e37,0,0,0,0,0x3ce83e37,0,0,0,0,0x3ce83e37,
0xbe390000,0,0,0,0,0xbe390000,0,0,0,0,0xbe390000,0,0,0,0,0xbe390000,
0xbe03be03,0,0,0,0,0xbe03be03,0,0,0,0,0xbe03be03,0,0,0,0,0xbe03be03,
0xbe163dda,0,0,0,0,0xbe163dda,0,0,0,0,0xbe163dda,0,0,0,0,0xbe163dda,
0xbe25bda8,0,0,0,0,0xbe25bda8,0,0,0,0,0xbe25bda8,0,0,0,0,0xbe25bda8,
0xbe16bdda,0,0,0,0,0xbe16bdda,0,0,0,0,0xbe16bdda,0,0,0,0,0xbe16bdda,
0x3da8be25,0,0,0,0,0x3da8be25,0,0,0,0,0x3da8be25,0,0,0,0,0x3da8be25,
0x3e16bdda,0,0,0,0,0x3e16bdda,0,0,0,0,0x3e16bdda,0,0,0,0,0x3e16bdda,
0x3da83e25,0,0,0,0,0x3da83e25,0,0,0,0,0x3da83e25,0,0,0,0,0x3da83e25,
0x3e303d65,0,0,0,0,0x3e303d65,0,0,0,0,0x3e303d65,0,0,0,0,0x3e303d65,
0xbce83e37,0,0,0,0,0xbce83e37,0,0,0,0,0xbce83e37,0,0,0,0,0xbce83e37,
0xbe303d65,0,0,0,0,0xbe303d65,0,0,0,0,0xbe303d65,0,0,0,0,0xbe303d65,
0xbce8be37,0,0,0,0,0xbce8be37,0,0,0,0,0xbce8be37,0,0,0,0,0xbce8be37,
0xbe390000,0,0,0,0,0xbe390000,0,0,0,0,0xbe390000,0,0,0,0,0xbe390000,
0xbce8be37,0,0,0,0,0xbce8be37,0,0,0,0,0xbce8be37,0,0,0,0,0xbce8be37,
0x3e390000,0,0,0,0,0x3e390000,0,0,0,0,0x3e390000,0,0,0,0,0x3e390000,
0xbce83e37,0,0,0,0,0xbce83e37,0,0,0,0,0xbce83e37,0,0,0,0,0xbce83e37,
0x3e30bd65,0,0,0,0,0x3e30bd65,0,0,0,0,0x3e30bd65,0,0,0,0,0x3e30bd65,
0x3da83e25,0,0,0,0,0x3da83e25,0,0,0,0,0x3da83e25,0,0,0,0,0x3da83e25,
0xbe30bd65,0,0,0,0,0xbe30bd65,0,0,0,0,0xbe30bd65,0,0,0,0,0xbe30bd65,
0x3da8be25,0,0,0,0,0x3da8be25,0,0,0,0,0x3da8be25,0,0,0,0,0x3da8be25,
0xbe163dda,0,0,0,0,0xbe163dda,0,0,0,0,0xbe163dda,0,0,0,0,0xbe163dda,
0xbe03be03,0,0,0,0,0xbe03be03,0,0,0,0,0xbe03be03,0,0,0,0,0xbe03be03,
0x3e163dda,0,0,0,0,0x3e163dda,0,0,0,0,0x3e163dda,0,0,0,0,0x3e163dda,
0xbe033e03,0,0,0,0,0xbe033e03,0,0,0,0,0xbe033e03,0,0,0,0,0xbe033e03,
0x3ddabe16,0,0,0,0,0x3ddabe16,0,0,0,0,0x3ddabe16,0,0,0,0,0x3ddabe16,
0x3e253da8,0,0,0,0,0x3e253da8,0,0,0,0,0x3e253da8,0,0,0,0,0x3e253da8,
0xbddabe16,0,0,0,0,0xbddabe16,0,0,0,0,0xbddabe16,0,0,0,0,0xbddabe16,
0x3e25bda8,0,0,0,0,0x3e25bda8,0,0,0,0,0x3e25bda8,0,0,0,0,0x3e25bda8,
0xbd653e30,0,0,0,0,0xbd653e30,0,0,0,0,0xbd653e30,0,0,0,0,0xbd653e30,
0xbe37bce8,0,0,0,0,0xbe37bce8,0,0,0,0,0xbe37bce8,0,0,0,0,0xbe37bce8,
0x3d653e30,0,0,0,0,0x3d653e30,0,0,0,0,0x3d653e30,0,0,0,0,0x3d653e30,
0xbe373ce8,0,0,0,0,0xbe373ce8,0,0,0,0,0xbe373ce8,0,0,0,0,0xbe373ce8,
0x3d653e30,0,0,0,0,0x3d653e30,0,0,0,0,0x3d653e30,0,0,0,0,0x3d653e30,
0xbe37bce8,0,0,0,0,0xbe37bce8,0,0,0,0,0xbe37bce8,0,0,0,0,0xbe37bce8,
0xbe390000,0,0,0,0,0xbe390000,0,0,0,0,0xbe390000,0,0,0,0,0xbe390000,
0x3e03be03,0,0,0,0,0x3e03be03,0,0,0,0,0x3e03be03,0,0,0,0,0x3e03be03,
0x3ddabe16,0,0,0,0,0x3ddabe16,0,0,0,0,0x3ddabe16,0,0,0,0,0x3ddabe16,
0x3da83e25,0,0,0,0,0x3da83e25,0,0,0,0,0x3da83e25,0,0,0,0,0x3da83e25,
0x80003e39,0,0,0,0,0x80003e39,0,0,0,0,0x80003e39,0,0,0,0,0x80003e39,
0xbe03be03,0,0,0,0,0xbe03be03,0,0,0,0,0xbe03be03,0,0,0,0,0xbe03be03,
0xbe390000,0,0,0,0,0xbe390000,0,0,0,0,0xbe390000,0,0,0,0,0xbe390000,
0x3da8be25,0,0,0,0,0x3da8be25,0,0,0,0,0x3da8be25,0,0,0,0,0x3da8be25,
0x3e390000,0,0,0,0,0x3e390000,0,0,0,0,0x3e390000,0,0,0,0,0x3e390000,
0xbe033e03,0,0,0,0,0xbe033e03,0,0,0,0,0xbe033e03,0,0,0,0,0xbe033e03,
0x3dda3e16,0,0,0,0,0x3dda3e16,0,0,0,0,0x3dda3e16,0,0,0,0,0x3dda3e16,
0xbe373ce8,0,0,0,0,0xbe373ce8,0,0,0,0,0xbe373ce8,0,0,0,0,0xbe373ce8,
0x8000be39,0,0,0,0,0x8000be39,0,0,0,0,0x8000be39,0,0,0,0,0x8000be39,
0x3e033e03,0,0,0,0,0x3e033e03,0,0,0,0,0x3e033e03,0,0,0,0,0x3e033e03,
0x3d65be30,0,0,0,0,0x3d65be30,0,0,0,0,0x3d65be30,0,0,0,0,0x3d65be30,
0x3e033e03,0,0,0,0,0x3e033e03,0,0,0,0,0x3e033e03,0,0,0,0,0x3e033e03,
0xbe390000,0,0,0,0,0xbe390000,0,0,0,0,0xbe390000,0,0,0,0,0xbe390000,
0x3e03be03,0,0,0,0,0x3e03be03,0,0,0,0,0x3e03be03,0,0,0,0,0x3e03be03,
0xbe303d65,0,0,0,0,0xbe303d65,0,0,0,0,0xbe303d65,0,0,0,0,0xbe303d65,
0x3ce8be37,0,0,0,0,0x3ce8be37,0,0,0,0,0x3ce8be37,0,0,0,0,0x3ce8be37,
0x80003e39,0,0,0,0,0x80003e39,0,0,0,0,0x80003e39,0,0,0,0,0x80003e39,
0xbe03be03,0,0,0,0,0xbe03be03,0,0,0,0,0xbe03be03,0,0,0,0,0xbe03be03,
0x3e163dda,0,0,0,0,0x3e163dda,0,0,0,0,0x3e163dda,0,0,0,0,0x3e163dda,
0xbe253da8,0,0,0,0,0xbe253da8,0,0,0,0,0xbe253da8,0,0,0,0,0xbe253da8,
0x3e390000,0,0,0,0,0x3e390000,0,0,0,0,0x3e390000,0,0,0,0,0x3e390000,
0xbe033e03,0,0,0,0,0xbe033e03,0,0,0,0,0xbe033e03,0,0,0,0,0xbe033e03,
0x3d65be30,0,0,0,0,0x3d65be30,0,0,0,0,0x3d65be30,0,0,0,0,0x3d65be30,
0x3ce83e37,0,0,0,0,0x3ce83e37,0,0,0,0,0x3ce83e37,0,0,0,0,0x3ce83e37,
0x3e163dda,0,0,0,0,0x3e163dda,0,0,0,0,0x3e163dda,0,0,0,0,0x3e163dda,
0xbe25bda8,0,0,0,0,0xbe25bda8,0,0,0,0,0xbe25bda8,0,0,0,0,0xbe25bda8,
0xbddabe16,0,0,0,0,0xbddabe16,0,0,0,0,0xbddabe16,0,0,0,0,0xbddabe16,
0x3e253da8,0,0,0,0,0x3e253da8,0,0,0,0,0x3e253da8,0,0,0,0,0x3e253da8,
0x3e303d65,0,0,0,0,0x3e303d65,0,0,0,0,0x3e303d65,0,0,0,0,0x3e303d65,
0xbe37bce8,0,0,0,0,0xbe37bce8,0,0,0,0,0xbe37bce8,0,0,0,0,0xbe37bce8,
0xbe390000,0,0,0,0,0xbe390000,0,0,0,0,0xbe390000,0,0,0,0,0xbe390000,
0x3e25bda8,0,0,0,0,0x3e25bda8,0,0,0,0,0x3e25bda8,0,0,0,0,0x3e25bda8,
0x3e390000,0,0,0,0,0x3e390000,0,0,0,0,0x3e390000,0,0,0,0,0x3e390000,
0xbe373ce8,0,0,0,0,0xbe373ce8,0,0,0,0,0xbe373ce8,0,0,0,0,0xbe373ce8,
0xbdda3e16,0,0,0,0,0xbdda3e16,0,0,0,0,0xbdda3e16,0,0,0,0,0xbdda3e16,
0x3ce8be37,0,0,0,0,0x3ce8be37,0,0,0,0,0x3ce8be37,0,0,0,0,0x3ce8be37,
0x3e30bd65,0,0,0,0,0x3e30bd65,0,0,0,0,0x3e30bd65,0,0,0,0,0x3e30bd65,
0xbe253da8,0,0,0,0,0xbe253da8,0,0,0,0,0xbe253da8,0,0,0,0,0xbe253da8,
0x3d653e30,0,0,0,0,0x3d653e30,0,0,0,0,0x3d653e30,0,0,0,0,0x3d653e30,
0xbe03be03,0,0,0,0,0xbe03be03,0,0,0,0,0xbe03be03,0,0,0,0,0xbe03be03,
0x3e16bdda,0,0,0,0,0x3e16bdda,0,0,0,0,0x3e16bdda,0,0,0,0,0x3e16bdda,
0xbe033e03,0,0,0,0,0xbe033e03,0,0,0,0,0xbe033e03,0,0,0,0,0xbe033e03,
0x3e303d65,0,0,0,0,0x3e303d65,0,0,0,0,0x3e303d65,0,0,0,0,0x3e303d65,
0xbe373ce8,0,0,0,0,0xbe373ce8,0,0,0,0,0xbe373ce8,0,0,0,0,0xbe373ce8,
0x3ddabe16,0,0,0,0,0x3ddabe16,0,0,0,0,0x3ddabe16,0,0,0,0,0x3ddabe16,
0xbda83e25,0,0,0,0,0xbda83e25,0,0,0,0,0xbda83e25,0,0,0,0,0xbda83e25,
0x3e16bdda,0,0,0,0,0x3e16bdda,0,0,0,0,0x3e16bdda,0,0,0,0,0x3e16bdda,
0xbda83e25,0,0,0,0,0xbda83e25,0,0,0,0,0xbda83e25,0,0,0,0,0xbda83e25,
0x3d65be30,0,0,0,0,0x3d65be30,0,0,0,0,0x3d65be30,0,0,0,0,0x3d65be30,
0xbce83e37,0,0,0,0,0xbce83e37,0,0,0,0,0xbce83e37,0,0,0,0,0xbce83e37,
0,0,0xbe163dda,0,0,0,0,0xbe163dda,0,0,0xbe253da8,0,0,0,0,0xbe253da8,
0,0,0xbe303d65,0,0,0,0,0xbe303d65,0,0,0xbe373ce8,0,0,0,0,0xbe373ce8,
0,0,0xbd65be30,0,0,0,0,0xbd65be30,0,0,0x3ce8be37,0,0,0,0,0x3ce8be37,
0,0,0x3ddabe16,0,0,0,0,0x3ddabe16,0,0,0x3e25bda8,0,0,0,0,0x3e25bda8,
0,0,0xbe390000,0,0,0,0,0xbe390000,0,0,0xbe37bce8,0,0,0,0,0xbe37bce8,
0,0,0xbe30bd65,0,0,0,0,0xbe30bd65,0,0,0xbe25bda8,0,0,0,0,0xbe25bda8,
0,0,0x3e390000,0,0,0,0,0x3e390000,0,0,0x3e253da8,0,0,0,0,0x3e253da8,
0,0,0x3dda3e16,0,0,0,0,0x3dda3e16,0,0,0x3ce83e37,0,0,0,0,0x3ce83e37,
0,0,0xbe16bdda,0,0,0,0,0xbe16bdda,0,0,0xbe03be03,0,0,0,0,0xbe03be03,
0,0,0xbddabe16,0,0,0,0,0xbddabe16,0,0,0xbda8be25,0,0,0,0,0xbda8be25,
0,0,0xbd653e30,0,0,0,0,0xbd653e30,0,0,0xbe033e03,0,0,0,0,0xbe033e03,
0,0,0xbe303d65,0,0,0,0,0xbe303d65,0,0,0xbe37bce8,0,0,0,0,0xbe37bce8,
0,0,0xbd65be30,0,0,0,0,0xbd65be30,0,0,0xbce8be37,0,0,0,0,0xbce8be37,
0,0,0,0,0,0,0,0,0,0,0,0,0,0,0,0,
0,0,0xbe16bdda,0,0,0,0,0xbe16bdda,0,0,0xbda8be25,0,0,0,0,0xbda8be25,
0,0,0,0,0,0,0,0,0,0,0,0,0,0,0,0,
0,0,0x3e390000,0,0,0,0,0x3e390000,0,0,0x3e033e03,0,0,0,0,0x3e033e03,
0,0,0x80003e39,0,0,0,0,0x80003e39,0,0,0xbe033e03,0,0,0,0,0xbe033e03,
0,0,0xbd653e30,0,0,0,0,0xbd653e30,0,0,0xbe373ce8,0,0,0,0,0xbe373ce8,
0,0,0xbddabe16,0,0,0,0,0xbddabe16,0,0,0x3da8be25,0,0,0,0,0x3da8be25,
0,0,0xbe390000,0,0,0,0,0xbe390000,0,0,0xbe03be03,0,0,0,0,0xbe03be03,
0,0,0x8000be39,0,0,0,0,0x8000be39,0,0,0x3e03be03,0,0,0,0,0x3e03be03,
0,0,0x3e390000,0,0,0,0,0x3e390000,0,0,0x3da83e25,0,0,0,0,0x3da83e25,
0,0,0xbdda3e16,0,0,0,0,0xbdda3e16,0,0,0xbe37bce8,0,0,0,0,0xbe37bce8,
0,0,0x3e390000,0,0,0,0,0x3e390000,0,0,0x3e033e03,0,0,0,0,0x3e033e03,
0,0,0x80003e39,0,0,0,0,0x80003e39,0,0,0xbe033e03,0,0,0,0,0xbe033e03,
0,0,0xbd65be30,0,0,0,0,0xbd65be30,0,0,0x3e03be03,0,0,0,0,0x3e03be03,
0,0,0x3e303d65,0,0,0,0,0x3e303d65,0,0,0x3ce83e37,0,0,0,0,0x3ce83e37,
0,0,0xbe390000,0,0,0,0,0xbe390000,0,0,0xbe03be03,0,0,0,0,0xbe03be03,
0,0,0,0,0,0,0,0,0,0,0,0,0,0,0,0,
0,0,0xbe163dda,0,0,0,0,0xbe163dda,0,0,0xbe25bda8,0,0,0,0,0xbe25bda8,
0,0,0,0,0,0,0,0,0,0,0,0,0,0,0,0,
0,0,0xbe16bdda,0,0,0,0,0xbe16bdda,0,0,0x3da8be25,0,0,0,0,0x3da8be25,
0,0,0x3e303d65,0,0,0,0,0x3e303d65,0,0,0xbce83e37,0,0,0,0,0xbce83e37,
0,0,0x3e16bdda,0,0,0,0,0x3e16bdda,0,0,0x3da83e25,0,0,0,0,0x3da83e25,
0,0,0xbe303d65,0,0,0,0,0xbe303d65,0,0,0xbce8be37,0,0,0,0,0xbce8be37,
0,0,0xbe390000,0,0,0,0,0xbe390000,0,0,0xbce8be37,0,0,0,0,0xbce8be37,
0,0,0x3e30bd65,0,0,0,0,0x3e30bd65,0,0,0x3da83e25,0,0,0,0,0x3da83e25,
0,0,0x3e390000,0,0,0,0,0x3e390000,0,0,0xbce83e37,0,0,0,0,0xbce83e37,
0,0,0xbe30bd65,0,0,0,0,0xbe30bd65,0,0,0x3da8be25,0,0,0,0,0x3da8be25,
0,0,0xbe163dda,0,0,0,0,0xbe163dda,0,0,0xbe03be03,0,0,0,0,0xbe03be03,
0,0,0x3ddabe16,0,0,0,0,0x3ddabe16,0,0,0x3e253da8,0,0,0,0,0x3e253da8,
0,0,0x3e163dda,0,0,0,0,0x3e163dda,0,0,0xbe033e03,0,0,0,0,0xbe033e03,
0,0,0xbddabe16,0,0,0,0,0xbddabe16,0,0,0x3e25bda8,0,0,0,0,0x3e25bda8,
0,0,0xbd653e30,0,0,0,0,0xbd653e30,0,0,0xbe37bce8,0,0,0,0,0xbe37bce8,
0,0,0,0,0,0,0,0,0,0,0,0,0,0,0,0,
0,0,0x3d653e30,0,0,0,0,0x3d653e30,0,0,0xbe373ce8,0,0,0,0,0xbe373ce8,
0,0,0,0,0,0,0,0,0,0,0,0,0,0,0,0,
0,0,0x3d653e30,0,0,0,0,0x3d653e30,0,0,0xbe37bce8,0,0,0,0,0xbe37bce8,
0,0,0x3ddabe16,0,0,0,0,0x3ddabe16,0,0,0x3da83e25,0,0,0,0,0x3da83e25,
0,0,0xbe390000,0,0,0,0,0xbe390000,0,0,0x3e03be03,0,0,0,0,0x3e03be03,
0,0,0x80003e39,0,0,0,0,0x80003e39,0,0,0xbe03be03,0,0,0,0,0xbe03be03,
0,0,0xbe390000,0,0,0,0,0xbe390000,0,0,0x3da8be25,0,0,0,0,0x3da8be25,
0,0,0x3dda3e16,0,0,0,0,0x3dda3e16,0,0,0xbe373ce8,0,0,0,0,0xbe373ce8,
0,0,0x3e390000,0,0,0,0,0x3e390000,0,0,0xbe033e03,0,0,0,0,0xbe033e03,
0,0,0x8000be39,0,0,0,0,0x8000be39,0,0,0x3e033e03,0,0,0,0,0x3e033e03,
0,0,0x3d65be30,0,0,0,0,0x3d65be30,0,0,0x3e033e03,0,0,0,0,0x3e033e03,
0,0,0xbe303d65,0,0,0,0,0xbe303d65,0,0,0x3ce8be37,0,0,0,0,0x3ce8be37,
0,0,0xbe390000,0,0,0,0,0xbe390000,0,0,0x3e03be03,0,0,0,0,0x3e03be03,
0,0,0x80003e39,0,0,0,0,0x80003e39,0,0,0xbe03be03,0,0,0,0,0xbe03be03,
0,0,0x3e163dda,0,0,0,0,0x3e163dda,0,0,0xbe253da8,0,0,0,0,0xbe253da8,
0,0,0,0,0,0,0,0,0,0,0,0,0,0,0,0,
0,0,0x3e390000,0,0,0,0,0x3e390000,0,0,0xbe033e03,0,0,0,0,0xbe033e03,
0,0,0,0,0,0,0,0,0,0,0,0,0,0,0,0,
0,0,0x3d65be30,0,0,0,0,0x3d65be30,0,0,0x3ce83e37,0,0,0,0,0x3ce83e37,
0,0,0xbddabe16,0,0,0,0,0xbddabe16,0,0,0x3e253da8,0,0,0,0,0x3e253da8,
0,0,0x3e163dda,0,0,0,0,0x3e163dda,0,0,0xbe25bda8,0,0,0,0,0xbe25bda8,
0,0,0x3e303d65,0,0,0,0,0x3e303d65,0,0,0xbe37bce8,0,0,0,0,0xbe37bce8,
0,0,0xbe390000,0,0,0,0,0xbe390000,0,0,0x3e25bda8,0,0,0,0,0x3e25bda8,
0,0,0xbdda3e16,0,0,0,0,0xbdda3e16,0,0,0x3ce8be37,0,0,0,0,0x3ce8be37,
0,0,0x3e390000,0,0,0,0,0x3e390000,0,0,0xbe373ce8,0,0,0,0,0xbe373ce8,
0,0,0x3e30bd65,0,0,0,0,0x3e30bd65,0,0,0xbe253da8,0,0,0,0,0xbe253da8,
0,0,0x3d653e30,0,0,0,0,0x3d653e30,0,0,0xbe03be03,0,0,0,0,0xbe03be03,
0,0,0x3e303d65,0,0,0,0,0x3e303d65,0,0,0xbe373ce8,0,0,0,0,0xbe373ce8,
0,0,0x3e16bdda,0,0,0,0,0x3e16bdda,0,0,0xbe033e03,0,0,0,0,0xbe033e03,
0,0,0x3ddabe16,0,0,0,0,0x3ddabe16,0,0,0xbda83e25,0,0,0,0,0xbda83e25,
0,0,0x3e16bdda,0,0,0,0,0x3e16bdda,0,0,0xbda83e25,0,0,0,0,0xbda83e25,
0,0,0,0,0,0,0,0,0,0,0,0,0,0,0,0,
0,0,0x3d65be30,0,0,0,0,0x3d65be30,0,0,0xbce83e37,0,0,0,0,0xbce83e37,
0,0,0,0,0,0,0,0,0,0,0,0,0,0,0,0,
};
constexpr unsigned long long COS_PK0 = 0x3f903f9a3fa03fa2ull;
constexpr unsigned long long COS_PK1 = 0x3f133f3e3f653f83ull;
constexpr unsigned long long COS_PK2 = 0x3e4b3ec8ull;

__device__ __forceinline__ void wgmma_ss_n80_z(float (&d)[40], uint64_t da, uint64_t db) {
  asm volatile("{\n.reg .pred p;\nsetp.ne.b32 p, 0, 0;\nwgmma.mma_async.sync.aligned.m64n80k16.f32.bf16.bf16 {%0,%1,%2,%3,%4,%5,%6,%7,%8,%9,%10,%11,%12,%13,%14,%15,%16,%17,%18,%19,%20,%21,%22,%23,%24,%25,%26,%27,%28,%29,%30,%31,%32,%33,%34,%35,%36,%37,%38,%39}, %40, %41, p, 1, 1, 1, 0;\n}\n"
    : "+f"(d[0]), "+f"(d[1]), "+f"(d[2]), "+f"(d[3]), "+f"(d[4]), "+f"(d[5]), "+f"(d[6]), "+f"(d[7]), "+f"(d[8]), "+f"(d[9]), "+f"(d[10]), "+f"(d[11]), "+f"(d[12]), "+f"(d[13]), "+f"(d[14]), "+f"(d[15]), "+f"(d[16]), "+f"(d[17]), "+f"(d[18]), "+f"(d[19]), "+f"(d[20]), "+f"(d[21]), "+f"(d[22]), "+f"(d[23]), "+f"(d[24]), "+f"(d[25]), "+f"(d[26]), "+f"(d[27]), "+f"(d[28]), "+f"(d[29]), "+f"(d[30]), "+f"(d[31]), "+f"(d[32]), "+f"(d[33]), "+f"(d[34]), "+f"(d[35]), "+f"(d[36]), "+f"(d[37]), "+f"(d[38]), "+f"(d[39])
    : "l"(da), "l"(db));
}
__device__ __forceinline__ void wgmma_ss_n80_a(float (&d)[40], uint64_t da, uint64_t db) {
  asm volatile("{\n.reg .pred p;\nsetp.ne.b32 p, 1, 0;\nwgmma.mma_async.sync.aligned.m64n80k16.f32.bf16.bf16 {%0,%1,%2,%3,%4,%5,%6,%7,%8,%9,%10,%11,%12,%13,%14,%15,%16,%17,%18,%19,%20,%21,%22,%23,%24,%25,%26,%27,%28,%29,%30,%31,%32,%33,%34,%35,%36,%37,%38,%39}, %40, %41, p, 1, 1, 1, 0;\n}\n"
    : "+f"(d[0]), "+f"(d[1]), "+f"(d[2]), "+f"(d[3]), "+f"(d[4]), "+f"(d[5]), "+f"(d[6]), "+f"(d[7]), "+f"(d[8]), "+f"(d[9]), "+f"(d[10]), "+f"(d[11]), "+f"(d[12]), "+f"(d[13]), "+f"(d[14]), "+f"(d[15]), "+f"(d[16]), "+f"(d[17]), "+f"(d[18]), "+f"(d[19]), "+f"(d[20]), "+f"(d[21]), "+f"(d[22]), "+f"(d[23]), "+f"(d[24]), "+f"(d[25]), "+f"(d[26]), "+f"(d[27]), "+f"(d[28]), "+f"(d[29]), "+f"(d[30]), "+f"(d[31]), "+f"(d[32]), "+f"(d[33]), "+f"(d[34]), "+f"(d[35]), "+f"(d[36]), "+f"(d[37]), "+f"(d[38]), "+f"(d[39])
    : "l"(da), "l"(db));
}

__device__ __forceinline__ void wgmma_rs_n40_z(float (&d)[20], uint32_t a0, uint32_t a1, uint32_t a2, uint32_t a3, uint64_t db) {
  asm volatile("{\n.reg .pred p;\nsetp.ne.b32 p, 0, 0;\nwgmma.mma_async.sync.aligned.m64n40k16.f32.bf16.bf16 {%0,%1,%2,%3,%4,%5,%6,%7,%8,%9,%10,%11,%12,%13,%14,%15,%16,%17,%18,%19}, {%20,%21,%22,%23}, %24, p, 1, 1, 0;\n}\n"
    : "+f"(d[0]), "+f"(d[1]), "+f"(d[2]), "+f"(d[3]), "+f"(d[4]), "+f"(d[5]), "+f"(d[6]), "+f"(d[7]), "+f"(d[8]), "+f"(d[9]), "+f"(d[10]), "+f"(d[11]), "+f"(d[12]), "+f"(d[13]), "+f"(d[14]), "+f"(d[15]), "+f"(d[16]), "+f"(d[17]), "+f"(d[18]), "+f"(d[19])
    : "r"(a0), "r"(a1), "r"(a2), "r"(a3), "l"(db));
}
__device__ __forceinline__ void wgmma_rs_n40_a(float (&d)[20], uint32_t a0, uint32_t a1, uint32_t a2, uint32_t a3, uint64_t db) {
  asm volatile("{\n.reg .pred p;\nsetp.ne.b32 p, 1, 0;\nwgmma.mma_async.sync.aligned.m64n40k16.f32.bf16.bf16 {%0,%1,%2,%3,%4,%5,%6,%7,%8,%9,%10,%11,%12,%13,%14,%15,%16,%17,%18,%19}, {%20,%21,%22,%23}, %24, p, 1, 1, 0;\n}\n"
    : "+f"(d[0]), "+f"(d[1]), "+f"(d[2]), "+f"(d[3]), "+f"(d[4]), "+f"(d[5]), "+f"(d[6]), "+f"(d[7]), "+f"(d[8]), "+f"(d[9]), "+f"(d[10]), "+f"(d[11]), "+f"(d[12]), "+f"(d[13]), "+f"(d[14]), "+f"(d[15]), "+f"(d[16]), "+f"(d[17]), "+f"(d[18]), "+f"(d[19])
    : "r"(a0), "r"(a1), "r"(a2), "r"(a3), "l"(db));
}

__device__ __forceinline__ void wgmma_rs_n128_z(float (&d)[64], uint32_t a0, uint32_t a1, uint32_t a2, uint32_t a3, uint64_t db) {
  asm volatile("{\n.reg .pred p;\nsetp.ne.b32 p, 0, 0;\nwgmma.mma_async.sync.aligned.m64n128k16.f32.bf16.bf16 {%0,%1,%2,%3,%4,%5,%6,%7,%8,%9,%10,%11,%12,%13,%14,%15,%16,%17,%18,%19,%20,%21,%22,%23,%24,%25,%26,%27,%28,%29,%30,%31,%32,%33,%34,%35,%36,%37,%38,%39,%40,%41,%42,%43,%44,%45,%46,%47,%48,%49,%50,%51,%52,%53,%54,%55,%56,%57,%58,%59,%60,%61,%62,%63}, {%64,%65,%66,%67}, %68, p, 1, 1, 1;\n}\n"
    : "+f"(d[0]), "+f"(d[1]), "+f"(d[2]), "+f"(d[3]), "+f"(d[4]), "+f"(d[5]), "+f"(d[6]), "+f"(d[7]), "+f"(d[8]), "+f"(d[9]), "+f"(d[10]), "+f"(d[11]), "+f"(d[12]), "+f"(d[13]), "+f"(d[14]), "+f"(d[15]), "+f"(d[16]), "+f"(d[17]), "+f"(d[18]), "+f"(d[19]), "+f"(d[20]), "+f"(d[21]), "+f"(d[22]), "+f"(d[23]), "+f"(d[24]), "+f"(d[25]), "+f"(d[26]), "+f"(d[27]), "+f"(d[28]), "+f"(d[29]), "+f"(d[30]), "+f"(d[31]), "+f"(d[32]), "+f"(d[33]), "+f"(d[34]), "+f"(d[35]), "+f"(d[36]), "+f"(d[37]), "+f"(d[38]), "+f"(d[39]), "+f"(d[40]), "+f"(d[41]), "+f"(d[42]), "+f"(d[43]), "+f"(d[44]), "+f"(d[45]), "+f"(d[46]), "+f"(d[47]), "+f"(d[48]), "+f"(d[49]), "+f"(d[50]), "+f"(d[51]), "+f"(d[52]), "+f"(d[53]), "+f"(d[54]), "+f"(d[55]), "+f"(d[56]), "+f"(d[57]), "+f"(d[58]), "+f"(d[59]), "+f"(d[60]), "+f"(d[61]), "+f"(d[62]), "+f"(d[63])
    : "r"(a0), "r"(a1), "r"(a2), "r"(a3), "l"(db));
}
__device__ __forceinline__ void wgmma_rs_n128_a(float (&d)[64], uint32_t a0, uint32_t a1, uint32_t a2, uint32_t a3, uint64_t db) {
  asm volatile("{\n.reg .pred p;\nsetp.ne.b32 p, 1, 0;\nwgmma.mma_async.sync.aligned.m64n128k16.f32.bf16.bf16 {%0,%1,%2,%3,%4,%5,%6,%7,%8,%9,%10,%11,%12,%13,%14,%15,%16,%17,%18,%19,%20,%21,%22,%23,%24,%25,%26,%27,%28,%29,%30,%31,%32,%33,%34,%35,%36,%37,%38,%39,%40,%41,%42,%43,%44,%45,%46,%47,%48,%49,%50,%51,%52,%53,%54,%55,%56,%57,%58,%59,%60,%61,%62,%63}, {%64,%65,%66,%67}, %68, p, 1, 1, 1;\n}\n"
    : "+f"(d[0]), "+f"(d[1]), "+f"(d[2]), "+f"(d[3]), "+f"(d[4]), "+f"(d[5]), "+f"(d[6]), "+f"(d[7]), "+f"(d[8]), "+f"(d[9]), "+f"(d[10]), "+f"(d[11]), "+f"(d[12]), "+f"(d[13]), "+f"(d[14]), "+f"(d[15]), "+f"(d[16]), "+f"(d[17]), "+f"(d[18]), "+f"(d[19]), "+f"(d[20]), "+f"(d[21]), "+f"(d[22]), "+f"(d[23]), "+f"(d[24]), "+f"(d[25]), "+f"(d[26]), "+f"(d[27]), "+f"(d[28]), "+f"(d[29]), "+f"(d[30]), "+f"(d[31]), "+f"(d[32]), "+f"(d[33]), "+f"(d[34]), "+f"(d[35]), "+f"(d[36]), "+f"(d[37]), "+f"(d[38]), "+f"(d[39]), "+f"(d[40]), "+f"(d[41]), "+f"(d[42]), "+f"(d[43]), "+f"(d[44]), "+f"(d[45]), "+f"(d[46]), "+f"(d[47]), "+f"(d[48]), "+f"(d[49]), "+f"(d[50]), "+f"(d[51]), "+f"(d[52]), "+f"(d[53]), "+f"(d[54]), "+f"(d[55]), "+f"(d[56]), "+f"(d[57]), "+f"(d[58]), "+f"(d[59]), "+f"(d[60]), "+f"(d[61]), "+f"(d[62]), "+f"(d[63])
    : "r"(a0), "r"(a1), "r"(a2), "r"(a3), "l"(db));
}

__device__ __forceinline__ void wgmma_rs_n32_z(float (&d)[16], uint32_t a0, uint32_t a1, uint32_t a2, uint32_t a3, uint64_t db) {
  asm volatile("{\n.reg .pred p;\nsetp.ne.b32 p, 0, 0;\nwgmma.mma_async.sync.aligned.m64n32k16.f32.bf16.bf16 {%0,%1,%2,%3,%4,%5,%6,%7,%8,%9,%10,%11,%12,%13,%14,%15}, {%16,%17,%18,%19}, %20, p, 1, 1, 0;\n}\n"
    : "+f"(d[0]), "+f"(d[1]), "+f"(d[2]), "+f"(d[3]), "+f"(d[4]), "+f"(d[5]), "+f"(d[6]), "+f"(d[7]), "+f"(d[8]), "+f"(d[9]), "+f"(d[10]), "+f"(d[11]), "+f"(d[12]), "+f"(d[13]), "+f"(d[14]), "+f"(d[15])
    : "r"(a0), "r"(a1), "r"(a2), "r"(a3), "l"(db));
}
__device__ __forceinline__ void wgmma_rs_n32_a(float (&d)[16], uint32_t a0, uint32_t a1, uint32_t a2, uint32_t a3, uint64_t db) {
  asm volatile("{\n.reg .pred p;\nsetp.ne.b32 p, 1, 0;\nwgmma.mma_async.sync.aligned.m64n32k16.f32.bf16.bf16 {%0,%1,%2,%3,%4,%5,%6,%7,%8,%9,%10,%11,%12,%13,%14,%15}, {%16,%17,%18,%19}, %20, p, 1, 1, 0;\n}\n"
    : "+f"(d[0]), "+f"(d[1]), "+f"(d[2]), "+f"(d[3]), "+f"(d[4]), "+f"(d[5]), "+f"(d[6]), "+f"(d[7]), "+f"(d[8]), "+f"(d[9]), "+f"(d[10]), "+f"(d[11]), "+f"(d[12]), "+f"(d[13]), "+f"(d[14]), "+f"(d[15])
    : "r"(a0), "r"(a1), "r"(a2), "r"(a3), "l"(db));
}

__device__ __forceinline__ void wgmma_rs_n64_z(float (&d)[32], uint32_t a0, uint32_t a1, uint32_t a2, uint32_t a3, uint64_t db) {
  asm volatile("{\n.reg .pred p;\nsetp.ne.b32 p, 0, 0;\nwgmma.mma_async.sync.aligned.m64n64k16.f32.bf16.bf16 {%0,%1,%2,%3,%4,%5,%6,%7,%8,%9,%10,%11,%12,%13,%14,%15,%16,%17,%18,%19,%20,%21,%22,%23,%24,%25,%26,%27,%28,%29,%30,%31}, {%32,%33,%34,%35}, %36, p, 1, 1, 0;\n}\n"
    : "+f"(d[0]), "+f"(d[1]), "+f"(d[2]), "+f"(d[3]), "+f"(d[4]), "+f"(d[5]), "+f"(d[6]), "+f"(d[7]), "+f"(d[8]), "+f"(d[9]), "+f"(d[10]), "+f"(d[11]), "+f"(d[12]), "+f"(d[13]), "+f"(d[14]), "+f"(d[15]), "+f"(d[16]), "+f"(d[17]), "+f"(d[18]), "+f"(d[19]), "+f"(d[20]), "+f"(d[21]), "+f"(d[22]), "+f"(d[23]), "+f"(d[24]), "+f"(d[25]), "+f"(d[26]), "+f"(d[27]), "+f"(d[28]), "+f"(d[29]), "+f"(d[30]), "+f"(d[31])
    : "r"(a0), "r"(a1), "r"(a2), "r"(a3), "l"(db));
}
__device__ __forceinline__ void wgmma_rs_n64_a(float (&d)[32], uint32_t a0, uint32_t a1, uint32_t a2, uint32_t a3, uint64_t db) {
  asm volatile("{\n.reg .pred p;\nsetp.ne.b32 p, 1, 0;\nwgmma.mma_async.sync.aligned.m64n64k16.f32.bf16.bf16 {%0,%1,%2,%3,%4,%5,%6,%7,%8,%9,%10,%11,%12,%13,%14,%15,%16,%17,%18,%19,%20,%21,%22,%23,%24,%25,%26,%27,%28,%29,%30,%31}, {%32,%33,%34,%35}, %36, p, 1, 1, 0;\n}\n"
    : "+f"(d[0]), "+f"(d[1]), "+f"(d[2]), "+f"(d[3]), "+f"(d[4]), "+f"(d[5]), "+f"(d[6]), "+f"(d[7]), "+f"(d[8]), "+f"(d[9]), "+f"(d[10]), "+f"(d[11]), "+f"(d[12]), "+f"(d[13]), "+f"(d[14]), "+f"(d[15]), "+f"(d[16]), "+f"(d[17]), "+f"(d[18]), "+f"(d[19]), "+f"(d[20]), "+f"(d[21]), "+f"(d[22]), "+f"(d[23]), "+f"(d[24]), "+f"(d[25]), "+f"(d[26]), "+f"(d[27]), "+f"(d[28]), "+f"(d[29]), "+f"(d[30]), "+f"(d[31])
    : "r"(a0), "r"(a1), "r"(a2), "r"(a3), "l"(db));
}

__device__ __forceinline__ void wgmma_ss_n32_z(float (&d)[16], uint64_t da, uint64_t db) {
  asm volatile("{\n.reg .pred p;\nsetp.ne.b32 p, 0, 0;\nwgmma.mma_async.sync.aligned.m64n32k16.f32.bf16.bf16 {%0,%1,%2,%3,%4,%5,%6,%7,%8,%9,%10,%11,%12,%13,%14,%15}, %16, %17, p, 1, 1, 1, 0;\n}\n"
    : "+f"(d[0]), "+f"(d[1]), "+f"(d[2]), "+f"(d[3]), "+f"(d[4]), "+f"(d[5]), "+f"(d[6]), "+f"(d[7]), "+f"(d[8]), "+f"(d[9]), "+f"(d[10]), "+f"(d[11]), "+f"(d[12]), "+f"(d[13]), "+f"(d[14]), "+f"(d[15])
    : "l"(da), "l"(db));
}
__device__ __forceinline__ void wgmma_ss_n32_a(float (&d)[16], uint64_t da, uint64_t db) {
  asm volatile("{\n.reg .pred p;\nsetp.ne.b32 p, 1, 0;\nwgmma.mma_async.sync.aligned.m64n32k16.f32.bf16.bf16 {%0,%1,%2,%3,%4,%5,%6,%7,%8,%9,%10,%11,%12,%13,%14,%15}, %16, %17, p, 1, 1, 1, 0;\n}\n"
    : "+f"(d[0]), "+f"(d[1]), "+f"(d[2]), "+f"(d[3]), "+f"(d[4]), "+f"(d[5]), "+f"(d[6]), "+f"(d[7]), "+f"(d[8]), "+f"(d[9]), "+f"(d[10]), "+f"(d[11]), "+f"(d[12]), "+f"(d[13]), "+f"(d[14]), "+f"(d[15])
    : "l"(da), "l"(db));
}

__device__ __forceinline__ void wgmma_ss_n40_z(float (&d)[20], uint64_t da, uint64_t db) {
  asm volatile("{\n.reg .pred p;\nsetp.ne.b32 p, 0, 0;\nwgmma.mma_async.sync.aligned.m64n40k16.f32.bf16.bf16 {%0,%1,%2,%3,%4,%5,%6,%7,%8,%9,%10,%11,%12,%13,%14,%15,%16,%17,%18,%19}, %20, %21, p, 1, 1, 1, 0;\n}\n"
    : "+f"(d[0]), "+f"(d[1]), "+f"(d[2]), "+f"(d[3]), "+f"(d[4]), "+f"(d[5]), "+f"(d[6]), "+f"(d[7]), "+f"(d[8]), "+f"(d[9]), "+f"(d[10]), "+f"(d[11]), "+f"(d[12]), "+f"(d[13]), "+f"(d[14]), "+f"(d[15]), "+f"(d[16]), "+f"(d[17]), "+f"(d[18]), "+f"(d[19])
    : "l"(da), "l"(db));
}
__device__ __forceinline__ void wgmma_ss_n40_a(float (&d)[20], uint64_t da, uint64_t db) {
  asm volatile("{\n.reg .pred p;\nsetp.ne.b32 p, 1, 0;\nwgmma.mma_async.sync.aligned.m64n40k16.f32.bf16.bf16 {%0,%1,%2,%3,%4,%5,%6,%7,%8,%9,%10,%11,%12,%13,%14,%15,%16,%17,%18,%19}, %20, %21, p, 1, 1, 1, 0;\n}\n"
    : "+f"(d[0]), "+f"(d[1]), "+f"(d[2]), "+f"(d[3]), "+f"(d[4]), "+f"(d[5]), "+f"(d[6]), "+f"(d[7]), "+f"(d[8]), "+f"(d[9]), "+f"(d[10]), "+f"(d[11]), "+f"(d[12]), "+f"(d[13]), "+f"(d[14]), "+f"(d[15]), "+f"(d[16]), "+f"(d[17]), "+f"(d[18]), "+f"(d[19])
    : "l"(da), "l"(db));
}

constexpr int NSM = 132, NH = 66;
constexpr int S0 = 0, S1 = 51200, S2 = 102400;
constexpr int C1 = 153600, C3 = C1, RG = C1 + 18432;
constexpr int WP = RG, TBL = RG + 28672, WS2 = RG + 30720;
constexpr int BARS = RG + 49152;
__host__ __device__ constexpr int wst_off(int i) { return i < 12 ? S2 + i * 4096 : WS2 + (i - 12) * 4096; }
constexpr int NBAR = 280;
constexpr int REL = BARS + NBAR * 8;
constexpr int SMEM_BYTES = REL + 16;
constexpr int B_XF = 0, B_CF1 = 15, B_CF3 = 16, B_WF = 17  , B_P1D = 18, B_REL = 21, B_ROLE = 22, B_SIG = 24;
constexpr int B_RF = 32, B_RE = 46, B_YF = 60, B_WRD = 75, B_SFREE = 89, B_WCH = 131, B_RDY = 136, B_WE = 205, B_WL = 217, B_FIN = 229, B_TOK = 232;
constexpr int R_P2 = 15, R_P3 = 57;
constexpr int CNT_P1 = 0, CNT_P2 = 4, CNT_W = 8, CNT_RANK = 9, NCLS = 10, CNT_DONE = 0, CNT_REL = 1, NCNT = 2;
constexpr int SIG_W = 0, SIG_P1 = 1, SIG_P2 = 4;
#define PFS 9088
#define T1MASK 0x3e00
#define T2MASK 0x3e00

__device__ uint4 g_scr[(14 << 21) / 16];
__device__ __align__(128) uint4 g_wf[200 * 72 * 32];
__device__ __align__(128) unsigned g_cnt[NCNT * 32];
__device__ __forceinline__ int slot_line(int chunk, int pg, int cls) {
    return (pg & 1) << 6 | (pg >> 1) << 9 | (chunk & 1) << 10 | (chunk >> 1) << 12 | ((pg ^ (pg >> 1) ^ chunk ^ (chunk >> 1) ^ cls) & 1) << 5;
}
__device__ __forceinline__ int phi_line(int phi, uint32_t rel) {
    return (phi >> 4) << 14 | (phi & 3) << 7 | ((phi >> 2) & 1) << 11 | ((phi >> 3) & 1) << 13 | ((rel >> (phi >> 4)) & 1) << 5;
}
__device__ __forceinline__ int extra_mask(int rk) { return rk < 60 ? 0 : rk < 62 ? 1 : rk < 64 ? 10 : 4; }
__device__ __forceinline__ int wslot(int pc) {
    return (int)((0x576476503421ull >> (4 * pc)) & 3) * 12288 + (((0x576476503421ull >> (4 * pc)) & 4) ? S0 : RG);
}
__device__ __forceinline__ int xslot(int n) { return ((n & 4) ? S2 : RG) + ((n + 1) & 3) * 12288; }
__device__ __forceinline__ int extra_phi(int rk) { return 198 + (rk & 1); }
__host__ __device__ constexpr int quad_off(int Q) { return (Q >> 2) * 4096 + (Q & 3) * 512; }

struct Maps { CUtensorMap w, x34, x6, x28, wst, f16, f8, y4, y2; };
struct Ptrs { char* scr; const char* wf; const void* tab1; const void* tab3; unsigned* cnt; const char* x; };

__device__ __forceinline__ uint32_t smem_u32(const void* p) { return (uint32_t)__cvta_generic_to_shared(p); }
__device__ __forceinline__ void mbar_wait(uint32_t bar) {
    uint32_t ok, it = 0;
    do {
        asm volatile("{\n.reg .pred p;\nmbarrier.try_wait.parity.shared::cta.b64 p, [%1], 0;\nselp.u32 %0, 1, 0, p;\n}" : "=r"(ok) : "r"(bar) : "memory");
        if (++it > (1u << 22)) break;
    } while (!ok);
}
__device__ __forceinline__ bool mbar_test(uint32_t bar) {
    uint32_t ok;
    asm volatile("{\n.reg .pred p;\nmbarrier.test_wait.parity.shared::cta.b64 p, [%1], 0;\nselp.u32 %0, 1, 0, p;\n}" : "=r"(ok) : "r"(bar) : "memory");
    return ok;
}
__device__ __forceinline__ void fence_async() { asm volatile("fence.proxy.async;" ::: "memory"); }
__device__ __forceinline__ void fence_async_smem() { asm volatile("fence.proxy.async.shared::cta;" ::: "memory"); }
#define ELECT "{\n.reg .pred p;\nelect.sync _|p, 0xffffffff;\n@p "
__device__ __forceinline__ void e_arrive(uint32_t bar) { asm volatile(ELECT "mbarrier.arrive.shared::cta.b64 _, [%0];\n}" :: "r"(bar) : "memory"); }
__device__ __forceinline__ void e_expect(uint32_t bar, uint32_t bytes) { asm volatile(ELECT "mbarrier.arrive.expect_tx.shared::cta.b64 _, [%0], %1;\n}" :: "r"(bar), "r"(bytes) : "memory"); }
__device__ __forceinline__ void e_g2s(uint32_t dst, const void* src, uint32_t bytes, uint32_t bar) {
    asm volatile(ELECT "cp.async.bulk.shared::cluster.global.mbarrier::complete_tx::bytes [%0], [%1], %2, [%3];\n}" :: "r"(dst), "l"(src), "r"(bytes), "r"(bar) : "memory");
}
__device__ __forceinline__ void e_s2g(void* dst, uint32_t src, uint32_t bytes) {
    asm volatile(ELECT "cp.async.bulk.global.shared::cta.bulk_group [%0], [%1], %2;\n}" :: "l"(dst), "r"(src), "r"(bytes) : "memory");
}
__device__ __forceinline__ void e_ld3(uint32_t dst, const CUtensorMap* m, int c0, int c1, int c2, uint32_t bar) {
    asm volatile(ELECT "cp.async.bulk.tensor.3d.shared::cluster.global.mbarrier::complete_tx::bytes [%0], [%1, {%3, %4, %5}], [%2];\n}"
                 :: "r"(dst), "l"(m), "r"(bar), "r"(c0), "r"(c1), "r"(c2) : "memory");
}
__device__ __forceinline__ void e_ld4(uint32_t dst, const CUtensorMap* m, int c0, int c3, uint32_t bar) {
    asm volatile(ELECT "cp.async.bulk.tensor.4d.shared::cluster.global.mbarrier::complete_tx::bytes [%0], [%1, {%3, %5, %5, %4}], [%2];\n}"
                 :: "r"(dst), "l"(m), "r"(bar), "r"(c0), "r"(c3), "r"(0) : "memory");
}
__device__ __forceinline__ void e_st3(const CUtensorMap* m, uint32_t src, int c0, int c1, int c2) {
    asm volatile(ELECT "cp.async.bulk.tensor.3d.global.shared::cta.bulk_group [%0, {%2, %3, %4}], [%1];\n}" :: "l"(m), "r"(src), "r"(c0), "r"(c1), "r"(c2) : "memory");
}
__device__ __forceinline__ void e_ld5(uint32_t dst, const CUtensorMap* m, int c4, uint32_t bar) {
    asm volatile(ELECT "cp.async.bulk.tensor.5d.shared::cluster.global.mbarrier::complete_tx::bytes [%0], [%1, {%4, %4, %4, %4, %3}], [%2];\n}"
                 :: "r"(dst), "l"(m), "r"(bar), "r"(c4), "r"(0) : "memory");
}
__device__ __forceinline__ void e_st5(const CUtensorMap* m, uint32_t src, int c4) {
    asm volatile(ELECT "cp.async.bulk.tensor.5d.global.shared::cta.bulk_group [%0, {%3, %3, %3, %3, %2}], [%1];\n}" :: "l"(m), "r"(src), "r"(c4), "r"(0) : "memory");
}
__device__ __forceinline__ void bulk_commit() { asm volatile("cp.async.bulk.commit_group;" ::: "memory"); }
template <int N> __device__ __forceinline__ void bulk_wait() { asm volatile("cp.async.bulk.wait_group %0;" :: "n"(N) : "memory"); }
template <int N> __device__ __forceinline__ void bulk_wait_read() { asm volatile("cp.async.bulk.wait_group.read %0;" :: "n"(N) : "memory"); }
__device__ __forceinline__ void wg_bar(int id) { asm volatile("bar.sync %0, 128;" :: "r"(id) : "memory"); }
__device__ __forceinline__ void bb_break(uint32_t v) { asm volatile("{\n.reg .pred p;\nsetp.eq.u32 p, %0, 0x7fc17fc1;\n@p nanosleep.u32 0;\n}" :: "r"(v) : "memory"); }
__device__ __forceinline__ uint32_t uni(uint32_t v) { return __shfl_sync(0xffffffffu, v, 0); }
__device__ __forceinline__ char* cls_cnt(char* scr, int cls) { return scr + slot_line(3, 2, cls) * 128; }
__device__ __forceinline__ uint32_t cnt_wait(const void* p, unsigned target) {
    uint32_t v = 0;
#pragma unroll 1
    for (unsigned it = 0; it < (1u << 22) && v < target; it++) {
        asm volatile("ld.acquire.gpu.global.u32 %0, [%1];" : "=r"(v) : "l"(p) : "memory");
        v = uni(v);
    }
    asm volatile("fence.proxy.async.global;" ::: "memory");
    return v;
}
__device__ __forceinline__ void wg_fence() { asm volatile("wgmma.fence.sync.aligned;" ::: "memory"); }
__device__ __forceinline__ void wg_commit() { asm volatile("wgmma.commit_group.sync.aligned;" ::: "memory"); }
template <int N> __device__ __forceinline__ void wg_wait() { asm volatile("wgmma.wait_group.sync.aligned %0;" :: "n"(N) : "memory"); }
template <int N> __device__ __forceinline__ void reg_fence(float (&d)[N]) {
#pragma unroll
    for (int i = 0; i < N; i++) asm volatile("" : "+f"(d[i]) :: "memory");
}
template <int N> __device__ __forceinline__ void zero(float (&d)[N]) {
#pragma unroll
    for (int i = 0; i < N; i++) d[i] = 0.f;
}
__device__ __forceinline__ uint32_t pack2(float lo, float hi) {
    uint32_t r; asm volatile("cvt.rn.bf16x2.f32 %0, %1, %2;" : "=r"(r) : "f"(hi), "f"(lo)); return r;
}
__device__ __forceinline__ void stm4(uint32_t a, uint32_t r0, uint32_t r1, uint32_t r2, uint32_t r3) {
    asm volatile("stmatrix.sync.aligned.m8n8.x4.trans.shared.b16 [%0], {%1,%2,%3,%4};" :: "r"(a), "r"(r0), "r"(r1), "r"(r2), "r"(r3) : "memory");
}
__device__ __forceinline__ void stm2(uint32_t a, uint32_t r0, uint32_t r1) {
    asm volatile("stmatrix.sync.aligned.m8n8.x2.trans.shared.b16 [%0], {%1,%2};" :: "r"(a), "r"(r0), "r"(r1) : "memory");
}
struct Desc {
    uint32_t lo, hi;
    __device__ __forceinline__ operator uint64_t() const { return ((uint64_t)hi << 32) | lo; }
    __device__ __forceinline__ Desc operator+(uint32_t o) const { return Desc{lo + o, hi}; }
    __device__ __forceinline__ Desc operator^(uint32_t o) const { return Desc{lo ^ o, hi}; }
};
__device__ __forceinline__ Desc mkdesc(uint32_t addr, uint32_t lbo, uint32_t sbo, uint32_t swz) {
    return Desc{((addr & 0x3FFFF) >> 4) | ((lbo >> 4) << 16), (sbo >> 4) | (swz << 30)};
}
__device__ __forceinline__ uint32_t cos_bits(int k) {
    if (k > 20) k = 40 - k;
    const bool neg = k > 10;
    if (neg) k = 20 - k;
    const unsigned long long pk = k < 4 ? COS_PK0 : k < 8 ? COS_PK1 : COS_PK2;
    return (uint32_t)((pk >> (16 * (k & 3))) & 0xffff) ^ (neg ? 0x8000u : 0u);
}

__device__ __forceinline__ void task_w(int wg, int k, uint32_t sb) {
    const int tid = threadIdx.x & 127, w = uni(tid >> 5), lane = tid & 31, q = lane & 3;
    const int tb = 14 * k, t1 = min(tb + 14, 1800), cb0 = tb / 25;
    float acc[64];
    zero(acc);
    const int oc0 = tb - 25 * cb0, Lt = t1 - tb, L0 = min(Lt, 25 - oc0), n0 = (L0 + 3) >> 2;
    uint32_t a[2][4][4];
    auto gen = [&](uint32_t (&a)[4][4], int at) {
        const int phi = 8 * ((at < n0 ? oc0 + 4 * at : 4 * (at - n0)) + w) + (lane >> 2), f = (phi * 205) >> 12;
        const uint32_t ca = 8 * f + 4, cw = (phi - 20 * f) * 8, p0 = sb + TBL + cw * 2 * q;
#pragma unroll
        for (int kh = 0; kh < 7; kh++) {
            uint32_t v0, v1;
            asm volatile("ld.shared.u32 %0, [%1];" : "=r"(v0) : "r"(p0 + ca * kh));
            asm volatile("ld.shared.u32 %0, [%1];" : "=r"(v1) : "r"(p0 + cw + ca * kh));
            const int h = kh == 6 ? 1 : kh & 1;
            a[kh >> 1][2 * h] = __byte_perm(v0, v1, 0x5410);
            a[kh >> 1][2 * h + 1] = __byte_perm(v0, v1, 0x7632);
        }
        a[3][0] = 0; a[3][1] = 0;
    };
    gen(a[0], wg);
    if (wg) gen(a[1], wg + 2);
#pragma unroll 1
    for (int n = 0; n < 2; n++) {
        const int at = wg + 2 * n, i0 = at < n0 ? 4 * at : L0 + 4 * (at - n0), cnt = (at < n0 ? L0 : Lt) - i0, cb = cb0 + (at >= n0);
        if (cnt <= 0 || (n && !wg)) break;
        if (n) {
#pragma unroll
            for (int j = 0; j < 16; j++) a[0][j >> 2][j & 3] = a[1][j >> 2][j & 3];
        }
        const Desc dB = mkdesc(sb + WP + (cb - cb0) * 14336, 3584, 512, 2);
        if (at) mbar_wait(sb + BARS + 8 * (B_WCH + at - 1));
        mbar_wait(sb + BARS + 8 * (B_WF + 2 * (cb - cb0)));
        wg_fence();
        wgmma_rs_n128_z(acc, a[0][0][0], a[0][0][1], a[0][0][2], a[0][0][3], dB);
        wgmma_rs_n128_a(acc, a[0][1][0], a[0][1][1], a[0][1][2], a[0][1][3], dB + (uint32_t)(16 * 64 >> 4));
        wgmma_rs_n128_a(acc, a[0][2][0], a[0][2][1], a[0][2][2], a[0][2][3], dB + (uint32_t)(32 * 64 >> 4));
        wgmma_rs_n128_a(acc, a[0][3][0], a[0][3][1], a[0][3][2], a[0][3][3], dB + (uint32_t)(40 * 64 >> 4));
        wg_commit();
        wg_wait<0>();
        reg_fence(acc);
        e_arrive(sb + BARS + 8 * (B_WCH + at));
        if (w < cnt) {
            const uint32_t dst = sb + wst_off(i0 + w) + (lane >> 2) * 512 + (lane & 4) * 16 + ((q ^ cb) & 3) * 16;
#pragma unroll
            for (int j = 0; j < 4; j++)
#pragma unroll
                for (int e = 0; e < 2; e++)
                    asm volatile("st.shared.v4.u32 [%0], {%1,%2,%3,%4};" :: "r"((dst ^ (e * 64)) + j * 128),
                                 "r"(pack2(acc[4 * j + e], acc[16 + 4 * j + e])), "r"(pack2(acc[4 * j + 2 + e], acc[16 + 4 * j + 2 + e])),
                                 "r"(pack2(acc[32 + 4 * j + e], acc[48 + 4 * j + e])), "r"(pack2(acc[32 + 4 * j + 2 + e], acc[48 + 4 * j + 2 + e])) : "memory");
            fence_async_smem();
            e_arrive(sb + BARS + 8 * (B_WRD + i0 + w));
        }
    }
}

__device__ __forceinline__ void task_p1(int wg, int pair, uint32_t sb) {
    const int tid = threadIdx.x & 127, w = tid >> 5, lane = tid & 31;
    const uint32_t buf = sb + wg * 51200, bars = sb + BARS;
    uint32_t fr[5][10][2];
    float A[40], d[20];
    zero(A);
    {
        const Desc dA = mkdesc(buf, 3584, 512, 2), dB = mkdesc(sb + C1, 128, 256, 0);
        auto issue = [&](int g, float (&d)[40]) {
            mbar_wait(bars + 8 * (B_XF + wg * 5 + g));
            wg_fence();
            wgmma_ss_n80_z(d, dA + (uint32_t)(g * 8704 >> 4), dB);
#pragma unroll
            for (int j = 1; j < 5; j++) wgmma_ss_n80_a(d, dA + (uint32_t)((g * 8704 + j * 1024) >> 4), dB + (uint32_t)(j * 2560 >> 4));
            wg_commit();
        };
        auto pack = [&](int g, float (&d)[40]) {
            reg_fence(d);
#pragma unroll
            for (int f = 0; f < 10; f++) {
                fr[g][f][0] = pack2(d[4 * f], d[4 * f + 1]);
                fr[g][f][1] = pack2(d[4 * f + 2], d[4 * f + 3]);
            }
        };
        mbar_wait(bars + 8 * B_CF1);
#pragma unroll
        for (int g = 0; g < 4; g++) { issue(g, A); wg_wait<0>(); pack(g, A); }
        zero(d);
        mbar_wait(bars + 8 * (B_XF + wg * 5 + 4));
#pragma unroll
        for (int h = 0; h < 2; h++) {
            wg_fence();
            wgmma_ss_n40_z(d, dA + (uint32_t)(4 * 8704 >> 4), dB + (uint32_t)(h * 1280 >> 4));
#pragma unroll
            for (int j = 1; j < 5; j++) wgmma_ss_n40_a(d, dA + (uint32_t)((4 * 8704 + j * 1024) >> 4), dB + (uint32_t)((j * 2560 + h * 1280) >> 4));
            wg_commit(); wg_wait<0>(); reg_fence(d);
#pragma unroll
            for (int f = 0; f < 5; f++) { fr[4][5 * h + f][0] = pack2(d[4 * f], d[4 * f + 1]); fr[4][5 * h + f][1] = pack2(d[4 * f + 2], d[4 * f + 3]); }
        }
    }
    bb_break(sb);
    wg_bar(1 + wg);
    {
        const Desc dB = mkdesc(sb + C1 + 12800, 128, 256, 0);
        const int i = lane & 7, mi = lane >> 3, th = w >> 1, tz = (2 * pair + th) & 3;
        const uint32_t s0 = buf + (i >> 1) * 128 + (i & 1) * 64 + (((2 * (w & 1) + (mi & 1)) ^ tz ^ (i >> 1)) << 4);
        const uint32_t sA = s0 + th * 2048 + (mi >> 1) * 512, sB = s0 + th * 2048 + (mi >> 1) * 2560, sC = s0 + th * 1024 + (mi >> 1) * 512;
        auto issue = [&](int f, float (&d)[20]) {
            wg_fence();
            wgmma_rs_n40_z(d, fr[0][f][0], fr[0][f][1], fr[1][f][0], fr[1][f][1], dB);
            wgmma_rs_n40_a(d, fr[2][f][0], fr[2][f][1], fr[3][f][0], fr[3][f][1], dB + (uint32_t)(1280 >> 4));
            wgmma_rs_n40_a(d, fr[4][f % 5][0], fr[4][f % 5][1], fr[4][f % 5 + 5][0], fr[4][f % 5 + 5][1], dB + (uint32_t)((2560 + (f / 5) * 1280) >> 4));
            wg_commit();
        };
#pragma unroll
        for (int f = 0; f < 10; f++) {
            issue(f, d);
            if (f && !(f & 1)) { fence_async_smem(); e_arrive(bars + 8 * (B_RDY + wg * 5 + (f >> 1) - 1)); }
            wg_wait<0>(); reg_fence(d);
            const int Q = 5 * f;
            stm4(((Q & 3) == 3 ? sB : sA) + quad_off(Q), pack2(d[0], d[1]), pack2(d[2], d[3]), pack2(d[4], d[5]), pack2(d[6], d[7]));
            stm2(sA + quad_off(Q + 2), pack2(d[8], d[9]), pack2(d[10], d[11]));
            stm4((f == 9 ? sC : ((Q + 3) & 3) == 3 ? sB : sA) + quad_off(Q + 3), pack2(d[12], d[13]), pack2(d[14], d[15]), pack2(d[16], d[17]), pack2(d[18], d[19]));
            if (f == 9) { fence_async_smem(); e_arrive(bars + 8 * (B_RDY + wg * 5 + (f >> 1))); }
        }
    }
}

__device__ __forceinline__ void task_p2(int wg, int rk, uint32_t sb) {
    const int tid = threadIdx.x & 127, w = tid >> 5, lane = tid & 31;
    const uint32_t bars = sb + BARS;
    const int phi0 = 3 * rk, phiE = extra_phi(rk), mE = extra_mask(rk);
    uint4 wA[6], wB[6], wC[6], wE[6];
    auto ldw = [&](uint4 (&a)[6], int j, int phi) {
        const int pc = 3 * j + wg;
        const uint32_t p = sb + wslot(pc) + (lane & 3) * 512 + w * 128 + (((lane >> 2) ^ phi) & 1) * 64 + (((lane >> 3) ^ lane) & 3) * 16 + (phi & 1) * 8;
        mbar_wait(bars + 8 * (B_WL + pc));
#pragma unroll
        for (int s = 0; s < 6; s++) {
            asm volatile("ld.shared.v2.u32 {%0, %1}, [%2];" : "=r"(a[s].x), "=r"(a[s].y) : "r"(p + s * 2048) : "memory");
            asm volatile("ld.shared.v2.u32 {%0, %1}, [%2];" : "=r"(a[s].z), "=r"(a[s].w) : "r"((p ^ 8) + s * 2048) : "memory");
        }
        uint32_t dep = 0;
#pragma unroll
        for (int s = 0; s < 6; s++) dep |= a[s].x ^ a[s].z;
        if (__any_sync(0xffffffffu, dep == 0x7fc17fc1u)) __nanosleep(0);
        e_arrive(bars + 8 * (B_WE + pc));
    };
    ldw(wA, 0, phi0); ldw(wB, 1, phi0 + 1);
    mbar_wait(bars + 8 * (B_SIG + SIG_P1 + 1));
    const int i = lane & 7, mi = lane >> 3;
    const uint32_t soff = sb + S1 + wg * 4096 + mi * 512 + (i >> 1) * 128 + (i & 1) * 64;
    const int xo = w ^ (i >> 1);
    float d[32];
    zero(d);
    int n = 0;
    uint32_t xb = ((sb + xslot(0)) & 0x3FFFF) >> 4 | 1u << 16, mb = bars + 8 * wg;
    bool landed = false;
    auto unit = [&](const uint4 (&a)[6], int z) {
        const Desc d0{xb + (z & 2), (512u >> 4) | (2u << 30)}, d1 = d0 ^ 2u;
        if (!landed) mbar_wait(bars + 8 * (B_RF + n));
        mbar_wait(mb + 8 * (B_TOK - 1));
        wg_fence();
        wgmma_rs_n64_z(d, a[0].x, a[0].y, a[0].z, a[0].w, d0);
        wgmma_rs_n64_a(d, a[1].x, a[1].y, a[1].z, a[1].w, d1);
        e_arrive(bars + 8 * (n ? B_RE + n - 1 : B_RE + 13));
        const bool sfree = mbar_test(n >= 4 ? mb + 8 * (B_SFREE - 12) : bars + 8 * (B_TOK - 1));
        landed = mbar_test(bars + 8 * (B_RF + n + 1));
        wgmma_rs_n64_a(d, a[2].x, a[2].y, a[2].z, a[2].w, d0 + (uint32_t)(4096 >> 4));
        wgmma_rs_n64_a(d, a[3].x, a[3].y, a[3].z, a[3].w, d1 + (uint32_t)(4096 >> 4));
        e_arrive(mb + 8 * B_TOK);
        wgmma_rs_n64_a(d, a[4].x, a[4].y, a[4].z, a[4].w, d0 + (uint32_t)(8192 >> 4));
        wgmma_rs_n64_a(d, a[5].x, a[5].y, a[5].z, a[5].w, d1 + (uint32_t)(8192 >> 4));
        wg_commit();
        if (!sfree) mbar_wait(mb + 8 * (B_SFREE - 12));
        const uint32_t a0 = soff + (n & 3) * 12288 + ((xo ^ z) << 4);
        n++;
        xb = ((sb + xslot(n)) & 0x3FFFF) >> 4 | 1u << 16;
        wg_wait<0>();
        reg_fence(d);
        uint32_t p[8];
#pragma unroll
        for (int j = 0; j < 8; j++) p[j] = pack2(d[4 * j] - d[4 * j + 3], d[4 * j + 2] + d[4 * j + 1]);
        stm4(a0, p[0], p[1], p[2], p[3]);
        stm4(a0 + 2048, p[4], p[5], p[6], p[7]);
        fence_async_smem();
        e_arrive(mb + 8 * (B_RDY + R_P2));
        mb += 24;
    };
    const int zA = phi0 & 3, zB = (phi0 + 1) & 3, zC = (phi0 + 2) & 3, zE = phiE & 3;
#pragma unroll 1
    for (int it = 0; it < 4; it++) {
        unit(wA, zA);
        unit(wB, zB);
        if (it == 0) ldw(wC, 2, phi0 + 2);
        unit(wC, zC);
        if (it == 0 && mE) ldw(wE, 3, phiE);
        if (mE >> it & 1) unit(wE, zE);
    }
}

__device__ __forceinline__ void task_p3(int wg, int pair, uint32_t sb) {
    const int tid = threadIdx.x & 127, w = tid >> 5, lane = tid & 31;
    const uint32_t buf = sb + (wg ? 3 - wg : 0) * 51200, bars = sb + BARS;
    uint32_t fr[10][4][2];
    float acc[2][16];
    zero(acc[0]); zero(acc[1]);
    {
        const Desc dB = mkdesc(sb + C3, 128, 256, 0);
        const uint32_t a0 = (buf & 0x3FFFF) >> 4;
        auto dq = [&](int Q) {
            return Desc{a0 + (uint32_t)((quad_off(Q) >> 4) | ((Q < 48 ? 2048 : 1024) >> 4) << 16), (uint32_t)((quad_off(Q + 1) - quad_off(Q)) >> 4) | (2u << 30)};
        };
        auto issue = [&](int f) {
            if (!(f & 1)) mbar_wait(bars + 8 * (B_YF + wg * 5 + (f >> 1)));
            wg_fence();
            wgmma_ss_n32_z(acc[f & 1], dq(5 * f), dB);
            wgmma_ss_n32_a(acc[f & 1], dq(5 * f + 1), dB + (uint32_t)(1024 >> 4));
            wgmma_ss_n32_a(acc[f & 1], dq(5 * f + 3), dB + (uint32_t)(2048 >> 4));
            wg_commit();
        };
        mbar_wait(bars + 8 * B_CF3);
        issue(0);
#pragma unroll
        for (int f = 0; f < 10; f++) {
            if (f < 9) { issue(f + 1); wg_wait<1>(); } else wg_wait<0>();
            float (&d)[16] = acc[f & 1];
            reg_fence(d);
#pragma unroll
            for (int g = 0; g < 4; g++) { fr[f][g][0] = pack2(d[4 * g], d[4 * g + 1]); fr[f][g][1] = pack2(d[4 * g + 2], d[4 * g + 3]); }
        }
    }
    {
        const Desc dB = mkdesc(sb + C3 + 3072, 128, 256, 0);
        const int i = lane & 7, mi = lane >> 3, th = w >> 1, tz = (2 * pair + th) & 3;
        const int oct = (2 * (w & 1) + (mi & 1)) ^ tz;
        const uint32_t soff = buf + th * 3584 + (mi >> 1) * 512 + i * 64 + ((oct ^ (i >> 1)) << 4);
        auto mma = [&](int t, int s) {
            if (t > 6) return;
            const int g = t < 6 ? 1 + (t >> 1) : 0;
            const uint32_t o = t < 6 ? (t & 1) * 1024 : 8960, st = t < 6 ? 1792 : 1024;
            if (s == 0) { wg_fence(); wgmma_rs_n32_z(acc[t & 1], fr[0][g][0], fr[0][g][1], fr[1][g][0], fr[1][g][1], dB + (o >> 4)); }
            else wgmma_rs_n32_a(acc[t & 1], fr[2 * s][g][0], fr[2 * s][g][1], fr[2 * s + 1][g][0], fr[2 * s + 1][g][1], dB + ((o + s * st) >> 4));
            if (s == 4) wg_commit();
        };
        const int row = th * 14 + 4 * (mi >> 1) + (i >> 1);
        const uint32_t z0 = buf + row * 128 + (i & 1) * 64 + ((oct ^ (row & 3)) << 4), z1 = (lane & 20) == 20 ? buf + 4096 + lane * 16 : z0 + 1024;
        bb_break(sb);
#pragma unroll
        for (int s = 0; s < 5; s++) mma(0, s);
        wg_bar(1 + wg);
#pragma unroll
        for (int t = 0; t < 7; t++) {
#pragma unroll
            for (int s = 0; s < 2; s++) mma(t + 1, s);
            if (t < 6) { wg_commit(); wg_wait<1>(); } else wg_wait<0>();
            float (&d)[16] = acc[t & 1];
            reg_fence(d);
            const uint32_t a = soff + (1 + (t >> 1)) * 7168 + (t & 1) * 2048;
            stm4(t < 6 ? a : z0, pack2(d[0], d[1]), pack2(d[2], d[3]), pack2(d[4], d[5]), pack2(d[6], d[7]));
            mma(t + 1, 2);
            if (t & 1) stm2(a + 1024, pack2(d[8], d[9]), pack2(d[10], d[11]));
            else stm4(t < 6 ? a + 1024 : z1, pack2(d[8], d[9]), pack2(d[10], d[11]), pack2(d[12], d[13]), pack2(d[14], d[15]));
#pragma unroll
            for (int s = 3; s < 5; s++) mma(t + 1, s);
            if ((t & 1) || t == 6) { fence_async_smem(); e_arrive(bars + 8 * (B_RDY + R_P3 + wg * 4 + (t >> 1))); }
        }
    }
}

__device__ __forceinline__ void load_x(int cls, int rk, int u, uint32_t sb, const Maps& mp) {
    const int id = u * NH + rk, pl = id / 3, c0 = 32 * (id - 3 * pl), tp = cls * 4 + (pl >> 4), col = 14 * (pl & 15) - 8;
    const uint32_t bar = sb + BARS + 8 * (B_XF + u * 5), dst = sb + u * 51200;
    const int wrap = col < 0 ? 224 : 0;
    if (tp) {
#pragma unroll
        for (int g = 0; g < 5; g++) e_ld3(dst + g * 8704, &mp.x34, c0, col + 4 * g + (g < 2 ? wrap : 0), 28 * tp - 6, bar + 8 * g);
    } else {
#pragma unroll
        for (int g = 0; g < 5; g++) {
            e_ld3(dst + g * 8704, &mp.x6, c0, col + 4 * g + (g < 2 ? wrap : 0), 218, bar + 8 * g);
            e_ld3(dst + g * 8704 + 1536, &mp.x28, c0, col + 4 * g + (g < 2 ? wrap : 0), 0, bar + 8 * g);
        }
    }
}

__device__ __forceinline__ void load_x_box(int cls, int rk, int u, int g, uint32_t sb, const Maps& mp) {
    const int id = u * NH + rk, pl = id / 3, c0 = 32 * (id - 3 * pl), tp = cls * 4 + (pl >> 4), col = 14 * (pl & 15) - 8 + 4 * g;
    e_ld3(sb + u * 51200 + g * 8704, &mp.x34, c0, col < 0 ? col + 224 : col, 28 * tp - 6, sb + BARS + 8 * (B_XF + u * 5 + g));
}

__device__ __forceinline__ void load_first(uint32_t sb, const Maps& mp, const Ptrs& pt) {
    const uint32_t bars = sb + BARS;
    const int k = blockIdx.x;
    if (k < 129) {
        const int cb0 = 14 * k / 25, cb1 = min((14 * k + 13) / 25, 71);
#pragma unroll 1
        for (int cb = cb0; cb <= cb1; cb++) {
            const int b = cb / 24, i0 = 16 * ((cb >> 2) - 6 * b) + 2 * (cb & 3);
            const uint32_t bar = bars + 8 * (B_WF + 2 * (cb - cb0));
            e_expect(bar, 14336);
            e_ld4(sb + WP + (cb - cb0) * 14336, &mp.w, 32 * b, i0, bar);
            e_ld4(sb + WP + (cb - cb0) * 14336 + 7168, &mp.w, 32 * b, i0 + 8, bar);
        }
    }
    asm volatile(ELECT "cp.async.bulk.prefetch.L2.global [%0], %1;\n}" :: "l"(pt.x + (k & 1) * (112 * 43008) + (k >> 1) * PFS), "n"(PFS) : "memory");
    e_expect(bars + 8 * B_CF1, 17920); e_g2s(sb + C1, pt.tab1, 17920, bars + 8 * B_CF1);
    if ((threadIdx.x & 31) < 15) asm volatile("mbarrier.arrive.expect_tx.shared::cta.b64 _, [%0], 8704;" :: "r"(bars + 8 * (B_XF + (threadIdx.x & 31))) : "memory");
    __syncwarp();
}

__device__ __forceinline__ uint32_t get_rel(uint32_t sb) {
    mbar_wait(sb + BARS + 8 * B_REL);
    uint32_t v; asm volatile("ld.shared.u32 %0, [%1];" : "=r"(v) : "r"(sb + REL) : "memory");
    return uni(v);
}

__device__ __forceinline__ void load_warp(int cls, int rk, uint32_t sb, const Ptrs& pt) {
    const uint32_t bars = sb + BARS;
    mbar_wait(bars + 8 * (B_SIG + SIG_P1));
    const uint32_t rel = get_rel(sb);
    const char* cnt = cls_cnt(pt.scr, cls);
    const int mE = extra_mask(rk);
    const int lpA = phi_line(3 * rk, rel), lpB = phi_line(3 * rk + 1, rel), lpC = phi_line(3 * rk + 2, rel), lpE = phi_line(extra_phi(rk), rel);
    e_arrive(bars + 8 * (B_TOK - 1));
    if ((threadIdx.x & 31) < 14) asm volatile("mbarrier.arrive.expect_tx.shared::cta.b64 _, [%0], 12288;" :: "r"(bars + 8 * (B_RF + (threadIdx.x & 31))) : "memory");
    __syncwarp();
    int n = 0;
#pragma unroll 1
    for (int pg = 0; pg < 4; pg++) {
        const int l0 = slot_line(0, pg, cls), l1 = slot_line(1, pg, cls), l2 = slot_line(2, pg, cls);
        auto unit = [&](int lp) {
            const uint32_t bar = bars + 8 * (B_RF + n), dst = sb + xslot(n);
            mbar_wait(bars + 8 * (n >= 8 ? B_RE + n - 8 : n >= 4 ? B_SIG + SIG_P1 + (rk < 60 ? 2 : 1) : B_WE + ((0x4310 >> (4 * n)) & 15)));
            e_g2s(dst, pt.scr + (size_t)(lp ^ l0) * 128, 4096, bar);
            e_g2s(dst + 4096, pt.scr + (size_t)(lp ^ l1) * 128, 4096, bar);
            e_g2s(dst + 8192, pt.scr + (size_t)(lp ^ l2) * 128, 4096, bar);
            n++;
        };
        cnt_wait(cnt + (CNT_P1 + pg) * 128, 48);
        unit(lpA); unit(lpB); unit(lpC);
        if (mE >> pg & 1) unit(lpE);
        if (pg == 1) { mbar_wait(bars + 8 * B_P1D); e_expect(bars + 8 * B_CF3, 17152); e_g2s(sb + C3, pt.tab3, 17152, bars + 8 * B_CF3); }
    }
}

__device__ __forceinline__ int near_page(char* p) {
#pragma unroll
    for (int e = 0; e < 4; e++) asm volatile("st.relaxed.gpu.global.v4.u32 [%0], {%1, %1, %1, %1};" :: "l"(p + (e >> 1) * 4096 + (e & 1) * 16), "r"(0) : "memory");
    uint32_t v0, v1, t0, t1;
    asm volatile("atom.relaxed.gpu.global.exch.b32 %0, [%1], 1;" : "=r"(v0) : "l"(p) : "memory");
    asm volatile("atom.relaxed.gpu.global.exch.b32 %0, [%1], 1;" : "=r"(v1) : "l"(p + 4096) : "memory");
    asm volatile("{\n.reg .pred p;\nsetp.ne.u32 p, %1, 0xffffffff;\nmov.u32 %0, 0;\n@p mov.u32 %0, %%clock;\n}" : "=r"(t0) : "r"(v0) : "memory");
    asm volatile("{\n.reg .pred p;\nsetp.ne.u32 p, %1, 0xffffffff;\nmov.u32 %0, 0;\n@p mov.u32 %0, %%clock;\n}" : "=r"(t1) : "r"(v1) : "memory");
    return t1 - t0 < 80;
}

__device__ __forceinline__ uint32_t find_role(uint32_t sb, char* scr) {
    const int k = blockIdx.x;
    int c = near_page(scr + (slot_line(3, 3, 0) + phi_line(1 + (k >> 5), 0) + (k & 31)) * 128);
    int r;
    asm volatile("atom.relaxed.gpu.global.add.u32 %0, [%1], 1;" : "=r"(r) : "l"(cls_cnt(scr, c) + CNT_RANK * 128) : "memory");
    asm volatile("st.shared.u32 [%0], %1;" :: "r"(sb + REL + 8), "r"(c) : "memory");
    if (r >= NH) { c ^= 1; r = NSM - 1 - r; }
    asm volatile("st.shared.u32 [%0], %1;" :: "r"(sb + REL + 4), "r"(c << 8 | r) : "memory");
    return c << 8 | r;
}
__device__ __forceinline__ void get_role(uint32_t sb, int& cls, int& rk) {
    mbar_wait(sb + BARS + 8 * B_ROLE);
    uint32_t v; asm volatile("ld.shared.u32 %0, [%1];" : "=r"(v) : "r"(sb + REL + 4) : "memory");
    v = uni(v); cls = v >> 8; rk = v & 255;
}

__device__ __forceinline__ void load3_warp(int cls, int rk, uint32_t sb, const Maps& mp, const Ptrs& pt) {
    const uint32_t bars = sb + BARS;
    mbar_wait(bars + 8 * B_XF);
    const uint32_t rel = cnt_wait(pt.cnt + CNT_REL * 32, 12u << 16);
    asm volatile("st.shared.u32 [%0], %1;" :: "r"(sb + REL), "r"(rel) : "memory");
    __syncwarp();
    e_arrive(bars + 8 * B_REL);
    mbar_wait(bars + 8 * (B_SIG + SIG_W));
    cnt_wait(cls_cnt(pt.scr, cls) + CNT_W * 128, NSM);
    {
        const int np = rk >= 60 ? 12 : 9;
#pragma unroll 1
        for (int o = 0; o < np; o++) {
            const int pc = (0xba9876524310ull >> (4 * o)) & 15;
            if (o == 4) mbar_wait(bars + 8 * (B_SIG + SIG_P1));
            if (o >= 8) mbar_wait(bars + 8 * (B_WE + ((0x5762 >> (4 * (o - 8))) & 15)));
            if (o >= 4) mbar_wait(bars + 8 * (B_WL + ((0xba9876524310ull >> (4 * (o - 4))) & 15)));
            e_expect(bars + 8 * (B_WL + pc), 12288);
            e_g2s(sb + wslot(pc), pt.wf + (pc < 9 ? 9 * rk + pc : 3 * extra_phi(rk) + pc - 9) * 12288, 12288, bars + 8 * (B_WL + pc));
        }
        if (np == 12) { mbar_wait(bars + 8 * (B_WE + 9)); mbar_wait(bars + 8 * (B_WE + 10)); mbar_wait(bars + 8 * (B_WE + 11)); }
    }
    mbar_wait(bars + 8 * (B_SIG + SIG_P2 + 1));
    const int nu = rk < 60 ? 3 : 2;
#pragma unroll 1
    for (int u = 0; u < nu; u++) {
        const int id = u * NH + rk, pl = id / 3, chunk = id - 3 * pl;
        const int l0 = slot_line(chunk, pl >> 4, cls) + (pl & 15) * 2;
        const uint32_t buf = sb + (u ? 3 - u : 0) * 51200, bar = bars + 8 * (B_YF + u * 5);
#pragma unroll
        for (int j = 0; j < 5; j++) e_expect(bar + 8 * j, j == 4 ? 10240 : (j & 1) ? 8192 : 12288);
        if (u) mbar_wait(bars + 8 * (B_SIG + SIG_P2 + 3));
        cnt_wait(cls_cnt(pt.scr, cls) + (CNT_P2 + (pl >> 4)) * 128, NH);
        if (u == nu - 1) e_arrive(bars + 8 * B_FIN);
        const uint32_t r2 = uni(rel) << 5;
#pragma unroll
        for (int G = 0; G < 13; G++)
            e_ld5(buf + G * 4096, G < 12 ? &mp.f16 : &mp.f8, (l0 ^ ((r2 >> G) & 32)) + (G << 14), bar + 8 * ((2 * G) / 5));
    }
}

__device__ __forceinline__ void store_warp(uint32_t sb, const Maps& mp, const Ptrs& pt) {
    const uint32_t bars = sb + BARS;
    const int k = blockIdx.x;
    uint32_t pa = 0, pb = 0, qa = 0, qb = 0;
    auto arr2 = [&](uint32_t& a, uint32_t& b) { if (a) e_arrive(a); if (b) e_arrive(b); a = b = 0; };
    auto pre = [&](int idx) {
        const uint32_t bar = bars + 8 * idx;
        if ((pb | qb) && !mbar_test(bar)) { bulk_wait<0>(); arr2(qa, qb); arr2(pa, pb); }
        mbar_wait(bar);
    };
    auto post = [&](uint32_t fr) {
        bulk_commit(); bulk_wait_read<2>();
        if (qb) bulk_wait<2>();
        arr2(qa, qb); qa = pa; qb = pb; pb = 0; pa = fr;
    };
    auto after = [&](int sig) { pb = bars + 8 * (B_SIG + sig); };
    int cls, rk; get_role(sb, cls, rk);
    {
        int cb = 14 * k / 25, oc = 14 * k - 25 * cb;
        int g1 = 0;
#pragma unroll 1
        for (int i = 0; i < 14 && cb < 72; i++) {
            pre(B_WRD + i);
            e_st3(&mp.wst, sb + wst_off(i), 0, 8 * oc, cb);
            post(0);
            if (T1MASK >> i & 1) load_x_box(cls, rk, 1, g1++, sb, mp);
            if (++oc == 25) { oc = 0; cb++; }
        }
#pragma unroll 1
        for (; g1 < 5; g1++) load_x_box(cls, rk, 1, g1, sb, mp);
        after(SIG_W);
    }
    pre(B_REL);
    const uint32_t rel = get_rel(sb);
    const int nu = rk < 60 ? 3 : 2;
    int g2 = 0;
#pragma unroll 1
    for (int u = 0; u < nu; u++) {
        const int id = u * NH + rk, pl = id / 3, chunk = id - 3 * pl;
        const int l0 = slot_line(chunk, pl >> 4, cls) + (pl & 15) * 2;
        int j = B_RDY + u * 5;
        const int m2 = nu == 3 ? (u == 0 ? T2MASK & 0x1fff : u == 1 ? T2MASK >> 13 : 0) : 0;
#pragma unroll 1
        for (int G = 0; G < 13; G++) {
            if (0x4a5 >> G & 1) pre(j++);
            e_st5(G < 12 ? &mp.f16 : &mp.f8, sb + u * 51200 + G * 4096, (l0 ^ ((rel >> G) & 1) << 5) + (G << 14));
            post(0);
            if (m2 >> G & 1) load_x_box(cls, rk, 2, g2++, sb, mp);
        }
        after(SIG_P1 + u);
    }
    const int mE = extra_mask(rk);
    int n = 0;
#pragma unroll 1
    for (int pg = 0; pg < 4; pg++) {
        const int nj = 3 + (mE >> pg & 1);
        const int l0 = slot_line(0, pg, cls), l1 = slot_line(1, pg, cls), l2 = slot_line(2, pg, cls);
#pragma unroll 1
        for (int j = 0; j < nj; j++) {
            const int lp = phi_line(j == 3 ? extra_phi(rk) : 3 * rk + j, rel);
#pragma unroll
            for (int b = 0; b < 3; b++) {
                pre(B_RDY + R_P2 + n * 3 + b);
                e_s2g(pt.scr + (size_t)(lp ^ (b == 0 ? l0 : b == 1 ? l1 : l2)) * 128, sb + S1 + (n & 3) * 12288 + b * 4096, 4096);
                post(bars + 8 * (B_SFREE + n * 3 + b));
            }
            n++;
        }
        after(SIG_P2 + pg);
    }
#pragma unroll 1
    for (int u = 0; u < nu; u++) {
        const int id = u * NH + rk, pl = id / 3, chunk = id - 3 * pl, tp = cls * 4 + (pl >> 4), tx = pl & 15;
        const uint32_t buf = sb + (u ? 3 - u : 0) * 51200;
#pragma unroll
        for (int gg = 1; gg < 5; gg++) {
            pre(B_RDY + R_P3 + u * 4 + gg - 1);
            if (gg < 4) e_st3(&mp.y4, buf + gg * 7168, 32 * chunk, 14 * tx - 4 + 4 * gg, 28 * tp);
            else e_st3(&mp.y2, buf, 32 * chunk, tx == 0 ? 222 : 14 * tx - 2, 28 * tp);
            post(0);
        }
    }
    bulk_wait_read<0>();
}

__device__ __forceinline__ void signal_warp(int cls, int rk, uint32_t sb, const Ptrs& pt) {
    const uint32_t bars = sb + BARS;
    char* cnt = cls_cnt(pt.scr, cls);
    if (threadIdx.x & 31) return;
#pragma unroll 1
    for (int c = 0; c < 8; c++) {
        if (c == SIG_P1 + 2 && rk >= 60) continue;
        char* ctr = cnt + (c == SIG_W ? CNT_W : c < SIG_P2 ? CNT_P1 + ((c - SIG_P1) * NH + rk) / 48 : CNT_P2 + c - SIG_P2) * 128;
        mbar_wait(bars + 8 * (B_SIG + c));
        fence_async();
        asm volatile("red.relaxed.gpu.global.add.u32 [%0], 1;" :: "l"(ctr) : "memory");
        if (c == SIG_W) asm volatile("red.relaxed.gpu.global.add.u32 [%0], 1;" :: "l"((uintptr_t)ctr ^ 4096) : "memory");
    }
    mbar_wait(bars + 8 * B_FIN);
    unsigned old;
    asm volatile("atom.add.relaxed.gpu.global.u32 %0, [%1], 1;" : "=r"(old) : "l"(pt.cnt + CNT_DONE * 32) : "memory");
    if (old == NSM - 1) {
#pragma unroll
        for (int c = 0; c < NCNT; c++) pt.cnt[c * 32] = 0;
#pragma unroll 1
        for (int c = 0; c < NCLS; c++) { *reinterpret_cast<unsigned*>(cnt + c * 128) = 0; *reinterpret_cast<unsigned*>(((uintptr_t)cnt ^ 4096) + c * 128) = 0; }
    }
}

__global__ void __launch_bounds__(512, 1) fftconv_kernel(const Ptrs pt, const __grid_constant__ Maps mp) {
    extern __shared__ __align__(1024) uint8_t smem[];
    const uint32_t sb = smem_u32(smem);
    const int tid = threadIdx.x, warp = uni(tid >> 5), wg = warp >> 2;
    int cls, rk;
    auto bar_init = [&](int i) {
        uint32_t c = 1;
        if (i == B_P1D || (i >= B_RE && i < B_RE + 14)) c = 12;
        else if ((i >= B_WCH && i < B_WL) || i >= B_TOK) c = 4;
        asm volatile("st.shared.v2.u32 [%0], {%1, %2};" :: "r"(sb + BARS + 8 * i), "r"((0x100000u - c) << 1), "r"((0x100000u - c) << 11) : "memory");
        fence_async_smem();
    };
    if (wg == 3) {
        asm volatile("setmaxnreg.dec.sync.aligned.u32 32;");
        if (warp == 12) {
            bar_init(tid & 31);
            __syncwarp();
            asm volatile("bar.arrive 4, 416;" ::: "memory");
            load_first(sb, mp, pt);
            asm volatile("bar.sync 5, 416;" ::: "memory");
            get_role(sb, cls, rk);
            load_warp(cls, rk, sb, pt);
        } else if (warp == 13) {
            if ((tid & 31) < 8) asm volatile("prefetch.tensormap [%0];" :: "l"(reinterpret_cast<const CUtensorMap*>(&mp) + 1 + (tid & 31)) : "memory");
            __syncwarp();
            asm volatile("bar.sync 6, 416;" ::: "memory");
            store_warp(sb, mp, pt);
        } else if (warp == 14) {
            const int G = blockIdx.x - 119;
            int sel = 0;
            if (G >= 1 && (tid & 31) == 0) sel = near_page(pt.scr + ((size_t)G << 21) + slot_line(3, 3, 0) * 128);
            __syncwarp();
            asm volatile("bar.sync 7, 416;" ::: "memory");
            get_role(sb, cls, rk);
            if (G >= 1 && (tid & 31) == 0) {
                uint32_t c; asm volatile("ld.shared.u32 %0, [%1];" : "=r"(c) : "r"(sb + REL + 8) : "memory");
                asm volatile("red.relaxed.gpu.global.add.u32 [%0], %1;" :: "l"(pt.cnt + CNT_REL * 32), "r"(0x10000u | (sel ^ c) << G) : "memory");
            }
            __syncwarp();
            load3_warp(cls, rk, sb, mp, pt);
        } else {
            uint32_t role = 0;
            if ((tid & 31) == 0) role = find_role(sb, pt.scr);
            role = uni(role); cls = role >> 8; rk = role & 255;
            asm volatile("bar.sync 8, 416;" ::: "memory");
            load_x(cls, rk, 0, sb, mp);
            e_arrive(sb + BARS + 8 * B_ROLE);
            signal_warp(cls, rk, sb, pt);
        }
    } else {
        if (tid >= 32 && tid < NBAR) bar_init(tid);
        {
            const int r = tid % 40;
            asm volatile("st.shared.u32 [%0], %1;" :: "r"(sb + TBL + 4 * tid), "r"(cos_bits(r) | (cos_bits(r < 30 ? r + 10 : r - 30) << 16)) : "memory");
        }
        __syncwarp();
        asm volatile("bar.sync 4, 416;" ::: "memory");
        asm volatile("bar.arrive 5, 416;" ::: "memory");
        asm volatile("bar.arrive 6, 416;" ::: "memory");
        asm volatile("bar.arrive 7, 416;" ::: "memory");
        asm volatile("bar.arrive 8, 416;" ::: "memory");
        task_w(wg, blockIdx.x, sb);
        asm volatile("setmaxnreg.inc.sync.aligned.u32 160;");
        get_role(sb, cls, rk);
        const int id = wg * NH + rk;
        if (id < 192) task_p1(wg, id / 3, sb);
        e_arrive(sb + BARS + 8 * B_P1D);
        task_p2(wg, rk, sb);
        if (id < 192) task_p3(wg, id / 3, sb);
    }
}

__global__ void fallback_kernel(const __nv_bfloat16* x, const __nv_bfloat16* w, __nv_bfloat16* y) {
    const int px = blockIdx.x, o = threadIdx.x, h = px / 224, c = px % 224;
    float acc = 0.f;
    for (int kh = 0; kh < 7; kh++)
        for (int kw = 0; kw < 7; kw++) {
            const __nv_bfloat16* xp = x + (((h - kh + 224) % 224) * 224 + (c - kw + 224) % 224) * 96;
            const __nv_bfloat16* wp = w + (kh * 7 + kw) * 9216 + o;
            for (int i = 0; i < 96; i++) acc += __bfloat162float(xp[i]) * __bfloat162float(wp[i * 96]);
        }
    y[px * 96 + o] = __float2bfloat16(acc);
}

typedef CUresult (*EncodeFn)(CUtensorMap*, CUtensorMapDataType, cuuint32_t, void*, const cuuint64_t*, const cuuint64_t*, const cuuint32_t*, const cuuint32_t*,
                             CUtensorMapInterleave, CUtensorMapSwizzle, CUtensorMapL2promotion, CUtensorMapFloatOOBfill);

static void encode3(EncodeFn fn, CUtensorMap* m, void* ptr, uint64_t d0, uint64_t d1, uint64_t d2, uint64_t s1, uint64_t s2,
                    uint32_t b0, uint32_t b1, uint32_t b2, CUtensorMapSwizzle sw, CUtensorMapL2promotion promo = CU_TENSOR_MAP_L2_PROMOTION_NONE) {
    cuuint64_t dims[3] = {d0, d1, d2}, strides[2] = {s1, s2};
    cuuint32_t box[3] = {b0, b1, b2}, es[3] = {1, 1, 1};
    fn(m, CU_TENSOR_MAP_DATA_TYPE_BFLOAT16, 3, ptr, dims, strides, box, es, CU_TENSOR_MAP_INTERLEAVE_NONE, sw,
       promo, CU_TENSOR_MAP_FLOAT_OOB_FILL_NONE);
}

extern "C" void kernel_launch(void* const* d_in, const int* in_sizes, int n_in, void* d_out, int out_size) {
    (void)in_sizes; (void)n_in; (void)out_size;
    int dev = 0, nsm = 0;
    cudaGetDevice(&dev);
    cudaDeviceGetAttribute(&nsm, cudaDevAttrMultiProcessorCount, dev);
    if (nsm < NSM) {
        fallback_kernel<<<224 * 224, 96>>>((const __nv_bfloat16*)d_in[0], (const __nv_bfloat16*)d_in[1], (__nv_bfloat16*)d_out);
        return;
    }
    void* fnp = nullptr; cudaDriverEntryPointQueryResult qr;
    cudaGetDriverEntryPoint("cuTensorMapEncodeTiled", &fnp, cudaEnableDefault, &qr);
    EncodeFn fn = (EncodeFn)fnp;
    void* xf = nullptr; cudaGetSymbolAddress(&xf, g_scr);
    xf = (void*)(((uintptr_t)xf + (1u << 21) - 1) & ~(uintptr_t)((1u << 21) - 1));
    void* wf = nullptr; cudaGetSymbolAddress(&wf, g_wf);
    Maps mp;
    Ptrs pt;
    pt.scr = (char*)xf; pt.wf = (const char*)wf; pt.x = (const char*)d_in[0];
    void* p = nullptr;
    cudaGetSymbolAddress(&p, TAB_P1); pt.tab1 = p;
    cudaGetSymbolAddress(&p, TAB_P3); pt.tab3 = p;
    cudaGetSymbolAddress(&p, g_cnt); pt.cnt = (unsigned*)p;
    {
        cuuint32_t b16[5] = {64, 4, 2, 2, 2}, b8[5] = {64, 4, 2, 1, 2}, es[5] = {1, 1, 1, 1, 1};
        cuuint64_t d[5] = {64, 4, 2, 2, 13 << 14}, st[4] = {16384, 262144, 1048576, 128};
        fn(&mp.f16, CU_TENSOR_MAP_DATA_TYPE_BFLOAT16, 5, xf, d, st, b16, es, CU_TENSOR_MAP_INTERLEAVE_NONE, CU_TENSOR_MAP_SWIZZLE_NONE, CU_TENSOR_MAP_L2_PROMOTION_NONE, CU_TENSOR_MAP_FLOAT_OOB_FILL_NONE);
        fn(&mp.f8, CU_TENSOR_MAP_DATA_TYPE_BFLOAT16, 5, xf, d, st, b8, es, CU_TENSOR_MAP_INTERLEAVE_NONE, CU_TENSOR_MAP_SWIZZLE_NONE, CU_TENSOR_MAP_L2_PROMOTION_NONE, CU_TENSOR_MAP_FLOAT_OOB_FILL_NONE);
    }
    encode3(fn, &mp.x6, d_in[0], 96, 224, 224, 192, 224 * 192, 32, 4, 6, CU_TENSOR_MAP_SWIZZLE_64B, CU_TENSOR_MAP_L2_PROMOTION_L2_128B);
    encode3(fn, &mp.x34, d_in[0], 96, 224, 224, 192, 224 * 192, 32, 4, 34, CU_TENSOR_MAP_SWIZZLE_64B, CU_TENSOR_MAP_L2_PROMOTION_L2_128B);
    encode3(fn, &mp.x28, d_in[0], 96, 224, 224, 192, 224 * 192, 32, 4, 28, CU_TENSOR_MAP_SWIZZLE_64B, CU_TENSOR_MAP_L2_PROMOTION_L2_128B);
    {
        cuuint32_t box[4] = {32, 8, 7, 2}, es[4] = {1, 1, 1, 1};
        cuuint64_t d[4] = {96, 7, 7, 96}, st[3] = {18432, 7 * 18432, 192};
        fn(&mp.w, CU_TENSOR_MAP_DATA_TYPE_BFLOAT16, 4, d_in[1], d, st, box, es, CU_TENSOR_MAP_INTERLEAVE_NONE, CU_TENSOR_MAP_SWIZZLE_64B, CU_TENSOR_MAP_L2_PROMOTION_NONE, CU_TENSOR_MAP_FLOAT_OOB_FILL_NONE);
    }
    encode3(fn, &mp.wst, wf, 256, 200, 72, 36864, 512, 256, 8, 1, CU_TENSOR_MAP_SWIZZLE_NONE);
    encode3(fn, &mp.y4, d_out, 96, 224, 224, 192, 224 * 192, 32, 4, 28, CU_TENSOR_MAP_SWIZZLE_64B);
    encode3(fn, &mp.y2, d_out, 96, 224, 224, 192, 224 * 192, 32, 2, 28, CU_TENSOR_MAP_SWIZZLE_64B);
    constexpr int SMEM_LAUNCH = SMEM_BYTES;
    cudaFuncSetAttribute(fftconv_kernel, cudaFuncAttributeMaxDynamicSharedMemorySize, SMEM_LAUNCH);
    fftconv_kernel<<<NSM, 512, SMEM_LAUNCH>>>(pt, mp);
}
```

```cpp
#include <cuda_runtime.h>
#include <cuda_bf16.h>
#include <cuda.h>
#include <stdint.h>

__device__ __align__(128) const uint32_t TAB_P1[4480] = {
0x3e75,0,0x3e72,0,0x8000,0,0xbd19,0,0x3e750000,0,0x3e720000,0,0x80000000,0,0xbd190000,0,
0,0x3e75,0,0x3e72,0,0x8000,0,0xbd19,0,0x3e750000,0,0x3e720000,0,0x80000000,0,0xbd190000,
0x3e69,0,0x3e5a,0,0xbd97,0,0xbdde,0,0x3e690000,0,0x3e5a0000,0,0xbd970000,0,0xbdde0000,0,
0,0x3e69,0,0x3e5a,0,0xbd97,0,0xbdde,0,0x3e690000,0,0x3e5a0000,0,0xbd970000,0,0xbdde0000,
0x3e75,0,0x3e5a,0,0x8000,0,0xbdde,0,0x3e750000,0,0x3e5a0000,0,0x80000000,0,0xbdde0000,0,
0,0x3e75,0,0x3e5a,0,0x8000,0,0xbdde,0,0x3e750000,0,0x3e5a0000,0,0x80000000,0,0xbdde0000,
0x3e10,0,0x3d19,0,0xbe46,0,0xbe72,0,0x3e100000,0,0x3d190000,0,0xbe460000,0,0xbe720000,0,
0,0x3e10,0,0x3d19,0,0xbe46,0,0xbe72,0,0x3e100000,0,0x3d190000,0,0xbe460000,0,0xbe720000,
0x3e75,0,0x3e2d,0,0x8000,0,0xbe2d,0,0x3e750000,0,0x3e2d0000,0,0x80000000,0,0xbe2d0000,0,
0,0x3e75,0,0x3e2d,0,0x8000,0,0xbe2d,0,0x3e750000,0,0x3e2d0000,0,0x80000000,0,0xbe2d0000,
0,0,0xbe2d,0,0xbe75,0,0xbe2d,0,0,0,0xbe2d0000,0,0xbe750000,0,0xbe2d0000,0,
0,0,0,0xbe2d,0,0xbe75,0,0xbe2d,0,0,0,0xbe2d0000,0,0xbe750000,0,0xbe2d0000,
0x3e75,0,0x3dde,0,0x8000,0,0xbe5a,0,0x3e750000,0,0x3dde0000,0,0x80000000,0,0xbe5a0000,0,
0,0x3e75,0,0x3dde,0,0x8000,0,0xbe5a,0,0x3e750000,0,0x3dde0000,0,0x80000000,0,0xbe5a0000,
0xbe10,0,0xbe72,0,0xbe46,0,0x3d19,0,0xbe100000,0,0xbe720000,0,0xbe460000,0,0x3d190000,0,
0,0xbe10,0,0xbe72,0,0xbe46,0,0x3d19,0,0xbe100000,0,0xbe720000,0,0xbe460000,0,0x3d190000,
0x3e75,0,0x3d19,0,0x8000,0,0xbe72,0,0x3e750000,0,0x3d190000,0,0x80000000,0,0xbe720000,0,
0,0x3e75,0,0x3d19,0,0x8000,0,0xbe72,0,0x3e750000,0,0x3d190000,0,0x80000000,0,0xbe720000,
0xbe69,0,0xbdde,0,0xbd97,0,0x3e5a,0,0xbe690000,0,0xbdde0000,0,0xbd970000,0,0x3e5a0000,0,
0,0xbe69,0,0xbdde,0,0xbd97,0,0x3e5a,0,0xbe690000,0,0xbdde0000,0,0xbd970000,0,0x3e5a0000,
0x3e75,0,0xbd19,0,0x8000,0,0xbe72,0,0x3e750000,0,0xbd190000,0,0x80000000,0,0xbe720000,0,
0,0x3e75,0,0xbd19,0,0x8000,0,0xbe72,0,0x3e750000,0,0xbd190000,0,0x80000000,0,0xbe720000,
0xbe69,0,0x3dde,0,0x3d97,0,0x3e5a,0,0xbe690000,0,0x3dde0000,0,0x3d970000,0,0x3e5a0000,0,
0,0xbe69,0,0x3dde,0,0x3d97,0,0x3e5a,0,0xbe690000,0,0x3dde0000,0,0x3d970000,0,0x3e5a0000,
0x3e75,0,0xbdde,0,0x8000,0,0xbe5a,0,0x3e750000,0,0xbdde0000,0,0x80000000,0,0xbe5a0000,0,
0,0x3e75,0,0xbdde,0,0x8000,0,0xbe5a,0,0x3e750000,0,0xbdde0000,0,0x80000000,0,0xbe5a0000,
0xbe10,0,0x3e72,0,0x3e46,0,0x3d19,0,0xbe100000,0,0x3e720000,0,0x3e460000,0,0x3d190000,0,
0,0xbe10,0,0x3e72,0,0x3e46,0,0x3d19,0,0xbe100000,0,0x3e720000,0,0x3e460000,0,0x3d190000,
0x3e75,0,0xbe2d,0,0x8000,0,0xbe2d,0,0x3e750000,0,0xbe2d0000,0,0x80000000,0,0xbe2d0000,0,
0,0x3e75,0,0xbe2d,0,0x8000,0,0xbe2d,0,0x3e750000,0,0xbe2d0000,0,0x80000000,0,0xbe2d0000,
0,0,0x3e2d,0,0x3e75,0,0xbe2d,0,0,0,0x3e2d0000,0,0x3e750000,0,0xbe2d0000,0,
0,0,0,0x3e2d,0,0x3e75,0,0xbe2d,0,0,0,0x3e2d0000,0,0x3e750000,0,0xbe2d0000,
0x3e75,0,0xbe5a,0,0x8000,0,0xbdde,0,0x3e750000,0,0xbe5a0000,0,0x80000000,0,0xbdde0000,0,
0,0x3e75,0,0xbe5a,0,0x8000,0,0xbdde,0,0x3e750000,0,0xbe5a0000,0,0x80000000,0,0xbdde0000,
0x3e10,0,0xbd19,0,0x3e46,0,0xbe72,0,0x3e100000,0,0xbd190000,0,0x3e460000,0,0xbe720000,0,
0,0x3e10,0,0xbd19,0,0x3e46,0,0xbe72,0,0x3e100000,0,0xbd190000,0,0x3e460000,0,0xbe720000,
0x3e75,0,0xbe72,0,0x8000,0,0xbd19,0,0x3e750000,0,0xbe720000,0,0x80000000,0,0xbd190000,0,
0,0x3e75,0,0xbe72,0,0x8000,0,0xbd19,0,0x3e750000,0,0xbe720000,0,0x80000000,0,0xbd190000,
0x3e69,0,0xbe5a,0,0x3d97,0,0xbdde,0,0x3e690000,0,0xbe5a0000,0,0x3d970000,0,0xbdde0000,0,
0,0x3e69,0,0xbe5a,0,0x3d97,0,0xbdde,0,0x3e690000,0,0xbe5a0000,0,0x3d970000,0,0xbdde0000,
0x3e46,0,0x3e2d,0,0xbe10,0,0xbe2d,0,0x3e460000,0,0x3e2d0000,0,0xbe100000,0,0xbe2d0000,0,
0,0x3e46,0,0x3e2d,0,0xbe10,0,0xbe2d,0,0x3e460000,0,0x3e2d0000,0,0xbe100000,0,0xbe2d0000,
0x3e10,0,0x3dde,0,0xbe46,0,0xbe5a,0,0x3e100000,0,0x3dde0000,0,0xbe460000,0,0xbe5a0000,0,
0,0x3e10,0,0x3dde,0,0xbe46,0,0xbe5a,0,0x3e100000,0,0x3dde0000,0,0xbe460000,0,0xbe5a0000,
0xbd97,0,0xbe2d,0,0xbe69,0,0xbe2d,0,0xbd970000,0,0xbe2d0000,0,0xbe690000,0,0xbe2d0000,0,
0,0xbd97,0,0xbe2d,0,0xbe69,0,0xbe2d,0,0xbd970000,0,0xbe2d0000,0,0xbe690000,0,0xbe2d0000,
0xbe69,0,0xbe72,0,0xbd97,0,0x3d19,0,0xbe690000,0,0xbe720000,0,0xbd970000,0,0x3d190000,0,
0,0xbe69,0,0xbe72,0,0xbd97,0,0x3d19,0,0xbe690000,0,0xbe720000,0,0xbd970000,0,0x3d190000,
0xbe75,0,0xbe2d,0,0x8000,0,0x3e2d,0,0xbe750000,0,0xbe2d0000,0,0x80000000,0,0x3e2d0000,0,
0,0xbe75,0,0xbe2d,0,0x8000,0,0x3e2d,0,0xbe750000,0,0xbe2d0000,0,0x80000000,0,0x3e2d0000,
0,0,0x3e2d,0,0x3e75,0,0x3e2d,0,0,0,0x3e2d0000,0,0x3e750000,0,0x3e2d0000,0,
0,0,0,0x3e2d,0,0x3e75,0,0x3e2d,0,0,0,0x3e2d0000,0,0x3e750000,0,0x3e2d0000,
0xbd97,0,0x3e2d,0,0x3e69,0,0x3e2d,0,0xbd970000,0,0x3e2d0000,0,0x3e690000,0,0x3e2d0000,0,
0,0xbd97,0,0x3e2d,0,0x3e69,0,0x3e2d,0,0xbd970000,0,0x3e2d0000,0,0x3e690000,0,0x3e2d0000,
0x3e69,0,0x3d19,0,0xbd97,0,0xbe72,0,0x3e690000,0,0x3d190000,0,0xbd970000,0,0xbe720000,0,
0,0x3e69,0,0x3d19,0,0xbd97,0,0xbe72,0,0x3e690000,0,0x3d190000,0,0xbd970000,0,0xbe720000,
0x3e46,0,0x3e2d,0,0x3e10,0,0xbe2d,0,0x3e460000,0,0x3e2d0000,0,0x3e100000,0,0xbe2d0000,0,
0,0x3e46,0,0x3e2d,0,0x3e10,0,0xbe2d,0,0x3e460000,0,0x3e2d0000,0,0x3e100000,0,0xbe2d0000,
0xbe10,0,0xbe5a,0,0xbe46,0,0x3dde,0,0xbe100000,0,0xbe5a0000,0,0xbe460000,0,0x3dde0000,0,
0,0xbe10,0,0xbe5a,0,0xbe46,0,0x3dde,0,0xbe100000,0,0xbe5a0000,0,0xbe460000,0,0x3dde0000,
0x3e46,0,0xbe2d,0,0xbe10,0,0xbe2d,0,0x3e460000,0,0xbe2d0000,0,0xbe100000,0,0xbe2d0000,0,
0,0x3e46,0,0xbe2d,0,0xbe10,0,0xbe2d,0,0x3e460000,0,0xbe2d0000,0,0xbe100000,0,0xbe2d0000,
0xbe10,0,0x3e5a,0,0x3e46,0,0x3dde,0,0xbe100000,0,0x3e5a0000,0,0x3e460000,0,0x3dde0000,0,
0,0xbe10,0,0x3e5a,0,0x3e46,0,0x3dde,0,0xbe100000,0,0x3e5a0000,0,0x3e460000,0,0x3dde0000,
0xbd97,0,0xbe2d,0,0xbe69,0,0x3e2d,0,0xbd970000,0,0xbe2d0000,0,0xbe690000,0,0x3e2d0000,0,
0,0xbd97,0,0xbe2d,0,0xbe69,0,0x3e2d,0,0xbd970000,0,0xbe2d0000,0,0xbe690000,0,0x3e2d0000,
0x3e69,0,0xbd19,0,0x3d97,0,0xbe72,0,0x3e690000,0,0xbd190000,0,0x3d970000,0,0xbe720000,0,
0,0x3e69,0,0xbd19,0,0x3d97,0,0xbe72,0,0x3e690000,0,0xbd190000,0,0x3d970000,0,0xbe720000,
0xbe75,0,0x3e2d,0,0x8000,0,0x3e2d,0,0xbe750000,0,0x3e2d0000,0,0x80000000,0,0x3e2d0000,0,
0,0xbe75,0,0x3e2d,0,0x8000,0,0x3e2d,0,0xbe750000,0,0x3e2d0000,0,0x80000000,0,0x3e2d0000,
0,0,0xbe2d,0,0xbe75,0,0x3e2d,0,0,0,0xbe2d0000,0,0xbe750000,0,0x3e2d0000,0,
0,0,0,0xbe2d,0,0xbe75,0,0x3e2d,0,0,0,0xbe2d0000,0,0xbe750000,0,0x3e2d0000,
0xbd97,0,0x3e2d,0,0x3e69,0,0xbe2d,0,0xbd970000,0,0x3e2d0000,0,0x3e690000,0,0xbe2d0000,0,
0,0xbd97,0,0x3e2d,0,0x3e69,0,0xbe2d,0,0xbd970000,0,0x3e2d0000,0,0x3e690000,0,0xbe2d0000,
0xbe69,0,0x3e72,0,0x3d97,0,0x3d19,0,0xbe690000,0,0x3e720000,0,0x3d970000,0,0x3d190000,0,
0,0xbe69,0,0x3e72,0,0x3d97,0,0x3d19,0,0xbe690000,0,0x3e720000,0,0x3d970000,0,0x3d190000,
0x3e46,0,0xbe2d,0,0x3e10,0,0xbe2d,0,0x3e460000,0,0xbe2d0000,0,0x3e100000,0,0xbe2d0000,0,
0,0x3e46,0,0xbe2d,0,0x3e10,0,0xbe2d,0,0x3e460000,0,0xbe2d0000,0,0x3e100000,0,0xbe2d0000,
0x3e10,0,0xbdde,0,0x3e46,0,0xbe5a,0,0x3e100000,0,0xbdde0000,0,0x3e460000,0,0xbe5a0000,0,
0,0x3e10,0,0xbdde,0,0x3e46,0,0xbe5a,0,0x3e100000,0,0xbdde0000,0,0x3e460000,0,0xbe5a0000,
0x3d97,0,0x3d19,0,0xbe69,0,0xbe72,0,0x3d970000,0,0x3d190000,0,0xbe690000,0,0xbe720000,0,
0,0x3d97,0,0x3d19,0,0xbe69,0,0xbe72,0,0x3d970000,0,0x3d190000,0,0xbe690000,0,0xbe720000,
0,0,0xbd19,0,0xbe75,0,0xbe72,0,0,0,0xbd190000,0,0xbe750000,0,0xbe720000,0,
0,0,0,0xbd19,0,0xbe75,0,0xbe72,0,0,0,0xbd190000,0,0xbe750000,0,0xbe720000,
0xbe46,0,0xbdde,0,0x3e10,0,0x3e5a,0,0xbe460000,0,0xbdde0000,0,0x3e100000,0,0x3e5a0000,0,
0,0xbe46,0,0xbdde,0,0x3e10,0,0x3e5a,0,0xbe460000,0,0xbdde0000,0,0x3e100000,0,0x3e5a0000,
0,0,0x3dde,0,0x3e75,0,0x3e5a,0,0,0,0x3dde0000,0,0x3e750000,0,0x3e5a0000,0,
0,0,0,0x3dde,0,0x3e75,0,0x3e5a,0,0,0,0x3dde0000,0,0x3e750000,0,0x3e5a0000,
0x3e75,0,0x3e2d,0,0x8000,0,0xbe2d,0,0x3e750000,0,0x3e2d0000,0,0x80000000,0,0xbe2d0000,0,
0,0x3e75,0,0x3e2d,0,0x8000,0,0xbe2d,0,0x3e750000,0,0x3e2d0000,0,0x80000000,0,0xbe2d0000,
0,0,0xbe2d,0,0xbe75,0,0xbe2d,0,0,0,0xbe2d0000,0,0xbe750000,0,0xbe2d0000,0,
0,0,0,0xbe2d,0,0xbe75,0,0xbe2d,0,0,0,0xbe2d0000,0,0xbe750000,0,0xbe2d0000,
0xbe46,0,0xbe5a,0,0xbe10,0,0x3dde,0,0xbe460000,0,0xbe5a0000,0,0xbe100000,0,0x3dde0000,0,
0,0xbe46,0,0xbe5a,0,0xbe10,0,0x3dde,0,0xbe460000,0,0xbe5a0000,0,0xbe100000,0,0x3dde0000,
0,0,0x3e5a,0,0x3e75,0,0x3dde,0,0,0,0x3e5a0000,0,0x3e750000,0,0x3dde0000,0,
0,0,0,0x3e5a,0,0x3e75,0,0x3dde,0,0,0,0x3e5a0000,0,0x3e750000,0,0x3dde0000,
0x3d97,0,0x3e72,0,0x3e69,0,0xbd19,0,0x3d970000,0,0x3e720000,0,0x3e690000,0,0xbd190000,0,
0,0x3d97,0,0x3e72,0,0x3e69,0,0xbd19,0,0x3d970000,0,0x3e720000,0,0x3e690000,0,0xbd190000,
0,0,0xbe72,0,0xbe75,0,0xbd19,0,0,0,0xbe720000,0,0xbe750000,0,0xbd190000,0,
0,0,0,0xbe72,0,0xbe75,0,0xbd19,0,0,0,0xbe720000,0,0xbe750000,0,0xbd190000,
0x3d97,0,0xbe72,0,0xbe69,0,0xbd19,0,0x3d970000,0,0xbe720000,0,0xbe690000,0,0xbd190000,0,
0,0x3d97,0,0xbe72,0,0xbe69,0,0xbd19,0,0x3d970000,0,0xbe720000,0,0xbe690000,0,0xbd190000,
0,0,0x3e72,0,0x3e75,0,0xbd19,0,0,0,0x3e720000,0,0x3e750000,0,0xbd190000,0,
0,0,0,0x3e72,0,0x3e75,0,0xbd19,0,0,0,0x3e720000,0,0x3e750000,0,0xbd190000,
0xbe46,0,0x3e5a,0,0x3e10,0,0x3dde,0,0xbe460000,0,0x3e5a0000,0,0x3e100000,0,0x3dde0000,0,
0,0xbe46,0,0x3e5a,0,0x3e10,0,0x3dde,0,0xbe460000,0,0x3e5a0000,0,0x3e100000,0,0x3dde0000,
0,0,0xbe5a,0,0xbe75,0,0x3dde,0,0,0,0xbe5a0000,0,0xbe750000,0,0x3dde0000,0,
0,0,0,0xbe5a,0,0xbe75,0,0x3dde,0,0,0,0xbe5a0000,0,0xbe750000,0,0x3dde0000,
0x3e75,0,0xbe2d,0,0x8000,0,0xbe2d,0,0x3e750000,0,0xbe2d0000,0,0x80000000,0,0xbe2d0000,0,
0,0x3e75,0,0xbe2d,0,0x8000,0,0xbe2d,0,0x3e750000,0,0xbe2d0000,0,0x80000000,0,0xbe2d0000,
0,0,0x3e2d,0,0x3e75,0,0xbe2d,0,0,0,0x3e2d0000,0,0x3e750000,0,0xbe2d0000,0,
0,0,0,0x3e2d,0,0x3e75,0,0xbe2d,0,0,0,0x3e2d0000,0,0x3e750000,0,0xbe2d0000,
0xbe46,0,0x3dde,0,0xbe10,0,0x3e5a,0,0xbe460000,0,0x3dde0000,0,0xbe100000,0,0x3e5a0000,0,
0,0xbe46,0,0x3dde,0,0xbe10,0,0x3e5a,0,0xbe460000,0,0x3dde0000,0,0xbe100000,0,0x3e5a0000,
0,0,0xbdde,0,0xbe75,0,0x3e5a,0,0,0,0xbdde0000,0,0xbe750000,0,0x3e5a0000,0,
0,0,0,0xbdde,0,0xbe75,0,0x3e5a,0,0,0,0xbdde0000,0,0xbe750000,0,0x3e5a0000,
0x3d97,0,0xbd19,0,0x3e69,0,0xbe72,0,0x3d970000,0,0xbd190000,0,0x3e690000,0,0xbe720000,0,
0,0x3d97,0,0xbd19,0,0x3e69,0,0xbe72,0,0x3d970000,0,0xbd190000,0,0x3e690000,0,0xbe720000,
0,0,0x3d19,0,0x3e75,0,0xbe72,0,0,0,0x3d190000,0,0x3e750000,0,0xbe720000,0,
0,0,0,0x3d19,0,0x3e75,0,0xbe72,0,0,0,0x3d190000,0,0x3e750000,0,0xbe720000,
0xbd97,0,0xbdde,0,0xbe69,0,0xbe5a,0,0xbd970000,0,0xbdde0000,0,0xbe690000,0,0xbe5a0000,0,
0,0xbd97,0,0xbdde,0,0xbe69,0,0xbe5a,0,0xbd970000,0,0xbdde0000,0,0xbe690000,0,0xbe5a0000,
0xbe10,0,0xbe2d,0,0xbe46,0,0xbe2d,0,0xbe100000,0,0xbe2d0000,0,0xbe460000,0,0xbe2d0000,0,
0,0xbe10,0,0xbe2d,0,0xbe46,0,0xbe2d,0,0xbe100000,0,0xbe2d0000,0,0xbe460000,0,0xbe2d0000,
0x3e46,0,0x3e72,0,0x3e10,0,0x3d19,0,0x3e460000,0,0x3e720000,0,0x3e100000,0,0x3d190000,0,
0,0x3e46,0,0x3e72,0,0x3e10,0,0x3d19,0,0x3e460000,0,0x3e720000,0,0x3e100000,0,0x3d190000,
0x3e69,0,0x3e2d,0,0xbd97,0,0xbe2d,0,0x3e690000,0,0x3e2d0000,0,0xbd970000,0,0xbe2d0000,0,
0,0x3e69,0,0x3e2d,0,0xbd97,0,0xbe2d,0,0x3e690000,0,0x3e2d0000,0,0xbd970000,0,0xbe2d0000,
0xbe75,0,0xbe2d,0,0x8000,0,0x3e2d,0,0xbe750000,0,0xbe2d0000,0,0x80000000,0,0x3e2d0000,0,
0,0xbe75,0,0xbe2d,0,0x8000,0,0x3e2d,0,0xbe750000,0,0xbe2d0000,0,0x80000000,0,0x3e2d0000,
0,0,0x3e2d,0,0x3e75,0,0x3e2d,0,0,0,0x3e2d0000,0,0x3e750000,0,0x3e2d0000,0,
0,0,0,0x3e2d,0,0x3e75,0,0x3e2d,0,0,0,0x3e2d0000,0,0x3e750000,0,0x3e2d0000,
0x3e46,0,0xbd19,0,0xbe10,0,0xbe72,0,0x3e460000,0,0xbd190000,0,0xbe100000,0,0xbe720000,0,
0,0x3e46,0,0xbd19,0,0xbe10,0,0xbe72,0,0x3e460000,0,0xbd190000,0,0xbe100000,0,0xbe720000,
0xbe69,0,0xbe2d,0,0xbd97,0,0x3e2d,0,0xbe690000,0,0xbe2d0000,0,0xbd970000,0,0x3e2d0000,0,
0,0xbe69,0,0xbe2d,0,0xbd97,0,0x3e2d,0,0xbe690000,0,0xbe2d0000,0,0xbd970000,0,0x3e2d0000,
0xbd97,0,0x3e5a,0,0x3e69,0,0x3dde,0,0xbd970000,0,0x3e5a0000,0,0x3e690000,0,0x3dde0000,0,
0,0xbd97,0,0x3e5a,0,0x3e69,0,0x3dde,0,0xbd970000,0,0x3e5a0000,0,0x3e690000,0,0x3dde0000,
0x3e10,0,0xbe2d,0,0xbe46,0,0xbe2d,0,0x3e100000,0,0xbe2d0000,0,0xbe460000,0,0xbe2d0000,0,
0,0x3e10,0,0xbe2d,0,0xbe46,0,0xbe2d,0,0x3e100000,0,0xbe2d0000,0,0xbe460000,0,0xbe2d0000,
0xbd97,0,0xbe5a,0,0xbe69,0,0x3dde,0,0xbd970000,0,0xbe5a0000,0,0xbe690000,0,0x3dde0000,0,
0,0xbd97,0,0xbe5a,0,0xbe69,0,0x3dde,0,0xbd970000,0,0xbe5a0000,0,0xbe690000,0,0x3dde0000,
0x3e10,0,0x3e2d,0,0x3e46,0,0xbe2d,0,0x3e100000,0,0x3e2d0000,0,0x3e460000,0,0xbe2d0000,0,
0,0x3e10,0,0x3e2d,0,0x3e46,0,0xbe2d,0,0x3e100000,0,0x3e2d0000,0,0x3e460000,0,0xbe2d0000,
0x3e46,0,0x3d19,0,0x3e10,0,0xbe72,0,0x3e460000,0,0x3d190000,0,0x3e100000,0,0xbe720000,0,
0,0x3e46,0,0x3d19,0,0x3e10,0,0xbe72,0,0x3e460000,0,0x3d190000,0,0x3e100000,0,0xbe720000,
0xbe69,0,0x3e2d,0,0x3d97,0,0x3e2d,0,0xbe690000,0,0x3e2d0000,0,0x3d970000,0,0x3e2d0000,0,
0,0xbe69,0,0x3e2d,0,0x3d97,0,0x3e2d,0,0xbe690000,0,0x3e2d0000,0,0x3d970000,0,0x3e2d0000,
0xbe75,0,0x3e2d,0,0x8000,0,0x3e2d,0,0xbe750000,0,0x3e2d0000,0,0x80000000,0,0x3e2d0000,0,
0,0xbe75,0,0x3e2d,0,0x8000,0,0x3e2d,0,0xbe750000,0,0x3e2d0000,0,0x80000000,0,0x3e2d0000,
0,0,0xbe2d,0,0xbe75,0,0x3e2d,0,0,0,0xbe2d0000,0,0xbe750000,0,0x3e2d0000,0,
0,0,0,0xbe2d,0,0xbe75,0,0x3e2d,0,0,0,0xbe2d0000,0,0xbe750000,0,0x3e2d0000,
0x3e46,0,0xbe72,0,0xbe10,0,0x3d19,0,0x3e460000,0,0xbe720000,0,0xbe100000,0,0x3d190000,0,
0,0x3e46,0,0xbe72,0,0xbe10,0,0x3d19,0,0x3e460000,0,0xbe720000,0,0xbe100000,0,0x3d190000,
0x3e69,0,0xbe2d,0,0x3d97,0,0xbe2d,0,0x3e690000,0,0xbe2d0000,0,0x3d970000,0,0xbe2d0000,0,
0,0x3e69,0,0xbe2d,0,0x3d97,0,0xbe2d,0,0x3e690000,0,0xbe2d0000,0,0x3d970000,0,0xbe2d0000,
0xbd97,0,0x3dde,0,0x3e69,0,0xbe5a,0,0xbd970000,0,0x3dde0000,0,0x3e690000,0,0xbe5a0000,0,
0,0xbd97,0,0x3dde,0,0x3e69,0,0xbe5a,0,0xbd970000,0,0x3dde0000,0,0x3e690000,0,0xbe5a0000,
0xbe10,0,0x3e2d,0,0x3e46,0,0xbe2d,0,0xbe100000,0,0x3e2d0000,0,0x3e460000,0,0xbe2d0000,0,
0,0xbe10,0,0x3e2d,0,0x3e46,0,0xbe2d,0,0xbe100000,0,0x3e2d0000,0,0x3e460000,0,0xbe2d0000,
0xbe46,0,0xbe5a,0,0xbe10,0,0xbdde,0,0xbe460000,0,0xbe5a0000,0,0xbe100000,0,0xbdde0000,0,
0,0xbe46,0,0xbe5a,0,0xbe10,0,0xbdde,0,0xbe460000,0,0xbe5a0000,0,0xbe100000,0,0xbdde0000,
0xbe69,0,0xbe72,0,0xbd97,0,0xbd19,0,0xbe690000,0,0xbe720000,0,0xbd970000,0,0xbd190000,0,
0,0xbe69,0,0xbe72,0,0xbd97,0,0xbd19,0,0xbe690000,0,0xbe720000,0,0xbd970000,0,0xbd190000,
0x3d97,0,0xbd19,0,0xbe69,0,0xbe72,0,0x3d970000,0,0xbd190000,0,0xbe690000,0,0xbe720000,0,
0,0x3d97,0,0xbd19,0,0xbe69,0,0xbe72,0,0x3d970000,0,0xbd190000,0,0xbe690000,0,0xbe720000,
0xbe10,0,0xbe5a,0,0xbe46,0,0xbdde,0,0xbe100000,0,0xbe5a0000,0,0xbe460000,0,0xbdde0000,0,
0,0xbe10,0,0xbe5a,0,0xbe46,0,0xbdde,0,0xbe100000,0,0xbe5a0000,0,0xbe460000,0,0xbdde0000,
0x3e75,0,0x3e2d,0,0x8000,0,0xbe2d,0,0x3e750000,0,0x3e2d0000,0,0x80000000,0,0xbe2d0000,0,
0,0x3e75,0,0x3e2d,0,0x8000,0,0xbe2d,0,0x3e750000,0,0x3e2d0000,0,0x80000000,0,0xbe2d0000,
0,0,0xbe2d,0,0xbe75,0,0xbe2d,0,0,0,0xbe2d0000,0,0xbe750000,0,0xbe2d0000,0,
0,0,0,0xbe2d,0,0xbe75,0,0xbe2d,0,0,0,0xbe2d0000,0,0xbe750000,0,0xbe2d0000,
0x3d97,0,0x3e72,0,0x3e69,0,0x3d19,0,0x3d970000,0,0x3e720000,0,0x3e690000,0,0x3d190000,0,
0,0x3d97,0,0x3e72,0,0x3e69,0,0x3d19,0,0x3d970000,0,0x3e720000,0,0x3e690000,0,0x3d190000,
0x3e10,0,0xbdde,0,0xbe46,0,0xbe5a,0,0x3e100000,0,0xbdde0000,0,0xbe460000,0,0xbe5a0000,0,
0,0x3e10,0,0xbdde,0,0xbe46,0,0xbe5a,0,0x3e100000,0,0xbdde0000,0,0xbe460000,0,0xbe5a0000,
0xbe46,0,0x3dde,0,0x3e10,0,0x3e5a,0,0xbe460000,0,0x3dde0000,0,0x3e100000,0,0x3e5a0000,0,
0,0xbe46,0,0x3dde,0,0x3e10,0,0x3e5a,0,0xbe460000,0,0x3dde0000,0,0x3e100000,0,0x3e5a0000,
0x3e69,0,0xbd19,0,0xbd97,0,0xbe72,0,0x3e690000,0,0xbd190000,0,0xbd970000,0,0xbe720000,0,
0,0x3e69,0,0xbd19,0,0xbd97,0,0xbe72,0,0x3e690000,0,0xbd190000,0,0xbd970000,0,0xbe720000,
0xbe46,0,0xbdde,0,0xbe10,0,0x3e5a,0,0xbe460000,0,0xbdde0000,0,0xbe100000,0,0x3e5a0000,0,
0,0xbe46,0,0xbdde,0,0xbe10,0,0x3e5a,0,0xbe460000,0,0xbdde0000,0,0xbe100000,0,0x3e5a0000,
0x3e69,0,0x3d19,0,0x3d97,0,0xbe72,0,0x3e690000,0,0x3d190000,0,0x3d970000,0,0xbe720000,0,
0,0x3e69,0,0x3d19,0,0x3d97,0,0xbe72,0,0x3e690000,0,0x3d190000,0,0x3d970000,0,0xbe720000,
0x3d97,0,0xbe72,0,0xbe69,0,0x3d19,0,0x3d970000,0,0xbe720000,0,0xbe690000,0,0x3d190000,0,
0,0x3d97,0,0xbe72,0,0xbe69,0,0x3d19,0,0x3d970000,0,0xbe720000,0,0xbe690000,0,0x3d190000,
0x3e10,0,0x3dde,0,0x3e46,0,0xbe5a,0,0x3e100000,0,0x3dde0000,0,0x3e460000,0,0xbe5a0000,0,
0,0x3e10,0,0x3dde,0,0x3e46,0,0xbe5a,0,0x3e100000,0,0x3dde0000,0,0x3e460000,0,0xbe5a0000,
0x3e75,0,0xbe2d,0,0x8000,0,0xbe2d,0,0x3e750000,0,0xbe2d0000,0,0x80000000,0,0xbe2d0000,0,
0,0x3e75,0,0xbe2d,0,0x8000,0,0xbe2d,0,0x3e750000,0,0xbe2d0000,0,0x80000000,0,0xbe2d0000,
0,0,0x3e2d,0,0x3e75,0,0xbe2d,0,0,0,0x3e2d0000,0,0x3e750000,0,0xbe2d0000,0,
0,0,0,0x3e2d,0,0x3e75,0,0xbe2d,0,0,0,0x3e2d0000,0,0x3e750000,0,0xbe2d0000,
0x3d97,0,0x3d19,0,0x3e69,0,0xbe72,0,0x3d970000,0,0x3d190000,0,0x3e690000,0,0xbe720000,0,
0,0x3d97,0,0x3d19,0,0x3e69,0,0xbe72,0,0x3d970000,0,0x3d190000,0,0x3e690000,0,0xbe720000,
0xbe10,0,0x3e5a,0,0x3e46,0,0xbdde,0,0xbe100000,0,0x3e5a0000,0,0x3e460000,0,0xbdde0000,0,
0,0xbe10,0,0x3e5a,0,0x3e46,0,0xbdde,0,0xbe100000,0,0x3e5a0000,0,0x3e460000,0,0xbdde0000,
0xbe46,0,0x3e5a,0,0x3e10,0,0xbdde,0,0xbe460000,0,0x3e5a0000,0,0x3e100000,0,0xbdde0000,0,
0,0xbe46,0,0x3e5a,0,0x3e10,0,0xbdde,0,0xbe460000,0,0x3e5a0000,0,0x3e100000,0,0xbdde0000,
0xbe69,0,0x3e72,0,0x3d97,0,0xbd19,0,0xbe690000,0,0x3e720000,0,0x3d970000,0,0xbd190000,0,
0,0xbe69,0,0x3e72,0,0x3d97,0,0xbd19,0,0xbe690000,0,0x3e720000,0,0x3d970000,0,0xbd190000,
0x3eb7,0x3eb7,0x3eb7,0x3eb7,0x3eb78000,0x3eb78000,0x3eb78000,0x3eb78000,0x3eb7,0x3de23eae,0x3e573e94,0x3e943e57,0x3eb78000,0x3eaebde2,0x3e94be57,0x3e57be94,
0x3eb7,0x3e573e94,0x3eae3de2,0x3eaebde2,0x3eb78000,0x3e94be57,0x3de2beae,0xbde2beae,0x3eb7,0x3e943e57,0x3eaebde2,0x3de2beae,0x3eb78000,0x3e57be94,0xbde2beae,0xbeaebde2,
0x3eb7,0x3eb7,0x3eb7,0x3eb7,0x3eb78000,0x3eb78000,0x3eb78000,0x3eb78000,0x3eae3de2,0x3eb70000,0x3eaebde2,0x3e94be57,0x3de2beae,0xbeb7,0xbde2beae,0xbe57be94,
0x3e57be94,0xbeb7,0xbe57be94,0xbeaebde2,0xbe94be57,0xbeb78000,0xbe943e57,0xbde23eae,0xbe57be94,0xbeb70000,0xbe573e94,0x3de23eae,0xbe943e57,0x3eb7,0x3e943e57,0x3eaebde2,
0x3eb7,0x3eae3de2,0x3e57be94,0xbe57be94,0x3eb78000,0x3de2beae,0xbe94be57,0xbe943e57,0x3eb7,0x3eb70000,0xbeb7,0xbeb70000,0x3eb78000,0xbeb7,0xbeb78000,0x3eb7,
0x3eb7,0x3eaebde2,0xbe57be94,0xbe573e94,0x3eb78000,0xbde2beae,0xbe943e57,0x3e943e57,0x3eb7,0x3e94be57,0xbeaebde2,0x3de23eae,0x3eb78000,0xbe57be94,0xbde23eae,0x3eaebde2,
0xbeae3de2,0x3eb7,0x3eae3de2,0x3e57be94,0x3de23eae,0x3eb78000,0x3de2beae,0xbe94be57,0x3eb7,0x3eb70000,0xbeb7,0xbeb70000,0x3eb78000,0xbeb7,0xbeb78000,0x3eb7,
0x3eae3de2,0xbeb7,0xbeae3de2,0x3e573e94,0x3de2beae,0xbeb78000,0x3de23eae,0x3e94be57,0x3e57be94,0xbeb70000,0x3e573e94,0x3de2beae,0xbe94be57,0x3eb7,0x3e94be57,0xbeaebde2,
0x3eb7,0x3e57be94,0xbeae3de2,0x3eae3de2,0x3eb78000,0xbe94be57,0x3de23eae,0x3de2beae,0x3eb7,0x3de2beae,0xbe573e94,0x3e94be57,0x3eb78000,0xbeaebde2,0x3e943e57,0xbe57be94,
0x3eb7,0xbeb7,0x3eb7,0xbeb7,0x3eb78000,0xbeb78000,0x3eb78000,0xbeb78000,0x3eb7,0xbde2beae,0x3e573e94,0xbe94be57,0x3eb78000,0xbeae3de2,0x3e94be57,0xbe573e94,
0xbe57be94,0x3eb7,0x3e57be94,0xbeae3de2,0xbe943e57,0x3eb78000,0xbe94be57,0x3de23eae,0xbeae3de2,0x3eb70000,0xbeaebde2,0x3e943e57,0x3de23eae,0xbeb7,0xbde23eae,0x3e57be94,
0x3eb7,0xbeb7,0x3eb7,0xbeb7,0x3eb78000,0xbeb78000,0x3eb78000,0xbeb78000,0x3eae3de2,0xbeb70000,0x3eaebde2,0xbe943e57,0x3de2beae,0x3eb7,0xbde2beae,0x3e573e94,
0x3eb7,0xbe57be94,0x3eae3de2,0xbeae3de2,0x3eb78000,0xbe943e57,0x3de2beae,0x3de23eae,0x3eb7,0xbe94be57,0x3eaebde2,0xbde23eae,0x3eb78000,0xbe573e94,0xbde2beae,0x3eae3de2,
0x3eb7,0xbeaebde2,0x3e57be94,0x3e573e94,0x3eb78000,0xbde23eae,0xbe94be57,0x3e94be57,0x3eb7,0xbeb70000,0xbeb7,0x3eb70000,0x3eb78000,0x3eb7,0xbeb78000,0xbeb7,
0x3e57be94,0x3eb7,0xbe57be94,0x3eae3de2,0xbe94be57,0x3eb78000,0xbe943e57,0x3de2beae,0xbe57be94,0x3eb70000,0xbe573e94,0xbde2beae,0xbe943e57,0xbeb7,0x3e943e57,0xbeae3de2,
0xbeae3de2,0xbeb7,0x3eae3de2,0xbe573e94,0x3de23eae,0xbeb78000,0x3de2beae,0x3e943e57,0x3eb7,0xbeb70000,0xbeb7,0x3eb70000,0x3eb78000,0x3eb7,0xbeb78000,0xbeb7,
0x3eb7,0xbeae3de2,0xbe57be94,0x3e57be94,0x3eb78000,0x3de23eae,0xbe943e57,0xbe94be57,0x3eb7,0xbe943e57,0xbeaebde2,0xbde2beae,0x3eb78000,0x3e573e94,0xbde23eae,0xbeae3de2,
0x3eb7,0xbe573e94,0xbeae3de2,0xbeaebde2,0x3eb78000,0x3e943e57,0x3de23eae,0xbde23eae,0x3eb7,0xbde23eae,0xbe573e94,0xbe943e57,0x3eb78000,0x3eae3de2,0x3e943e57,0x3e573e94,
0x3eae3de2,0x3eb7,0xbeae3de2,0xbe57be94,0x3de2beae,0x3eb78000,0x3de23eae,0xbe943e57,0x3e57be94,0x3eb70000,0x3e573e94,0xbde23eae,0xbe94be57,0xbeb7,0x3e94be57,0x3eae3de2,
0xbe57be94,0xbeb7,0x3e57be94,0x3eaebde2,0xbe943e57,0xbeb78000,0xbe94be57,0xbde2beae,0xbeae3de2,0xbeb70000,0xbeaebde2,0xbe94be57,0x3de23eae,0x3eb7,0xbde23eae,0xbe573e94,
0x3eb7,0x3eb7,0x3eb7,0x3eb7,0x3eb78000,0x3eb78000,0x3eb78000,0x3eb78000,0x3e57be94,0x3de2beae,0xbeb7,0xbde2beae,0xbe94be57,0xbeaebde2,0xbeb78000,0xbeae3de2,
0xbeae3de2,0xbe573e94,0x3eb7,0x3e573e94,0x3de23eae,0x3e943e57,0x3eb78000,0x3e94be57,0x3eae3de2,0x3e94be57,0xbeb7,0xbe94be57,0x3de2beae,0xbe57be94,0xbeb78000,0xbe573e94,
0x3eb7,0x3eb7,0x3eb7,0x3eb7,0x3eb78000,0x3eb78000,0x3eb78000,0x3eb78000,0xbe57be94,0xbe94be57,0xbeaebde2,0xbeb70000,0xbe943e57,0xbe573e94,0xbde23eae,0x3eb7,
0x3eae3de2,0x3eaebde2,0x3e57be94,0xbeb7,0x3de2beae,0xbde2beae,0xbe94be57,0xbeb78000,0xbeae3de2,0xbde23eae,0x3e573e94,0x3eb70000,0x3de23eae,0x3eae3de2,0x3e94be57,0xbeb7,
0xbe57be94,0xbeae3de2,0x3eb7,0x3eae3de2,0xbe943e57,0x3de23eae,0x3eb78000,0x3de2beae,0x3eb7,0x3eb70000,0xbeb7,0xbeb70000,0x3eb78000,0xbeb7,0xbeb78000,0x3eb7,
0x3e57be94,0xbeaebde2,0x3eb7,0x3eaebde2,0xbe94be57,0xbde23eae,0x3eb78000,0xbde2beae,0xbeae3de2,0x3e943e57,0xbeb7,0xbe943e57,0x3de23eae,0x3e57be94,0xbeb78000,0x3e573e94,
0x3e57be94,0xbe57be94,0xbeae3de2,0x3eb7,0xbe94be57,0xbe943e57,0x3de23eae,0x3eb78000,0x3eb7,0x3eb70000,0xbeb7,0xbeb70000,0x3eb78000,0xbeb7,0xbeb78000,0x3eb7,
0xbe57be94,0xbe573e94,0x3eae3de2,0xbeb7,0xbe943e57,0x3e943e57,0x3de2beae,0xbeb78000,0x3eae3de2,0xbde2beae,0xbe573e94,0x3eb70000,0x3de2beae,0xbeae3de2,0x3e943e57,0xbeb7,
0x3eae3de2,0xbe57be94,0x3eb7,0x3e57be94,0x3de2beae,0xbe943e57,0x3eb78000,0xbe94be57,0xbe57be94,0x3de23eae,0xbeb7,0xbde23eae,0xbe943e57,0x3eaebde2,0xbeb78000,0x3eae3de2,
0x3eb7,0xbeb7,0x3eb7,0xbeb7,0x3eb78000,0xbeb78000,0x3eb78000,0xbeb78000,0x3e57be94,0xbde23eae,0xbeb7,0x3de23eae,0xbe94be57,0x3eae3de2,0xbeb78000,0x3eaebde2,
0xbeae3de2,0x3eae3de2,0xbe57be94,0x3eb7,0x3de23eae,0x3de2beae,0xbe943e57,0x3eb78000,0x3e57be94,0xbe943e57,0x3eaebde2,0xbeb70000,0xbe94be57,0x3e573e94,0xbde2beae,0x3eb7,
0x3eb7,0xbeb7,0x3eb7,0xbeb7,0x3eb78000,0xbeb78000,0x3eb78000,0xbeb78000,0xbe57be94,0x3e943e57,0xbeaebde2,0x3eb70000,0xbe943e57,0x3e57be94,0xbde23eae,0xbeb7,
0xbeae3de2,0x3e57be94,0x3eb7,0xbe57be94,0x3de23eae,0xbe94be57,0x3eb78000,0xbe943e57,0x3eae3de2,0xbe943e57,0xbeb7,0x3e943e57,0x3de2beae,0x3e573e94,0xbeb78000,0x3e57be94,
0xbe57be94,0x3eaebde2,0x3eb7,0xbeaebde2,0xbe943e57,0xbde2beae,0x3eb78000,0xbde23eae,0x3eb7,0xbeb70000,0xbeb7,0x3eb70000,0x3eb78000,0x3eb7,0xbeb78000,0xbeb7,
0x3eae3de2,0xbeae3de2,0x3e57be94,0x3eb7,0x3de2beae,0x3de23eae,0xbe94be57,0x3eb78000,0xbeae3de2,0x3de2beae,0x3e573e94,0xbeb70000,0x3de23eae,0xbeaebde2,0x3e94be57,0x3eb7,
0x3e57be94,0x3e573e94,0xbeae3de2,0xbeb7,0xbe94be57,0x3e94be57,0x3de23eae,0xbeb78000,0x3eb7,0xbeb70000,0xbeb7,0x3eb70000,0x3eb78000,0x3eb7,0xbeb78000,0xbeb7,
0x3e57be94,0x3eae3de2,0x3eb7,0xbeae3de2,0xbe94be57,0x3de2beae,0x3eb78000,0x3de23eae,0xbeae3de2,0xbe94be57,0xbeb7,0x3e94be57,0x3de23eae,0xbe573e94,0xbeb78000,0xbe57be94,
0x3eae3de2,0x3e573e94,0x3eb7,0xbe573e94,0x3de2beae,0x3e94be57,0x3eb78000,0x3e943e57,0xbe57be94,0xbde2beae,0xbeb7,0x3de2beae,0xbe943e57,0xbeae3de2,0xbeb78000,0xbeaebde2,
0xbe57be94,0x3e57be94,0x3eae3de2,0x3eb7,0xbe943e57,0xbe94be57,0x3de2beae,0x3eb78000,0x3eae3de2,0x3de23eae,0xbe573e94,0xbeb70000,0x3de2beae,0x3eaebde2,0x3e943e57,0x3eb7,
0xbeae3de2,0xbeaebde2,0xbe57be94,0xbeb7,0x3de23eae,0xbde23eae,0xbe943e57,0xbeb78000,0x3e57be94,0x3e94be57,0x3eaebde2,0x3eb70000,0xbe94be57,0xbe57be94,0xbde2beae,0xbeb7,
0x3eb7,0x3eb7,0x3eb7,0x3eb7,0x3eb78000,0x3eb78000,0x3eb78000,0x3eb78000,0xbeae3de2,0xbe943e57,0xbe573e94,0xbde23eae,0x3de23eae,0x3e573e94,0x3e943e57,0x3eae3de2,
0xbe57be94,0xbeaebde2,0xbeae3de2,0xbe573e94,0xbe943e57,0xbde23eae,0x3de23eae,0x3e943e57,0x3e57be94,0xbde2beae,0xbeaebde2,0xbe943e57,0xbe94be57,0xbeae3de2,0xbde23eae,0x3e573e94,
0,0,0,0,0,0,0,0,0,0,0,0,0,0,0,0,
0,0,0,0,0,0,0,0,0,0,0,0,0,0,0,0,
0x3eae3de2,0x3e57be94,0xbe57be94,0xbeae3de2,0x3de2beae,0xbe94be57,0xbe943e57,0x3de23eae,0x3eb7,0x3eb70000,0xbeb7,0xbeb70000,0x3eb78000,0xbeb7,0xbeb78000,0x3eb7,
0xbeae3de2,0x3e573e94,0x3e57be94,0xbeaebde2,0x3de23eae,0x3e94be57,0xbe94be57,0xbde23eae,0xbe57be94,0xbde23eae,0x3eaebde2,0xbe94be57,0xbe943e57,0x3eae3de2,0xbde2beae,0xbe573e94,
0,0,0,0,0,0,0,0,0,0,0,0,0,0,0,0,
0,0,0,0,0,0,0,0,0,0,0,0,0,0,0,0,
0x3e57be94,0xbeae3de2,0x3eae3de2,0xbe57be94,0xbe94be57,0x3de23eae,0x3de2beae,0xbe943e57,0x3eae3de2,0xbe94be57,0x3e573e94,0xbde2beae,0x3de2beae,0xbe573e94,0x3e94be57,0xbeae3de2,
0x3eb7,0xbeb7,0x3eb7,0xbeb7,0x3eb78000,0xbeb78000,0x3eb78000,0xbeb78000,0xbeae3de2,0x3e94be57,0xbe573e94,0x3de2beae,0x3de23eae,0xbe57be94,0x3e943e57,0xbeaebde2,
0,0,0,0,0,0,0,0,0,0,0,0,0,0,0,0,
0,0,0,0,0,0,0,0,0,0,0,0,0,0,0,0,
0xbe57be94,0x3eae3de2,0xbeae3de2,0x3e57be94,0xbe943e57,0x3de2beae,0x3de23eae,0xbe94be57,0x3e57be94,0x3de23eae,0xbeaebde2,0x3e94be57,0xbe94be57,0x3eaebde2,0xbde23eae,0xbe57be94,
0x3eae3de2,0xbe573e94,0xbe57be94,0x3eaebde2,0x3de2beae,0x3e943e57,0xbe943e57,0xbde2beae,0x3eb7,0xbeb70000,0xbeb7,0x3eb70000,0x3eb78000,0x3eb7,0xbeb78000,0xbeb7,
0,0,0,0,0,0,0,0,0,0,0,0,0,0,0,0,
0,0,0,0,0,0,0,0,0,0,0,0,0,0,0,0,
0xbeae3de2,0xbe57be94,0x3e57be94,0x3eae3de2,0x3de23eae,0xbe943e57,0xbe94be57,0x3de2beae,0xbe57be94,0x3de2beae,0x3eaebde2,0x3e943e57,0xbe943e57,0xbeaebde2,0xbde2beae,0x3e57be94,
0x3e57be94,0x3eaebde2,0x3eae3de2,0x3e573e94,0xbe94be57,0xbde2beae,0x3de2beae,0x3e94be57,0x3eae3de2,0x3e943e57,0x3e573e94,0x3de23eae,0x3de2beae,0x3e57be94,0x3e94be57,0x3eaebde2,
0,0,0,0,0,0,0,0,0,0,0,0,0,0,0,0,
0,0,0,0,0,0,0,0,0,0,0,0,0,0,0,0,
0,0,0,0,0,0,0,0,0,0,0,0,0,0,0,0,
0,0,0,0,0,0,0,0,0,0,0,0,0,0,0,0,
0x3eb7,0x3eb7,0x3eb7,0x3eb7,0x3eb78000,0x3eb78000,0x3eb78000,0x3eb78000,0xbeae3de2,0xbe943e57,0xbe573e94,0xbde23eae,0x3de23eae,0x3e573e94,0x3e943e57,0x3eae3de2,
0xbe57be94,0xbeaebde2,0xbeae3de2,0xbe573e94,0xbe943e57,0xbde23eae,0x3de23eae,0x3e943e57,0x3e57be94,0xbde2beae,0xbeaebde2,0xbe943e57,0xbe94be57,0xbeae3de2,0xbde23eae,0x3e573e94,
0,0,0,0,0,0,0,0,0,0,0,0,0,0,0,0,
0,0,0,0,0,0,0,0,0,0,0,0,0,0,0,0,
0x3eae3de2,0x3e57be94,0xbe57be94,0xbeae3de2,0x3de2beae,0xbe94be57,0xbe943e57,0x3de23eae,0x3eb7,0x3eb70000,0xbeb7,0xbeb70000,0x3eb78000,0xbeb7,0xbeb78000,0x3eb7,
0xbeae3de2,0x3e573e94,0x3e57be94,0xbeaebde2,0x3de23eae,0x3e94be57,0xbe94be57,0xbde23eae,0xbe57be94,0xbde23eae,0x3eaebde2,0xbe94be57,0xbe943e57,0x3eae3de2,0xbde2beae,0xbe573e94,
0,0,0,0,0,0,0,0,0,0,0,0,0,0,0,0,
0,0,0,0,0,0,0,0,0,0,0,0,0,0,0,0,
0x3e57be94,0xbeae3de2,0x3eae3de2,0xbe57be94,0xbe94be57,0x3de23eae,0x3de2beae,0xbe943e57,0x3eae3de2,0xbe94be57,0x3e573e94,0xbde2beae,0x3de2beae,0xbe573e94,0x3e94be57,0xbeae3de2,
0x3eb7,0xbeb7,0x3eb7,0xbeb7,0x3eb78000,0xbeb78000,0x3eb78000,0xbeb78000,0xbeae3de2,0x3e94be57,0xbe573e94,0x3de2beae,0x3de23eae,0xbe57be94,0x3e943e57,0xbeaebde2,
0,0,0,0,0,0,0,0,0,0,0,0,0,0,0,0,
0,0,0,0,0,0,0,0,0,0,0,0,0,0,0,0,
0xbe57be94,0x3eae3de2,0xbeae3de2,0x3e57be94,0xbe943e57,0x3de2beae,0x3de23eae,0xbe94be57,0x3e57be94,0x3de23eae,0xbeaebde2,0x3e94be57,0xbe94be57,0x3eaebde2,0xbde23eae,0xbe57be94,
0x3eae3de2,0xbe573e94,0xbe57be94,0x3eaebde2,0x3de2beae,0x3e943e57,0xbe943e57,0xbde2beae,0x3eb7,0xbeb70000,0xbeb7,0x3eb70000,0x3eb78000,0x3eb7,0xbeb78000,0xbeb7,
0,0,0,0,0,0,0,0,0,0,0,0,0,0,0,0,
0,0,0,0,0,0,0,0,0,0,0,0,0,0,0,0,
0xbeae3de2,0xbe57be94,0x3e57be94,0x3eae3de2,0x3de23eae,0xbe943e57,0xbe94be57,0x3de2beae,0xbe57be94,0x3de2beae,0x3eaebde2,0x3e943e57,0xbe943e57,0xbeaebde2,0xbde2beae,0x3e57be94,
0x3e57be94,0x3eaebde2,0x3eae3de2,0x3e573e94,0xbe94be57,0xbde2beae,0x3de2beae,0x3e94be57,0x3eae3de2,0x3e943e57,0x3e573e94,0x3de23eae,0x3de2beae,0x3e57be94,0x3e94be57,0x3eaebde2,
};
__device__ __align__(128) const uint32_t TAB_P3[4288] = {
0,0,0,0,0,0,0,0,0,0,0,0,0,0,0,0,
0x80003e83,0xbe79bda2,0x3e1abe54,0x3e1a3e54,0x3e830000,0xbda23e79,0xbe54be1a,0x3e54be1a,0x80003e83,0xbe54be1a,0x3e79bda2,0xbda23e79,0x3e830000,0xbe1a3e54,0xbda2be79,0x3e793da2,
0,0,0,0,0,0,0,0,0,0,0,0,0,0,0,0,
0xbe793da2,0x8000be83,0x3e793da2,0xbe1a3e54,0x3da23e79,0xbe830000,0x3da2be79,0x3e543e1a,0xbe1abe54,0x3e830000,0xbe1a3e54,0xbda2be79,0xbe543e1a,0xbe83,0x3e543e1a,0xbe793da2,
0x80003e83,0xbe1abe54,0x3e793da2,0xbe793da2,0x3e830000,0xbe543e1a,0x3da2be79,0x3da23e79,0x80003e83,0xbda2be79,0x3e1a3e54,0xbe54be1a,0x3e830000,0xbe793da2,0x3e54be1a,0xbe1a3e54,
0x80003e83,0x8000be83,0x80003e83,0x8000be83,0x3e830000,0xbe830000,0x3e830000,0xbe830000,0x80003e83,0x3da2be79,0xbe1a3e54,0x3e54be1a,0x3e830000,0xbe79bda2,0x3e543e1a,0xbe1abe54,
0x3e1abe54,0x80003e83,0xbe1abe54,0x3e793da2,0xbe54be1a,0x3e830000,0xbe543e1a,0x3da2be79,0x3e793da2,0xbe830000,0x3e79bda2,0xbe543e1a,0x3da2be79,0x3e83,0xbda2be79,0x3e1a3e54,
0x80003e83,0x8000be83,0x80003e83,0x8000be83,0x3e830000,0xbe830000,0x3e830000,0xbe830000,0xbe793da2,0x3e830000,0xbe79bda2,0x3e543e1a,0x3da23e79,0xbe83,0xbda23e79,0x3e1abe54,
0x80003e83,0x3e1abe54,0xbe793da2,0x3e793da2,0x3e830000,0xbe54be1a,0x3da23e79,0x3da2be79,0x80003e83,0x3e54be1a,0xbe79bda2,0x3da23e79,0x3e830000,0xbe1abe54,0xbda23e79,0x3e79bda2,
0x80003e83,0x3e79bda2,0xbe1abe54,0xbe1a3e54,0x3e830000,0xbda2be79,0xbe543e1a,0x3e543e1a,0x80003e83,0x3e830000,0x8000be83,0xbe830000,0x3e830000,0xbe83,0xbe830000,0x3e83,
0xbe1abe54,0x80003e83,0x3e1abe54,0xbe793da2,0xbe543e1a,0x3e830000,0xbe54be1a,0x3da23e79,0x3e1abe54,0xbe830000,0x3e1a3e54,0x3da2be79,0xbe54be1a,0x3e83,0x3e54be1a,0xbe79bda2,
0x3e793da2,0x8000be83,0xbe793da2,0x3e1a3e54,0x3da2be79,0xbe830000,0x3da23e79,0x3e54be1a,0x80003e83,0x3e830000,0x8000be83,0xbe830000,0x3e830000,0xbe83,0xbe830000,0x3e83,
0x80003e83,0x3e793da2,0x3e1abe54,0xbe1abe54,0x3e830000,0x3da2be79,0xbe54be1a,0xbe543e1a,0x80003e83,0x3e543e1a,0x3e79bda2,0x3da2be79,0x3e830000,0x3e1abe54,0xbda2be79,0xbe79bda2,
0x80003e83,0x3e1a3e54,0x3e793da2,0x3e79bda2,0x3e830000,0x3e54be1a,0x3da2be79,0xbda2be79,0x80003e83,0x3da23e79,0x3e1a3e54,0x3e543e1a,0x3e830000,0x3e79bda2,0x3e54be1a,0x3e1abe54,
0xbe793da2,0x80003e83,0x3e793da2,0x3e1abe54,0x3da23e79,0x3e830000,0x3da2be79,0xbe54be1a,0xbe1abe54,0xbe830000,0xbe1a3e54,0x3da23e79,0xbe543e1a,0x3e83,0x3e543e1a,0x3e79bda2,
0x3e1abe54,0x8000be83,0xbe1abe54,0xbe79bda2,0xbe54be1a,0xbe830000,0xbe543e1a,0xbda23e79,0x3e793da2,0x3e830000,0x3e79bda2,0x3e54be1a,0x3da2be79,0xbe83,0xbda2be79,0xbe1abe54,
0,0,0,0,0,0,0,0,0,0,0,0,0,0,0,0,
0,0,0,0,0,0,0,0,0,0,0,0,0,0,0,0,
0,0,0,0,0,0,0,0,0,0,0,0,0,0,0,0,
0xbe1abe54,0x3e79bda2,0x80003e83,0xbe79bda2,0xbe543e1a,0xbda2be79,0x3e830000,0xbda23e79,0x3e793da2,0xbe543e1a,0x8000be83,0x3e543e1a,0x3da2be79,0x3e1a3e54,0xbe830000,0x3e1abe54,
0,0,0,0,0,0,0,0,0,0,0,0,0,0,0,0,
0,0,0,0,0,0,0,0,0,0,0,0,0,0,0,0,
0xbe793da2,0x3e1abe54,0x80003e83,0xbe1abe54,0x3da23e79,0xbe54be1a,0x3e830000,0xbe543e1a,0x3e1abe54,0xbda23e79,0x8000be83,0x3da23e79,0xbe54be1a,0x3e793da2,0xbe830000,0x3e79bda2,
0x80003e83,0x8000be83,0x80003e83,0x8000be83,0x3e830000,0xbe830000,0x3e830000,0xbe830000,0xbe1abe54,0x3da23e79,0x8000be83,0xbda23e79,0xbe543e1a,0x3e79bda2,0xbe830000,0x3e793da2,
0,0,0,0,0,0,0,0,0,0,0,0,0,0,0,0,
0,0,0,0,0,0,0,0,0,0,0,0,0,0,0,0,
0x3e793da2,0xbe1abe54,0x80003e83,0x3e1abe54,0x3da2be79,0xbe543e1a,0x3e830000,0xbe54be1a,0xbe793da2,0x3e543e1a,0x8000be83,0xbe543e1a,0x3da23e79,0x3e1abe54,0xbe830000,0x3e1a3e54,
0x3e1abe54,0xbe79bda2,0x80003e83,0x3e79bda2,0xbe54be1a,0xbda23e79,0x3e830000,0xbda2be79,0x80003e83,0x3e830000,0x8000be83,0xbe830000,0x3e830000,0xbe83,0xbe830000,0x3e83,
0,0,0,0,0,0,0,0,0,0,0,0,0,0,0,0,
0,0,0,0,0,0,0,0,0,0,0,0,0,0,0,0,
0xbe1abe54,0xbe793da2,0x80003e83,0x3e793da2,0xbe543e1a,0x3da23e79,0x3e830000,0x3da2be79,0x3e793da2,0x3e54be1a,0x8000be83,0xbe54be1a,0x3da2be79,0xbe1abe54,0xbe830000,0xbe1a3e54,
0xbe793da2,0xbe1a3e54,0x80003e83,0x3e1a3e54,0x3da23e79,0x3e543e1a,0x3e830000,0x3e54be1a,0x3e1abe54,0x3da2be79,0x8000be83,0xbda2be79,0xbe54be1a,0xbe79bda2,0xbe830000,0xbe793da2,
0,0,0,0,0,0,0,0,0,0,0,0,0,0,0,0,
0x3e1abe54,0x3e1a3e54,0xbe793da2,0x8000be83,0xbe54be1a,0x3e54be1a,0x3da23e79,0xbe830000,0xbe793da2,0x3da2be79,0x3e1a3e54,0xbe830000,0x3da23e79,0xbe79bda2,0x3e54be1a,0x3e83,
0,0,0,0,0,0,0,0,0,0,0,0,0,0,0,0,
0x3e793da2,0xbe1a3e54,0xbe1abe54,0x3e79bda2,0x3da2be79,0x3e543e1a,0xbe543e1a,0xbda2be79,0x3e1abe54,0x3da23e79,0xbe79bda2,0x3e54be1a,0xbe54be1a,0x3e79bda2,0xbda23e79,0xbe1abe54,
0x3e793da2,0xbe793da2,0x3e1abe54,0x80003e83,0x3da2be79,0x3da23e79,0xbe54be1a,0x3e830000,0xbe1abe54,0x3e543e1a,0xbe79bda2,0x3e830000,0xbe543e1a,0x3e1abe54,0xbda23e79,0xbe83,
0x80003e83,0x8000be83,0x80003e83,0x8000be83,0x3e830000,0xbe830000,0x3e830000,0xbe830000,0x3e1abe54,0xbe543e1a,0x3e79bda2,0xbe830000,0xbe54be1a,0x3e1a3e54,0xbda2be79,0x3e83,
0xbe1abe54,0x3e793da2,0xbe793da2,0x3e1abe54,0xbe543e1a,0x3da2be79,0x3da23e79,0xbe54be1a,0xbe793da2,0x3e54be1a,0xbe1a3e54,0x3da2be79,0x3da23e79,0xbe1abe54,0x3e543e1a,0xbe79bda2,
0x80003e83,0x8000be83,0x80003e83,0x8000be83,0x3e830000,0xbe830000,0x3e830000,0xbe830000,0x3e793da2,0xbe54be1a,0x3e1a3e54,0xbda2be79,0x3da2be79,0xbe1a3e54,0x3e54be1a,0xbe793da2,
0xbe793da2,0x3e793da2,0xbe1abe54,0x80003e83,0x3da23e79,0x3da2be79,0xbe543e1a,0x3e830000,0x3e793da2,0xbda2be79,0xbe1a3e54,0x3e830000,0x3da2be79,0xbe793da2,0x3e543e1a,0xbe83,
0xbe1abe54,0xbe1a3e54,0x3e793da2,0x8000be83,0xbe543e1a,0x3e543e1a,0x3da2be79,0xbe830000,0x80003e83,0x3e830000,0x8000be83,0xbe830000,0x3e830000,0xbe83,0xbe830000,0x3e83,
0x3e1abe54,0xbe793da2,0x3e793da2,0xbe1abe54,0xbe54be1a,0x3da23e79,0x3da2be79,0xbe543e1a,0xbe1abe54,0xbda23e79,0x3e79bda2,0xbe54be1a,0xbe543e1a,0x3e793da2,0xbda2be79,0xbe1a3e54,
0xbe793da2,0x3e1a3e54,0x3e1abe54,0xbe79bda2,0x3da23e79,0x3e54be1a,0xbe54be1a,0xbda23e79,0x80003e83,0x3e830000,0x8000be83,0xbe830000,0x3e830000,0xbe83,0xbe830000,0x3e83,
0x3e1abe54,0xbe1abe54,0xbe793da2,0x80003e83,0xbe54be1a,0xbe543e1a,0x3da23e79,0x3e830000,0xbe793da2,0xbda23e79,0x3e1a3e54,0x3e830000,0x3da23e79,0x3e793da2,0x3e54be1a,0xbe83,
0x3e793da2,0x3e79bda2,0x3e1abe54,0x8000be83,0x3da2be79,0xbda2be79,0xbe54be1a,0xbe830000,0xbe1abe54,0xbe54be1a,0xbe79bda2,0xbe830000,0xbe543e1a,0xbe1a3e54,0xbda23e79,0x3e83,
0x3e793da2,0x3e1abe54,0xbe1abe54,0xbe793da2,0x3da2be79,0xbe54be1a,0xbe543e1a,0x3da23e79,0x3e1abe54,0xbda2be79,0xbe79bda2,0xbe543e1a,0xbe54be1a,0xbe793da2,0xbda23e79,0x3e1a3e54,
0xbe1abe54,0xbe79bda2,0xbe793da2,0xbe1a3e54,0xbe543e1a,0xbda23e79,0x3da23e79,0x3e543e1a,0xbe793da2,0xbe543e1a,0xbe1a3e54,0xbda23e79,0x3da23e79,0x3e1a3e54,0x3e543e1a,0x3e793da2,
0xbe163dda,0,0,0,0,0xbe163dda,0,0,0,0,0xbe163dda,0,0,0,0,0xbe163dda,
0xbe253da8,0,0,0,0,0xbe253da8,0,0,0,0,0xbe253da8,0,0,0,0,0xbe253da8,
0xbd65be30,0,0,0,0,0xbd65be30,0,0,0,0,0xbd65be30,0,0,0,0,0xbd65be30,
0x3ce8be37,0,0,0,0,0x3ce8be37,0,0,0,0,0x3ce8be37,0,0,0,0,0x3ce8be37,
0xbe303d65,0,0,0,0,0xbe303d65,0,0,0,0,0xbe303d65,0,0,0,0,0xbe303d65,
0xbe373ce8,0,0,0,0,0xbe373ce8,0,0,0,0,0xbe373ce8,0,0,0,0,0xbe373ce8,
0x3ddabe16,0,0,0,0,0x3ddabe16,0,0,0,0,0x3ddabe16,0,0,0,0,0x3ddabe16,
0x3e25bda8,0,0,0,0,0x3e25bda8,0,0,0,0,0x3e25bda8,0,0,0,0,0x3e25bda8,
0xbe390000,0,0,0,0,0xbe390000,0,0,0,0,0xbe390000,0,0,0,0,0xbe390000,
0xbe37bce8,0,0,0,0,0xbe37bce8,0,0,0,0,0xbe37bce8,0,0,0,0,0xbe37bce8,
0x3e390000,0,0,0,0,0x3e390000,0,0,0,0,0x3e390000,0,0,0,0,0x3e390000,
0x3e253da8,0,0,0,0,0x3e253da8,0,0,0,0,0x3e253da8,0,0,0,0,0x3e253da8,
0xbe30bd65,0,0,0,0,0xbe30bd65,0,0,0,0,0xbe30bd65,0,0,0,0,0xbe30bd65,
0xbe25bda8,0,0,0,0,0xbe25bda8,0,0,0,0,0xbe25bda8,0,0,0,0,0xbe25bda8,
0x3dda3e16,0,0,0,0,0x3dda3e16,0,0,0,0,0x3dda3e16,0,0,0,0,0x3dda3e16,
0x3ce83e37,0,0,0,0,0x3ce83e37,0,0,0,0,0x3ce83e37,0,0,0,0,0x3ce83e37,
0xbe16bdda,0,0,0,0,0xbe16bdda,0,0,0,0,0xbe16bdda,0,0,0,0,0xbe16bdda,
0xbe03be03,0,0,0,0,0xbe03be03,0,0,0,0,0xbe03be03,0,0,0,0,0xbe03be03,
0xbd653e30,0,0,0,0,0xbd653e30,0,0,0,0,0xbd653e30,0,0,0,0,0xbd653e30,
0xbe033e03,0,0,0,0,0xbe033e03,0,0,0,0,0xbe033e03,0,0,0,0,0xbe033e03,
0xbddabe16,0,0,0,0,0xbddabe16,0,0,0,0,0xbddabe16,0,0,0,0,0xbddabe16,
0xbda8be25,0,0,0,0,0xbda8be25,0,0,0,0,0xbda8be25,0,0,0,0,0xbda8be25,
0xbe303d65,0,0,0,0,0xbe303d65,0,0,0,0,0xbe303d65,0,0,0,0,0xbe303d65,
0xbe37bce8,0,0,0,0,0xbe37bce8,0,0,0,0,0xbe37bce8,0,0,0,0,0xbe37bce8,
0xbd65be30,0,0,0,0,0xbd65be30,0,0,0,0,0xbd65be30,0,0,0,0,0xbd65be30,
0xbce8be37,0,0,0,0,0xbce8be37,0,0,0,0,0xbce8be37,0,0,0,0,0xbce8be37,
0xbe16bdda,0,0,0,0,0xbe16bdda,0,0,0,0,0xbe16bdda,0,0,0,0,0xbe16bdda,
0xbda8be25,0,0,0,0,0xbda8be25,0,0,0,0,0xbda8be25,0,0,0,0,0xbda8be25,
0x3e390000,0,0,0,0,0x3e390000,0,0,0,0,0x3e390000,0,0,0,0,0x3e390000,
0x3e033e03,0,0,0,0,0x3e033e03,0,0,0,0,0x3e033e03,0,0,0,0,0x3e033e03,
0xbd653e30,0,0,0,0,0xbd653e30,0,0,0,0,0xbd653e30,0,0,0,0,0xbd653e30,
0xbe373ce8,0,0,0,0,0xbe373ce8,0,0,0,0,0xbe373ce8,0,0,0,0,0xbe373ce8,
0x80003e39,0,0,0,0,0x80003e39,0,0,0,0,0x80003e39,0,0,0,0,0x80003e39,
0xbe033e03,0,0,0,0,0xbe033e03,0,0,0,0,0xbe033e03,0,0,0,0,0xbe033e03,
0xbddabe16,0,0,0,0,0xbddabe16,0,0,0,0,0xbddabe16,0,0,0,0,0xbddabe16,
0x3da8be25,0,0,0,0,0x3da8be25,0,0,0,0,0x3da8be25,0,0,0,0,0x3da8be25,
0xbe390000,0,0,0,0,0xbe390000,0,0,0,0,0xbe390000,0,0,0,0,0xbe390000,
0xbe03be03,0,0,0,0,0xbe03be03,0,0,0,0,0xbe03be03,0,0,0,0,0xbe03be03,
0x3e390000,0,0,0,0,0x3e390000,0,0,0,0,0x3e390000,0,0,0,0,0x3e390000,
0x3da83e25,0,0,0,0,0x3da83e25,0,0,0,0,0x3da83e25,0,0,0,0,0x3da83e25,
0x8000be39,0,0,0,0,0x8000be39,0,0,0,0,0x8000be39,0,0,0,0,0x8000be39,
0x3e03be03,0,0,0,0,0x3e03be03,0,0,0,0,0x3e03be03,0,0,0,0,0x3e03be03,
0xbdda3e16,0,0,0,0,0xbdda3e16,0,0,0,0,0xbdda3e16,0,0,0,0,0xbdda3e16,
0xbe37bce8,0,0,0,0,0xbe37bce8,0,0,0,0,0xbe37bce8,0,0,0,0,0xbe37bce8,
0x3e390000,0,0,0,0,0x3e390000,0,0,0,0,0x3e390000,0,0,0,0,0x3e390000,
0x3e033e03,0,0,0,0,0x3e033e03,0,0,0,0,0x3e033e03,0,0,0,0,0x3e033e03,
0xbd65be30,0,0,0,0,0xbd65be30,0,0,0,0,0xbd65be30,0,0,0,0,0xbd65be30,
0x3e03be03,0,0,0,0,0x3e03be03,0,0,0,0,0x3e03be03,0,0,0,0,0x3e03be03,
0x80003e39,0,0,0,0,0x80003e39,0,0,0,0,0x80003e39,0,0,0,0,0x80003e39,
0xbe033e03,0,0,0,0,0xbe033e03,0,0,0,0,0xbe033e03,0,0,0,0,0xbe033e03,
0x3e303d65,0,0,0,0,0x3e303d65,0,0,0,0,0x3e303d65,0,0,0,0,0x3e303d65,
0x3ce83e37,0,0,0,0,0x3ce83e37,0,0,0,0,0x3ce83e37,0,0,0,0,0x3ce83e37,
0xbe390000,0,0,0,0,0xbe390000,0,0,0,0,0xbe390000,0,0,0,0,0xbe390000,
0xbe03be03,0,0,0,0,0xbe03be03,0,0,0,0,0xbe03be03,0,0,0,0,0xbe03be03,
0xbe163dda,0,0,0,0,0xbe163dda,0,0,0,0,0xbe163dda,0,0,0,0,0xbe163dda,
0xbe25bda8,0,0,0,0,0xbe25bda8,0,0,0,0,0xbe25bda8,0,0,0,0,0xbe25bda8,
0xbe16bdda,0,0,0,0,0xbe16bdda,0,0,0,0,0xbe16bdda,0,0,0,0,0xbe16bdda,
0x3da8be25,0,0,0,0,0x3da8be25,0,0,0,0,0x3da8be25,0,0,0,0,0x3da8be25,
0x3e16bdda,0,0,0,0,0x3e16bdda,0,0,0,0,0x3e16bdda,0,0,0,0,0x3e16bdda,
0x3da83e25,0,0,0,0,0x3da83e25,0,0,0,0,0x3da83e25,0,0,0,0,0x3da83e25,
0x3e303d65,0,0,0,0,0x3e303d65,0,0,0,0,0x3e303d65,0,0,0,0,0x3e303d65,
0xbce83e37,0,0,0,0,0xbce83e37,0,0,0,0,0xbce83e37,0,0,0,0,0xbce83e37,
0xbe303d65,0,0,0,0,0xbe303d65,0,0,0,0,0xbe303d65,0,0,0,0,0xbe303d65,
0xbce8be37,0,0,0,0,0xbce8be37,0,0,0,0,0xbce8be37,0,0,0,0,0xbce8be37,
0xbe390000,0,0,0,0,0xbe390000,0,0,0,0,0xbe390000,0,0,0,0,0xbe390000,
0xbce8be37,0,0,0,0,0xbce8be37,0,0,0,0,0xbce8be37,0,0,0,0,0xbce8be37,
0x3e390000,0,0,0,0,0x3e390000,0,0,0,0,0x3e390000,0,0,0,0,0x3e390000,
0xbce83e37,0,0,0,0,0xbce83e37,0,0,0,0,0xbce83e37,0,0,0,0,0xbce83e37,
0x3e30bd65,0,0,0,0,0x3e30bd65,0,0,0,0,0x3e30bd65,0,0,0,0,0x3e30bd65,
0x3da83e25,0,0,0,0,0x3da83e25,0,0,0,0,0x3da83e25,0,0,0,0,0x3da83e25,
0xbe30bd65,0,0,0,0,0xbe30bd65,0,0,0,0,0xbe30bd65,0,0,0,0,0xbe30bd65,
0x3da8be25,0,0,0,0,0x3da8be25,0,0,0,0,0x3da8be25,0,0,0,0,0x3da8be25,
0xbe163dda,0,0,0,0,0xbe163dda,0,0,0,0,0xbe163dda,0,0,0,0,0xbe163dda,
0xbe03be03,0,0,0,0,0xbe03be03,0,0,0,0,0xbe03be03,0,0,0,0,0xbe03be03,
0x3e163dda,0,0,0,0,0x3e163dda,0,0,0,0,0x3e163dda,0,0,0,0,0x3e163dda,
0xbe033e03,0,0,0,0,0xbe033e03,0,0,0,0,0xbe033e03,0,0,0,0,0xbe033e03,
0x3ddabe16,0,0,0,0,0x3ddabe16,0,0,0,0,0x3ddabe16,0,0,0,0,0x3ddabe16,
0x3e253da8,0,0,0,0,0x3e253da8,0,0,0,0,0x3e253da8,0,0,0,0,0x3e253da8,
0xbddabe16,0,0,0,0,0xbddabe16,0,0,0,0,0xbddabe16,0,0,0,0,0xbddabe16,
0x3e25bda8,0,0,0,0,0x3e25bda8,0,0,0,0,0x3e25bda8,0,0,0,0,0x3e25bda8,
0xbd653e30,0,0,0,0,0xbd653e30,0,0,0,0,0xbd653e30,0,0,0,0,0xbd653e30,
0xbe37bce8,0,0,0,0,0xbe37bce8,0,0,0,0,0xbe37bce8,0,0,0,0,0xbe37bce8,
0x3d653e30,0,0,0,0,0x3d653e30,0,0,0,0,0x3d653e30,0,0,0,0,0x3d653e30,
0xbe373ce8,0,0,0,0,0xbe373ce8,0,0,0,0,0xbe373ce8,0,0,0,0,0xbe373ce8,
0x3d653e30,0,0,0,0,0x3d653e30,0,0,0,0,0x3d653e30,0,0,0,0,0x3d653e30,
0xbe37bce8,0,0,0,0,0xbe37bce8,0,0,0,0,0xbe37bce8,0,0,0,0,0xbe37bce8,
0xbe390000,0,0,0,0,0xbe390000,0,0,0,0,0xbe390000,0,0,0,0,0xbe390000,
0x3e03be03,0,0,0,0,0x3e03be03,0,0,0,0,0x3e03be03,0,0,0,0,0x3e03be03,
0x3ddabe16,0,0,0,0,0x3ddabe16,0,0,0,0,0x3ddabe16,0,0,0,0,0x3ddabe16,
0x3da83e25,0,0,0,0,0x3da83e25,0,0,0,0,0x3da83e25,0,0,0,0,0x3da83e25,
0x80003e39,0,0,0,0,0x80003e39,0,0,0,0,0x80003e39,0,0,0,0,0x80003e39,
0xbe03be03,0,0,0,0,0xbe03be03,0,0,0,0,0xbe03be03,0,0,0,0,0xbe03be03,
0xbe390000,0,0,0,0,0xbe390000,0,0,0,0,0xbe390000,0,0,0,0,0xbe390000,
0x3da8be25,0,0,0,0,0x3da8be25,0,0,0,0,0x3da8be25,0,0,0,0,0x3da8be25,
0x3e390000,0,0,0,0,0x3e390000,0,0,0,0,0x3e390000,0,0,0,0,0x3e390000,
0xbe033e03,0,0,0,0,0xbe033e03,0,0,0,0,0xbe033e03,0,0,0,0,0xbe033e03,
0x3dda3e16,0,0,0,0,0x3dda3e16,0,0,0,0,0x3dda3e16,0,0,0,0,0x3dda3e16,
0xbe373ce8,0,0,0,0,0xbe373ce8,0,0,0,0,0xbe373ce8,0,0,0,0,0xbe373ce8,
0x8000be39,0,0,0,0,0x8000be39,0,0,0,0,0x8000be39,0,0,0,0,0x8000be39,
0x3e033e03,0,0,0,0,0x3e033e03,0,0,0,0,0x3e033e03,0,0,0,0,0x3e033e03,
0x3d65be30,0,0,0,0,0x3d65be30,0,0,0,0,0x3d65be30,0,0,0,0,0x3d65be30,
0x3e033e03,0,0,0,0,0x3e033e03,0,0,0,0,0x3e033e03,0,0,0,0,0x3e033e03,
0xbe390000,0,0,0,0,0xbe390000,0,0,0,0,0xbe390000,0,0,0,0,0xbe390000,
0x3e03be03,0,0,0,0,0x3e03be03,0,0,0,0,0x3e03be03,0,0,0,0,0x3e03be03,
0xbe303d65,0,0,0,0,0xbe303d65,0,0,0,0,0xbe303d65,0,0,0,0,0xbe303d65,
0x3ce8be37,0,0,0,0,0x3ce8be37,0,0,0,0,0x3ce8be37,0,0,0,0,0x3ce8be37,
0x80003e39,0,0,0,0,0x80003e39,0,0,0,0,0x80003e39,0,0,0,0,0x80003e39,
0xbe03be03,0,0,0,0,0xbe03be03,0,0,0,0,0xbe03be03,0,0,0,0,0xbe03be03,
0x3e163dda,0,0,0,0,0x3e163dda,0,0,0,0,0x3e163dda,0,0,0,0,0x3e163dda,
0xbe253da8,0,0,0,0,0xbe253da8,0,0,0,0,0xbe253da8,0,0,0,0,0xbe253da8,
0x3e390000,0,0,0,0,0x3e390000,0,0,0,0,0x3e390000,0,0,0,0,0x3e390000,
0xbe033e03,0,0,0,0,0xbe033e03,0,0,0,0,0xbe033e03,0,0,0,0,0xbe033e03,
0x3d65be30,0,0,0,0,0x3d65be30,0,0,0,0,0x3d65be30,0,0,0,0,0x3d65be30,
0x3ce83e37,0,0,0,0,0x3ce83e37,0,0,0,0,0x3ce83e37,0,0,0,0,0x3ce83e37,
0x3e163dda,0,0,0,0,0x3e163dda,0,0,0,0,0x3e163dda,0,0,0,0,0x3e163dda,
0xbe25bda8,0,0,0,0,0xbe25bda8,0,0,0,0,0xbe25bda8,0,0,0,0,0xbe25bda8,
0xbddabe16,0,0,0,0,0xbddabe16,0,0,0,0,0xbddabe16,0,0,0,0,0xbddabe16,
0x3e253da8,0,0,0,0,0x3e253da8,0,0,0,0,0x3e253da8,0,0,0,0,0x3e253da8,
0x3e303d65,0,0,0,0,0x3e303d65,0,0,0,0,0x3e303d65,0,0,0,0,0x3e303d65,
0xbe37bce8,0,0,0,0,0xbe37bce8,0,0,0,0,0xbe37bce8,0,0,0,0,0xbe37bce8,
0xbe390000,0,0,0,0,0xbe390000,0,0,0,0,0xbe390000,0,0,0,0,0xbe390000,
0x3e25bda8,0,0,0,0,0x3e25bda8,0,0,0,0,0x3e25bda8,0,0,0,0,0x3e25bda8,
0x3e390000,0,0,0,0,0x3e390000,0,0,0,0,0x3e390000,0,0,0,0,0x3e390000,
0xbe373ce8,0,0,0,0,0xbe373ce8,0,0,0,0,0xbe373ce8,0,0,0,0,0xbe373ce8,
0xbdda3e16,0,0,0,0,0xbdda3e16,0,0,0,0,0xbdda3e16,0,0,0,0,0xbdda3e16,
0x3ce8be37,0,0,0,0,0x3ce8be37,0,0,0,0,0x3ce8be37,0,0,0,0,0x3ce8be37,
0x3e30bd65,0,0,0,0,0x3e30bd65,0,0,0,0,0x3e30bd65,0,0,0,0,0x3e30bd65,
0xbe253da8,0,0,0,0,0xbe253da8,0,0,0,0,0xbe253da8,0,0,0,0,0xbe253da8,
0x3d653e30,0,0,0,0,0x3d653e30,0,0,0,0,0x3d653e30,0,0,0,0,0x3d653e30,
0xbe03be03,0,0,0,0,0xbe03be03,0,0,0,0,0xbe03be03,0,0,0,0,0xbe03be03,
0x3e16bdda,0,0,0,0,0x3e16bdda,0,0,0,0,0x3e16bdda,0,0,0,0,0x3e16bdda,
0xbe033e03,0,0,0,0,0xbe033e03,0,0,0,0,0xbe033e03,0,0,0,0,0xbe033e03,
0x3e303d65,0,0,0,0,0x3e303d65,0,0,0,0,0x3e303d65,0,0,0,0,0x3e303d65,
0xbe373ce8,0,0,0,0,0xbe373ce8,0,0,0,0,0xbe373ce8,0,0,0,0,0xbe373ce8,
0x3ddabe16,0,0,0,0,0x3ddabe16,0,0,0,0,0x3ddabe16,0,0,0,0,0x3ddabe16,
0xbda83e25,0,0,0,0,0xbda83e25,0,0,0,0,0xbda83e25,0,0,0,0,0xbda83e25,
0x3e16bdda,0,0,0,0,0x3e16bdda,0,0,0,0,0x3e16bdda,0,0,0,0,0x3e16bdda,
0xbda83e25,0,0,0,0,0xbda83e25,0,0,0,0,0xbda83e25,0,0,0,0,0xbda83e25,
0x3d65be30,0,0,0,0,0x3d65be30,0,0,0,0,0x3d65be30,0,0,0,0,0x3d65be30,
0xbce83e37,0,0,0,0,0xbce83e37,0,0,0,0,0xbce83e37,0,0,0,0,0xbce83e37,
0,0,0xbe163dda,0,0,0,0,0xbe163dda,0,0,0xbe253da8,0,0,0,0,0xbe253da8,
0,0,0xbe303d65,0,0,0,0,0xbe303d65,0,0,0xbe373ce8,0,0,0,0,0xbe373ce8,
0,0,0xbd65be30,0,0,0,0,0xbd65be30,0,0,0x3ce8be37,0,0,0,0,0x3ce8be37,
0,0,0x3ddabe16,0,0,0,0,0x3ddabe16,0,0,0x3e25bda8,0,0,0,0,0x3e25bda8,
0,0,0xbe390000,0,0,0,0,0xbe390000,0,0,0xbe37bce8,0,0,0,0,0xbe37bce8,
0,0,0xbe30bd65,0,0,0,0,0xbe30bd65,0,0,0xbe25bda8,0,0,0,0,0xbe25bda8,
0,0,0x3e390000,0,0,0,0,0x3e390000,0,0,0x3e253da8,0,0,0,0,0x3e253da8,
0,0,0x3dda3e16,0,0,0,0,0x3dda3e16,0,0,0x3ce83e37,0,0,0,0,0x3ce83e37,
0,0,0xbe16bdda,0,0,0,0,0xbe16bdda,0,0,0xbe03be03,0,0,0,0,0xbe03be03,
0,0,0xbddabe16,0,0,0,0,0xbddabe16,0,0,0xbda8be25,0,0,0,0,0xbda8be25,
0,0,0xbd653e30,0,0,0,0,0xbd653e30,0,0,0xbe033e03,0,0,0,0,0xbe033e03,
0,0,0xbe303d65,0,0,0,0,0xbe303d65,0,0,0xbe37bce8,0,0,0,0,0xbe37bce8,
0,0,0xbd65be30,0,0,0,0,0xbd65be30,0,0,0xbce8be37,0,0,0,0,0xbce8be37,
0,0,0,0,0,0,0,0,0,0,0,0,0,0,0,0,
0,0,0xbe16bdda,0,0,0,0,0xbe16bdda,0,0,0xbda8be25,0,0,0,0,0xbda8be25,
0,0,0,0,0,0,0,0,0,0,0,0,0,0,0,0,
0,0,0x3e390000,0,0,0,0,0x3e390000,0,0,0x3e033e03,0,0,0,0,0x3e033e03,
0,0,0x80003e39,0,0,0,0,0x80003e39,0,0,0xbe033e03,0,0,0,0,0xbe033e03,
0,0,0xbd653e30,0,0,0,0,0xbd653e30,0,0,0xbe373ce8,0,0,0,0,0xbe373ce8,
0,0,0xbddabe16,0,0,0,0,0xbddabe16,0,0,0x3da8be25,0,0,0,0,0x3da8be25,
0,0,0xbe390000,0,0,0,0,0xbe390000,0,0,0xbe03be03,0,0,0,0,0xbe03be03,
0,0,0x8000be39,0,0,0,0,0x8000be39,0,0,0x3e03be03,0,0,0,0,0x3e03be03,
0,0,0x3e390000,0,0,0,0,0x3e390000,0,0,0x3da83e25,0,0,0,0,0x3da83e25,
0,0,0xbdda3e16,0,0,0,0,0xbdda3e16,0,0,0xbe37bce8,0,0,0,0,0xbe37bce8,
0,0,0x3e390000,0,0,0,0,0x3e390000,0,0,0x3e033e03,0,0,0,0,0x3e033e03,
0,0,0x80003e39,0,0,0,0,0x80003e39,0,0,0xbe033e03,0,0,0,0,0xbe033e03,
0,0,0xbd65be30,0,0,0,0,0xbd65be30,0,0,0x3e03be03,0,0,0,0,0x3e03be03,
0,0,0x3e303d65,0,0,0,0,0x3e303d65,0,0,0x3ce83e37,0,0,0,0,0x3ce83e37,
0,0,0xbe390000,0,0,0,0,0xbe390000,0,0,0xbe03be03,0,0,0,0,0xbe03be03,
0,0,0,0,0,0,0,0,0,0,0,0,0,0,0,0,
0,0,0xbe163dda,0,0,0,0,0xbe163dda,0,0,0xbe25bda8,0,0,0,0,0xbe25bda8,
0,0,0,0,0,0,0,0,0,0,0,0,0,0,0,0,
0,0,0xbe16bdda,0,0,0,0,0xbe16bdda,0,0,0x3da8be25,0,0,0,0,0x3da8be25,
0,0,0x3e303d65,0,0,0,0,0x3e303d65,0,0,0xbce83e37,0,0,0,0,0xbce83e37,
0,0,0x3e16bdda,0,0,0,0,0x3e16bdda,0,0,0x3da83e25,0,0,0,0,0x3da83e25,
0,0,0xbe303d65,0,0,0,0,0xbe303d65,0,0,0xbce8be37,0,0,0,0,0xbce8be37,
0,0,0xbe390000,0,0,0,0,0xbe390000,0,0,0xbce8be37,0,0,0,0,0xbce8be37,
0,0,0x3e30bd65,0,0,0,0,0x3e30bd65,0,0,0x3da83e25,0,0,0,0,0x3da83e25,
0,0,0x3e390000,0,0,0,0,0x3e390000,0,0,0xbce83e37,0,0,0,0,0xbce83e37,
0,0,0xbe30bd65,0,0,0,0,0xbe30bd65,0,0,0x3da8be25,0,0,0,0,0x3da8be25,
0,0,0xbe163dda,0,0,0,0,0xbe163dda,0,0,0xbe03be03,0,0,0,0,0xbe03be03,
0,0,0x3ddabe16,0,0,0,0,0x3ddabe16,0,0,0x3e253da8,0,0,0,0,0x3e253da8,
0,0,0x3e163dda,0,0,0,0,0x3e163dda,0,0,0xbe033e03,0,0,0,0,0xbe033e03,
0,0,0xbddabe16,0,0,0,0,0xbddabe16,0,0,0x3e25bda8,0,0,0,0,0x3e25bda8,
0,0,0xbd653e30,0,0,0,0,0xbd653e30,0,0,0xbe37bce8,0,0,0,0,0xbe37bce8,
0,0,0,0,0,0,0,0,0,0,0,0,0,0,0,0,
0,0,0x3d653e30,0,0,0,0,0x3d653e30,0,0,0xbe373ce8,0,0,0,0,0xbe373ce8,
0,0,0,0,0,0,0,0,0,0,0,0,0,0,0,0,
0,0,0x3d653e30,0,0,0,0,0x3d653e30,0,0,0xbe37bce8,0,0,0,0,0xbe37bce8,
0,0,0x3ddabe16,0,0,0,0,0x3ddabe16,0,0,0x3da83e25,0,0,0,0,0x3da83e25,
0,0,0xbe390000,0,0,0,0,0xbe390000,0,0,0x3e03be03,0,0,0,0,0x3e03be03,
0,0,0x80003e39,0,0,0,0,0x80003e39,0,0,0xbe03be03,0,0,0,0,0xbe03be03,
0,0,0xbe390000,0,0,0,0,0xbe390000,0,0,0x3da8be25,0,0,0,0,0x3da8be25,
0,0,0x3dda3e16,0,0,0,0,0x3dda3e16,0,0,0xbe373ce8,0,0,0,0,0xbe373ce8,
0,0,0x3e390000,0,0,0,0,0x3e390000,0,0,0xbe033e03,0,0,0,0,0xbe033e03,
0,0,0x8000be39,0,0,0,0,0x8000be39,0,0,0x3e033e03,0,0,0,0,0x3e033e03,
0,0,0x3d65be30,0,0,0,0,0x3d65be30,0,0,0x3e033e03,0,0,0,0,0x3e033e03,
0,0,0xbe303d65,0,0,0,0,0xbe303d65,0,0,0x3ce8be37,0,0,0,0,0x3ce8be37,
0,0,0xbe390000,0,0,0,0,0xbe390000,0,0,0x3e03be03,0,0,0,0,0x3e03be03,
0,0,0x80003e39,0,0,0,0,0x80003e39,0,0,0xbe03be03,0,0,0,0,0xbe03be03,
0,0,0x3e163dda,0,0,0,0,0x3e163dda,0,0,0xbe253da8,0,0,0,0,0xbe253da8,
0,0,0,0,0,0,0,0,0,0,0,0,0,0,0,0,
0,0,0x3e390000,0,0,0,0,0x3e390000,0,0,0xbe033e03,0,0,0,0,0xbe033e03,
0,0,0,0,0,0,0,0,0,0,0,0,0,0,0,0,
0,0,0x3d65be30,0,0,0,0,0x3d65be30,0,0,0x3ce83e37,0,0,0,0,0x3ce83e37,
0,0,0xbddabe16,0,0,0,0,0xbddabe16,0,0,0x3e253da8,0,0,0,0,0x3e253da8,
0,0,0x3e163dda,0,0,0,0,0x3e163dda,0,0,0xbe25bda8,0,0,0,0,0xbe25bda8,
0,0,0x3e303d65,0,0,0,0,0x3e303d65,0,0,0xbe37bce8,0,0,0,0,0xbe37bce8,
0,0,0xbe390000,0,0,0,0,0xbe390000,0,0,0x3e25bda8,0,0,0,0,0x3e25bda8,
0,0,0xbdda3e16,0,0,0,0,0xbdda3e16,0,0,0x3ce8be37,0,0,0,0,0x3ce8be37,
0,0,0x3e390000,0,0,0,0,0x3e390000,0,0,0xbe373ce8,0,0,0,0,0xbe373ce8,
0,0,0x3e30bd65,0,0,0,0,0x3e30bd65,0,0,0xbe253da8,0,0,0,0,0xbe253da8,
0,0,0x3d653e30,0,0,0,0,0x3d653e30,0,0,0xbe03be03,0,0,0,0,0xbe03be03,
0,0,0x3e303d65,0,0,0,0,0x3e303d65,0,0,0xbe373ce8,0,0,0,0,0xbe373ce8,
0,0,0x3e16bdda,0,0,0,0,0x3e16bdda,0,0,0xbe033e03,0,0,0,0,0xbe033e03,
0,0,0x3ddabe16,0,0,0,0,0x3ddabe16,0,0,0xbda83e25,0,0,0,0,0xbda83e25,
0,0,0x3e16bdda,0,0,0,0,0x3e16bdda,0,0,0xbda83e25,0,0,0,0,0xbda83e25,
0,0,0,0,0,0,0,0,0,0,0,0,0,0,0,0,
0,0,0x3d65be30,0,0,0,0,0x3d65be30,0,0,0xbce83e37,0,0,0,0,0xbce83e37,
0,0,0,0,0,0,0,0,0,0,0,0,0,0,0,0,
};
constexpr unsigned long long COS_PK0 = 0x3f903f9a3fa03fa2ull;
constexpr unsigned long long COS_PK1 = 0x3f133f3e3f653f83ull;
constexpr unsigned long long COS_PK2 = 0x3e4b3ec8ull;

__device__ __forceinline__ void wgmma_ss_n80_z(float (&d)[40], uint64_t da, uint64_t db) {
  asm volatile("{\n.reg .pred p;\nsetp.ne.b32 p, 0, 0;\nwgmma.mma_async.sync.aligned.m64n80k16.f32.bf16.bf16 {%0,%1,%2,%3,%4,%5,%6,%7,%8,%9,%10,%11,%12,%13,%14,%15,%16,%17,%18,%19,%20,%21,%22,%23,%24,%25,%26,%27,%28,%29,%30,%31,%32,%33,%34,%35,%36,%37,%38,%39}, %40, %41, p, 1, 1, 1, 0;\n}\n"
    : "+f"(d[0]), "+f"(d[1]), "+f"(d[2]), "+f"(d[3]), "+f"(d[4]), "+f"(d[5]), "+f"(d[6]), "+f"(d[7]), "+f"(d[8]), "+f"(d[9]), "+f"(d[10]), "+f"(d[11]), "+f"(d[12]), "+f"(d[13]), "+f"(d[14]), "+f"(d[15]), "+f"(d[16]), "+f"(d[17]), "+f"(d[18]), "+f"(d[19]), "+f"(d[20]), "+f"(d[21]), "+f"(d[22]), "+f"(d[23]), "+f"(d[24]), "+f"(d[25]), "+f"(d[26]), "+f"(d[27]), "+f"(d[28]), "+f"(d[29]), "+f"(d[30]), "+f"(d[31]), "+f"(d[32]), "+f"(d[33]), "+f"(d[34]), "+f"(d[35]), "+f"(d[36]), "+f"(d[37]), "+f"(d[38]), "+f"(d[39])
    : "l"(da), "l"(db));
}
__device__ __forceinline__ void wgmma_ss_n80_a(float (&d)[40], uint64_t da, uint64_t db) {
  asm volatile("{\n.reg .pred p;\nsetp.ne.b32 p, 1, 0;\nwgmma.mma_async.sync.aligned.m64n80k16.f32.bf16.bf16 {%0,%1,%2,%3,%4,%5,%6,%7,%8,%9,%10,%11,%12,%13,%14,%15,%16,%17,%18,%19,%20,%21,%22,%23,%24,%25,%26,%27,%28,%29,%30,%31,%32,%33,%34,%35,%36,%37,%38,%39}, %40, %41, p, 1, 1, 1, 0;\n}\n"
    : "+f"(d[0]), "+f"(d[1]), "+f"(d[2]), "+f"(d[3]), "+f"(d[4]), "+f"(d[5]), "+f"(d[6]), "+f"(d[7]), "+f"(d[8]), "+f"(d[9]), "+f"(d[10]), "+f"(d[11]), "+f"(d[12]), "+f"(d[13]), "+f"(d[14]), "+f"(d[15]), "+f"(d[16]), "+f"(d[17]), "+f"(d[18]), "+f"(d[19]), "+f"(d[20]), "+f"(d[21]), "+f"(d[22]), "+f"(d[23]), "+f"(d[24]), "+f"(d[25]), "+f"(d[26]), "+f"(d[27]), "+f"(d[28]), "+f"(d[29]), "+f"(d[30]), "+f"(d[31]), "+f"(d[32]), "+f"(d[33]), "+f"(d[34]), "+f"(d[35]), "+f"(d[36]), "+f"(d[37]), "+f"(d[38]), "+f"(d[39])
    : "l"(da), "l"(db));
}

__device__ __forceinline__ void wgmma_rs_n40_z(float (&d)[20], uint32_t a0, uint32_t a1, uint32_t a2, uint32_t a3, uint64_t db) {
  asm volatile("{\n.reg .pred p;\nsetp.ne.b32 p, 0, 0;\nwgmma.mma_async.sync.aligned.m64n40k16.f32.bf16.bf16 {%0,%1,%2,%3,%4,%5,%6,%7,%8,%9,%10,%11,%12,%13,%14,%15,%16,%17,%18,%19}, {%20,%21,%22,%23}, %24, p, 1, 1, 0;\n}\n"
    : "+f"(d[0]), "+f"(d[1]), "+f"(d[2]), "+f"(d[3]), "+f"(d[4]), "+f"(d[5]), "+f"(d[6]), "+f"(d[7]), "+f"(d[8]), "+f"(d[9]), "+f"(d[10]), "+f"(d[11]), "+f"(d[12]), "+f"(d[13]), "+f"(d[14]), "+f"(d[15]), "+f"(d[16]), "+f"(d[17]), "+f"(d[18]), "+f"(d[19])
    : "r"(a0), "r"(a1), "r"(a2), "r"(a3), "l"(db));
}
__device__ __forceinline__ void wgmma_rs_n40_a(float (&d)[20], uint32_t a0, uint32_t a1, uint32_t a2, uint32_t a3, uint64_t db) {
  asm volatile("{\n.reg .pred p;\nsetp.ne.b32 p, 1, 0;\nwgmma.mma_async.sync.aligned.m64n40k16.f32.bf16.bf16 {%0,%1,%2,%3,%4,%5,%6,%7,%8,%9,%10,%11,%12,%13,%14,%15,%16,%17,%18,%19}, {%20,%21,%22,%23}, %24, p, 1, 1, 0;\n}\n"
    : "+f"(d[0]), "+f"(d[1]), "+f"(d[2]), "+f"(d[3]), "+f"(d[4]), "+f"(d[5]), "+f"(d[6]), "+f"(d[7]), "+f"(d[8]), "+f"(d[9]), "+f"(d[10]), "+f"(d[11]), "+f"(d[12]), "+f"(d[13]), "+f"(d[14]), "+f"(d[15]), "+f"(d[16]), "+f"(d[17]), "+f"(d[18]), "+f"(d[19])
    : "r"(a0), "r"(a1), "r"(a2), "r"(a3), "l"(db));
}

__device__ __forceinline__ void wgmma_rs_n128_z(float (&d)[64], uint32_t a0, uint32_t a1, uint32_t a2, uint32_t a3, uint64_t db) {
  asm volatile("{\n.reg .pred p;\nsetp.ne.b32 p, 0, 0;\nwgmma.mma_async.sync.aligned.m64n128k16.f32.bf16.bf16 {%0,%1,%2,%3,%4,%5,%6,%7,%8,%9,%10,%11,%12,%13,%14,%15,%16,%17,%18,%19,%20,%21,%22,%23,%24,%25,%26,%27,%28,%29,%30,%31,%32,%33,%34,%35,%36,%37,%38,%39,%40,%41,%42,%43,%44,%45,%46,%47,%48,%49,%50,%51,%52,%53,%54,%55,%56,%57,%58,%59,%60,%61,%62,%63}, {%64,%65,%66,%67}, %68, p, 1, 1, 1;\n}\n"
    : "+f"(d[0]), "+f"(d[1]), "+f"(d[2]), "+f"(d[3]), "+f"(d[4]), "+f"(d[5]), "+f"(d[6]), "+f"(d[7]), "+f"(d[8]), "+f"(d[9]), "+f"(d[10]), "+f"(d[11]), "+f"(d[12]), "+f"(d[13]), "+f"(d[14]), "+f"(d[15]), "+f"(d[16]), "+f"(d[17]), "+f"(d[18]), "+f"(d[19]), "+f"(d[20]), "+f"(d[21]), "+f"(d[22]), "+f"(d[23]), "+f"(d[24]), "+f"(d[25]), "+f"(d[26]), "+f"(d[27]), "+f"(d[28]), "+f"(d[29]), "+f"(d[30]), "+f"(d[31]), "+f"(d[32]), "+f"(d[33]), "+f"(d[34]), "+f"(d[35]), "+f"(d[36]), "+f"(d[37]), "+f"(d[38]), "+f"(d[39]), "+f"(d[40]), "+f"(d[41]), "+f"(d[42]), "+f"(d[43]), "+f"(d[44]), "+f"(d[45]), "+f"(d[46]), "+f"(d[47]), "+f"(d[48]), "+f"(d[49]), "+f"(d[50]), "+f"(d[51]), "+f"(d[52]), "+f"(d[53]), "+f"(d[54]), "+f"(d[55]), "+f"(d[56]), "+f"(d[57]), "+f"(d[58]), "+f"(d[59]), "+f"(d[60]), "+f"(d[61]), "+f"(d[62]), "+f"(d[63])
    : "r"(a0), "r"(a1), "r"(a2), "r"(a3), "l"(db));
}
__device__ __forceinline__ void wgmma_rs_n128_a(float (&d)[64], uint32_t a0, uint32_t a1, uint32_t a2, uint32_t a3, uint64_t db) {
  asm volatile("{\n.reg .pred p;\nsetp.ne.b32 p, 1, 0;\nwgmma.mma_async.sync.aligned.m64n128k16.f32.bf16.bf16 {%0,%1,%2,%3,%4,%5,%6,%7,%8,%9,%10,%11,%12,%13,%14,%15,%16,%17,%18,%19,%20,%21,%22,%23,%24,%25,%26,%27,%28,%29,%30,%31,%32,%33,%34,%35,%36,%37,%38,%39,%40,%41,%42,%43,%44,%45,%46,%47,%48,%49,%50,%51,%52,%53,%54,%55,%56,%57,%58,%59,%60,%61,%62,%63}, {%64,%65,%66,%67}, %68, p, 1, 1, 1;\n}\n"
    : "+f"(d[0]), "+f"(d[1]), "+f"(d[2]), "+f"(d[3]), "+f"(d[4]), "+f"(d[5]), "+f"(d[6]), "+f"(d[7]), "+f"(d[8]), "+f"(d[9]), "+f"(d[10]), "+f"(d[11]), "+f"(d[12]), "+f"(d[13]), "+f"(d[14]), "+f"(d[15]), "+f"(d[16]), "+f"(d[17]), "+f"(d[18]), "+f"(d[19]), "+f"(d[20]), "+f"(d[21]), "+f"(d[22]), "+f"(d[23]), "+f"(d[24]), "+f"(d[25]), "+f"(d[26]), "+f"(d[27]), "+f"(d[28]), "+f"(d[29]), "+f"(d[30]), "+f"(d[31]), "+f"(d[32]), "+f"(d[33]), "+f"(d[34]), "+f"(d[35]), "+f"(d[36]), "+f"(d[37]), "+f"(d[38]), "+f"(d[39]), "+f"(d[40]), "+f"(d[41]), "+f"(d[42]), "+f"(d[43]), "+f"(d[44]), "+f"(d[45]), "+f"(d[46]), "+f"(d[47]), "+f"(d[48]), "+f"(d[49]), "+f"(d[50]), "+f"(d[51]), "+f"(d[52]), "+f"(d[53]), "+f"(d[54]), "+f"(d[55]), "+f"(d[56]), "+f"(d[57]), "+f"(d[58]), "+f"(d[59]), "+f"(d[60]), "+f"(d[61]), "+f"(d[62]), "+f"(d[63])
    : "r"(a0), "r"(a1), "r"(a2), "r"(a3), "l"(db));
}

__device__ __forceinline__ void wgmma_rs_n32_z(float (&d)[16], uint32_t a0, uint32_t a1, uint32_t a2, uint32_t a3, uint64_t db) {
  asm volatile("{\n.reg .pred p;\nsetp.ne.b32 p, 0, 0;\nwgmma.mma_async.sync.aligned.m64n32k16.f32.bf16.bf16 {%0,%1,%2,%3,%4,%5,%6,%7,%8,%9,%10,%11,%12,%13,%14,%15}, {%16,%17,%18,%19}, %20, p, 1, 1, 0;\n}\n"
    : "+f"(d[0]), "+f"(d[1]), "+f"(d[2]), "+f"(d[3]), "+f"(d[4]), "+f"(d[5]), "+f"(d[6]), "+f"(d[7]), "+f"(d[8]), "+f"(d[9]), "+f"(d[10]), "+f"(d[11]), "+f"(d[12]), "+f"(d[13]), "+f"(d[14]), "+f"(d[15])
    : "r"(a0), "r"(a1), "r"(a2), "r"(a3), "l"(db));
}
__device__ __forceinline__ void wgmma_rs_n32_a(float (&d)[16], uint32_t a0, uint32_t a1, uint32_t a2, uint32_t a3, uint64_t db) {
  asm volatile("{\n.reg .pred p;\nsetp.ne.b32 p, 1, 0;\nwgmma.mma_async.sync.aligned.m64n32k16.f32.bf16.bf16 {%0,%1,%2,%3,%4,%5,%6,%7,%8,%9,%10,%11,%12,%13,%14,%15}, {%16,%17,%18,%19}, %20, p, 1, 1, 0;\n}\n"
    : "+f"(d[0]), "+f"(d[1]), "+f"(d[2]), "+f"(d[3]), "+f"(d[4]), "+f"(d[5]), "+f"(d[6]), "+f"(d[7]), "+f"(d[8]), "+f"(d[9]), "+f"(d[10]), "+f"(d[11]), "+f"(d[12]), "+f"(d[13]), "+f"(d[14]), "+f"(d[15])
    : "r"(a0), "r"(a1), "r"(a2), "r"(a3), "l"(db));
}

__device__ __forceinline__ void wgmma_rs_n64_z(float (&d)[32], uint32_t a0, uint32_t a1, uint32_t a2, uint32_t a3, uint64_t db) {
  asm volatile("{\n.reg .pred p;\nsetp.ne.b32 p, 0, 0;\nwgmma.mma_async.sync.aligned.m64n64k16.f32.bf16.bf16 {%0,%1,%2,%3,%4,%5,%6,%7,%8,%9,%10,%11,%12,%13,%14,%15,%16,%17,%18,%19,%20,%21,%22,%23,%24,%25,%26,%27,%28,%29,%30,%31}, {%32,%33,%34,%35}, %36, p, 1, 1, 0;\n}\n"
    : "+f"(d[0]), "+f"(d[1]), "+f"(d[2]), "+f"(d[3]), "+f"(d[4]), "+f"(d[5]), "+f"(d[6]), "+f"(d[7]), "+f"(d[8]), "+f"(d[9]), "+f"(d[10]), "+f"(d[11]), "+f"(d[12]), "+f"(d[13]), "+f"(d[14]), "+f"(d[15]), "+f"(d[16]), "+f"(d[17]), "+f"(d[18]), "+f"(d[19]), "+f"(d[20]), "+f"(d[21]), "+f"(d[22]), "+f"(d[23]), "+f"(d[24]), "+f"(d[25]), "+f"(d[26]), "+f"(d[27]), "+f"(d[28]), "+f"(d[29]), "+f"(d[30]), "+f"(d[31])
    : "r"(a0), "r"(a1), "r"(a2), "r"(a3), "l"(db));
}
__device__ __forceinline__ void wgmma_rs_n64_a(float (&d)[32], uint32_t a0, uint32_t a1, uint32_t a2, uint32_t a3, uint64_t db) {
  asm volatile("{\n.reg .pred p;\nsetp.ne.b32 p, 1, 0;\nwgmma.mma_async.sync.aligned.m64n64k16.f32.bf16.bf16 {%0,%1,%2,%3,%4,%5,%6,%7,%8,%9,%10,%11,%12,%13,%14,%15,%16,%17,%18,%19,%20,%21,%22,%23,%24,%25,%26,%27,%28,%29,%30,%31}, {%32,%33,%34,%35}, %36, p, 1, 1, 0;\n}\n"
    : "+f"(d[0]), "+f"(d[1]), "+f"(d[2]), "+f"(d[3]), "+f"(d[4]), "+f"(d[5]), "+f"(d[6]), "+f"(d[7]), "+f"(d[8]), "+f"(d[9]), "+f"(d[10]), "+f"(d[11]), "+f"(d[12]), "+f"(d[13]), "+f"(d[14]), "+f"(d[15]), "+f"(d[16]), "+f"(d[17]), "+f"(d[18]), "+f"(d[19]), "+f"(d[20]), "+f"(d[21]), "+f"(d[22]), "+f"(d[23]), "+f"(d[24]), "+f"(d[25]), "+f"(d[26]), "+f"(d[27]), "+f"(d[28]), "+f"(d[29]), "+f"(d[30]), "+f"(d[31])
    : "r"(a0), "r"(a1), "r"(a2), "r"(a3), "l"(db));
}

__device__ __forceinline__ void wgmma_ss_n32_z(float (&d)[16], uint64_t da, uint64_t db) {
  asm volatile("{\n.reg .pred p;\nsetp.ne.b32 p, 0, 0;\nwgmma.mma_async.sync.aligned.m64n32k16.f32.bf16.bf16 {%0,%1,%2,%3,%4,%5,%6,%7,%8,%9,%10,%11,%12,%13,%14,%15}, %16, %17, p, 1, 1, 1, 0;\n}\n"
    : "+f"(d[0]), "+f"(d[1]), "+f"(d[2]), "+f"(d[3]), "+f"(d[4]), "+f"(d[5]), "+f"(d[6]), "+f"(d[7]), "+f"(d[8]), "+f"(d[9]), "+f"(d[10]), "+f"(d[11]), "+f"(d[12]), "+f"(d[13]), "+f"(d[14]), "+f"(d[15])
    : "l"(da), "l"(db));
}
__device__ __forceinline__ void wgmma_ss_n32_a(float (&d)[16], uint64_t da, uint64_t db) {
  asm volatile("{\n.reg .pred p;\nsetp.ne.b32 p, 1, 0;\nwgmma.mma_async.sync.aligned.m64n32k16.f32.bf16.bf16 {%0,%1,%2,%3,%4,%5,%6,%7,%8,%9,%10,%11,%12,%13,%14,%15}, %16, %17, p, 1, 1, 1, 0;\n}\n"
    : "+f"(d[0]), "+f"(d[1]), "+f"(d[2]), "+f"(d[3]), "+f"(d[4]), "+f"(d[5]), "+f"(d[6]), "+f"(d[7]), "+f"(d[8]), "+f"(d[9]), "+f"(d[10]), "+f"(d[11]), "+f"(d[12]), "+f"(d[13]), "+f"(d[14]), "+f"(d[15])
    : "l"(da), "l"(db));
}

__device__ __forceinline__ void wgmma_ss_n40_z(float (&d)[20], uint64_t da, uint64_t db) {
  asm volatile("{\n.reg .pred p;\nsetp.ne.b32 p, 0, 0;\nwgmma.mma_async.sync.aligned.m64n40k16.f32.bf16.bf16 {%0,%1,%2,%3,%4,%5,%6,%7,%8,%9,%10,%11,%12,%13,%14,%15,%16,%17,%18,%19}, %20, %21, p, 1, 1, 1, 0;\n}\n"
    : "+f"(d[0]), "+f"(d[1]), "+f"(d[2]), "+f"(d[3]), "+f"(d[4]), "+f"(d[5]), "+f"(d[6]), "+f"(d[7]), "+f"(d[8]), "+f"(d[9]), "+f"(d[10]), "+f"(d[11]), "+f"(d[12]), "+f"(d[13]), "+f"(d[14]), "+f"(d[15]), "+f"(d[16]), "+f"(d[17]), "+f"(d[18]), "+f"(d[19])
    : "l"(da), "l"(db));
}
__device__ __forceinline__ void wgmma_ss_n40_a(float (&d)[20], uint64_t da, uint64_t db) {
  asm volatile("{\n.reg .pred p;\nsetp.ne.b32 p, 1, 0;\nwgmma.mma_async.sync.aligned.m64n40k16.f32.bf16.bf16 {%0,%1,%2,%3,%4,%5,%6,%7,%8,%9,%10,%11,%12,%13,%14,%15,%16,%17,%18,%19}, %20, %21, p, 1, 1, 1, 0;\n}\n"
    : "+f"(d[0]), "+f"(d[1]), "+f"(d[2]), "+f"(d[3]), "+f"(d[4]), "+f"(d[5]), "+f"(d[6]), "+f"(d[7]), "+f"(d[8]), "+f"(d[9]), "+f"(d[10]), "+f"(d[11]), "+f"(d[12]), "+f"(d[13]), "+f"(d[14]), "+f"(d[15]), "+f"(d[16]), "+f"(d[17]), "+f"(d[18]), "+f"(d[19])
    : "l"(da), "l"(db));
}

constexpr int NSM = 132, NH = 66;
constexpr int S0 = 0, S1 = 51200, S2 = 102400;
constexpr int C1 = 153600, C3 = C1, RG = C1 + 18432;
constexpr int WP = RG, TBL = RG + 28672, WS2 = RG + 30720;
constexpr int BARS = RG + 49152;
__host__ __device__ constexpr int wst_off(int i) { return i < 12 ? S2 + i * 4096 : WS2 + (i - 12) * 4096; }
constexpr int NBAR = 280;
constexpr int REL = BARS + NBAR * 8;
constexpr int SMEM_BYTES = REL + 16;
constexpr int B_XF = 0, B_CF1 = 15, B_CF3 = 16, B_WF = 17  , B_P1D = 18, B_REL = 21, B_ROLE = 22, B_SIG = 24;
constexpr int B_RF = 32, B_RE = 46, B_YF = 60, B_WRD = 75, B_SFREE = 89, B_WCH = 131, B_RDY = 136, B_WE = 205, B_WL = 217, B_FIN = 229, B_TOK = 232;
constexpr int R_P2 = 15, R_P3 = 57;
constexpr int CNT_P1 = 0, CNT_P2 = 4, CNT_W = 8, CNT_RANK = 9, NCLS = 10, CNT_DONE = 0, CNT_REL = 1, NCNT = 2;
constexpr int SIG_W = 0, SIG_P1 = 1, SIG_P2 = 4;
#define PFS 9088
#define T1MASK 0x3e00
#define T2MASK 0xf80

__device__ uint4 g_scr[(14 << 21) / 16];
__device__ __align__(128) uint4 g_wf[200 * 72 * 32];
__device__ __align__(128) unsigned g_cnt[NCNT * 32];
__device__ __forceinline__ int slot_line(int chunk, int pg, int cls) {
    return (pg & 1) << 6 | (pg >> 1) << 9 | (chunk & 1) << 10 | (chunk >> 1) << 12 | ((pg ^ (pg >> 1) ^ chunk ^ (chunk >> 1) ^ cls) & 1) << 5;
}
__device__ __forceinline__ int phi_line(int phi, uint32_t rel) {
    return (phi >> 4) << 14 | (phi & 3) << 7 | ((phi >> 2) & 1) << 11 | ((phi >> 3) & 1) << 13 | ((rel >> (phi >> 4)) & 1) << 5;
}
__device__ __forceinline__ int extra_mask(int rk) { return rk < 60 ? 0 : rk < 62 ? 1 : rk < 64 ? 10 : 4; }
__device__ __forceinline__ int wslot(int pc) {
    return (int)((0x576476503421ull >> (4 * pc)) & 3) * 12288 + (((0x576476503421ull >> (4 * pc)) & 4) ? S0 : RG);
}
__device__ __forceinline__ int xslot(int n) { return ((n & 4) ? S2 : RG) + ((n + 1) & 3) * 12288; }
__device__ __forceinline__ int extra_phi(int rk) { return 198 + (rk & 1); }
__host__ __device__ constexpr int quad_off(int Q) { return (Q >> 2) * 4096 + (Q & 3) * 512; }

struct Maps { CUtensorMap w, x34, x6, x28, wst, f16, f8, y4, y2; };
struct Ptrs { char* scr; const char* wf; const void* tab1; const void* tab3; unsigned* cnt; const char* x; };

__device__ __forceinline__ uint32_t smem_u32(const void* p) { return (uint32_t)__cvta_generic_to_shared(p); }
__device__ __forceinline__ void mbar_wait(uint32_t bar) {
    uint32_t ok, it = 0;
    do {
        asm volatile("{\n.reg .pred p;\nmbarrier.try_wait.parity.shared::cta.b64 p, [%1], 0;\nselp.u32 %0, 1, 0, p;\n}" : "=r"(ok) : "r"(bar) : "memory");
        if (++it > (1u << 22)) break;
    } while (!ok);
}
__device__ __forceinline__ bool mbar_test(uint32_t bar) {
    uint32_t ok;
    asm volatile("{\n.reg .pred p;\nmbarrier.test_wait.parity.shared::cta.b64 p, [%1], 0;\nselp.u32 %0, 1, 0, p;\n}" : "=r"(ok) : "r"(bar) : "memory");
    return ok;
}
__device__ __forceinline__ void fence_async() { asm volatile("fence.proxy.async;" ::: "memory"); }
__device__ __forceinline__ void fence_async_smem() { asm volatile("fence.proxy.async.shared::cta;" ::: "memory"); }
#define ELECT "{\n.reg .pred p;\nelect.sync _|p, 0xffffffff;\n@p "
__device__ __forceinline__ void e_arrive(uint32_t bar) { asm volatile(ELECT "mbarrier.arrive.shared::cta.b64 _, [%0];\n}" :: "r"(bar) : "memory"); }
__device__ __forceinline__ void e_expect(uint32_t bar, uint32_t bytes) { asm volatile(ELECT "mbarrier.arrive.expect_tx.shared::cta.b64 _, [%0], %1;\n}" :: "r"(bar), "r"(bytes) : "memory"); }
__device__ __forceinline__ void e_g2s(uint32_t dst, const void* src, uint32_t bytes, uint32_t bar) {
    asm volatile(ELECT "cp.async.bulk.shared::cluster.global.mbarrier::complete_tx::bytes [%0], [%1], %2, [%3];\n}" :: "r"(dst), "l"(src), "r"(bytes), "r"(bar) : "memory");
}
__device__ __forceinline__ void e_s2g(void* dst, uint32_t src, uint32_t bytes) {
    asm volatile(ELECT "cp.async.bulk.global.shared::cta.bulk_group [%0], [%1], %2;\n}" :: "l"(dst), "r"(src), "r"(bytes) : "memory");
}
__device__ __forceinline__ void e_ld3(uint32_t dst, const CUtensorMap* m, int c0, int c1, int c2, uint32_t bar) {
    asm volatile(ELECT "cp.async.bulk.tensor.3d.shared::cluster.global.mbarrier::complete_tx::bytes [%0], [%1, {%3, %4, %5}], [%2];\n}"
                 :: "r"(dst), "l"(m), "r"(bar), "r"(c0), "r"(c1), "r"(c2) : "memory");
}
__device__ __forceinline__ void e_ld4(uint32_t dst, const CUtensorMap* m, int c0, int c3, uint32_t bar) {
    asm volatile(ELECT "cp.async.bulk.tensor.4d.shared::cluster.global.mbarrier::complete_tx::bytes [%0], [%1, {%3, %5, %5, %4}], [%2];\n}"
                 :: "r"(dst), "l"(m), "r"(bar), "r"(c0), "r"(c3), "r"(0) : "memory");
}
__device__ __forceinline__ void e_st3(const CUtensorMap* m, uint32_t src, int c0, int c1, int c2) {
    asm volatile(ELECT "cp.async.bulk.tensor.3d.global.shared::cta.bulk_group [%0, {%2, %3, %4}], [%1];\n}" :: "l"(m), "r"(src), "r"(c0), "r"(c1), "r"(c2) : "memory");
}
__device__ __forceinline__ void e_ld5(uint32_t dst, const CUtensorMap* m, int c4, uint32_t bar) {
    asm volatile(ELECT "cp.async.bulk.tensor.5d.shared::cluster.global.mbarrier::complete_tx::bytes [%0], [%1, {%4, %4, %4, %4, %3}], [%2];\n}"
                 :: "r"(dst), "l"(m), "r"(bar), "r"(c4), "r"(0) : "memory");
}
__device__ __forceinline__ void e_st5(const CUtensorMap* m, uint32_t src, int c4) {
    asm volatile(ELECT "cp.async.bulk.tensor.5d.global.shared::cta.bulk_group [%0, {%3, %3, %3, %3, %2}], [%1];\n}" :: "l"(m), "r"(src), "r"(c4), "r"(0) : "memory");
}
__device__ __forceinline__ void bulk_commit() { asm volatile("cp.async.bulk.commit_group;" ::: "memory"); }
template <int N> __device__ __forceinline__ void bulk_wait() { asm volatile("cp.async.bulk.wait_group %0;" :: "n"(N) : "memory"); }
template <int N> __device__ __forceinline__ void bulk_wait_read() { asm volatile("cp.async.bulk.wait_group.read %0;" :: "n"(N) : "memory"); }
__device__ __forceinline__ void wg_bar(int id) { asm volatile("bar.sync %0, 128;" :: "r"(id) : "memory"); }
__device__ __forceinline__ void bb_break(uint32_t v) { asm volatile("{\n.reg .pred p;\nsetp.eq.u32 p, %0, 0x7fc17fc1;\n@p nanosleep.u32 0;\n}" :: "r"(v) : "memory"); }
__device__ __forceinline__ uint32_t uni(uint32_t v) { return __shfl_sync(0xffffffffu, v, 0); }
__device__ __forceinline__ char* cls_cnt(char* scr, int cls) { return scr + slot_line(3, 2, cls) * 128; }
__device__ __forceinline__ uint32_t cnt_wait(const void* p, unsigned target) {
    uint32_t v = 0;
#pragma unroll 1
    for (unsigned it = 0; it < (1u << 22) && v < target; it++) {
        asm volatile("ld.acquire.gpu.global.u32 %0, [%1];" : "=r"(v) : "l"(p) : "memory");
        v = uni(v);
    }
    asm volatile("fence.proxy.async.global;" ::: "memory");
    return v;
}
__device__ __forceinline__ void wg_fence() { asm volatile("wgmma.fence.sync.aligned;" ::: "memory"); }
__device__ __forceinline__ void wg_commit() { asm volatile("wgmma.commit_group.sync.aligned;" ::: "memory"); }
template <int N> __device__ __forceinline__ void wg_wait() { asm volatile("wgmma.wait_group.sync.aligned %0;" :: "n"(N) : "memory"); }
template <int N> __device__ __forceinline__ void reg_fence(float (&d)[N]) {
#pragma unroll
    for (int i = 0; i < N; i++) asm volatile("" : "+f"(d[i]) :: "memory");
}
template <int N> __device__ __forceinline__ void zero(float (&d)[N]) {
#pragma unroll
    for (int i = 0; i < N; i++) d[i] = 0.f;
}
__device__ __forceinline__ uint32_t pack2(float lo, float hi) {
    uint32_t r; asm volatile("cvt.rn.bf16x2.f32 %0, %1, %2;" : "=r"(r) : "f"(hi), "f"(lo)); return r;
}
__device__ __forceinline__ void stm4(uint32_t a, uint32_t r0, uint32_t r1, uint32_t r2, uint32_t r3) {
    asm volatile("stmatrix.sync.aligned.m8n8.x4.trans.shared.b16 [%0], {%1,%2,%3,%4};" :: "r"(a), "r"(r0), "r"(r1), "r"(r2), "r"(r3) : "memory");
}
__device__ __forceinline__ void stm2(uint32_t a, uint32_t r0, uint32_t r1) {
    asm volatile("stmatrix.sync.aligned.m8n8.x2.trans.shared.b16 [%0], {%1,%2};" :: "r"(a), "r"(r0), "r"(r1) : "memory");
}
struct Desc {
    uint32_t lo, hi;
    __device__ __forceinline__ operator uint64_t() const { return ((uint64_t)hi << 32) | lo; }
    __device__ __forceinline__ Desc operator+(uint32_t o) const { return Desc{lo + o, hi}; }
    __device__ __forceinline__ Desc operator^(uint32_t o) const { return Desc{lo ^ o, hi}; }
};
__device__ __forceinline__ Desc mkdesc(uint32_t addr, uint32_t lbo, uint32_t sbo, uint32_t swz) {
    return Desc{((addr & 0x3FFFF) >> 4) | ((lbo >> 4) << 16), (sbo >> 4) | (swz << 30)};
}
__device__ __forceinline__ uint32_t cos_bits(int k) {
    if (k > 20) k = 40 - k;
    const bool neg = k > 10;
    if (neg) k = 20 - k;
    const unsigned long long pk = k < 4 ? COS_PK0 : k < 8 ? COS_PK1 : COS_PK2;
    return (uint32_t)((pk >> (16 * (k & 3))) & 0xffff) ^ (neg ? 0x8000u : 0u);
}

__device__ __forceinline__ void task_w(int wg, int k, uint32_t sb) {
    const int tid = threadIdx.x & 127, w = uni(tid >> 5), lane = tid & 31, q = lane & 3;
    const int tb = 14 * k, t1 = min(tb + 14, 1800), cb0 = tb / 25;
    float acc[64];
    zero(acc);
    const int oc0 = tb - 25 * cb0, Lt = t1 - tb, L0 = min(Lt, 25 - oc0), n0 = (L0 + 3) >> 2;
    uint32_t a[2][4][4];
    auto gen = [&](uint32_t (&a)[4][4], int at) {
        const int phi = 8 * ((at < n0 ? oc0 + 4 * at : 4 * (at - n0)) + w) + (lane >> 2), f = (phi * 205) >> 12;
        const uint32_t ca = 8 * f + 4, cw = (phi - 20 * f) * 8, p0 = sb + TBL + cw * 2 * q;
#pragma unroll
        for (int kh = 0; kh < 7; kh++) {
            uint32_t v0, v1;
            asm volatile("ld.shared.u32 %0, [%1];" : "=r"(v0) : "r"(p0 + ca * kh));
            asm volatile("ld.shared.u32 %0, [%1];" : "=r"(v1) : "r"(p0 + cw + ca * kh));
            const int h = kh == 6 ? 1 : kh & 1;
            a[kh >> 1][2 * h] = __byte_perm(v0, v1, 0x5410);
            a[kh >> 1][2 * h + 1] = __byte_perm(v0, v1, 0x7632);
        }
        a[3][0] = 0; a[3][1] = 0;
    };
    gen(a[0], wg);
    if (wg) gen(a[1], wg + 2);
#pragma unroll 1
    for (int n = 0; n < 2; n++) {
        const int at = wg + 2 * n, i0 = at < n0 ? 4 * at : L0 + 4 * (at - n0), cnt = (at < n0 ? L0 : Lt) - i0, cb = cb0 + (at >= n0);
        if (cnt <= 0 || (n && !wg)) break;
        if (n) {
#pragma unroll
            for (int j = 0; j < 16; j++) a[0][j >> 2][j & 3] = a[1][j >> 2][j & 3];
        }
        const Desc dB = mkdesc(sb + WP + (cb - cb0) * 14336, 3584, 512, 2);
        if (at) mbar_wait(sb + BARS + 8 * (B_WCH + at - 1));
        mbar_wait(sb + BARS + 8 * (B_WF + 2 * (cb - cb0)));
        wg_fence();
        wgmma_rs_n128_z(acc, a[0][0][0], a[0][0][1], a[0][0][2], a[0][0][3], dB);
        wgmma_rs_n128_a(acc, a[0][1][0], a[0][1][1], a[0][1][2], a[0][1][3], dB + (uint32_t)(16 * 64 >> 4));
        wgmma_rs_n128_a(acc, a[0][2][0], a[0][2][1], a[0][2][2], a[0][2][3], dB + (uint32_t)(32 * 64 >> 4));
        wgmma_rs_n128_a(acc, a[0][3][0], a[0][3][1], a[0][3][2], a[0][3][3], dB + (uint32_t)(40 * 64 >> 4));
        wg_commit();
        wg_wait<0>();
        reg_fence(acc);
        e_arrive(sb + BARS + 8 * (B_WCH + at));
        if (w < cnt) {
            const uint32_t dst = sb + wst_off(i0 + w) + (lane >> 2) * 512 + (lane & 4) * 16 + ((q ^ cb) & 3) * 16;
#pragma unroll
            for (int j = 0; j < 4; j++)
#pragma unroll
                for (int e = 0; e < 2; e++)
                    asm volatile("st.shared.v4.u32 [%0], {%1,%2,%3,%4};" :: "r"((dst ^ (e * 64)) + j * 128),
                                 "r"(pack2(acc[4 * j + e], acc[16 + 4 * j + e])), "r"(pack2(acc[4 * j + 2 + e], acc[16 + 4 * j + 2 + e])),
                                 "r"(pack2(acc[32 + 4 * j + e], acc[48 + 4 * j + e])), "r"(pack2(acc[32 + 4 * j + 2 + e], acc[48 + 4 * j + 2 + e])) : "memory");
            fence_async_smem();
            e_arrive(sb + BARS + 8 * (B_WRD + i0 + w));
        }
    }
}

__device__ __forceinline__ void task_p1(int wg, int pair, uint32_t sb) {
    const int tid = threadIdx.x & 127, w = tid >> 5, lane = tid & 31;
    const uint32_t buf = sb + wg * 51200, bars = sb + BARS;
    uint32_t fr[5][10][2];
    float A[40], d[20];
    zero(A);
    {
        const Desc dA = mkdesc(buf, 3584, 512, 2), dB = mkdesc(sb + C1, 128, 256, 0);
        auto issue = [&](int g, float (&d)[40]) {
            mbar_wait(bars + 8 * (B_XF + wg * 5 + g));
            wg_fence();
            wgmma_ss_n80_z(d, dA + (uint32_t)(g * 8704 >> 4), dB);
#pragma unroll
            for (int j = 1; j < 5; j++) wgmma_ss_n80_a(d, dA + (uint32_t)((g * 8704 + j * 1024) >> 4), dB + (uint32_t)(j * 2560 >> 4));
            wg_commit();
        };
        auto pack = [&](int g, float (&d)[40]) {
            reg_fence(d);
#pragma unroll
            for (int f = 0; f < 10; f++) {
                fr[g][f][0] = pack2(d[4 * f], d[4 * f + 1]);
                fr[g][f][1] = pack2(d[4 * f + 2], d[4 * f + 3]);
            }
        };
        mbar_wait(bars + 8 * B_CF1);
#pragma unroll
        for (int g = 0; g < 4; g++) { issue(g, A); wg_wait<0>(); pack(g, A); }
        zero(d);
        mbar_wait(bars + 8 * (B_XF + wg * 5 + 4));
#pragma unroll
        for (int h = 0; h < 2; h++) {
            wg_fence();
            wgmma_ss_n40_z(d, dA + (uint32_t)(4 * 8704 >> 4), dB + (uint32_t)(h * 1280 >> 4));
#pragma unroll
            for (int j = 1; j < 5; j++) wgmma_ss_n40_a(d, dA + (uint32_t)((4 * 8704 + j * 1024) >> 4), dB + (uint32_t)((j * 2560 + h * 1280) >> 4));
            wg_commit(); wg_wait<0>(); reg_fence(d);
#pragma unroll
            for (int f = 0; f < 5; f++) { fr[4][5 * h + f][0] = pack2(d[4 * f], d[4 * f + 1]); fr[4][5 * h + f][1] = pack2(d[4 * f + 2], d[4 * f + 3]); }
        }
    }
    bb_break(sb);
    wg_bar(1 + wg);
    {
        const Desc dB = mkdesc(sb + C1 + 12800, 128, 256, 0);
        const int i = lane & 7, mi = lane >> 3, th = w >> 1, tz = (2 * pair + th) & 3;
        const uint32_t s0 = buf + (i >> 1) * 128 + (i & 1) * 64 + (((2 * (w & 1) + (mi & 1)) ^ tz ^ (i >> 1)) << 4);
        const uint32_t sA = s0 + th * 2048 + (mi >> 1) * 512, sB = s0 + th * 2048 + (mi >> 1) * 2560, sC = s0 + th * 1024 + (mi >> 1) * 512;
        auto issue = [&](int f, float (&d)[20]) {
            wg_fence();
            wgmma_rs_n40_z(d, fr[0][f][0], fr[0][f][1], fr[1][f][0], fr[1][f][1], dB);
            wgmma_rs_n40_a(d, fr[2][f][0], fr[2][f][1], fr[3][f][0], fr[3][f][1], dB + (uint32_t)(1280 >> 4));
            wgmma_rs_n40_a(d, fr[4][f % 5][0], fr[4][f % 5][1], fr[4][f % 5 + 5][0], fr[4][f % 5 + 5][1], dB + (uint32_t)((2560 + (f / 5) * 1280) >> 4));
            wg_commit();
        };
#pragma unroll
        for (int f = 0; f < 10; f++) {
            issue(f, d);
            if (f && !(f & 1)) { fence_async_smem(); e_arrive(bars + 8 * (B_RDY + wg * 5 + (f >> 1) - 1)); }
            wg_wait<0>(); reg_fence(d);
            const int Q = 5 * f;
            stm4(((Q & 3) == 3 ? sB : sA) + quad_off(Q), pack2(d[0], d[1]), pack2(d[2], d[3]), pack2(d[4], d[5]), pack2(d[6], d[7]));
            stm2(sA + quad_off(Q + 2), pack2(d[8], d[9]), pack2(d[10], d[11]));
            stm4((f == 9 ? sC : ((Q + 3) & 3) == 3 ? sB : sA) + quad_off(Q + 3), pack2(d[12], d[13]), pack2(d[14], d[15]), pack2(d[16], d[17]), pack2(d[18], d[19]));
            if (f == 9) { fence_async_smem(); e_arrive(bars + 8 * (B_RDY + wg * 5 + (f >> 1))); }
        }
    }
}

__device__ __forceinline__ void task_p2(int wg, int rk, uint32_t sb) {
    const int tid = threadIdx.x & 127, w = tid >> 5, lane = tid & 31;
    const uint32_t bars = sb + BARS;
    const int phi0 = 3 * rk, phiE = extra_phi(rk), mE = extra_mask(rk);
    uint4 wA[6], wB[6], wC[6], wE[6];
    auto ldw = [&](uint4 (&a)[6], int j, int phi) {
        const int pc = 3 * j + wg;
        const uint32_t p = sb + wslot(pc) + (lane & 3) * 512 + w * 128 + (((lane >> 2) ^ phi) & 1) * 64 + (((lane >> 3) ^ lane) & 3) * 16 + (phi & 1) * 8;
        mbar_wait(bars + 8 * (B_WL + pc));
#pragma unroll
        for (int s = 0; s < 6; s++) {
            asm volatile("ld.shared.v2.u32 {%0, %1}, [%2];" : "=r"(a[s].x), "=r"(a[s].y) : "r"(p + s * 2048) : "memory");
            asm volatile("ld.shared.v2.u32 {%0, %1}, [%2];" : "=r"(a[s].z), "=r"(a[s].w) : "r"((p ^ 8) + s * 2048) : "memory");
        }
        uint32_t dep = 0;
#pragma unroll
        for (int s = 0; s < 6; s++) dep |= a[s].x ^ a[s].z;
        if (__any_sync(0xffffffffu, dep == 0x7fc17fc1u)) __nanosleep(0);
        e_arrive(bars + 8 * (B_WE + pc));
    };
    ldw(wA, 0, phi0); ldw(wB, 1, phi0 + 1);
    bool haveC = false;
#pragma unroll 1
    for (uint32_t it = 0; it < (1u << 22); it++) {
        haveC = mbar_test(bars + 8 * (B_WL + 6 + wg));
        if (haveC || mbar_test(bars + 8 * B_RF)) break;
        __nanosleep(50);
    }
    if (haveC) ldw(wC, 2, phi0 + 2);
    mbar_wait(bars + 8 * (B_SIG + SIG_P1 + 1));
    const int i = lane & 7, mi = lane >> 3;
    const uint32_t soff = sb + S1 + wg * 4096 + mi * 512 + (i >> 1) * 128 + (i & 1) * 64;
    const int xo = w ^ (i >> 1);
    float d[32];
    zero(d);
    int n = 0;
    uint32_t xb = ((sb + xslot(0)) & 0x3FFFF) >> 4 | 1u << 16, mb = bars + 8 * wg;
    bool landed = false;
    auto unit = [&](const uint4 (&a)[6], int z) {
        const Desc d0{xb + (z & 2), (512u >> 4) | (2u << 30)}, d1 = d0 ^ 2u;
        if (!landed) mbar_wait(bars + 8 * (B_RF + n));
        mbar_wait(mb + 8 * (B_TOK - 1));
        wg_fence();
        wgmma_rs_n64_z(d, a[0].x, a[0].y, a[0].z, a[0].w, d0);
        wgmma_rs_n64_a(d, a[1].x, a[1].y, a[1].z, a[1].w, d1);
        e_arrive(bars + 8 * (n ? B_RE + n - 1 : B_RE + 13));
        const bool sfree = mbar_test(n >= 4 ? mb + 8 * (B_SFREE - 12) : bars + 8 * (B_TOK - 1));
        landed = mbar_test(bars + 8 * (B_RF + n + 1));
        wgmma_rs_n64_a(d, a[2].x, a[2].y, a[2].z, a[2].w, d0 + (uint32_t)(4096 >> 4));
        wgmma_rs_n64_a(d, a[3].x, a[3].y, a[3].z, a[3].w, d1 + (uint32_t)(4096 >> 4));
        e_arrive(mb + 8 * B_TOK);
        wgmma_rs_n64_a(d, a[4].x, a[4].y, a[4].z, a[4].w, d0 + (uint32_t)(8192 >> 4));
        wgmma_rs_n64_a(d, a[5].x, a[5].y, a[5].z, a[5].w, d1 + (uint32_t)(8192 >> 4));
        wg_commit();
        if (!sfree) mbar_wait(mb + 8 * (B_SFREE - 12));
        const uint32_t a0 = soff + (n & 3) * 12288 + ((xo ^ z) << 4);
        n++;
        xb = ((sb + xslot(n)) & 0x3FFFF) >> 4 | 1u << 16;
        wg_wait<0>();
        reg_fence(d);
        uint32_t p[8];
#pragma unroll
        for (int j = 0; j < 8; j++) p[j] = pack2(d[4 * j] - d[4 * j + 3], d[4 * j + 2] + d[4 * j + 1]);
        stm4(a0, p[0], p[1], p[2], p[3]);
        stm4(a0 + 2048, p[4], p[5], p[6], p[7]);
        fence_async_smem();
        e_arrive(mb + 8 * (B_RDY + R_P2));
        mb += 24;
    };
    const int zA = phi0 & 3, zB = (phi0 + 1) & 3, zC = (phi0 + 2) & 3, zE = phiE & 3;
#pragma unroll 1
    for (int it = 0; it < 4; it++) {
        unit(wA, zA);
        unit(wB, zB);
        if (it == 0 && !haveC) ldw(wC, 2, phi0 + 2);
        unit(wC, zC);
        if (it == 0 && mE) ldw(wE, 3, phiE);
        if (mE >> it & 1) unit(wE, zE);
    }
}

__device__ __forceinline__ void task_p3(int wg, int pair, uint32_t sb) {
    const int tid = threadIdx.x & 127, w = tid >> 5, lane = tid & 31;
    const uint32_t buf = sb + (wg ? 3 - wg : 0) * 51200, bars = sb + BARS;
    uint32_t fr[10][4][2];
    float acc[2][16];
    zero(acc[0]); zero(acc[1]);
    {
        const Desc dB = mkdesc(sb + C3, 128, 256, 0);
        const uint32_t a0 = (buf & 0x3FFFF) >> 4;
        auto dq = [&](int Q) {
            return Desc{a0 + (uint32_t)((quad_off(Q) >> 4) | ((Q < 48 ? 2048 : 1024) >> 4) << 16), (uint32_t)((quad_off(Q + 1) - quad_off(Q)) >> 4) | (2u << 30)};
        };
        auto issue = [&](int f) {
            if (!(f & 1)) mbar_wait(bars + 8 * (B_YF + wg * 5 + (f >> 1)));
            wg_fence();
            wgmma_ss_n32_z(acc[f & 1], dq(5 * f), dB);
            wgmma_ss_n32_a(acc[f & 1], dq(5 * f + 1), dB + (uint32_t)(1024 >> 4));
            wgmma_ss_n32_a(acc[f & 1], dq(5 * f + 3), dB + (uint32_t)(2048 >> 4));
            wg_commit();
        };
        mbar_wait(bars + 8 * B_CF3);
        issue(0);
#pragma unroll
        for (int f = 0; f < 10; f++) {
            if (f < 9) { issue(f + 1); wg_wait<1>(); } else wg_wait<0>();
            float (&d)[16] = acc[f & 1];
            reg_fence(d);
#pragma unroll
            for (int g = 0; g < 4; g++) { fr[f][g][0] = pack2(d[4 * g], d[4 * g + 1]); fr[f][g][1] = pack2(d[4 * g + 2], d[4 * g + 3]); }
        }
    }
    {
        const Desc dB = mkdesc(sb + C3 + 3072, 128, 256, 0);
        const int i = lane & 7, mi = lane >> 3, th = w >> 1, tz = (2 * pair + th) & 3;
        const int oct = (2 * (w & 1) + (mi & 1)) ^ tz;
        const uint32_t soff = buf + th * 3584 + (mi >> 1) * 512 + i * 64 + ((oct ^ (i >> 1)) << 4);
        auto mma = [&](int t, int s) {
            if (t > 6) return;
            const int g = t < 6 ? 1 + (t >> 1) : 0;
            const uint32_t o = t < 6 ? (t & 1) * 1024 : 8960, st = t < 6 ? 1792 : 1024;
            if (s == 0) { wg_fence(); wgmma_rs_n32_z(acc[t & 1], fr[0][g][0], fr[0][g][1], fr[1][g][0], fr[1][g][1], dB + (o >> 4)); }
            else wgmma_rs_n32_a(acc[t & 1], fr[2 * s][g][0], fr[2 * s][g][1], fr[2 * s + 1][g][0], fr[2 * s + 1][g][1], dB + ((o + s * st) >> 4));
            if (s == 4) wg_commit();
        };
        const int row = th * 14 + 4 * (mi >> 1) + (i >> 1);
        const uint32_t z0 = buf + row * 128 + (i & 1) * 64 + ((oct ^ (row & 3)) << 4), z1 = (lane & 20) == 20 ? buf + 4096 + lane * 16 : z0 + 1024;
        bb_break(sb);
#pragma unroll
        for (int s = 0; s < 5; s++) mma(0, s);
        wg_bar(1 + wg);
#pragma unroll
        for (int t = 0; t < 7; t++) {
#pragma unroll
            for (int s = 0; s < 2; s++) mma(t + 1, s);
            if (t < 6) { wg_commit(); wg_wait<1>(); } else wg_wait<0>();
            float (&d)[16] = acc[t & 1];
            reg_fence(d);
            const uint32_t a = soff + (1 + (t >> 1)) * 7168 + (t & 1) * 2048;
            stm4(t < 6 ? a : z0, pack2(d[0], d[1]), pack2(d[2], d[3]), pack2(d[4], d[5]), pack2(d[6], d[7]));
            mma(t + 1, 2);
            if (t & 1) stm2(a + 1024, pack2(d[8], d[9]), pack2(d[10], d[11]));
            else stm4(t < 6 ? a + 1024 : z1, pack2(d[8], d[9]), pack2(d[10], d[11]), pack2(d[12], d[13]), pack2(d[14], d[15]));
#pragma unroll
            for (int s = 3; s < 5; s++) mma(t + 1, s);
            if ((t & 1) || t == 6) { fence_async_smem(); e_arrive(bars + 8 * (B_RDY + R_P3 + wg * 4 + (t >> 1))); }
        }
    }
}

__device__ __forceinline__ void load_x(int cls, int rk, int u, uint32_t sb, const Maps& mp) {
    const int id = u * NH + rk, pl = id / 3, c0 = 32 * (id - 3 * pl), tp = cls * 4 + (pl >> 4), col = 14 * (pl & 15) - 8;
    const uint32_t bar = sb + BARS + 8 * (B_XF + u * 5), dst = sb + u * 51200;
    const int wrap = col < 0 ? 224 : 0;
    if (tp) {
#pragma unroll
        for (int g = 0; g < 5; g++) e_ld3(dst + g * 8704, &mp.x34, c0, col + 4 * g + (g < 2 ? wrap : 0), 28 * tp - 6, bar + 8 * g);
    } else {
#pragma unroll
        for (int g = 0; g < 5; g++) {
            e_ld3(dst + g * 8704, &mp.x6, c0, col + 4 * g + (g < 2 ? wrap : 0), 218, bar + 8 * g);
            e_ld3(dst + g * 8704 + 1536, &mp.x28, c0, col + 4 * g + (g < 2 ? wrap : 0), 0, bar + 8 * g);
        }
    }
}

__device__ __forceinline__ void load_x_box(int cls, int rk, int u, int g, uint32_t sb, const Maps& mp) {
    const int id = u * NH + rk, pl = id / 3, c0 = 32 * (id - 3 * pl), tp = cls * 4 + (pl >> 4), col = 14 * (pl & 15) - 8 + 4 * g;
    e_ld3(sb + u * 51200 + g * 8704, &mp.x34, c0, col < 0 ? col + 224 : col, 28 * tp - 6, sb + BARS + 8 * (B_XF + u * 5 + g));
}

__device__ __forceinline__ void load_first(uint32_t sb, const Maps& mp, const Ptrs& pt) {
    const uint32_t bars = sb + BARS;
    const int k = blockIdx.x;
    if (k < 129) {
        const int cb0 = 14 * k / 25, cb1 = min((14 * k + 13) / 25, 71);
#pragma unroll 1
        for (int cb = cb0; cb <= cb1; cb++) {
            const int b = cb / 24, i0 = 16 * ((cb >> 2) - 6 * b) + 2 * (cb & 3);
            const uint32_t bar = bars + 8 * (B_WF + 2 * (cb - cb0));
            e_expect(bar, 14336);
            e_ld4(sb + WP + (cb - cb0) * 14336, &mp.w, 32 * b, i0, bar);
            e_ld4(sb + WP + (cb - cb0) * 14336 + 7168, &mp.w, 32 * b, i0 + 8, bar);
        }
    }
    asm volatile(ELECT "cp.async.bulk.prefetch.L2.global [%0], %1;\n}" :: "l"(pt.x + (k & 1) * (112 * 43008) + (k >> 1) * PFS), "n"(PFS) : "memory");
    e_expect(bars + 8 * B_CF1, 17920); e_g2s(sb + C1, pt.tab1, 17920, bars + 8 * B_CF1);
    if ((threadIdx.x & 31) < 15) asm volatile("mbarrier.arrive.expect_tx.shared::cta.b64 _, [%0], 8704;" :: "r"(bars + 8 * (B_XF + (threadIdx.x & 31))) : "memory");
    __syncwarp();
}

__device__ __forceinline__ uint32_t get_rel(uint32_t sb) {
    mbar_wait(sb + BARS + 8 * B_REL);
    uint32_t v; asm volatile("ld.shared.u32 %0, [%1];" : "=r"(v) : "r"(sb + REL) : "memory");
    return uni(v);
}

__device__ __forceinline__ void load_warp(int cls, int rk, uint32_t sb, const Ptrs& pt) {
    const uint32_t bars = sb + BARS;
    mbar_wait(bars + 8 * (B_SIG + SIG_P1));
    const uint32_t rel = get_rel(sb);
    const char* cnt = cls_cnt(pt.scr, cls);
    const int mE = extra_mask(rk);
    const int lpA = phi_line(3 * rk, rel), lpB = phi_line(3 * rk + 1, rel), lpC = phi_line(3 * rk + 2, rel), lpE = phi_line(extra_phi(rk), rel);
    e_arrive(bars + 8 * (B_TOK - 1));
    if ((threadIdx.x & 31) < 14) asm volatile("mbarrier.arrive.expect_tx.shared::cta.b64 _, [%0], 12288;" :: "r"(bars + 8 * (B_RF + (threadIdx.x & 31))) : "memory");
    __syncwarp();
    int n = 0;
#pragma unroll 1
    for (int pg = 0; pg < 4; pg++) {
        const int l0 = slot_line(0, pg, cls), l1 = slot_line(1, pg, cls), l2 = slot_line(2, pg, cls);
        auto unit = [&](int lp) {
            const uint32_t bar = bars + 8 * (B_RF + n), dst = sb + xslot(n);
            mbar_wait(bars + 8 * (n >= 8 ? B_RE + n - 8 : n >= 4 ? B_SIG + SIG_P1 + (rk < 60 ? 2 : 1) : B_WE + ((0x4310 >> (4 * n)) & 15)));
            e_g2s(dst, pt.scr + (size_t)(lp ^ l0) * 128, 4096, bar);
            e_g2s(dst + 4096, pt.scr + (size_t)(lp ^ l1) * 128, 4096, bar);
            e_g2s(dst + 8192, pt.scr + (size_t)(lp ^ l2) * 128, 4096, bar);
            n++;
        };
        cnt_wait(cnt + (CNT_P1 + pg) * 128, 48);
        unit(lpA); unit(lpB); unit(lpC);
        if (mE >> pg & 1) unit(lpE);
        if (pg == 1) { mbar_wait(bars + 8 * B_P1D); e_expect(bars + 8 * B_CF3, 17152); e_g2s(sb + C3, pt.tab3, 17152, bars + 8 * B_CF3); }
    }
}

__device__ __forceinline__ int near_page(char* p) {
#pragma unroll
    for (int e = 0; e < 4; e++) asm volatile("st.relaxed.gpu.global.v4.u32 [%0], {%1, %1, %1, %1};" :: "l"(p + (e >> 1) * 4096 + (e & 1) * 16), "r"(0) : "memory");
    uint32_t v0, v1, t0, t1;
    asm volatile("atom.relaxed.gpu.global.exch.b32 %0, [%1], 1;" : "=r"(v0) : "l"(p) : "memory");
    asm volatile("atom.relaxed.gpu.global.exch.b32 %0, [%1], 1;" : "=r"(v1) : "l"(p + 4096) : "memory");
    asm volatile("{\n.reg .pred p;\nsetp.ne.u32 p, %1, 0xffffffff;\nmov.u32 %0, 0;\n@p mov.u32 %0, %%clock;\n}" : "=r"(t0) : "r"(v0) : "memory");
    asm volatile("{\n.reg .pred p;\nsetp.ne.u32 p, %1, 0xffffffff;\nmov.u32 %0, 0;\n@p mov.u32 %0, %%clock;\n}" : "=r"(t1) : "r"(v1) : "memory");
    return t1 - t0 < 80;
}

__device__ __forceinline__ uint32_t find_role(uint32_t sb, char* scr) {
    const int k = blockIdx.x;
    int c = near_page(scr + (slot_line(3, 3, 0) + phi_line(1 + (k >> 5), 0) + (k & 31)) * 128);
    int r;
    asm volatile("atom.relaxed.gpu.global.add.u32 %0, [%1], 1;" : "=r"(r) : "l"(cls_cnt(scr, c) + CNT_RANK * 128) : "memory");
    asm volatile("st.shared.u32 [%0], %1;" :: "r"(sb + REL + 8), "r"(c) : "memory");
    if (r >= NH) { c ^= 1; r = NSM - 1 - r; }
    asm volatile("st.shared.u32 [%0], %1;" :: "r"(sb + REL + 4), "r"(c << 8 | r) : "memory");
    return c << 8 | r;
}
__device__ __forceinline__ void get_role(uint32_t sb, int& cls, int& rk) {
    mbar_wait(sb + BARS + 8 * B_ROLE);
    uint32_t v; asm volatile("ld.shared.u32 %0, [%1];" : "=r"(v) : "r"(sb + REL + 4) : "memory");
    v = uni(v); cls = v >> 8; rk = v & 255;
}

__device__ __forceinline__ void load3_warp(int cls, int rk, uint32_t sb, const Maps& mp, const Ptrs& pt) {
    const uint32_t bars = sb + BARS;
    mbar_wait(bars + 8 * B_XF);
    const uint32_t rel = cnt_wait(pt.cnt + CNT_REL * 32, 12u << 16);
    asm volatile("st.shared.u32 [%0], %1;" :: "r"(sb + REL), "r"(rel) : "memory");
    __syncwarp();
    e_arrive(bars + 8 * B_REL);
    mbar_wait(bars + 8 * (B_SIG + SIG_W));
    cnt_wait(cls_cnt(pt.scr, cls) + CNT_W * 128, NSM);
    {
        const int np = rk >= 60 ? 12 : 9;
#pragma unroll 1
        for (int pc = 0; pc < np; pc++) {
            if (pc == 2) mbar_wait(bars + 8 * (B_SIG + SIG_P1));
            if (pc >= 8) mbar_wait(bars + 8 * (B_WE + ((0x5762 >> (4 * (pc - 8))) & 15)));
            if (pc >= 5) mbar_wait(bars + 8 * (B_WL + pc - 5));
            e_expect(bars + 8 * (B_WL + pc), 12288);
            e_g2s(sb + wslot(pc), pt.wf + (pc < 9 ? 9 * rk + pc : 3 * extra_phi(rk) + pc - 9) * 12288, 12288, bars + 8 * (B_WL + pc));
        }
        if (np == 12) { mbar_wait(bars + 8 * (B_WE + 9)); mbar_wait(bars + 8 * (B_WE + 10)); mbar_wait(bars + 8 * (B_WE + 11)); }
    }
    mbar_wait(bars + 8 * (B_SIG + SIG_P2 + 1));
    const int nu = rk < 60 ? 3 : 2;
#pragma unroll 1
    for (int u = 0; u < nu; u++) {
        const int id = u * NH + rk, pl = id / 3, chunk = id - 3 * pl;
        const int l0 = slot_line(chunk, pl >> 4, cls) + (pl & 15) * 2;
        const uint32_t buf = sb + (u ? 3 - u : 0) * 51200, bar = bars + 8 * (B_YF + u * 5);
#pragma unroll
        for (int j = 0; j < 5; j++) e_expect(bar + 8 * j, j == 4 ? 10240 : (j & 1) ? 8192 : 12288);
        if (u) mbar_wait(bars + 8 * (B_SIG + SIG_P2 + 3));
        cnt_wait(cls_cnt(pt.scr, cls) + (CNT_P2 + (pl >> 4)) * 128, NH);
        if (u == nu - 1) e_arrive(bars + 8 * B_FIN);
        const uint32_t r2 = uni(rel) << 5;
#pragma unroll
        for (int G = 0; G < 13; G++)
            e_ld5(buf + G * 4096, G < 12 ? &mp.f16 : &mp.f8, (l0 ^ ((r2 >> G) & 32)) + (G << 14), bar + 8 * ((2 * G) / 5));
    }
}

__device__ __forceinline__ void store_warp(uint32_t sb, const Maps& mp, const Ptrs& pt) {
    const uint32_t bars = sb + BARS;
    const int k = blockIdx.x;
    uint32_t pa = 0, pb = 0, qa = 0, qb = 0;
    auto arr2 = [&](uint32_t& a, uint32_t& b) { if (a) e_arrive(a); if (b) e_arrive(b); a = b = 0; };
    auto pre = [&](int idx) {
        const uint32_t bar = bars + 8 * idx;
        if ((pb | qb) && !mbar_test(bar)) { bulk_wait<0>(); arr2(qa, qb); arr2(pa, pb); }
        mbar_wait(bar);
    };
    auto post = [&](uint32_t fr) {
        bulk_commit(); bulk_wait_read<2>();
        if (qb) bulk_wait<2>();
        arr2(qa, qb); qa = pa; qb = pb; pb = 0; pa = fr;
    };
    auto after = [&](int sig) { pb = bars + 8 * (B_SIG + sig); };
    int cls, rk; get_role(sb, cls, rk);
    {
        int cb = 14 * k / 25, oc = 14 * k - 25 * cb;
        int g1 = 0;
#pragma unroll 1
        for (int i = 0; i < 14 && cb < 72; i++) {
            pre(B_WRD + i);
            e_st3(&mp.wst, sb + wst_off(i), 0, 8 * oc, cb);
            post(0);
            if (T1MASK >> i & 1) load_x_box(cls, rk, 1, g1++, sb, mp);
            if (++oc == 25) { oc = 0; cb++; }
        }
#pragma unroll 1
        for (; g1 < 5; g1++) load_x_box(cls, rk, 1, g1, sb, mp);
        after(SIG_W);
    }
    pre(B_REL);
    const uint32_t rel = get_rel(sb);
    const int nu = rk < 60 ? 3 : 2;
    int g2 = 0;
#pragma unroll 1
    for (int u = 0; u < nu; u++) {
        const int id = u * NH + rk, pl = id / 3, chunk = id - 3 * pl;
        const int l0 = slot_line(chunk, pl >> 4, cls) + (pl & 15) * 2;
        int j = B_RDY + u * 5;
        const int m2 = nu == 3 ? (u == 0 ? T2MASK & 0x1fff : u == 1 ? T2MASK >> 13 : 0) : 0;
#pragma unroll 1
        for (int G = 0; G < 13; G++) {
            if (0x4a5 >> G & 1) pre(j++);
            e_st5(G < 12 ? &mp.f16 : &mp.f8, sb + u * 51200 + G * 4096, (l0 ^ ((rel >> G) & 1) << 5) + (G << 14));
            post(0);
            if (m2 >> G & 1) load_x_box(cls, rk, 2, g2++, sb, mp);
        }
        after(SIG_P1 + u);
    }
    const int mE = extra_mask(rk);
    int n = 0;
#pragma unroll 1
    for (int pg = 0; pg < 4; pg++) {
        const int nj = 3 + (mE >> pg & 1);
        const int l0 = slot_line(0, pg, cls), l1 = slot_line(1, pg, cls), l2 = slot_line(2, pg, cls);
#pragma unroll 1
        for (int j = 0; j < nj; j++) {
            const int lp = phi_line(j == 3 ? extra_phi(rk) : 3 * rk + j, rel);
#pragma unroll
            for (int b = 0; b < 3; b++) {
                pre(B_RDY + R_P2 + n * 3 + b);
                e_s2g(pt.scr + (size_t)(lp ^ (b == 0 ? l0 : b == 1 ? l1 : l2)) * 128, sb + S1 + (n & 3) * 12288 + b * 4096, 4096);
                post(bars + 8 * (B_SFREE + n * 3 + b));
            }
            n++;
        }
        after(SIG_P2 + pg);
    }
#pragma unroll 1
    for (int u = 0; u < nu; u++) {
        const int id = u * NH + rk, pl = id / 3, chunk = id - 3 * pl, tp = cls * 4 + (pl >> 4), tx = pl & 15;
        const uint32_t buf = sb + (u ? 3 - u : 0) * 51200;
#pragma unroll
        for (int gg = 1; gg < 5; gg++) {
            pre(B_RDY + R_P3 + u * 4 + gg - 1);
            if (gg < 4) e_st3(&mp.y4, buf + gg * 7168, 32 * chunk, 14 * tx - 4 + 4 * gg, 28 * tp);
            else e_st3(&mp.y2, buf, 32 * chunk, tx == 0 ? 222 : 14 * tx - 2, 28 * tp);
            post(0);
        }
    }
    bulk_wait_read<0>();
}

__device__ __forceinline__ void signal_warp(int cls, int rk, uint32_t sb, const Ptrs& pt) {
    const uint32_t bars = sb + BARS;
    char* cnt = cls_cnt(pt.scr, cls);
    if (threadIdx.x & 31) return;
#pragma unroll 1
    for (int c = 0; c < 8; c++) {
        if (c == SIG_P1 + 2 && rk >= 60) continue;
        char* ctr = cnt + (c == SIG_W ? CNT_W : c < SIG_P2 ? CNT_P1 + ((c - SIG_P1) * NH + rk) / 48 : CNT_P2 + c - SIG_P2) * 128;
        mbar_wait(bars + 8 * (B_SIG + c));
        fence_async();
        asm volatile("red.relaxed.gpu.global.add.u32 [%0], 1;" :: "l"(ctr) : "memory");
        if (c == SIG_W) asm volatile("red.relaxed.gpu.global.add.u32 [%0], 1;" :: "l"((uintptr_t)ctr ^ 4096) : "memory");
    }
    mbar_wait(bars + 8 * B_FIN);
    unsigned old;
    asm volatile("atom.add.relaxed.gpu.global.u32 %0, [%1], 1;" : "=r"(old) : "l"(pt.cnt + CNT_DONE * 32) : "memory");
    if (old == NSM - 1) {
#pragma unroll
        for (int c = 0; c < NCNT; c++) pt.cnt[c * 32] = 0;
#pragma unroll 1
        for (int c = 0; c < NCLS; c++) { *reinterpret_cast<unsigned*>(cnt + c * 128) = 0; *reinterpret_cast<unsigned*>(((uintptr_t)cnt ^ 4096) + c * 128) = 0; }
    }
}

__global__ void __launch_bounds__(512, 1) fftconv_kernel(const Ptrs pt, const __grid_constant__ Maps mp) {
    extern __shared__ __align__(1024) uint8_t smem[];
    const uint32_t sb = smem_u32(smem);
    const int tid = threadIdx.x, warp = uni(tid >> 5), wg = warp >> 2;
    int cls, rk;
    auto bar_init = [&](int i) {
        uint32_t c = 1;
        if (i == B_P1D || (i >= B_RE && i < B_RE + 14)) c = 12;
        else if ((i >= B_WCH && i < B_WL) || i >= B_TOK) c = 4;
        asm volatile("st.shared.v2.u32 [%0], {%1, %2};" :: "r"(sb + BARS + 8 * i), "r"((0x100000u - c) << 1), "r"((0x100000u - c) << 11) : "memory");
        fence_async_smem();
    };
    if (wg == 3) {
        asm volatile("setmaxnreg.dec.sync.aligned.u32 32;");
        if (warp == 12) {
            bar_init(tid & 31);
            __syncwarp();
            asm volatile("bar.arrive 4, 416;" ::: "memory");
            load_first(sb, mp, pt);
            asm volatile("bar.sync 5, 416;" ::: "memory");
            get_role(sb, cls, rk);
            load_warp(cls, rk, sb, pt);
        } else if (warp == 13) {
            if ((tid & 31) < 8) asm volatile("prefetch.tensormap [%0];" :: "l"(reinterpret_cast<const CUtensorMap*>(&mp) + 1 + (tid & 31)) : "memory");
            __syncwarp();
            asm volatile("bar.sync 6, 416;" ::: "memory");
            store_warp(sb, mp, pt);
        } else if (warp == 14) {
            const int G = blockIdx.x - 119;
            int sel = 0;
            if (G >= 1 && (tid & 31) == 0) sel = near_page(pt.scr + ((size_t)G << 21) + slot_line(3, 3, 0) * 128);
            __syncwarp();
            asm volatile("bar.sync 7, 416;" ::: "memory");
            get_role(sb, cls, rk);
            if (G >= 1 && (tid & 31) == 0) {
                uint32_t c; asm volatile("ld.shared.u32 %0, [%1];" : "=r"(c) : "r"(sb + REL + 8) : "memory");
                asm volatile("red.relaxed.gpu.global.add.u32 [%0], %1;" :: "l"(pt.cnt + CNT_REL * 32), "r"(0x10000u | (sel ^ c) << G) : "memory");
            }
            __syncwarp();
            load3_warp(cls, rk, sb, mp, pt);
        } else {
            uint32_t role = 0;
            if ((tid & 31) == 0) role = find_role(sb, pt.scr);
            role = uni(role); cls = role >> 8; rk = role & 255;
            asm volatile("bar.sync 8, 416;" ::: "memory");
            load_x(cls, rk, 0, sb, mp);
            e_arrive(sb + BARS + 8 * B_ROLE);
            signal_warp(cls, rk, sb, pt);
        }
    } else {
        if (tid >= 32 && tid < NBAR) bar_init(tid);
        {
            const int r = tid % 40;
            asm volatile("st.shared.u32 [%0], %1;" :: "r"(sb + TBL + 4 * tid), "r"(cos_bits(r) | (cos_bits(r < 30 ? r + 10 : r - 30) << 16)) : "memory");
        }
        __syncwarp();
        asm volatile("bar.sync 4, 416;" ::: "memory");
        asm volatile("bar.arrive 5, 416;" ::: "memory");
        asm volatile("bar.arrive 6, 416;" ::: "memory");
        asm volatile("bar.arrive 7, 416;" ::: "memory");
        asm volatile("bar.arrive 8, 416;" ::: "memory");
        task_w(wg, blockIdx.x, sb);
        asm volatile("setmaxnreg.inc.sync.aligned.u32 160;");
        get_role(sb, cls, rk);
        const int id = wg * NH + rk;
        if (id < 192) task_p1(wg, id / 3, sb);
        e_arrive(sb + BARS + 8 * B_P1D);
        task_p2(wg, rk, sb);
        if (id < 192) task_p3(wg, id / 3, sb);
    }
}

__global__ void fallback_kernel(const __nv_bfloat16* x, const __nv_bfloat16* w, __nv_bfloat16* y) {
    const int px = blockIdx.x, o = threadIdx.x, h = px / 224, c = px % 224;
    float acc = 0.f;
    for (int kh = 0; kh < 7; kh++)
        for (int kw = 0; kw < 7; kw++) {
            const __nv_bfloat16* xp = x + (((h - kh + 224) % 224) * 224 + (c - kw + 224) % 224) * 96;
            const __nv_bfloat16* wp = w + (kh * 7 + kw) * 9216 + o;
            for (int i = 0; i < 96; i++) acc += __bfloat162float(xp[i]) * __bfloat162float(wp[i * 96]);
        }
    y[px * 96 + o] = __float2bfloat16(acc);
}

typedef CUresult (*EncodeFn)(CUtensorMap*, CUtensorMapDataType, cuuint32_t, void*, const cuuint64_t*, const cuuint64_t*, const cuuint32_t*, const cuuint32_t*,
                             CUtensorMapInterleave, CUtensorMapSwizzle, CUtensorMapL2promotion, CUtensorMapFloatOOBfill);

static void encode3(EncodeFn fn, CUtensorMap* m, void* ptr, uint64_t d0, uint64_t d1, uint64_t d2, uint64_t s1, uint64_t s2,
                    uint32_t b0, uint32_t b1, uint32_t b2, CUtensorMapSwizzle sw, CUtensorMapL2promotion promo = CU_TENSOR_MAP_L2_PROMOTION_NONE) {
    cuuint64_t dims[3] = {d0, d1, d2}, strides[2] = {s1, s2};
    cuuint32_t box[3] = {b0, b1, b2}, es[3] = {1, 1, 1};
    fn(m, CU_TENSOR_MAP_DATA_TYPE_BFLOAT16, 3, ptr, dims, strides, box, es, CU_TENSOR_MAP_INTERLEAVE_NONE, sw,
       promo, CU_TENSOR_MAP_FLOAT_OOB_FILL_NONE);
}

extern "C" void kernel_launch(void* const* d_in, const int* in_sizes, int n_in, void* d_out, int out_size) {
    (void)in_sizes; (void)n_in; (void)out_size;
    int dev = 0, nsm = 0;
    cudaGetDevice(&dev);
    cudaDeviceGetAttribute(&nsm, cudaDevAttrMultiProcessorCount, dev);
    if (nsm < NSM) {
        fallback_kernel<<<224 * 224, 96>>>((const __nv_bfloat16*)d_in[0], (const __nv_bfloat16*)d_in[1], (__nv_bfloat16*)d_out);
        return;
    }
    void* fnp = nullptr; cudaDriverEntryPointQueryResult qr;
    cudaGetDriverEntryPoint("cuTensorMapEncodeTiled", &fnp, cudaEnableDefault, &qr);
    EncodeFn fn = (EncodeFn)fnp;
    void* xf = nullptr; cudaGetSymbolAddress(&xf, g_scr);
    xf = (void*)(((uintptr_t)xf + (1u << 21) - 1) & ~(uintptr_t)((1u << 21) - 1));
    void* wf = nullptr; cudaGetSymbolAddress(&wf, g_wf);
    Maps mp;
    Ptrs pt;
    pt.scr = (char*)xf; pt.wf = (const char*)wf; pt.x = (const char*)d_in[0];
    void* p = nullptr;
    cudaGetSymbolAddress(&p, TAB_P1); pt.tab1 = p;
    cudaGetSymbolAddress(&p, TAB_P3); pt.tab3 = p;
    cudaGetSymbolAddress(&p, g_cnt); pt.cnt = (unsigned*)p;
    {
        cuuint32_t b16[5] = {64, 4, 2, 2, 2}, b8[5] = {64, 4, 2, 1, 2}, es[5] = {1, 1, 1, 1, 1};
        cuuint64_t d[5] = {64, 4, 2, 2, 13 << 14}, st[4] = {16384, 262144, 1048576, 128};
        fn(&mp.f16, CU_TENSOR_MAP_DATA_TYPE_BFLOAT16, 5, xf, d, st, b16, es, CU_TENSOR_MAP_INTERLEAVE_NONE, CU_TENSOR_MAP_SWIZZLE_NONE, CU_TENSOR_MAP_L2_PROMOTION_NONE, CU_TENSOR_MAP_FLOAT_OOB_FILL_NONE);
        fn(&mp.f8, CU_TENSOR_MAP_DATA_TYPE_BFLOAT16, 5, xf, d, st, b8, es, CU_TENSOR_MAP_INTERLEAVE_NONE, CU_TENSOR_MAP_SWIZZLE_NONE, CU_TENSOR_MAP_L2_PROMOTION_NONE, CU_TENSOR_MAP_FLOAT_OOB_FILL_NONE);
    }
    encode3(fn, &mp.x6, d_in[0], 96, 224, 224, 192, 224 * 192, 32, 4, 6, CU_TENSOR_MAP_SWIZZLE_64B, CU_TENSOR_MAP_L2_PROMOTION_L2_128B);
    encode3(fn, &mp.x34, d_in[0], 96, 224, 224, 192, 224 * 192, 32, 4, 34, CU_TENSOR_MAP_SWIZZLE_64B, CU_TENSOR_MAP_L2_PROMOTION_L2_128B);
    encode3(fn, &mp.x28, d_in[0], 96, 224, 224, 192, 224 * 192, 32, 4, 28, CU_TENSOR_MAP_SWIZZLE_64B, CU_TENSOR_MAP_L2_PROMOTION_L2_128B);
    {
        cuuint32_t box[4] = {32, 8, 7, 2}, es[4] = {1, 1, 1, 1};
        cuuint64_t d[4] = {96, 7, 7, 96}, st[3] = {18432, 7 * 18432, 192};
        fn(&mp.w, CU_TENSOR_MAP_DATA_TYPE_BFLOAT16, 4, d_in[1], d, st, box, es, CU_TENSOR_MAP_INTERLEAVE_NONE, CU_TENSOR_MAP_SWIZZLE_64B, CU_TENSOR_MAP_L2_PROMOTION_NONE, CU_TENSOR_MAP_FLOAT_OOB_FILL_NONE);
    }
    encode3(fn, &mp.wst, wf, 256, 200, 72, 36864, 512, 256, 8, 1, CU_TENSOR_MAP_SWIZZLE_NONE);
    encode3(fn, &mp.y4, d_out, 96, 224, 224, 192, 224 * 192, 32, 4, 28, CU_TENSOR_MAP_SWIZZLE_64B);
    encode3(fn, &mp.y2, d_out, 96, 224, 224, 192, 224 * 192, 32, 2, 28, CU_TENSOR_MAP_SWIZZLE_64B);
    constexpr int SMEM_LAUNCH = SMEM_BYTES;
    cudaFuncSetAttribute(fftconv_kernel, cudaFuncAttributeMaxDynamicSharedMemorySize, SMEM_LAUNCH);
    fftconv_kernel<<<NSM, 512, SMEM_LAUNCH>>>(pt, mp);
}
```

```cpp
#include <cuda_runtime.h>
#include <cuda_bf16.h>
#include <cuda.h>
#include <stdint.h>

__device__ __align__(128) const uint32_t TAB_P1[4480] = {
0x3e75,0,0x3e72,0,0x8000,0,0xbd19,0,0x3e750000,0,0x3e720000,0,0x80000000,0,0xbd190000,0,
0,0x3e75,0,0x3e72,0,0x8000,0,0xbd19,0,0x3e750000,0,0x3e720000,0,0x80000000,0,0xbd190000,
0x3e69,0,0x3e5a,0,0xbd97,0,0xbdde,0,0x3e690000,0,0x3e5a0000,0,0xbd970000,0,0xbdde0000,0,
0,0x3e69,0,0x3e5a,0,0xbd97,0,0xbdde,0,0x3e690000,0,0x3e5a0000,0,0xbd970000,0,0xbdde0000,
0x3e75,0,0x3e5a,0,0x8000,0,0xbdde,0,0x3e750000,0,0x3e5a0000,0,0x80000000,0,0xbdde0000,0,
0,0x3e75,0,0x3e5a,0,0x8000,0,0xbdde,0,0x3e750000,0,0x3e5a0000,0,0x80000000,0,0xbdde0000,
0x3e10,0,0x3d19,0,0xbe46,0,0xbe72,0,0x3e100000,0,0x3d190000,0,0xbe460000,0,0xbe720000,0,
0,0x3e10,0,0x3d19,0,0xbe46,0,0xbe72,0,0x3e100000,0,0x3d190000,0,0xbe460000,0,0xbe720000,
0x3e75,0,0x3e2d,0,0x8000,0,0xbe2d,0,0x3e750000,0,0x3e2d0000,0,0x80000000,0,0xbe2d0000,0,
0,0x3e75,0,0x3e2d,0,0x8000,0,0xbe2d,0,0x3e750000,0,0x3e2d0000,0,0x80000000,0,0xbe2d0000,
0,0,0xbe2d,0,0xbe75,0,0xbe2d,0,0,0,0xbe2d0000,0,0xbe750000,0,0xbe2d0000,0,
0,0,0,0xbe2d,0,0xbe75,0,0xbe2d,0,0,0,0xbe2d0000,0,0xbe750000,0,0xbe2d0000,
0x3e75,0,0x3dde,0,0x8000,0,0xbe5a,0,0x3e750000,0,0x3dde0000,0,0x80000000,0,0xbe5a0000,0,
0,0x3e75,0,0x3dde,0,0x8000,0,0xbe5a,0,0x3e750000,0,0x3dde0000,0,0x80000000,0,0xbe5a0000,
0xbe10,0,0xbe72,0,0xbe46,0,0x3d19,0,0xbe100000,0,0xbe720000,0,0xbe460000,0,0x3d190000,0,
0,0xbe10,0,0xbe72,0,0xbe46,0,0x3d19,0,0xbe100000,0,0xbe720000,0,0xbe460000,0,0x3d190000,
0x3e75,0,0x3d19,0,0x8000,0,0xbe72,0,0x3e750000,0,0x3d190000,0,0x80000000,0,0xbe720000,0,
0,0x3e75,0,0x3d19,0,0x8000,0,0xbe72,0,0x3e750000,0,0x3d190000,0,0x80000000,0,0xbe720000,
0xbe69,0,0xbdde,0,0xbd97,0,0x3e5a,0,0xbe690000,0,0xbdde0000,0,0xbd970000,0,0x3e5a0000,0,
0,0xbe69,0,0xbdde,0,0xbd97,0,0x3e5a,0,0xbe690000,0,0xbdde0000,0,0xbd970000,0,0x3e5a0000,
0x3e75,0,0xbd19,0,0x8000,0,0xbe72,0,0x3e750000,0,0xbd190000,0,0x80000000,0,0xbe720000,0,
0,0x3e75,0,0xbd19,0,0x8000,0,0xbe72,0,0x3e750000,0,0xbd190000,0,0x80000000,0,0xbe720000,
0xbe69,0,0x3dde,0,0x3d97,0,0x3e5a,0,0xbe690000,0,0x3dde0000,0,0x3d970000,0,0x3e5a0000,0,
0,0xbe69,0,0x3dde,0,0x3d97,0,0x3e5a,0,0xbe690000,0,0x3dde0000,0,0x3d970000,0,0x3e5a0000,
0x3e75,0,0xbdde,0,0x8000,0,0xbe5a,0,0x3e750000,0,0xbdde0000,0,0x80000000,0,0xbe5a0000,0,
0,0x3e75,0,0xbdde,0,0x8000,0,0xbe5a,0,0x3e750000,0,0xbdde0000,0,0x80000000,0,0xbe5a0000,
0xbe10,0,0x3e72,0,0x3e46,0,0x3d19,0,0xbe100000,0,0x3e720000,0,0x3e460000,0,0x3d190000,0,
0,0xbe10,0,0x3e72,0,0x3e46,0,0x3d19,0,0xbe100000,0,0x3e720000,0,0x3e460000,0,0x3d190000,
0x3e75,0,0xbe2d,0,0x8000,0,0xbe2d,0,0x3e750000,0,0xbe2d0000,0,0x80000000,0,0xbe2d0000,0,
0,0x3e75,0,0xbe2d,0,0x8000,0,0xbe2d,0,0x3e750000,0,0xbe2d0000,0,0x80000000,0,0xbe2d0000,
0,0,0x3e2d,0,0x3e75,0,0xbe2d,0,0,0,0x3e2d0000,0,0x3e750000,0,0xbe2d0000,0,
0,0,0,0x3e2d,0,0x3e75,0,0xbe2d,0,0,0,0x3e2d0000,0,0x3e750000,0,0xbe2d0000,
0x3e75,0,0xbe5a,0,0x8000,0,0xbdde,0,0x3e750000,0,0xbe5a0000,0,0x80000000,0,0xbdde0000,0,
0,0x3e75,0,0xbe5a,0,0x8000,0,0xbdde,0,0x3e750000,0,0xbe5a0000,0,0x80000000,0,0xbdde0000,
0x3e10,0,0xbd19,0,0x3e46,0,0xbe72,0,0x3e100000,0,0xbd190000,0,0x3e460000,0,0xbe720000,0,
0,0x3e10,0,0xbd19,0,0x3e46,0,0xbe72,0,0x3e100000,0,0xbd190000,0,0x3e460000,0,0xbe720000,
0x3e75,0,0xbe72,0,0x8000,0,0xbd19,0,0x3e750000,0,0xbe720000,0,0x80000000,0,0xbd190000,0,
0,0x3e75,0,0xbe72,0,0x8000,0,0xbd19,0,0x3e750000,0,0xbe720000,0,0x80000000,0,0xbd190000,
0x3e69,0,0xbe5a,0,0x3d97,0,0xbdde,0,0x3e690000,0,0xbe5a0000,0,0x3d970000,0,0xbdde0000,0,
0,0x3e69,0,0xbe5a,0,0x3d97,0,0xbdde,0,0x3e690000,0,0xbe5a0000,0,0x3d970000,0,0xbdde0000,
0x3e46,0,0x3e2d,0,0xbe10,0,0xbe2d,0,0x3e460000,0,0x3e2d0000,0,0xbe100000,0,0xbe2d0000,0,
0,0x3e46,0,0x3e2d,0,0xbe10,0,0xbe2d,0,0x3e460000,0,0x3e2d0000,0,0xbe100000,0,0xbe2d0000,
0x3e10,0,0x3dde,0,0xbe46,0,0xbe5a,0,0x3e100000,0,0x3dde0000,0,0xbe460000,0,0xbe5a0000,0,
0,0x3e10,0,0x3dde,0,0xbe46,0,0xbe5a,0,0x3e100000,0,0x3dde0000,0,0xbe460000,0,0xbe5a0000,
0xbd97,0,0xbe2d,0,0xbe69,0,0xbe2d,0,0xbd970000,0,0xbe2d0000,0,0xbe690000,0,0xbe2d0000,0,
0,0xbd97,0,0xbe2d,0,0xbe69,0,0xbe2d,0,0xbd970000,0,0xbe2d0000,0,0xbe690000,0,0xbe2d0000,
0xbe69,0,0xbe72,0,0xbd97,0,0x3d19,0,0xbe690000,0,0xbe720000,0,0xbd970000,0,0x3d190000,0,
0,0xbe69,0,0xbe72,0,0xbd97,0,0x3d19,0,0xbe690000,0,0xbe720000,0,0xbd970000,0,0x3d190000,
0xbe75,0,0xbe2d,0,0x8000,0,0x3e2d,0,0xbe750000,0,0xbe2d0000,0,0x80000000,0,0x3e2d0000,0,
0,0xbe75,0,0xbe2d,0,0x8000,0,0x3e2d,0,0xbe750000,0,0xbe2d0000,0,0x80000000,0,0x3e2d0000,
0,0,0x3e2d,0,0x3e75,0,0x3e2d,0,0,0,0x3e2d0000,0,0x3e750000,0,0x3e2d0000,0,
0,0,0,0x3e2d,0,0x3e75,0,0x3e2d,0,0,0,0x3e2d0000,0,0x3e750000,0,0x3e2d0000,
0xbd97,0,0x3e2d,0,0x3e69,0,0x3e2d,0,0xbd970000,0,0x3e2d0000,0,0x3e690000,0,0x3e2d0000,0,
0,0xbd97,0,0x3e2d,0,0x3e69,0,0x3e2d,0,0xbd970000,0,0x3e2d0000,0,0x3e690000,0,0x3e2d0000,
0x3e69,0,0x3d19,0,0xbd97,0,0xbe72,0,0x3e690000,0,0x3d190000,0,0xbd970000,0,0xbe720000,0,
0,0x3e69,0,0x3d19,0,0xbd97,0,0xbe72,0,0x3e690000,0,0x3d190000,0,0xbd970000,0,0xbe720000,
0x3e46,0,0x3e2d,0,0x3e10,0,0xbe2d,0,0x3e460000,0,0x3e2d0000,0,0x3e100000,0,0xbe2d0000,0,
0,0x3e46,0,0x3e2d,0,0x3e10,0,0xbe2d,0,0x3e460000,0,0x3e2d0000,0,0x3e100000,0,0xbe2d0000,
0xbe10,0,0xbe5a,0,0xbe46,0,0x3dde,0,0xbe100000,0,0xbe5a0000,0,0xbe460000,0,0x3dde0000,0,
0,0xbe10,0,0xbe5a,0,0xbe46,0,0x3dde,0,0xbe100000,0,0xbe5a0000,0,0xbe460000,0,0x3dde0000,
0x3e46,0,0xbe2d,0,0xbe10,0,0xbe2d,0,0x3e460000,0,0xbe2d0000,0,0xbe100000,0,0xbe2d0000,0,
0,0x3e46,0,0xbe2d,0,0xbe10,0,0xbe2d,0,0x3e460000,0,0xbe2d0000,0,0xbe100000,0,0xbe2d0000,
0xbe10,0,0x3e5a,0,0x3e46,0,0x3dde,0,0xbe100000,0,0x3e5a0000,0,0x3e460000,0,0x3dde0000,0,
0,0xbe10,0,0x3e5a,0,0x3e46,0,0x3dde,0,0xbe100000,0,0x3e5a0000,0,0x3e460000,0,0x3dde0000,
0xbd97,0,0xbe2d,0,0xbe69,0,0x3e2d,0,0xbd970000,0,0xbe2d0000,0,0xbe690000,0,0x3e2d0000,0,
0,0xbd97,0,0xbe2d,0,0xbe69,0,0x3e2d,0,0xbd970000,0,0xbe2d0000,0,0xbe690000,0,0x3e2d0000,
0x3e69,0,0xbd19,0,0x3d97,0,0xbe72,0,0x3e690000,0,0xbd190000,0,0x3d970000,0,0xbe720000,0,
0,0x3e69,0,0xbd19,0,0x3d97,0,0xbe72,0,0x3e690000,0,0xbd190000,0,0x3d970000,0,0xbe720000,
0xbe75,0,0x3e2d,0,0x8000,0,0x3e2d,0,0xbe750000,0,0x3e2d0000,0,0x80000000,0,0x3e2d0000,0,
0,0xbe75,0,0x3e2d,0,0x8000,0,0x3e2d,0,0xbe750000,0,0x3e2d0000,0,0x80000000,0,0x3e2d0000,
0,0,0xbe2d,0,0xbe75,0,0x3e2d,0,0,0,0xbe2d0000,0,0xbe750000,0,0x3e2d0000,0,
0,0,0,0xbe2d,0,0xbe75,0,0x3e2d,0,0,0,0xbe2d0000,0,0xbe750000,0,0x3e2d0000,
0xbd97,0,0x3e2d,0,0x3e69,0,0xbe2d,0,0xbd970000,0,0x3e2d0000,0,0x3e690000,0,0xbe2d0000,0,
0,0xbd97,0,0x3e2d,0,0x3e69,0,0xbe2d,0,0xbd970000,0,0x3e2d0000,0,0x3e690000,0,0xbe2d0000,
0xbe69,0,0x3e72,0,0x3d97,0,0x3d19,0,0xbe690000,0,0x3e720000,0,0x3d970000,0,0x3d190000,0,
0,0xbe69,0,0x3e72,0,0x3d97,0,0x3d19,0,0xbe690000,0,0x3e720000,0,0x3d970000,0,0x3d190000,
0x3e46,0,0xbe2d,0,0x3e10,0,0xbe2d,0,0x3e460000,0,0xbe2d0000,0,0x3e100000,0,0xbe2d0000,0,
0,0x3e46,0,0xbe2d,0,0x3e10,0,0xbe2d,0,0x3e460000,0,0xbe2d0000,0,0x3e100000,0,0xbe2d0000,
0x3e10,0,0xbdde,0,0x3e46,0,0xbe5a,0,0x3e100000,0,0xbdde0000,0,0x3e460000,0,0xbe5a0000,0,
0,0x3e10,0,0xbdde,0,0x3e46,0,0xbe5a,0,0x3e100000,0,0xbdde0000,0,0x3e460000,0,0xbe5a0000,
0x3d97,0,0x3d19,0,0xbe69,0,0xbe72,0,0x3d970000,0,0x3d190000,0,0xbe690000,0,0xbe720000,0,
0,0x3d97,0,0x3d19,0,0xbe69,0,0xbe72,0,0x3d970000,0,0x3d190000,0,0xbe690000,0,0xbe720000,
0,0,0xbd19,0,0xbe75,0,0xbe72,0,0,0,0xbd190000,0,0xbe750000,0,0xbe720000,0,
0,0,0,0xbd19,0,0xbe75,0,0xbe72,0,0,0,0xbd190000,0,0xbe750000,0,0xbe720000,
0xbe46,0,0xbdde,0,0x3e10,0,0x3e5a,0,0xbe460000,0,0xbdde0000,0,0x3e100000,0,0x3e5a0000,0,
0,0xbe46,0,0xbdde,0,0x3e10,0,0x3e5a,0,0xbe460000,0,0xbdde0000,0,0x3e100000,0,0x3e5a0000,
0,0,0x3dde,0,0x3e75,0,0x3e5a,0,0,0,0x3dde0000,0,0x3e750000,0,0x3e5a0000,0,
0,0,0,0x3dde,0,0x3e75,0,0x3e5a,0,0,0,0x3dde0000,0,0x3e750000,0,0x3e5a0000,
0x3e75,0,0x3e2d,0,0x8000,0,0xbe2d,0,0x3e750000,0,0x3e2d0000,0,0x80000000,0,0xbe2d0000,0,
0,0x3e75,0,0x3e2d,0,0x8000,0,0xbe2d,0,0x3e750000,0,0x3e2d0000,0,0x80000000,0,0xbe2d0000,
0,0,0xbe2d,0,0xbe75,0,0xbe2d,0,0,0,0xbe2d0000,0,0xbe750000,0,0xbe2d0000,0,
0,0,0,0xbe2d,0,0xbe75,0,0xbe2d,0,0,0,0xbe2d0000,0,0xbe750000,0,0xbe2d0000,
0xbe46,0,0xbe5a,0,0xbe10,0,0x3dde,0,0xbe460000,0,0xbe5a0000,0,0xbe100000,0,0x3dde0000,0,
0,0xbe46,0,0xbe5a,0,0xbe10,0,0x3dde,0,0xbe460000,0,0xbe5a0000,0,0xbe100000,0,0x3dde0000,
0,0,0x3e5a,0,0x3e75,0,0x3dde,0,0,0,0x3e5a0000,0,0x3e750000,0,0x3dde0000,0,
0,0,0,0x3e5a,0,0x3e75,0,0x3dde,0,0,0,0x3e5a0000,0,0x3e750000,0,0x3dde0000,
0x3d97,0,0x3e72,0,0x3e69,0,0xbd19,0,0x3d970000,0,0x3e720000,0,0x3e690000,0,0xbd190000,0,
0,0x3d97,0,0x3e72,0,0x3e69,0,0xbd19,0,0x3d970000,0,0x3e720000,0,0x3e690000,0,0xbd190000,
0,0,0xbe72,0,0xbe75,0,0xbd19,0,0,0,0xbe720000,0,0xbe750000,0,0xbd190000,0,
0,0,0,0xbe72,0,0xbe75,0,0xbd19,0,0,0,0xbe720000,0,0xbe750000,0,0xbd190000,
0x3d97,0,0xbe72,0,0xbe69,0,0xbd19,0,0x3d970000,0,0xbe720000,0,0xbe690000,0,0xbd190000,0,
0,0x3d97,0,0xbe72,0,0xbe69,0,0xbd19,0,0x3d970000,0,0xbe720000,0,0xbe690000,0,0xbd190000,
0,0,0x3e72,0,0x3e75,0,0xbd19,0,0,0,0x3e720000,0,0x3e750000,0,0xbd190000,0,
0,0,0,0x3e72,0,0x3e75,0,0xbd19,0,0,0,0x3e720000,0,0x3e750000,0,0xbd190000,
0xbe46,0,0x3e5a,0,0x3e10,0,0x3dde,0,0xbe460000,0,0x3e5a0000,0,0x3e100000,0,0x3dde0000,0,
0,0xbe46,0,0x3e5a,0,0x3e10,0,0x3dde,0,0xbe460000,0,0x3e5a0000,0,0x3e100000,0,0x3dde0000,
0,0,0xbe5a,0,0xbe75,0,0x3dde,0,0,0,0xbe5a0000,0,0xbe750000,0,0x3dde0000,0,
0,0,0,0xbe5a,0,0xbe75,0,0x3dde,0,0,0,0xbe5a0000,0,0xbe750000,0,0x3dde0000,
0x3e75,0,0xbe2d,0,0x8000,0,0xbe2d,0,0x3e750000,0,0xbe2d0000,0,0x80000000,0,0xbe2d0000,0,
0,0x3e75,0,0xbe2d,0,0x8000,0,0xbe2d,0,0x3e750000,0,0xbe2d0000,0,0x80000000,0,0xbe2d0000,
0,0,0x3e2d,0,0x3e75,0,0xbe2d,0,0,0,0x3e2d0000,0,0x3e750000,0,0xbe2d0000,0,
0,0,0,0x3e2d,0,0x3e75,0,0xbe2d,0,0,0,0x3e2d0000,0,0x3e750000,0,0xbe2d0000,
0xbe46,0,0x3dde,0,0xbe10,0,0x3e5a,0,0xbe460000,0,0x3dde0000,0,0xbe100000,0,0x3e5a0000,0,
0,0xbe46,0,0x3dde,0,0xbe10,0,0x3e5a,0,0xbe460000,0,0x3dde0000,0,0xbe100000,0,0x3e5a0000,
0,0,0xbdde,0,0xbe75,0,0x3e5a,0,0,0,0xbdde0000,0,0xbe750000,0,0x3e5a0000,0,
0,0,0,0xbdde,0,0xbe75,0,0x3e5a,0,0,0,0xbdde0000,0,0xbe750000,0,0x3e5a0000,
0x3d97,0,0xbd19,0,0x3e69,0,0xbe72,0,0x3d970000,0,0xbd190000,0,0x3e690000,0,0xbe720000,0,
0,0x3d97,0,0xbd19,0,0x3e69,0,0xbe72,0,0x3d970000,0,0xbd190000,0,0x3e690000,0,0xbe720000,
0,0,0x3d19,0,0x3e75,0,0xbe72,0,0,0,0x3d190000,0,0x3e750000,0,0xbe720000,0,
0,0,0,0x3d19,0,0x3e75,0,0xbe72,0,0,0,0x3d190000,0,0x3e750000,0,0xbe720000,
0xbd97,0,0xbdde,0,0xbe69,0,0xbe5a,0,0xbd970000,0,0xbdde0000,0,0xbe690000,0,0xbe5a0000,0,
0,0xbd97,0,0xbdde,0,0xbe69,0,0xbe5a,0,0xbd970000,0,0xbdde0000,0,0xbe690000,0,0xbe5a0000,
0xbe10,0,0xbe2d,0,0xbe46,0,0xbe2d,0,0xbe100000,0,0xbe2d0000,0,0xbe460000,0,0xbe2d0000,0,
0,0xbe10,0,0xbe2d,0,0xbe46,0,0xbe2d,0,0xbe100000,0,0xbe2d0000,0,0xbe460000,0,0xbe2d0000,
0x3e46,0,0x3e72,0,0x3e10,0,0x3d19,0,0x3e460000,0,0x3e720000,0,0x3e100000,0,0x3d190000,0,
0,0x3e46,0,0x3e72,0,0x3e10,0,0x3d19,0,0x3e460000,0,0x3e720000,0,0x3e100000,0,0x3d190000,
0x3e69,0,0x3e2d,0,0xbd97,0,0xbe2d,0,0x3e690000,0,0x3e2d0000,0,0xbd970000,0,0xbe2d0000,0,
0,0x3e69,0,0x3e2d,0,0xbd97,0,0xbe2d,0,0x3e690000,0,0x3e2d0000,0,0xbd970000,0,0xbe2d0000,
0xbe75,0,0xbe2d,0,0x8000,0,0x3e2d,0,0xbe750000,0,0xbe2d0000,0,0x80000000,0,0x3e2d0000,0,
0,0xbe75,0,0xbe2d,0,0x8000,0,0x3e2d,0,0xbe750000,0,0xbe2d0000,0,0x80000000,0,0x3e2d0000,
0,0,0x3e2d,0,0x3e75,0,0x3e2d,0,0,0,0x3e2d0000,0,0x3e750000,0,0x3e2d0000,0,
0,0,0,0x3e2d,0,0x3e75,0,0x3e2d,0,0,0,0x3e2d0000,0,0x3e750000,0,0x3e2d0000,
0x3e46,0,0xbd19,0,0xbe10,0,0xbe72,0,0x3e460000,0,0xbd190000,0,0xbe100000,0,0xbe720000,0,
0,0x3e46,0,0xbd19,0,0xbe10,0,0xbe72,0,0x3e460000,0,0xbd190000,0,0xbe100000,0,0xbe720000,
0xbe69,0,0xbe2d,0,0xbd97,0,0x3e2d,0,0xbe690000,0,0xbe2d0000,0,0xbd970000,0,0x3e2d0000,0,
0,0xbe69,0,0xbe2d,0,0xbd97,0,0x3e2d,0,0xbe690000,0,0xbe2d0000,0,0xbd970000,0,0x3e2d0000,
0xbd97,0,0x3e5a,0,0x3e69,0,0x3dde,0,0xbd970000,0,0x3e5a0000,0,0x3e690000,0,0x3dde0000,0,
0,0xbd97,0,0x3e5a,0,0x3e69,0,0x3dde,0,0xbd970000,0,0x3e5a0000,0,0x3e690000,0,0x3dde0000,
0x3e10,0,0xbe2d,0,0xbe46,0,0xbe2d,0,0x3e100000,0,0xbe2d0000,0,0xbe460000,0,0xbe2d0000,0,
0,0x3e10,0,0xbe2d,0,0xbe46,0,0xbe2d,0,0x3e100000,0,0xbe2d0000,0,0xbe460000,0,0xbe2d0000,
0xbd97,0,0xbe5a,0,0xbe69,0,0x3dde,0,0xbd970000,0,0xbe5a0000,0,0xbe690000,0,0x3dde0000,0,
0,0xbd97,0,0xbe5a,0,0xbe69,0,0x3dde,0,0xbd970000,0,0xbe5a0000,0,0xbe690000,0,0x3dde0000,
0x3e10,0,0x3e2d,0,0x3e46,0,0xbe2d,0,0x3e100000,0,0x3e2d0000,0,0x3e460000,0,0xbe2d0000,0,
0,0x3e10,0,0x3e2d,0,0x3e46,0,0xbe2d,0,0x3e100000,0,0x3e2d0000,0,0x3e460000,0,0xbe2d0000,
0x3e46,0,0x3d19,0,0x3e10,0,0xbe72,0,0x3e460000,0,0x3d190000,0,0x3e100000,0,0xbe720000,0,
0,0x3e46,0,0x3d19,0,0x3e10,0,0xbe72,0,0x3e460000,0,0x3d190000,0,0x3e100000,0,0xbe720000,
0xbe69,0,0x3e2d,0,0x3d97,0,0x3e2d,0,0xbe690000,0,0x3e2d0000,0,0x3d970000,0,0x3e2d0000,0,
0,0xbe69,0,0x3e2d,0,0x3d97,0,0x3e2d,0,0xbe690000,0,0x3e2d0000,0,0x3d970000,0,0x3e2d0000,
0xbe75,0,0x3e2d,0,0x8000,0,0x3e2d,0,0xbe750000,0,0x3e2d0000,0,0x80000000,0,0x3e2d0000,0,
0,0xbe75,0,0x3e2d,0,0x8000,0,0x3e2d,0,0xbe750000,0,0x3e2d0000,0,0x80000000,0,0x3e2d0000,
0,0,0xbe2d,0,0xbe75,0,0x3e2d,0,0,0,0xbe2d0000,0,0xbe750000,0,0x3e2d0000,0,
0,0,0,0xbe2d,0,0xbe75,0,0x3e2d,0,0,0,0xbe2d0000,0,0xbe750000,0,0x3e2d0000,
0x3e46,0,0xbe72,0,0xbe10,0,0x3d19,0,0x3e460000,0,0xbe720000,0,0xbe100000,0,0x3d190000,0,
0,0x3e46,0,0xbe72,0,0xbe10,0,0x3d19,0,0x3e460000,0,0xbe720000,0,0xbe100000,0,0x3d190000,
0x3e69,0,0xbe2d,0,0x3d97,0,0xbe2d,0,0x3e690000,0,0xbe2d0000,0,0x3d970000,0,0xbe2d0000,0,
0,0x3e69,0,0xbe2d,0,0x3d97,0,0xbe2d,0,0x3e690000,0,0xbe2d0000,0,0x3d970000,0,0xbe2d0000,
0xbd97,0,0x3dde,0,0x3e69,0,0xbe5a,0,0xbd970000,0,0x3dde0000,0,0x3e690000,0,0xbe5a0000,0,
0,0xbd97,0,0x3dde,0,0x3e69,0,0xbe5a,0,0xbd970000,0,0x3dde0000,0,0x3e690000,0,0xbe5a0000,
0xbe10,0,0x3e2d,0,0x3e46,0,0xbe2d,0,0xbe100000,0,0x3e2d0000,0,0x3e460000,0,0xbe2d0000,0,
0,0xbe10,0,0x3e2d,0,0x3e46,0,0xbe2d,0,0xbe100000,0,0x3e2d0000,0,0x3e460000,0,0xbe2d0000,
0xbe46,0,0xbe5a,0,0xbe10,0,0xbdde,0,0xbe460000,0,0xbe5a0000,0,0xbe100000,0,0xbdde0000,0,
0,0xbe46,0,0xbe5a,0,0xbe10,0,0xbdde,0,0xbe460000,0,0xbe5a0000,0,0xbe100000,0,0xbdde0000,
0xbe69,0,0xbe72,0,0xbd97,0,0xbd19,0,0xbe690000,0,0xbe720000,0,0xbd970000,0,0xbd190000,0,
0,0xbe69,0,0xbe72,0,0xbd97,0,0xbd19,0,0xbe690000,0,0xbe720000,0,0xbd970000,0,0xbd190000,
0x3d97,0,0xbd19,0,0xbe69,0,0xbe72,0,0x3d970000,0,0xbd190000,0,0xbe690000,0,0xbe720000,0,
0,0x3d97,0,0xbd19,0,0xbe69,0,0xbe72,0,0x3d970000,0,0xbd190000,0,0xbe690000,0,0xbe720000,
0xbe10,0,0xbe5a,0,0xbe46,0,0xbdde,0,0xbe100000,0,0xbe5a0000,0,0xbe460000,0,0xbdde0000,0,
0,0xbe10,0,0xbe5a,0,0xbe46,0,0xbdde,0,0xbe100000,0,0xbe5a0000,0,0xbe460000,0,0xbdde0000,
0x3e75,0,0x3e2d,0,0x8000,0,0xbe2d,0,0x3e750000,0,0x3e2d0000,0,0x80000000,0,0xbe2d0000,0,
0,0x3e75,0,0x3e2d,0,0x8000,0,0xbe2d,0,0x3e750000,0,0x3e2d0000,0,0x80000000,0,0xbe2d0000,
0,0,0xbe2d,0,0xbe75,0,0xbe2d,0,0,0,0xbe2d0000,0,0xbe750000,0,0xbe2d0000,0,
0,0,0,0xbe2d,0,0xbe75,0,0xbe2d,0,0,0,0xbe2d0000,0,0xbe750000,0,0xbe2d0000,
0x3d97,0,0x3e72,0,0x3e69,0,0x3d19,0,0x3d970000,0,0x3e720000,0,0x3e690000,0,0x3d190000,0,
0,0x3d97,0,0x3e72,0,0x3e69,0,0x3d19,0,0x3d970000,0,0x3e720000,0,0x3e690000,0,0x3d190000,
0x3e10,0,0xbdde,0,0xbe46,0,0xbe5a,0,0x3e100000,0,0xbdde0000,0,0xbe460000,0,0xbe5a0000,0,
0,0x3e10,0,0xbdde,0,0xbe46,0,0xbe5a,0,0x3e100000,0,0xbdde0000,0,0xbe460000,0,0xbe5a0000,
0xbe46,0,0x3dde,0,0x3e10,0,0x3e5a,0,0xbe460000,0,0x3dde0000,0,0x3e100000,0,0x3e5a0000,0,
0,0xbe46,0,0x3dde,0,0x3e10,0,0x3e5a,0,0xbe460000,0,0x3dde0000,0,0x3e100000,0,0x3e5a0000,
0x3e69,0,0xbd19,0,0xbd97,0,0xbe72,0,0x3e690000,0,0xbd190000,0,0xbd970000,0,0xbe720000,0,
0,0x3e69,0,0xbd19,0,0xbd97,0,0xbe72,0,0x3e690000,0,0xbd190000,0,0xbd970000,0,0xbe720000,
0xbe46,0,0xbdde,0,0xbe10,0,0x3e5a,0,0xbe460000,0,0xbdde0000,0,0xbe100000,0,0x3e5a0000,0,
0,0xbe46,0,0xbdde,0,0xbe10,0,0x3e5a,0,0xbe460000,0,0xbdde0000,0,0xbe100000,0,0x3e5a0000,
0x3e69,0,0x3d19,0,0x3d97,0,0xbe72,0,0x3e690000,0,0x3d190000,0,0x3d970000,0,0xbe720000,0,
0,0x3e69,0,0x3d19,0,0x3d97,0,0xbe72,0,0x3e690000,0,0x3d190000,0,0x3d970000,0,0xbe720000,
0x3d97,0,0xbe72,0,0xbe69,0,0x3d19,0,0x3d970000,0,0xbe720000,0,0xbe690000,0,0x3d190000,0,
0,0x3d97,0,0xbe72,0,0xbe69,0,0x3d19,0,0x3d970000,0,0xbe720000,0,0xbe690000,0,0x3d190000,
0x3e10,0,0x3dde,0,0x3e46,0,0xbe5a,0,0x3e100000,0,0x3dde0000,0,0x3e460000,0,0xbe5a0000,0,
0,0x3e10,0,0x3dde,0,0x3e46,0,0xbe5a,0,0x3e100000,0,0x3dde0000,0,0x3e460000,0,0xbe5a0000,
0x3e75,0,0xbe2d,0,0x8000,0,0xbe2d,0,0x3e750000,0,0xbe2d0000,0,0x80000000,0,0xbe2d0000,0,
0,0x3e75,0,0xbe2d,0,0x8000,0,0xbe2d,0,0x3e750000,0,0xbe2d0000,0,0x80000000,0,0xbe2d0000,
0,0,0x3e2d,0,0x3e75,0,0xbe2d,0,0,0,0x3e2d0000,0,0x3e750000,0,0xbe2d0000,0,
0,0,0,0x3e2d,0,0x3e75,0,0xbe2d,0,0,0,0x3e2d0000,0,0x3e750000,0,0xbe2d0000,
0x3d97,0,0x3d19,0,0x3e69,0,0xbe72,0,0x3d970000,0,0x3d190000,0,0x3e690000,0,0xbe720000,0,
0,0x3d97,0,0x3d19,0,0x3e69,0,0xbe72,0,0x3d970000,0,0x3d190000,0,0x3e690000,0,0xbe720000,
0xbe10,0,0x3e5a,0,0x3e46,0,0xbdde,0,0xbe100000,0,0x3e5a0000,0,0x3e460000,0,0xbdde0000,0,
0,0xbe10,0,0x3e5a,0,0x3e46,0,0xbdde,0,0xbe100000,0,0x3e5a0000,0,0x3e460000,0,0xbdde0000,
0xbe46,0,0x3e5a,0,0x3e10,0,0xbdde,0,0xbe460000,0,0x3e5a0000,0,0x3e100000,0,0xbdde0000,0,
0,0xbe46,0,0x3e5a,0,0x3e10,0,0xbdde,0,0xbe460000,0,0x3e5a0000,0,0x3e100000,0,0xbdde0000,
0xbe69,0,0x3e72,0,0x3d97,0,0xbd19,0,0xbe690000,0,0x3e720000,0,0x3d970000,0,0xbd190000,0,
0,0xbe69,0,0x3e72,0,0x3d97,0,0xbd19,0,0xbe690000,0,0x3e720000,0,0x3d970000,0,0xbd190000,
0x3eb7,0x3eb7,0x3eb7,0x3eb7,0x3eb78000,0x3eb78000,0x3eb78000,0x3eb78000,0x3eb7,0x3de23eae,0x3e573e94,0x3e943e57,0x3eb78000,0x3eaebde2,0x3e94be57,0x3e57be94,
0x3eb7,0x3e573e94,0x3eae3de2,0x3eaebde2,0x3eb78000,0x3e94be57,0x3de2beae,0xbde2beae,0x3eb7,0x3e943e57,0x3eaebde2,0x3de2beae,0x3eb78000,0x3e57be94,0xbde2beae,0xbeaebde2,
0x3eb7,0x3eb7,0x3eb7,0x3eb7,0x3eb78000,0x3eb78000,0x3eb78000,0x3eb78000,0x3eae3de2,0x3eb70000,0x3eaebde2,0x3e94be57,0x3de2beae,0xbeb7,0xbde2beae,0xbe57be94,
0x3e57be94,0xbeb7,0xbe57be94,0xbeaebde2,0xbe94be57,0xbeb78000,0xbe943e57,0xbde23eae,0xbe57be94,0xbeb70000,0xbe573e94,0x3de23eae,0xbe943e57,0x3eb7,0x3e943e57,0x3eaebde2,
0x3eb7,0x3eae3de2,0x3e57be94,0xbe57be94,0x3eb78000,0x3de2beae,0xbe94be57,0xbe943e57,0x3eb7,0x3eb70000,0xbeb7,0xbeb70000,0x3eb78000,0xbeb7,0xbeb78000,0x3eb7,
0x3eb7,0x3eaebde2,0xbe57be94,0xbe573e94,0x3eb78000,0xbde2beae,0xbe943e57,0x3e943e57,0x3eb7,0x3e94be57,0xbeaebde2,0x3de23eae,0x3eb78000,0xbe57be94,0xbde23eae,0x3eaebde2,
0xbeae3de2,0x3eb7,0x3eae3de2,0x3e57be94,0x3de23eae,0x3eb78000,0x3de2beae,0xbe94be57,0x3eb7,0x3eb70000,0xbeb7,0xbeb70000,0x3eb78000,0xbeb7,0xbeb78000,0x3eb7,
0x3eae3de2,0xbeb7,0xbeae3de2,0x3e573e94,0x3de2beae,0xbeb78000,0x3de23eae,0x3e94be57,0x3e57be94,0xbeb70000,0x3e573e94,0x3de2beae,0xbe94be57,0x3eb7,0x3e94be57,0xbeaebde2,
0x3eb7,0x3e57be94,0xbeae3de2,0x3eae3de2,0x3eb78000,0xbe94be57,0x3de23eae,0x3de2beae,0x3eb7,0x3de2beae,0xbe573e94,0x3e94be57,0x3eb78000,0xbeaebde2,0x3e943e57,0xbe57be94,
0x3eb7,0xbeb7,0x3eb7,0xbeb7,0x3eb78000,0xbeb78000,0x3eb78000,0xbeb78000,0x3eb7,0xbde2beae,0x3e573e94,0xbe94be57,0x3eb78000,0xbeae3de2,0x3e94be57,0xbe573e94,
0xbe57be94,0x3eb7,0x3e57be94,0xbeae3de2,0xbe943e57,0x3eb78000,0xbe94be57,0x3de23eae,0xbeae3de2,0x3eb70000,0xbeaebde2,0x3e943e57,0x3de23eae,0xbeb7,0xbde23eae,0x3e57be94,
0x3eb7,0xbeb7,0x3eb7,0xbeb7,0x3eb78000,0xbeb78000,0x3eb78000,0xbeb78000,0x3eae3de2,0xbeb70000,0x3eaebde2,0xbe943e57,0x3de2beae,0x3eb7,0xbde2beae,0x3e573e94,
0x3eb7,0xbe57be94,0x3eae3de2,0xbeae3de2,0x3eb78000,0xbe943e57,0x3de2beae,0x3de23eae,0x3eb7,0xbe94be57,0x3eaebde2,0xbde23eae,0x3eb78000,0xbe573e94,0xbde2beae,0x3eae3de2,
0x3eb7,0xbeaebde2,0x3e57be94,0x3e573e94,0x3eb78000,0xbde23eae,0xbe94be57,0x3e94be57,0x3eb7,0xbeb70000,0xbeb7,0x3eb70000,0x3eb78000,0x3eb7,0xbeb78000,0xbeb7,
0x3e57be94,0x3eb7,0xbe57be94,0x3eae3de2,0xbe94be57,0x3eb78000,0xbe943e57,0x3de2beae,0xbe57be94,0x3eb70000,0xbe573e94,0xbde2beae,0xbe943e57,0xbeb7,0x3e943e57,0xbeae3de2,
0xbeae3de2,0xbeb7,0x3eae3de2,0xbe573e94,0x3de23eae,0xbeb78000,0x3de2beae,0x3e943e57,0x3eb7,0xbeb70000,0xbeb7,0x3eb70000,0x3eb78000,0x3eb7,0xbeb78000,0xbeb7,
0x3eb7,0xbeae3de2,0xbe57be94,0x3e57be94,0x3eb78000,0x3de23eae,0xbe943e57,0xbe94be57,0x3eb7,0xbe943e57,0xbeaebde2,0xbde2beae,0x3eb78000,0x3e573e94,0xbde23eae,0xbeae3de2,
0x3eb7,0xbe573e94,0xbeae3de2,0xbeaebde2,0x3eb78000,0x3e943e57,0x3de23eae,0xbde23eae,0x3eb7,0xbde23eae,0xbe573e94,0xbe943e57,0x3eb78000,0x3eae3de2,0x3e943e57,0x3e573e94,
0x3eae3de2,0x3eb7,0xbeae3de2,0xbe57be94,0x3de2beae,0x3eb78000,0x3de23eae,0xbe943e57,0x3e57be94,0x3eb70000,0x3e573e94,0xbde23eae,0xbe94be57,0xbeb7,0x3e94be57,0x3eae3de2,
0xbe57be94,0xbeb7,0x3e57be94,0x3eaebde2,0xbe943e57,0xbeb78000,0xbe94be57,0xbde2beae,0xbeae3de2,0xbeb70000,0xbeaebde2,0xbe94be57,0x3de23eae,0x3eb7,0xbde23eae,0xbe573e94,
0x3eb7,0x3eb7,0x3eb7,0x3eb7,0x3eb78000,0x3eb78000,0x3eb78000,0x3eb78000,0x3e57be94,0x3de2beae,0xbeb7,0xbde2beae,0xbe94be57,0xbeaebde2,0xbeb78000,0xbeae3de2,
0xbeae3de2,0xbe573e94,0x3eb7,0x3e573e94,0x3de23eae,0x3e943e57,0x3eb78000,0x3e94be57,0x3eae3de2,0x3e94be57,0xbeb7,0xbe94be57,0x3de2beae,0xbe57be94,0xbeb78000,0xbe573e94,
0x3eb7,0x3eb7,0x3eb7,0x3eb7,0x3eb78000,0x3eb78000,0x3eb78000,0x3eb78000,0xbe57be94,0xbe94be57,0xbeaebde2,0xbeb70000,0xbe943e57,0xbe573e94,0xbde23eae,0x3eb7,
0x3eae3de2,0x3eaebde2,0x3e57be94,0xbeb7,0x3de2beae,0xbde2beae,0xbe94be57,0xbeb78000,0xbeae3de2,0xbde23eae,0x3e573e94,0x3eb70000,0x3de23eae,0x3eae3de2,0x3e94be57,0xbeb7,
0xbe57be94,0xbeae3de2,0x3eb7,0x3eae3de2,0xbe943e57,0x3de23eae,0x3eb78000,0x3de2beae,0x3eb7,0x3eb70000,0xbeb7,0xbeb70000,0x3eb78000,0xbeb7,0xbeb78000,0x3eb7,
0x3e57be94,0xbeaebde2,0x3eb7,0x3eaebde2,0xbe94be57,0xbde23eae,0x3eb78000,0xbde2beae,0xbeae3de2,0x3e943e57,0xbeb7,0xbe943e57,0x3de23eae,0x3e57be94,0xbeb78000,0x3e573e94,
0x3e57be94,0xbe57be94,0xbeae3de2,0x3eb7,0xbe94be57,0xbe943e57,0x3de23eae,0x3eb78000,0x3eb7,0x3eb70000,0xbeb7,0xbeb70000,0x3eb78000,0xbeb7,0xbeb78000,0x3eb7,
0xbe57be94,0xbe573e94,0x3eae3de2,0xbeb7,0xbe943e57,0x3e943e57,0x3de2beae,0xbeb78000,0x3eae3de2,0xbde2beae,0xbe573e94,0x3eb70000,0x3de2beae,0xbeae3de2,0x3e943e57,0xbeb7,
0x3eae3de2,0xbe57be94,0x3eb7,0x3e57be94,0x3de2beae,0xbe943e57,0x3eb78000,0xbe94be57,0xbe57be94,0x3de23eae,0xbeb7,0xbde23eae,0xbe943e57,0x3eaebde2,0xbeb78000,0x3eae3de2,
0x3eb7,0xbeb7,0x3eb7,0xbeb7,0x3eb78000,0xbeb78000,0x3eb78000,0xbeb78000,0x3e57be94,0xbde23eae,0xbeb7,0x3de23eae,0xbe94be57,0x3eae3de2,0xbeb78000,0x3eaebde2,
0xbeae3de2,0x3eae3de2,0xbe57be94,0x3eb7,0x3de23eae,0x3de2beae,0xbe943e57,0x3eb78000,0x3e57be94,0xbe943e57,0x3eaebde2,0xbeb70000,0xbe94be57,0x3e573e94,0xbde2beae,0x3eb7,
0x3eb7,0xbeb7,0x3eb7,0xbeb7,0x3eb78000,0xbeb78000,0x3eb78000,0xbeb78000,0xbe57be94,0x3e943e57,0xbeaebde2,0x3eb70000,0xbe943e57,0x3e57be94,0xbde23eae,0xbeb7,
0xbeae3de2,0x3e57be94,0x3eb7,0xbe57be94,0x3de23eae,0xbe94be57,0x3eb78000,0xbe943e57,0x3eae3de2,0xbe943e57,0xbeb7,0x3e943e57,0x3de2beae,0x3e573e94,0xbeb78000,0x3e57be94,
0xbe57be94,0x3eaebde2,0x3eb7,0xbeaebde2,0xbe943e57,0xbde2beae,0x3eb78000,0xbde23eae,0x3eb7,0xbeb70000,0xbeb7,0x3eb70000,0x3eb78000,0x3eb7,0xbeb78000,0xbeb7,
0x3eae3de2,0xbeae3de2,0x3e57be94,0x3eb7,0x3de2beae,0x3de23eae,0xbe94be57,0x3eb78000,0xbeae3de2,0x3de2beae,0x3e573e94,0xbeb70000,0x3de23eae,0xbeaebde2,0x3e94be57,0x3eb7,
0x3e57be94,0x3e573e94,0xbeae3de2,0xbeb7,0xbe94be57,0x3e94be57,0x3de23eae,0xbeb78000,0x3eb7,0xbeb70000,0xbeb7,0x3eb70000,0x3eb78000,0x3eb7,0xbeb78000,0xbeb7,
0x3e57be94,0x3eae3de2,0x3eb7,0xbeae3de2,0xbe94be57,0x3de2beae,0x3eb78000,0x3de23eae,0xbeae3de2,0xbe94be57,0xbeb7,0x3e94be57,0x3de23eae,0xbe573e94,0xbeb78000,0xbe57be94,
0x3eae3de2,0x3e573e94,0x3eb7,0xbe573e94,0x3de2beae,0x3e94be57,0x3eb78000,0x3e943e57,0xbe57be94,0xbde2beae,0xbeb7,0x3de2beae,0xbe943e57,0xbeae3de2,0xbeb78000,0xbeaebde2,
0xbe57be94,0x3e57be94,0x3eae3de2,0x3eb7,0xbe943e57,0xbe94be57,0x3de2beae,0x3eb78000,0x3eae3de2,0x3de23eae,0xbe573e94,0xbeb70000,0x3de2beae,0x3eaebde2,0x3e943e57,0x3eb7,
0xbeae3de2,0xbeaebde2,0xbe57be94,0xbeb7,0x3de23eae,0xbde23eae,0xbe943e57,0xbeb78000,0x3e57be94,0x3e94be57,0x3eaebde2,0x3eb70000,0xbe94be57,0xbe57be94,0xbde2beae,0xbeb7,
0x3eb7,0x3eb7,0x3eb7,0x3eb7,0x3eb78000,0x3eb78000,0x3eb78000,0x3eb78000,0xbeae3de2,0xbe943e57,0xbe573e94,0xbde23eae,0x3de23eae,0x3e573e94,0x3e943e57,0x3eae3de2,
0xbe57be94,0xbeaebde2,0xbeae3de2,0xbe573e94,0xbe943e57,0xbde23eae,0x3de23eae,0x3e943e57,0x3e57be94,0xbde2beae,0xbeaebde2,0xbe943e57,0xbe94be57,0xbeae3de2,0xbde23eae,0x3e573e94,
0,0,0,0,0,0,0,0,0,0,0,0,0,0,0,0,
0,0,0,0,0,0,0,0,0,0,0,0,0,0,0,0,
0x3eae3de2,0x3e57be94,0xbe57be94,0xbeae3de2,0x3de2beae,0xbe94be57,0xbe943e57,0x3de23eae,0x3eb7,0x3eb70000,0xbeb7,0xbeb70000,0x3eb78000,0xbeb7,0xbeb78000,0x3eb7,
0xbeae3de2,0x3e573e94,0x3e57be94,0xbeaebde2,0x3de23eae,0x3e94be57,0xbe94be57,0xbde23eae,0xbe57be94,0xbde23eae,0x3eaebde2,0xbe94be57,0xbe943e57,0x3eae3de2,0xbde2beae,0xbe573e94,
0,0,0,0,0,0,0,0,0,0,0,0,0,0,0,0,
0,0,0,0,0,0,0,0,0,0,0,0,0,0,0,0,
0x3e57be94,0xbeae3de2,0x3eae3de2,0xbe57be94,0xbe94be57,0x3de23eae,0x3de2beae,0xbe943e57,0x3eae3de2,0xbe94be57,0x3e573e94,0xbde2beae,0x3de2beae,0xbe573e94,0x3e94be57,0xbeae3de2,
0x3eb7,0xbeb7,0x3eb7,0xbeb7,0x3eb78000,0xbeb78000,0x3eb78000,0xbeb78000,0xbeae3de2,0x3e94be57,0xbe573e94,0x3de2beae,0x3de23eae,0xbe57be94,0x3e943e57,0xbeaebde2,
0,0,0,0,0,0,0,0,0,0,0,0,0,0,0,0,
0,0,0,0,0,0,0,0,0,0,0,0,0,0,0,0,
0xbe57be94,0x3eae3de2,0xbeae3de2,0x3e57be94,0xbe943e57,0x3de2beae,0x3de23eae,0xbe94be57,0x3e57be94,0x3de23eae,0xbeaebde2,0x3e94be57,0xbe94be57,0x3eaebde2,0xbde23eae,0xbe57be94,
0x3eae3de2,0xbe573e94,0xbe57be94,0x3eaebde2,0x3de2beae,0x3e943e57,0xbe943e57,0xbde2beae,0x3eb7,0xbeb70000,0xbeb7,0x3eb70000,0x3eb78000,0x3eb7,0xbeb78000,0xbeb7,
0,0,0,0,0,0,0,0,0,0,0,0,0,0,0,0,
0,0,0,0,0,0,0,0,0,0,0,0,0,0,0,0,
0xbeae3de2,0xbe57be94,0x3e57be94,0x3eae3de2,0x3de23eae,0xbe943e57,0xbe94be57,0x3de2beae,0xbe57be94,0x3de2beae,0x3eaebde2,0x3e943e57,0xbe943e57,0xbeaebde2,0xbde2beae,0x3e57be94,
0x3e57be94,0x3eaebde2,0x3eae3de2,0x3e573e94,0xbe94be57,0xbde2beae,0x3de2beae,0x3e94be57,0x3eae3de2,0x3e943e57,0x3e573e94,0x3de23eae,0x3de2beae,0x3e57be94,0x3e94be57,0x3eaebde2,
0,0,0,0,0,0,0,0,0,0,0,0,0,0,0,0,
0,0,0,0,0,0,0,0,0,0,0,0,0,0,0,0,
0,0,0,0,0,0,0,0,0,0,0,0,0,0,0,0,
0,0,0,0,0,0,0,0,0,0,0,0,0,0,0,0,
0x3eb7,0x3eb7,0x3eb7,0x3eb7,0x3eb78000,0x3eb78000,0x3eb78000,0x3eb78000,0xbeae3de2,0xbe943e57,0xbe573e94,0xbde23eae,0x3de23eae,0x3e573e94,0x3e943e57,0x3eae3de2,
0xbe57be94,0xbeaebde2,0xbeae3de2,0xbe573e94,0xbe943e57,0xbde23eae,0x3de23eae,0x3e943e57,0x3e57be94,0xbde2beae,0xbeaebde2,0xbe943e57,0xbe94be57,0xbeae3de2,0xbde23eae,0x3e573e94,
0,0,0,0,0,0,0,0,0,0,0,0,0,0,0,0,
0,0,0,0,0,0,0,0,0,0,0,0,0,0,0,0,
0x3eae3de2,0x3e57be94,0xbe57be94,0xbeae3de2,0x3de2beae,0xbe94be57,0xbe943e57,0x3de23eae,0x3eb7,0x3eb70000,0xbeb7,0xbeb70000,0x3eb78000,0xbeb7,0xbeb78000,0x3eb7,
0xbeae3de2,0x3e573e94,0x3e57be94,0xbeaebde2,0x3de23eae,0x3e94be57,0xbe94be57,0xbde23eae,0xbe57be94,0xbde23eae,0x3eaebde2,0xbe94be57,0xbe943e57,0x3eae3de2,0xbde2beae,0xbe573e94,
0,0,0,0,0,0,0,0,0,0,0,0,0,0,0,0,
0,0,0,0,0,0,0,0,0,0,0,0,0,0,0,0,
0x3e57be94,0xbeae3de2,0x3eae3de2,0xbe57be94,0xbe94be57,0x3de23eae,0x3de2beae,0xbe943e57,0x3eae3de2,0xbe94be57,0x3e573e94,0xbde2beae,0x3de2beae,0xbe573e94,0x3e94be57,0xbeae3de2,
0x3eb7,0xbeb7,0x3eb7,0xbeb7,0x3eb78000,0xbeb78000,0x3eb78000,0xbeb78000,0xbeae3de2,0x3e94be57,0xbe573e94,0x3de2beae,0x3de23eae,0xbe57be94,0x3e943e57,0xbeaebde2,
0,0,0,0,0,0,0,0,0,0,0,0,0,0,0,0,
0,0,0,0,0,0,0,0,0,0,0,0,0,0,0,0,
0xbe57be94,0x3eae3de2,0xbeae3de2,0x3e57be94,0xbe943e57,0x3de2beae,0x3de23eae,0xbe94be57,0x3e57be94,0x3de23eae,0xbeaebde2,0x3e94be57,0xbe94be57,0x3eaebde2,0xbde23eae,0xbe57be94,
0x3eae3de2,0xbe573e94,0xbe57be94,0x3eaebde2,0x3de2beae,0x3e943e57,0xbe943e57,0xbde2beae,0x3eb7,0xbeb70000,0xbeb7,0x3eb70000,0x3eb78000,0x3eb7,0xbeb78000,0xbeb7,
0,0,0,0,0,0,0,0,0,0,0,0,0,0,0,0,
0,0,0,0,0,0,0,0,0,0,0,0,0,0,0,0,
0xbeae3de2,0xbe57be94,0x3e57be94,0x3eae3de2,0x3de23eae,0xbe943e57,0xbe94be57,0x3de2beae,0xbe57be94,0x3de2beae,0x3eaebde2,0x3e943e57,0xbe943e57,0xbeaebde2,0xbde2beae,0x3e57be94,
0x3e57be94,0x3eaebde2,0x3eae3de2,0x3e573e94,0xbe94be57,0xbde2beae,0x3de2beae,0x3e94be57,0x3eae3de2,0x3e943e57,0x3e573e94,0x3de23eae,0x3de2beae,0x3e57be94,0x3e94be57,0x3eaebde2,
};
__device__ __align__(128) const uint32_t TAB_P3[4288] = {
0,0,0,0,0,0,0,0,0,0,0,0,0,0,0,0,
0x80003e83,0xbe79bda2,0x3e1abe54,0x3e1a3e54,0x3e830000,0xbda23e79,0xbe54be1a,0x3e54be1a,0x80003e83,0xbe54be1a,0x3e79bda2,0xbda23e79,0x3e830000,0xbe1a3e54,0xbda2be79,0x3e793da2,
0,0,0,0,0,0,0,0,0,0,0,0,0,0,0,0,
0xbe793da2,0x8000be83,0x3e793da2,0xbe1a3e54,0x3da23e79,0xbe830000,0x3da2be79,0x3e543e1a,0xbe1abe54,0x3e830000,0xbe1a3e54,0xbda2be79,0xbe543e1a,0xbe83,0x3e543e1a,0xbe793da2,
0x80003e83,0xbe1abe54,0x3e793da2,0xbe793da2,0x3e830000,0xbe543e1a,0x3da2be79,0x3da23e79,0x80003e83,0xbda2be79,0x3e1a3e54,0xbe54be1a,0x3e830000,0xbe793da2,0x3e54be1a,0xbe1a3e54,
0x80003e83,0x8000be83,0x80003e83,0x8000be83,0x3e830000,0xbe830000,0x3e830000,0xbe830000,0x80003e83,0x3da2be79,0xbe1a3e54,0x3e54be1a,0x3e830000,0xbe79bda2,0x3e543e1a,0xbe1abe54,
0x3e1abe54,0x80003e83,0xbe1abe54,0x3e793da2,0xbe54be1a,0x3e830000,0xbe543e1a,0x3da2be79,0x3e793da2,0xbe830000,0x3e79bda2,0xbe543e1a,0x3da2be79,0x3e83,0xbda2be79,0x3e1a3e54,
0x80003e83,0x8000be83,0x80003e83,0x8000be83,0x3e830000,0xbe830000,0x3e830000,0xbe830000,0xbe793da2,0x3e830000,0xbe79bda2,0x3e543e1a,0x3da23e79,0xbe83,0xbda23e79,0x3e1abe54,
0x80003e83,0x3e1abe54,0xbe793da2,0x3e793da2,0x3e830000,0xbe54be1a,0x3da23e79,0x3da2be79,0x80003e83,0x3e54be1a,0xbe79bda2,0x3da23e79,0x3e830000,0xbe1abe54,0xbda23e79,0x3e79bda2,
0x80003e83,0x3e79bda2,0xbe1abe54,0xbe1a3e54,0x3e830000,0xbda2be79,0xbe543e1a,0x3e543e1a,0x80003e83,0x3e830000,0x8000be83,0xbe830000,0x3e830000,0xbe83,0xbe830000,0x3e83,
0xbe1abe54,0x80003e83,0x3e1abe54,0xbe793da2,0xbe543e1a,0x3e830000,0xbe54be1a,0x3da23e79,0x3e1abe54,0xbe830000,0x3e1a3e54,0x3da2be79,0xbe54be1a,0x3e83,0x3e54be1a,0xbe79bda2,
0x3e793da2,0x8000be83,0xbe793da2,0x3e1a3e54,0x3da2be79,0xbe830000,0x3da23e79,0x3e54be1a,0x80003e83,0x3e830000,0x8000be83,0xbe830000,0x3e830000,0xbe83,0xbe830000,0x3e83,
0x80003e83,0x3e793da2,0x3e1abe54,0xbe1abe54,0x3e830000,0x3da2be79,0xbe54be1a,0xbe543e1a,0x80003e83,0x3e543e1a,0x3e79bda2,0x3da2be79,0x3e830000,0x3e1abe54,0xbda2be79,0xbe79bda2,
0x80003e83,0x3e1a3e54,0x3e793da2,0x3e79bda2,0x3e830000,0x3e54be1a,0x3da2be79,0xbda2be79,0x80003e83,0x3da23e79,0x3e1a3e54,0x3e543e1a,0x3e830000,0x3e79bda2,0x3e54be1a,0x3e1abe54,
0xbe793da2,0x80003e83,0x3e793da2,0x3e1abe54,0x3da23e79,0x3e830000,0x3da2be79,0xbe54be1a,0xbe1abe54,0xbe830000,0xbe1a3e54,0x3da23e79,0xbe543e1a,0x3e83,0x3e543e1a,0x3e79bda2,
0x3e1abe54,0x8000be83,0xbe1abe54,0xbe79bda2,0xbe54be1a,0xbe830000,0xbe543e1a,0xbda23e79,0x3e793da2,0x3e830000,0x3e79bda2,0x3e54be1a,0x3da2be79,0xbe83,0xbda2be79,0xbe1abe54,
0,0,0,0,0,0,0,0,0,0,0,0,0,0,0,0,
0,0,0,0,0,0,0,0,0,0,0,0,0,0,0,0,
0,0,0,0,0,0,0,0,0,0,0,0,0,0,0,0,
0xbe1abe54,0x3e79bda2,0x80003e83,0xbe79bda2,0xbe543e1a,0xbda2be79,0x3e830000,0xbda23e79,0x3e793da2,0xbe543e1a,0x8000be83,0x3e543e1a,0x3da2be79,0x3e1a3e54,0xbe830000,0x3e1abe54,
0,0,0,0,0,0,0,0,0,0,0,0,0,0,0,0,
0,0,0,0,0,0,0,0,0,0,0,0,0,0,0,0,
0xbe793da2,0x3e1abe54,0x80003e83,0xbe1abe54,0x3da23e79,0xbe54be1a,0x3e830000,0xbe543e1a,0x3e1abe54,0xbda23e79,0x8000be83,0x3da23e79,0xbe54be1a,0x3e793da2,0xbe830000,0x3e79bda2,
0x80003e83,0x8000be83,0x80003e83,0x8000be83,0x3e830000,0xbe830000,0x3e830000,0xbe830000,0xbe1abe54,0x3da23e79,0x8000be83,0xbda23e79,0xbe543e1a,0x3e79bda2,0xbe830000,0x3e793da2,
0,0,0,0,0,0,0,0,0,0,0,0,0,0,0,0,
0,0,0,0,0,0,0,0,0,0,0,0,0,0,0,0,
0x3e793da2,0xbe1abe54,0x80003e83,0x3e1abe54,0x3da2be79,0xbe543e1a,0x3e830000,0xbe54be1a,0xbe793da2,0x3e543e1a,0x8000be83,0xbe543e1a,0x3da23e79,0x3e1abe54,0xbe830000,0x3e1a3e54,
0x3e1abe54,0xbe79bda2,0x80003e83,0x3e79bda2,0xbe54be1a,0xbda23e79,0x3e830000,0xbda2be79,0x80003e83,0x3e830000,0x8000be83,0xbe830000,0x3e830000,0xbe83,0xbe830000,0x3e83,
0,0,0,0,0,0,0,0,0,0,0,0,0,0,0,0,
0,0,0,0,0,0,0,0,0,0,0,0,0,0,0,0,
0xbe1abe54,0xbe793da2,0x80003e83,0x3e793da2,0xbe543e1a,0x3da23e79,0x3e830000,0x3da2be79,0x3e793da2,0x3e54be1a,0x8000be83,0xbe54be1a,0x3da2be79,0xbe1abe54,0xbe830000,0xbe1a3e54,
0xbe793da2,0xbe1a3e54,0x80003e83,0x3e1a3e54,0x3da23e79,0x3e543e1a,0x3e830000,0x3e54be1a,0x3e1abe54,0x3da2be79,0x8000be83,0xbda2be79,0xbe54be1a,0xbe79bda2,0xbe830000,0xbe793da2,
0,0,0,0,0,0,0,0,0,0,0,0,0,0,0,0,
0x3e1abe54,0x3e1a3e54,0xbe793da2,0x8000be83,0xbe54be1a,0x3e54be1a,0x3da23e79,0xbe830000,0xbe793da2,0x3da2be79,0x3e1a3e54,0xbe830000,0x3da23e79,0xbe79bda2,0x3e54be1a,0x3e83,
0,0,0,0,0,0,0,0,0,0,0,0,0,0,0,0,
0x3e793da2,0xbe1a3e54,0xbe1abe54,0x3e79bda2,0x3da2be79,0x3e543e1a,0xbe543e1a,0xbda2be79,0x3e1abe54,0x3da23e79,0xbe79bda2,0x3e54be1a,0xbe54be1a,0x3e79bda2,0xbda23e79,0xbe1abe54,
0x3e793da2,0xbe793da2,0x3e1abe54,0x80003e83,0x3da2be79,0x3da23e79,0xbe54be1a,0x3e830000,0xbe1abe54,0x3e543e1a,0xbe79bda2,0x3e830000,0xbe543e1a,0x3e1abe54,0xbda23e79,0xbe83,
0x80003e83,0x8000be83,0x80003e83,0x8000be83,0x3e830000,0xbe830000,0x3e830000,0xbe830000,0x3e1abe54,0xbe543e1a,0x3e79bda2,0xbe830000,0xbe54be1a,0x3e1a3e54,0xbda2be79,0x3e83,
0xbe1abe54,0x3e793da2,0xbe793da2,0x3e1abe54,0xbe543e1a,0x3da2be79,0x3da23e79,0xbe54be1a,0xbe793da2,0x3e54be1a,0xbe1a3e54,0x3da2be79,0x3da23e79,0xbe1abe54,0x3e543e1a,0xbe79bda2,
0x80003e83,0x8000be83,0x80003e83,0x8000be83,0x3e830000,0xbe830000,0x3e830000,0xbe830000,0x3e793da2,0xbe54be1a,0x3e1a3e54,0xbda2be79,0x3da2be79,0xbe1a3e54,0x3e54be1a,0xbe793da2,
0xbe793da2,0x3e793da2,0xbe1abe54,0x80003e83,0x3da23e79,0x3da2be79,0xbe543e1a,0x3e830000,0x3e793da2,0xbda2be79,0xbe1a3e54,0x3e830000,0x3da2be79,0xbe793da2,0x3e543e1a,0xbe83,
0xbe1abe54,0xbe1a3e54,0x3e793da2,0x8000be83,0xbe543e1a,0x3e543e1a,0x3da2be79,0xbe830000,0x80003e83,0x3e830000,0x8000be83,0xbe830000,0x3e830000,0xbe83,0xbe830000,0x3e83,
0x3e1abe54,0xbe793da2,0x3e793da2,0xbe1abe54,0xbe54be1a,0x3da23e79,0x3da2be79,0xbe543e1a,0xbe1abe54,0xbda23e79,0x3e79bda2,0xbe54be1a,0xbe543e1a,0x3e793da2,0xbda2be79,0xbe1a3e54,
0xbe793da2,0x3e1a3e54,0x3e1abe54,0xbe79bda2,0x3da23e79,0x3e54be1a,0xbe54be1a,0xbda23e79,0x80003e83,0x3e830000,0x8000be83,0xbe830000,0x3e830000,0xbe83,0xbe830000,0x3e83,
0x3e1abe54,0xbe1abe54,0xbe793da2,0x80003e83,0xbe54be1a,0xbe543e1a,0x3da23e79,0x3e830000,0xbe793da2,0xbda23e79,0x3e1a3e54,0x3e830000,0x3da23e79,0x3e793da2,0x3e54be1a,0xbe83,
0x3e793da2,0x3e79bda2,0x3e1abe54,0x8000be83,0x3da2be79,0xbda2be79,0xbe54be1a,0xbe830000,0xbe1abe54,0xbe54be1a,0xbe79bda2,0xbe830000,0xbe543e1a,0xbe1a3e54,0xbda23e79,0x3e83,
0x3e793da2,0x3e1abe54,0xbe1abe54,0xbe793da2,0x3da2be79,0xbe54be1a,0xbe543e1a,0x3da23e79,0x3e1abe54,0xbda2be79,0xbe79bda2,0xbe543e1a,0xbe54be1a,0xbe793da2,0xbda23e79,0x3e1a3e54,
0xbe1abe54,0xbe79bda2,0xbe793da2,0xbe1a3e54,0xbe543e1a,0xbda23e79,0x3da23e79,0x3e543e1a,0xbe793da2,0xbe543e1a,0xbe1a3e54,0xbda23e79,0x3da23e79,0x3e1a3e54,0x3e543e1a,0x3e793da2,
0xbe163dda,0,0,0,0,0xbe163dda,0,0,0,0,0xbe163dda,0,0,0,0,0xbe163dda,
0xbe253da8,0,0,0,0,0xbe253da8,0,0,0,0,0xbe253da8,0,0,0,0,0xbe253da8,
0xbd65be30,0,0,0,0,0xbd65be30,0,0,0,0,0xbd65be30,0,0,0,0,0xbd65be30,
0x3ce8be37,0,0,0,0,0x3ce8be37,0,0,0,0,0x3ce8be37,0,0,0,0,0x3ce8be37,
0xbe303d65,0,0,0,0,0xbe303d65,0,0,0,0,0xbe303d65,0,0,0,0,0xbe303d65,
0xbe373ce8,0,0,0,0,0xbe373ce8,0,0,0,0,0xbe373ce8,0,0,0,0,0xbe373ce8,
0x3ddabe16,0,0,0,0,0x3ddabe16,0,0,0,0,0x3ddabe16,0,0,0,0,0x3ddabe16,
0x3e25bda8,0,0,0,0,0x3e25bda8,0,0,0,0,0x3e25bda8,0,0,0,0,0x3e25bda8,
0xbe390000,0,0,0,0,0xbe390000,0,0,0,0,0xbe390000,0,0,0,0,0xbe390000,
0xbe37bce8,0,0,0,0,0xbe37bce8,0,0,0,0,0xbe37bce8,0,0,0,0,0xbe37bce8,
0x3e390000,0,0,0,0,0x3e390000,0,0,0,0,0x3e390000,0,0,0,0,0x3e390000,
0x3e253da8,0,0,0,0,0x3e253da8,0,0,0,0,0x3e253da8,0,0,0,0,0x3e253da8,
0xbe30bd65,0,0,0,0,0xbe30bd65,0,0,0,0,0xbe30bd65,0,0,0,0,0xbe30bd65,
0xbe25bda8,0,0,0,0,0xbe25bda8,0,0,0,0,0xbe25bda8,0,0,0,0,0xbe25bda8,
0x3dda3e16,0,0,0,0,0x3dda3e16,0,0,0,0,0x3dda3e16,0,0,0,0,0x3dda3e16,
0x3ce83e37,0,0,0,0,0x3ce83e37,0,0,0,0,0x3ce83e37,0,0,0,0,0x3ce83e37,
0xbe16bdda,0,0,0,0,0xbe16bdda,0,0,0,0,0xbe16bdda,0,0,0,0,0xbe16bdda,
0xbe03be03,0,0,0,0,0xbe03be03,0,0,0,0,0xbe03be03,0,0,0,0,0xbe03be03,
0xbd653e30,0,0,0,0,0xbd653e30,0,0,0,0,0xbd653e30,0,0,0,0,0xbd653e30,
0xbe033e03,0,0,0,0,0xbe033e03,0,0,0,0,0xbe033e03,0,0,0,0,0xbe033e03,
0xbddabe16,0,0,0,0,0xbddabe16,0,0,0,0,0xbddabe16,0,0,0,0,0xbddabe16,
0xbda8be25,0,0,0,0,0xbda8be25,0,0,0,0,0xbda8be25,0,0,0,0,0xbda8be25,
0xbe303d65,0,0,0,0,0xbe303d65,0,0,0,0,0xbe303d65,0,0,0,0,0xbe303d65,
0xbe37bce8,0,0,0,0,0xbe37bce8,0,0,0,0,0xbe37bce8,0,0,0,0,0xbe37bce8,
0xbd65be30,0,0,0,0,0xbd65be30,0,0,0,0,0xbd65be30,0,0,0,0,0xbd65be30,
0xbce8be37,0,0,0,0,0xbce8be37,0,0,0,0,0xbce8be37,0,0,0,0,0xbce8be37,
0xbe16bdda,0,0,0,0,0xbe16bdda,0,0,0,0,0xbe16bdda,0,0,0,0,0xbe16bdda,
0xbda8be25,0,0,0,0,0xbda8be25,0,0,0,0,0xbda8be25,0,0,0,0,0xbda8be25,
0x3e390000,0,0,0,0,0x3e390000,0,0,0,0,0x3e390000,0,0,0,0,0x3e390000,
0x3e033e03,0,0,0,0,0x3e033e03,0,0,0,0,0x3e033e03,0,0,0,0,0x3e033e03,
0xbd653e30,0,0,0,0,0xbd653e30,0,0,0,0,0xbd653e30,0,0,0,0,0xbd653e30,
0xbe373ce8,0,0,0,0,0xbe373ce8,0,0,0,0,0xbe373ce8,0,0,0,0,0xbe373ce8,
0x80003e39,0,0,0,0,0x80003e39,0,0,0,0,0x80003e39,0,0,0,0,0x80003e39,
0xbe033e03,0,0,0,0,0xbe033e03,0,0,0,0,0xbe033e03,0,0,0,0,0xbe033e03,
0xbddabe16,0,0,0,0,0xbddabe16,0,0,0,0,0xbddabe16,0,0,0,0,0xbddabe16,
0x3da8be25,0,0,0,0,0x3da8be25,0,0,0,0,0x3da8be25,0,0,0,0,0x3da8be25,
0xbe390000,0,0,0,0,0xbe390000,0,0,0,0,0xbe390000,0,0,0,0,0xbe390000,
0xbe03be03,0,0,0,0,0xbe03be03,0,0,0,0,0xbe03be03,0,0,0,0,0xbe03be03,
0x3e390000,0,0,0,0,0x3e390000,0,0,0,0,0x3e390000,0,0,0,0,0x3e390000,
0x3da83e25,0,0,0,0,0x3da83e25,0,0,0,0,0x3da83e25,0,0,0,0,0x3da83e25,
0x8000be39,0,0,0,0,0x8000be39,0,0,0,0,0x8000be39,0,0,0,0,0x8000be39,
0x3e03be03,0,0,0,0,0x3e03be03,0,0,0,0,0x3e03be03,0,0,0,0,0x3e03be03,
0xbdda3e16,0,0,0,0,0xbdda3e16,0,0,0,0,0xbdda3e16,0,0,0,0,0xbdda3e16,
0xbe37bce8,0,0,0,0,0xbe37bce8,0,0,0,0,0xbe37bce8,0,0,0,0,0xbe37bce8,
0x3e390000,0,0,0,0,0x3e390000,0,0,0,0,0x3e390000,0,0,0,0,0x3e390000,
0x3e033e03,0,0,0,0,0x3e033e03,0,0,0,0,0x3e033e03,0,0,0,0,0x3e033e03,
0xbd65be30,0,0,0,0,0xbd65be30,0,0,0,0,0xbd65be30,0,0,0,0,0xbd65be30,
0x3e03be03,0,0,0,0,0x3e03be03,0,0,0,0,0x3e03be03,0,0,0,0,0x3e03be03,
0x80003e39,0,0,0,0,0x80003e39,0,0,0,0,0x80003e39,0,0,0,0,0x80003e39,
0xbe033e03,0,0,0,0,0xbe033e03,0,0,0,0,0xbe033e03,0,0,0,0,0xbe033e03,
0x3e303d65,0,0,0,0,0x3e303d65,0,0,0,0,0x3e303d65,0,0,0,0,0x3e303d65,
0x3ce83e37,0,0,0,0,0x3ce83e37,0,0,0,0,0x3ce83e37,0,0,0,0,0x3ce83e37,
0xbe390000,0,0,0,0,0xbe390000,0,0,0,0,0xbe390000,0,0,0,0,0xbe390000,
0xbe03be03,0,0,0,0,0xbe03be03,0,0,0,0,0xbe03be03,0,0,0,0,0xbe03be03,
0xbe163dda,0,0,0,0,0xbe163dda,0,0,0,0,0xbe163dda,0,0,0,0,0xbe163dda,
0xbe25bda8,0,0,0,0,0xbe25bda8,0,0,0,0,0xbe25bda8,0,0,0,0,0xbe25bda8,
0xbe16bdda,0,0,0,0,0xbe16bdda,0,0,0,0,0xbe16bdda,0,0,0,0,0xbe16bdda,
0x3da8be25,0,0,0,0,0x3da8be25,0,0,0,0,0x3da8be25,0,0,0,0,0x3da8be25,
0x3e16bdda,0,0,0,0,0x3e16bdda,0,0,0,0,0x3e16bdda,0,0,0,0,0x3e16bdda,
0x3da83e25,0,0,0,0,0x3da83e25,0,0,0,0,0x3da83e25,0,0,0,0,0x3da83e25,
0x3e303d65,0,0,0,0,0x3e303d65,0,0,0,0,0x3e303d65,0,0,0,0,0x3e303d65,
0xbce83e37,0,0,0,0,0xbce83e37,0,0,0,0,0xbce83e37,0,0,0,0,0xbce83e37,
0xbe303d65,0,0,0,0,0xbe303d65,0,0,0,0,0xbe303d65,0,0,0,0,0xbe303d65,
0xbce8be37,0,0,0,0,0xbce8be37,0,0,0,0,0xbce8be37,0,0,0,0,0xbce8be37,
0xbe390000,0,0,0,0,0xbe390000,0,0,0,0,0xbe390000,0,0,0,0,0xbe390000,
0xbce8be37,0,0,0,0,0xbce8be37,0,0,0,0,0xbce8be37,0,0,0,0,0xbce8be37,
0x3e390000,0,0,0,0,0x3e390000,0,0,0,0,0x3e390000,0,0,0,0,0x3e390000,
0xbce83e37,0,0,0,0,0xbce83e37,0,0,0,0,0xbce83e37,0,0,0,0,0xbce83e37,
0x3e30bd65,0,0,0,0,0x3e30bd65,0,0,0,0,0x3e30bd65,0,0,0,0,0x3e30bd65,
0x3da83e25,0,0,0,0,0x3da83e25,0,0,0,0,0x3da83e25,0,0,0,0,0x3da83e25,
0xbe30bd65,0,0,0,0,0xbe30bd65,0,0,0,0,0xbe30bd65,0,0,0,0,0xbe30bd65,
0x3da8be25,0,0,0,0,0x3da8be25,0,0,0,0,0x3da8be25,0,0,0,0,0x3da8be25,
0xbe163dda,0,0,0,0,0xbe163dda,0,0,0,0,0xbe163dda,0,0,0,0,0xbe163dda,
0xbe03be03,0,0,0,0,0xbe03be03,0,0,0,0,0xbe03be03,0,0,0,0,0xbe03be03,
0x3e163dda,0,0,0,0,0x3e163dda,0,0,0,0,0x3e163dda,0,0,0,0,0x3e163dda,
0xbe033e03,0,0,0,0,0xbe033e03,0,0,0,0,0xbe033e03,0,0,0,0,0xbe033e03,
0x3ddabe16,0,0,0,0,0x3ddabe16,0,0,0,0,0x3ddabe16,0,0,0,0,0x3ddabe16,
0x3e253da8,0,0,0,0,0x3e253da8,0,0,0,0,0x3e253da8,0,0,0,0,0x3e253da8,
0xbddabe16,0,0,0,0,0xbddabe16,0,0,0,0,0xbddabe16,0,0,0,0,0xbddabe16,
0x3e25bda8,0,0,0,0,0x3e25bda8,0,0,0,0,0x3e25bda8,0,0,0,0,0x3e25bda8,
0xbd653e30,0,0,0,0,0xbd653e30,0,0,0,0,0xbd653e30,0,0,0,0,0xbd653e30,
0xbe37bce8,0,0,0,0,0xbe37bce8,0,0,0,0,0xbe37bce8,0,0,0,0,0xbe37bce8,
0x3d653e30,0,0,0,0,0x3d653e30,0,0,0,0,0x3d653e30,0,0,0,0,0x3d653e30,
0xbe373ce8,0,0,0,0,0xbe373ce8,0,0,0,0,0xbe373ce8,0,0,0,0,0xbe373ce8,
0x3d653e30,0,0,0,0,0x3d653e30,0,0,0,0,0x3d653e30,0,0,0,0,0x3d653e30,
0xbe37bce8,0,0,0,0,0xbe37bce8,0,0,0,0,0xbe37bce8,0,0,0,0,0xbe37bce8,
0xbe390000,0,0,0,0,0xbe390000,0,0,0,0,0xbe390000,0,0,0,0,0xbe390000,
0x3e03be03,0,0,0,0,0x3e03be03,0,0,0,0,0x3e03be03,0,0,0,0,0x3e03be03,
0x3ddabe16,0,0,0,0,0x3ddabe16,0,0,0,0,0x3ddabe16,0,0,0,0,0x3ddabe16,
0x3da83e25,0,0,0,0,0x3da83e25,0,0,0,0,0x3da83e25,0,0,0,0,0x3da83e25,
0x80003e39,0,0,0,0,0x80003e39,0,0,0,0,0x80003e39,0,0,0,0,0x80003e39,
0xbe03be03,0,0,0,0,0xbe03be03,0,0,0,0,0xbe03be03,0,0,0,0,0xbe03be03,
0xbe390000,0,0,0,0,0xbe390000,0,0,0,0,0xbe390000,0,0,0,0,0xbe390000,
0x3da8be25,0,0,0,0,0x3da8be25,0,0,0,0,0x3da8be25,0,0,0,0,0x3da8be25,
0x3e390000,0,0,0,0,0x3e390000,0,0,0,0,0x3e390000,0,0,0,0,0x3e390000,
0xbe033e03,0,0,0,0,0xbe033e03,0,0,0,0,0xbe033e03,0,0,0,0,0xbe033e03,
0x3dda3e16,0,0,0,0,0x3dda3e16,0,0,0,0,0x3dda3e16,0,0,0,0,0x3dda3e16,
0xbe373ce8,0,0,0,0,0xbe373ce8,0,0,0,0,0xbe373ce8,0,0,0,0,0xbe373ce8,
0x8000be39,0,0,0,0,0x8000be39,0,0,0,0,0x8000be39,0,0,0,0,0x8000be39,
0x3e033e03,0,0,0,0,0x3e033e03,0,0,0,0,0x3e033e03,0,0,0,0,0x3e033e03,
0x3d65be30,0,0,0,0,0x3d65be30,0,0,0,0,0x3d65be30,0,0,0,0,0x3d65be30,
0x3e033e03,0,0,0,0,0x3e033e03,0,0,0,0,0x3e033e03,0,0,0,0,0x3e033e03,
0xbe390000,0,0,0,0,0xbe390000,0,0,0,0,0xbe390000,0,0,0,0,0xbe390000,
0x3e03be03,0,0,0,0,0x3e03be03,0,0,0,0,0x3e03be03,0,0,0,0,0x3e03be03,
0xbe303d65,0,0,0,0,0xbe303d65,0,0,0,0,0xbe303d65,0,0,0,0,0xbe303d65,
0x3ce8be37,0,0,0,0,0x3ce8be37,0,0,0,0,0x3ce8be37,0,0,0,0,0x3ce8be37,
0x80003e39,0,0,0,0,0x80003e39,0,0,0,0,0x80003e39,0,0,0,0,0x80003e39,
0xbe03be03,0,0,0,0,0xbe03be03,0,0,0,0,0xbe03be03,0,0,0,0,0xbe03be03,
0x3e163dda,0,0,0,0,0x3e163dda,0,0,0,0,0x3e163dda,0,0,0,0,0x3e163dda,
0xbe253da8,0,0,0,0,0xbe253da8,0,0,0,0,0xbe253da8,0,0,0,0,0xbe253da8,
0x3e390000,0,0,0,0,0x3e390000,0,0,0,0,0x3e390000,0,0,0,0,0x3e390000,
0xbe033e03,0,0,0,0,0xbe033e03,0,0,0,0,0xbe033e03,0,0,0,0,0xbe033e03,
0x3d65be30,0,0,0,0,0x3d65be30,0,0,0,0,0x3d65be30,0,0,0,0,0x3d65be30,
0x3ce83e37,0,0,0,0,0x3ce83e37,0,0,0,0,0x3ce83e37,0,0,0,0,0x3ce83e37,
0x3e163dda,0,0,0,0,0x3e163dda,0,0,0,0,0x3e163dda,0,0,0,0,0x3e163dda,
0xbe25bda8,0,0,0,0,0xbe25bda8,0,0,0,0,0xbe25bda8,0,0,0,0,0xbe25bda8,
0xbddabe16,0,0,0,0,0xbddabe16,0,0,0,0,0xbddabe16,0,0,0,0,0xbddabe16,
0x3e253da8,0,0,0,0,0x3e253da8,0,0,0,0,0x3e253da8,0,0,0,0,0x3e253da8,
0x3e303d65,0,0,0,0,0x3e303d65,0,0,0,0,0x3e303d65,0,0,0,0,0x3e303d65,
0xbe37bce8,0,0,0,0,0xbe37bce8,0,0,0,0,0xbe37bce8,0,0,0,0,0xbe37bce8,
0xbe390000,0,0,0,0,0xbe390000,0,0,0,0,0xbe390000,0,0,0,0,0xbe390000,
0x3e25bda8,0,0,0,0,0x3e25bda8,0,0,0,0,0x3e25bda8,0,0,0,0,0x3e25bda8,
0x3e390000,0,0,0,0,0x3e390000,0,0,0,0,0x3e390000,0,0,0,0,0x3e390000,
0xbe373ce8,0,0,0,0,0xbe373ce8,0,0,0,0,0xbe373ce8,0,0,0,0,0xbe373ce8,
0xbdda3e16,0,0,0,0,0xbdda3e16,0,0,0,0,0xbdda3e16,0,0,0,0,0xbdda3e16,
0x3ce8be37,0,0,0,0,0x3ce8be37,0,0,0,0,0x3ce8be37,0,0,0,0,0x3ce8be37,
0x3e30bd65,0,0,0,0,0x3e30bd65,0,0,0,0,0x3e30bd65,0,0,0,0,0x3e30bd65,
0xbe253da8,0,0,0,0,0xbe253da8,0,0,0,0,0xbe253da8,0,0,0,0,0xbe253da8,
0x3d653e30,0,0,0,0,0x3d653e30,0,0,0,0,0x3d653e30,0,0,0,0,0x3d653e30,
0xbe03be03,0,0,0,0,0xbe03be03,0,0,0,0,0xbe03be03,0,0,0,0,0xbe03be03,
0x3e16bdda,0,0,0,0,0x3e16bdda,0,0,0,0,0x3e16bdda,0,0,0,0,0x3e16bdda,
0xbe033e03,0,0,0,0,0xbe033e03,0,0,0,0,0xbe033e03,0,0,0,0,0xbe033e03,
0x3e303d65,0,0,0,0,0x3e303d65,0,0,0,0,0x3e303d65,0,0,0,0,0x3e303d65,
0xbe373ce8,0,0,0,0,0xbe373ce8,0,0,0,0,0xbe373ce8,0,0,0,0,0xbe373ce8,
0x3ddabe16,0,0,0,0,0x3ddabe16,0,0,0,0,0x3ddabe16,0,0,0,0,0x3ddabe16,
0xbda83e25,0,0,0,0,0xbda83e25,0,0,0,0,0xbda83e25,0,0,0,0,0xbda83e25,
0x3e16bdda,0,0,0,0,0x3e16bdda,0,0,0,0,0x3e16bdda,0,0,0,0,0x3e16bdda,
0xbda83e25,0,0,0,0,0xbda83e25,0,0,0,0,0xbda83e25,0,0,0,0,0xbda83e25,
0x3d65be30,0,0,0,0,0x3d65be30,0,0,0,0,0x3d65be30,0,0,0,0,0x3d65be30,
0xbce83e37,0,0,0,0,0xbce83e37,0,0,0,0,0xbce83e37,0,0,0,0,0xbce83e37,
0,0,0xbe163dda,0,0,0,0,0xbe163dda,0,0,0xbe253da8,0,0,0,0,0xbe253da8,
0,0,0xbe303d65,0,0,0,0,0xbe303d65,0,0,0xbe373ce8,0,0,0,0,0xbe373ce8,
0,0,0xbd65be30,0,0,0,0,0xbd65be30,0,0,0x3ce8be37,0,0,0,0,0x3ce8be37,
0,0,0x3ddabe16,0,0,0,0,0x3ddabe16,0,0,0x3e25bda8,0,0,0,0,0x3e25bda8,
0,0,0xbe390000,0,0,0,0,0xbe390000,0,0,0xbe37bce8,0,0,0,0,0xbe37bce8,
0,0,0xbe30bd65,0,0,0,0,0xbe30bd65,0,0,0xbe25bda8,0,0,0,0,0xbe25bda8,
0,0,0x3e390000,0,0,0,0,0x3e390000,0,0,0x3e253da8,0,0,0,0,0x3e253da8,
0,0,0x3dda3e16,0,0,0,0,0x3dda3e16,0,0,0x3ce83e37,0,0,0,0,0x3ce83e37,
0,0,0xbe16bdda,0,0,0,0,0xbe16bdda,0,0,0xbe03be03,0,0,0,0,0xbe03be03,
0,0,0xbddabe16,0,0,0,0,0xbddabe16,0,0,0xbda8be25,0,0,0,0,0xbda8be25,
0,0,0xbd653e30,0,0,0,0,0xbd653e30,0,0,0xbe033e03,0,0,0,0,0xbe033e03,
0,0,0xbe303d65,0,0,0,0,0xbe303d65,0,0,0xbe37bce8,0,0,0,0,0xbe37bce8,
0,0,0xbd65be30,0,0,0,0,0xbd65be30,0,0,0xbce8be37,0,0,0,0,0xbce8be37,
0,0,0,0,0,0,0,0,0,0,0,0,0,0,0,0,
0,0,0xbe16bdda,0,0,0,0,0xbe16bdda,0,0,0xbda8be25,0,0,0,0,0xbda8be25,
0,0,0,0,0,0,0,0,0,0,0,0,0,0,0,0,
0,0,0x3e390000,0,0,0,0,0x3e390000,0,0,0x3e033e03,0,0,0,0,0x3e033e03,
0,0,0x80003e39,0,0,0,0,0x80003e39,0,0,0xbe033e03,0,0,0,0,0xbe033e03,
0,0,0xbd653e30,0,0,0,0,0xbd653e30,0,0,0xbe373ce8,0,0,0,0,0xbe373ce8,
0,0,0xbddabe16,0,0,0,0,0xbddabe16,0,0,0x3da8be25,0,0,0,0,0x3da8be25,
0,0,0xbe390000,0,0,0,0,0xbe390000,0,0,0xbe03be03,0,0,0,0,0xbe03be03,
0,0,0x8000be39,0,0,0,0,0x8000be39,0,0,0x3e03be03,0,0,0,0,0x3e03be03,
0,0,0x3e390000,0,0,0,0,0x3e390000,0,0,0x3da83e25,0,0,0,0,0x3da83e25,
0,0,0xbdda3e16,0,0,0,0,0xbdda3e16,0,0,0xbe37bce8,0,0,0,0,0xbe37bce8,
0,0,0x3e390000,0,0,0,0,0x3e390000,0,0,0x3e033e03,0,0,0,0,0x3e033e03,
0,0,0x80003e39,0,0,0,0,0x80003e39,0,0,0xbe033e03,0,0,0,0,0xbe033e03,
0,0,0xbd65be30,0,0,0,0,0xbd65be30,0,0,0x3e03be03,0,0,0,0,0x3e03be03,
0,0,0x3e303d65,0,0,0,0,0x3e303d65,0,0,0x3ce83e37,0,0,0,0,0x3ce83e37,
0,0,0xbe390000,0,0,0,0,0xbe390000,0,0,0xbe03be03,0,0,0,0,0xbe03be03,
0,0,0,0,0,0,0,0,0,0,0,0,0,0,0,0,
0,0,0xbe163dda,0,0,0,0,0xbe163dda,0,0,0xbe25bda8,0,0,0,0,0xbe25bda8,
0,0,0,0,0,0,0,0,0,0,0,0,0,0,0,0,
0,0,0xbe16bdda,0,0,0,0,0xbe16bdda,0,0,0x3da8be25,0,0,0,0,0x3da8be25,
0,0,0x3e303d65,0,0,0,0,0x3e303d65,0,0,0xbce83e37,0,0,0,0,0xbce83e37,
0,0,0x3e16bdda,0,0,0,0,0x3e16bdda,0,0,0x3da83e25,0,0,0,0,0x3da83e25,
0,0,0xbe303d65,0,0,0,0,0xbe303d65,0,0,0xbce8be37,0,0,0,0,0xbce8be37,
0,0,0xbe390000,0,0,0,0,0xbe390000,0,0,0xbce8be37,0,0,0,0,0xbce8be37,
0,0,0x3e30bd65,0,0,0,0,0x3e30bd65,0,0,0x3da83e25,0,0,0,0,0x3da83e25,
0,0,0x3e390000,0,0,0,0,0x3e390000,0,0,0xbce83e37,0,0,0,0,0xbce83e37,
0,0,0xbe30bd65,0,0,0,0,0xbe30bd65,0,0,0x3da8be25,0,0,0,0,0x3da8be25,
0,0,0xbe163dda,0,0,0,0,0xbe163dda,0,0,0xbe03be03,0,0,0,0,0xbe03be03,
0,0,0x3ddabe16,0,0,0,0,0x3ddabe16,0,0,0x3e253da8,0,0,0,0,0x3e253da8,
0,0,0x3e163dda,0,0,0,0,0x3e163dda,0,0,0xbe033e03,0,0,0,0,0xbe033e03,
0,0,0xbddabe16,0,0,0,0,0xbddabe16,0,0,0x3e25bda8,0,0,0,0,0x3e25bda8,
0,0,0xbd653e30,0,0,0,0,0xbd653e30,0,0,0xbe37bce8,0,0,0,0,0xbe37bce8,
0,0,0,0,0,0,0,0,0,0,0,0,0,0,0,0,
0,0,0x3d653e30,0,0,0,0,0x3d653e30,0,0,0xbe373ce8,0,0,0,0,0xbe373ce8,
0,0,0,0,0,0,0,0,0,0,0,0,0,0,0,0,
0,0,0x3d653e30,0,0,0,0,0x3d653e30,0,0,0xbe37bce8,0,0,0,0,0xbe37bce8,
0,0,0x3ddabe16,0,0,0,0,0x3ddabe16,0,0,0x3da83e25,0,0,0,0,0x3da83e25,
0,0,0xbe390000,0,0,0,0,0xbe390000,0,0,0x3e03be03,0,0,0,0,0x3e03be03,
0,0,0x80003e39,0,0,0,0,0x80003e39,0,0,0xbe03be03,0,0,0,0,0xbe03be03,
0,0,0xbe390000,0,0,0,0,0xbe390000,0,0,0x3da8be25,0,0,0,0,0x3da8be25,
0,0,0x3dda3e16,0,0,0,0,0x3dda3e16,0,0,0xbe373ce8,0,0,0,0,0xbe373ce8,
0,0,0x3e390000,0,0,0,0,0x3e390000,0,0,0xbe033e03,0,0,0,0,0xbe033e03,
0,0,0x8000be39,0,0,0,0,0x8000be39,0,0,0x3e033e03,0,0,0,0,0x3e033e03,
0,0,0x3d65be30,0,0,0,0,0x3d65be30,0,0,0x3e033e03,0,0,0,0,0x3e033e03,
0,0,0xbe303d65,0,0,0,0,0xbe303d65,0,0,0x3ce8be37,0,0,0,0,0x3ce8be37,
0,0,0xbe390000,0,0,0,0,0xbe390000,0,0,0x3e03be03,0,0,0,0,0x3e03be03,
0,0,0x80003e39,0,0,0,0,0x80003e39,0,0,0xbe03be03,0,0,0,0,0xbe03be03,
0,0,0x3e163dda,0,0,0,0,0x3e163dda,0,0,0xbe253da8,0,0,0,0,0xbe253da8,
0,0,0,0,0,0,0,0,0,0,0,0,0,0,0,0,
0,0,0x3e390000,0,0,0,0,0x3e390000,0,0,0xbe033e03,0,0,0,0,0xbe033e03,
0,0,0,0,0,0,0,0,0,0,0,0,0,0,0,0,
0,0,0x3d65be30,0,0,0,0,0x3d65be30,0,0,0x3ce83e37,0,0,0,0,0x3ce83e37,
0,0,0xbddabe16,0,0,0,0,0xbddabe16,0,0,0x3e253da8,0,0,0,0,0x3e253da8,
0,0,0x3e163dda,0,0,0,0,0x3e163dda,0,0,0xbe25bda8,0,0,0,0,0xbe25bda8,
0,0,0x3e303d65,0,0,0,0,0x3e303d65,0,0,0xbe37bce8,0,0,0,0,0xbe37bce8,
0,0,0xbe390000,0,0,0,0,0xbe390000,0,0,0x3e25bda8,0,0,0,0,0x3e25bda8,
0,0,0xbdda3e16,0,0,0,0,0xbdda3e16,0,0,0x3ce8be37,0,0,0,0,0x3ce8be37,
0,0,0x3e390000,0,0,0,0,0x3e390000,0,0,0xbe373ce8,0,0,0,0,0xbe373ce8,
0,0,0x3e30bd65,0,0,0,0,0x3e30bd65,0,0,0xbe253da8,0,0,0,0,0xbe253da8,
0,0,0x3d653e30,0,0,0,0,0x3d653e30,0,0,0xbe03be03,0,0,0,0,0xbe03be03,
0,0,0x3e303d65,0,0,0,0,0x3e303d65,0,0,0xbe373ce8,0,0,0,0,0xbe373ce8,
0,0,0x3e16bdda,0,0,0,0,0x3e16bdda,0,0,0xbe033e03,0,0,0,0,0xbe033e03,
0,0,0x3ddabe16,0,0,0,0,0x3ddabe16,0,0,0xbda83e25,0,0,0,0,0xbda83e25,
0,0,0x3e16bdda,0,0,0,0,0x3e16bdda,0,0,0xbda83e25,0,0,0,0,0xbda83e25,
0,0,0,0,0,0,0,0,0,0,0,0,0,0,0,0,
0,0,0x3d65be30,0,0,0,0,0x3d65be30,0,0,0xbce83e37,0,0,0,0,0xbce83e37,
0,0,0,0,0,0,0,0,0,0,0,0,0,0,0,0,
};
constexpr unsigned long long COS_PK0 = 0x3f903f9a3fa03fa2ull;
constexpr unsigned long long COS_PK1 = 0x3f133f3e3f653f83ull;
constexpr unsigned long long COS_PK2 = 0x3e4b3ec8ull;

__device__ __forceinline__ void wgmma_ss_n80_z(float (&d)[40], uint64_t da, uint64_t db) {
  asm volatile("{\n.reg .pred p;\nsetp.ne.b32 p, 0, 0;\nwgmma.mma_async.sync.aligned.m64n80k16.f32.bf16.bf16 {%0,%1,%2,%3,%4,%5,%6,%7,%8,%9,%10,%11,%12,%13,%14,%15,%16,%17,%18,%19,%20,%21,%22,%23,%24,%25,%26,%27,%28,%29,%30,%31,%32,%33,%34,%35,%36,%37,%38,%39}, %40, %41, p, 1, 1, 1, 0;\n}\n"
    : "+f"(d[0]), "+f"(d[1]), "+f"(d[2]), "+f"(d[3]), "+f"(d[4]), "+f"(d[5]), "+f"(d[6]), "+f"(d[7]), "+f"(d[8]), "+f"(d[9]), "+f"(d[10]), "+f"(d[11]), "+f"(d[12]), "+f"(d[13]), "+f"(d[14]), "+f"(d[15]), "+f"(d[16]), "+f"(d[17]), "+f"(d[18]), "+f"(d[19]), "+f"(d[20]), "+f"(d[21]), "+f"(d[22]), "+f"(d[23]), "+f"(d[24]), "+f"(d[25]), "+f"(d[26]), "+f"(d[27]), "+f"(d[28]), "+f"(d[29]), "+f"(d[30]), "+f"(d[31]), "+f"(d[32]), "+f"(d[33]), "+f"(d[34]), "+f"(d[35]), "+f"(d[36]), "+f"(d[37]), "+f"(d[38]), "+f"(d[39])
    : "l"(da), "l"(db));
}
__device__ __forceinline__ void wgmma_ss_n80_a(float (&d)[40], uint64_t da, uint64_t db) {
  asm volatile("{\n.reg .pred p;\nsetp.ne.b32 p, 1, 0;\nwgmma.mma_async.sync.aligned.m64n80k16.f32.bf16.bf16 {%0,%1,%2,%3,%4,%5,%6,%7,%8,%9,%10,%11,%12,%13,%14,%15,%16,%17,%18,%19,%20,%21,%22,%23,%24,%25,%26,%27,%28,%29,%30,%31,%32,%33,%34,%35,%36,%37,%38,%39}, %40, %41, p, 1, 1, 1, 0;\n}\n"
    : "+f"(d[0]), "+f"(d[1]), "+f"(d[2]), "+f"(d[3]), "+f"(d[4]), "+f"(d[5]), "+f"(d[6]), "+f"(d[7]), "+f"(d[8]), "+f"(d[9]), "+f"(d[10]), "+f"(d[11]), "+f"(d[12]), "+f"(d[13]), "+f"(d[14]), "+f"(d[15]), "+f"(d[16]), "+f"(d[17]), "+f"(d[18]), "+f"(d[19]), "+f"(d[20]), "+f"(d[21]), "+f"(d[22]), "+f"(d[23]), "+f"(d[24]), "+f"(d[25]), "+f"(d[26]), "+f"(d[27]), "+f"(d[28]), "+f"(d[29]), "+f"(d[30]), "+f"(d[31]), "+f"(d[32]), "+f"(d[33]), "+f"(d[34]), "+f"(d[35]), "+f"(d[36]), "+f"(d[37]), "+f"(d[38]), "+f"(d[39])
    : "l"(da), "l"(db));
}

__device__ __forceinline__ void wgmma_rs_n40_z(float (&d)[20], uint32_t a0, uint32_t a1, uint32_t a2, uint32_t a3, uint64_t db) {
  asm volatile("{\n.reg .pred p;\nsetp.ne.b32 p, 0, 0;\nwgmma.mma_async.sync.aligned.m64n40k16.f32.bf16.bf16 {%0,%1,%2,%3,%4,%5,%6,%7,%8,%9,%10,%11,%12,%13,%14,%15,%16,%17,%18,%19}, {%20,%21,%22,%23}, %24, p, 1, 1, 0;\n}\n"
    : "+f"(d[0]), "+f"(d[1]), "+f"(d[2]), "+f"(d[3]), "+f"(d[4]), "+f"(d[5]), "+f"(d[6]), "+f"(d[7]), "+f"(d[8]), "+f"(d[9]), "+f"(d[10]), "+f"(d[11]), "+f"(d[12]), "+f"(d[13]), "+f"(d[14]), "+f"(d[15]), "+f"(d[16]), "+f"(d[17]), "+f"(d[18]), "+f"(d[19])
    : "r"(a0), "r"(a1), "r"(a2), "r"(a3), "l"(db));
}
__device__ __forceinline__ void wgmma_rs_n40_a(float (&d)[20], uint32_t a0, uint32_t a1, uint32_t a2, uint32_t a3, uint64_t db) {
  asm volatile("{\n.reg .pred p;\nsetp.ne.b32 p, 1, 0;\nwgmma.mma_async.sync.aligned.m64n40k16.f32.bf16.bf16 {%0,%1,%2,%3,%4,%5,%6,%7,%8,%9,%10,%11,%12,%13,%14,%15,%16,%17,%18,%19}, {%20,%21,%22,%23}, %24, p, 1, 1, 0;\n}\n"
    : "+f"(d[0]), "+f"(d[1]), "+f"(d[2]), "+f"(d[3]), "+f"(d[4]), "+f"(d[5]), "+f"(d[6]), "+f"(d[7]), "+f"(d[8]), "+f"(d[9]), "+f"(d[10]), "+f"(d[11]), "+f"(d[12]), "+f"(d[13]), "+f"(d[14]), "+f"(d[15]), "+f"(d[16]), "+f"(d[17]), "+f"(d[18]), "+f"(d[19])
    : "r"(a0), "r"(a1), "r"(a2), "r"(a3), "l"(db));
}

__device__ __forceinline__ void wgmma_rs_n128_z(float (&d)[64], uint32_t a0, uint32_t a1, uint32_t a2, uint32_t a3, uint64_t db) {
  asm volatile("{\n.reg .pred p;\nsetp.ne.b32 p, 0, 0;\nwgmma.mma_async.sync.aligned.m64n128k16.f32.bf16.bf16 {%0,%1,%2,%3,%4,%5,%6,%7,%8,%9,%10,%11,%12,%13,%14,%15,%16,%17,%18,%19,%20,%21,%22,%23,%24,%25,%26,%27,%28,%29,%30,%31,%32,%33,%34,%35,%36,%37,%38,%39,%40,%41,%42,%43,%44,%45,%46,%47,%48,%49,%50,%51,%52,%53,%54,%55,%56,%57,%58,%59,%60,%61,%62,%63}, {%64,%65,%66,%67}, %68, p, 1, 1, 1;\n}\n"
    : "+f"(d[0]), "+f"(d[1]), "+f"(d[2]), "+f"(d[3]), "+f"(d[4]), "+f"(d[5]), "+f"(d[6]), "+f"(d[7]), "+f"(d[8]), "+f"(d[9]), "+f"(d[10]), "+f"(d[11]), "+f"(d[12]), "+f"(d[13]), "+f"(d[14]), "+f"(d[15]), "+f"(d[16]), "+f"(d[17]), "+f"(d[18]), "+f"(d[19]), "+f"(d[20]), "+f"(d[21]), "+f"(d[22]), "+f"(d[23]), "+f"(d[24]), "+f"(d[25]), "+f"(d[26]), "+f"(d[27]), "+f"(d[28]), "+f"(d[29]), "+f"(d[30]), "+f"(d[31]), "+f"(d[32]), "+f"(d[33]), "+f"(d[34]), "+f"(d[35]), "+f"(d[36]), "+f"(d[37]), "+f"(d[38]), "+f"(d[39]), "+f"(d[40]), "+f"(d[41]), "+f"(d[42]), "+f"(d[43]), "+f"(d[44]), "+f"(d[45]), "+f"(d[46]), "+f"(d[47]), "+f"(d[48]), "+f"(d[49]), "+f"(d[50]), "+f"(d[51]), "+f"(d[52]), "+f"(d[53]), "+f"(d[54]), "+f"(d[55]), "+f"(d[56]), "+f"(d[57]), "+f"(d[58]), "+f"(d[59]), "+f"(d[60]), "+f"(d[61]), "+f"(d[62]), "+f"(d[63])
    : "r"(a0), "r"(a1), "r"(a2), "r"(a3), "l"(db));
}
__device__ __forceinline__ void wgmma_rs_n128_a(float (&d)[64], uint32_t a0, uint32_t a1, uint32_t a2, uint32_t a3, uint64_t db) {
  asm volatile("{\n.reg .pred p;\nsetp.ne.b32 p, 1, 0;\nwgmma.mma_async.sync.aligned.m64n128k16.f32.bf16.bf16 {%0,%1,%2,%3,%4,%5,%6,%7,%8,%9,%10,%11,%12,%13,%14,%15,%16,%17,%18,%19,%20,%21,%22,%23,%24,%25,%26,%27,%28,%29,%30,%31,%32,%33,%34,%35,%36,%37,%38,%39,%40,%41,%42,%43,%44,%45,%46,%47,%48,%49,%50,%51,%52,%53,%54,%55,%56,%57,%58,%59,%60,%61,%62,%63}, {%64,%65,%66,%67}, %68, p, 1, 1, 1;\n}\n"
    : "+f"(d[0]), "+f"(d[1]), "+f"(d[2]), "+f"(d[3]), "+f"(d[4]), "+f"(d[5]), "+f"(d[6]), "+f"(d[7]), "+f"(d[8]), "+f"(d[9]), "+f"(d[10]), "+f"(d[11]), "+f"(d[12]), "+f"(d[13]), "+f"(d[14]), "+f"(d[15]), "+f"(d[16]), "+f"(d[17]), "+f"(d[18]), "+f"(d[19]), "+f"(d[20]), "+f"(d[21]), "+f"(d[22]), "+f"(d[23]), "+f"(d[24]), "+f"(d[25]), "+f"(d[26]), "+f"(d[27]), "+f"(d[28]), "+f"(d[29]), "+f"(d[30]), "+f"(d[31]), "+f"(d[32]), "+f"(d[33]), "+f"(d[34]), "+f"(d[35]), "+f"(d[36]), "+f"(d[37]), "+f"(d[38]), "+f"(d[39]), "+f"(d[40]), "+f"(d[41]), "+f"(d[42]), "+f"(d[43]), "+f"(d[44]), "+f"(d[45]), "+f"(d[46]), "+f"(d[47]), "+f"(d[48]), "+f"(d[49]), "+f"(d[50]), "+f"(d[51]), "+f"(d[52]), "+f"(d[53]), "+f"(d[54]), "+f"(d[55]), "+f"(d[56]), "+f"(d[57]), "+f"(d[58]), "+f"(d[59]), "+f"(d[60]), "+f"(d[61]), "+f"(d[62]), "+f"(d[63])
    : "r"(a0), "r"(a1), "r"(a2), "r"(a3), "l"(db));
}

__device__ __forceinline__ void wgmma_rs_n32_z(float (&d)[16], uint32_t a0, uint32_t a1, uint32_t a2, uint32_t a3, uint64_t db) {
  asm volatile("{\n.reg .pred p;\nsetp.ne.b32 p, 0, 0;\nwgmma.mma_async.sync.aligned.m64n32k16.f32.bf16.bf16 {%0,%1,%2,%3,%4,%5,%6,%7,%8,%9,%10,%11,%12,%13,%14,%15}, {%16,%17,%18,%19}, %20, p, 1, 1, 0;\n}\n"
    : "+f"(d[0]), "+f"(d[1]), "+f"(d[2]), "+f"(d[3]), "+f"(d[4]), "+f"(d[5]), "+f"(d[6]), "+f"(d[7]), "+f"(d[8]), "+f"(d[9]), "+f"(d[10]), "+f"(d[11]), "+f"(d[12]), "+f"(d[13]), "+f"(d[14]), "+f"(d[15])
    : "r"(a0), "r"(a1), "r"(a2), "r"(a3), "l"(db));
}
__device__ __forceinline__ void wgmma_rs_n32_a(float (&d)[16], uint32_t a0, uint32_t a1, uint32_t a2, uint32_t a3, uint64_t db) {
  asm volatile("{\n.reg .pred p;\nsetp.ne.b32 p, 1, 0;\nwgmma.mma_async.sync.aligned.m64n32k16.f32.bf16.bf16 {%0,%1,%2,%3,%4,%5,%6,%7,%8,%9,%10,%11,%12,%13,%14,%15}, {%16,%17,%18,%19}, %20, p, 1, 1, 0;\n}\n"
    : "+f"(d[0]), "+f"(d[1]), "+f"(d[2]), "+f"(d[3]), "+f"(d[4]), "+f"(d[5]), "+f"(d[6]), "+f"(d[7]), "+f"(d[8]), "+f"(d[9]), "+f"(d[10]), "+f"(d[11]), "+f"(d[12]), "+f"(d[13]), "+f"(d[14]), "+f"(d[15])
    : "r"(a0), "r"(a1), "r"(a2), "r"(a3), "l"(db));
}

__device__ __forceinline__ void wgmma_rs_n64_z(float (&d)[32], uint32_t a0, uint32_t a1, uint32_t a2, uint32_t a3, uint64_t db) {
  asm volatile("{\n.reg .pred p;\nsetp.ne.b32 p, 0, 0;\nwgmma.mma_async.sync.aligned.m64n64k16.f32.bf16.bf16 {%0,%1,%2,%3,%4,%5,%6,%7,%8,%9,%10,%11,%12,%13,%14,%15,%16,%17,%18,%19,%20,%21,%22,%23,%24,%25,%26,%27,%28,%29,%30,%31}, {%32,%33,%34,%35}, %36, p, 1, 1, 0;\n}\n"
    : "+f"(d[0]), "+f"(d[1]), "+f"(d[2]), "+f"(d[3]), "+f"(d[4]), "+f"(d[5]), "+f"(d[6]), "+f"(d[7]), "+f"(d[8]), "+f"(d[9]), "+f"(d[10]), "+f"(d[11]), "+f"(d[12]), "+f"(d[13]), "+f"(d[14]), "+f"(d[15]), "+f"(d[16]), "+f"(d[17]), "+f"(d[18]), "+f"(d[19]), "+f"(d[20]), "+f"(d[21]), "+f"(d[22]), "+f"(d[23]), "+f"(d[24]), "+f"(d[25]), "+f"(d[26]), "+f"(d[27]), "+f"(d[28]), "+f"(d[29]), "+f"(d[30]), "+f"(d[31])
    : "r"(a0), "r"(a1), "r"(a2), "r"(a3), "l"(db));
}
__device__ __forceinline__ void wgmma_rs_n64_a(float (&d)[32], uint32_t a0, uint32_t a1, uint32_t a2, uint32_t a3, uint64_t db) {
  asm volatile("{\n.reg .pred p;\nsetp.ne.b32 p, 1, 0;\nwgmma.mma_async.sync.aligned.m64n64k16.f32.bf16.bf16 {%0,%1,%2,%3,%4,%5,%6,%7,%8,%9,%10,%11,%12,%13,%14,%15,%16,%17,%18,%19,%20,%21,%22,%23,%24,%25,%26,%27,%28,%29,%30,%31}, {%32,%33,%34,%35}, %36, p, 1, 1, 0;\n}\n"
    : "+f"(d[0]), "+f"(d[1]), "+f"(d[2]), "+f"(d[3]), "+f"(d[4]), "+f"(d[5]), "+f"(d[6]), "+f"(d[7]), "+f"(d[8]), "+f"(d[9]), "+f"(d[10]), "+f"(d[11]), "+f"(d[12]), "+f"(d[13]), "+f"(d[14]), "+f"(d[15]), "+f"(d[16]), "+f"(d[17]), "+f"(d[18]), "+f"(d[19]), "+f"(d[20]), "+f"(d[21]), "+f"(d[22]), "+f"(d[23]), "+f"(d[24]), "+f"(d[25]), "+f"(d[26]), "+f"(d[27]), "+f"(d[28]), "+f"(d[29]), "+f"(d[30]), "+f"(d[31])
    : "r"(a0), "r"(a1), "r"(a2), "r"(a3), "l"(db));
}

__device__ __forceinline__ void wgmma_ss_n32_z(float (&d)[16], uint64_t da, uint64_t db) {
  asm volatile("{\n.reg .pred p;\nsetp.ne.b32 p, 0, 0;\nwgmma.mma_async.sync.aligned.m64n32k16.f32.bf16.bf16 {%0,%1,%2,%3,%4,%5,%6,%7,%8,%9,%10,%11,%12,%13,%14,%15}, %16, %17, p, 1, 1, 1, 0;\n}\n"
    : "+f"(d[0]), "+f"(d[1]), "+f"(d[2]), "+f"(d[3]), "+f"(d[4]), "+f"(d[5]), "+f"(d[6]), "+f"(d[7]), "+f"(d[8]), "+f"(d[9]), "+f"(d[10]), "+f"(d[11]), "+f"(d[12]), "+f"(d[13]), "+f"(d[14]), "+f"(d[15])
    : "l"(da), "l"(db));
}
__device__ __forceinline__ void wgmma_ss_n32_a(float (&d)[16], uint64_t da, uint64_t db) {
  asm volatile("{\n.reg .pred p;\nsetp.ne.b32 p, 1, 0;\nwgmma.mma_async.sync.aligned.m64n32k16.f32.bf16.bf16 {%0,%1,%2,%3,%4,%5,%6,%7,%8,%9,%10,%11,%12,%13,%14,%15}, %16, %17, p, 1, 1, 1, 0;\n}\n"
    : "+f"(d[0]), "+f"(d[1]), "+f"(d[2]), "+f"(d[3]), "+f"(d[4]), "+f"(d[5]), "+f"(d[6]), "+f"(d[7]), "+f"(d[8]), "+f"(d[9]), "+f"(d[10]), "+f"(d[11]), "+f"(d[12]), "+f"(d[13]), "+f"(d[14]), "+f"(d[15])
    : "l"(da), "l"(db));
}

__device__ __forceinline__ void wgmma_ss_n40_z(float (&d)[20], uint64_t da, uint64_t db) {
  asm volatile("{\n.reg .pred p;\nsetp.ne.b32 p, 0, 0;\nwgmma.mma_async.sync.aligned.m64n40k16.f32.bf16.bf16 {%0,%1,%2,%3,%4,%5,%6,%7,%8,%9,%10,%11,%12,%13,%14,%15,%16,%17,%18,%19}, %20, %21, p, 1, 1, 1, 0;\n}\n"
    : "+f"(d[0]), "+f"(d[1]), "+f"(d[2]), "+f"(d[3]), "+f"(d[4]), "+f"(d[5]), "+f"(d[6]), "+f"(d[7]), "+f"(d[8]), "+f"(d[9]), "+f"(d[10]), "+f"(d[11]), "+f"(d[12]), "+f"(d[13]), "+f"(d[14]), "+f"(d[15]), "+f"(d[16]), "+f"(d[17]), "+f"(d[18]), "+f"(d[19])
    : "l"(da), "l"(db));
}
__device__ __forceinline__ void wgmma_ss_n40_a(float (&d)[20], uint64_t da, uint64_t db) {
  asm volatile("{\n.reg .pred p;\nsetp.ne.b32 p, 1, 0;\nwgmma.mma_async.sync.aligned.m64n40k16.f32.bf16.bf16 {%0,%1,%2,%3,%4,%5,%6,%7,%8,%9,%10,%11,%12,%13,%14,%15,%16,%17,%18,%19}, %20, %21, p, 1, 1, 1, 0;\n}\n"
    : "+f"(d[0]), "+f"(d[1]), "+f"(d[2]), "+f"(d[3]), "+f"(d[4]), "+f"(d[5]), "+f"(d[6]), "+f"(d[7]), "+f"(d[8]), "+f"(d[9]), "+f"(d[10]), "+f"(d[11]), "+f"(d[12]), "+f"(d[13]), "+f"(d[14]), "+f"(d[15]), "+f"(d[16]), "+f"(d[17]), "+f"(d[18]), "+f"(d[19])
    : "l"(da), "l"(db));
}

constexpr int NSM = 132, NH = 66;
constexpr int S0 = 0, S1 = 51200, S2 = 102400;
constexpr int C1 = 153600, C3 = C1, RG = C1 + 18432;
constexpr int WP = RG, TBL = RG + 28672, WS2 = RG + 30720;
constexpr int BARS = RG + 49152;
__host__ __device__ constexpr int wst_off(int i) { return i < 12 ? S2 + i * 4096 : WS2 + (i - 12) * 4096; }
constexpr int NBAR = 280;
constexpr int REL = BARS + NBAR * 8;
constexpr int SMEM_BYTES = REL + 16;
constexpr int B_XF = 0, B_CF1 = 15, B_CF3 = 16, B_WF = 17  , B_P1D = 18, B_REL = 21, B_ROLE = 22, B_SIG = 24;
constexpr int B_RF = 32, B_RE = 46, B_YF = 60, B_WRD = 75, B_SFREE = 89, B_WCH = 131, B_RDY = 136, B_WE = 205, B_WL = 217, B_FIN = 229, B_TOK = 232;
constexpr int R_P2 = 15, R_P3 = 57;
constexpr int CNT_P1 = 0, CNT_P2 = 4, CNT_W = 8, CNT_RANK = 9, NCLS = 10, CNT_DONE = 0, CNT_REL = 1, NCNT = 2;
constexpr int SIG_W = 0, SIG_P1 = 1, SIG_P2 = 4;
#define PFS 9088
#define T1MASK 0x3e00
#define T2MASK 0xf80

__device__ uint4 g_scr[(14 << 21) / 16];
__device__ __align__(128) uint4 g_wf[200 * 72 * 32];
__device__ __align__(128) unsigned g_cnt[NCNT * 32];
__device__ __forceinline__ int slot_line(int chunk, int pg, int cls) {
    return (pg & 1) << 6 | (pg >> 1) << 9 | (chunk & 1) << 10 | (chunk >> 1) << 12 | ((pg ^ (pg >> 1) ^ chunk ^ (chunk >> 1) ^ cls) & 1) << 5;
}
__device__ __forceinline__ int phi_line(int phi, uint32_t rel) {
    return (phi >> 4) << 14 | (phi & 3) << 7 | ((phi >> 2) & 1) << 11 | ((phi >> 3) & 1) << 13 | ((rel >> (phi >> 4)) & 1) << 5;
}
__device__ __forceinline__ int extra_mask(int rk) { return rk < 60 ? 0 : rk < 62 ? 1 : rk < 64 ? 10 : 4; }
__device__ __forceinline__ int wslot(int pc) {
    return (int)((0x576476503421ull >> (4 * pc)) & 3) * 12288 + (((0x576476503421ull >> (4 * pc)) & 4) ? S0 : RG);
}
__device__ __forceinline__ int xslot(int n) { return ((n & 4) ? S2 : RG) + ((n + 1) & 3) * 12288; }
__device__ __forceinline__ int extra_phi(int rk) { return 198 + (rk & 1); }
__host__ __device__ constexpr int quad_off(int Q) { return (Q >> 2) * 4096 + (Q & 3) * 512; }

struct Maps { CUtensorMap w, x34, x6, x28, wst, f16, f8, y4, y2; };
struct Ptrs { char* scr; const char* wf; const void* tab1; const void* tab3; unsigned* cnt; const char* x; };

__device__ __forceinline__ uint32_t smem_u32(const void* p) { return (uint32_t)__cvta_generic_to_shared(p); }
__device__ __forceinline__ void mbar_wait(uint32_t bar) {
    uint32_t ok, it = 0;
    do {
        asm volatile("{\n.reg .pred p;\nmbarrier.try_wait.parity.shared::cta.b64 p, [%1], 0;\nselp.u32 %0, 1, 0, p;\n}" : "=r"(ok) : "r"(bar) : "memory");
        if (++it > (1u << 22)) break;
    } while (!ok);
}
__device__ __forceinline__ bool mbar_test(uint32_t bar) {
    uint32_t ok;
    asm volatile("{\n.reg .pred p;\nmbarrier.test_wait.parity.shared::cta.b64 p, [%1], 0;\nselp.u32 %0, 1, 0, p;\n}" : "=r"(ok) : "r"(bar) : "memory");
    return ok;
}
__device__ __forceinline__ void fence_async() { asm volatile("fence.proxy.async;" ::: "memory"); }
__device__ __forceinline__ void fence_async_smem() { asm volatile("fence.proxy.async.shared::cta;" ::: "memory"); }
#define ELECT "{\n.reg .pred p;\nelect.sync _|p, 0xffffffff;\n@p "
__device__ __forceinline__ void e_arrive(uint32_t bar) { asm volatile(ELECT "mbarrier.arrive.shared::cta.b64 _, [%0];\n}" :: "r"(bar) : "memory"); }
__device__ __forceinline__ void e_expect(uint32_t bar, uint32_t bytes) { asm volatile(ELECT "mbarrier.arrive.expect_tx.shared::cta.b64 _, [%0], %1;\n}" :: "r"(bar), "r"(bytes) : "memory"); }
__device__ __forceinline__ void e_g2s(uint32_t dst, const void* src, uint32_t bytes, uint32_t bar) {
    asm volatile(ELECT "cp.async.bulk.shared::cluster.global.mbarrier::complete_tx::bytes [%0], [%1], %2, [%3];\n}" :: "r"(dst), "l"(src), "r"(bytes), "r"(bar) : "memory");
}
__device__ __forceinline__ void e_s2g(void* dst, uint32_t src, uint32_t bytes) {
    asm volatile(ELECT "cp.async.bulk.global.shared::cta.bulk_group [%0], [%1], %2;\n}" :: "l"(dst), "r"(src), "r"(bytes) : "memory");
}
__device__ __forceinline__ void e_ld3(uint32_t dst, const CUtensorMap* m, int c0, int c1, int c2, uint32_t bar) {
    asm volatile(ELECT "cp.async.bulk.tensor.3d.shared::cluster.global.mbarrier::complete_tx::bytes [%0], [%1, {%3, %4, %5}], [%2];\n}"
                 :: "r"(dst), "l"(m), "r"(bar), "r"(c0), "r"(c1), "r"(c2) : "memory");
}
__device__ __forceinline__ void e_ldw(uint32_t dst, const CUtensorMap* m, int c0, int c3, uint32_t bar) {
    asm volatile(ELECT "cp.async.bulk.tensor.5d.shared::cluster.global.mbarrier::complete_tx::bytes [%0], [%1, {%3, %5, %5, %4, %5}], [%2];\n}"
                 :: "r"(dst), "l"(m), "r"(bar), "r"(c0), "r"(c3), "r"(0) : "memory");
}
__device__ __forceinline__ void e_st3(const CUtensorMap* m, uint32_t src, int c0, int c1, int c2) {
    asm volatile(ELECT "cp.async.bulk.tensor.3d.global.shared::cta.bulk_group [%0, {%2, %3, %4}], [%1];\n}" :: "l"(m), "r"(src), "r"(c0), "r"(c1), "r"(c2) : "memory");
}
__device__ __forceinline__ void e_ld5(uint32_t dst, const CUtensorMap* m, int c4, uint32_t bar) {
    asm volatile(ELECT "cp.async.bulk.tensor.5d.shared::cluster.global.mbarrier::complete_tx::bytes [%0], [%1, {%4, %4, %4, %4, %3}], [%2];\n}"
                 :: "r"(dst), "l"(m), "r"(bar), "r"(c4), "r"(0) : "memory");
}
__device__ __forceinline__ void e_st5(const CUtensorMap* m, uint32_t src, int c4) {
    asm volatile(ELECT "cp.async.bulk.tensor.5d.global.shared::cta.bulk_group [%0, {%3, %3, %3, %3, %2}], [%1];\n}" :: "l"(m), "r"(src), "r"(c4), "r"(0) : "memory");
}
__device__ __forceinline__ void bulk_commit() { asm volatile("cp.async.bulk.commit_group;" ::: "memory"); }
template <int N> __device__ __forceinline__ void bulk_wait() { asm volatile("cp.async.bulk.wait_group %0;" :: "n"(N) : "memory"); }
template <int N> __device__ __forceinline__ void bulk_wait_read() { asm volatile("cp.async.bulk.wait_group.read %0;" :: "n"(N) : "memory"); }
__device__ __forceinline__ void wg_bar(int id) { asm volatile("bar.sync %0, 128;" :: "r"(id) : "memory"); }
__device__ __forceinline__ void bb_break(uint32_t v) { asm volatile("{\n.reg .pred p;\nsetp.eq.u32 p, %0, 0x7fc17fc1;\n@p nanosleep.u32 0;\n}" :: "r"(v) : "memory"); }
__device__ __forceinline__ uint32_t uni(uint32_t v) { return __shfl_sync(0xffffffffu, v, 0); }
__device__ __forceinline__ char* cls_cnt(char* scr, int cls) { return scr + slot_line(3, 2, cls) * 128; }
__device__ __forceinline__ uint32_t cnt_wait(const void* p, unsigned target) {
    uint32_t v = 0;
#pragma unroll 1
    for (unsigned it = 0; it < (1u << 22) && v < target; it++) {
        asm volatile("ld.acquire.gpu.global.u32 %0, [%1];" : "=r"(v) : "l"(p) : "memory");
        v = uni(v);
    }
    asm volatile("fence.proxy.async.global;" ::: "memory");
    return v;
}
__device__ __forceinline__ void wg_fence() { asm volatile("wgmma.fence.sync.aligned;" ::: "memory"); }
__device__ __forceinline__ void wg_commit() { asm volatile("wgmma.commit_group.sync.aligned;" ::: "memory"); }
template <int N> __device__ __forceinline__ void wg_wait() { asm volatile("wgmma.wait_group.sync.aligned %0;" :: "n"(N) : "memory"); }
template <int N> __device__ __forceinline__ void reg_fence(float (&d)[N]) {
#pragma unroll
    for (int i = 0; i < N; i++) asm volatile("" : "+f"(d[i]) :: "memory");
}
template <int N> __device__ __forceinline__ void zero(float (&d)[N]) {
#pragma unroll
    for (int i = 0; i < N; i++) d[i] = 0.f;
}
__device__ __forceinline__ uint32_t pack2(float lo, float hi) {
    uint32_t r; asm volatile("cvt.rn.bf16x2.f32 %0, %1, %2;" : "=r"(r) : "f"(hi), "f"(lo)); return r;
}
__device__ __forceinline__ void stm4(uint32_t a, uint32_t r0, uint32_t r1, uint32_t r2, uint32_t r3) {
    asm volatile("stmatrix.sync.aligned.m8n8.x4.trans.shared.b16 [%0], {%1,%2,%3,%4};" :: "r"(a), "r"(r0), "r"(r1), "r"(r2), "r"(r3) : "memory");
}
__device__ __forceinline__ void stm2(uint32_t a, uint32_t r0, uint32_t r1) {
    asm volatile("stmatrix.sync.aligned.m8n8.x2.trans.shared.b16 [%0], {%1,%2};" :: "r"(a), "r"(r0), "r"(r1) : "memory");
}
struct Desc {
    uint32_t lo, hi;
    __device__ __forceinline__ operator uint64_t() const { return ((uint64_t)hi << 32) | lo; }
    __device__ __forceinline__ Desc operator+(uint32_t o) const { return Desc{lo + o, hi}; }
    __device__ __forceinline__ Desc operator^(uint32_t o) const { return Desc{lo ^ o, hi}; }
};
__device__ __forceinline__ Desc mkdesc(uint32_t addr, uint32_t lbo, uint32_t sbo, uint32_t swz) {
    return Desc{((addr & 0x3FFFF) >> 4) | ((lbo >> 4) << 16), (sbo >> 4) | (swz << 30)};
}
__device__ __forceinline__ uint32_t cos_bits(int k) {
    if (k > 20) k = 40 - k;
    const bool neg = k > 10;
    if (neg) k = 20 - k;
    const unsigned long long pk = k < 4 ? COS_PK0 : k < 8 ? COS_PK1 : COS_PK2;
    return (uint32_t)((pk >> (16 * (k & 3))) & 0xffff) ^ (neg ? 0x8000u : 0u);
}

__device__ __forceinline__ void task_w(int wg, int k, uint32_t sb) {
    const int tid = threadIdx.x & 127, w = uni(tid >> 5), lane = tid & 31, q = lane & 3;
    const int tb = 14 * k, t1 = min(tb + 14, 1800), cb0 = tb / 25;
    float acc[64];
    zero(acc);
    const int oc0 = tb - 25 * cb0, Lt = t1 - tb, L0 = min(Lt, 25 - oc0), n0 = (L0 + 3) >> 2;
    uint32_t a[2][4][4];
    auto gen = [&](uint32_t (&a)[4][4], int at) {
        const int phi = 8 * ((at < n0 ? oc0 + 4 * at : 4 * (at - n0)) + w) + (lane >> 2), f = (phi * 205) >> 12;
        const uint32_t ca = 8 * f + 4, cw = (phi - 20 * f) * 8, p0 = sb + TBL + cw * 2 * q;
#pragma unroll
        for (int kh = 0; kh < 7; kh++) {
            uint32_t v0, v1;
            asm volatile("ld.shared.u32 %0, [%1];" : "=r"(v0) : "r"(p0 + ca * kh));
            asm volatile("ld.shared.u32 %0, [%1];" : "=r"(v1) : "r"(p0 + cw + ca * kh));
            const int h = kh == 6 ? 1 : kh & 1;
            a[kh >> 1][2 * h] = __byte_perm(v0, v1, 0x5410);
            a[kh >> 1][2 * h + 1] = __byte_perm(v0, v1, 0x7632);
        }
        a[3][0] = 0; a[3][1] = 0;
    };
    gen(a[0], wg);
    if (wg) gen(a[1], wg + 2);
#pragma unroll 1
    for (int n = 0; n < 2; n++) {
        const int at = wg + 2 * n, i0 = at < n0 ? 4 * at : L0 + 4 * (at - n0), cnt = (at < n0 ? L0 : Lt) - i0, cb = cb0 + (at >= n0);
        if (cnt <= 0 || (n && !wg)) break;
        if (n) {
#pragma unroll
            for (int j = 0; j < 16; j++) a[0][j >> 2][j & 3] = a[1][j >> 2][j & 3];
        }
        const Desc dB = mkdesc(sb + WP + (cb - cb0) * 14336, 3584, 512, 2);
        if (at) mbar_wait(sb + BARS + 8 * (B_WCH + at - 1));
        mbar_wait(sb + BARS + 8 * (B_WF + 2 * (cb - cb0)));
        wg_fence();
        wgmma_rs_n128_z(acc, a[0][0][0], a[0][0][1], a[0][0][2], a[0][0][3], dB);
        wgmma_rs_n128_a(acc, a[0][1][0], a[0][1][1], a[0][1][2], a[0][1][3], dB + (uint32_t)(16 * 64 >> 4));
        wgmma_rs_n128_a(acc, a[0][2][0], a[0][2][1], a[0][2][2], a[0][2][3], dB + (uint32_t)(32 * 64 >> 4));
        wgmma_rs_n128_a(acc, a[0][3][0], a[0][3][1], a[0][3][2], a[0][3][3], dB + (uint32_t)(40 * 64 >> 4));
        wg_commit();
        wg_wait<0>();
        reg_fence(acc);
        e_arrive(sb + BARS + 8 * (B_WCH + at));
        if (w < cnt) {
            const uint32_t dst = sb + wst_off(i0 + w) + (lane >> 2) * 512 + (lane & 4) * 16 + ((q ^ cb) & 3) * 16;
#pragma unroll
            for (int j = 0; j < 4; j++)
#pragma unroll
                for (int e = 0; e < 2; e++)
                    asm volatile("st.shared.v4.u32 [%0], {%1,%2,%3,%4};" :: "r"((dst ^ (e * 64)) + j * 128),
                                 "r"(pack2(acc[4 * j + e], acc[16 + 4 * j + e])), "r"(pack2(acc[4 * j + 2 + e], acc[16 + 4 * j + 2 + e])),
                                 "r"(pack2(acc[32 + 4 * j + e], acc[48 + 4 * j + e])), "r"(pack2(acc[32 + 4 * j + 2 + e], acc[48 + 4 * j + 2 + e])) : "memory");
            fence_async_smem();
            e_arrive(sb + BARS + 8 * (B_WRD + i0 + w));
        }
    }
}

__device__ __forceinline__ void task_p1(int wg, int pair, uint32_t sb) {
    const int tid = threadIdx.x & 127, w = tid >> 5, lane = tid & 31;
    const uint32_t buf = sb + wg * 51200, bars = sb + BARS;
    uint32_t fr[5][10][2];
    float A[40], d[20];
    zero(A);
    {
        const Desc dA = mkdesc(buf, 3584, 512, 2), dB = mkdesc(sb + C1, 128, 256, 0);
        auto issue = [&](int g, float (&d)[40]) {
            mbar_wait(bars + 8 * (B_XF + wg * 5 + g));
            wg_fence();
            wgmma_ss_n80_z(d, dA + (uint32_t)(g * 8704 >> 4), dB);
#pragma unroll
            for (int j = 1; j < 5; j++) wgmma_ss_n80_a(d, dA + (uint32_t)((g * 8704 + j * 1024) >> 4), dB + (uint32_t)(j * 2560 >> 4));
            wg_commit();
        };
        auto pack = [&](int g, float (&d)[40]) {
            reg_fence(d);
#pragma unroll
            for (int f = 0; f < 10; f++) {
                fr[g][f][0] = pack2(d[4 * f], d[4 * f + 1]);
                fr[g][f][1] = pack2(d[4 * f + 2], d[4 * f + 3]);
            }
        };
        mbar_wait(bars + 8 * B_CF1);
#pragma unroll
        for (int g = 0; g < 4; g++) { issue(g, A); wg_wait<0>(); pack(g, A); }
        zero(d);
        mbar_wait(bars + 8 * (B_XF + wg * 5 + 4));
#pragma unroll
        for (int h = 0; h < 2; h++) {
            wg_fence();
            wgmma_ss_n40_z(d, dA + (uint32_t)(4 * 8704 >> 4), dB + (uint32_t)(h * 1280 >> 4));
#pragma unroll
            for (int j = 1; j < 5; j++) wgmma_ss_n40_a(d, dA + (uint32_t)((4 * 8704 + j * 1024) >> 4), dB + (uint32_t)((j * 2560 + h * 1280) >> 4));
            wg_commit(); wg_wait<0>(); reg_fence(d);
#pragma unroll
            for (int f = 0; f < 5; f++) { fr[4][5 * h + f][0] = pack2(d[4 * f], d[4 * f + 1]); fr[4][5 * h + f][1] = pack2(d[4 * f + 2], d[4 * f + 3]); }
        }
    }
    bb_break(sb);
    wg_bar(1 + wg);
    {
        const Desc dB = mkdesc(sb + C1 + 12800, 128, 256, 0);
        const int i = lane & 7, mi = lane >> 3, th = w >> 1, tz = (2 * pair + th) & 3;
        const uint32_t s0 = buf + (i >> 1) * 128 + (i & 1) * 64 + (((2 * (w & 1) + (mi & 1)) ^ tz ^ (i >> 1)) << 4);
        const uint32_t sA = s0 + th * 2048 + (mi >> 1) * 512, sB = s0 + th * 2048 + (mi >> 1) * 2560, sC = s0 + th * 1024 + (mi >> 1) * 512;
        auto issue = [&](int f, float (&d)[20]) {
            wg_fence();
            wgmma_rs_n40_z(d, fr[0][f][0], fr[0][f][1], fr[1][f][0], fr[1][f][1], dB);
            wgmma_rs_n40_a(d, fr[2][f][0], fr[2][f][1], fr[3][f][0], fr[3][f][1], dB + (uint32_t)(1280 >> 4));
            wgmma_rs_n40_a(d, fr[4][f % 5][0], fr[4][f % 5][1], fr[4][f % 5 + 5][0], fr[4][f % 5 + 5][1], dB + (uint32_t)((2560 + (f / 5) * 1280) >> 4));
            wg_commit();
        };
#pragma unroll
        for (int f = 0; f < 10; f++) {
            issue(f, d);
            if (f && !(f & 1)) { fence_async_smem(); e_arrive(bars + 8 * (B_RDY + wg * 5 + (f >> 1) - 1)); }
            wg_wait<0>(); reg_fence(d);
            const int Q = 5 * f;
            stm4(((Q & 3) == 3 ? sB : sA) + quad_off(Q), pack2(d[0], d[1]), pack2(d[2], d[3]), pack2(d[4], d[5]), pack2(d[6], d[7]));
            stm2(sA + quad_off(Q + 2), pack2(d[8], d[9]), pack2(d[10], d[11]));
            stm4((f == 9 ? sC : ((Q + 3) & 3) == 3 ? sB : sA) + quad_off(Q + 3), pack2(d[12], d[13]), pack2(d[14], d[15]), pack2(d[16], d[17]), pack2(d[18], d[19]));
            if (f == 9) { fence_async_smem(); e_arrive(bars + 8 * (B_RDY + wg * 5 + (f >> 1))); }
        }
    }
}

__device__ __forceinline__ void task_p2(int wg, int rk, uint32_t sb) {
    const int tid = threadIdx.x & 127, w = tid >> 5, lane = tid & 31;
    const uint32_t bars = sb + BARS;
    const int phi0 = 3 * rk, phiE = extra_phi(rk), mE = extra_mask(rk);
    uint4 wA[6], wB[6], wC[6], wE[6];
    auto ldw = [&](uint4 (&a)[6], int j, int phi) {
        const int pc = 3 * j + wg;
        const uint32_t p = sb + wslot(pc) + (lane & 3) * 512 + w * 128 + (((lane >> 2) ^ phi) & 1) * 64 + (((lane >> 3) ^ lane) & 3) * 16 + (phi & 1) * 8;
        mbar_wait(bars + 8 * (B_WL + pc));
#pragma unroll
        for (int s = 0; s < 6; s++) {
            asm volatile("ld.shared.v2.u32 {%0, %1}, [%2];" : "=r"(a[s].x), "=r"(a[s].y) : "r"(p + s * 2048) : "memory");
            asm volatile("ld.shared.v2.u32 {%0, %1}, [%2];" : "=r"(a[s].z), "=r"(a[s].w) : "r"((p ^ 8) + s * 2048) : "memory");
        }
        uint32_t dep = 0;
#pragma unroll
        for (int s = 0; s < 6; s++) dep |= a[s].x ^ a[s].z;
        if (__any_sync(0xffffffffu, dep == 0x7fc17fc1u)) __nanosleep(0);
        e_arrive(bars + 8 * (B_WE + pc));
    };
    ldw(wA, 0, phi0); ldw(wB, 1, phi0 + 1);
    bool haveC = false;
#pragma unroll 1
    for (uint32_t it = 0; it < (1u << 22); it++) {
        haveC = mbar_test(bars + 8 * (B_WL + 6 + wg));
        if (haveC || mbar_test(bars + 8 * B_RF)) break;
        __nanosleep(50);
    }
    if (haveC) ldw(wC, 2, phi0 + 2);
    mbar_wait(bars + 8 * (B_SIG + SIG_P1 + 1));
    const int i = lane & 7, mi = lane >> 3;
    const uint32_t soff = sb + S1 + wg * 4096 + mi * 512 + (i >> 1) * 128 + (i & 1) * 64;
    const int xo = w ^ (i >> 1);
    float d[32];
    zero(d);
    int n = 0;
    uint32_t xb = ((sb + xslot(0)) & 0x3FFFF) >> 4 | 1u << 16, mb = bars + 8 * wg;
    bool landed = false;
    auto unit = [&](const uint4 (&a)[6], int z) {
        const Desc d0{xb + (z & 2), (512u >> 4) | (2u << 30)}, d1 = d0 ^ 2u;
        if (!landed) mbar_wait(bars + 8 * (B_RF + n));
        mbar_wait(mb + 8 * (B_TOK - 1));
        wg_fence();
        wgmma_rs_n64_z(d, a[0].x, a[0].y, a[0].z, a[0].w, d0);
        wgmma_rs_n64_a(d, a[1].x, a[1].y, a[1].z, a[1].w, d1);
        e_arrive(bars + 8 * (n ? B_RE + n - 1 : B_RE + 13));
        const bool sfree = mbar_test(n >= 4 ? mb + 8 * (B_SFREE - 12) : bars + 8 * (B_TOK - 1));
        landed = mbar_test(bars + 8 * (B_RF + n + 1));
        wgmma_rs_n64_a(d, a[2].x, a[2].y, a[2].z, a[2].w, d0 + (uint32_t)(4096 >> 4));
        wgmma_rs_n64_a(d, a[3].x, a[3].y, a[3].z, a[3].w, d1 + (uint32_t)(4096 >> 4));
        e_arrive(mb + 8 * B_TOK);
        wgmma_rs_n64_a(d, a[4].x, a[4].y, a[4].z, a[4].w, d0 + (uint32_t)(8192 >> 4));
        wgmma_rs_n64_a(d, a[5].x, a[5].y, a[5].z, a[5].w, d1 + (uint32_t)(8192 >> 4));
        wg_commit();
        if (!sfree) mbar_wait(mb + 8 * (B_SFREE - 12));
        const uint32_t a0 = soff + (n & 3) * 12288 + ((xo ^ z) << 4);
        n++;
        xb = ((sb + xslot(n)) & 0x3FFFF) >> 4 | 1u << 16;
        wg_wait<0>();
        reg_fence(d);
        uint32_t p[8];
#pragma unroll
        for (int j = 0; j < 8; j++) p[j] = pack2(d[4 * j] - d[4 * j + 3], d[4 * j + 2] + d[4 * j + 1]);
        stm4(a0, p[0], p[1], p[2], p[3]);
        stm4(a0 + 2048, p[4], p[5], p[6], p[7]);
        fence_async_smem();
        e_arrive(mb + 8 * (B_RDY + R_P2));
        mb += 24;
    };
    const int zA = phi0 & 3, zB = (phi0 + 1) & 3, zC = (phi0 + 2) & 3, zE = phiE & 3;
#pragma unroll 1
    for (int it = 0; it < 4; it++) {
        unit(wA, zA);
        unit(wB, zB);
        if (it == 0 && !haveC) ldw(wC, 2, phi0 + 2);
        unit(wC, zC);
        if (it == 0 && mE) ldw(wE, 3, phiE);
        if (mE >> it & 1) unit(wE, zE);
    }
}

__device__ __forceinline__ void task_p3(int wg, int pair, uint32_t sb) {
    const int tid = threadIdx.x & 127, w = tid >> 5, lane = tid & 31;
    const uint32_t buf = sb + (wg ? 3 - wg : 0) * 51200, bars = sb + BARS;
    uint32_t fr[10][4][2];
    float acc[2][16];
    zero(acc[0]); zero(acc[1]);
    {
        const Desc dB = mkdesc(sb + C3, 128, 256, 0);
        const uint32_t a0 = (buf & 0x3FFFF) >> 4;
        auto dq = [&](int Q) {
            return Desc{a0 + (uint32_t)((quad_off(Q) >> 4) | ((Q < 48 ? 2048 : 1024) >> 4) << 16), (uint32_t)((quad_off(Q + 1) - quad_off(Q)) >> 4) | (2u << 30)};
        };
        auto issue = [&](int f) {
            if (!(f & 1)) mbar_wait(bars + 8 * (B_YF + wg * 5 + (f >> 1)));
            wg_fence();
            wgmma_ss_n32_z(acc[f & 1], dq(5 * f), dB);
            wgmma_ss_n32_a(acc[f & 1], dq(5 * f + 1), dB + (uint32_t)(1024 >> 4));
            wgmma_ss_n32_a(acc[f & 1], dq(5 * f + 3), dB + (uint32_t)(2048 >> 4));
            wg_commit();
        };
        mbar_wait(bars + 8 * B_CF3);
        issue(0);
#pragma unroll
        for (int f = 0; f < 10; f++) {
            if (f < 9) { issue(f + 1); wg_wait<1>(); } else wg_wait<0>();
            float (&d)[16] = acc[f & 1];
            reg_fence(d);
#pragma unroll
            for (int g = 0; g < 4; g++) { fr[f][g][0] = pack2(d[4 * g], d[4 * g + 1]); fr[f][g][1] = pack2(d[4 * g + 2], d[4 * g + 3]); }
        }
    }
    {
        const Desc dB = mkdesc(sb + C3 + 3072, 128, 256, 0);
        const int i = lane & 7, mi = lane >> 3, th = w >> 1, tz = (2 * pair + th) & 3;
        const int oct = (2 * (w & 1) + (mi & 1)) ^ tz;
        const uint32_t soff = buf + th * 3584 + (mi >> 1) * 512 + i * 64 + ((oct ^ (i >> 1)) << 4);
        auto mma = [&](int t, int s) {
            if (t > 6) return;
            const int g = t < 6 ? 1 + (t >> 1) : 0;
            const uint32_t o = t < 6 ? (t & 1) * 1024 : 8960, st = t < 6 ? 1792 : 1024;
            if (s == 0) { wg_fence(); wgmma_rs_n32_z(acc[t & 1], fr[0][g][0], fr[0][g][1], fr[1][g][0], fr[1][g][1], dB + (o >> 4)); }
            else wgmma_rs_n32_a(acc[t & 1], fr[2 * s][g][0], fr[2 * s][g][1], fr[2 * s + 1][g][0], fr[2 * s + 1][g][1], dB + ((o + s * st) >> 4));
            if (s == 4) wg_commit();
        };
        const int row = th * 14 + 4 * (mi >> 1) + (i >> 1);
        const uint32_t z0 = buf + row * 128 + (i & 1) * 64 + ((oct ^ (row & 3)) << 4), z1 = (lane & 20) == 20 ? buf + 4096 + lane * 16 : z0 + 1024;
        bb_break(sb);
#pragma unroll
        for (int s = 0; s < 5; s++) mma(0, s);
        wg_bar(1 + wg);
#pragma unroll
        for (int t = 0; t < 7; t++) {
#pragma unroll
            for (int s = 0; s < 2; s++) mma(t + 1, s);
            if (t < 6) { wg_commit(); wg_wait<1>(); } else wg_wait<0>();
            float (&d)[16] = acc[t & 1];
            reg_fence(d);
            const uint32_t a = soff + (1 + (t >> 1)) * 7168 + (t & 1) * 2048;
            stm4(t < 6 ? a : z0, pack2(d[0], d[1]), pack2(d[2], d[3]), pack2(d[4], d[5]), pack2(d[6], d[7]));
            mma(t + 1, 2);
            if (t & 1) stm2(a + 1024, pack2(d[8], d[9]), pack2(d[10], d[11]));
            else stm4(t < 6 ? a + 1024 : z1, pack2(d[8], d[9]), pack2(d[10], d[11]), pack2(d[12], d[13]), pack2(d[14], d[15]));
#pragma unroll
            for (int s = 3; s < 5; s++) mma(t + 1, s);
            if ((t & 1) || t == 6) { fence_async_smem(); e_arrive(bars + 8 * (B_RDY + R_P3 + wg * 4 + (t >> 1))); }
        }
    }
}

__device__ __forceinline__ void load_x(int cls, int rk, int u, uint32_t sb, const Maps& mp) {
    const int id = u * NH + rk, pl = id / 3, c0 = 32 * (id - 3 * pl), tp = cls * 4 + (pl >> 4), col = 14 * (pl & 15) - 8;
    const uint32_t bar = sb + BARS + 8 * (B_XF + u * 5), dst = sb + u * 51200;
    const int wrap = col < 0 ? 224 : 0;
    if (tp) {
#pragma unroll
        for (int g = 0; g < 5; g++) e_ld3(dst + g * 8704, &mp.x34, c0, col + 4 * g + (g < 2 ? wrap : 0), 28 * tp - 6, bar + 8 * g);
    } else {
#pragma unroll
        for (int g = 0; g < 5; g++) {
            e_ld3(dst + g * 8704, &mp.x6, c0, col + 4 * g + (g < 2 ? wrap : 0), 218, bar + 8 * g);
            e_ld3(dst + g * 8704 + 1536, &mp.x28, c0, col + 4 * g + (g < 2 ? wrap : 0), 0, bar + 8 * g);
        }
    }
}

__device__ __forceinline__ void load_x_box(int cls, int rk, int u, int g, uint32_t sb, const Maps& mp) {
    const int id = u * NH + rk, pl = id / 3, c0 = 32 * (id - 3 * pl), tp = cls * 4 + (pl >> 4), col = 14 * (pl & 15) - 8 + 4 * g;
    e_ld3(sb + u * 51200 + g * 8704, &mp.x34, c0, col < 0 ? col + 224 : col, 28 * tp - 6, sb + BARS + 8 * (B_XF + u * 5 + g));
}

__device__ __forceinline__ void load_first(uint32_t sb, const Maps& mp, const Ptrs& pt) {
    const uint32_t bars = sb + BARS;
    const int k = blockIdx.x;
    const uint32_t cb0 = (uint32_t)k * 18351u >> 15, cb1 = ((uint32_t)k * 14u + 13u) * 5243u >> 17;
    auto block = [&](uint32_t cb, int j) {
        const uint32_t b = cb * 43u >> 10;
        e_ldw(sb + WP + j * 14336, &mp.w, 32 * b, 4 * (cb & ~3u) - 96 * b + 2 * (cb & 3), bars + 8 * (B_WF + 2 * j));
        e_expect(bars + 8 * (B_WF + 2 * j), 14336);
    };
    block(cb0, 0);
    if (cb1 != cb0 && cb1 < 72) block(cb1, 1);
    e_expect(bars + 8 * B_CF1, 17920); e_g2s(sb + C1, pt.tab1, 17920, bars + 8 * B_CF1);
    if ((threadIdx.x & 31) < 15) asm volatile("mbarrier.arrive.expect_tx.shared::cta.b64 _, [%0], 8704;" :: "r"(bars + 8 * (B_XF + (threadIdx.x & 31))) : "memory");
    __syncwarp();
}

__device__ __forceinline__ uint32_t get_rel(uint32_t sb) {
    mbar_wait(sb + BARS + 8 * B_REL);
    uint32_t v; asm volatile("ld.shared.u32 %0, [%1];" : "=r"(v) : "r"(sb + REL) : "memory");
    return uni(v);
}

__device__ __forceinline__ void load_warp(int cls, int rk, uint32_t sb, const Ptrs& pt) {
    const uint32_t bars = sb + BARS;
    mbar_wait(bars + 8 * (B_SIG + SIG_P1));
    const uint32_t rel = get_rel(sb);
    const char* cnt = cls_cnt(pt.scr, cls);
    const int mE = extra_mask(rk);
    const int lpA = phi_line(3 * rk, rel), lpB = phi_line(3 * rk + 1, rel), lpC = phi_line(3 * rk + 2, rel), lpE = phi_line(extra_phi(rk), rel);
    e_arrive(bars + 8 * (B_TOK - 1));
    if ((threadIdx.x & 31) < 14) asm volatile("mbarrier.arrive.expect_tx.shared::cta.b64 _, [%0], 12288;" :: "r"(bars + 8 * (B_RF + (threadIdx.x & 31))) : "memory");
    __syncwarp();
    int n = 0;
#pragma unroll 1
    for (int pg = 0; pg < 4; pg++) {
        const int l0 = slot_line(0, pg, cls), l1 = slot_line(1, pg, cls), l2 = slot_line(2, pg, cls);
        auto unit = [&](int lp) {
            const uint32_t bar = bars + 8 * (B_RF + n), dst = sb + xslot(n);
            mbar_wait(bars + 8 * (n >= 8 ? B_RE + n - 8 : n >= 4 ? B_SIG + SIG_P1 + (rk < 60 ? 2 : 1) : B_WE + ((0x4310 >> (4 * n)) & 15)));
            e_g2s(dst, pt.scr + (size_t)(lp ^ l0) * 128, 4096, bar);
            e_g2s(dst + 4096, pt.scr + (size_t)(lp ^ l1) * 128, 4096, bar);
            e_g2s(dst + 8192, pt.scr + (size_t)(lp ^ l2) * 128, 4096, bar);
            n++;
        };
        cnt_wait(cnt + (CNT_P1 + pg) * 128, 48);
        unit(lpA); unit(lpB); unit(lpC);
        if (mE >> pg & 1) unit(lpE);
        if (pg == 1) { mbar_wait(bars + 8 * B_P1D); e_expect(bars + 8 * B_CF3, 17152); e_g2s(sb + C3, pt.tab3, 17152, bars + 8 * B_CF3); }
    }
}

__device__ __forceinline__ int near_page(char* p) {
#pragma unroll
    for (int e = 0; e < 4; e++) asm volatile("st.relaxed.gpu.global.v4.u32 [%0], {%1, %1, %1, %1};" :: "l"(p + (e >> 1) * 4096 + (e & 1) * 16), "r"(0) : "memory");
    uint32_t v0, v1, t0, t1;
    asm volatile("atom.relaxed.gpu.global.exch.b32 %0, [%1], 1;" : "=r"(v0) : "l"(p) : "memory");
    asm volatile("atom.relaxed.gpu.global.exch.b32 %0, [%1], 1;" : "=r"(v1) : "l"(p + 4096) : "memory");
    asm volatile("{\n.reg .pred p;\nsetp.ne.u32 p, %1, 0xffffffff;\nmov.u32 %0, 0;\n@p mov.u32 %0, %%clock;\n}" : "=r"(t0) : "r"(v0) : "memory");
    asm volatile("{\n.reg .pred p;\nsetp.ne.u32 p, %1, 0xffffffff;\nmov.u32 %0, 0;\n@p mov.u32 %0, %%clock;\n}" : "=r"(t1) : "r"(v1) : "memory");
    return t1 - t0 < 80;
}

__device__ __forceinline__ uint32_t find_role(uint32_t sb, char* scr, const char* x) {
    const int k = blockIdx.x;
    int c = near_page(scr + (slot_line(3, 3, 0) + phi_line(1 + (k >> 5), 0) + (k & 31)) * 128);
    int r;
    asm volatile("atom.relaxed.gpu.global.add.u32 %0, [%1], 1;" : "=r"(r) : "l"(cls_cnt(scr, c) + CNT_RANK * 128) : "memory");
    asm volatile("cp.async.bulk.prefetch.L2.global [%0], %1;" :: "l"(x + (k & 1) * (112 * 43008) + (k >> 1) * PFS), "n"(PFS) : "memory");
    asm volatile("st.shared.u32 [%0], %1;" :: "r"(sb + REL + 8), "r"(c) : "memory");
    if (r >= NH) { c ^= 1; r = NSM - 1 - r; }
    asm volatile("st.shared.u32 [%0], %1;" :: "r"(sb + REL + 4), "r"(c << 8 | r) : "memory");
    return c << 8 | r;
}
__device__ __forceinline__ void get_role(uint32_t sb, int& cls, int& rk) {
    mbar_wait(sb + BARS + 8 * B_ROLE);
    uint32_t v; asm volatile("ld.shared.u32 %0, [%1];" : "=r"(v) : "r"(sb + REL + 4) : "memory");
    v = uni(v); cls = v >> 8; rk = v & 255;
}

__device__ __forceinline__ void load3_warp(int cls, int rk, uint32_t sb, const Maps& mp, const Ptrs& pt) {
    const uint32_t bars = sb + BARS;
    mbar_wait(bars + 8 * B_XF);
    const uint32_t rel = cnt_wait(pt.cnt + CNT_REL * 32, 12u << 16);
    asm volatile("st.shared.u32 [%0], %1;" :: "r"(sb + REL), "r"(rel) : "memory");
    __syncwarp();
    e_arrive(bars + 8 * B_REL);
    mbar_wait(bars + 8 * (B_SIG + SIG_W));
    cnt_wait(cls_cnt(pt.scr, cls) + CNT_W * 128, NSM);
    {
        const int np = rk >= 60 ? 12 : 9;
#pragma unroll 1
        for (int pc = 0; pc < np; pc++) {
            if (pc == 2) mbar_wait(bars + 8 * (B_SIG + SIG_P1));
            if (pc >= 8) mbar_wait(bars + 8 * (B_WE + ((0x5762 >> (4 * (pc - 8))) & 15)));
            if (pc >= 5) mbar_wait(bars + 8 * (B_WL + pc - 5));
            e_expect(bars + 8 * (B_WL + pc), 12288);
            e_g2s(sb + wslot(pc), pt.wf + (pc < 9 ? 9 * rk + pc : 3 * extra_phi(rk) + pc - 9) * 12288, 12288, bars + 8 * (B_WL + pc));
        }
        if (np == 12) { mbar_wait(bars + 8 * (B_WE + 9)); mbar_wait(bars + 8 * (B_WE + 10)); mbar_wait(bars + 8 * (B_WE + 11)); }
    }
    mbar_wait(bars + 8 * (B_SIG + SIG_P2 + 1));
    const int nu = rk < 60 ? 3 : 2;
#pragma unroll 1
    for (int u = 0; u < nu; u++) {
        const int id = u * NH + rk, pl = id / 3, chunk = id - 3 * pl;
        const int l0 = slot_line(chunk, pl >> 4, cls) + (pl & 15) * 2;
        const uint32_t buf = sb + (u ? 3 - u : 0) * 51200, bar = bars + 8 * (B_YF + u * 5);
#pragma unroll
        for (int j = 0; j < 5; j++) e_expect(bar + 8 * j, j == 4 ? 10240 : (j & 1) ? 8192 : 12288);
        if (u) mbar_wait(bars + 8 * (B_SIG + SIG_P2 + 3));
        cnt_wait(cls_cnt(pt.scr, cls) + (CNT_P2 + (pl >> 4)) * 128, NH);
        if (u == nu - 1) e_arrive(bars + 8 * B_FIN);
        const uint32_t r2 = uni(rel) << 5;
#pragma unroll
        for (int G = 0; G < 13; G++)
            e_ld5(buf + G * 4096, G < 12 ? &mp.f16 : &mp.f8, (l0 ^ ((r2 >> G) & 32)) + (G << 14), bar + 8 * ((2 * G) / 5));
    }
}

__device__ __forceinline__ void store_warp(uint32_t sb, const Maps& mp, const Ptrs& pt) {
    const uint32_t bars = sb + BARS;
    const int k = blockIdx.x;
    uint32_t pa = 0, pb = 0, qa = 0, qb = 0;
    auto arr2 = [&](uint32_t& a, uint32_t& b) { if (a) e_arrive(a); if (b) e_arrive(b); a = b = 0; };
    auto pre = [&](int idx) {
        const uint32_t bar = bars + 8 * idx;
        if ((pb | qb) && !mbar_test(bar)) { bulk_wait<0>(); arr2(qa, qb); arr2(pa, pb); }
        mbar_wait(bar);
    };
    auto post = [&](uint32_t fr) {
        bulk_commit(); bulk_wait_read<2>();
        if (qb) bulk_wait<2>();
        arr2(qa, qb); qa = pa; qb = pb; pb = 0; pa = fr;
    };
    auto after = [&](int sig) { pb = bars + 8 * (B_SIG + sig); };
    int cls, rk; get_role(sb, cls, rk);
    {
        int cb = 14 * k / 25, oc = 14 * k - 25 * cb;
        int g1 = 0;
#pragma unroll 1
        for (int i = 0; i < 14 && cb < 72; i++) {
            pre(B_WRD + i);
            e_st3(&mp.wst, sb + wst_off(i), 0, 8 * oc, cb);
            post(0);
            if (T1MASK >> i & 1) load_x_box(cls, rk, 1, g1++, sb, mp);
            if (++oc == 25) { oc = 0; cb++; }
        }
#pragma unroll 1
        for (; g1 < 5; g1++) load_x_box(cls, rk, 1, g1, sb, mp);
        after(SIG_W);
    }
    pre(B_REL);
    const uint32_t rel = get_rel(sb);
    const int nu = rk < 60 ? 3 : 2;
    int g2 = 0;
#pragma unroll 1
    for (int u = 0; u < nu; u++) {
        const int id = u * NH + rk, pl = id / 3, chunk = id - 3 * pl;
        const int l0 = slot_line(chunk, pl >> 4, cls) + (pl & 15) * 2;
        int j = B_RDY + u * 5;
        const int m2 = nu == 3 ? (u == 0 ? T2MASK & 0x1fff : u == 1 ? T2MASK >> 13 : 0) : 0;
#pragma unroll 1
        for (int G = 0; G < 13; G++) {
            if (0x4a5 >> G & 1) pre(j++);
            e_st5(G < 12 ? &mp.f16 : &mp.f8, sb + u * 51200 + G * 4096, (l0 ^ ((rel >> G) & 1) << 5) + (G << 14));
            post(0);
            if (m2 >> G & 1) load_x_box(cls, rk, 2, g2++, sb, mp);
        }
        after(SIG_P1 + u);
    }
    const int mE = extra_mask(rk);
    int n = 0;
#pragma unroll 1
    for (int pg = 0; pg < 4; pg++) {
        const int nj = 3 + (mE >> pg & 1);
        const int l0 = slot_line(0, pg, cls), l1 = slot_line(1, pg, cls), l2 = slot_line(2, pg, cls);
#pragma unroll 1
        for (int j = 0; j < nj; j++) {
            const int lp = phi_line(j == 3 ? extra_phi(rk) : 3 * rk + j, rel);
#pragma unroll
            for (int b = 0; b < 3; b++) {
                pre(B_RDY + R_P2 + n * 3 + b);
                e_s2g(pt.scr + (size_t)(lp ^ (b == 0 ? l0 : b == 1 ? l1 : l2)) * 128, sb + S1 + (n & 3) * 12288 + b * 4096, 4096);
                post(bars + 8 * (B_SFREE + n * 3 + b));
            }
            n++;
        }
        after(SIG_P2 + pg);
    }
#pragma unroll 1
    for (int u = 0; u < nu; u++) {
        const int id = u * NH + rk, pl = id / 3, chunk = id - 3 * pl, tp = cls * 4 + (pl >> 4), tx = pl & 15;
        const uint32_t buf = sb + (u ? 3 - u : 0) * 51200;
#pragma unroll
        for (int gg = 1; gg < 5; gg++) {
            pre(B_RDY + R_P3 + u * 4 + gg - 1);
            if (gg < 4) e_st3(&mp.y4, buf + gg * 7168, 32 * chunk, 14 * tx - 4 + 4 * gg, 28 * tp);
            else e_st3(&mp.y2, buf, 32 * chunk, tx == 0 ? 222 : 14 * tx - 2, 28 * tp);
            post(0);
        }
    }
    bulk_wait_read<0>();
}

__device__ __forceinline__ void signal_warp(int cls, int rk, uint32_t sb, const Ptrs& pt) {
    const uint32_t bars = sb + BARS;
    char* cnt = cls_cnt(pt.scr, cls);
    if (threadIdx.x & 31) return;
#pragma unroll 1
    for (int c = 0; c < 8; c++) {
        if (c == SIG_P1 + 2 && rk >= 60) continue;
        char* ctr = cnt + (c == SIG_W ? CNT_W : c < SIG_P2 ? CNT_P1 + ((c - SIG_P1) * NH + rk) / 48 : CNT_P2 + c - SIG_P2) * 128;
        mbar_wait(bars + 8 * (B_SIG + c));
        fence_async();
        asm volatile("red.relaxed.gpu.global.add.u32 [%0], 1;" :: "l"(ctr) : "memory");
        if (c == SIG_W) asm volatile("red.relaxed.gpu.global.add.u32 [%0], 1;" :: "l"((uintptr_t)ctr ^ 4096) : "memory");
    }
    mbar_wait(bars + 8 * B_FIN);
    unsigned old;
    asm volatile("atom.add.relaxed.gpu.global.u32 %0, [%1], 1;" : "=r"(old) : "l"(pt.cnt + CNT_DONE * 32) : "memory");
    if (old == NSM - 1) {
#pragma unroll
        for (int c = 0; c < NCNT; c++) pt.cnt[c * 32] = 0;
#pragma unroll 1
        for (int c = 0; c < NCLS; c++) { *reinterpret_cast<unsigned*>(cnt + c * 128) = 0; *reinterpret_cast<unsigned*>(((uintptr_t)cnt ^ 4096) + c * 128) = 0; }
    }
}

__global__ void __launch_bounds__(512, 1) fftconv_kernel(const Ptrs pt, const __grid_constant__ Maps mp) {
    extern __shared__ __align__(1024) uint8_t smem[];
    const uint32_t sb = smem_u32(smem);
    const int tid = threadIdx.x, warp = uni(tid >> 5), wg = warp >> 2;
    int cls, rk;
    auto bar_init = [&](int i) {
        uint32_t c = 1;
        if (i == B_P1D || (i >= B_RE && i < B_RE + 14)) c = 12;
        else if ((i >= B_WCH && i < B_WL) || i >= B_TOK) c = 4;
        asm volatile("st.shared.v2.u32 [%0], {%1, %2};" :: "r"(sb + BARS + 8 * i), "r"((0x100000u - c) << 1), "r"((0x100000u - c) << 11) : "memory");
        fence_async_smem();
    };
    if (wg == 3) {
        asm volatile("setmaxnreg.dec.sync.aligned.u32 32;");
        if (warp == 12) {
            bar_init(tid & 31);
            __syncwarp();
            asm volatile("bar.arrive 4, 416;" ::: "memory");
            load_first(sb, mp, pt);
            asm volatile("bar.sync 5, 416;" ::: "memory");
            get_role(sb, cls, rk);
            load_warp(cls, rk, sb, pt);
        } else if (warp == 13) {
            if ((tid & 31) < 8) asm volatile("prefetch.tensormap [%0];" :: "l"(reinterpret_cast<const CUtensorMap*>(&mp) + 1 + (tid & 31)) : "memory");
            __syncwarp();
            asm volatile("bar.sync 6, 416;" ::: "memory");
            store_warp(sb, mp, pt);
        } else if (warp == 14) {
            const int G = blockIdx.x - 119;
            int sel = 0;
            if (G >= 1 && (tid & 31) == 0) sel = near_page(pt.scr + ((size_t)G << 21) + slot_line(3, 3, 0) * 128);
            __syncwarp();
            asm volatile("bar.sync 7, 416;" ::: "memory");
            get_role(sb, cls, rk);
            if (G >= 1 && (tid & 31) == 0) {
                uint32_t c; asm volatile("ld.shared.u32 %0, [%1];" : "=r"(c) : "r"(sb + REL + 8) : "memory");
                asm volatile("red.relaxed.gpu.global.add.u32 [%0], %1;" :: "l"(pt.cnt + CNT_REL * 32), "r"(0x10000u | (sel ^ c) << G) : "memory");
            }
            __syncwarp();
            load3_warp(cls, rk, sb, mp, pt);
        } else {
            uint32_t role = 0;
            if ((tid & 31) == 0) role = find_role(sb, pt.scr, pt.x);
            role = uni(role); cls = role >> 8; rk = role & 255;
            asm volatile("bar.sync 8, 416;" ::: "memory");
            load_x(cls, rk, 0, sb, mp);
            e_arrive(sb + BARS + 8 * B_ROLE);
            signal_warp(cls, rk, sb, pt);
        }
    } else {
        if (tid >= 32 && tid < NBAR) bar_init(tid);
        {
            const int r = tid % 40;
            asm volatile("st.shared.u32 [%0], %1;" :: "r"(sb + TBL + 4 * tid), "r"(cos_bits(r) | (cos_bits(r < 30 ? r + 10 : r - 30) << 16)) : "memory");
        }
        __syncwarp();
        asm volatile("bar.sync 4, 416;" ::: "memory");
        asm volatile("bar.arrive 5, 416;" ::: "memory");
        asm volatile("bar.arrive 6, 416;" ::: "memory");
        asm volatile("bar.arrive 7, 416;" ::: "memory");
        asm volatile("bar.arrive 8, 416;" ::: "memory");
        task_w(wg, blockIdx.x, sb);
        asm volatile("setmaxnreg.inc.sync.aligned.u32 160;");
        get_role(sb, cls, rk);
        const int id = wg * NH + rk;
        if (id < 192) task_p1(wg, id / 3, sb);
        e_arrive(sb + BARS + 8 * B_P1D);
        task_p2(wg, rk, sb);
        if (id < 192) task_p3(wg, id / 3, sb);
    }
}

__global__ void fallback_kernel(const __nv_bfloat16* x, const __nv_bfloat16* w, __nv_bfloat16* y) {
    const int px = blockIdx.x, o = threadIdx.x, h = px / 224, c = px % 224;
    float acc = 0.f;
    for (int kh = 0; kh < 7; kh++)
        for (int kw = 0; kw < 7; kw++) {
            const __nv_bfloat16* xp = x + (((h - kh + 224) % 224) * 224 + (c - kw + 224) % 224) * 96;
            const __nv_bfloat16* wp = w + (kh * 7 + kw) * 9216 + o;
            for (int i = 0; i < 96; i++) acc += __bfloat162float(xp[i]) * __bfloat162float(wp[i * 96]);
        }
    y[px * 96 + o] = __float2bfloat16(acc);
}

typedef CUresult (*EncodeFn)(CUtensorMap*, CUtensorMapDataType, cuuint32_t, void*, const cuuint64_t*, const cuuint64_t*, const cuuint32_t*, const cuuint32_t*,
                             CUtensorMapInterleave, CUtensorMapSwizzle, CUtensorMapL2promotion, CUtensorMapFloatOOBfill);

static void encode3(EncodeFn fn, CUtensorMap* m, void* ptr, uint64_t d0, uint64_t d1, uint64_t d2, uint64_t s1, uint64_t s2,
                    uint32_t b0, uint32_t b1, uint32_t b2, CUtensorMapSwizzle sw, CUtensorMapL2promotion promo = CU_TENSOR_MAP_L2_PROMOTION_NONE) {
    cuuint64_t dims[3] = {d0, d1, d2}, strides[2] = {s1, s2};
    cuuint32_t box[3] = {b0, b1, b2}, es[3] = {1, 1, 1};
    fn(m, CU_TENSOR_MAP_DATA_TYPE_BFLOAT16, 3, ptr, dims, strides, box, es, CU_TENSOR_MAP_INTERLEAVE_NONE, sw,
       promo, CU_TENSOR_MAP_FLOAT_OOB_FILL_NONE);
}

extern "C" void kernel_launch(void* const* d_in, const int* in_sizes, int n_in, void* d_out, int out_size) {
    (void)in_sizes; (void)n_in; (void)out_size;
    int dev = 0, nsm = 0;
    cudaGetDevice(&dev);
    cudaDeviceGetAttribute(&nsm, cudaDevAttrMultiProcessorCount, dev);
    if (nsm < NSM) {
        fallback_kernel<<<224 * 224, 96>>>((const __nv_bfloat16*)d_in[0], (const __nv_bfloat16*)d_in[1], (__nv_bfloat16*)d_out);
        return;
    }
    void* fnp = nullptr; cudaDriverEntryPointQueryResult qr;
    cudaGetDriverEntryPoint("cuTensorMapEncodeTiled", &fnp, cudaEnableDefault, &qr);
    EncodeFn fn = (EncodeFn)fnp;
    void* xf = nullptr; cudaGetSymbolAddress(&xf, g_scr);
    xf = (void*)(((uintptr_t)xf + (1u << 21) - 1) & ~(uintptr_t)((1u << 21) - 1));
    void* wf = nullptr; cudaGetSymbolAddress(&wf, g_wf);
    Maps mp;
    Ptrs pt;
    pt.scr = (char*)xf; pt.wf = (const char*)wf; pt.x = (const char*)d_in[0];
    void* p = nullptr;
    cudaGetSymbolAddress(&p, TAB_P1); pt.tab1 = p;
    cudaGetSymbolAddress(&p, TAB_P3); pt.tab3 = p;
    cudaGetSymbolAddress(&p, g_cnt); pt.cnt = (unsigned*)p;
    {
        cuuint32_t b16[5] = {64, 4, 2, 2, 2}, b8[5] = {64, 4, 2, 1, 2}, es[5] = {1, 1, 1, 1, 1};
        cuuint64_t d[5] = {64, 4, 2, 2, 13 << 14}, st[4] = {16384, 262144, 1048576, 128};
        fn(&mp.f16, CU_TENSOR_MAP_DATA_TYPE_BFLOAT16, 5, xf, d, st, b16, es, CU_TENSOR_MAP_INTERLEAVE_NONE, CU_TENSOR_MAP_SWIZZLE_NONE, CU_TENSOR_MAP_L2_PROMOTION_NONE, CU_TENSOR_MAP_FLOAT_OOB_FILL_NONE);
        fn(&mp.f8, CU_TENSOR_MAP_DATA_TYPE_BFLOAT16, 5, xf, d, st, b8, es, CU_TENSOR_MAP_INTERLEAVE_NONE, CU_TENSOR_MAP_SWIZZLE_NONE, CU_TENSOR_MAP_L2_PROMOTION_NONE, CU_TENSOR_MAP_FLOAT_OOB_FILL_NONE);
    }
    encode3(fn, &mp.x6, d_in[0], 96, 224, 224, 192, 224 * 192, 32, 4, 6, CU_TENSOR_MAP_SWIZZLE_64B, CU_TENSOR_MAP_L2_PROMOTION_L2_128B);
    encode3(fn, &mp.x34, d_in[0], 96, 224, 224, 192, 224 * 192, 32, 4, 34, CU_TENSOR_MAP_SWIZZLE_64B, CU_TENSOR_MAP_L2_PROMOTION_L2_128B);
    encode3(fn, &mp.x28, d_in[0], 96, 224, 224, 192, 224 * 192, 32, 4, 28, CU_TENSOR_MAP_SWIZZLE_64B, CU_TENSOR_MAP_L2_PROMOTION_L2_128B);
    {
        cuuint32_t box[5] = {32, 8, 7, 2, 2}, es[5] = {1, 1, 1, 1, 1};
        cuuint64_t d[5] = {96, 7, 7, 88, 2}, st[4] = {18432, 7 * 18432, 192, 8 * 192};
        fn(&mp.w, CU_TENSOR_MAP_DATA_TYPE_BFLOAT16, 5, d_in[1], d, st, box, es, CU_TENSOR_MAP_INTERLEAVE_NONE, CU_TENSOR_MAP_SWIZZLE_64B, CU_TENSOR_MAP_L2_PROMOTION_NONE, CU_TENSOR_MAP_FLOAT_OOB_FILL_NONE);
    }
    encode3(fn, &mp.wst, wf, 256, 200, 72, 36864, 512, 256, 8, 1, CU_TENSOR_MAP_SWIZZLE_NONE);
    encode3(fn, &mp.y4, d_out, 96, 224, 224, 192, 224 * 192, 32, 4, 28, CU_TENSOR_MAP_SWIZZLE_64B);
    encode3(fn, &mp.y2, d_out, 96, 224, 224, 192, 224 * 192, 32, 2, 28, CU_TENSOR_MAP_SWIZZLE_64B);
    constexpr int SMEM_LAUNCH = SMEM_BYTES;
    cudaFuncSetAttribute(fftconv_kernel, cudaFuncAttributeMaxDynamicSharedMemorySize, SMEM_LAUNCH);
    fftconv_kernel<<<NSM, 512, SMEM_LAUNCH>>>(pt, mp);
}
```

```cpp
#include <cuda_runtime.h>
#include <cuda_bf16.h>
#include <cuda.h>
#include <stdint.h>

__device__ __align__(128) const uint32_t TAB_P1[4480] = {
0x3e75,0,0x3e72,0,0x8000,0,0xbd19,0,0x3e750000,0,0x3e720000,0,0x80000000,0,0xbd190000,0,
0,0x3e75,0,0x3e72,0,0x8000,0,0xbd19,0,0x3e750000,0,0x3e720000,0,0x80000000,0,0xbd190000,
0x3e69,0,0x3e5a,0,0xbd97,0,0xbdde,0,0x3e690000,0,0x3e5a0000,0,0xbd970000,0,0xbdde0000,0,
0,0x3e69,0,0x3e5a,0,0xbd97,0,0xbdde,0,0x3e690000,0,0x3e5a0000,0,0xbd970000,0,0xbdde0000,
0x3e75,0,0x3e5a,0,0x8000,0,0xbdde,0,0x3e750000,0,0x3e5a0000,0,0x80000000,0,0xbdde0000,0,
0,0x3e75,0,0x3e5a,0,0x8000,0,0xbdde,0,0x3e750000,0,0x3e5a0000,0,0x80000000,0,0xbdde0000,
0x3e10,0,0x3d19,0,0xbe46,0,0xbe72,0,0x3e100000,0,0x3d190000,0,0xbe460000,0,0xbe720000,0,
0,0x3e10,0,0x3d19,0,0xbe46,0,0xbe72,0,0x3e100000,0,0x3d190000,0,0xbe460000,0,0xbe720000,
0x3e75,0,0x3e2d,0,0x8000,0,0xbe2d,0,0x3e750000,0,0x3e2d0000,0,0x80000000,0,0xbe2d0000,0,
0,0x3e75,0,0x3e2d,0,0x8000,0,0xbe2d,0,0x3e750000,0,0x3e2d0000,0,0x80000000,0,0xbe2d0000,
0,0,0xbe2d,0,0xbe75,0,0xbe2d,0,0,0,0xbe2d0000,0,0xbe750000,0,0xbe2d0000,0,
0,0,0,0xbe2d,0,0xbe75,0,0xbe2d,0,0,0,0xbe2d0000,0,0xbe750000,0,0xbe2d0000,
0x3e75,0,0x3dde,0,0x8000,0,0xbe5a,0,0x3e750000,0,0x3dde0000,0,0x80000000,0,0xbe5a0000,0,
0,0x3e75,0,0x3dde,0,0x8000,0,0xbe5a,0,0x3e750000,0,0x3dde0000,0,0x80000000,0,0xbe5a0000,
0xbe10,0,0xbe72,0,0xbe46,0,0x3d19,0,0xbe100000,0,0xbe720000,0,0xbe460000,0,0x3d190000,0,
0,0xbe10,0,0xbe72,0,0xbe46,0,0x3d19,0,0xbe100000,0,0xbe720000,0,0xbe460000,0,0x3d190000,
0x3e75,0,0x3d19,0,0x8000,0,0xbe72,0,0x3e750000,0,0x3d190000,0,0x80000000,0,0xbe720000,0,
0,0x3e75,0,0x3d19,0,0x8000,0,0xbe72,0,0x3e750000,0,0x3d190000,0,0x80000000,0,0xbe720000,
0xbe69,0,0xbdde,0,0xbd97,0,0x3e5a,0,0xbe690000,0,0xbdde0000,0,0xbd970000,0,0x3e5a0000,0,
0,0xbe69,0,0xbdde,0,0xbd97,0,0x3e5a,0,0xbe690000,0,0xbdde0000,0,0xbd970000,0,0x3e5a0000,
0x3e75,0,0xbd19,0,0x8000,0,0xbe72,0,0x3e750000,0,0xbd190000,0,0x80000000,0,0xbe720000,0,
0,0x3e75,0,0xbd19,0,0x8000,0,0xbe72,0,0x3e750000,0,0xbd190000,0,0x80000000,0,0xbe720000,
0xbe69,0,0x3dde,0,0x3d97,0,0x3e5a,0,0xbe690000,0,0x3dde0000,0,0x3d970000,0,0x3e5a0000,0,
0,0xbe69,0,0x3dde,0,0x3d97,0,0x3e5a,0,0xbe690000,0,0x3dde0000,0,0x3d970000,0,0x3e5a0000,
0x3e75,0,0xbdde,0,0x8000,0,0xbe5a,0,0x3e750000,0,0xbdde0000,0,0x80000000,0,0xbe5a0000,0,
0,0x3e75,0,0xbdde,0,0x8000,0,0xbe5a,0,0x3e750000,0,0xbdde0000,0,0x80000000,0,0xbe5a0000,
0xbe10,0,0x3e72,0,0x3e46,0,0x3d19,0,0xbe100000,0,0x3e720000,0,0x3e460000,0,0x3d190000,0,
0,0xbe10,0,0x3e72,0,0x3e46,0,0x3d19,0,0xbe100000,0,0x3e720000,0,0x3e460000,0,0x3d190000,
0x3e75,0,0xbe2d,0,0x8000,0,0xbe2d,0,0x3e750000,0,0xbe2d0000,0,0x80000000,0,0xbe2d0000,0,
0,0x3e75,0,0xbe2d,0,0x8000,0,0xbe2d,0,0x3e750000,0,0xbe2d0000,0,0x80000000,0,0xbe2d0000,
0,0,0x3e2d,0,0x3e75,0,0xbe2d,0,0,0,0x3e2d0000,0,0x3e750000,0,0xbe2d0000,0,
0,0,0,0x3e2d,0,0x3e75,0,0xbe2d,0,0,0,0x3e2d0000,0,0x3e750000,0,0xbe2d0000,
0x3e75,0,0xbe5a,0,0x8000,0,0xbdde,0,0x3e750000,0,0xbe5a0000,0,0x80000000,0,0xbdde0000,0,
0,0x3e75,0,0xbe5a,0,0x8000,0,0xbdde,0,0x3e750000,0,0xbe5a0000,0,0x80000000,0,0xbdde0000,
0x3e10,0,0xbd19,0,0x3e46,0,0xbe72,0,0x3e100000,0,0xbd190000,0,0x3e460000,0,0xbe720000,0,
0,0x3e10,0,0xbd19,0,0x3e46,0,0xbe72,0,0x3e100000,0,0xbd190000,0,0x3e460000,0,0xbe720000,
0x3e75,0,0xbe72,0,0x8000,0,0xbd19,0,0x3e750000,0,0xbe720000,0,0x80000000,0,0xbd190000,0,
0,0x3e75,0,0xbe72,0,0x8000,0,0xbd19,0,0x3e750000,0,0xbe720000,0,0x80000000,0,0xbd190000,
0x3e69,0,0xbe5a,0,0x3d97,0,0xbdde,0,0x3e690000,0,0xbe5a0000,0,0x3d970000,0,0xbdde0000,0,
0,0x3e69,0,0xbe5a,0,0x3d97,0,0xbdde,0,0x3e690000,0,0xbe5a0000,0,0x3d970000,0,0xbdde0000,
0x3e46,0,0x3e2d,0,0xbe10,0,0xbe2d,0,0x3e460000,0,0x3e2d0000,0,0xbe100000,0,0xbe2d0000,0,
0,0x3e46,0,0x3e2d,0,0xbe10,0,0xbe2d,0,0x3e460000,0,0x3e2d0000,0,0xbe100000,0,0xbe2d0000,
0x3e10,0,0x3dde,0,0xbe46,0,0xbe5a,0,0x3e100000,0,0x3dde0000,0,0xbe460000,0,0xbe5a0000,0,
0,0x3e10,0,0x3dde,0,0xbe46,0,0xbe5a,0,0x3e100000,0,0x3dde0000,0,0xbe460000,0,0xbe5a0000,
0xbd97,0,0xbe2d,0,0xbe69,0,0xbe2d,0,0xbd970000,0,0xbe2d0000,0,0xbe690000,0,0xbe2d0000,0,
0,0xbd97,0,0xbe2d,0,0xbe69,0,0xbe2d,0,0xbd970000,0,0xbe2d0000,0,0xbe690000,0,0xbe2d0000,
0xbe69,0,0xbe72,0,0xbd97,0,0x3d19,0,0xbe690000,0,0xbe720000,0,0xbd970000,0,0x3d190000,0,
0,0xbe69,0,0xbe72,0,0xbd97,0,0x3d19,0,0xbe690000,0,0xbe720000,0,0xbd970000,0,0x3d190000,
0xbe75,0,0xbe2d,0,0x8000,0,0x3e2d,0,0xbe750000,0,0xbe2d0000,0,0x80000000,0,0x3e2d0000,0,
0,0xbe75,0,0xbe2d,0,0x8000,0,0x3e2d,0,0xbe750000,0,0xbe2d0000,0,0x80000000,0,0x3e2d0000,
0,0,0x3e2d,0,0x3e75,0,0x3e2d,0,0,0,0x3e2d0000,0,0x3e750000,0,0x3e2d0000,0,
0,0,0,0x3e2d,0,0x3e75,0,0x3e2d,0,0,0,0x3e2d0000,0,0x3e750000,0,0x3e2d0000,
0xbd97,0,0x3e2d,0,0x3e69,0,0x3e2d,0,0xbd970000,0,0x3e2d0000,0,0x3e690000,0,0x3e2d0000,0,
0,0xbd97,0,0x3e2d,0,0x3e69,0,0x3e2d,0,0xbd970000,0,0x3e2d0000,0,0x3e690000,0,0x3e2d0000,
0x3e69,0,0x3d19,0,0xbd97,0,0xbe72,0,0x3e690000,0,0x3d190000,0,0xbd970000,0,0xbe720000,0,
0,0x3e69,0,0x3d19,0,0xbd97,0,0xbe72,0,0x3e690000,0,0x3d190000,0,0xbd970000,0,0xbe720000,
0x3e46,0,0x3e2d,0,0x3e10,0,0xbe2d,0,0x3e460000,0,0x3e2d0000,0,0x3e100000,0,0xbe2d0000,0,
0,0x3e46,0,0x3e2d,0,0x3e10,0,0xbe2d,0,0x3e460000,0,0x3e2d0000,0,0x3e100000,0,0xbe2d0000,
0xbe10,0,0xbe5a,0,0xbe46,0,0x3dde,0,0xbe100000,0,0xbe5a0000,0,0xbe460000,0,0x3dde0000,0,
0,0xbe10,0,0xbe5a,0,0xbe46,0,0x3dde,0,0xbe100000,0,0xbe5a0000,0,0xbe460000,0,0x3dde0000,
0x3e46,0,0xbe2d,0,0xbe10,0,0xbe2d,0,0x3e460000,0,0xbe2d0000,0,0xbe100000,0,0xbe2d0000,0,
0,0x3e46,0,0xbe2d,0,0xbe10,0,0xbe2d,0,0x3e460000,0,0xbe2d0000,0,0xbe100000,0,0xbe2d0000,
0xbe10,0,0x3e5a,0,0x3e46,0,0x3dde,0,0xbe100000,0,0x3e5a0000,0,0x3e460000,0,0x3dde0000,0,
0,0xbe10,0,0x3e5a,0,0x3e46,0,0x3dde,0,0xbe100000,0,0x3e5a0000,0,0x3e460000,0,0x3dde0000,
0xbd97,0,0xbe2d,0,0xbe69,0,0x3e2d,0,0xbd970000,0,0xbe2d0000,0,0xbe690000,0,0x3e2d0000,0,
0,0xbd97,0,0xbe2d,0,0xbe69,0,0x3e2d,0,0xbd970000,0,0xbe2d0000,0,0xbe690000,0,0x3e2d0000,
0x3e69,0,0xbd19,0,0x3d97,0,0xbe72,0,0x3e690000,0,0xbd190000,0,0x3d970000,0,0xbe720000,0,
0,0x3e69,0,0xbd19,0,0x3d97,0,0xbe72,0,0x3e690000,0,0xbd190000,0,0x3d970000,0,0xbe720000,
0xbe75,0,0x3e2d,0,0x8000,0,0x3e2d,0,0xbe750000,0,0x3e2d0000,0,0x80000000,0,0x3e2d0000,0,
0,0xbe75,0,0x3e2d,0,0x8000,0,0x3e2d,0,0xbe750000,0,0x3e2d0000,0,0x80000000,0,0x3e2d0000,
0,0,0xbe2d,0,0xbe75,0,0x3e2d,0,0,0,0xbe2d0000,0,0xbe750000,0,0x3e2d0000,0,
0,0,0,0xbe2d,0,0xbe75,0,0x3e2d,0,0,0,0xbe2d0000,0,0xbe750000,0,0x3e2d0000,
0xbd97,0,0x3e2d,0,0x3e69,0,0xbe2d,0,0xbd970000,0,0x3e2d0000,0,0x3e690000,0,0xbe2d0000,0,
0,0xbd97,0,0x3e2d,0,0x3e69,0,0xbe2d,0,0xbd970000,0,0x3e2d0000,0,0x3e690000,0,0xbe2d0000,
0xbe69,0,0x3e72,0,0x3d97,0,0x3d19,0,0xbe690000,0,0x3e720000,0,0x3d970000,0,0x3d190000,0,
0,0xbe69,0,0x3e72,0,0x3d97,0,0x3d19,0,0xbe690000,0,0x3e720000,0,0x3d970000,0,0x3d190000,
0x3e46,0,0xbe2d,0,0x3e10,0,0xbe2d,0,0x3e460000,0,0xbe2d0000,0,0x3e100000,0,0xbe2d0000,0,
0,0x3e46,0,0xbe2d,0,0x3e10,0,0xbe2d,0,0x3e460000,0,0xbe2d0000,0,0x3e100000,0,0xbe2d0000,
0x3e10,0,0xbdde,0,0x3e46,0,0xbe5a,0,0x3e100000,0,0xbdde0000,0,0x3e460000,0,0xbe5a0000,0,
0,0x3e10,0,0xbdde,0,0x3e46,0,0xbe5a,0,0x3e100000,0,0xbdde0000,0,0x3e460000,0,0xbe5a0000,
0x3d97,0,0x3d19,0,0xbe69,0,0xbe72,0,0x3d970000,0,0x3d190000,0,0xbe690000,0,0xbe720000,0,
0,0x3d97,0,0x3d19,0,0xbe69,0,0xbe72,0,0x3d970000,0,0x3d190000,0,0xbe690000,0,0xbe720000,
0,0,0xbd19,0,0xbe75,0,0xbe72,0,0,0,0xbd190000,0,0xbe750000,0,0xbe720000,0,
0,0,0,0xbd19,0,0xbe75,0,0xbe72,0,0,0,0xbd190000,0,0xbe750000,0,0xbe720000,
0xbe46,0,0xbdde,0,0x3e10,0,0x3e5a,0,0xbe460000,0,0xbdde0000,0,0x3e100000,0,0x3e5a0000,0,
0,0xbe46,0,0xbdde,0,0x3e10,0,0x3e5a,0,0xbe460000,0,0xbdde0000,0,0x3e100000,0,0x3e5a0000,
0,0,0x3dde,0,0x3e75,0,0x3e5a,0,0,0,0x3dde0000,0,0x3e750000,0,0x3e5a0000,0,
0,0,0,0x3dde,0,0x3e75,0,0x3e5a,0,0,0,0x3dde0000,0,0x3e750000,0,0x3e5a0000,
0x3e75,0,0x3e2d,0,0x8000,0,0xbe2d,0,0x3e750000,0,0x3e2d0000,0,0x80000000,0,0xbe2d0000,0,
0,0x3e75,0,0x3e2d,0,0x8000,0,0xbe2d,0,0x3e750000,0,0x3e2d0000,0,0x80000000,0,0xbe2d0000,
0,0,0xbe2d,0,0xbe75,0,0xbe2d,0,0,0,0xbe2d0000,0,0xbe750000,0,0xbe2d0000,0,
0,0,0,0xbe2d,0,0xbe75,0,0xbe2d,0,0,0,0xbe2d0000,0,0xbe750000,0,0xbe2d0000,
0xbe46,0,0xbe5a,0,0xbe10,0,0x3dde,0,0xbe460000,0,0xbe5a0000,0,0xbe100000,0,0x3dde0000,0,
0,0xbe46,0,0xbe5a,0,0xbe10,0,0x3dde,0,0xbe460000,0,0xbe5a0000,0,0xbe100000,0,0x3dde0000,
0,0,0x3e5a,0,0x3e75,0,0x3dde,0,0,0,0x3e5a0000,0,0x3e750000,0,0x3dde0000,0,
0,0,0,0x3e5a,0,0x3e75,0,0x3dde,0,0,0,0x3e5a0000,0,0x3e750000,0,0x3dde0000,
0x3d97,0,0x3e72,0,0x3e69,0,0xbd19,0,0x3d970000,0,0x3e720000,0,0x3e690000,0,0xbd190000,0,
0,0x3d97,0,0x3e72,0,0x3e69,0,0xbd19,0,0x3d970000,0,0x3e720000,0,0x3e690000,0,0xbd190000,
0,0,0xbe72,0,0xbe75,0,0xbd19,0,0,0,0xbe720000,0,0xbe750000,0,0xbd190000,0,
0,0,0,0xbe72,0,0xbe75,0,0xbd19,0,0,0,0xbe720000,0,0xbe750000,0,0xbd190000,
0x3d97,0,0xbe72,0,0xbe69,0,0xbd19,0,0x3d970000,0,0xbe720000,0,0xbe690000,0,0xbd190000,0,
0,0x3d97,0,0xbe72,0,0xbe69,0,0xbd19,0,0x3d970000,0,0xbe720000,0,0xbe690000,0,0xbd190000,
0,0,0x3e72,0,0x3e75,0,0xbd19,0,0,0,0x3e720000,0,0x3e750000,0,0xbd190000,0,
0,0,0,0x3e72,0,0x3e75,0,0xbd19,0,0,0,0x3e720000,0,0x3e750000,0,0xbd190000,
0xbe46,0,0x3e5a,0,0x3e10,0,0x3dde,0,0xbe460000,0,0x3e5a0000,0,0x3e100000,0,0x3dde0000,0,
0,0xbe46,0,0x3e5a,0,0x3e10,0,0x3dde,0,0xbe460000,0,0x3e5a0000,0,0x3e100000,0,0x3dde0000,
0,0,0xbe5a,0,0xbe75,0,0x3dde,0,0,0,0xbe5a0000,0,0xbe750000,0,0x3dde0000,0,
0,0,0,0xbe5a,0,0xbe75,0,0x3dde,0,0,0,0xbe5a0000,0,0xbe750000,0,0x3dde0000,
0x3e75,0,0xbe2d,0,0x8000,0,0xbe2d,0,0x3e750000,0,0xbe2d0000,0,0x80000000,0,0xbe2d0000,0,
0,0x3e75,0,0xbe2d,0,0x8000,0,0xbe2d,0,0x3e750000,0,0xbe2d0000,0,0x80000000,0,0xbe2d0000,
0,0,0x3e2d,0,0x3e75,0,0xbe2d,0,0,0,0x3e2d0000,0,0x3e750000,0,0xbe2d0000,0,
0,0,0,0x3e2d,0,0x3e75,0,0xbe2d,0,0,0,0x3e2d0000,0,0x3e750000,0,0xbe2d0000,
0xbe46,0,0x3dde,0,0xbe10,0,0x3e5a,0,0xbe460000,0,0x3dde0000,0,0xbe100000,0,0x3e5a0000,0,
0,0xbe46,0,0x3dde,0,0xbe10,0,0x3e5a,0,0xbe460000,0,0x3dde0000,0,0xbe100000,0,0x3e5a0000,
0,0,0xbdde,0,0xbe75,0,0x3e5a,0,0,0,0xbdde0000,0,0xbe750000,0,0x3e5a0000,0,
0,0,0,0xbdde,0,0xbe75,0,0x3e5a,0,0,0,0xbdde0000,0,0xbe750000,0,0x3e5a0000,
0x3d97,0,0xbd19,0,0x3e69,0,0xbe72,0,0x3d970000,0,0xbd190000,0,0x3e690000,0,0xbe720000,0,
0,0x3d97,0,0xbd19,0,0x3e69,0,0xbe72,0,0x3d970000,0,0xbd190000,0,0x3e690000,0,0xbe720000,
0,0,0x3d19,0,0x3e75,0,0xbe72,0,0,0,0x3d190000,0,0x3e750000,0,0xbe720000,0,
0,0,0,0x3d19,0,0x3e75,0,0xbe72,0,0,0,0x3d190000,0,0x3e750000,0,0xbe720000,
0xbd97,0,0xbdde,0,0xbe69,0,0xbe5a,0,0xbd970000,0,0xbdde0000,0,0xbe690000,0,0xbe5a0000,0,
0,0xbd97,0,0xbdde,0,0xbe69,0,0xbe5a,0,0xbd970000,0,0xbdde0000,0,0xbe690000,0,0xbe5a0000,
0xbe10,0,0xbe2d,0,0xbe46,0,0xbe2d,0,0xbe100000,0,0xbe2d0000,0,0xbe460000,0,0xbe2d0000,0,
0,0xbe10,0,0xbe2d,0,0xbe46,0,0xbe2d,0,0xbe100000,0,0xbe2d0000,0,0xbe460000,0,0xbe2d0000,
0x3e46,0,0x3e72,0,0x3e10,0,0x3d19,0,0x3e460000,0,0x3e720000,0,0x3e100000,0,0x3d190000,0,
0,0x3e46,0,0x3e72,0,0x3e10,0,0x3d19,0,0x3e460000,0,0x3e720000,0,0x3e100000,0,0x3d190000,
0x3e69,0,0x3e2d,0,0xbd97,0,0xbe2d,0,0x3e690000,0,0x3e2d0000,0,0xbd970000,0,0xbe2d0000,0,
0,0x3e69,0,0x3e2d,0,0xbd97,0,0xbe2d,0,0x3e690000,0,0x3e2d0000,0,0xbd970000,0,0xbe2d0000,
0xbe75,0,0xbe2d,0,0x8000,0,0x3e2d,0,0xbe750000,0,0xbe2d0000,0,0x80000000,0,0x3e2d0000,0,
0,0xbe75,0,0xbe2d,0,0x8000,0,0x3e2d,0,0xbe750000,0,0xbe2d0000,0,0x80000000,0,0x3e2d0000,
0,0,0x3e2d,0,0x3e75,0,0x3e2d,0,0,0,0x3e2d0000,0,0x3e750000,0,0x3e2d0000,0,
0,0,0,0x3e2d,0,0x3e75,0,0x3e2d,0,0,0,0x3e2d0000,0,0x3e750000,0,0x3e2d0000,
0x3e46,0,0xbd19,0,0xbe10,0,0xbe72,0,0x3e460000,0,0xbd190000,0,0xbe100000,0,0xbe720000,0,
0,0x3e46,0,0xbd19,0,0xbe10,0,0xbe72,0,0x3e460000,0,0xbd190000,0,0xbe100000,0,0xbe720000,
0xbe69,0,0xbe2d,0,0xbd97,0,0x3e2d,0,0xbe690000,0,0xbe2d0000,0,0xbd970000,0,0x3e2d0000,0,
0,0xbe69,0,0xbe2d,0,0xbd97,0,0x3e2d,0,0xbe690000,0,0xbe2d0000,0,0xbd970000,0,0x3e2d0000,
0xbd97,0,0x3e5a,0,0x3e69,0,0x3dde,0,0xbd970000,0,0x3e5a0000,0,0x3e690000,0,0x3dde0000,0,
0,0xbd97,0,0x3e5a,0,0x3e69,0,0x3dde,0,0xbd970000,0,0x3e5a0000,0,0x3e690000,0,0x3dde0000,
0x3e10,0,0xbe2d,0,0xbe46,0,0xbe2d,0,0x3e100000,0,0xbe2d0000,0,0xbe460000,0,0xbe2d0000,0,
0,0x3e10,0,0xbe2d,0,0xbe46,0,0xbe2d,0,0x3e100000,0,0xbe2d0000,0,0xbe460000,0,0xbe2d0000,
0xbd97,0,0xbe5a,0,0xbe69,0,0x3dde,0,0xbd970000,0,0xbe5a0000,0,0xbe690000,0,0x3dde0000,0,
0,0xbd97,0,0xbe5a,0,0xbe69,0,0x3dde,0,0xbd970000,0,0xbe5a0000,0,0xbe690000,0,0x3dde0000,
0x3e10,0,0x3e2d,0,0x3e46,0,0xbe2d,0,0x3e100000,0,0x3e2d0000,0,0x3e460000,0,0xbe2d0000,0,
0,0x3e10,0,0x3e2d,0,0x3e46,0,0xbe2d,0,0x3e100000,0,0x3e2d0000,0,0x3e460000,0,0xbe2d0000,
0x3e46,0,0x3d19,0,0x3e10,0,0xbe72,0,0x3e460000,0,0x3d190000,0,0x3e100000,0,0xbe720000,0,
0,0x3e46,0,0x3d19,0,0x3e10,0,0xbe72,0,0x3e460000,0,0x3d190000,0,0x3e100000,0,0xbe720000,
0xbe69,0,0x3e2d,0,0x3d97,0,0x3e2d,0,0xbe690000,0,0x3e2d0000,0,0x3d970000,0,0x3e2d0000,0,
0,0xbe69,0,0x3e2d,0,0x3d97,0,0x3e2d,0,0xbe690000,0,0x3e2d0000,0,0x3d970000,0,0x3e2d0000,
0xbe75,0,0x3e2d,0,0x8000,0,0x3e2d,0,0xbe750000,0,0x3e2d0000,0,0x80000000,0,0x3e2d0000,0,
0,0xbe75,0,0x3e2d,0,0x8000,0,0x3e2d,0,0xbe750000,0,0x3e2d0000,0,0x80000000,0,0x3e2d0000,
0,0,0xbe2d,0,0xbe75,0,0x3e2d,0,0,0,0xbe2d0000,0,0xbe750000,0,0x3e2d0000,0,
0,0,0,0xbe2d,0,0xbe75,0,0x3e2d,0,0,0,0xbe2d0000,0,0xbe750000,0,0x3e2d0000,
0x3e46,0,0xbe72,0,0xbe10,0,0x3d19,0,0x3e460000,0,0xbe720000,0,0xbe100000,0,0x3d190000,0,
0,0x3e46,0,0xbe72,0,0xbe10,0,0x3d19,0,0x3e460000,0,0xbe720000,0,0xbe100000,0,0x3d190000,
0x3e69,0,0xbe2d,0,0x3d97,0,0xbe2d,0,0x3e690000,0,0xbe2d0000,0,0x3d970000,0,0xbe2d0000,0,
0,0x3e69,0,0xbe2d,0,0x3d97,0,0xbe2d,0,0x3e690000,0,0xbe2d0000,0,0x3d970000,0,0xbe2d0000,
0xbd97,0,0x3dde,0,0x3e69,0,0xbe5a,0,0xbd970000,0,0x3dde0000,0,0x3e690000,0,0xbe5a0000,0,
0,0xbd97,0,0x3dde,0,0x3e69,0,0xbe5a,0,0xbd970000,0,0x3dde0000,0,0x3e690000,0,0xbe5a0000,
0xbe10,0,0x3e2d,0,0x3e46,0,0xbe2d,0,0xbe100000,0,0x3e2d0000,0,0x3e460000,0,0xbe2d0000,0,
0,0xbe10,0,0x3e2d,0,0x3e46,0,0xbe2d,0,0xbe100000,0,0x3e2d0000,0,0x3e460000,0,0xbe2d0000,
0xbe46,0,0xbe5a,0,0xbe10,0,0xbdde,0,0xbe460000,0,0xbe5a0000,0,0xbe100000,0,0xbdde0000,0,
0,0xbe46,0,0xbe5a,0,0xbe10,0,0xbdde,0,0xbe460000,0,0xbe5a0000,0,0xbe100000,0,0xbdde0000,
0xbe69,0,0xbe72,0,0xbd97,0,0xbd19,0,0xbe690000,0,0xbe720000,0,0xbd970000,0,0xbd190000,0,
0,0xbe69,0,0xbe72,0,0xbd97,0,0xbd19,0,0xbe690000,0,0xbe720000,0,0xbd970000,0,0xbd190000,
0x3d97,0,0xbd19,0,0xbe69,0,0xbe72,0,0x3d970000,0,0xbd190000,0,0xbe690000,0,0xbe720000,0,
0,0x3d97,0,0xbd19,0,0xbe69,0,0xbe72,0,0x3d970000,0,0xbd190000,0,0xbe690000,0,0xbe720000,
0xbe10,0,0xbe5a,0,0xbe46,0,0xbdde,0,0xbe100000,0,0xbe5a0000,0,0xbe460000,0,0xbdde0000,0,
0,0xbe10,0,0xbe5a,0,0xbe46,0,0xbdde,0,0xbe100000,0,0xbe5a0000,0,0xbe460000,0,0xbdde0000,
0x3e75,0,0x3e2d,0,0x8000,0,0xbe2d,0,0x3e750000,0,0x3e2d0000,0,0x80000000,0,0xbe2d0000,0,
0,0x3e75,0,0x3e2d,0,0x8000,0,0xbe2d,0,0x3e750000,0,0x3e2d0000,0,0x80000000,0,0xbe2d0000,
0,0,0xbe2d,0,0xbe75,0,0xbe2d,0,0,0,0xbe2d0000,0,0xbe750000,0,0xbe2d0000,0,
0,0,0,0xbe2d,0,0xbe75,0,0xbe2d,0,0,0,0xbe2d0000,0,0xbe750000,0,0xbe2d0000,
0x3d97,0,0x3e72,0,0x3e69,0,0x3d19,0,0x3d970000,0,0x3e720000,0,0x3e690000,0,0x3d190000,0,
0,0x3d97,0,0x3e72,0,0x3e69,0,0x3d19,0,0x3d970000,0,0x3e720000,0,0x3e690000,0,0x3d190000,
0x3e10,0,0xbdde,0,0xbe46,0,0xbe5a,0,0x3e100000,0,0xbdde0000,0,0xbe460000,0,0xbe5a0000,0,
0,0x3e10,0,0xbdde,0,0xbe46,0,0xbe5a,0,0x3e100000,0,0xbdde0000,0,0xbe460000,0,0xbe5a0000,
0xbe46,0,0x3dde,0,0x3e10,0,0x3e5a,0,0xbe460000,0,0x3dde0000,0,0x3e100000,0,0x3e5a0000,0,
0,0xbe46,0,0x3dde,0,0x3e10,0,0x3e5a,0,0xbe460000,0,0x3dde0000,0,0x3e100000,0,0x3e5a0000,
0x3e69,0,0xbd19,0,0xbd97,0,0xbe72,0,0x3e690000,0,0xbd190000,0,0xbd970000,0,0xbe720000,0,
0,0x3e69,0,0xbd19,0,0xbd97,0,0xbe72,0,0x3e690000,0,0xbd190000,0,0xbd970000,0,0xbe720000,
0xbe46,0,0xbdde,0,0xbe10,0,0x3e5a,0,0xbe460000,0,0xbdde0000,0,0xbe100000,0,0x3e5a0000,0,
0,0xbe46,0,0xbdde,0,0xbe10,0,0x3e5a,0,0xbe460000,0,0xbdde0000,0,0xbe100000,0,0x3e5a0000,
0x3e69,0,0x3d19,0,0x3d97,0,0xbe72,0,0x3e690000,0,0x3d190000,0,0x3d970000,0,0xbe720000,0,
0,0x3e69,0,0x3d19,0,0x3d97,0,0xbe72,0,0x3e690000,0,0x3d190000,0,0x3d970000,0,0xbe720000,
0x3d97,0,0xbe72,0,0xbe69,0,0x3d19,0,0x3d970000,0,0xbe720000,0,0xbe690000,0,0x3d190000,0,
0,0x3d97,0,0xbe72,0,0xbe69,0,0x3d19,0,0x3d970000,0,0xbe720000,0,0xbe690000,0,0x3d190000,
0x3e10,0,0x3dde,0,0x3e46,0,0xbe5a,0,0x3e100000,0,0x3dde0000,0,0x3e460000,0,0xbe5a0000,0,
0,0x3e10,0,0x3dde,0,0x3e46,0,0xbe5a,0,0x3e100000,0,0x3dde0000,0,0x3e460000,0,0xbe5a0000,
0x3e75,0,0xbe2d,0,0x8000,0,0xbe2d,0,0x3e750000,0,0xbe2d0000,0,0x80000000,0,0xbe2d0000,0,
0,0x3e75,0,0xbe2d,0,0x8000,0,0xbe2d,0,0x3e750000,0,0xbe2d0000,0,0x80000000,0,0xbe2d0000,
0,0,0x3e2d,0,0x3e75,0,0xbe2d,0,0,0,0x3e2d0000,0,0x3e750000,0,0xbe2d0000,0,
0,0,0,0x3e2d,0,0x3e75,0,0xbe2d,0,0,0,0x3e2d0000,0,0x3e750000,0,0xbe2d0000,
0x3d97,0,0x3d19,0,0x3e69,0,0xbe72,0,0x3d970000,0,0x3d190000,0,0x3e690000,0,0xbe720000,0,
0,0x3d97,0,0x3d19,0,0x3e69,0,0xbe72,0,0x3d970000,0,0x3d190000,0,0x3e690000,0,0xbe720000,
0xbe10,0,0x3e5a,0,0x3e46,0,0xbdde,0,0xbe100000,0,0x3e5a0000,0,0x3e460000,0,0xbdde0000,0,
0,0xbe10,0,0x3e5a,0,0x3e46,0,0xbdde,0,0xbe100000,0,0x3e5a0000,0,0x3e460000,0,0xbdde0000,
0xbe46,0,0x3e5a,0,0x3e10,0,0xbdde,0,0xbe460000,0,0x3e5a0000,0,0x3e100000,0,0xbdde0000,0,
0,0xbe46,0,0x3e5a,0,0x3e10,0,0xbdde,0,0xbe460000,0,0x3e5a0000,0,0x3e100000,0,0xbdde0000,
0xbe69,0,0x3e72,0,0x3d97,0,0xbd19,0,0xbe690000,0,0x3e720000,0,0x3d970000,0,0xbd190000,0,
0,0xbe69,0,0x3e72,0,0x3d97,0,0xbd19,0,0xbe690000,0,0x3e720000,0,0x3d970000,0,0xbd190000,
0x3eb7,0x3eb7,0x3eb7,0x3eb7,0x3eb78000,0x3eb78000,0x3eb78000,0x3eb78000,0x3eb7,0x3de23eae,0x3e573e94,0x3e943e57,0x3eb78000,0x3eaebde2,0x3e94be57,0x3e57be94,
0x3eb7,0x3e573e94,0x3eae3de2,0x3eaebde2,0x3eb78000,0x3e94be57,0x3de2beae,0xbde2beae,0x3eb7,0x3e943e57,0x3eaebde2,0x3de2beae,0x3eb78000,0x3e57be94,0xbde2beae,0xbeaebde2,
0x3eb7,0x3eb7,0x3eb7,0x3eb7,0x3eb78000,0x3eb78000,0x3eb78000,0x3eb78000,0x3eae3de2,0x3eb70000,0x3eaebde2,0x3e94be57,0x3de2beae,0xbeb7,0xbde2beae,0xbe57be94,
0x3e57be94,0xbeb7,0xbe57be94,0xbeaebde2,0xbe94be57,0xbeb78000,0xbe943e57,0xbde23eae,0xbe57be94,0xbeb70000,0xbe573e94,0x3de23eae,0xbe943e57,0x3eb7,0x3e943e57,0x3eaebde2,
0x3eb7,0x3eae3de2,0x3e57be94,0xbe57be94,0x3eb78000,0x3de2beae,0xbe94be57,0xbe943e57,0x3eb7,0x3eb70000,0xbeb7,0xbeb70000,0x3eb78000,0xbeb7,0xbeb78000,0x3eb7,
0x3eb7,0x3eaebde2,0xbe57be94,0xbe573e94,0x3eb78000,0xbde2beae,0xbe943e57,0x3e943e57,0x3eb7,0x3e94be57,0xbeaebde2,0x3de23eae,0x3eb78000,0xbe57be94,0xbde23eae,0x3eaebde2,
0xbeae3de2,0x3eb7,0x3eae3de2,0x3e57be94,0x3de23eae,0x3eb78000,0x3de2beae,0xbe94be57,0x3eb7,0x3eb70000,0xbeb7,0xbeb70000,0x3eb78000,0xbeb7,0xbeb78000,0x3eb7,
0x3eae3de2,0xbeb7,0xbeae3de2,0x3e573e94,0x3de2beae,0xbeb78000,0x3de23eae,0x3e94be57,0x3e57be94,0xbeb70000,0x3e573e94,0x3de2beae,0xbe94be57,0x3eb7,0x3e94be57,0xbeaebde2,
0x3eb7,0x3e57be94,0xbeae3de2,0x3eae3de2,0x3eb78000,0xbe94be57,0x3de23eae,0x3de2beae,0x3eb7,0x3de2beae,0xbe573e94,0x3e94be57,0x3eb78000,0xbeaebde2,0x3e943e57,0xbe57be94,
0x3eb7,0xbeb7,0x3eb7,0xbeb7,0x3eb78000,0xbeb78000,0x3eb78000,0xbeb78000,0x3eb7,0xbde2beae,0x3e573e94,0xbe94be57,0x3eb78000,0xbeae3de2,0x3e94be57,0xbe573e94,
0xbe57be94,0x3eb7,0x3e57be94,0xbeae3de2,0xbe943e57,0x3eb78000,0xbe94be57,0x3de23eae,0xbeae3de2,0x3eb70000,0xbeaebde2,0x3e943e57,0x3de23eae,0xbeb7,0xbde23eae,0x3e57be94,
0x3eb7,0xbeb7,0x3eb7,0xbeb7,0x3eb78000,0xbeb78000,0x3eb78000,0xbeb78000,0x3eae3de2,0xbeb70000,0x3eaebde2,0xbe943e57,0x3de2beae,0x3eb7,0xbde2beae,0x3e573e94,
0x3eb7,0xbe57be94,0x3eae3de2,0xbeae3de2,0x3eb78000,0xbe943e57,0x3de2beae,0x3de23eae,0x3eb7,0xbe94be57,0x3eaebde2,0xbde23eae,0x3eb78000,0xbe573e94,0xbde2beae,0x3eae3de2,
0x3eb7,0xbeaebde2,0x3e57be94,0x3e573e94,0x3eb78000,0xbde23eae,0xbe94be57,0x3e94be57,0x3eb7,0xbeb70000,0xbeb7,0x3eb70000,0x3eb78000,0x3eb7,0xbeb78000,0xbeb7,
0x3e57be94,0x3eb7,0xbe57be94,0x3eae3de2,0xbe94be57,0x3eb78000,0xbe943e57,0x3de2beae,0xbe57be94,0x3eb70000,0xbe573e94,0xbde2beae,0xbe943e57,0xbeb7,0x3e943e57,0xbeae3de2,
0xbeae3de2,0xbeb7,0x3eae3de2,0xbe573e94,0x3de23eae,0xbeb78000,0x3de2beae,0x3e943e57,0x3eb7,0xbeb70000,0xbeb7,0x3eb70000,0x3eb78000,0x3eb7,0xbeb78000,0xbeb7,
0x3eb7,0xbeae3de2,0xbe57be94,0x3e57be94,0x3eb78000,0x3de23eae,0xbe943e57,0xbe94be57,0x3eb7,0xbe943e57,0xbeaebde2,0xbde2beae,0x3eb78000,0x3e573e94,0xbde23eae,0xbeae3de2,
0x3eb7,0xbe573e94,0xbeae3de2,0xbeaebde2,0x3eb78000,0x3e943e57,0x3de23eae,0xbde23eae,0x3eb7,0xbde23eae,0xbe573e94,0xbe943e57,0x3eb78000,0x3eae3de2,0x3e943e57,0x3e573e94,
0x3eae3de2,0x3eb7,0xbeae3de2,0xbe57be94,0x3de2beae,0x3eb78000,0x3de23eae,0xbe943e57,0x3e57be94,0x3eb70000,0x3e573e94,0xbde23eae,0xbe94be57,0xbeb7,0x3e94be57,0x3eae3de2,
0xbe57be94,0xbeb7,0x3e57be94,0x3eaebde2,0xbe943e57,0xbeb78000,0xbe94be57,0xbde2beae,0xbeae3de2,0xbeb70000,0xbeaebde2,0xbe94be57,0x3de23eae,0x3eb7,0xbde23eae,0xbe573e94,
0x3eb7,0x3eb7,0x3eb7,0x3eb7,0x3eb78000,0x3eb78000,0x3eb78000,0x3eb78000,0x3e57be94,0x3de2beae,0xbeb7,0xbde2beae,0xbe94be57,0xbeaebde2,0xbeb78000,0xbeae3de2,
0xbeae3de2,0xbe573e94,0x3eb7,0x3e573e94,0x3de23eae,0x3e943e57,0x3eb78000,0x3e94be57,0x3eae3de2,0x3e94be57,0xbeb7,0xbe94be57,0x3de2beae,0xbe57be94,0xbeb78000,0xbe573e94,
0x3eb7,0x3eb7,0x3eb7,0x3eb7,0x3eb78000,0x3eb78000,0x3eb78000,0x3eb78000,0xbe57be94,0xbe94be57,0xbeaebde2,0xbeb70000,0xbe943e57,0xbe573e94,0xbde23eae,0x3eb7,
0x3eae3de2,0x3eaebde2,0x3e57be94,0xbeb7,0x3de2beae,0xbde2beae,0xbe94be57,0xbeb78000,0xbeae3de2,0xbde23eae,0x3e573e94,0x3eb70000,0x3de23eae,0x3eae3de2,0x3e94be57,0xbeb7,
0xbe57be94,0xbeae3de2,0x3eb7,0x3eae3de2,0xbe943e57,0x3de23eae,0x3eb78000,0x3de2beae,0x3eb7,0x3eb70000,0xbeb7,0xbeb70000,0x3eb78000,0xbeb7,0xbeb78000,0x3eb7,
0x3e57be94,0xbeaebde2,0x3eb7,0x3eaebde2,0xbe94be57,0xbde23eae,0x3eb78000,0xbde2beae,0xbeae3de2,0x3e943e57,0xbeb7,0xbe943e57,0x3de23eae,0x3e57be94,0xbeb78000,0x3e573e94,
0x3e57be94,0xbe57be94,0xbeae3de2,0x3eb7,0xbe94be57,0xbe943e57,0x3de23eae,0x3eb78000,0x3eb7,0x3eb70000,0xbeb7,0xbeb70000,0x3eb78000,0xbeb7,0xbeb78000,0x3eb7,
0xbe57be94,0xbe573e94,0x3eae3de2,0xbeb7,0xbe943e57,0x3e943e57,0x3de2beae,0xbeb78000,0x3eae3de2,0xbde2beae,0xbe573e94,0x3eb70000,0x3de2beae,0xbeae3de2,0x3e943e57,0xbeb7,
0x3eae3de2,0xbe57be94,0x3eb7,0x3e57be94,0x3de2beae,0xbe943e57,0x3eb78000,0xbe94be57,0xbe57be94,0x3de23eae,0xbeb7,0xbde23eae,0xbe943e57,0x3eaebde2,0xbeb78000,0x3eae3de2,
0x3eb7,0xbeb7,0x3eb7,0xbeb7,0x3eb78000,0xbeb78000,0x3eb78000,0xbeb78000,0x3e57be94,0xbde23eae,0xbeb7,0x3de23eae,0xbe94be57,0x3eae3de2,0xbeb78000,0x3eaebde2,
0xbeae3de2,0x3eae3de2,0xbe57be94,0x3eb7,0x3de23eae,0x3de2beae,0xbe943e57,0x3eb78000,0x3e57be94,0xbe943e57,0x3eaebde2,0xbeb70000,0xbe94be57,0x3e573e94,0xbde2beae,0x3eb7,
0x3eb7,0xbeb7,0x3eb7,0xbeb7,0x3eb78000,0xbeb78000,0x3eb78000,0xbeb78000,0xbe57be94,0x3e943e57,0xbeaebde2,0x3eb70000,0xbe943e57,0x3e57be94,0xbde23eae,0xbeb7,
0xbeae3de2,0x3e57be94,0x3eb7,0xbe57be94,0x3de23eae,0xbe94be57,0x3eb78000,0xbe943e57,0x3eae3de2,0xbe943e57,0xbeb7,0x3e943e57,0x3de2beae,0x3e573e94,0xbeb78000,0x3e57be94,
0xbe57be94,0x3eaebde2,0x3eb7,0xbeaebde2,0xbe943e57,0xbde2beae,0x3eb78000,0xbde23eae,0x3eb7,0xbeb70000,0xbeb7,0x3eb70000,0x3eb78000,0x3eb7,0xbeb78000,0xbeb7,
0x3eae3de2,0xbeae3de2,0x3e57be94,0x3eb7,0x3de2beae,0x3de23eae,0xbe94be57,0x3eb78000,0xbeae3de2,0x3de2beae,0x3e573e94,0xbeb70000,0x3de23eae,0xbeaebde2,0x3e94be57,0x3eb7,
0x3e57be94,0x3e573e94,0xbeae3de2,0xbeb7,0xbe94be57,0x3e94be57,0x3de23eae,0xbeb78000,0x3eb7,0xbeb70000,0xbeb7,0x3eb70000,0x3eb78000,0x3eb7,0xbeb78000,0xbeb7,
0x3e57be94,0x3eae3de2,0x3eb7,0xbeae3de2,0xbe94be57,0x3de2beae,0x3eb78000,0x3de23eae,0xbeae3de2,0xbe94be57,0xbeb7,0x3e94be57,0x3de23eae,0xbe573e94,0xbeb78000,0xbe57be94,
0x3eae3de2,0x3e573e94,0x3eb7,0xbe573e94,0x3de2beae,0x3e94be57,0x3eb78000,0x3e943e57,0xbe57be94,0xbde2beae,0xbeb7,0x3de2beae,0xbe943e57,0xbeae3de2,0xbeb78000,0xbeaebde2,
0xbe57be94,0x3e57be94,0x3eae3de2,0x3eb7,0xbe943e57,0xbe94be57,0x3de2beae,0x3eb78000,0x3eae3de2,0x3de23eae,0xbe573e94,0xbeb70000,0x3de2beae,0x3eaebde2,0x3e943e57,0x3eb7,
0xbeae3de2,0xbeaebde2,0xbe57be94,0xbeb7,0x3de23eae,0xbde23eae,0xbe943e57,0xbeb78000,0x3e57be94,0x3e94be57,0x3eaebde2,0x3eb70000,0xbe94be57,0xbe57be94,0xbde2beae,0xbeb7,
0x3eb7,0x3eb7,0x3eb7,0x3eb7,0x3eb78000,0x3eb78000,0x3eb78000,0x3eb78000,0xbeae3de2,0xbe943e57,0xbe573e94,0xbde23eae,0x3de23eae,0x3e573e94,0x3e943e57,0x3eae3de2,
0xbe57be94,0xbeaebde2,0xbeae3de2,0xbe573e94,0xbe943e57,0xbde23eae,0x3de23eae,0x3e943e57,0x3e57be94,0xbde2beae,0xbeaebde2,0xbe943e57,0xbe94be57,0xbeae3de2,0xbde23eae,0x3e573e94,
0,0,0,0,0,0,0,0,0,0,0,0,0,0,0,0,
0,0,0,0,0,0,0,0,0,0,0,0,0,0,0,0,
0x3eae3de2,0x3e57be94,0xbe57be94,0xbeae3de2,0x3de2beae,0xbe94be57,0xbe943e57,0x3de23eae,0x3eb7,0x3eb70000,0xbeb7,0xbeb70000,0x3eb78000,0xbeb7,0xbeb78000,0x3eb7,
0xbeae3de2,0x3e573e94,0x3e57be94,0xbeaebde2,0x3de23eae,0x3e94be57,0xbe94be57,0xbde23eae,0xbe57be94,0xbde23eae,0x3eaebde2,0xbe94be57,0xbe943e57,0x3eae3de2,0xbde2beae,0xbe573e94,
0,0,0,0,0,0,0,0,0,0,0,0,0,0,0,0,
0,0,0,0,0,0,0,0,0,0,0,0,0,0,0,0,
0x3e57be94,0xbeae3de2,0x3eae3de2,0xbe57be94,0xbe94be57,0x3de23eae,0x3de2beae,0xbe943e57,0x3eae3de2,0xbe94be57,0x3e573e94,0xbde2beae,0x3de2beae,0xbe573e94,0x3e94be57,0xbeae3de2,
0x3eb7,0xbeb7,0x3eb7,0xbeb7,0x3eb78000,0xbeb78000,0x3eb78000,0xbeb78000,0xbeae3de2,0x3e94be57,0xbe573e94,0x3de2beae,0x3de23eae,0xbe57be94,0x3e943e57,0xbeaebde2,
0,0,0,0,0,0,0,0,0,0,0,0,0,0,0,0,
0,0,0,0,0,0,0,0,0,0,0,0,0,0,0,0,
0xbe57be94,0x3eae3de2,0xbeae3de2,0x3e57be94,0xbe943e57,0x3de2beae,0x3de23eae,0xbe94be57,0x3e57be94,0x3de23eae,0xbeaebde2,0x3e94be57,0xbe94be57,0x3eaebde2,0xbde23eae,0xbe57be94,
0x3eae3de2,0xbe573e94,0xbe57be94,0x3eaebde2,0x3de2beae,0x3e943e57,0xbe943e57,0xbde2beae,0x3eb7,0xbeb70000,0xbeb7,0x3eb70000,0x3eb78000,0x3eb7,0xbeb78000,0xbeb7,
0,0,0,0,0,0,0,0,0,0,0,0,0,0,0,0,
0,0,0,0,0,0,0,0,0,0,0,0,0,0,0,0,
0xbeae3de2,0xbe57be94,0x3e57be94,0x3eae3de2,0x3de23eae,0xbe943e57,0xbe94be57,0x3de2beae,0xbe57be94,0x3de2beae,0x3eaebde2,0x3e943e57,0xbe943e57,0xbeaebde2,0xbde2beae,0x3e57be94,
0x3e57be94,0x3eaebde2,0x3eae3de2,0x3e573e94,0xbe94be57,0xbde2beae,0x3de2beae,0x3e94be57,0x3eae3de2,0x3e943e57,0x3e573e94,0x3de23eae,0x3de2beae,0x3e57be94,0x3e94be57,0x3eaebde2,
0,0,0,0,0,0,0,0,0,0,0,0,0,0,0,0,
0,0,0,0,0,0,0,0,0,0,0,0,0,0,0,0,
0,0,0,0,0,0,0,0,0,0,0,0,0,0,0,0,
0,0,0,0,0,0,0,0,0,0,0,0,0,0,0,0,
0x3eb7,0x3eb7,0x3eb7,0x3eb7,0x3eb78000,0x3eb78000,0x3eb78000,0x3eb78000,0xbeae3de2,0xbe943e57,0xbe573e94,0xbde23eae,0x3de23eae,0x3e573e94,0x3e943e57,0x3eae3de2,
0xbe57be94,0xbeaebde2,0xbeae3de2,0xbe573e94,0xbe943e57,0xbde23eae,0x3de23eae,0x3e943e57,0x3e57be94,0xbde2beae,0xbeaebde2,0xbe943e57,0xbe94be57,0xbeae3de2,0xbde23eae,0x3e573e94,
0,0,0,0,0,0,0,0,0,0,0,0,0,0,0,0,
0,0,0,0,0,0,0,0,0,0,0,0,0,0,0,0,
0x3eae3de2,0x3e57be94,0xbe57be94,0xbeae3de2,0x3de2beae,0xbe94be57,0xbe943e57,0x3de23eae,0x3eb7,0x3eb70000,0xbeb7,0xbeb70000,0x3eb78000,0xbeb7,0xbeb78000,0x3eb7,
0xbeae3de2,0x3e573e94,0x3e57be94,0xbeaebde2,0x3de23eae,0x3e94be57,0xbe94be57,0xbde23eae,0xbe57be94,0xbde23eae,0x3eaebde2,0xbe94be57,0xbe943e57,0x3eae3de2,0xbde2beae,0xbe573e94,
0,0,0,0,0,0,0,0,0,0,0,0,0,0,0,0,
0,0,0,0,0,0,0,0,0,0,0,0,0,0,0,0,
0x3e57be94,0xbeae3de2,0x3eae3de2,0xbe57be94,0xbe94be57,0x3de23eae,0x3de2beae,0xbe943e57,0x3eae3de2,0xbe94be57,0x3e573e94,0xbde2beae,0x3de2beae,0xbe573e94,0x3e94be57,0xbeae3de2,
0x3eb7,0xbeb7,0x3eb7,0xbeb7,0x3eb78000,0xbeb78000,0x3eb78000,0xbeb78000,0xbeae3de2,0x3e94be57,0xbe573e94,0x3de2beae,0x3de23eae,0xbe57be94,0x3e943e57,0xbeaebde2,
0,0,0,0,0,0,0,0,0,0,0,0,0,0,0,0,
0,0,0,0,0,0,0,0,0,0,0,0,0,0,0,0,
0xbe57be94,0x3eae3de2,0xbeae3de2,0x3e57be94,0xbe943e57,0x3de2beae,0x3de23eae,0xbe94be57,0x3e57be94,0x3de23eae,0xbeaebde2,0x3e94be57,0xbe94be57,0x3eaebde2,0xbde23eae,0xbe57be94,
0x3eae3de2,0xbe573e94,0xbe57be94,0x3eaebde2,0x3de2beae,0x3e943e57,0xbe943e57,0xbde2beae,0x3eb7,0xbeb70000,0xbeb7,0x3eb70000,0x3eb78000,0x3eb7,0xbeb78000,0xbeb7,
0,0,0,0,0,0,0,0,0,0,0,0,0,0,0,0,
0,0,0,0,0,0,0,0,0,0,0,0,0,0,0,0,
0xbeae3de2,0xbe57be94,0x3e57be94,0x3eae3de2,0x3de23eae,0xbe943e57,0xbe94be57,0x3de2beae,0xbe57be94,0x3de2beae,0x3eaebde2,0x3e943e57,0xbe943e57,0xbeaebde2,0xbde2beae,0x3e57be94,
0x3e57be94,0x3eaebde2,0x3eae3de2,0x3e573e94,0xbe94be57,0xbde2beae,0x3de2beae,0x3e94be57,0x3eae3de2,0x3e943e57,0x3e573e94,0x3de23eae,0x3de2beae,0x3e57be94,0x3e94be57,0x3eaebde2,
};
__device__ __align__(128) const uint32_t TAB_P3[4288] = {
0,0,0,0,0,0,0,0,0,0,0,0,0,0,0,0,
0x80003e83,0xbe79bda2,0x3e1abe54,0x3e1a3e54,0x3e830000,0xbda23e79,0xbe54be1a,0x3e54be1a,0x80003e83,0xbe54be1a,0x3e79bda2,0xbda23e79,0x3e830000,0xbe1a3e54,0xbda2be79,0x3e793da2,
0,0,0,0,0,0,0,0,0,0,0,0,0,0,0,0,
0xbe793da2,0x8000be83,0x3e793da2,0xbe1a3e54,0x3da23e79,0xbe830000,0x3da2be79,0x3e543e1a,0xbe1abe54,0x3e830000,0xbe1a3e54,0xbda2be79,0xbe543e1a,0xbe83,0x3e543e1a,0xbe793da2,
0x80003e83,0xbe1abe54,0x3e793da2,0xbe793da2,0x3e830000,0xbe543e1a,0x3da2be79,0x3da23e79,0x80003e83,0xbda2be79,0x3e1a3e54,0xbe54be1a,0x3e830000,0xbe793da2,0x3e54be1a,0xbe1a3e54,
0x80003e83,0x8000be83,0x80003e83,0x8000be83,0x3e830000,0xbe830000,0x3e830000,0xbe830000,0x80003e83,0x3da2be79,0xbe1a3e54,0x3e54be1a,0x3e830000,0xbe79bda2,0x3e543e1a,0xbe1abe54,
0x3e1abe54,0x80003e83,0xbe1abe54,0x3e793da2,0xbe54be1a,0x3e830000,0xbe543e1a,0x3da2be79,0x3e793da2,0xbe830000,0x3e79bda2,0xbe543e1a,0x3da2be79,0x3e83,0xbda2be79,0x3e1a3e54,
0x80003e83,0x8000be83,0x80003e83,0x8000be83,0x3e830000,0xbe830000,0x3e830000,0xbe830000,0xbe793da2,0x3e830000,0xbe79bda2,0x3e543e1a,0x3da23e79,0xbe83,0xbda23e79,0x3e1abe54,
0x80003e83,0x3e1abe54,0xbe793da2,0x3e793da2,0x3e830000,0xbe54be1a,0x3da23e79,0x3da2be79,0x80003e83,0x3e54be1a,0xbe79bda2,0x3da23e79,0x3e830000,0xbe1abe54,0xbda23e79,0x3e79bda2,
0x80003e83,0x3e79bda2,0xbe1abe54,0xbe1a3e54,0x3e830000,0xbda2be79,0xbe543e1a,0x3e543e1a,0x80003e83,0x3e830000,0x8000be83,0xbe830000,0x3e830000,0xbe83,0xbe830000,0x3e83,
0xbe1abe54,0x80003e83,0x3e1abe54,0xbe793da2,0xbe543e1a,0x3e830000,0xbe54be1a,0x3da23e79,0x3e1abe54,0xbe830000,0x3e1a3e54,0x3da2be79,0xbe54be1a,0x3e83,0x3e54be1a,0xbe79bda2,
0x3e793da2,0x8000be83,0xbe793da2,0x3e1a3e54,0x3da2be79,0xbe830000,0x3da23e79,0x3e54be1a,0x80003e83,0x3e830000,0x8000be83,0xbe830000,0x3e830000,0xbe83,0xbe830000,0x3e83,
0x80003e83,0x3e793da2,0x3e1abe54,0xbe1abe54,0x3e830000,0x3da2be79,0xbe54be1a,0xbe543e1a,0x80003e83,0x3e543e1a,0x3e79bda2,0x3da2be79,0x3e830000,0x3e1abe54,0xbda2be79,0xbe79bda2,
0x80003e83,0x3e1a3e54,0x3e793da2,0x3e79bda2,0x3e830000,0x3e54be1a,0x3da2be79,0xbda2be79,0x80003e83,0x3da23e79,0x3e1a3e54,0x3e543e1a,0x3e830000,0x3e79bda2,0x3e54be1a,0x3e1abe54,
0xbe793da2,0x80003e83,0x3e793da2,0x3e1abe54,0x3da23e79,0x3e830000,0x3da2be79,0xbe54be1a,0xbe1abe54,0xbe830000,0xbe1a3e54,0x3da23e79,0xbe543e1a,0x3e83,0x3e543e1a,0x3e79bda2,
0x3e1abe54,0x8000be83,0xbe1abe54,0xbe79bda2,0xbe54be1a,0xbe830000,0xbe543e1a,0xbda23e79,0x3e793da2,0x3e830000,0x3e79bda2,0x3e54be1a,0x3da2be79,0xbe83,0xbda2be79,0xbe1abe54,
0,0,0,0,0,0,0,0,0,0,0,0,0,0,0,0,
0,0,0,0,0,0,0,0,0,0,0,0,0,0,0,0,
0,0,0,0,0,0,0,0,0,0,0,0,0,0,0,0,
0xbe1abe54,0x3e79bda2,0x80003e83,0xbe79bda2,0xbe543e1a,0xbda2be79,0x3e830000,0xbda23e79,0x3e793da2,0xbe543e1a,0x8000be83,0x3e543e1a,0x3da2be79,0x3e1a3e54,0xbe830000,0x3e1abe54,
0,0,0,0,0,0,0,0,0,0,0,0,0,0,0,0,
0,0,0,0,0,0,0,0,0,0,0,0,0,0,0,0,
0xbe793da2,0x3e1abe54,0x80003e83,0xbe1abe54,0x3da23e79,0xbe54be1a,0x3e830000,0xbe543e1a,0x3e1abe54,0xbda23e79,0x8000be83,0x3da23e79,0xbe54be1a,0x3e793da2,0xbe830000,0x3e79bda2,
0x80003e83,0x8000be83,0x80003e83,0x8000be83,0x3e830000,0xbe830000,0x3e830000,0xbe830000,0xbe1abe54,0x3da23e79,0x8000be83,0xbda23e79,0xbe543e1a,0x3e79bda2,0xbe830000,0x3e793da2,
0,0,0,0,0,0,0,0,0,0,0,0,0,0,0,0,
0,0,0,0,0,0,0,0,0,0,0,0,0,0,0,0,
0x3e793da2,0xbe1abe54,0x80003e83,0x3e1abe54,0x3da2be79,0xbe543e1a,0x3e830000,0xbe54be1a,0xbe793da2,0x3e543e1a,0x8000be83,0xbe543e1a,0x3da23e79,0x3e1abe54,0xbe830000,0x3e1a3e54,
0x3e1abe54,0xbe79bda2,0x80003e83,0x3e79bda2,0xbe54be1a,0xbda23e79,0x3e830000,0xbda2be79,0x80003e83,0x3e830000,0x8000be83,0xbe830000,0x3e830000,0xbe83,0xbe830000,0x3e83,
0,0,0,0,0,0,0,0,0,0,0,0,0,0,0,0,
0,0,0,0,0,0,0,0,0,0,0,0,0,0,0,0,
0xbe1abe54,0xbe793da2,0x80003e83,0x3e793da2,0xbe543e1a,0x3da23e79,0x3e830000,0x3da2be79,0x3e793da2,0x3e54be1a,0x8000be83,0xbe54be1a,0x3da2be79,0xbe1abe54,0xbe830000,0xbe1a3e54,
0xbe793da2,0xbe1a3e54,0x80003e83,0x3e1a3e54,0x3da23e79,0x3e543e1a,0x3e830000,0x3e54be1a,0x3e1abe54,0x3da2be79,0x8000be83,0xbda2be79,0xbe54be1a,0xbe79bda2,0xbe830000,0xbe793da2,
0,0,0,0,0,0,0,0,0,0,0,0,0,0,0,0,
0x3e1abe54,0x3e1a3e54,0xbe793da2,0x8000be83,0xbe54be1a,0x3e54be1a,0x3da23e79,0xbe830000,0xbe793da2,0x3da2be79,0x3e1a3e54,0xbe830000,0x3da23e79,0xbe79bda2,0x3e54be1a,0x3e83,
0,0,0,0,0,0,0,0,0,0,0,0,0,0,0,0,
0x3e793da2,0xbe1a3e54,0xbe1abe54,0x3e79bda2,0x3da2be79,0x3e543e1a,0xbe543e1a,0xbda2be79,0x3e1abe54,0x3da23e79,0xbe79bda2,0x3e54be1a,0xbe54be1a,0x3e79bda2,0xbda23e79,0xbe1abe54,
0x3e793da2,0xbe793da2,0x3e1abe54,0x80003e83,0x3da2be79,0x3da23e79,0xbe54be1a,0x3e830000,0xbe1abe54,0x3e543e1a,0xbe79bda2,0x3e830000,0xbe543e1a,0x3e1abe54,0xbda23e79,0xbe83,
0x80003e83,0x8000be83,0x80003e83,0x8000be83,0x3e830000,0xbe830000,0x3e830000,0xbe830000,0x3e1abe54,0xbe543e1a,0x3e79bda2,0xbe830000,0xbe54be1a,0x3e1a3e54,0xbda2be79,0x3e83,
0xbe1abe54,0x3e793da2,0xbe793da2,0x3e1abe54,0xbe543e1a,0x3da2be79,0x3da23e79,0xbe54be1a,0xbe793da2,0x3e54be1a,0xbe1a3e54,0x3da2be79,0x3da23e79,0xbe1abe54,0x3e543e1a,0xbe79bda2,
0x80003e83,0x8000be83,0x80003e83,0x8000be83,0x3e830000,0xbe830000,0x3e830000,0xbe830000,0x3e793da2,0xbe54be1a,0x3e1a3e54,0xbda2be79,0x3da2be79,0xbe1a3e54,0x3e54be1a,0xbe793da2,
0xbe793da2,0x3e793da2,0xbe1abe54,0x80003e83,0x3da23e79,0x3da2be79,0xbe543e1a,0x3e830000,0x3e793da2,0xbda2be79,0xbe1a3e54,0x3e830000,0x3da2be79,0xbe793da2,0x3e543e1a,0xbe83,
0xbe1abe54,0xbe1a3e54,0x3e793da2,0x8000be83,0xbe543e1a,0x3e543e1a,0x3da2be79,0xbe830000,0x80003e83,0x3e830000,0x8000be83,0xbe830000,0x3e830000,0xbe83,0xbe830000,0x3e83,
0x3e1abe54,0xbe793da2,0x3e793da2,0xbe1abe54,0xbe54be1a,0x3da23e79,0x3da2be79,0xbe543e1a,0xbe1abe54,0xbda23e79,0x3e79bda2,0xbe54be1a,0xbe543e1a,0x3e793da2,0xbda2be79,0xbe1a3e54,
0xbe793da2,0x3e1a3e54,0x3e1abe54,0xbe79bda2,0x3da23e79,0x3e54be1a,0xbe54be1a,0xbda23e79,0x80003e83,0x3e830000,0x8000be83,0xbe830000,0x3e830000,0xbe83,0xbe830000,0x3e83,
0x3e1abe54,0xbe1abe54,0xbe793da2,0x80003e83,0xbe54be1a,0xbe543e1a,0x3da23e79,0x3e830000,0xbe793da2,0xbda23e79,0x3e1a3e54,0x3e830000,0x3da23e79,0x3e793da2,0x3e54be1a,0xbe83,
0x3e793da2,0x3e79bda2,0x3e1abe54,0x8000be83,0x3da2be79,0xbda2be79,0xbe54be1a,0xbe830000,0xbe1abe54,0xbe54be1a,0xbe79bda2,0xbe830000,0xbe543e1a,0xbe1a3e54,0xbda23e79,0x3e83,
0x3e793da2,0x3e1abe54,0xbe1abe54,0xbe793da2,0x3da2be79,0xbe54be1a,0xbe543e1a,0x3da23e79,0x3e1abe54,0xbda2be79,0xbe79bda2,0xbe543e1a,0xbe54be1a,0xbe793da2,0xbda23e79,0x3e1a3e54,
0xbe1abe54,0xbe79bda2,0xbe793da2,0xbe1a3e54,0xbe543e1a,0xbda23e79,0x3da23e79,0x3e543e1a,0xbe793da2,0xbe543e1a,0xbe1a3e54,0xbda23e79,0x3da23e79,0x3e1a3e54,0x3e543e1a,0x3e793da2,
0xbe163dda,0,0,0,0,0xbe163dda,0,0,0,0,0xbe163dda,0,0,0,0,0xbe163dda,
0xbe253da8,0,0,0,0,0xbe253da8,0,0,0,0,0xbe253da8,0,0,0,0,0xbe253da8,
0xbd65be30,0,0,0,0,0xbd65be30,0,0,0,0,0xbd65be30,0,0,0,0,0xbd65be30,
0x3ce8be37,0,0,0,0,0x3ce8be37,0,0,0,0,0x3ce8be37,0,0,0,0,0x3ce8be37,
0xbe303d65,0,0,0,0,0xbe303d65,0,0,0,0,0xbe303d65,0,0,0,0,0xbe303d65,
0xbe373ce8,0,0,0,0,0xbe373ce8,0,0,0,0,0xbe373ce8,0,0,0,0,0xbe373ce8,
0x3ddabe16,0,0,0,0,0x3ddabe16,0,0,0,0,0x3ddabe16,0,0,0,0,0x3ddabe16,
0x3e25bda8,0,0,0,0,0x3e25bda8,0,0,0,0,0x3e25bda8,0,0,0,0,0x3e25bda8,
0xbe390000,0,0,0,0,0xbe390000,0,0,0,0,0xbe390000,0,0,0,0,0xbe390000,
0xbe37bce8,0,0,0,0,0xbe37bce8,0,0,0,0,0xbe37bce8,0,0,0,0,0xbe37bce8,
0x3e390000,0,0,0,0,0x3e390000,0,0,0,0,0x3e390000,0,0,0,0,0x3e390000,
0x3e253da8,0,0,0,0,0x3e253da8,0,0,0,0,0x3e253da8,0,0,0,0,0x3e253da8,
0xbe30bd65,0,0,0,0,0xbe30bd65,0,0,0,0,0xbe30bd65,0,0,0,0,0xbe30bd65,
0xbe25bda8,0,0,0,0,0xbe25bda8,0,0,0,0,0xbe25bda8,0,0,0,0,0xbe25bda8,
0x3dda3e16,0,0,0,0,0x3dda3e16,0,0,0,0,0x3dda3e16,0,0,0,0,0x3dda3e16,
0x3ce83e37,0,0,0,0,0x3ce83e37,0,0,0,0,0x3ce83e37,0,0,0,0,0x3ce83e37,
0xbe16bdda,0,0,0,0,0xbe16bdda,0,0,0,0,0xbe16bdda,0,0,0,0,0xbe16bdda,
0xbe03be03,0,0,0,0,0xbe03be03,0,0,0,0,0xbe03be03,0,0,0,0,0xbe03be03,
0xbd653e30,0,0,0,0,0xbd653e30,0,0,0,0,0xbd653e30,0,0,0,0,0xbd653e30,
0xbe033e03,0,0,0,0,0xbe033e03,0,0,0,0,0xbe033e03,0,0,0,0,0xbe033e03,
0xbddabe16,0,0,0,0,0xbddabe16,0,0,0,0,0xbddabe16,0,0,0,0,0xbddabe16,
0xbda8be25,0,0,0,0,0xbda8be25,0,0,0,0,0xbda8be25,0,0,0,0,0xbda8be25,
0xbe303d65,0,0,0,0,0xbe303d65,0,0,0,0,0xbe303d65,0,0,0,0,0xbe303d65,
0xbe37bce8,0,0,0,0,0xbe37bce8,0,0,0,0,0xbe37bce8,0,0,0,0,0xbe37bce8,
0xbd65be30,0,0,0,0,0xbd65be30,0,0,0,0,0xbd65be30,0,0,0,0,0xbd65be30,
0xbce8be37,0,0,0,0,0xbce8be37,0,0,0,0,0xbce8be37,0,0,0,0,0xbce8be37,
0xbe16bdda,0,0,0,0,0xbe16bdda,0,0,0,0,0xbe16bdda,0,0,0,0,0xbe16bdda,
0xbda8be25,0,0,0,0,0xbda8be25,0,0,0,0,0xbda8be25,0,0,0,0,0xbda8be25,
0x3e390000,0,0,0,0,0x3e390000,0,0,0,0,0x3e390000,0,0,0,0,0x3e390000,
0x3e033e03,0,0,0,0,0x3e033e03,0,0,0,0,0x3e033e03,0,0,0,0,0x3e033e03,
0xbd653e30,0,0,0,0,0xbd653e30,0,0,0,0,0xbd653e30,0,0,0,0,0xbd653e30,
0xbe373ce8,0,0,0,0,0xbe373ce8,0,0,0,0,0xbe373ce8,0,0,0,0,0xbe373ce8,
0x80003e39,0,0,0,0,0x80003e39,0,0,0,0,0x80003e39,0,0,0,0,0x80003e39,
0xbe033e03,0,0,0,0,0xbe033e03,0,0,0,0,0xbe033e03,0,0,0,0,0xbe033e03,
0xbddabe16,0,0,0,0,0xbddabe16,0,0,0,0,0xbddabe16,0,0,0,0,0xbddabe16,
0x3da8be25,0,0,0,0,0x3da8be25,0,0,0,0,0x3da8be25,0,0,0,0,0x3da8be25,
0xbe390000,0,0,0,0,0xbe390000,0,0,0,0,0xbe390000,0,0,0,0,0xbe390000,
0xbe03be03,0,0,0,0,0xbe03be03,0,0,0,0,0xbe03be03,0,0,0,0,0xbe03be03,
0x3e390000,0,0,0,0,0x3e390000,0,0,0,0,0x3e390000,0,0,0,0,0x3e390000,
0x3da83e25,0,0,0,0,0x3da83e25,0,0,0,0,0x3da83e25,0,0,0,0,0x3da83e25,
0x8000be39,0,0,0,0,0x8000be39,0,0,0,0,0x8000be39,0,0,0,0,0x8000be39,
0x3e03be03,0,0,0,0,0x3e03be03,0,0,0,0,0x3e03be03,0,0,0,0,0x3e03be03,
0xbdda3e16,0,0,0,0,0xbdda3e16,0,0,0,0,0xbdda3e16,0,0,0,0,0xbdda3e16,
0xbe37bce8,0,0,0,0,0xbe37bce8,0,0,0,0,0xbe37bce8,0,0,0,0,0xbe37bce8,
0x3e390000,0,0,0,0,0x3e390000,0,0,0,0,0x3e390000,0,0,0,0,0x3e390000,
0x3e033e03,0,0,0,0,0x3e033e03,0,0,0,0,0x3e033e03,0,0,0,0,0x3e033e03,
0xbd65be30,0,0,0,0,0xbd65be30,0,0,0,0,0xbd65be30,0,0,0,0,0xbd65be30,
0x3e03be03,0,0,0,0,0x3e03be03,0,0,0,0,0x3e03be03,0,0,0,0,0x3e03be03,
0x80003e39,0,0,0,0,0x80003e39,0,0,0,0,0x80003e39,0,0,0,0,0x80003e39,
0xbe033e03,0,0,0,0,0xbe033e03,0,0,0,0,0xbe033e03,0,0,0,0,0xbe033e03,
0x3e303d65,0,0,0,0,0x3e303d65,0,0,0,0,0x3e303d65,0,0,0,0,0x3e303d65,
0x3ce83e37,0,0,0,0,0x3ce83e37,0,0,0,0,0x3ce83e37,0,0,0,0,0x3ce83e37,
0xbe390000,0,0,0,0,0xbe390000,0,0,0,0,0xbe390000,0,0,0,0,0xbe390000,
0xbe03be03,0,0,0,0,0xbe03be03,0,0,0,0,0xbe03be03,0,0,0,0,0xbe03be03,
0xbe163dda,0,0,0,0,0xbe163dda,0,0,0,0,0xbe163dda,0,0,0,0,0xbe163dda,
0xbe25bda8,0,0,0,0,0xbe25bda8,0,0,0,0,0xbe25bda8,0,0,0,0,0xbe25bda8,
0xbe16bdda,0,0,0,0,0xbe16bdda,0,0,0,0,0xbe16bdda,0,0,0,0,0xbe16bdda,
0x3da8be25,0,0,0,0,0x3da8be25,0,0,0,0,0x3da8be25,0,0,0,0,0x3da8be25,
0x3e16bdda,0,0,0,0,0x3e16bdda,0,0,0,0,0x3e16bdda,0,0,0,0,0x3e16bdda,
0x3da83e25,0,0,0,0,0x3da83e25,0,0,0,0,0x3da83e25,0,0,0,0,0x3da83e25,
0x3e303d65,0,0,0,0,0x3e303d65,0,0,0,0,0x3e303d65,0,0,0,0,0x3e303d65,
0xbce83e37,0,0,0,0,0xbce83e37,0,0,0,0,0xbce83e37,0,0,0,0,0xbce83e37,
0xbe303d65,0,0,0,0,0xbe303d65,0,0,0,0,0xbe303d65,0,0,0,0,0xbe303d65,
0xbce8be37,0,0,0,0,0xbce8be37,0,0,0,0,0xbce8be37,0,0,0,0,0xbce8be37,
0xbe390000,0,0,0,0,0xbe390000,0,0,0,0,0xbe390000,0,0,0,0,0xbe390000,
0xbce8be37,0,0,0,0,0xbce8be37,0,0,0,0,0xbce8be37,0,0,0,0,0xbce8be37,
0x3e390000,0,0,0,0,0x3e390000,0,0,0,0,0x3e390000,0,0,0,0,0x3e390000,
0xbce83e37,0,0,0,0,0xbce83e37,0,0,0,0,0xbce83e37,0,0,0,0,0xbce83e37,
0x3e30bd65,0,0,0,0,0x3e30bd65,0,0,0,0,0x3e30bd65,0,0,0,0,0x3e30bd65,
0x3da83e25,0,0,0,0,0x3da83e25,0,0,0,0,0x3da83e25,0,0,0,0,0x3da83e25,
0xbe30bd65,0,0,0,0,0xbe30bd65,0,0,0,0,0xbe30bd65,0,0,0,0,0xbe30bd65,
0x3da8be25,0,0,0,0,0x3da8be25,0,0,0,0,0x3da8be25,0,0,0,0,0x3da8be25,
0xbe163dda,0,0,0,0,0xbe163dda,0,0,0,0,0xbe163dda,0,0,0,0,0xbe163dda,
0xbe03be03,0,0,0,0,0xbe03be03,0,0,0,0,0xbe03be03,0,0,0,0,0xbe03be03,
0x3e163dda,0,0,0,0,0x3e163dda,0,0,0,0,0x3e163dda,0,0,0,0,0x3e163dda,
0xbe033e03,0,0,0,0,0xbe033e03,0,0,0,0,0xbe033e03,0,0,0,0,0xbe033e03,
0x3ddabe16,0,0,0,0,0x3ddabe16,0,0,0,0,0x3ddabe16,0,0,0,0,0x3ddabe16,
0x3e253da8,0,0,0,0,0x3e253da8,0,0,0,0,0x3e253da8,0,0,0,0,0x3e253da8,
0xbddabe16,0,0,0,0,0xbddabe16,0,0,0,0,0xbddabe16,0,0,0,0,0xbddabe16,
0x3e25bda8,0,0,0,0,0x3e25bda8,0,0,0,0,0x3e25bda8,0,0,0,0,0x3e25bda8,
0xbd653e30,0,0,0,0,0xbd653e30,0,0,0,0,0xbd653e30,0,0,0,0,0xbd653e30,
0xbe37bce8,0,0,0,0,0xbe37bce8,0,0,0,0,0xbe37bce8,0,0,0,0,0xbe37bce8,
0x3d653e30,0,0,0,0,0x3d653e30,0,0,0,0,0x3d653e30,0,0,0,0,0x3d653e30,
0xbe373ce8,0,0,0,0,0xbe373ce8,0,0,0,0,0xbe373ce8,0,0,0,0,0xbe373ce8,
0x3d653e30,0,0,0,0,0x3d653e30,0,0,0,0,0x3d653e30,0,0,0,0,0x3d653e30,
0xbe37bce8,0,0,0,0,0xbe37bce8,0,0,0,0,0xbe37bce8,0,0,0,0,0xbe37bce8,
0xbe390000,0,0,0,0,0xbe390000,0,0,0,0,0xbe390000,0,0,0,0,0xbe390000,
0x3e03be03,0,0,0,0,0x3e03be03,0,0,0,0,0x3e03be03,0,0,0,0,0x3e03be03,
0x3ddabe16,0,0,0,0,0x3ddabe16,0,0,0,0,0x3ddabe16,0,0,0,0,0x3ddabe16,
0x3da83e25,0,0,0,0,0x3da83e25,0,0,0,0,0x3da83e25,0,0,0,0,0x3da83e25,
0x80003e39,0,0,0,0,0x80003e39,0,0,0,0,0x80003e39,0,0,0,0,0x80003e39,
0xbe03be03,0,0,0,0,0xbe03be03,0,0,0,0,0xbe03be03,0,0,0,0,0xbe03be03,
0xbe390000,0,0,0,0,0xbe390000,0,0,0,0,0xbe390000,0,0,0,0,0xbe390000,
0x3da8be25,0,0,0,0,0x3da8be25,0,0,0,0,0x3da8be25,0,0,0,0,0x3da8be25,
0x3e390000,0,0,0,0,0x3e390000,0,0,0,0,0x3e390000,0,0,0,0,0x3e390000,
0xbe033e03,0,0,0,0,0xbe033e03,0,0,0,0,0xbe033e03,0,0,0,0,0xbe033e03,
0x3dda3e16,0,0,0,0,0x3dda3e16,0,0,0,0,0x3dda3e16,0,0,0,0,0x3dda3e16,
0xbe373ce8,0,0,0,0,0xbe373ce8,0,0,0,0,0xbe373ce8,0,0,0,0,0xbe373ce8,
0x8000be39,0,0,0,0,0x8000be39,0,0,0,0,0x8000be39,0,0,0,0,0x8000be39,
0x3e033e03,0,0,0,0,0x3e033e03,0,0,0,0,0x3e033e03,0,0,0,0,0x3e033e03,
0x3d65be30,0,0,0,0,0x3d65be30,0,0,0,0,0x3d65be30,0,0,0,0,0x3d65be30,
0x3e033e03,0,0,0,0,0x3e033e03,0,0,0,0,0x3e033e03,0,0,0,0,0x3e033e03,
0xbe390000,0,0,0,0,0xbe390000,0,0,0,0,0xbe390000,0,0,0,0,0xbe390000,
0x3e03be03,0,0,0,0,0x3e03be03,0,0,0,0,0x3e03be03,0,0,0,0,0x3e03be03,
0xbe303d65,0,0,0,0,0xbe303d65,0,0,0,0,0xbe303d65,0,0,0,0,0xbe303d65,
0x3ce8be37,0,0,0,0,0x3ce8be37,0,0,0,0,0x3ce8be37,0,0,0,0,0x3ce8be37,
0x80003e39,0,0,0,0,0x80003e39,0,0,0,0,0x80003e39,0,0,0,0,0x80003e39,
0xbe03be03,0,0,0,0,0xbe03be03,0,0,0,0,0xbe03be03,0,0,0,0,0xbe03be03,
0x3e163dda,0,0,0,0,0x3e163dda,0,0,0,0,0x3e163dda,0,0,0,0,0x3e163dda,
0xbe253da8,0,0,0,0,0xbe253da8,0,0,0,0,0xbe253da8,0,0,0,0,0xbe253da8,
0x3e390000,0,0,0,0,0x3e390000,0,0,0,0,0x3e390000,0,0,0,0,0x3e390000,
0xbe033e03,0,0,0,0,0xbe033e03,0,0,0,0,0xbe033e03,0,0,0,0,0xbe033e03,
0x3d65be30,0,0,0,0,0x3d65be30,0,0,0,0,0x3d65be30,0,0,0,0,0x3d65be30,
0x3ce83e37,0,0,0,0,0x3ce83e37,0,0,0,0,0x3ce83e37,0,0,0,0,0x3ce83e37,
0x3e163dda,0,0,0,0,0x3e163dda,0,0,0,0,0x3e163dda,0,0,0,0,0x3e163dda,
0xbe25bda8,0,0,0,0,0xbe25bda8,0,0,0,0,0xbe25bda8,0,0,0,0,0xbe25bda8,
0xbddabe16,0,0,0,0,0xbddabe16,0,0,0,0,0xbddabe16,0,0,0,0,0xbddabe16,
0x3e253da8,0,0,0,0,0x3e253da8,0,0,0,0,0x3e253da8,0,0,0,0,0x3e253da8,
0x3e303d65,0,0,0,0,0x3e303d65,0,0,0,0,0x3e303d65,0,0,0,0,0x3e303d65,
0xbe37bce8,0,0,0,0,0xbe37bce8,0,0,0,0,0xbe37bce8,0,0,0,0,0xbe37bce8,
0xbe390000,0,0,0,0,0xbe390000,0,0,0,0,0xbe390000,0,0,0,0,0xbe390000,
0x3e25bda8,0,0,0,0,0x3e25bda8,0,0,0,0,0x3e25bda8,0,0,0,0,0x3e25bda8,
0x3e390000,0,0,0,0,0x3e390000,0,0,0,0,0x3e390000,0,0,0,0,0x3e390000,
0xbe373ce8,0,0,0,0,0xbe373ce8,0,0,0,0,0xbe373ce8,0,0,0,0,0xbe373ce8,
0xbdda3e16,0,0,0,0,0xbdda3e16,0,0,0,0,0xbdda3e16,0,0,0,0,0xbdda3e16,
0x3ce8be37,0,0,0,0,0x3ce8be37,0,0,0,0,0x3ce8be37,0,0,0,0,0x3ce8be37,
0x3e30bd65,0,0,0,0,0x3e30bd65,0,0,0,0,0x3e30bd65,0,0,0,0,0x3e30bd65,
0xbe253da8,0,0,0,0,0xbe253da8,0,0,0,0,0xbe253da8,0,0,0,0,0xbe253da8,
0x3d653e30,0,0,0,0,0x3d653e30,0,0,0,0,0x3d653e30,0,0,0,0,0x3d653e30,
0xbe03be03,0,0,0,0,0xbe03be03,0,0,0,0,0xbe03be03,0,0,0,0,0xbe03be03,
0x3e16bdda,0,0,0,0,0x3e16bdda,0,0,0,0,0x3e16bdda,0,0,0,0,0x3e16bdda,
0xbe033e03,0,0,0,0,0xbe033e03,0,0,0,0,0xbe033e03,0,0,0,0,0xbe033e03,
0x3e303d65,0,0,0,0,0x3e303d65,0,0,0,0,0x3e303d65,0,0,0,0,0x3e303d65,
0xbe373ce8,0,0,0,0,0xbe373ce8,0,0,0,0,0xbe373ce8,0,0,0,0,0xbe373ce8,
0x3ddabe16,0,0,0,0,0x3ddabe16,0,0,0,0,0x3ddabe16,0,0,0,0,0x3ddabe16,
0xbda83e25,0,0,0,0,0xbda83e25,0,0,0,0,0xbda83e25,0,0,0,0,0xbda83e25,
0x3e16bdda,0,0,0,0,0x3e16bdda,0,0,0,0,0x3e16bdda,0,0,0,0,0x3e16bdda,
0xbda83e25,0,0,0,0,0xbda83e25,0,0,0,0,0xbda83e25,0,0,0,0,0xbda83e25,
0x3d65be30,0,0,0,0,0x3d65be30,0,0,0,0,0x3d65be30,0,0,0,0,0x3d65be30,
0xbce83e37,0,0,0,0,0xbce83e37,0,0,0,0,0xbce83e37,0,0,0,0,0xbce83e37,
0,0,0xbe163dda,0,0,0,0,0xbe163dda,0,0,0xbe253da8,0,0,0,0,0xbe253da8,
0,0,0xbe303d65,0,0,0,0,0xbe303d65,0,0,0xbe373ce8,0,0,0,0,0xbe373ce8,
0,0,0xbd65be30,0,0,0,0,0xbd65be30,0,0,0x3ce8be37,0,0,0,0,0x3ce8be37,
0,0,0x3ddabe16,0,0,0,0,0x3ddabe16,0,0,0x3e25bda8,0,0,0,0,0x3e25bda8,
0,0,0xbe390000,0,0,0,0,0xbe390000,0,0,0xbe37bce8,0,0,0,0,0xbe37bce8,
0,0,0xbe30bd65,0,0,0,0,0xbe30bd65,0,0,0xbe25bda8,0,0,0,0,0xbe25bda8,
0,0,0x3e390000,0,0,0,0,0x3e390000,0,0,0x3e253da8,0,0,0,0,0x3e253da8,
0,0,0x3dda3e16,0,0,0,0,0x3dda3e16,0,0,0x3ce83e37,0,0,0,0,0x3ce83e37,
0,0,0xbe16bdda,0,0,0,0,0xbe16bdda,0,0,0xbe03be03,0,0,0,0,0xbe03be03,
0,0,0xbddabe16,0,0,0,0,0xbddabe16,0,0,0xbda8be25,0,0,0,0,0xbda8be25,
0,0,0xbd653e30,0,0,0,0,0xbd653e30,0,0,0xbe033e03,0,0,0,0,0xbe033e03,
0,0,0xbe303d65,0,0,0,0,0xbe303d65,0,0,0xbe37bce8,0,0,0,0,0xbe37bce8,
0,0,0xbd65be30,0,0,0,0,0xbd65be30,0,0,0xbce8be37,0,0,0,0,0xbce8be37,
0,0,0,0,0,0,0,0,0,0,0,0,0,0,0,0,
0,0,0xbe16bdda,0,0,0,0,0xbe16bdda,0,0,0xbda8be25,0,0,0,0,0xbda8be25,
0,0,0,0,0,0,0,0,0,0,0,0,0,0,0,0,
0,0,0x3e390000,0,0,0,0,0x3e390000,0,0,0x3e033e03,0,0,0,0,0x3e033e03,
0,0,0x80003e39,0,0,0,0,0x80003e39,0,0,0xbe033e03,0,0,0,0,0xbe033e03,
0,0,0xbd653e30,0,0,0,0,0xbd653e30,0,0,0xbe373ce8,0,0,0,0,0xbe373ce8,
0,0,0xbddabe16,0,0,0,0,0xbddabe16,0,0,0x3da8be25,0,0,0,0,0x3da8be25,
0,0,0xbe390000,0,0,0,0,0xbe390000,0,0,0xbe03be03,0,0,0,0,0xbe03be03,
0,0,0x8000be39,0,0,0,0,0x8000be39,0,0,0x3e03be03,0,0,0,0,0x3e03be03,
0,0,0x3e390000,0,0,0,0,0x3e390000,0,0,0x3da83e25,0,0,0,0,0x3da83e25,
0,0,0xbdda3e16,0,0,0,0,0xbdda3e16,0,0,0xbe37bce8,0,0,0,0,0xbe37bce8,
0,0,0x3e390000,0,0,0,0,0x3e390000,0,0,0x3e033e03,0,0,0,0,0x3e033e03,
0,0,0x80003e39,0,0,0,0,0x80003e39,0,0,0xbe033e03,0,0,0,0,0xbe033e03,
0,0,0xbd65be30,0,0,0,0,0xbd65be30,0,0,0x3e03be03,0,0,0,0,0x3e03be03,
0,0,0x3e303d65,0,0,0,0,0x3e303d65,0,0,0x3ce83e37,0,0,0,0,0x3ce83e37,
0,0,0xbe390000,0,0,0,0,0xbe390000,0,0,0xbe03be03,0,0,0,0,0xbe03be03,
0,0,0,0,0,0,0,0,0,0,0,0,0,0,0,0,
0,0,0xbe163dda,0,0,0,0,0xbe163dda,0,0,0xbe25bda8,0,0,0,0,0xbe25bda8,
0,0,0,0,0,0,0,0,0,0,0,0,0,0,0,0,
0,0,0xbe16bdda,0,0,0,0,0xbe16bdda,0,0,0x3da8be25,0,0,0,0,0x3da8be25,
0,0,0x3e303d65,0,0,0,0,0x3e303d65,0,0,0xbce83e37,0,0,0,0,0xbce83e37,
0,0,0x3e16bdda,0,0,0,0,0x3e16bdda,0,0,0x3da83e25,0,0,0,0,0x3da83e25,
0,0,0xbe303d65,0,0,0,0,0xbe303d65,0,0,0xbce8be37,0,0,0,0,0xbce8be37,
0,0,0xbe390000,0,0,0,0,0xbe390000,0,0,0xbce8be37,0,0,0,0,0xbce8be37,
0,0,0x3e30bd65,0,0,0,0,0x3e30bd65,0,0,0x3da83e25,0,0,0,0,0x3da83e25,
0,0,0x3e390000,0,0,0,0,0x3e390000,0,0,0xbce83e37,0,0,0,0,0xbce83e37,
0,0,0xbe30bd65,0,0,0,0,0xbe30bd65,0,0,0x3da8be25,0,0,0,0,0x3da8be25,
0,0,0xbe163dda,0,0,0,0,0xbe163dda,0,0,0xbe03be03,0,0,0,0,0xbe03be03,
0,0,0x3ddabe16,0,0,0,0,0x3ddabe16,0,0,0x3e253da8,0,0,0,0,0x3e253da8,
0,0,0x3e163dda,0,0,0,0,0x3e163dda,0,0,0xbe033e03,0,0,0,0,0xbe033e03,
0,0,0xbddabe16,0,0,0,0,0xbddabe16,0,0,0x3e25bda8,0,0,0,0,0x3e25bda8,
0,0,0xbd653e30,0,0,0,0,0xbd653e30,0,0,0xbe37bce8,0,0,0,0,0xbe37bce8,
0,0,0,0,0,0,0,0,0,0,0,0,0,0,0,0,
0,0,0x3d653e30,0,0,0,0,0x3d653e30,0,0,0xbe373ce8,0,0,0,0,0xbe373ce8,
0,0,0,0,0,0,0,0,0,0,0,0,0,0,0,0,
0,0,0x3d653e30,0,0,0,0,0x3d653e30,0,0,0xbe37bce8,0,0,0,0,0xbe37bce8,
0,0,0x3ddabe16,0,0,0,0,0x3ddabe16,0,0,0x3da83e25,0,0,0,0,0x3da83e25,
0,0,0xbe390000,0,0,0,0,0xbe390000,0,0,0x3e03be03,0,0,0,0,0x3e03be03,
0,0,0x80003e39,0,0,0,0,0x80003e39,0,0,0xbe03be03,0,0,0,0,0xbe03be03,
0,0,0xbe390000,0,0,0,0,0xbe390000,0,0,0x3da8be25,0,0,0,0,0x3da8be25,
0,0,0x3dda3e16,0,0,0,0,0x3dda3e16,0,0,0xbe373ce8,0,0,0,0,0xbe373ce8,
0,0,0x3e390000,0,0,0,0,0x3e390000,0,0,0xbe033e03,0,0,0,0,0xbe033e03,
0,0,0x8000be39,0,0,0,0,0x8000be39,0,0,0x3e033e03,0,0,0,0,0x3e033e03,
0,0,0x3d65be30,0,0,0,0,0x3d65be30,0,0,0x3e033e03,0,0,0,0,0x3e033e03,
0,0,0xbe303d65,0,0,0,0,0xbe303d65,0,0,0x3ce8be37,0,0,0,0,0x3ce8be37,
0,0,0xbe390000,0,0,0,0,0xbe390000,0,0,0x3e03be03,0,0,0,0,0x3e03be03,
0,0,0x80003e39,0,0,0,0,0x80003e39,0,0,0xbe03be03,0,0,0,0,0xbe03be03,
0,0,0x3e163dda,0,0,0,0,0x3e163dda,0,0,0xbe253da8,0,0,0,0,0xbe253da8,
0,0,0,0,0,0,0,0,0,0,0,0,0,0,0,0,
0,0,0x3e390000,0,0,0,0,0x3e390000,0,0,0xbe033e03,0,0,0,0,0xbe033e03,
0,0,0,0,0,0,0,0,0,0,0,0,0,0,0,0,
0,0,0x3d65be30,0,0,0,0,0x3d65be30,0,0,0x3ce83e37,0,0,0,0,0x3ce83e37,
0,0,0xbddabe16,0,0,0,0,0xbddabe16,0,0,0x3e253da8,0,0,0,0,0x3e253da8,
0,0,0x3e163dda,0,0,0,0,0x3e163dda,0,0,0xbe25bda8,0,0,0,0,0xbe25bda8,
0,0,0x3e303d65,0,0,0,0,0x3e303d65,0,0,0xbe37bce8,0,0,0,0,0xbe37bce8,
0,0,0xbe390000,0,0,0,0,0xbe390000,0,0,0x3e25bda8,0,0,0,0,0x3e25bda8,
0,0,0xbdda3e16,0,0,0,0,0xbdda3e16,0,0,0x3ce8be37,0,0,0,0,0x3ce8be37,
0,0,0x3e390000,0,0,0,0,0x3e390000,0,0,0xbe373ce8,0,0,0,0,0xbe373ce8,
0,0,0x3e30bd65,0,0,0,0,0x3e30bd65,0,0,0xbe253da8,0,0,0,0,0xbe253da8,
0,0,0x3d653e30,0,0,0,0,0x3d653e30,0,0,0xbe03be03,0,0,0,0,0xbe03be03,
0,0,0x3e303d65,0,0,0,0,0x3e303d65,0,0,0xbe373ce8,0,0,0,0,0xbe373ce8,
0,0,0x3e16bdda,0,0,0,0,0x3e16bdda,0,0,0xbe033e03,0,0,0,0,0xbe033e03,
0,0,0x3ddabe16,0,0,0,0,0x3ddabe16,0,0,0xbda83e25,0,0,0,0,0xbda83e25,
0,0,0x3e16bdda,0,0,0,0,0x3e16bdda,0,0,0xbda83e25,0,0,0,0,0xbda83e25,
0,0,0,0,0,0,0,0,0,0,0,0,0,0,0,0,
0,0,0x3d65be30,0,0,0,0,0x3d65be30,0,0,0xbce83e37,0,0,0,0,0xbce83e37,
0,0,0,0,0,0,0,0,0,0,0,0,0,0,0,0,
};
constexpr unsigned long long COS_PK0 = 0x3f903f9a3fa03fa2ull;
constexpr unsigned long long COS_PK1 = 0x3f133f3e3f653f83ull;
constexpr unsigned long long COS_PK2 = 0x3e4b3ec8ull;

__device__ __forceinline__ void wgmma_ss_n80_z(float (&d)[40], uint64_t da, uint64_t db) {
  asm volatile("{\n.reg .pred p;\nsetp.ne.b32 p, 0, 0;\nwgmma.mma_async.sync.aligned.m64n80k16.f32.bf16.bf16 {%0,%1,%2,%3,%4,%5,%6,%7,%8,%9,%10,%11,%12,%13,%14,%15,%16,%17,%18,%19,%20,%21,%22,%23,%24,%25,%26,%27,%28,%29,%30,%31,%32,%33,%34,%35,%36,%37,%38,%39}, %40, %41, p, 1, 1, 1, 0;\n}\n"
    : "+f"(d[0]), "+f"(d[1]), "+f"(d[2]), "+f"(d[3]), "+f"(d[4]), "+f"(d[5]), "+f"(d[6]), "+f"(d[7]), "+f"(d[8]), "+f"(d[9]), "+f"(d[10]), "+f"(d[11]), "+f"(d[12]), "+f"(d[13]), "+f"(d[14]), "+f"(d[15]), "+f"(d[16]), "+f"(d[17]), "+f"(d[18]), "+f"(d[19]), "+f"(d[20]), "+f"(d[21]), "+f"(d[22]), "+f"(d[23]), "+f"(d[24]), "+f"(d[25]), "+f"(d[26]), "+f"(d[27]), "+f"(d[28]), "+f"(d[29]), "+f"(d[30]), "+f"(d[31]), "+f"(d[32]), "+f"(d[33]), "+f"(d[34]), "+f"(d[35]), "+f"(d[36]), "+f"(d[37]), "+f"(d[38]), "+f"(d[39])
    : "l"(da), "l"(db));
}
__device__ __forceinline__ void wgmma_ss_n80_a(float (&d)[40], uint64_t da, uint64_t db) {
  asm volatile("{\n.reg .pred p;\nsetp.ne.b32 p, 1, 0;\nwgmma.mma_async.sync.aligned.m64n80k16.f32.bf16.bf16 {%0,%1,%2,%3,%4,%5,%6,%7,%8,%9,%10,%11,%12,%13,%14,%15,%16,%17,%18,%19,%20,%21,%22,%23,%24,%25,%26,%27,%28,%29,%30,%31,%32,%33,%34,%35,%36,%37,%38,%39}, %40, %41, p, 1, 1, 1, 0;\n}\n"
    : "+f"(d[0]), "+f"(d[1]), "+f"(d[2]), "+f"(d[3]), "+f"(d[4]), "+f"(d[5]), "+f"(d[6]), "+f"(d[7]), "+f"(d[8]), "+f"(d[9]), "+f"(d[10]), "+f"(d[11]), "+f"(d[12]), "+f"(d[13]), "+f"(d[14]), "+f"(d[15]), "+f"(d[16]), "+f"(d[17]), "+f"(d[18]), "+f"(d[19]), "+f"(d[20]), "+f"(d[21]), "+f"(d[22]), "+f"(d[23]), "+f"(d[24]), "+f"(d[25]), "+f"(d[26]), "+f"(d[27]), "+f"(d[28]), "+f"(d[29]), "+f"(d[30]), "+f"(d[31]), "+f"(d[32]), "+f"(d[33]), "+f"(d[34]), "+f"(d[35]), "+f"(d[36]), "+f"(d[37]), "+f"(d[38]), "+f"(d[39])
    : "l"(da), "l"(db));
}

__device__ __forceinline__ void wgmma_rs_n40_z(float (&d)[20], uint32_t a0, uint32_t a1, uint32_t a2, uint32_t a3, uint64_t db) {
  asm volatile("{\n.reg .pred p;\nsetp.ne.b32 p, 0, 0;\nwgmma.mma_async.sync.aligned.m64n40k16.f32.bf16.bf16 {%0,%1,%2,%3,%4,%5,%6,%7,%8,%9,%10,%11,%12,%13,%14,%15,%16,%17,%18,%19}, {%20,%21,%22,%23}, %24, p, 1, 1, 0;\n}\n"
    : "+f"(d[0]), "+f"(d[1]), "+f"(d[2]), "+f"(d[3]), "+f"(d[4]), "+f"(d[5]), "+f"(d[6]), "+f"(d[7]), "+f"(d[8]), "+f"(d[9]), "+f"(d[10]), "+f"(d[11]), "+f"(d[12]), "+f"(d[13]), "+f"(d[14]), "+f"(d[15]), "+f"(d[16]), "+f"(d[17]), "+f"(d[18]), "+f"(d[19])
    : "r"(a0), "r"(a1), "r"(a2), "r"(a3), "l"(db));
}
__device__ __forceinline__ void wgmma_rs_n40_a(float (&d)[20], uint32_t a0, uint32_t a1, uint32_t a2, uint32_t a3, uint64_t db) {
  asm volatile("{\n.reg .pred p;\nsetp.ne.b32 p, 1, 0;\nwgmma.mma_async.sync.aligned.m64n40k16.f32.bf16.bf16 {%0,%1,%2,%3,%4,%5,%6,%7,%8,%9,%10,%11,%12,%13,%14,%15,%16,%17,%18,%19}, {%20,%21,%22,%23}, %24, p, 1, 1, 0;\n}\n"
    : "+f"(d[0]), "+f"(d[1]), "+f"(d[2]), "+f"(d[3]), "+f"(d[4]), "+f"(d[5]), "+f"(d[6]), "+f"(d[7]), "+f"(d[8]), "+f"(d[9]), "+f"(d[10]), "+f"(d[11]), "+f"(d[12]), "+f"(d[13]), "+f"(d[14]), "+f"(d[15]), "+f"(d[16]), "+f"(d[17]), "+f"(d[18]), "+f"(d[19])
    : "r"(a0), "r"(a1), "r"(a2), "r"(a3), "l"(db));
}

__device__ __forceinline__ void wgmma_rs_n128_z(float (&d)[64], uint32_t a0, uint32_t a1, uint32_t a2, uint32_t a3, uint64_t db) {
  asm volatile("{\n.reg .pred p;\nsetp.ne.b32 p, 0, 0;\nwgmma.mma_async.sync.aligned.m64n128k16.f32.bf16.bf16 {%0,%1,%2,%3,%4,%5,%6,%7,%8,%9,%10,%11,%12,%13,%14,%15,%16,%17,%18,%19,%20,%21,%22,%23,%24,%25,%26,%27,%28,%29,%30,%31,%32,%33,%34,%35,%36,%37,%38,%39,%40,%41,%42,%43,%44,%45,%46,%47,%48,%49,%50,%51,%52,%53,%54,%55,%56,%57,%58,%59,%60,%61,%62,%63}, {%64,%65,%66,%67}, %68, p, 1, 1, 1;\n}\n"
    : "+f"(d[0]), "+f"(d[1]), "+f"(d[2]), "+f"(d[3]), "+f"(d[4]), "+f"(d[5]), "+f"(d[6]), "+f"(d[7]), "+f"(d[8]), "+f"(d[9]), "+f"(d[10]), "+f"(d[11]), "+f"(d[12]), "+f"(d[13]), "+f"(d[14]), "+f"(d[15]), "+f"(d[16]), "+f"(d[17]), "+f"(d[18]), "+f"(d[19]), "+f"(d[20]), "+f"(d[21]), "+f"(d[22]), "+f"(d[23]), "+f"(d[24]), "+f"(d[25]), "+f"(d[26]), "+f"(d[27]), "+f"(d[28]), "+f"(d[29]), "+f"(d[30]), "+f"(d[31]), "+f"(d[32]), "+f"(d[33]), "+f"(d[34]), "+f"(d[35]), "+f"(d[36]), "+f"(d[37]), "+f"(d[38]), "+f"(d[39]), "+f"(d[40]), "+f"(d[41]), "+f"(d[42]), "+f"(d[43]), "+f"(d[44]), "+f"(d[45]), "+f"(d[46]), "+f"(d[47]), "+f"(d[48]), "+f"(d[49]), "+f"(d[50]), "+f"(d[51]), "+f"(d[52]), "+f"(d[53]), "+f"(d[54]), "+f"(d[55]), "+f"(d[56]), "+f"(d[57]), "+f"(d[58]), "+f"(d[59]), "+f"(d[60]), "+f"(d[61]), "+f"(d[62]), "+f"(d[63])
    : "r"(a0), "r"(a1), "r"(a2), "r"(a3), "l"(db));
}
__device__ __forceinline__ void wgmma_rs_n128_a(float (&d)[64], uint32_t a0, uint32_t a1, uint32_t a2, uint32_t a3, uint64_t db) {
  asm volatile("{\n.reg .pred p;\nsetp.ne.b32 p, 1, 0;\nwgmma.mma_async.sync.aligned.m64n128k16.f32.bf16.bf16 {%0,%1,%2,%3,%4,%5,%6,%7,%8,%9,%10,%11,%12,%13,%14,%15,%16,%17,%18,%19,%20,%21,%22,%23,%24,%25,%26,%27,%28,%29,%30,%31,%32,%33,%34,%35,%36,%37,%38,%39,%40,%41,%42,%43,%44,%45,%46,%47,%48,%49,%50,%51,%52,%53,%54,%55,%56,%57,%58,%59,%60,%61,%62,%63}, {%64,%65,%66,%67}, %68, p, 1, 1, 1;\n}\n"
    : "+f"(d[0]), "+f"(d[1]), "+f"(d[2]), "+f"(d[3]), "+f"(d[4]), "+f"(d[5]), "+f"(d[6]), "+f"(d[7]), "+f"(d[8]), "+f"(d[9]), "+f"(d[10]), "+f"(d[11]), "+f"(d[12]), "+f"(d[13]), "+f"(d[14]), "+f"(d[15]), "+f"(d[16]), "+f"(d[17]), "+f"(d[18]), "+f"(d[19]), "+f"(d[20]), "+f"(d[21]), "+f"(d[22]), "+f"(d[23]), "+f"(d[24]), "+f"(d[25]), "+f"(d[26]), "+f"(d[27]), "+f"(d[28]), "+f"(d[29]), "+f"(d[30]), "+f"(d[31]), "+f"(d[32]), "+f"(d[33]), "+f"(d[34]), "+f"(d[35]), "+f"(d[36]), "+f"(d[37]), "+f"(d[38]), "+f"(d[39]), "+f"(d[40]), "+f"(d[41]), "+f"(d[42]), "+f"(d[43]), "+f"(d[44]), "+f"(d[45]), "+f"(d[46]), "+f"(d[47]), "+f"(d[48]), "+f"(d[49]), "+f"(d[50]), "+f"(d[51]), "+f"(d[52]), "+f"(d[53]), "+f"(d[54]), "+f"(d[55]), "+f"(d[56]), "+f"(d[57]), "+f"(d[58]), "+f"(d[59]), "+f"(d[60]), "+f"(d[61]), "+f"(d[62]), "+f"(d[63])
    : "r"(a0), "r"(a1), "r"(a2), "r"(a3), "l"(db));
}

__device__ __forceinline__ void wgmma_rs_n32_z(float (&d)[16], uint32_t a0, uint32_t a1, uint32_t a2, uint32_t a3, uint64_t db) {
  asm volatile("{\n.reg .pred p;\nsetp.ne.b32 p, 0, 0;\nwgmma.mma_async.sync.aligned.m64n32k16.f32.bf16.bf16 {%0,%1,%2,%3,%4,%5,%6,%7,%8,%9,%10,%11,%12,%13,%14,%15}, {%16,%17,%18,%19}, %20, p, 1, 1, 0;\n}\n"
    : "+f"(d[0]), "+f"(d[1]), "+f"(d[2]), "+f"(d[3]), "+f"(d[4]), "+f"(d[5]), "+f"(d[6]), "+f"(d[7]), "+f"(d[8]), "+f"(d[9]), "+f"(d[10]), "+f"(d[11]), "+f"(d[12]), "+f"(d[13]), "+f"(d[14]), "+f"(d[15])
    : "r"(a0), "r"(a1), "r"(a2), "r"(a3), "l"(db));
}
__device__ __forceinline__ void wgmma_rs_n32_a(float (&d)[16], uint32_t a0, uint32_t a1, uint32_t a2, uint32_t a3, uint64_t db) {
  asm volatile("{\n.reg .pred p;\nsetp.ne.b32 p, 1, 0;\nwgmma.mma_async.sync.aligned.m64n32k16.f32.bf16.bf16 {%0,%1,%2,%3,%4,%5,%6,%7,%8,%9,%10,%11,%12,%13,%14,%15}, {%16,%17,%18,%19}, %20, p, 1, 1, 0;\n}\n"
    : "+f"(d[0]), "+f"(d[1]), "+f"(d[2]), "+f"(d[3]), "+f"(d[4]), "+f"(d[5]), "+f"(d[6]), "+f"(d[7]), "+f"(d[8]), "+f"(d[9]), "+f"(d[10]), "+f"(d[11]), "+f"(d[12]), "+f"(d[13]), "+f"(d[14]), "+f"(d[15])
    : "r"(a0), "r"(a1), "r"(a2), "r"(a3), "l"(db));
}

__device__ __forceinline__ void wgmma_rs_n64_z(float (&d)[32], uint32_t a0, uint32_t a1, uint32_t a2, uint32_t a3, uint64_t db) {
  asm volatile("{\n.reg .pred p;\nsetp.ne.b32 p, 0, 0;\nwgmma.mma_async.sync.aligned.m64n64k16.f32.bf16.bf16 {%0,%1,%2,%3,%4,%5,%6,%7,%8,%9,%10,%11,%12,%13,%14,%15,%16,%17,%18,%19,%20,%21,%22,%23,%24,%25,%26,%27,%28,%29,%30,%31}, {%32,%33,%34,%35}, %36, p, 1, 1, 0;\n}\n"
    : "+f"(d[0]), "+f"(d[1]), "+f"(d[2]), "+f"(d[3]), "+f"(d[4]), "+f"(d[5]), "+f"(d[6]), "+f"(d[7]), "+f"(d[8]), "+f"(d[9]), "+f"(d[10]), "+f"(d[11]), "+f"(d[12]), "+f"(d[13]), "+f"(d[14]), "+f"(d[15]), "+f"(d[16]), "+f"(d[17]), "+f"(d[18]), "+f"(d[19]), "+f"(d[20]), "+f"(d[21]), "+f"(d[22]), "+f"(d[23]), "+f"(d[24]), "+f"(d[25]), "+f"(d[26]), "+f"(d[27]), "+f"(d[28]), "+f"(d[29]), "+f"(d[30]), "+f"(d[31])
    : "r"(a0), "r"(a1), "r"(a2), "r"(a3), "l"(db));
}
__device__ __forceinline__ void wgmma_rs_n64_a(float (&d)[32], uint32_t a0, uint32_t a1, uint32_t a2, uint32_t a3, uint64_t db) {
  asm volatile("{\n.reg .pred p;\nsetp.ne.b32 p, 1, 0;\nwgmma.mma_async.sync.aligned.m64n64k16.f32.bf16.bf16 {%0,%1,%2,%3,%4,%5,%6,%7,%8,%9,%10,%11,%12,%13,%14,%15,%16,%17,%18,%19,%20,%21,%22,%23,%24,%25,%26,%27,%28,%29,%30,%31}, {%32,%33,%34,%35}, %36, p, 1, 1, 0;\n}\n"
    : "+f"(d[0]), "+f"(d[1]), "+f"(d[2]), "+f"(d[3]), "+f"(d[4]), "+f"(d[5]), "+f"(d[6]), "+f"(d[7]), "+f"(d[8]), "+f"(d[9]), "+f"(d[10]), "+f"(d[11]), "+f"(d[12]), "+f"(d[13]), "+f"(d[14]), "+f"(d[15]), "+f"(d[16]), "+f"(d[17]), "+f"(d[18]), "+f"(d[19]), "+f"(d[20]), "+f"(d[21]), "+f"(d[22]), "+f"(d[23]), "+f"(d[24]), "+f"(d[25]), "+f"(d[26]), "+f"(d[27]), "+f"(d[28]), "+f"(d[29]), "+f"(d[30]), "+f"(d[31])
    : "r"(a0), "r"(a1), "r"(a2), "r"(a3), "l"(db));
}

__device__ __forceinline__ void wgmma_ss_n32_z(float (&d)[16], uint64_t da, uint64_t db) {
  asm volatile("{\n.reg .pred p;\nsetp.ne.b32 p, 0, 0;\nwgmma.mma_async.sync.aligned.m64n32k16.f32.bf16.bf16 {%0,%1,%2,%3,%4,%5,%6,%7,%8,%9,%10,%11,%12,%13,%14,%15}, %16, %17, p, 1, 1, 1, 0;\n}\n"
    : "+f"(d[0]), "+f"(d[1]), "+f"(d[2]), "+f"(d[3]), "+f"(d[4]), "+f"(d[5]), "+f"(d[6]), "+f"(d[7]), "+f"(d[8]), "+f"(d[9]), "+f"(d[10]), "+f"(d[11]), "+f"(d[12]), "+f"(d[13]), "+f"(d[14]), "+f"(d[15])
    : "l"(da), "l"(db));
}
__device__ __forceinline__ void wgmma_ss_n32_a(float (&d)[16], uint64_t da, uint64_t db) {
  asm volatile("{\n.reg .pred p;\nsetp.ne.b32 p, 1, 0;\nwgmma.mma_async.sync.aligned.m64n32k16.f32.bf16.bf16 {%0,%1,%2,%3,%4,%5,%6,%7,%8,%9,%10,%11,%12,%13,%14,%15}, %16, %17, p, 1, 1, 1, 0;\n}\n"
    : "+f"(d[0]), "+f"(d[1]), "+f"(d[2]), "+f"(d[3]), "+f"(d[4]), "+f"(d[5]), "+f"(d[6]), "+f"(d[7]), "+f"(d[8]), "+f"(d[9]), "+f"(d[10]), "+f"(d[11]), "+f"(d[12]), "+f"(d[13]), "+f"(d[14]), "+f"(d[15])
    : "l"(da), "l"(db));
}

__device__ __forceinline__ void wgmma_ss_n40_z(float (&d)[20], uint64_t da, uint64_t db) {
  asm volatile("{\n.reg .pred p;\nsetp.ne.b32 p, 0, 0;\nwgmma.mma_async.sync.aligned.m64n40k16.f32.bf16.bf16 {%0,%1,%2,%3,%4,%5,%6,%7,%8,%9,%10,%11,%12,%13,%14,%15,%16,%17,%18,%19}, %20, %21, p, 1, 1, 1, 0;\n}\n"
    : "+f"(d[0]), "+f"(d[1]), "+f"(d[2]), "+f"(d[3]), "+f"(d[4]), "+f"(d[5]), "+f"(d[6]), "+f"(d[7]), "+f"(d[8]), "+f"(d[9]), "+f"(d[10]), "+f"(d[11]), "+f"(d[12]), "+f"(d[13]), "+f"(d[14]), "+f"(d[15]), "+f"(d[16]), "+f"(d[17]), "+f"(d[18]), "+f"(d[19])
    : "l"(da), "l"(db));
}
__device__ __forceinline__ void wgmma_ss_n40_a(float (&d)[20], uint64_t da, uint64_t db) {
  asm volatile("{\n.reg .pred p;\nsetp.ne.b32 p, 1, 0;\nwgmma.mma_async.sync.aligned.m64n40k16.f32.bf16.bf16 {%0,%1,%2,%3,%4,%5,%6,%7,%8,%9,%10,%11,%12,%13,%14,%15,%16,%17,%18,%19}, %20, %21, p, 1, 1, 1, 0;\n}\n"
    : "+f"(d[0]), "+f"(d[1]), "+f"(d[2]), "+f"(d[3]), "+f"(d[4]), "+f"(d[5]), "+f"(d[6]), "+f"(d[7]), "+f"(d[8]), "+f"(d[9]), "+f"(d[10]), "+f"(d[11]), "+f"(d[12]), "+f"(d[13]), "+f"(d[14]), "+f"(d[15]), "+f"(d[16]), "+f"(d[17]), "+f"(d[18]), "+f"(d[19])
    : "l"(da), "l"(db));
}

constexpr int NSM = 132, NH = 66;
constexpr int S0 = 0, S1 = 51200, S2 = 102400;
constexpr int C1 = 153600, C3 = C1, RG = C1 + 18432;
constexpr int WP = RG, TBL = RG + 28672, WS2 = RG + 30720;
constexpr int BARS = RG + 49152;
__host__ __device__ constexpr int wst_off(int i) { return i < 12 ? S2 + i * 4096 : WS2 + (i - 12) * 4096; }
constexpr int NBAR = 280;
constexpr int REL = BARS + NBAR * 8;
constexpr int SMEM_BYTES = REL + 16;
constexpr int B_XF = 0, B_CF1 = 15, B_CF3 = 16, B_WF = 17  , B_P1D = 18, B_REL = 21, B_ROLE = 22, B_SIG = 24;
constexpr int B_RF = 32, B_RE = 46, B_YF = 60, B_WRD = 75, B_SFREE = 89, B_WCH = 131, B_RDY = 136, B_WE = 205, B_WL = 217, B_FIN = 229, B_TOK = 232;
constexpr int R_P2 = 15, R_P3 = 57;
constexpr int CNT_P1 = 0, CNT_P2 = 4, CNT_W = 8, CNT_RANK = 9, NCLS = 10, CNT_DONE = 0, CNT_REL = 1, NCNT = 2;
constexpr int REP = 2;
constexpr int SIG_W = 0, SIG_P1 = 1, SIG_P2 = 4;
#define PFS 9088
#define T1MASK 0x3e00
#define T2MASK 0xf80

__device__ uint4 g_scr[(14 << 21) / 16];
__device__ __align__(128) uint4 g_wf[200 * 72 * 32];
__device__ __align__(128) unsigned g_cnt[NCNT * 32];
__device__ __forceinline__ int slot_line(int chunk, int pg, int cls) {
    return (pg & 1) << 6 | (pg >> 1) << 9 | (chunk & 1) << 10 | (chunk >> 1) << 12 | ((pg ^ (pg >> 1) ^ chunk ^ (chunk >> 1) ^ cls) & 1) << 5;
}
__device__ __forceinline__ int phi_line(int phi, uint32_t rel) {
    return (phi >> 4) << 14 | (phi & 3) << 7 | ((phi >> 2) & 1) << 11 | ((phi >> 3) & 1) << 13 | ((rel >> (phi >> 4)) & 1) << 5;
}
__device__ __forceinline__ int extra_mask(int rk) { return rk < 60 ? 0 : rk < 62 ? 1 : rk < 64 ? 10 : 4; }
__device__ __forceinline__ int wslot(int pc) {
    return (int)((0x576476503421ull >> (4 * pc)) & 3) * 12288 + (((0x576476503421ull >> (4 * pc)) & 4) ? S0 : RG);
}
__device__ __forceinline__ int xslot(int n) { return ((n & 4) ? S2 : RG) + ((n + 1) & 3) * 12288; }
__device__ __forceinline__ int extra_phi(int rk) { return 198 + (rk & 1); }
__host__ __device__ constexpr int quad_off(int Q) { return (Q >> 2) * 4096 + (Q & 3) * 512; }

struct Maps { CUtensorMap w, x34, x6, x28, wst, f16, f8, y4, y2; };
struct Ptrs { char* scr; const char* wf; const void* tab1; const void* tab3; unsigned* cnt; const char* x; };

__device__ __forceinline__ uint32_t smem_u32(const void* p) { return (uint32_t)__cvta_generic_to_shared(p); }
__device__ __forceinline__ void mbar_wait(uint32_t bar) {
    uint32_t ok, it = 0;
    do {
        asm volatile("{\n.reg .pred p;\nmbarrier.try_wait.parity.shared::cta.b64 p, [%1], 0;\nselp.u32 %0, 1, 0, p;\n}" : "=r"(ok) : "r"(bar) : "memory");
        if (++it > (1u << 22)) break;
    } while (!ok);
}
__device__ __forceinline__ bool mbar_test(uint32_t bar) {
    uint32_t ok;
    asm volatile("{\n.reg .pred p;\nmbarrier.test_wait.parity.shared::cta.b64 p, [%1], 0;\nselp.u32 %0, 1, 0, p;\n}" : "=r"(ok) : "r"(bar) : "memory");
    return ok;
}
__device__ __forceinline__ void fence_async() { asm volatile("fence.proxy.async;" ::: "memory"); }
__device__ __forceinline__ void fence_async_smem() { asm volatile("fence.proxy.async.shared::cta;" ::: "memory"); }
#define ELECT "{\n.reg .pred p;\nelect.sync _|p, 0xffffffff;\n@p "
__device__ __forceinline__ void e_arrive(uint32_t bar) { asm volatile(ELECT "mbarrier.arrive.shared::cta.b64 _, [%0];\n}" :: "r"(bar) : "memory"); }
__device__ __forceinline__ void e_expect(uint32_t bar, uint32_t bytes) { asm volatile(ELECT "mbarrier.arrive.expect_tx.shared::cta.b64 _, [%0], %1;\n}" :: "r"(bar), "r"(bytes) : "memory"); }
__device__ __forceinline__ void e_g2s(uint32_t dst, const void* src, uint32_t bytes, uint32_t bar) {
    asm volatile(ELECT "cp.async.bulk.shared::cluster.global.mbarrier::complete_tx::bytes [%0], [%1], %2, [%3];\n}" :: "r"(dst), "l"(src), "r"(bytes), "r"(bar) : "memory");
}
__device__ __forceinline__ void e_s2g(void* dst, uint32_t src, uint32_t bytes) {
    asm volatile(ELECT "cp.async.bulk.global.shared::cta.bulk_group [%0], [%1], %2;\n}" :: "l"(dst), "r"(src), "r"(bytes) : "memory");
}
__device__ __forceinline__ void e_ld3(uint32_t dst, const CUtensorMap* m, int c0, int c1, int c2, uint32_t bar) {
    asm volatile(ELECT "cp.async.bulk.tensor.3d.shared::cluster.global.mbarrier::complete_tx::bytes [%0], [%1, {%3, %4, %5}], [%2];\n}"
                 :: "r"(dst), "l"(m), "r"(bar), "r"(c0), "r"(c1), "r"(c2) : "memory");
}
__device__ __forceinline__ void e_ldw(uint32_t dst, const CUtensorMap* m, int c0, int c3, uint32_t bar) {
    asm volatile(ELECT "cp.async.bulk.tensor.5d.shared::cluster.global.mbarrier::complete_tx::bytes [%0], [%1, {%3, %5, %5, %4, %5}], [%2];\n}"
                 :: "r"(dst), "l"(m), "r"(bar), "r"(c0), "r"(c3), "r"(0) : "memory");
}
__device__ __forceinline__ void e_st3(const CUtensorMap* m, uint32_t src, int c0, int c1, int c2) {
    asm volatile(ELECT "cp.async.bulk.tensor.3d.global.shared::cta.bulk_group [%0, {%2, %3, %4}], [%1];\n}" :: "l"(m), "r"(src), "r"(c0), "r"(c1), "r"(c2) : "memory");
}
__device__ __forceinline__ void e_ld5(uint32_t dst, const CUtensorMap* m, int c4, uint32_t bar) {
    asm volatile(ELECT "cp.async.bulk.tensor.5d.shared::cluster.global.mbarrier::complete_tx::bytes [%0], [%1, {%4, %4, %4, %4, %3}], [%2];\n}"
                 :: "r"(dst), "l"(m), "r"(bar), "r"(c4), "r"(0) : "memory");
}
__device__ __forceinline__ void e_st5(const CUtensorMap* m, uint32_t src, int c4) {
    asm volatile(ELECT "cp.async.bulk.tensor.5d.global.shared::cta.bulk_group [%0, {%3, %3, %3, %3, %2}], [%1];\n}" :: "l"(m), "r"(src), "r"(c4), "r"(0) : "memory");
}
__device__ __forceinline__ void bulk_commit() { asm volatile("cp.async.bulk.commit_group;" ::: "memory"); }
template <int N> __device__ __forceinline__ void bulk_wait() { asm volatile("cp.async.bulk.wait_group %0;" :: "n"(N) : "memory"); }
template <int N> __device__ __forceinline__ void bulk_wait_read() { asm volatile("cp.async.bulk.wait_group.read %0;" :: "n"(N) : "memory"); }
__device__ __forceinline__ void wg_bar(int id) { asm volatile("bar.sync %0, 128;" :: "r"(id) : "memory"); }
__device__ __forceinline__ void bb_break(uint32_t v) { asm volatile("{\n.reg .pred p;\nsetp.eq.u32 p, %0, 0x7fc17fc1;\n@p nanosleep.u32 0;\n}" :: "r"(v) : "memory"); }
__device__ __forceinline__ uint32_t uni(uint32_t v) { return __shfl_sync(0xffffffffu, v, 0); }
__device__ __forceinline__ char* cls_cnt(char* scr, int cls) { return scr + slot_line(3, 2, cls) * 128; }
__device__ __forceinline__ uint32_t cnt_wait(const void* p, unsigned target) {
    uint32_t v = 0;
#pragma unroll 1
    for (unsigned it = 0; it < (1u << 22) && v < target; it++) {
        asm volatile("ld.acquire.gpu.global.u32 %0, [%1];" : "=r"(v) : "l"(p) : "memory");
        v = uni(v);
    }
    asm volatile("fence.proxy.async.global;" ::: "memory");
    return v;
}
__device__ __forceinline__ void wg_fence() { asm volatile("wgmma.fence.sync.aligned;" ::: "memory"); }
__device__ __forceinline__ void wg_commit() { asm volatile("wgmma.commit_group.sync.aligned;" ::: "memory"); }
template <int N> __device__ __forceinline__ void wg_wait() { asm volatile("wgmma.wait_group.sync.aligned %0;" :: "n"(N) : "memory"); }
template <int N> __device__ __forceinline__ void reg_fence(float (&d)[N]) {
#pragma unroll
    for (int i = 0; i < N; i++) asm volatile("" : "+f"(d[i]) :: "memory");
}
template <int N> __device__ __forceinline__ void zero(float (&d)[N]) {
#pragma unroll
    for (int i = 0; i < N; i++) d[i] = 0.f;
}
__device__ __forceinline__ uint32_t pack2(float lo, float hi) {
    uint32_t r; asm volatile("cvt.rn.bf16x2.f32 %0, %1, %2;" : "=r"(r) : "f"(hi), "f"(lo)); return r;
}
__device__ __forceinline__ void stm4(uint32_t a, uint32_t r0, uint32_t r1, uint32_t r2, uint32_t r3) {
    asm volatile("stmatrix.sync.aligned.m8n8.x4.trans.shared.b16 [%0], {%1,%2,%3,%4};" :: "r"(a), "r"(r0), "r"(r1), "r"(r2), "r"(r3) : "memory");
}
__device__ __forceinline__ void stm2(uint32_t a, uint32_t r0, uint32_t r1) {
    asm volatile("stmatrix.sync.aligned.m8n8.x2.trans.shared.b16 [%0], {%1,%2};" :: "r"(a), "r"(r0), "r"(r1) : "memory");
}
struct Desc {
    uint32_t lo, hi;
    __device__ __forceinline__ operator uint64_t() const { return ((uint64_t)hi << 32) | lo; }
    __device__ __forceinline__ Desc operator+(uint32_t o) const { return Desc{lo + o, hi}; }
    __device__ __forceinline__ Desc operator^(uint32_t o) const { return Desc{lo ^ o, hi}; }
};
__device__ __forceinline__ Desc mkdesc(uint32_t addr, uint32_t lbo, uint32_t sbo, uint32_t swz) {
    return Desc{((addr & 0x3FFFF) >> 4) | ((lbo >> 4) << 16), (sbo >> 4) | (swz << 30)};
}
__device__ __forceinline__ uint32_t cos_bits(int k) {
    if (k > 20) k = 40 - k;
    const bool neg = k > 10;
    if (neg) k = 20 - k;
    const unsigned long long pk = k < 4 ? COS_PK0 : k < 8 ? COS_PK1 : COS_PK2;
    return (uint32_t)((pk >> (16 * (k & 3))) & 0xffff) ^ (neg ? 0x8000u : 0u);
}

__device__ __forceinline__ void task_w(int wg, int k, uint32_t sb) {
    const int tid = threadIdx.x & 127, w = uni(tid >> 5), lane = tid & 31, q = lane & 3;
    const int tb = 14 * k, t1 = min(tb + 14, 1800), cb0 = tb / 25;
    float acc[64];
    zero(acc);
    const int oc0 = tb - 25 * cb0, Lt = t1 - tb, L0 = min(Lt, 25 - oc0), n0 = (L0 + 3) >> 2;
    uint32_t a[2][4][4];
    auto gen = [&](uint32_t (&a)[4][4], int at) {
        const int phi = 8 * ((at < n0 ? oc0 + 4 * at : 4 * (at - n0)) + w) + (lane >> 2), f = (phi * 205) >> 12;
        const uint32_t ca = 8 * f + 4, cw = (phi - 20 * f) * 8, p0 = sb + TBL + cw * 2 * q;
#pragma unroll
        for (int kh = 0; kh < 7; kh++) {
            uint32_t v0, v1;
            asm volatile("ld.shared.u32 %0, [%1];" : "=r"(v0) : "r"(p0 + ca * kh));
            asm volatile("ld.shared.u32 %0, [%1];" : "=r"(v1) : "r"(p0 + cw + ca * kh));
            const int h = kh == 6 ? 1 : kh & 1;
            a[kh >> 1][2 * h] = __byte_perm(v0, v1, 0x5410);
            a[kh >> 1][2 * h + 1] = __byte_perm(v0, v1, 0x7632);
        }
        a[3][0] = 0; a[3][1] = 0;
    };
    gen(a[0], wg);
    if (wg) gen(a[1], wg + 2);
#pragma unroll 1
    for (int n = 0; n < 2; n++) {
        const int at = wg + 2 * n, i0 = at < n0 ? 4 * at : L0 + 4 * (at - n0), cnt = (at < n0 ? L0 : Lt) - i0, cb = cb0 + (at >= n0);
        if (cnt <= 0 || (n && !wg)) break;
        if (n) {
#pragma unroll
            for (int j = 0; j < 16; j++) a[0][j >> 2][j & 3] = a[1][j >> 2][j & 3];
        }
        const Desc dB = mkdesc(sb + WP + (cb - cb0) * 14336, 3584, 512, 2);
        if (at) mbar_wait(sb + BARS + 8 * (B_WCH + at - 1));
        mbar_wait(sb + BARS + 8 * (B_WF + 2 * (cb - cb0)));
        wg_fence();
        wgmma_rs_n128_z(acc, a[0][0][0], a[0][0][1], a[0][0][2], a[0][0][3], dB);
        wgmma_rs_n128_a(acc, a[0][1][0], a[0][1][1], a[0][1][2], a[0][1][3], dB + (uint32_t)(16 * 64 >> 4));
        wgmma_rs_n128_a(acc, a[0][2][0], a[0][2][1], a[0][2][2], a[0][2][3], dB + (uint32_t)(32 * 64 >> 4));
        wgmma_rs_n128_a(acc, a[0][3][0], a[0][3][1], a[0][3][2], a[0][3][3], dB + (uint32_t)(40 * 64 >> 4));
        wg_commit();
        wg_wait<0>();
        reg_fence(acc);
        e_arrive(sb + BARS + 8 * (B_WCH + at));
        if (w < cnt) {
            const uint32_t dst = sb + wst_off(i0 + w) + (lane >> 2) * 512 + (lane & 4) * 16 + ((q ^ cb) & 3) * 16;
#pragma unroll
            for (int j = 0; j < 4; j++)
#pragma unroll
                for (int e = 0; e < 2; e++)
                    asm volatile("st.shared.v4.u32 [%0], {%1,%2,%3,%4};" :: "r"((dst ^ (e * 64)) + j * 128),
                                 "r"(pack2(acc[4 * j + e], acc[16 + 4 * j + e])), "r"(pack2(acc[4 * j + 2 + e], acc[16 + 4 * j + 2 + e])),
                                 "r"(pack2(acc[32 + 4 * j + e], acc[48 + 4 * j + e])), "r"(pack2(acc[32 + 4 * j + 2 + e], acc[48 + 4 * j + 2 + e])) : "memory");
            fence_async_smem();
            e_arrive(sb + BARS + 8 * (B_WRD + i0 + w));
        }
    }
}

__device__ __forceinline__ void task_p1(int wg, int pair, uint32_t sb) {
    const int tid = threadIdx.x & 127, w = tid >> 5, lane = tid & 31;
    const uint32_t buf = sb + wg * 51200, bars = sb + BARS;
    uint32_t fr[5][10][2];
    float A[40], d[20];
    zero(A);
    {
        const Desc dA = mkdesc(buf, 3584, 512, 2), dB = mkdesc(sb + C1, 128, 256, 0);
        auto issue = [&](int g, float (&d)[40]) {
            mbar_wait(bars + 8 * (B_XF + wg * 5 + g));
            wg_fence();
            wgmma_ss_n80_z(d, dA + (uint32_t)(g * 8704 >> 4), dB);
#pragma unroll
            for (int j = 1; j < 5; j++) wgmma_ss_n80_a(d, dA + (uint32_t)((g * 8704 + j * 1024) >> 4), dB + (uint32_t)(j * 2560 >> 4));
            wg_commit();
        };
        auto pack = [&](int g, float (&d)[40]) {
            reg_fence(d);
#pragma unroll
            for (int f = 0; f < 10; f++) {
                fr[g][f][0] = pack2(d[4 * f], d[4 * f + 1]);
                fr[g][f][1] = pack2(d[4 * f + 2], d[4 * f + 3]);
            }
        };
        mbar_wait(bars + 8 * B_CF1);
#pragma unroll
        for (int g = 0; g < 4; g++) { issue(g, A); wg_wait<0>(); pack(g, A); }
        zero(d);
        mbar_wait(bars + 8 * (B_XF + wg * 5 + 4));
#pragma unroll
        for (int h = 0; h < 2; h++) {
            wg_fence();
            wgmma_ss_n40_z(d, dA + (uint32_t)(4 * 8704 >> 4), dB + (uint32_t)(h * 1280 >> 4));
#pragma unroll
            for (int j = 1; j < 5; j++) wgmma_ss_n40_a(d, dA + (uint32_t)((4 * 8704 + j * 1024) >> 4), dB + (uint32_t)((j * 2560 + h * 1280) >> 4));
            wg_commit(); wg_wait<0>(); reg_fence(d);
#pragma unroll
            for (int f = 0; f < 5; f++) { fr[4][5 * h + f][0] = pack2(d[4 * f], d[4 * f + 1]); fr[4][5 * h + f][1] = pack2(d[4 * f + 2], d[4 * f + 3]); }
        }
    }
    bb_break(sb);
    wg_bar(1 + wg);
    {
        const Desc dB = mkdesc(sb + C1 + 12800, 128, 256, 0);
        const int i = lane & 7, mi = lane >> 3, th = w >> 1, tz = (2 * pair + th) & 3;
        const uint32_t s0 = buf + (i >> 1) * 128 + (i & 1) * 64 + (((2 * (w & 1) + (mi & 1)) ^ tz ^ (i >> 1)) << 4);
        const uint32_t sA = s0 + th * 2048 + (mi >> 1) * 512, sB = s0 + th * 2048 + (mi >> 1) * 2560, sC = s0 + th * 1024 + (mi >> 1) * 512;
        auto issue = [&](int f, float (&d)[20]) {
            wg_fence();
            wgmma_rs_n40_z(d, fr[0][f][0], fr[0][f][1], fr[1][f][0], fr[1][f][1], dB);
            wgmma_rs_n40_a(d, fr[2][f][0], fr[2][f][1], fr[3][f][0], fr[3][f][1], dB + (uint32_t)(1280 >> 4));
            wgmma_rs_n40_a(d, fr[4][f % 5][0], fr[4][f % 5][1], fr[4][f % 5 + 5][0], fr[4][f % 5 + 5][1], dB + (uint32_t)((2560 + (f / 5) * 1280) >> 4));
            wg_commit();
        };
#pragma unroll
        for (int f = 0; f < 10; f++) {
            issue(f, d);
            if (f && !(f & 1)) { fence_async_smem(); e_arrive(bars + 8 * (B_RDY + wg * 5 + (f >> 1) - 1)); }
            wg_wait<0>(); reg_fence(d);
            const int Q = 5 * f;
            stm4(((Q & 3) == 3 ? sB : sA) + quad_off(Q), pack2(d[0], d[1]), pack2(d[2], d[3]), pack2(d[4], d[5]), pack2(d[6], d[7]));
            stm2(sA + quad_off(Q + 2), pack2(d[8], d[9]), pack2(d[10], d[11]));
            stm4((f == 9 ? sC : ((Q + 3) & 3) == 3 ? sB : sA) + quad_off(Q + 3), pack2(d[12], d[13]), pack2(d[14], d[15]), pack2(d[16], d[17]), pack2(d[18], d[19]));
            if (f == 9) { fence_async_smem(); e_arrive(bars + 8 * (B_RDY + wg * 5 + (f >> 1))); }
        }
    }
}

__device__ __forceinline__ void task_p2(int wg, int rk, uint32_t sb) {
    const int tid = threadIdx.x & 127, w = tid >> 5, lane = tid & 31;
    const uint32_t bars = sb + BARS;
    const int phi0 = 3 * rk, phiE = extra_phi(rk), mE = extra_mask(rk);
    uint4 wA[6], wB[6], wC[6], wE[6];
    auto ldw = [&](uint4 (&a)[6], int j, int phi) {
        const int pc = 3 * j + wg;
        const uint32_t p = sb + wslot(pc) + (lane & 3) * 512 + w * 128 + (((lane >> 2) ^ phi) & 1) * 64 + (((lane >> 3) ^ lane) & 3) * 16 + (phi & 1) * 8;
        mbar_wait(bars + 8 * (B_WL + pc));
#pragma unroll
        for (int s = 0; s < 6; s++) {
            asm volatile("ld.shared.v2.u32 {%0, %1}, [%2];" : "=r"(a[s].x), "=r"(a[s].y) : "r"(p + s * 2048) : "memory");
            asm volatile("ld.shared.v2.u32 {%0, %1}, [%2];" : "=r"(a[s].z), "=r"(a[s].w) : "r"((p ^ 8) + s * 2048) : "memory");
        }
        uint32_t dep = 0;
#pragma unroll
        for (int s = 0; s < 6; s++) dep |= a[s].x ^ a[s].z;
        if (__any_sync(0xffffffffu, dep == 0x7fc17fc1u)) __nanosleep(0);
        e_arrive(bars + 8 * (B_WE + pc));
    };
    ldw(wA, 0, phi0); ldw(wB, 1, phi0 + 1);
    bool haveC = false;
#pragma unroll 1
    for (uint32_t it = 0; it < (1u << 22); it++) {
        haveC = mbar_test(bars + 8 * (B_WL + 6 + wg));
        if (haveC || mbar_test(bars + 8 * B_RF)) break;
        __nanosleep(50);
    }
    if (haveC) ldw(wC, 2, phi0 + 2);
    mbar_wait(bars + 8 * (B_SIG + SIG_P1 + 1));
    const int i = lane & 7, mi = lane >> 3;
    const uint32_t soff = sb + S1 + wg * 4096 + mi * 512 + (i >> 1) * 128 + (i & 1) * 64;
    const int xo = w ^ (i >> 1);
    float d[32];
    zero(d);
    int n = 0;
    uint32_t xb = ((sb + xslot(0)) & 0x3FFFF) >> 4 | 1u << 16, mb = bars + 8 * wg;
    bool landed = false;
    auto unit = [&](const uint4 (&a)[6], int z) {
        const Desc d0{xb + (z & 2), (512u >> 4) | (2u << 30)}, d1 = d0 ^ 2u;
        if (!landed) mbar_wait(bars + 8 * (B_RF + n));
        mbar_wait(mb + 8 * (B_TOK - 1));
        wg_fence();
        wgmma_rs_n64_z(d, a[0].x, a[0].y, a[0].z, a[0].w, d0);
        wgmma_rs_n64_a(d, a[1].x, a[1].y, a[1].z, a[1].w, d1);
        e_arrive(bars + 8 * (n ? B_RE + n - 1 : B_RE + 13));
        const bool sfree = mbar_test(n >= 4 ? mb + 8 * (B_SFREE - 12) : bars + 8 * (B_TOK - 1));
        landed = mbar_test(bars + 8 * (B_RF + n + 1));
        wgmma_rs_n64_a(d, a[2].x, a[2].y, a[2].z, a[2].w, d0 + (uint32_t)(4096 >> 4));
        wgmma_rs_n64_a(d, a[3].x, a[3].y, a[3].z, a[3].w, d1 + (uint32_t)(4096 >> 4));
        e_arrive(mb + 8 * B_TOK);
        wgmma_rs_n64_a(d, a[4].x, a[4].y, a[4].z, a[4].w, d0 + (uint32_t)(8192 >> 4));
        wgmma_rs_n64_a(d, a[5].x, a[5].y, a[5].z, a[5].w, d1 + (uint32_t)(8192 >> 4));
        wg_commit();
        if (!sfree) mbar_wait(mb + 8 * (B_SFREE - 12));
        const uint32_t a0 = soff + (n & 3) * 12288 + ((xo ^ z) << 4);
        n++;
        xb = ((sb + xslot(n)) & 0x3FFFF) >> 4 | 1u << 16;
        wg_wait<0>();
        reg_fence(d);
        uint32_t p[8];
#pragma unroll
        for (int j = 0; j < 8; j++) p[j] = pack2(d[4 * j] - d[4 * j + 3], d[4 * j + 2] + d[4 * j + 1]);
        stm4(a0, p[0], p[1], p[2], p[3]);
        stm4(a0 + 2048, p[4], p[5], p[6], p[7]);
        fence_async_smem();
        e_arrive(mb + 8 * (B_RDY + R_P2));
        mb += 24;
    };
    const int zA = phi0 & 3, zB = (phi0 + 1) & 3, zC = (phi0 + 2) & 3, zE = phiE & 3;
#pragma unroll 1
    for (int it = 0; it < 4; it++) {
        unit(wA, zA);
        unit(wB, zB);
        if (it == 0 && !haveC) ldw(wC, 2, phi0 + 2);
        unit(wC, zC);
        if (it == 0 && mE) ldw(wE, 3, phiE);
        if (mE >> it & 1) unit(wE, zE);
    }
}

__device__ __forceinline__ void task_p3(int wg, int pair, uint32_t sb) {
    const int tid = threadIdx.x & 127, w = tid >> 5, lane = tid & 31;
    const uint32_t buf = sb + (wg ? 3 - wg : 0) * 51200, bars = sb + BARS;
    uint32_t fr[10][4][2];
    float acc[2][16];
    zero(acc[0]); zero(acc[1]);
    {
        const Desc dB = mkdesc(sb + C3, 128, 256, 0);
        const uint32_t a0 = (buf & 0x3FFFF) >> 4;
        auto dq = [&](int Q) {
            return Desc{a0 + (uint32_t)((quad_off(Q) >> 4) | ((Q < 48 ? 2048 : 1024) >> 4) << 16), (uint32_t)((quad_off(Q + 1) - quad_off(Q)) >> 4) | (2u << 30)};
        };
        auto issue = [&](int f) {
            if (!(f & 1)) mbar_wait(bars + 8 * (B_YF + wg * 5 + (f >> 1)));
            wg_fence();
            wgmma_ss_n32_z(acc[f & 1], dq(5 * f), dB);
            wgmma_ss_n32_a(acc[f & 1], dq(5 * f + 1), dB + (uint32_t)(1024 >> 4));
            wgmma_ss_n32_a(acc[f & 1], dq(5 * f + 3), dB + (uint32_t)(2048 >> 4));
            wg_commit();
        };
        mbar_wait(bars + 8 * B_CF3);
        issue(0);
#pragma unroll
        for (int f = 0; f < 10; f++) {
            if (f < 9) { issue(f + 1); wg_wait<1>(); } else wg_wait<0>();
            float (&d)[16] = acc[f & 1];
            reg_fence(d);
#pragma unroll
            for (int g = 0; g < 4; g++) { fr[f][g][0] = pack2(d[4 * g], d[4 * g + 1]); fr[f][g][1] = pack2(d[4 * g + 2], d[4 * g + 3]); }
        }
    }
    {
        const Desc dB = mkdesc(sb + C3 + 3072, 128, 256, 0);
        const int i = lane & 7, mi = lane >> 3, th = w >> 1, tz = (2 * pair + th) & 3;
        const int oct = (2 * (w & 1) + (mi & 1)) ^ tz;
        const uint32_t soff = buf + th * 3584 + (mi >> 1) * 512 + i * 64 + ((oct ^ (i >> 1)) << 4);
        auto mma = [&](int t, int s) {
            if (t > 6) return;
            const int g = t < 6 ? 1 + (t >> 1) : 0;
            const uint32_t o = t < 6 ? (t & 1) * 1024 : 8960, st = t < 6 ? 1792 : 1024;
            if (s == 0) { wg_fence(); wgmma_rs_n32_z(acc[t & 1], fr[0][g][0], fr[0][g][1], fr[1][g][0], fr[1][g][1], dB + (o >> 4)); }
            else wgmma_rs_n32_a(acc[t & 1], fr[2 * s][g][0], fr[2 * s][g][1], fr[2 * s + 1][g][0], fr[2 * s + 1][g][1], dB + ((o + s * st) >> 4));
            if (s == 4) wg_commit();
        };
        const int row = th * 14 + 4 * (mi >> 1) + (i >> 1);
        const uint32_t z0 = buf + row * 128 + (i & 1) * 64 + ((oct ^ (row & 3)) << 4), z1 = (lane & 20) == 20 ? buf + 4096 + lane * 16 : z0 + 1024;
        bb_break(sb);
#pragma unroll
        for (int s = 0; s < 5; s++) mma(0, s);
        wg_bar(1 + wg);
#pragma unroll
        for (int t = 0; t < 7; t++) {
#pragma unroll
            for (int s = 0; s < 2; s++) mma(t + 1, s);
            if (t < 6) { wg_commit(); wg_wait<1>(); } else wg_wait<0>();
            float (&d)[16] = acc[t & 1];
            reg_fence(d);
            const uint32_t a = soff + (1 + (t >> 1)) * 7168 + (t & 1) * 2048;
            stm4(t < 6 ? a : z0, pack2(d[0], d[1]), pack2(d[2], d[3]), pack2(d[4], d[5]), pack2(d[6], d[7]));
            mma(t + 1, 2);
            if (t & 1) stm2(a + 1024, pack2(d[8], d[9]), pack2(d[10], d[11]));
            else stm4(t < 6 ? a + 1024 : z1, pack2(d[8], d[9]), pack2(d[10], d[11]), pack2(d[12], d[13]), pack2(d[14], d[15]));
#pragma unroll
            for (int s = 3; s < 5; s++) mma(t + 1, s);
            if ((t & 1) || t == 6) { fence_async_smem(); e_arrive(bars + 8 * (B_RDY + R_P3 + wg * 4 + (t >> 1))); }
        }
    }
}

__device__ __forceinline__ void load_x(int cls, int rk, int u, uint32_t sb, const Maps& mp) {
    const int id = u * NH + rk, pl = id / 3, c0 = 32 * (id - 3 * pl), tp = cls * 4 + (pl >> 4), col = 14 * (pl & 15) - 8;
    const uint32_t bar = sb + BARS + 8 * (B_XF + u * 5), dst = sb + u * 51200;
    const int wrap = col < 0 ? 224 : 0;
    if (tp) {
#pragma unroll
        for (int g = 0; g < 5; g++) e_ld3(dst + g * 8704, &mp.x34, c0, col + 4 * g + (g < 2 ? wrap : 0), 28 * tp - 6, bar + 8 * g);
    } else {
#pragma unroll
        for (int g = 0; g < 5; g++) {
            e_ld3(dst + g * 8704, &mp.x6, c0, col + 4 * g + (g < 2 ? wrap : 0), 218, bar + 8 * g);
            e_ld3(dst + g * 8704 + 1536, &mp.x28, c0, col + 4 * g + (g < 2 ? wrap : 0), 0, bar + 8 * g);
        }
    }
}

__device__ __forceinline__ void load_x_box(int cls, int rk, int u, int g, uint32_t sb, const Maps& mp) {
    const int id = u * NH + rk, pl = id / 3, c0 = 32 * (id - 3 * pl), tp = cls * 4 + (pl >> 4), col = 14 * (pl & 15) - 8 + 4 * g;
    e_ld3(sb + u * 51200 + g * 8704, &mp.x34, c0, col < 0 ? col + 224 : col, 28 * tp - 6, sb + BARS + 8 * (B_XF + u * 5 + g));
}

__device__ __forceinline__ void load_first(uint32_t sb, const Maps& mp, const Ptrs& pt) {
    const uint32_t bars = sb + BARS;
    const int k = blockIdx.x;
    const uint32_t cb0 = (uint32_t)k * 18351u >> 15, cb1 = ((uint32_t)k * 14u + 13u) * 5243u >> 17;
    auto block = [&](uint32_t cb, int j) {
        const uint32_t b = cb * 43u >> 10;
        e_ldw(sb + WP + j * 14336, &mp.w, 32 * b, 4 * (cb & ~3u) - 96 * b + 2 * (cb & 3), bars + 8 * (B_WF + 2 * j));
        e_expect(bars + 8 * (B_WF + 2 * j), 14336);
    };
    block(cb0, 0);
    if (cb1 != cb0 && cb1 < 72) block(cb1, 1);
    e_expect(bars + 8 * B_CF1, 17920); e_g2s(sb + C1, pt.tab1, 17920, bars + 8 * B_CF1);
    if ((threadIdx.x & 31) < 15) asm volatile("mbarrier.arrive.expect_tx.shared::cta.b64 _, [%0], 8704;" :: "r"(bars + 8 * (B_XF + (threadIdx.x & 31))) : "memory");
    __syncwarp();
}

__device__ __forceinline__ uint32_t get_rel(uint32_t sb) {
    mbar_wait(sb + BARS + 8 * B_REL);
    uint32_t v; asm volatile("ld.shared.u32 %0, [%1];" : "=r"(v) : "r"(sb + REL) : "memory");
    return uni(v);
}

__device__ __forceinline__ void load_warp(int cls, int rk, uint32_t sb, const Ptrs& pt) {
    const uint32_t bars = sb + BARS;
    mbar_wait(bars + 8 * (B_SIG + SIG_P1));
    const uint32_t rel = get_rel(sb);
    const char* cnt = cls_cnt(pt.scr, cls) + (rk & (REP - 1)) * 16384;
    const int mE = extra_mask(rk);
    const int lpA = phi_line(3 * rk, rel), lpB = phi_line(3 * rk + 1, rel), lpC = phi_line(3 * rk + 2, rel), lpE = phi_line(extra_phi(rk), rel);
    e_arrive(bars + 8 * (B_TOK - 1));
    if ((threadIdx.x & 31) < 14) asm volatile("mbarrier.arrive.expect_tx.shared::cta.b64 _, [%0], 12288;" :: "r"(bars + 8 * (B_RF + (threadIdx.x & 31))) : "memory");
    __syncwarp();
    int n = 0;
#pragma unroll 1
    for (int pg = 0; pg < 4; pg++) {
        const int l0 = slot_line(0, pg, cls), l1 = slot_line(1, pg, cls), l2 = slot_line(2, pg, cls);
        auto unit = [&](int lp) {
            const uint32_t bar = bars + 8 * (B_RF + n), dst = sb + xslot(n);
            mbar_wait(bars + 8 * (n >= 8 ? B_RE + n - 8 : n >= 4 ? B_SIG + SIG_P1 + (rk < 60 ? 2 : 1) : B_WE + ((0x4310 >> (4 * n)) & 15)));
            e_g2s(dst, pt.scr + (size_t)(lp ^ l0) * 128, 4096, bar);
            e_g2s(dst + 4096, pt.scr + (size_t)(lp ^ l1) * 128, 4096, bar);
            e_g2s(dst + 8192, pt.scr + (size_t)(lp ^ l2) * 128, 4096, bar);
            n++;
        };
        cnt_wait(cnt + (CNT_P1 + pg) * 128, 48);
        unit(lpA); unit(lpB); unit(lpC);
        if (mE >> pg & 1) unit(lpE);
        if (pg == 1) { mbar_wait(bars + 8 * B_P1D); e_expect(bars + 8 * B_CF3, 17152); e_g2s(sb + C3, pt.tab3, 17152, bars + 8 * B_CF3); }
    }
}

__device__ __forceinline__ int near_page(char* p) {
#pragma unroll
    for (int e = 0; e < 4; e++) asm volatile("st.relaxed.gpu.global.v4.u32 [%0], {%1, %1, %1, %1};" :: "l"(p + (e >> 1) * 4096 + (e & 1) * 16), "r"(0) : "memory");
    uint32_t v0, v1, t0, t1;
    asm volatile("atom.relaxed.gpu.global.exch.b32 %0, [%1], 1;" : "=r"(v0) : "l"(p) : "memory");
    asm volatile("atom.relaxed.gpu.global.exch.b32 %0, [%1], 1;" : "=r"(v1) : "l"(p + 4096) : "memory");
    asm volatile("{\n.reg .pred p;\nsetp.ne.u32 p, %1, 0xffffffff;\nmov.u32 %0, 0;\n@p mov.u32 %0, %%clock;\n}" : "=r"(t0) : "r"(v0) : "memory");
    asm volatile("{\n.reg .pred p;\nsetp.ne.u32 p, %1, 0xffffffff;\nmov.u32 %0, 0;\n@p mov.u32 %0, %%clock;\n}" : "=r"(t1) : "r"(v1) : "memory");
    return t1 - t0 < 80;
}

__device__ __forceinline__ uint32_t find_role(uint32_t sb, char* scr, const char* x) {
    const int k = blockIdx.x;
    int c = near_page(scr + (slot_line(3, 3, 0) + phi_line(1 + (k >> 5), 0) + (k & 31)) * 128);
    int r;
    asm volatile("atom.relaxed.gpu.global.add.u32 %0, [%1], 1;" : "=r"(r) : "l"(cls_cnt(scr, c) + CNT_RANK * 128) : "memory");
    asm volatile("cp.async.bulk.prefetch.L2.global [%0], %1;" :: "l"(x + (k & 1) * (112 * 43008) + (k >> 1) * PFS), "n"(PFS) : "memory");
    asm volatile("st.shared.u32 [%0], %1;" :: "r"(sb + REL + 8), "r"(c) : "memory");
    if (r >= NH) { c ^= 1; r = NSM - 1 - r; }
    asm volatile("st.shared.u32 [%0], %1;" :: "r"(sb + REL + 4), "r"(c << 8 | r) : "memory");
    return c << 8 | r;
}
__device__ __forceinline__ void get_role(uint32_t sb, int& cls, int& rk) {
    mbar_wait(sb + BARS + 8 * B_ROLE);
    uint32_t v; asm volatile("ld.shared.u32 %0, [%1];" : "=r"(v) : "r"(sb + REL + 4) : "memory");
    v = uni(v); cls = v >> 8; rk = v & 255;
}

__device__ __forceinline__ void load3_warp(int cls, int rk, uint32_t sb, const Maps& mp, const Ptrs& pt) {
    const uint32_t bars = sb + BARS;
    mbar_wait(bars + 8 * B_XF);
    const uint32_t rel = cnt_wait(pt.cnt + CNT_REL * 32, 12u << 16);
    asm volatile("st.shared.u32 [%0], %1;" :: "r"(sb + REL), "r"(rel) : "memory");
    __syncwarp();
    e_arrive(bars + 8 * B_REL);
    mbar_wait(bars + 8 * (B_SIG + SIG_W));
    cnt_wait(cls_cnt(pt.scr, cls) + (rk & (REP - 1)) * 16384 + CNT_W * 128, NSM);
    {
        const int np = rk >= 60 ? 12 : 9;
#pragma unroll 1
        for (int pc = 0; pc < np; pc++) {
            if (pc == 2) mbar_wait(bars + 8 * (B_SIG + SIG_P1));
            if (pc >= 8) mbar_wait(bars + 8 * (B_WE + ((0x5762 >> (4 * (pc - 8))) & 15)));
            if (pc >= 5) mbar_wait(bars + 8 * (B_WL + pc - 5));
            e_expect(bars + 8 * (B_WL + pc), 12288);
            e_g2s(sb + wslot(pc), pt.wf + (pc < 9 ? 9 * rk + pc : 3 * extra_phi(rk) + pc - 9) * 12288, 12288, bars + 8 * (B_WL + pc));
        }
        if (np == 12) { mbar_wait(bars + 8 * (B_WE + 9)); mbar_wait(bars + 8 * (B_WE + 10)); mbar_wait(bars + 8 * (B_WE + 11)); }
    }
    mbar_wait(bars + 8 * (B_SIG + SIG_P2 + 1));
    const int nu = rk < 60 ? 3 : 2;
#pragma unroll 1
    for (int u = 0; u < nu; u++) {
        const int id = u * NH + rk, pl = id / 3, chunk = id - 3 * pl;
        const int l0 = slot_line(chunk, pl >> 4, cls) + (pl & 15) * 2;
        const uint32_t buf = sb + (u ? 3 - u : 0) * 51200, bar = bars + 8 * (B_YF + u * 5);
#pragma unroll
        for (int j = 0; j < 5; j++) e_expect(bar + 8 * j, j == 4 ? 10240 : (j & 1) ? 8192 : 12288);
        if (u) mbar_wait(bars + 8 * (B_SIG + SIG_P2 + 3));
        cnt_wait(cls_cnt(pt.scr, cls) + (rk & (REP - 1)) * 16384 + (CNT_P2 + (pl >> 4)) * 128, NH);
        if (u == nu - 1) e_arrive(bars + 8 * B_FIN);
        const uint32_t r2 = uni(rel) << 5;
#pragma unroll
        for (int G = 0; G < 13; G++)
            e_ld5(buf + G * 4096, G < 12 ? &mp.f16 : &mp.f8, (l0 ^ ((r2 >> G) & 32)) + (G << 14), bar + 8 * ((2 * G) / 5));
    }
}

__device__ __forceinline__ void store_warp(uint32_t sb, const Maps& mp, const Ptrs& pt) {
    const uint32_t bars = sb + BARS;
    const int k = blockIdx.x;
    uint32_t pa = 0, pb = 0, qa = 0, qb = 0;
    auto arr2 = [&](uint32_t& a, uint32_t& b) { if (a) e_arrive(a); if (b) e_arrive(b); a = b = 0; };
    auto pre = [&](int idx) {
        const uint32_t bar = bars + 8 * idx;
        if ((pb | qb) && !mbar_test(bar)) { bulk_wait<0>(); arr2(qa, qb); arr2(pa, pb); }
        mbar_wait(bar);
    };
    auto post = [&](uint32_t fr) {
        bulk_commit(); bulk_wait_read<2>();
        if (qb) bulk_wait<2>();
        arr2(qa, qb); qa = pa; qb = pb; pb = 0; pa = fr;
    };
    auto after = [&](int sig) { pb = bars + 8 * (B_SIG + sig); };
    int cls, rk; get_role(sb, cls, rk);
    {
        int cb = 14 * k / 25, oc = 14 * k - 25 * cb;
        int g1 = 0;
#pragma unroll 1
        for (int i = 0; i < 14 && cb < 72; i++) {
            pre(B_WRD + i);
            e_st3(&mp.wst, sb + wst_off(i), 0, 8 * oc, cb);
            post(0);
            if (T1MASK >> i & 1) load_x_box(cls, rk, 1, g1++, sb, mp);
            if (++oc == 25) { oc = 0; cb++; }
        }
#pragma unroll 1
        for (; g1 < 5; g1++) load_x_box(cls, rk, 1, g1, sb, mp);
        after(SIG_W);
    }
    pre(B_REL);
    const uint32_t rel = get_rel(sb);
    const int nu = rk < 60 ? 3 : 2;
    int g2 = 0;
#pragma unroll 1
    for (int u = 0; u < nu; u++) {
        const int id = u * NH + rk, pl = id / 3, chunk = id - 3 * pl;
        const int l0 = slot_line(chunk, pl >> 4, cls) + (pl & 15) * 2;
        int j = B_RDY + u * 5;
        const int m2 = nu == 3 ? (u == 0 ? T2MASK & 0x1fff : u == 1 ? T2MASK >> 13 : 0) : 0;
#pragma unroll 1
        for (int G = 0; G < 13; G++) {
            if (0x4a5 >> G & 1) pre(j++);
            e_st5(G < 12 ? &mp.f16 : &mp.f8, sb + u * 51200 + G * 4096, (l0 ^ ((rel >> G) & 1) << 5) + (G << 14));
            post(0);
            if (m2 >> G & 1) load_x_box(cls, rk, 2, g2++, sb, mp);
        }
        after(SIG_P1 + u);
    }
    const int mE = extra_mask(rk);
    int n = 0;
#pragma unroll 1
    for (int pg = 0; pg < 4; pg++) {
        const int nj = 3 + (mE >> pg & 1);
        const int l0 = slot_line(0, pg, cls), l1 = slot_line(1, pg, cls), l2 = slot_line(2, pg, cls);
#pragma unroll 1
        for (int j = 0; j < nj; j++) {
            const int lp = phi_line(j == 3 ? extra_phi(rk) : 3 * rk + j, rel);
#pragma unroll
            for (int b = 0; b < 3; b++) {
                pre(B_RDY + R_P2 + n * 3 + b);
                e_s2g(pt.scr + (size_t)(lp ^ (b == 0 ? l0 : b == 1 ? l1 : l2)) * 128, sb + S1 + (n & 3) * 12288 + b * 4096, 4096);
                post(bars + 8 * (B_SFREE + n * 3 + b));
            }
            n++;
        }
        after(SIG_P2 + pg);
    }
#pragma unroll 1
    for (int u = 0; u < nu; u++) {
        const int id = u * NH + rk, pl = id / 3, chunk = id - 3 * pl, tp = cls * 4 + (pl >> 4), tx = pl & 15;
        const uint32_t buf = sb + (u ? 3 - u : 0) * 51200;
#pragma unroll
        for (int gg = 1; gg < 5; gg++) {
            pre(B_RDY + R_P3 + u * 4 + gg - 1);
            if (gg < 4) e_st3(&mp.y4, buf + gg * 7168, 32 * chunk, 14 * tx - 4 + 4 * gg, 28 * tp);
            else e_st3(&mp.y2, buf, 32 * chunk, tx == 0 ? 222 : 14 * tx - 2, 28 * tp);
            post(0);
        }
    }
    bulk_wait_read<0>();
}

__device__ __forceinline__ void signal_warp(int cls, int rk, uint32_t sb, const Ptrs& pt) {
    const uint32_t bars = sb + BARS;
    char* cnt = cls_cnt(pt.scr, cls);
    if (threadIdx.x & 31) return;
#pragma unroll 1
    for (int c = 0; c < 8; c++) {
        if (c == SIG_P1 + 2 && rk >= 60) continue;
        char* ctr = cnt + (c == SIG_W ? CNT_W : c < SIG_P2 ? CNT_P1 + ((c - SIG_P1) * NH + rk) / 48 : CNT_P2 + c - SIG_P2) * 128;
        mbar_wait(bars + 8 * (B_SIG + c));
        fence_async();
#pragma unroll
        for (int r = 0; r < REP; r++) {
            asm volatile("red.relaxed.gpu.global.add.u32 [%0], 1;" :: "l"(ctr + r * 16384) : "memory");
            if (c == SIG_W) asm volatile("red.relaxed.gpu.global.add.u32 [%0], 1;" :: "l"(((uintptr_t)ctr ^ 4096) + r * 16384) : "memory");
        }
    }
    mbar_wait(bars + 8 * B_FIN);
    unsigned old;
    asm volatile("atom.add.relaxed.gpu.global.u32 %0, [%1], 1;" : "=r"(old) : "l"(pt.cnt + CNT_DONE * 32) : "memory");
    if (old == NSM - 1) {
#pragma unroll
        for (int c = 0; c < NCNT; c++) pt.cnt[c * 32] = 0;
#pragma unroll 1
        for (int c = 0; c < NCLS; c++)
#pragma unroll
            for (int r = 0; r < REP; r++) { *reinterpret_cast<unsigned*>(cnt + c * 128 + r * 16384) = 0; *reinterpret_cast<unsigned*>(((uintptr_t)cnt ^ 4096) + c * 128 + r * 16384) = 0; }
    }
}

__global__ void __launch_bounds__(512, 1) fftconv_kernel(const Ptrs pt, const __grid_constant__ Maps mp) {
    extern __shared__ __align__(1024) uint8_t smem[];
    const uint32_t sb = smem_u32(smem);
    const int tid = threadIdx.x, warp = uni(tid >> 5), wg = warp >> 2;
    int cls, rk;
    auto bar_init = [&](int i) {
        uint32_t c = 1;
        if (i == B_P1D || (i >= B_RE && i < B_RE + 14)) c = 12;
        else if ((i >= B_WCH && i < B_WL) || i >= B_TOK) c = 4;
        asm volatile("st.shared.v2.u32 [%0], {%1, %2};" :: "r"(sb + BARS + 8 * i), "r"((0x100000u - c) << 1), "r"((0x100000u - c) << 11) : "memory");
        fence_async_smem();
    };
    if (wg == 3) {
        asm volatile("setmaxnreg.dec.sync.aligned.u32 32;");
        if (warp == 12) {
            bar_init(tid & 31);
            __syncwarp();
            asm volatile("bar.arrive 4, 416;" ::: "memory");
            load_first(sb, mp, pt);
            asm volatile("bar.sync 5, 416;" ::: "memory");
            get_role(sb, cls, rk);
            load_warp(cls, rk, sb, pt);
        } else if (warp == 13) {
            if ((tid & 31) < 8) asm volatile("prefetch.tensormap [%0];" :: "l"(reinterpret_cast<const CUtensorMap*>(&mp) + 1 + (tid & 31)) : "memory");
            __syncwarp();
            asm volatile("bar.sync 6, 416;" ::: "memory");
            store_warp(sb, mp, pt);
        } else if (warp == 14) {
            const int G = blockIdx.x - 119;
            int sel = 0;
            if (G >= 1 && (tid & 31) == 0) sel = near_page(pt.scr + ((size_t)G << 21) + slot_line(3, 3, 0) * 128);
            __syncwarp();
            asm volatile("bar.sync 7, 416;" ::: "memory");
            get_role(sb, cls, rk);
            if (G >= 1 && (tid & 31) == 0) {
                uint32_t c; asm volatile("ld.shared.u32 %0, [%1];" : "=r"(c) : "r"(sb + REL + 8) : "memory");
                asm volatile("red.relaxed.gpu.global.add.u32 [%0], %1;" :: "l"(pt.cnt + CNT_REL * 32), "r"(0x10000u | (sel ^ c) << G) : "memory");
            }
            __syncwarp();
            load3_warp(cls, rk, sb, mp, pt);
        } else {
            uint32_t role = 0;
            if ((tid & 31) == 0) role = find_role(sb, pt.scr, pt.x);
            role = uni(role); cls = role >> 8; rk = role & 255;
            asm volatile("bar.sync 8, 416;" ::: "memory");
            load_x(cls, rk, 0, sb, mp);
            e_arrive(sb + BARS + 8 * B_ROLE);
            signal_warp(cls, rk, sb, pt);
        }
    } else {
        if (tid >= 32 && tid < NBAR) bar_init(tid);
        {
            const int r = tid % 40;
            asm volatile("st.shared.u32 [%0], %1;" :: "r"(sb + TBL + 4 * tid), "r"(cos_bits(r) | (cos_bits(r < 30 ? r + 10 : r - 30) << 16)) : "memory");
        }
        __syncwarp();
        asm volatile("bar.sync 4, 416;" ::: "memory");
        asm volatile("bar.arrive 5, 416;" ::: "memory");
        asm volatile("bar.arrive 6, 416;" ::: "memory");
        asm volatile("bar.arrive 7, 416;" ::: "memory");
        asm volatile("bar.arrive 8, 416;" ::: "memory");
        task_w(wg, blockIdx.x, sb);
        asm volatile("setmaxnreg.inc.sync.aligned.u32 160;");
        get_role(sb, cls, rk);
        const int id = wg * NH + rk;
        if (id < 192) task_p1(wg, id / 3, sb);
        e_arrive(sb + BARS + 8 * B_P1D);
        task_p2(wg, rk, sb);
        if (id < 192) task_p3(wg, id / 3, sb);
    }
}

__global__ void fallback_kernel(const __nv_bfloat16* x, const __nv_bfloat16* w, __nv_bfloat16* y) {
    const int px = blockIdx.x, o = threadIdx.x, h = px / 224, c = px % 224;
    float acc = 0.f;
    for (int kh = 0; kh < 7; kh++)
        for (int kw = 0; kw < 7; kw++) {
            const __nv_bfloat16* xp = x + (((h - kh + 224) % 224) * 224 + (c - kw + 224) % 224) * 96;
            const __nv_bfloat16* wp = w + (kh * 7 + kw) * 9216 + o;
            for (int i = 0; i < 96; i++) acc += __bfloat162float(xp[i]) * __bfloat162float(wp[i * 96]);
        }
    y[px * 96 + o] = __float2bfloat16(acc);
}

typedef CUresult (*EncodeFn)(CUtensorMap*, CUtensorMapDataType, cuuint32_t, void*, const cuuint64_t*, const cuuint64_t*, const cuuint32_t*, const cuuint32_t*,
                             CUtensorMapInterleave, CUtensorMapSwizzle, CUtensorMapL2promotion, CUtensorMapFloatOOBfill);

static void encode3(EncodeFn fn, CUtensorMap* m, void* ptr, uint64_t d0, uint64_t d1, uint64_t d2, uint64_t s1, uint64_t s2,
                    uint32_t b0, uint32_t b1, uint32_t b2, CUtensorMapSwizzle sw, CUtensorMapL2promotion promo = CU_TENSOR_MAP_L2_PROMOTION_NONE) {
    cuuint64_t dims[3] = {d0, d1, d2}, strides[2] = {s1, s2};
    cuuint32_t box[3] = {b0, b1, b2}, es[3] = {1, 1, 1};
    fn(m, CU_TENSOR_MAP_DATA_TYPE_BFLOAT16, 3, ptr, dims, strides, box, es, CU_TENSOR_MAP_INTERLEAVE_NONE, sw,
       promo, CU_TENSOR_MAP_FLOAT_OOB_FILL_NONE);
}

extern "C" void kernel_launch(void* const* d_in, const int* in_sizes, int n_in, void* d_out, int out_size) {
    (void)in_sizes; (void)n_in; (void)out_size;
    int dev = 0, nsm = 0;
    cudaGetDevice(&dev);
    cudaDeviceGetAttribute(&nsm, cudaDevAttrMultiProcessorCount, dev);
    if (nsm < NSM) {
        fallback_kernel<<<224 * 224, 96>>>((const __nv_bfloat16*)d_in[0], (const __nv_bfloat16*)d_in[1], (__nv_bfloat16*)d_out);
        return;
    }
    void* fnp = nullptr; cudaDriverEntryPointQueryResult qr;
    cudaGetDriverEntryPoint("cuTensorMapEncodeTiled", &fnp, cudaEnableDefault, &qr);
    EncodeFn fn = (EncodeFn)fnp;
    void* xf = nullptr; cudaGetSymbolAddress(&xf, g_scr);
    xf = (void*)(((uintptr_t)xf + (1u << 21) - 1) & ~(uintptr_t)((1u << 21) - 1));
    void* wf = nullptr; cudaGetSymbolAddress(&wf, g_wf);
    Maps mp;
    Ptrs pt;
    pt.scr = (char*)xf; pt.wf = (const char*)wf; pt.x = (const char*)d_in[0];
    void* p = nullptr;
    cudaGetSymbolAddress(&p, TAB_P1); pt.tab1 = p;
    cudaGetSymbolAddress(&p, TAB_P3); pt.tab3 = p;
    cudaGetSymbolAddress(&p, g_cnt); pt.cnt = (unsigned*)p;
    {
        cuuint32_t b16[5] = {64, 4, 2, 2, 2}, b8[5] = {64, 4, 2, 1, 2}, es[5] = {1, 1, 1, 1, 1};
        cuuint64_t d[5] = {64, 4, 2, 2, 13 << 14}, st[4] = {16384, 262144, 1048576, 128};
        fn(&mp.f16, CU_TENSOR_MAP_DATA_TYPE_BFLOAT16, 5, xf, d, st, b16, es, CU_TENSOR_MAP_INTERLEAVE_NONE, CU_TENSOR_MAP_SWIZZLE_NONE, CU_TENSOR_MAP_L2_PROMOTION_NONE, CU_TENSOR_MAP_FLOAT_OOB_FILL_NONE);
        fn(&mp.f8, CU_TENSOR_MAP_DATA_TYPE_BFLOAT16, 5, xf, d, st, b8, es, CU_TENSOR_MAP_INTERLEAVE_NONE, CU_TENSOR_MAP_SWIZZLE_NONE, CU_TENSOR_MAP_L2_PROMOTION_NONE, CU_TENSOR_MAP_FLOAT_OOB_FILL_NONE);
    }
    encode3(fn, &mp.x6, d_in[0], 96, 224, 224, 192, 224 * 192, 32, 4, 6, CU_TENSOR_MAP_SWIZZLE_64B, CU_TENSOR_MAP_L2_PROMOTION_L2_128B);
    encode3(fn, &mp.x34, d_in[0], 96, 224, 224, 192, 224 * 192, 32, 4, 34, CU_TENSOR_MAP_SWIZZLE_64B, CU_TENSOR_MAP_L2_PROMOTION_L2_128B);
    encode3(fn, &mp.x28, d_in[0], 96, 224, 224, 192, 224 * 192, 32, 4, 28, CU_TENSOR_MAP_SWIZZLE_64B, CU_TENSOR_MAP_L2_PROMOTION_L2_128B);
    {
        cuuint32_t box[5] = {32, 8, 7, 2, 2}, es[5] = {1, 1, 1, 1, 1};
        cuuint64_t d[5] = {96, 7, 7, 88, 2}, st[4] = {18432, 7 * 18432, 192, 8 * 192};
        fn(&mp.w, CU_TENSOR_MAP_DATA_TYPE_BFLOAT16, 5, d_in[1], d, st, box, es, CU_TENSOR_MAP_INTERLEAVE_NONE, CU_TENSOR_MAP_SWIZZLE_64B, CU_TENSOR_MAP_L2_PROMOTION_NONE, CU_TENSOR_MAP_FLOAT_OOB_FILL_NONE);
    }
    encode3(fn, &mp.wst, wf, 256, 200, 72, 36864, 512, 256, 8, 1, CU_TENSOR_MAP_SWIZZLE_NONE);
    encode3(fn, &mp.y4, d_out, 96, 224, 224, 192, 224 * 192, 32, 4, 28, CU_TENSOR_MAP_SWIZZLE_64B);
    encode3(fn, &mp.y2, d_out, 96, 224, 224, 192, 224 * 192, 32, 2, 28, CU_TENSOR_MAP_SWIZZLE_64B);
    constexpr int SMEM_LAUNCH = SMEM_BYTES;
    cudaFuncSetAttribute(fftconv_kernel, cudaFuncAttributeMaxDynamicSharedMemorySize, SMEM_LAUNCH);
    fftconv_kernel<<<NSM, 512, SMEM_LAUNCH>>>(pt, mp);
}
```
